```python
import torch

def _softmax(x, axis=-1):
    return torch.softmax(x, dim=axis)

def _gelu(x):
    return torch.nn.functional.gelu(x, approximate='tanh')

def _silu(x):
    return torch.nn.functional.silu(x)

def _sigmoid(x):
    return torch.sigmoid(x)

def _layernorm(x, axis=-1, eps=1e-05):
    m = x.mean(dim=axis, keepdim=True)
    v = x.var(dim=axis, keepdim=True, unbiased=False)
    return (x - m) / torch.sqrt(v + eps)

def _scatter_add(tgt, idx, src, axis=0):
    return tgt.clone().index_add_(axis, idx, src)

def _segment_sum(src, seg, n):
    out = torch.zeros((n,) + src.shape[1:], dtype=src.dtype)
    return out.index_add_(0, seg, src)

def _pad(x, pw):
    flat = tuple((v for pair in reversed(pw) for v in pair))
    return torch.nn.functional.pad(x, flat)
kernel_name = 'interleave_layers__ssm_conv_h3__memory_aug_recurrent_mem_tr__prompt'

def setup_inputs():

    _w = lambda a: (lambda t: t.to(torch.bfloat16) if t.is_floating_point() else t)(torch.as_tensor(a))

    def _A_setup():
        B, S, D = (1, 2048, 576)
        ks = 4
        return {'q': _w((lambda *s: torch.randn(*s, dtype=torch.bfloat16) * 0.05)(B, S, D)), 'k': _w((lambda *s: torch.randn(*s, dtype=torch.bfloat16) * 0.2)(B, S, D)), 'v': _w((lambda *s: torch.randn(*s, dtype=torch.bfloat16) * 0.2)(B, S, D)), 'shift_k': _w((lambda *s: torch.randn(*s, dtype=torch.bfloat16) * 0.2)(D, ks) * 0.5), 'ssm_k': _w((lambda *s: torch.randn(*s, dtype=torch.bfloat16) * 0.4)(D, S) * (1.0 / S ** 0.5)), 'ssm_D': _w((lambda *s: torch.randn(*s, dtype=torch.bfloat16) * 0.2)(D))}
    _A_in = _A_setup()

    def _B_setup():
        B, S, Dm = (1, 2048, 576)
        H, Dh = (32, 128)
        M, seg = (8, 32)
        seg = min(seg, S)
        S = S // seg * seg
        return {'x': _w((lambda *s: torch.randn(*s, dtype=torch.bfloat16) * 0.05)(B, S, Dm)), 'mem0': _w((lambda *s: torch.randn(*s, dtype=torch.bfloat16) * 0.2)(B, M, Dm)), 'Wq': _w((lambda *s: torch.randn(*s, dtype=torch.bfloat16) * 1.6)(Dm, H, Dh) * Dm ** (-0.5)), 'Wk': _w((lambda *s: torch.randn(*s, dtype=torch.bfloat16) * 1.6)(Dm, H, Dh) * Dm ** (-0.5)), 'Wv': _w((lambda *s: torch.randn(*s, dtype=torch.bfloat16) * 0.2)(Dm, H, Dh) * Dm ** (-0.5)), 'Wo': _w((lambda *s: torch.randn(*s, dtype=torch.bfloat16) * 0.2)(H, Dh, Dm) * (H * Dh) ** (-0.5)), 'seg_len': seg}
    _B_in = _B_setup()
    return {'A_q': _A_in['q'], 'A_k': _A_in['k'], 'A_v': _A_in['v'], 'A_shift_k': _A_in['shift_k'], 'A_ssm_k': _A_in['ssm_k'], 'A_ssm_D': _A_in['ssm_D'], 'B_x': _B_in['x'], 'B_mem0': _B_in['mem0'], 'B_Wq': _B_in['Wq'], 'B_Wk': _B_in['Wk'], 'B_Wv': _B_in['Wv'], 'B_Wo': _B_in['Wo'], 'B_seg_len': _B_in['seg_len']}

def reference(A_q, A_k, A_v, A_shift_k, A_ssm_k, A_ssm_D, B_x, B_mem0, B_Wq, B_Wk, B_Wv, B_Wo, B_seg_len):

    def _A_ref(q, k, v, shift_k, ssm_k, ssm_D):
        B, S, D = q.shape
        ks = shift_k.shape[-1]
        k_pad = _pad(k, ((0, 0), (ks - 1, 0), (0, 0)))
        k_shift = torch.zeros_like(k)
        for t in range(ks):
            k_shift = k_shift + k_pad[:, t:t + S, :] * shift_k[:, ks - 1 - t][None, None, :]
        kv = k_shift * v
        L = 2 * S
        kv_pad = _pad(kv, ((0, 0), (0, S), (0, 0)))
        kf_pad = _pad(ssm_k, ((0, 0), (0, S)))
        kv_f = (lambda x, axes=(-2, -1): torch.fft.rfft2(x.float(), dim=axes))(kv_pad[:, None, :, :], axes=(1, 2))
        kf_f = (lambda x, axes=(-2, -1): torch.fft.rfft2(x.float(), dim=axes))(kf_pad[:, None, :], axes=(1, 2))
        kf_f = (lambda x, *d: x.permute(*d))(kf_f, 1, 2, 0)
        y_f = kv_f * kf_f[None, :, :, :]
        y = (lambda x, s, axes=(-2, -1): torch.fft.irfft2(x, s=s, dim=axes).to(torch.bfloat16))(y_f, (1, L), axes=(1, 2))[:, 0, :S, :]
        y = y + kv * ssm_D[None, None, :]
        return q * y

    def _B_ref(x, mem0, Wq, Wk, Wv, Wo, seg_len):
        B, S, Dm = x.shape
        H, Dh = (Wq.shape[1], Wq.shape[2])
        M = mem0.shape[1]
        scale = Dh ** (-0.5)
        n_seg = S // seg_len
        L = M + seg_len
        idx = torch.arange(L)
        mask = (idx[:, None] < M) | (idx[:, None] >= idx[None, :])
        mem = mem0
        outs = []
        for s in range(n_seg):
            xs = x[:, s * seg_len:(s + 1) * seg_len, :].clone()
            h = torch.concatenate([mem, xs], axis=1)
            q = torch.einsum('btd,dhe->bhte', h, Wq)
            k = torch.einsum('btd,dhe->bhte', h, Wk)
            v = torch.einsum('btd,dhe->bhte', h, Wv)
            scores = torch.einsum('bhqe,bhke->bhqk', q, k) * scale
            scores = torch.where(mask[None, None], scores, -1000000000.0)
            p = _softmax(scores, axis=-1)
            o = torch.einsum('bhqk,bhke->bhqe', p, v)
            o = torch.einsum('bhte,hed->btd', o, Wo)
            mem = o[:, :M, :].clone()
            outs.append(o[:, M:, :])
        return torch.concatenate(outs, axis=1)
    x = A_q
    x = x + _A_ref(_layernorm(x, axis=-1), A_k, A_v, A_shift_k, A_ssm_k, A_ssm_D)
    x = x + _B_ref(_layernorm(x, axis=-1), B_mem0, B_Wq, B_Wk, B_Wv, B_Wo, B_seg_len)
    x = x + _A_ref(_layernorm(x, axis=-1), A_k, A_v, A_shift_k, A_ssm_k, A_ssm_D)
    x = x + _B_ref(_layernorm(x, axis=-1), B_mem0, B_Wq, B_Wk, B_Wv, B_Wo, B_seg_len)
    return x
```

```cpp
#include <cuda_runtime.h>
#include <cuda_bf16.h>
#include <stdint.h>

namespace {

typedef __nv_bfloat16 bf16;

constexpr int SEQ = 2048, DM = 576, HD = 4096, NSEG = 64;
#define LAGV 6
constexpr int LAG = LAGV, STEPS = NSEG + LAG, RING = 8;
static_assert(LAG + 1 < RING, "ring");
constexpr int N_CHAIN = 64, N_G = 48, N_O = 18, N_F = 2;
constexpr uint32_t SBASE = 1024;
constexpr uint32_t SENT = 0xFFFFFFFFu;
constexpr int SPIN_MAX = 1 << 22;

__device__ __align__(1024) bf16 g_kvT[DM * SEQ];
__device__ __align__(1024) bf16 g_yT[DM * SEQ];
__device__ __align__(1024) bf16 g_y[SEQ * DM];
__device__ __align__(1024) bf16 g_x1[SEQ * DM];
__device__ __align__(1024) unsigned char g_lnimg[2 * NSEG * 9 * 4096];
__device__ __align__(1024) unsigned char g_qkv[RING * N_CHAIN * 24576];
__device__ __align__(1024) unsigned char g_oimg[RING * N_CHAIN * 8192];
constexpr int ARING = 16;
static_assert(ARING >= LAG + 4, "accumulator ring");
__device__ __align__(1024) float g_oacc[ARING * 64 * DM];
constexpr int MRING = 10;
static_assert(MRING >= LAG + 4, "m ring");
constexpr int XB_F = N_CHAIN * 3, XB_M = XB_F + 2, XB_REF = XB_M + MRING * 5, XB_N = XB_REF + 1, N_CTA = N_CHAIN + N_G + N_O + N_F;
__device__ __align__(8192) uint4 g_xb[XB_N * 512];
#define g_inbox g_xb
#define g_mimg ((uint32_t*)(g_xb + XB_M * 512))
__device__ uint32_t g_near[XB_N];
__device__ uint32_t g_side[N_CTA];
__device__ __align__(128) uint32_t g_gbar[2 * 32];
constexpr int FL_G = 0, FL_F = 96 * 8, FL_OCNT = FL_F + 2 * 8, OCRING = 16, FL_TICK = 992, FL_O = 2048;
static_assert(FL_OCNT + OCRING * 8 <= FL_TICK, "flag block");
#define g_fl ((uint32_t*)(g_xb + XB_F * 512))
__device__ __align__(1024) uint32_t g_lnflag[128 * 8];
#define TS(slot)
constexpr int OBSW = 0;
#define PROF(slot)
#define PROF0()
#define PCNT(slot)
#define PROF_DUMP()

#define NSLEEP 0
#define INFL 8
#define S1DLY 2500
#define S1G 1500
#define OTURN 4
#define FENCE1 1
#define FENCE2 0
#define VMIX 23
#define MOFF 1
#define SORD 1
#define EARLYQ 1
#define LOCK0 (LAG - 3)
#define MORD 0
#define VEARLY 1
#define T3(slot)
#define CK(i, dep)
#define CKW(i, dep)
#define CKDECL
#define CKOUT(base)
#define TR(slot)
__device__ __forceinline__ uint32_t clk() { uint32_t t; asm volatile("mov.u32 %0, %%clock;" : "=r"(t) :: "memory"); return t; }
__device__ __forceinline__ void wait_until(uint32_t t0, uint32_t d) {
  asm volatile("{.reg .pred p; .reg .u32 t;\n"
               "W: mov.u32 t, %%clock; shfl.sync.idx.b32 t, t, 0, 31, -1; sub.u32 t, t, %0; setp.lt.s32 p, t, 0; @p bra W;}" :: "r"(t0 + d) : "memory");
}
__device__ __forceinline__ uint32_t pack2(float lo, float hi) {
  uint32_t r; asm("cvt.rn.bf16x2.f32 %0, %1, %2;" : "=r"(r) : "f"(hi), "f"(lo)); return r;
}
__device__ __forceinline__ float bf_lo(uint32_t v) { return __uint_as_float(v << 16); }
__device__ __forceinline__ float bf_hi(uint32_t v) { return __uint_as_float(v & 0xFFFF0000u); }

__device__ __forceinline__ uint4 ld_relaxed4(const void* p) {
  uint4 v; asm volatile("ld.relaxed.gpu.global.v4.u32 {%0,%1,%2,%3}, [%4];" : "=r"(v.x), "=r"(v.y), "=r"(v.z), "=r"(v.w) : "l"(p) : "memory"); return v;
}
__device__ __forceinline__ void st_b128(void* p, uint32_t a, uint32_t b, uint32_t c, uint32_t d) {
  asm volatile("{.reg .b128 v; mov.b128 v, {%1,%2,%3,%4}; st.relaxed.gpu.global.b128 [%0], v;}" :: "l"(p), "r"(a), "r"(b), "r"(c), "r"(d) : "memory");
}
__device__ __forceinline__ void reload_b128(uint4& v, const void* p, uint32_t again) {
  asm volatile("{.reg .pred p; .reg .b128 v; setp.ne.u32 p, %5, 0; mov.b128 v, {%0,%1,%2,%3};\n"
               "@p ld.relaxed.gpu.global.b128 v, [%4]; mov.b128 {%0,%1,%2,%3}, v;}"
    : "+r"(v.x), "+r"(v.y), "+r"(v.z), "+r"(v.w) : "l"(p), "r"(again) : "memory");
}
__device__ __forceinline__ void reload4(uint4& v, const void* p, uint32_t again) {
  asm volatile("{.reg .pred p; setp.ne.u32 p, %5, 0; @p ld.relaxed.gpu.global.v4.u32 {%0,%1,%2,%3}, [%4];}"
    : "+r"(v.x), "+r"(v.y), "+r"(v.z), "+r"(v.w) : "l"(p), "r"(again) : "memory");
}
__device__ __forceinline__ void st_relaxed4(void* p, uint32_t a, uint32_t b, uint32_t c, uint32_t d) {
  asm volatile("st.relaxed.gpu.global.v4.u32 [%0], {%1,%2,%3,%4};" :: "l"(p), "r"(a), "r"(b), "r"(c), "r"(d) : "memory");
}
__device__ __forceinline__ void st_relaxed_if(void* p, uint32_t a, bool on) {
  asm volatile("{.reg .pred p; setp.ne.u32 p, %2, 0; @p st.relaxed.gpu.global.u32 [%0], %1;}" :: "l"(p), "r"(a), "r"((uint32_t)on) : "memory");
}
__device__ __forceinline__ uint32_t ld_acquire(const uint32_t* p) {
  uint32_t v; asm volatile("ld.acquire.gpu.global.u32 %0, [%1];" : "=r"(v) : "l"(p) : "memory"); return v;
}
__device__ __forceinline__ void st_release(uint32_t* p, uint32_t v) {
  asm volatile("st.release.gpu.global.u32 [%0], %1;" :: "l"(p), "r"(v) : "memory");
}
__device__ __forceinline__ void bulk_reduce(float* dst, uint32_t src, uint32_t bytes) {
  asm volatile("cp.reduce.async.bulk.global.shared::cta.bulk_group.add.f32 [%0], [%1], %2;" :: "l"(dst), "r"(src), "r"(bytes) : "memory");
}
__device__ __forceinline__ void bulk_done_inc(uint32_t* p) {
  asm volatile("cp.async.bulk.wait_group 0;\nred.relaxed.gpu.global.add.u32 [%0], 1;\nred.relaxed.gpu.global.add.u32 [%0+4096], 1;" :: "l"(p) : "memory");
}
__device__ __forceinline__ void flag_release(uint32_t* p, uint32_t v) {
  asm volatile("fence.release.gpu;\nst.relaxed.gpu.global.u32 [%0], %1;\nst.relaxed.gpu.global.u32 [%0+4096], %1;" :: "l"(p), "r"(v) : "memory");
}
__device__ __forceinline__ void spin_guard(int& it) {
  asm volatile("{.reg .pred p; add.s32 %0, %0, 1; setp.gt.s32 p, %0, %1; @p trap;}" : "+r"(it) : "n"(SPIN_MAX));
}
__device__ __forceinline__ void wait_flag(const uint32_t* p, uint32_t v) {
  int it = 0;
  while (ld_acquire(p) < v) { if (NSLEEP) __nanosleep(NSLEEP); spin_guard(it); }
}
__device__ __forceinline__ void wait_flags(const uint32_t* p, uint32_t v) {
  int it = 0;
  while (true) {
    uint32_t x; asm volatile("ld.relaxed.gpu.global.u32 %0, [%1];" : "=r"(x) : "l"(p) : "memory");
    if (__all_sync(~0u, x >= v)) break;
    spin_guard(it);
  }
  asm volatile("fence.acquire.gpu;" ::: "memory");
}
__device__ __forceinline__ void grid_arrive(int i) {
  asm volatile("red.release.gpu.global.add.u32 [%0], %1;" :: "l"(g_gbar + i * 32), "r"(blockIdx.x ? 1u : 257u - N_CTA) : "memory");
}
__device__ __forceinline__ void grid_wait(int i, uint32_t gen) {
  int it = 0;
  while (((ld_acquire(g_gbar + i * 32) ^ gen) >> 8) == 0) spin_guard(it);
}
__device__ __forceinline__ void bar_sync(int id, int cnt) { asm volatile("bar.sync %0, %1;" :: "r"(id), "r"(cnt) : "memory"); }
__device__ __forceinline__ void bar_arrive(int id, int cnt) { asm volatile("bar.arrive %0, %1;" :: "r"(id), "r"(cnt) : "memory"); }
template <int id, int cnt> __device__ __forceinline__ void bar_arrive_after(uint32_t a, uint32_t b) {
  asm volatile("{.reg .pred p; setp.ne.u32 p, %2, 0xfff12345; setp.ne.and.u32 p, %3, 0xfff12345, p; @p bar.arrive %0, %1;}" :: "n"(id), "n"(cnt), "r"(a), "r"(b) : "memory");
}
template <int id, int cnt> __device__ __forceinline__ void bar_sync_after(uint32_t a) {
  asm volatile("{.reg .pred p; setp.ne.u32 p, %2, 0xfff12345; @p bar.sync %0, %1;}" :: "n"(id), "n"(cnt), "r"(a) : "memory");
}
__device__ __forceinline__ void fence_async_smem() { asm volatile("fence.proxy.async.shared::cta;" ::: "memory"); }
__device__ __forceinline__ void fence_async_global() { asm volatile("fence.proxy.async.global;" ::: "memory"); }
__device__ __forceinline__ void mbar_init(uint32_t mb, int cnt) { asm volatile("mbarrier.init.shared::cta.b64 [%0], %1;" :: "r"(mb), "r"(cnt) : "memory"); }
__device__ __forceinline__ void mbar_arrive(uint32_t mb) { asm volatile("mbarrier.arrive.shared::cta.b64 _, [%0];" :: "r"(mb) : "memory"); }
__device__ __forceinline__ void mbar_expect(uint32_t mb, uint32_t bytes) {
  asm volatile("mbarrier.arrive.expect_tx.shared::cta.b64 _, [%0], %1;" :: "r"(mb), "r"(bytes) : "memory");
}
__device__ __forceinline__ void mbar_wait_guard(uint32_t mb, uint32_t parity) {
  uint32_t ok; int it = 0;
  while (true) {
    asm volatile("{.reg .pred p; mbarrier.try_wait.parity.shared::cta.b64 p, [%1], %2; selp.u32 %0, 1, 0, p;}" : "=r"(ok) : "r"(mb), "r"(parity) : "memory");
    if (ok) break;
    spin_guard(it);
  }
}
__device__ __forceinline__ void mbar_wait(uint32_t mb, uint32_t parity) {
  asm volatile("{.reg .pred p;\nW: mbarrier.try_wait.parity.shared::cta.b64 p, [%0], %1;\n@!p bra W;}" :: "r"(mb), "r"(parity) : "memory");
}
__device__ __forceinline__ void bulk_load(uint32_t dst, const void* src, uint32_t bytes, uint32_t mb) {
  asm volatile("cp.async.bulk.shared::cluster.global.mbarrier::complete_tx::bytes [%0], [%1], %2, [%3];" :: "r"(dst), "l"(src), "r"(bytes), "r"(mb) : "memory");
}
__device__ __forceinline__ void cp_async16(uint32_t dst, const void* src) {
  asm volatile("cp.async.cg.shared.global [%0], [%1], 16;" :: "r"(dst), "l"(src) : "memory");
}
__device__ __forceinline__ void cp_async_wait_all() { asm volatile("cp.async.wait_all;" ::: "memory"); }
__device__ __forceinline__ uint32_t mapa(uint32_t a, uint32_t rank) {
  uint32_t r; asm("mapa.shared::cluster.u32 %0, %1, %2;" : "=r"(r) : "r"(a), "r"(rank)); return r;
}
__device__ __forceinline__ void st_async4(uint32_t dst, float a, float b, float c, float d, uint32_t mb) {
  asm volatile("st.async.shared::cluster.mbarrier::complete_tx::bytes.v4.f32 [%0], {%1,%2,%3,%4}, [%5];" :: "r"(dst), "f"(a), "f"(b), "f"(c), "f"(d), "r"(mb) : "memory");
}
__device__ __forceinline__ void st_async2(uint32_t dst, float a, float b, uint32_t mb) {
  asm volatile("st.async.shared::cluster.mbarrier::complete_tx::bytes.v2.f32 [%0], {%1,%2}, [%3];" :: "r"(dst), "f"(a), "f"(b), "r"(mb) : "memory");
}
__device__ __forceinline__ void st_async1(uint32_t dst, uint32_t a, uint32_t mb) {
  asm volatile("st.async.shared::cluster.mbarrier::complete_tx::bytes.u32 [%0], %1, [%2];" :: "r"(dst), "r"(a), "r"(mb) : "memory");
}
__device__ __forceinline__ uint4 lds128(uint32_t a) {
  uint4 v; asm volatile("ld.shared.v4.u32 {%0,%1,%2,%3}, [%4];" : "=r"(v.x), "=r"(v.y), "=r"(v.z), "=r"(v.w) : "r"(a) : "memory"); return v;
}
__device__ __forceinline__ uint2 lds64(uint32_t a) {
  uint2 v; asm volatile("ld.shared.v2.u32 {%0,%1}, [%2];" : "=r"(v.x), "=r"(v.y) : "r"(a) : "memory"); return v;
}
__device__ __forceinline__ uint32_t lds32(uint32_t a) {
  uint32_t v; asm volatile("ld.shared.u32 %0, [%1];" : "=r"(v) : "r"(a) : "memory"); return v;
}
__device__ __forceinline__ void sts128(uint32_t a, uint4 v) {
  asm volatile("st.shared.v4.u32 [%0], {%1,%2,%3,%4};" :: "r"(a), "r"(v.x), "r"(v.y), "r"(v.z), "r"(v.w) : "memory");
}
__device__ __forceinline__ void sts64(uint32_t a, uint32_t x, uint32_t y) {
  asm volatile("st.shared.v2.u32 [%0], {%1,%2};" :: "r"(a), "r"(x), "r"(y) : "memory");
}
__device__ __forceinline__ void sts32(uint32_t a, uint32_t x) { asm volatile("st.shared.u32 [%0], %1;" :: "r"(a), "r"(x) : "memory"); }
__device__ __forceinline__ void ldsm4(uint32_t& r0, uint32_t& r1, uint32_t& r2, uint32_t& r3, uint32_t a) {
  asm volatile("ldmatrix.sync.aligned.m8n8.x4.shared.b16 {%0,%1,%2,%3}, [%4];" : "=r"(r0), "=r"(r1), "=r"(r2), "=r"(r3) : "r"(a) : "memory");
}
__device__ __forceinline__ void ldsm4t(uint32_t& r0, uint32_t& r1, uint32_t& r2, uint32_t& r3, uint32_t a) {
  asm volatile("ldmatrix.sync.aligned.m8n8.x4.trans.shared.b16 {%0,%1,%2,%3}, [%4];" : "=r"(r0), "=r"(r1), "=r"(r2), "=r"(r3) : "r"(a) : "memory");
}
__device__ __forceinline__ void stsm4(uint32_t a, uint32_t r0, uint32_t r1, uint32_t r2, uint32_t r3) {
  asm volatile("stmatrix.sync.aligned.m8n8.x4.shared.b16 [%0], {%1,%2,%3,%4};" :: "r"(a), "r"(r0), "r"(r1), "r"(r2), "r"(r3) : "memory");
}
__device__ __forceinline__ uint32_t movmat(uint32_t a) {
  uint32_t d; asm volatile("movmatrix.sync.aligned.m8n8.trans.b16 %0, %1;" : "=r"(d) : "r"(a)); return d;
}
__device__ __forceinline__ void mma16(float* d, uint32_t a0, uint32_t a1, uint32_t a2, uint32_t a3, uint32_t b0, uint32_t b1) {
  asm volatile("mma.sync.aligned.m16n8k16.row.col.f32.bf16.bf16.f32 {%0,%1,%2,%3}, {%4,%5,%6,%7}, {%8,%9}, {%0,%1,%2,%3};"
    : "+f"(d[0]), "+f"(d[1]), "+f"(d[2]), "+f"(d[3]) : "r"(a0), "r"(a1), "r"(a2), "r"(a3), "r"(b0), "r"(b1));
}
__device__ __forceinline__ void mma8(float* d, uint32_t a0, uint32_t a1, uint32_t b0) {
  asm volatile("mma.sync.aligned.m16n8k8.row.col.f32.bf16.bf16.f32 {%0,%1,%2,%3}, {%4,%5}, {%6}, {%0,%1,%2,%3};"
    : "+f"(d[0]), "+f"(d[1]), "+f"(d[2]), "+f"(d[3]) : "r"(a0), "r"(a1), "r"(b0));
}
__device__ __forceinline__ float rcp(float x) { float r; asm("rcp.approx.ftz.f32 %0, %1;" : "=f"(r) : "f"(x)); return r; }
__device__ __forceinline__ float ex2(float x) { float r; asm("ex2.approx.ftz.f32 %0, %1;" : "=f"(r) : "f"(x)); return r; }

__host__ __device__ constexpr uint64_t mkdesc(uint32_t off, uint32_t lbo, uint32_t sbo, uint32_t swz) {
  return (uint64_t)((SBASE + off) >> 4) | ((uint64_t)(lbo >> 4) << 16) | ((uint64_t)(sbo >> 4) << 32) | ((uint64_t)swz << 62);
}
__host__ __device__ constexpr uint64_t desc_sw128(uint32_t off) { return mkdesc(off, 16, 1024, 1); }
__host__ __device__ constexpr uint64_t desc_n16(uint32_t off) { return mkdesc(off, 256, 128, 0); }
__host__ __device__ constexpr uint64_t desc_m(uint32_t off) { return mkdesc(off, 16, 256, 3); }

__device__ __forceinline__ void wg_fence() { asm volatile("wgmma.fence.sync.aligned;" ::: "memory"); }
__device__ __forceinline__ void wg_commit() { asm volatile("wgmma.commit_group.sync.aligned;" ::: "memory"); }
template <int N> __device__ __forceinline__ void wg_wait() { asm volatile("wgmma.wait_group.sync.aligned %0;" :: "n"(N) : "memory"); }

#define ACC8(d) "+f"(d[0]), "+f"(d[1]), "+f"(d[2]), "+f"(d[3]), "+f"(d[4]), "+f"(d[5]), "+f"(d[6]), "+f"(d[7])
#define ACC32(d) ACC8(d), ACC8((d + 8)), ACC8((d + 16)), ACC8((d + 24))
#define R8 "{%0,%1,%2,%3,%4,%5,%6,%7}"
#define R32 "{%0,%1,%2,%3,%4,%5,%6,%7,%8,%9,%10,%11,%12,%13,%14,%15,%16,%17,%18,%19,%20,%21,%22,%23,%24,%25,%26,%27,%28,%29,%30,%31}"
template <int SD> __device__ __forceinline__ void wg_rs16(float* d, const uint32_t* a, uint64_t db) {
  asm volatile("wgmma.mma_async.sync.aligned.m64n16k16.f32.bf16.bf16 " R8 ", {%8,%9,%10,%11}, %12, %13, 1, 1, 1;"
    : ACC8(d) : "r"(a[0]), "r"(a[1]), "r"(a[2]), "r"(a[3]), "l"(db), "n"(SD));
}
template <int SD> __device__ __forceinline__ void wg_ss16(float* d, uint64_t da, uint64_t db) {
  asm volatile("wgmma.mma_async.sync.aligned.m64n16k16.f32.bf16.bf16 " R8 ", %8, %9, %10, 1, 1, 1, 1;"
    : ACC8(d) : "l"(da), "l"(db), "n"(SD));
}
template <int SD> __device__ __forceinline__ void wg_rs64(float* d, const uint32_t* a, uint64_t db) {
  asm volatile("wgmma.mma_async.sync.aligned.m64n64k16.f32.bf16.bf16 " R32 ", {%32,%33,%34,%35}, %36, %37, 1, 1, 0;"
    : ACC32(d) : "r"(a[0]), "r"(a[1]), "r"(a[2]), "r"(a[3]), "l"(db), "n"(SD));
}
template <int SD> __device__ __forceinline__ void wg_ss64(float* d, uint64_t da, uint64_t db) {
  asm volatile("wgmma.mma_async.sync.aligned.m64n64k16.f32.bf16.bf16 " R32 ", %32, %33, %34, 1, 1, 1, 0;"
    : ACC32(d) : "l"(da), "l"(db), "n"(SD));
}
template <int N> __device__ __forceinline__ void reg_inc() { asm volatile("setmaxnreg.inc.sync.aligned.u32 %0;" :: "n"(N)); }
template <int N> __device__ __forceinline__ void reg_dec() { asm volatile("setmaxnreg.dec.sync.aligned.u32 %0;" :: "n"(N)); }
__device__ __forceinline__ void cluster_sync() {
  asm volatile("barrier.cluster.arrive.relaxed.aligned;\nbarrier.cluster.wait.aligned;" ::: "memory");
}

template <int KS>
__device__ __forceinline__ void load_frags(uint32_t* a, uint32_t src) {
  const int lane = threadIdx.x & 31, w = (threadIdx.x >> 5) & 3;
  const int k = ((lane >> 4) << 3) + (lane & 7), u = w * 2 + ((lane >> 3) & 1);
  const uint32_t base = src + k * 128 + ((u ^ (k & 7)) << 4);
#pragma unroll
  for (int ks = 0; ks < KS; ks++) ldsm4t(a[ks * 4], a[ks * 4 + 1], a[ks * 4 + 2], a[ks * 4 + 3], base + ks * 2048);
}

__device__ __forceinline__ uint32_t badd2(uint32_t a, uint32_t b) { uint32_t r; asm("add.rn.bf16x2 %0, %1, %2;" : "=r"(r) : "r"(a), "r"(b)); return r; }
__device__ __forceinline__ uint32_t bsub2(uint32_t a, uint32_t b) { uint32_t r; asm("sub.rn.bf16x2 %0, %1, %2;" : "=r"(r) : "r"(a), "r"(b)); return r; }
__device__ __forceinline__ uint32_t bmul2(uint32_t a, uint32_t b) { uint32_t r; asm("mul.rn.bf16x2 %0, %1, %2;" : "=r"(r) : "r"(a), "r"(b)); return r; }
__device__ __forceinline__ float row_sum(const uint32_t* x) {
  const uint32_t ones = 0x3F803F80u;
  float a[4] = {0.f, 0.f, 0.f, 0.f}, b[4] = {0.f, 0.f, 0.f, 0.f};
  mma16(a, ones, ones, ones, ones, x[0], x[1]);
  mma16(b, ones, ones, ones, ones, x[2], x[3]);
  mma16(a, ones, ones, ones, ones, x[4], x[5]);
  mma16(b, ones, ones, ones, ones, x[6], x[7]);
  mma8(a, ones, ones, x[8]);
  float s = (a[0] + a[1]) + (b[0] + b[1]);
  s += __shfl_xor_sync(~0u, s, 1);
  return s + __shfl_xor_sync(~0u, s, 2);
}
__device__ __forceinline__ void layernorm9(const uint32_t* x, uint32_t* o) {
  const float mean = row_sum(x) * (1.f / DM);
  const uint32_t mb = pack2(mean, mean);
  float c[18], s0 = 0.f, s1 = 0.f;
#pragma unroll
  for (int i = 0; i < 9; i++) {
    const uint32_t d = bsub2(x[i], mb);
    c[2 * i] = bf_lo(d); c[2 * i + 1] = bf_hi(d);
    s0 = fmaf(c[2 * i], c[2 * i], s0); s1 = fmaf(c[2 * i + 1], c[2 * i + 1], s1);
  }
  float s = s0 + s1;
#pragma unroll
  for (int m = 16; m; m >>= 1) s += __shfl_xor_sync(~0u, s, m);
  const float off = mean - bf_lo(mb), var = fmaxf(fmaf(s, 1.f / DM, -off * off), 0.f);
  float sd;
  asm("sqrt.approx.f32 %0, %1;" : "=f"(sd) : "f"(bf_lo(pack2(bf_lo(pack2(var, 0.f)) + 1e-5f, 0.f))));
  const float inv = rcp(bf_lo(pack2(sd, 0.f)));
#pragma unroll
  for (int i = 0; i < 9; i++) o[i] = pack2(c[2 * i] * inv, c[2 * i + 1] * inv);
}
__device__ __forceinline__ void store_ln_row(int layer, int tok, const uint32_t* o) {
  const int lane = threadIdx.x & 31, r = tok & 31;
  unsigned char* p = g_lnimg + (size_t)(layer * NSEG + (tok >> 5)) * (9 * 4096) + r * 128 + (((lane >> 2) ^ (r & 7)) << 4) + (lane & 3) * 4;
#pragma unroll
  for (int i = 0; i < 9; i++) *(uint32_t*)(p + i * 4096) = o[i];
}
struct Params { const bf16 *X, *K, *V, *shift, *Hk, *Dk, *mem0, *Wq, *Wk, *Wv, *Wo; bf16* out; uint32_t dly[8]; };
#define DLY1 P.dly[0]
#define DLY3 P.dly[1]
#define KLATE P.dly[2]
#define DLYQ P.dly[3]
#define DLYK P.dly[4]
#define DLYG P.dly[5]
#define KWIN P.dly[6]
#define KMIN P.dly[7]
uint32_t h_dly[8] = {150, 1500, 0, 0, 3700, 1900, 2300, 0};

constexpr uint32_t C_W = 0, C_M = 147456, C_KV = C_M + 18432, C_QM = C_KV + 32768, C_KM = C_QM + 2048,
                   C_VM = C_KM + 2048, C_OI = C_VM + 2048, C_SX = C_OI + 4096, C_KM2 = C_SX + 2560, C_VM2 = C_KM2 + 1024,
                   C_KV2 = C_VM2 + 1024, C_Q = C_KV2 + 8192, C_BAR = C_Q + 8192;
constexpr uint32_t CB_FULL = C_BAR, CB_EMPTY = C_BAR + 16, CB_SX = C_BAR + 32, CB_OX = C_BAR + 40, CB_XX = C_BAR + 48, CB_Q = C_BAR + 56, C_SEL = C_BAR + 64, S_GEN = C_BAR + 128, CB_VF = C_BAR + 144, CB_M = C_BAR + 160;
constexpr uint32_t G_W = 0, G_RING = 147456, G_W2 = G_RING + 9 * 8192, G_BAR = G_W2 + 8192;
constexpr uint32_t O_W = 0, O_RING = 3 * 40960, O_ST = O_RING + 11 * 8192, O_BAR = O_ST + 16384, OB_ST = O_BAR + 64;
constexpr uint32_t F_XY = RING * 18432, F_A = F_XY + 36864, F_BAR = F_A + 36864;
constexpr uint32_t SMEM_BYTES = C_BAR + 256;
static_assert(G_BAR + 256 <= SMEM_BYTES && O_BAR + 256 <= SMEM_BYTES && F_BAR + 16 <= SMEM_BYTES && SMEM_BYTES <= 232448, "smem map");
enum { B_INIT = 1, B_M, B_QK, B_S, B_V, B_O, B_X, B_WG0, B_WG1, B_WG2, B_G, B_OE, B_T, B_R };

__device__ __forceinline__ uint4 pack_partial(const float* d, uint32_t tag) {
  return make_uint4((pack2(d[0], d[1]) & ~1u) | tag, pack2(d[4], d[5]), pack2(d[2], d[3]), pack2(d[6], d[7]));
}
__device__ __forceinline__ void store_partial(uint4* p, const uint4& v) { st_b128(p, v.x, v.y, v.z, v.w); }
template <bool GUARD>
__device__ __forceinline__ float2 gather_reduce(const uint4* p, uint32_t tag, uint32_t lane) {
  uint4 x[4];
  const uint32_t sel[4] = {(lane & 4) ? 0u : 0x3F803F80u, lane, (lane & 4) ? 0x3F803F80u : 0u, lane + 1};
#define G_LD(p, o, v) "@" p " ld.relaxed.gpu.global.b128 " v ", [%16+" o "];\n"
#define G_CK(p, v, r) "mov.b128 {" r "}, " v ";\n"
  asm volatile("{.reg .pred pa, pb, pc, pd, q; .reg .b128 a, b, c, d; .reg .b32 t, n;\n"
               "setp.eq.u32 pa, 0, 0; mov.pred pb, pa; mov.pred pc, pa; mov.pred pd, pa; mov.u32 n, 0;\n"
               "mov.b128 a, {n, n, n, n}; mov.b128 b, a; mov.b128 c, a; mov.b128 d, a;\n"
               "L:\n" G_LD("pa", "0", "a") G_LD("pb", "512", "b") G_LD("pc", "1024", "c") G_LD("pd", "1536", "d")
               "add.u32 n, n, %18; setp.gt.u32 q, n, %19; @q trap;\n"
               G_CK("pa", "a", "%0,%1,%2,%3") G_CK("pb", "b", "%4,%5,%6,%7") G_CK("pc", "c", "%8,%9,%10,%11") G_CK("pd", "d", "%12,%13,%14,%15")
               "lop3.b32 t, %0, %17, 1, 0x28; setp.ne.u32 pa, t, 0; lop3.b32 t, %4, %17, 1, 0x28; setp.ne.u32 pb, t, 0;\n"
               "lop3.b32 t, %8, %17, 1, 0x28; setp.ne.u32 pc, t, 0; lop3.b32 t, %12, %17, 1, 0x28; setp.ne.u32 pd, t, 0;\n"
               "or.pred q, pa, pb; or.pred q, q, pc; or.pred q, q, pd; vote.sync.any.pred q, q, -1; @q bra L;}"
               : "=&r"(x[0].x), "=&r"(x[0].y), "=&r"(x[0].z), "=&r"(x[0].w), "=&r"(x[1].x), "=&r"(x[1].y), "=&r"(x[1].z), "=&r"(x[1].w),
                 "=&r"(x[2].x), "=&r"(x[2].y), "=&r"(x[2].z), "=&r"(x[2].w), "=&r"(x[3].x), "=&r"(x[3].y), "=&r"(x[3].z), "=&r"(x[3].w)
               : "l"(p), "r"(tag), "n"(GUARD ? 1 : 0), "n"(SPIN_MAX) : "memory");
#undef G_LD
#undef G_CK
#pragma unroll
  for (int i = 0; i < 4; i++)
    asm volatile("movmatrix.sync.aligned.m8n8.trans.b16 %0, %0; movmatrix.sync.aligned.m8n8.trans.b16 %1, %1;\n"
                 "movmatrix.sync.aligned.m8n8.trans.b16 %2, %2; movmatrix.sync.aligned.m8n8.trans.b16 %3, %3;"
                 : "+r"(x[i].x), "+r"(x[i].y), "+r"(x[i].z), "+r"(x[i].w));
  float a[4] = {0.f, 0.f, 0.f, 0.f}, b[4] = {0.f, 0.f, 0.f, 0.f};
#pragma unroll
  for (int i = 0; i < 4; i++) {
    mma16(a, sel[0], sel[1], sel[2], sel[3], x[i].x, x[i].y);
    mma16(b, sel[0], sel[1], sel[2], sel[3], x[i].z, x[i].w);
  }
  return (lane & 8) ? make_float2(b[0], b[1]) : make_float2(a[0], a[1]);
}
__device__ __forceinline__ uint32_t sent_bad(const uint4& v) { return max(max(v.x, v.y), max(v.z, v.w)) == SENT; }

__host__ __device__ constexpr uint32_t m_off(int ks) { return C_M + (ks < 20 ? (ks >> 2) * 4096 : ((ks - 20) >> 2) * 4096 + 2048) + (ks & 3) * 512; }
template <int SD> __device__ __forceinline__ void m_rs(float* d, const uint32_t* a, int ks) { wg_rs16<SD>(d, a, desc_m(m_off(ks))); }
template <int SD> __device__ __forceinline__ void m_ss(float* d, int slot, int ks) { wg_ss16<SD>(d, desc_sw128(C_W + slot * 2048), desc_m(m_off(ks))); }
__device__ __forceinline__ void o_own(float* d, int slot) {
  wg_ss16<0>(d, desc_sw128(C_W + slot * 2048), desc_n16(C_OI));
#pragma unroll
  for (int ks = 1; ks < 4; ks++) wg_ss16<1>(d, desc_sw128(C_W + (slot + ks) * 2048), desc_n16(C_OI + ks * 512));
}
__device__ __forceinline__ int g_unit(int wg) {
  const int i = blockIdx.x - N_CHAIN;
  return i < 32 ? wg * 64 + i : 2 * i - 32 + wg;
}
__device__ __forceinline__ const bf16* slot_row(const Params& P, bool regs, int i, int r) {
  const int b = blockIdx.x;
  if (b < N_CHAIN) {
    const int wg = i >= 36, col = b * 64;
    i -= wg * 36;
    if (regs ? i < 24 : wg == 0 || i < 24) {
      const bf16* w; int ks;
      if (regs) { w = wg ? P.Wv : P.Wq; ks = wg ? i + (i >> 1) : i; }
      else if (wg == 0) { w = P.Wk; ks = i; }
      else if (i < 12) { w = P.Wq; ks = 24 + i; }
      else { w = P.Wv; ks = 3 * (i - 12) + 2; }
      return w + col + (size_t)(ks * 16 + ((r & 1) << 3) + (r >> 1)) * HD;
    }
    int ks, f;
    if (regs) { ks = i < 28 ? i - 20 : i - 28; f = (b & 1) * 320 + (i < 28 ? wg : wg + 2) * 64; }
    else { ks = i & 3; f = i < 28 ? 256 : (b & 1) * 320 + ((i >> 2) - 7) * 64; }
    return P.Wo + f + (size_t)((col ^ ((ks & 4) << 4)) + (ks & 3) * 16 + r) * DM;
  }
  if (b < N_CHAIN + N_G) {
    int wg = i >= 36, ks = i - wg * 36;
    if (i >= 72) { wg = (i - 72) >> 1; ks = 34 + (i & 1); regs = true; }
    const int q = g_unit(wg);
    const bf16* w = (q < 32 ? P.Wk : q < 64 ? P.Wv : P.Wq) + (q & 31) * 128 + (regs ? 0 : 64);
    return w + (size_t)(ks * 16 + r) * HD;
  }
  const int o = b - N_CHAIN - N_G, ksl = o / 3, per = regs ? 24 : 20, wg = i / per;
  const int k = (ksl * 11 - max(ksl - 4, 0)) * 64 + (i - wg * per + (regs ? 0 : 24)) * 16 + r;
  const int kk = (k & ~31) | (((k >> 1) & 3) << 3) | (((k >> 3) & 3) << 1) | (k & 1);
  return P.Wo + (size_t)kk * DM + ((o % 3) * 3 + (wg + ksl) % 3) * 64;
}
__device__ __forceinline__ void load_run(const Params& P, uint32_t dst, bool regs, int i0, int n) {
  const int r = (threadIdx.x & 127) >> 3, u = threadIdx.x & 7;
  const bf16* p0 = slot_row(P, regs, i0, r) + u * 8;
  const bf16* p1 = slot_row(P, regs, i0 + 1, r) + u * 8;
  const long step = n > 2 ? slot_row(P, regs, i0 + 2, r) + u * 8 - p0 : 0;
  dst += r * 128 + ((u ^ (r & 7)) << 4);
#pragma unroll 2
  for (int i = 0; i < n; i += 2, dst += 4096, p0 += step, p1 += step) {
    cp_async16(dst, p0);
    cp_async16(dst + 2048, p1);
    if (regs) asm volatile("cp.async.commit_group;\ncp.async.wait_group %0;" :: "n"(INFL) : "memory");
  }
}
__device__ __forceinline__ void load_wg(const Params& P, uint32_t sb, bool regs, int wg) {
  if (blockIdx.x < N_CHAIN) {
#pragma unroll 1
    for (int k = 0; k < 5; k++) {
      const int i0 = wg * 36 + (k < 2 ? k * 12 : 16 + k * 4);
      load_run(P, sb + i0 * 2048, regs, i0, k < 2 ? 12 : 4);
    }
  } else if (blockIdx.x < N_CHAIN + N_G) {
    load_run(P, sb + wg * 73728, regs, wg * 36, regs ? 34 : 36);
    if (!regs) load_run(P, sb + G_W2 + wg * 4096, false, 72 + wg * 2, 2);
  } else {
    const int per = regs ? 24 : 20;
    load_run(P, sb + wg * per * 2048, regs, wg * per, regs || blockIdx.x < N_CHAIN + N_G + 12 ? per : 16);
  }
}
__device__ __forceinline__ uint32_t near_half(uint32_t blk, uint32_t reader) {
  return __ldcg(g_near + blk) ^ __ldcg(g_side + blk % N_CTA) ^ __ldcg(g_side + reader);
}

__device__ __forceinline__ uint32_t opaque_tid() { uint32_t t; asm volatile("mov.u32 %0, %%tid.x;" : "=r"(t)); return t; }
__device__ __forceinline__ uint32_t m_block(uint32_t sb, int n, uint32_t r) {
  return (n % MRING) * 40960 + r * 8192 + ((lds32(sb + C_SEL + (n % MRING) * 4) >> r) & 1) * 4096;
}

template <int WG>
__device__ __forceinline__ void chain_proj(const Params& P, uint32_t sb) {
  const uint32_t c = blockIdx.x, h = c >> 1, j = c & 1;
  uint32_t a[144];
  uint32_t sels;
  {
    const uint32_t pslot = (threadIdx.x & 127) >> 2, rf = 2 * pslot + j, rs = 2 * pslot + ((threadIdx.x >> 1) & 1);
    sels = near_half(rf * 3, rf) | (near_half(rf * 3 + 1, rf) << 1) | (near_half(rs * 3 + 2, rs) << 2) | (near_half(c * 3 + 1, c) << 5);
    const uint32_t stage = sb + C_W + WG * 73728;
    load_frags<36>(a, stage);
    bar_sync(B_WG0 + WG, 128);
    load_wg(P, sb, false, WG);
    cp_async_wait_all();
    fence_async_smem();
    bar_sync(B_INIT, 320);
  }
  TS(4);

  uint32_t mph = 0;
  uint32_t t0 = clk() - DLY3;
#pragma unroll 1
  for (int n = 0; n < STEPS; n++) {
    float d[8];
    CKDECL;
    {
      const uint32_t t = opaque_tid(), w = (t >> 5) & 3, lane = t & 31;
      if (WG == 1 || w == 1) {
        const uint32_t r = WG ? w : 4, mb = sb + CB_M + r * 8, dst = sb + C_M + r * 4096;
        const unsigned char* src = (const unsigned char*)g_mimg + m_block(sb, n, r);
        const uint32_t chk = dst + lane * 32 + (lane & 4) * 4 + (lane >> 3) * 4;
        bar_sync(B_T, 192);
        uint32_t x;
        do {
          if (lane == 0) {
            mbar_expect(mb, WG ? 4096 : 2048);
            bulk_load(dst, src, WG ? 4096 : 2048, mb);
          }
          __syncwarp();
          mbar_wait(mb, mph);
          mph ^= 1;
          x = max(max(lds32(chk), lds32(chk + 1024)), WG ? max(lds32(chk + 2048), lds32(chk + 3072)) : max(lds32(chk ^ 8), lds32((chk ^ 8) + 1024)));
        } while (__any_sync(~0u, x == SENT));
      } else if (w == 3) {
        wait_until(t0, DLY3);
        bar_arrive(B_T, 192);
      }
      bar_sync(B_M, 256);
      if (WG == 0) bar_arrive(B_G, 288 + OBSW);
      CK(0, 0);
      wg_fence();
#pragma unroll
      for (int ks = 0; ks < 36; ks++) {
        if (WG == 1) { if (ks == 0) m_ss<0>(d, 0, 0); else m_ss<1>(d, ks, ks); }
        else if (ks == 0) m_rs<0>(d, a, 0);
        else if (ks < 24) m_rs<1>(d, a + ks * 4, ks);
        else m_ss<1>(d, 12 + ks, ks);
      }
      wg_commit();
    }
    const uint32_t t = opaque_tid() & 127, lane = t & 31, w = t >> 5;
    const uint32_t qk_dst = sb + (WG == 0 ? C_QM : C_KM) + t * 16;
    wg_wait<0>();
    CK(1, 0);
    const uint32_t f0 = pack2(d[0], d[1]), f1 = pack2(d[4], d[5]), f2 = pack2(d[2], d[3]), f3 = pack2(d[6], d[7]);
    stsm4(qk_dst, f0, f1, f2, f3);
    bar_arrive(B_QK, 384 + OBSW);
    if (WG == 1) {
      const uint32_t rb = mapa(sb, j ^ 1), fa = j ? f0 : f1, fb = j ? f2 : f3;
      wg_fence();
#pragma unroll
      for (int i = 0; i < VEARLY; i++) { if (i == 0) m_rs<0>(d, a, 0); else m_rs<1>(d, a + i * 4, i + (i >> 1)); }
      wg_commit();
      if (n + 1 < STEPS) bar_sync(B_S, 256);
      wg_fence();
#pragma unroll
      for (int i = 0; i < 12; i++) {
#pragma unroll
        for (int k = VEARLY + i * VMIX / 12; k < VEARLY + (i + 1) * VMIX / 12; k++) m_rs<1>(d, a + k * 4, k + (k >> 1));
        m_ss<1>(d, 48 + i, 3 * i + 2);
      }
#pragma unroll
      for (int k = VEARLY + VMIX; k < 24; k++) m_rs<1>(d, a + k * 4, k + (k >> 1));
      wg_commit();
      st_async1(rb + C_KM2 + w * 256 + lane * 4, fa, rb + CB_XX);
      st_async1(rb + C_KM2 + w * 256 + 128 + lane * 4, fb, rb + CB_XX);
      wg_wait<0>();
      CK(3, 0);
      sts64(sb + C_VM + t * 8, pack2(d[0], d[1]), pack2(d[2], d[3]));
      sts64(sb + C_VM + 1024 + t * 8, pack2(d[4], d[5]), pack2(d[6], d[7]));
      bar_arrive(B_V, 256);
      st_async2(rb + C_VM2 + t * 8, __uint_as_float(j ? pack2(d[0], d[1]) : pack2(d[4], d[5])),
                __uint_as_float(j ? pack2(d[2], d[3]) : pack2(d[6], d[7])), rb + CB_XX);
    }
    if (n + 1 == STEPS) break;
    const uint32_t tag = (n & 1) ^ 1;
    const uint32_t pslot = t >> 2;
    uint4* const dst_full = g_inbox + ((2 * pslot + j) * 1536 + WG * 128 + h * 4 + (lane & 3));
    uint4* const dst_shared = g_inbox + ((2 * pslot + ((lane >> 1) & 1)) * 1536 + 1024 + (sels & 4) * 64 + c * 2 + (lane & 1));
    bar_sync(B_O, 384);
    if (!FENCE2) fence_async_smem();
    CK(4, 0);
    float e[8];
    uint4 ps;
    wg_fence();
    if (WG == 0) {
      o_own(e, 60);
      wg_commit();
      o_own(d, 64);
      wg_commit();
      wg_wait<1>();
      ps = pack_partial(e, tag);
    } else {
      o_own(d, 68);
      wg_commit();
    }
    CK(2, 0);
    mbar_wait(sb + CB_OX, n & 1);
    fence_async_smem();
    CK(5, 0);
    wg_fence();
#pragma unroll
    for (int ks = 4; ks < 8; ks++) wg_rs16<1>(d, a + (20 + ks) * 4, desc_n16(C_OI + ks * 512));
    wg_commit();
    if (WG == 0) store_partial(dst_shared, ps);
    wg_rs16<0>(e, a + 28 * 4, desc_n16(C_OI));
#pragma unroll
    for (int ks = 1; ks < 8; ks++) wg_rs16<1>(e, a + (28 + ks) * 4, desc_n16(C_OI + ks * 512));
    wg_commit();
    wg_wait<1>();
    store_partial(dst_full + (sels & 1) * 256, pack_partial(d, tag));
    wg_wait<0>();
    CK(6, 0);
    store_partial(dst_full + 512 + (sels & 2) * 128, pack_partial(e, tag));
    CK(7, 0);
    bar_sync(B_OE, 480);
    if (WG == 0) t0 = clk();
    if (WG == 0 && !(w & 1)) {
      uint32_t woff = ((n + 1) % MRING) * 10240 + 4096 + w * 1024 + j * 512 + h * 16 + ((lane & 15) ^ ((h & 2) * 2)) + (lane >> 4) * 1024;
      asm volatile("" : "+r"(woff));
      const uint4* src = g_inbox + (c * 1536 + 512 + (sels & 32) * 8 + w * 64 + lane);
      wait_until(t0, DLY1);
      const float2 r = gather_reduce<false>(src, tag, lane);
      st_relaxed_if(g_mimg + woff, pack2(r.x, r.y), n >= LAG || !(lane & 4));
      bar_arrive(B_R, 288);
      TR(4 + (w >> 1));
    }
    CKOUT(WG * 8);
  }
}

__device__ __forceinline__ void chain_attn(const Params& P, uint32_t sb) {
  const int c = blockIdx.x, j = c & 1;
  const int tid = threadIdx.x, lane = tid & 31, w = (tid >> 5) & 3;
  const int l = w >> 1, u = w & 1;
  const uint32_t rb = mapa(sb, j ^ 1);
  const float sc = 0.08838834764831845f * 1.4426950408889634f;
  const uint32_t ones = 0x3F803F80u;
  const uint32_t km_off = C_KM + (lane >> 3) * 256 + l * 128 + (lane & 7) * 16;
  const uint32_t qm_off = C_QM + (lane >> 4) * 256 + l * 128 + (lane & 7) * 16;

#pragma unroll 1
  for (int n = 0; n < STEPS; n++) {
    const uint32_t kvb = sb + C_KV + (n & 1) * 16384 + l * 4096 + lane * 16;
    bar_arrive(B_G, 288 + OBSW);
    if (tid == 256) { mbar_expect(sb + CB_SX, 2560); mbar_expect(sb + CB_OX, 2048); mbar_expect(sb + CB_XX, 2048); }
    mbar_wait(sb + CB_FULL + (n & 1) * 8, (n >> 1) & 1);
    PROF(9);
    if (n == 0) TS(5);
    __syncwarp();
    {
      CKDECL;
      uint32_t km[8];
      uint4 kx[8];
#pragma unroll
      for (int i = 0; i < 8; i++) kx[i] = lds128((kvb + i * 512) ^ (u * 512));
      CKW(7, kx[7].x);
      mbar_wait(sb + CB_VF + (n & 1) * 8, (n >> 1) & 1);
      bar_sync(B_QK, 384 + OBSW);
      if (n + 1 == STEPS) {
        bar_sync(B_V, 256);
      } else {
      uint32_t qm[16];
#pragma unroll
      for (int ks = 0; ks < 4; ks++) ldsm4t(qm[4 * ks], qm[4 * ks + 1], qm[4 * ks + 2], qm[4 * ks + 3], sb + qm_off + ks * 512);
      ldsm4t(km[0], km[1], km[2], km[3], sb + km_off);
      ldsm4t(km[4], km[5], km[6], km[7], sb + km_off + 1024);
      CKW(0, qm[0]);
      float s[5][4];
#pragma unroll
      for (int i = 0; i < 5; i++) { s[i][0] = s[i][1] = s[i][2] = s[i][3] = 0.f; }
#pragma unroll
      for (int ks = 0; ks < 4; ks++) {
        const uint32_t* q = qm + 4 * ks;
        mma16(s[1], q[0], q[1], q[2], q[3], kx[2 * ks].x, kx[2 * ks].y);
        mma16(s[2], q[0], q[1], q[2], q[3], kx[2 * ks].z, kx[2 * ks].w);
        mma16(s[0], q[0], q[1], q[2], q[3], km[2 * ks], km[2 * ks + 1]);
        mma16(s[3], q[0], q[1], q[2], q[3], kx[2 * ks + 1].x, kx[2 * ks + 1].y);
        mma16(s[4], q[0], q[1], q[2], q[3], kx[2 * ks + 1].z, kx[2 * ks + 1].w);
      }
      const float s5[2] = {0.f, 0.f};
      const uint32_t sx = C_SX + l * 1280;
      st_async4(rb + sx + u * 512 + lane * 16, s[1][0], s[1][1], s[2][0], s[2][1], rb + CB_SX);
      st_async1(rb + sx + 1024 + u * 128 + lane * 4, __float_as_uint(u ? s[0][1] : s[0][0]), rb + CB_SX);
      bar_arrive_after<B_S, 256>(__float_as_uint(s[3][0]), __float_as_uint(s[4][0]));
      uint4 vx[4];
#pragma unroll
      for (int i = 0; i < 4; i++) vx[i] = lds128((kvb + 8192 + (4 * u + i) * 512) ^ (u * 512));
      if (!SORD) { s[4][0] += s5[0]; s[4][1] += s5[1]; }
      CK(2, 0);
      mbar_wait(sb + CB_SX, n & 1);
      CK(3, 0);
      const uint4 p0 = lds128(sb + sx + u * 512 + lane * 16), p1 = lds128(sb + sx + (u ^ 1) * 512 + lane * 16);
      const uint2 p2 = make_uint2(lds32(sb + sx + 1024 + lane * 4), lds32(sb + sx + 1152 + lane * 4));
      float t[10] = {s[0][0] + __uint_as_float(p2.x), s[0][1] + __uint_as_float(p2.y),
                     s[1][0] + __uint_as_float(p0.x), s[1][1] + __uint_as_float(p0.y),
                     s[2][0] + __uint_as_float(p0.z), s[2][1] + __uint_as_float(p0.w),
                     s[3][0] + __uint_as_float(p1.x), s[3][1] + __uint_as_float(p1.y),
                     s[4][0] + __uint_as_float(p1.z), s[4][1] + __uint_as_float(p1.w)};
      float mx = fmaxf(fmaxf(fmaxf(fmaxf(t[2], t[3]), fmaxf(t[4], t[5])), fmaxf(fmaxf(t[6], t[7]), fmaxf(t[8], t[9]))), fmaxf(t[0], t[1]));
      mx = fmaxf(fmaxf(mx, __shfl_xor_sync(~0u, mx, 1)), fmaxf(__shfl_xor_sync(~0u, mx, 2), __shfl_xor_sync(~0u, mx, 3)));
      const float ms = -mx * sc;
#pragma unroll
      for (int i = 0; i < 10; i++) t[i] = ex2(fmaf(t[i], sc, ms));
      uint32_t p[5];
#pragma unroll
      for (int i = 0; i < 5; i++) p[i] = pack2(t[2 * i], t[2 * i + 1]);
      p[1] |= (p[0] & p[3] & p[4]) & 0x80008000u;
      CKW(4, p[1]);
      float o[2][4], z[4] = {0.f, 0.f, 0.f, 0.f};
      mma16(z, ones, ones, ones, ones, p[1], p[2]);
#pragma unroll
      for (int i = 0; i < 2; i++) {
        o[i][0] = o[i][1] = o[i][2] = o[i][3] = 0.f;
        mma16(o[i], vx[2 * i].x, vx[2 * i].y, vx[2 * i].z, vx[2 * i].w, p[1], p[2]);
      }
      mma16(z, ones, ones, ones, ones, p[3], p[4]);
#pragma unroll
      for (int i = 0; i < 2; i++) mma16(o[i], vx[2 * i + 1].x, vx[2 * i + 1].y, vx[2 * i + 1].z, vx[2 * i + 1].w, p[3], p[4]);
      mma8(z, ones, ones, p[0]);
      bar_sync_after<B_V, 256>(p[1]);
      const uint2 vm0 = lds64(sb + C_VM + l * 1024 + (2 * u) * 256 + lane * 8), vm1 = lds64(sb + C_VM + l * 1024 + (2 * u + 1) * 256 + lane * 8);
      CKW(5, vm0.x);
      mma8(o[0], vm0.x, vm0.y, p[0]);
      mma8(o[1], vm1.x, vm1.y, p[0]);
      const float i0 = rcp(z[0]), i1 = rcp(z[1]);
      const uint32_t oo = C_OI + u * 1024 + l * 128 + lane * 4;
      uint32_t ow[4];
#pragma unroll
      for (int i = 0; i < 2; i++) { ow[2 * i] = pack2(o[i][0] * i0, o[i][1] * i1); ow[2 * i + 1] = pack2(o[i][2] * i0, o[i][3] * i1); }
#pragma unroll
      for (int i = 0; i < 4; i++) st_async1(rb + oo + 2048 + i * 256, ow[i], rb + CB_OX);
      stsm4(sb + C_OI + u * 1024 + l * 128 + (lane >> 3) * 256 + (lane & 7) * 16, ow[0], ow[1], ow[2], ow[3]);
      if (FENCE2) fence_async_smem();
      bar_arrive(B_O, 384);
      CK(6, 0);
      CKOUT(16);
      }
    }
    {
      const uint32_t ot = opaque_tid();
      const int lane = ot & 31, g = lane >> 2, tq = lane & 3, u = (ot >> 5) & 1, v = (ot >> 6) & 1;
      const uint32_t own = sb + C_KV + (n & 1) * 16384 + j * 4096 + lane * 16, oth = sb + C_KV2 + lane * 16;
      if (n + 1 < STEPS) bar_sync(B_OE, 480);
      mbar_wait(sb + CB_Q, n & 1);
      mbar_wait(sb + CB_XX, n & 1);
      PROF(10);
      float s[5][4];
#pragma unroll
      for (int i = 0; i < 5; i++) { s[i][0] = s[i][1] = s[i][2] = s[i][3] = 0.f; }
#pragma unroll
      for (int hf = 0; hf < 2; hf++) {
        uint32_t km[8];
        const uint32_t ka = hf ? sb + C_KM2 + lane * 16 : sb + C_KM + (lane >> 3) * 256 + j * 128 + (lane & 7) * 16;
        ldsm4t(km[0], km[1], km[2], km[3], ka);
        ldsm4t(km[4], km[5], km[6], km[7], ka + (hf ? 512 : 1024));
#pragma unroll
        for (int ks = 0; ks < 4; ks++) {
          const uint4 q = lds128(sb + C_Q + (j ^ hf) * 4096 + ks * 1024 + u * 512 + lane * 16);
          const uint4 k0 = lds128((hf ? oth : own) + (2 * ks) * 512);
          mma16(s[0], q.x, q.y, q.z, q.w, km[2 * ks], km[2 * ks + 1]);
          mma16(s[1], q.x, q.y, q.z, q.w, k0.x, k0.y);
          mma16(s[2], q.x, q.y, q.z, q.w, k0.z, k0.w);
          if (u) {
            const uint4 k1 = lds128((hf ? oth : own) + (2 * ks + 1) * 512);
            mma16(s[3], q.x, q.y, q.z, q.w, k1.x, k1.y);
            mma16(s[4], q.x, q.y, q.z, q.w, k1.z, k1.w);
          }
        }
      }
      const int row = 16 * u + g;
      float m0 = -INFINITY, m1 = -INFINITY;
#pragma unroll
      for (int i = 0; i < 5; i++) {
        s[i][0] *= sc; s[i][1] *= sc; s[i][2] *= sc; s[i][3] *= sc;
        if (i > 0) {
          const int key = 8 * (i - 1) + 2 * tq;
          const float neg = -1e9f * 1.4426950408889634f;
          if (key > row) s[i][0] = neg;
          if (key + 1 > row) s[i][1] = neg;
          if (key > row + 8) s[i][2] = neg;
          if (key + 1 > row + 8) s[i][3] = neg;
        }
        m0 = fmaxf(m0, fmaxf(s[i][0], s[i][1])); m1 = fmaxf(m1, fmaxf(s[i][2], s[i][3]));
      }
      m0 = fmaxf(m0, __shfl_xor_sync(~0u, m0, 1)); m1 = fmaxf(m1, __shfl_xor_sync(~0u, m1, 1));
      m0 = fmaxf(m0, __shfl_xor_sync(~0u, m0, 2)); m1 = fmaxf(m1, __shfl_xor_sync(~0u, m1, 2));
      float s0 = 0.f, s1 = 0.f;
#pragma unroll
      for (int i = 0; i < 5; i++) {
        s[i][0] = ex2(s[i][0] - m0); s[i][1] = ex2(s[i][1] - m0); s[i][2] = ex2(s[i][2] - m1); s[i][3] = ex2(s[i][3] - m1);
        s0 += s[i][0] + s[i][1]; s1 += s[i][2] + s[i][3];
      }
      s0 += __shfl_xor_sync(~0u, s0, 1); s1 += __shfl_xor_sync(~0u, s1, 1);
      s0 += __shfl_xor_sync(~0u, s0, 2); s1 += __shfl_xor_sync(~0u, s1, 2);
      const float i0 = rcp(s0), i1 = rcp(s1);
      uint32_t p[5][2];
#pragma unroll
      for (int i = 0; i < 5; i++) { p[i][0] = pack2(s[i][0] * i0, s[i][1] * i0); p[i][1] = pack2(s[i][2] * i1, s[i][3] * i1); }
      bar_sync(B_R, n + 1 < STEPS ? 288 : 128);
      float o[8][4];
      const uint32_t vb = v ? oth + 4096 : own + 8192, vmb = sb + (v ? C_VM2 : C_VM + j * 1024) + lane * 8;
#pragma unroll
      for (int ww = 0; ww < 4; ww++) {
        const uint4 v0 = lds128(vb + (2 * ww) * 512), v1 = lds128(vb + (2 * ww + 1) * 512);
        const uint2 vm = lds64(vmb + ww * 256);
        float* oa = o[2 * ww]; float* ob = o[2 * ww + 1];
        oa[0] = oa[1] = oa[2] = oa[3] = 0.f; ob[0] = ob[1] = ob[2] = ob[3] = 0.f;
        mma8(oa, p[0][0], p[0][1], vm.x);
        mma8(ob, p[0][0], p[0][1], vm.y);
        mma16(oa, p[1][0], p[1][1], p[2][0], p[2][1], v0.x, v0.z);
        mma16(ob, p[1][0], p[1][1], p[2][0], p[2][1], v0.y, v0.w);
        mma16(oa, p[3][0], p[3][1], p[4][0], p[4][1], v1.x, v1.z);
        mma16(ob, p[3][0], p[3][1], p[4][0], p[4][1], v1.y, v1.w);
      }
#pragma unroll
      for (int hh = 0; hh < 2; hh++)
#pragma unroll
        for (int q = 0; q < 2; q++)
          sts128(sb + C_Q + v * 4096 + (row + hh * 8) * 128 + (((4 * q + tq) ^ g) << 4),
                 make_uint4(pack2(o[4*q][2*hh], o[4*q][2*hh+1]), pack2(o[4*q+1][2*hh], o[4*q+1][2*hh+1]),
                            pack2(o[4*q+2][2*hh], o[4*q+2][2*hh+1]), pack2(o[4*q+3][2*hh], o[4*q+3][2*hh+1])));
      fence_async_smem();
    }
    PROF(11);
  }
  bar_arrive(B_G, 160);
  TS(6);
}

__device__ __forceinline__ void swap_q(const Params& P, uint32_t sb, int n) {
  const uint32_t c = blockIdx.x, t0 = clk();
  if (n > 0) {
    mbar_arrive(sb + CB_EMPTY + ((n - 1) & 1) * 8);
    unsigned char* dst = g_oimg + (uint32_t)((((n - 1) % RING) * N_CHAIN + (c & ~1u)) * 8192 + (c & 1) * 4096);
    asm volatile("cp.async.bulk.global.shared::cta.bulk_group [%0], [%1], 4096;" :: "l"(dst + (c & 1) * 8192), "r"(sb + C_Q) : "memory");
    asm volatile("cp.async.bulk.global.shared::cta.bulk_group [%0], [%1], 4096;" :: "l"(dst + ((c & 1) ^ 1) * 8192), "r"(sb + C_Q + 4096) : "memory");
    asm volatile("cp.async.bulk.commit_group;" ::: "memory");
    { const int n_ = n - 1; { const int n = n_; T3(4); (void)n; } }
    bulk_done_inc(g_fl + FL_O + c);
    { const int n_ = n - 1; { const int n = n_; T3(5); (void)n; } }
  }
  if (n < STEPS) {
    const uint32_t* fg = g_fl + FL_G + lds32(sb + C_SEL + MRING * 4);
    int it = 0;
    while (min(ld_acquire(fg + (64 + (c >> 1)) * 8), ld_acquire(fg + (32 + (c >> 1)) * 8)) <= (uint32_t)n) spin_guard(it);
    fence_async_global();
    if (n + 1 < STEPS) while ((int)(clk() - t0 - DLYQ) < 0) __nanosleep(20);
    const unsigned char* blk = g_qkv + (uint32_t)((n % RING) * (N_CHAIN * 24576));
    mbar_expect(sb + CB_Q, 16384);
    bulk_load(sb + C_Q, blk + (c * 24576 + 16384), 8192, sb + CB_Q);
    bulk_load(sb + C_KV2, blk + ((c ^ 1) * 24576 + (c & 1) * 4096), 4096, sb + CB_Q);
    bulk_load(sb + C_KV2 + 4096, blk + ((c ^ 1) * 24576 + 8192 + (c & 1) * 4096), 4096, sb + CB_Q);
  }
}

template <int W>
__device__ __forceinline__ void aux_loop(const Params& P, uint32_t sb, const uint4* src, uint32_t* dst) {
#pragma unroll 1
  for (int n = 0; n < STEPS; n++) {
    if (W == 1) {
      bar_sync(B_G, 288 + OBSW);
      if ((opaque_tid() & 31) == 0) swap_q(P, sb, n);
      __syncwarp();
    }
    dst += (n + 1) % MRING ? 10240 : -(MRING - 1) * 10240;
    if (n + 1 < STEPS) {
      bar_sync(B_OE, 480);
      const uint32_t lane = opaque_tid() & 31;
      const uint32_t t0 = clk();
      if (W == 3) { st_relaxed_if(g_fl + FL_TICK + lane * 1024, n + 1, blockIdx.x == 0 && lane < 2); TR(0); }
      wait_until(t0, DLY1);
      float2 r = gather_reduce<true>(src, (n & 1) ^ 1, lane);
      if (W == 3) {
        r.x += __shfl_xor_sync(~0u, r.x, 2);
        r.y += __shfl_xor_sync(~0u, r.y, 2);
      }
      st_relaxed_if(dst, pack2(r.x, r.y), n >= LAG || !(lane & 4));
      bar_arrive(B_R, 288);
      TR(W);
    }
  }
  if (W == 1) {
    bar_sync(B_G, 160);
    if ((opaque_tid() & 31) == 0) swap_q(P, sb, STEPS);
  }
}

__device__ __forceinline__ void chain_aux(const Params& P, uint32_t sb) {
  const uint32_t c = blockIdx.x, lane = threadIdx.x & 31, w = (threadIdx.x >> 5) & 3;
  if (w == 0) {
    bar_sync(B_R, 64);
    if (lane == 0) {
      const uint32_t* fkv = g_fl + FL_G + near_half(XB_F, c) * 1024 + (c >> 1) * 8;
#pragma unroll 1
      for (int n = 0; n < STEPS; n++) {
        mbar_wait_guard(sb + CB_EMPTY + (n & 1) * 8, ((n >> 1) & 1) ^ 1);
        const uint32_t t0 = clk();
        if (n > 1) while ((int)(clk() - t0 - KMIN) < 0) __nanosleep(20);
#pragma unroll 1
        for (int m = 0; m < 2; m++) {
          wait_flag(fkv + m * 256, n + 1);
          T3(m * 2);
          fence_async_global();
          const uint32_t dt = clk() - t0, go = n < 2 || dt < KWIN ? 0 : dt < DLYK + 450 ? DLYK : KLATE;
          while ((int)(clk() - t0 - go) < 0) __nanosleep(20);
          const uint32_t full = sb + (m ? CB_VF : CB_FULL) + (n & 1) * 8;
          mbar_expect(full, 8192);
          bulk_load(sb + C_KV + (n & 1) * 16384 + m * 8192, g_qkv + (uint32_t)(((n % RING) * N_CHAIN + c) * 24576 + m * 8192), 8192, full);
          T3(m * 2 + 1);
        }
      }
    }
  } else {
    const uint32_t sel = near_half(c * 3, c) | (near_half(c * 3 + 2, c) << 2);
    const uint4* src = g_inbox + (c * 1536 + lane + (w < 3 ? (sel & 1) * 256 + (w - 1) * 128 : 1024 + (sel & 4) * 64));
    uint32_t* dst = g_mimg + ((c >> 1) * 16 + (lane >> 4) * 1024 +
                              ((w < 3 ? (w - 1) * 2048 + (c & 1) * 512 + (lane & 15) : 4 * 2048 + (lane & 12) + (c & 1) * 2 + (lane & 1)) ^ (c & 4)));
    __syncwarp();
    if (w == 1) aux_loop<1>(P, sb, src, dst);
    else if (w == 2) aux_loop<2>(P, sb, src, dst);
    else aux_loop<3>(P, sb, src, dst);
  }
}

template <int WG>
__device__ __forceinline__ void g_math(const Params& P, uint32_t sb) {
  const int q = g_unit(WG);
  const int lane = threadIdx.x & 31, w = (threadIdx.x >> 5) & 3;
  const bool isq = q >= 64, isv = (q >> 5) == 1;
  uint32_t a[136];
  {
    const uint32_t stage = sb + G_W + WG * 73728;
    load_frags<34>(a, stage);
    bar_sync(B_WG0 + WG, 128);
    load_wg(P, sb, false, WG);
    cp_async_wait_all();
    fence_async_smem();
    bar_sync(B_WG0 + WG, 128);
  }
  TS(4);
  const uint32_t off0 = (q & 31) * 49152 + (q >> 5) * 8192 + w * 1024 + lane * 16;
  const uint32_t half = isq ? 4096 : 24576, slot = 28672 - half;
#pragma unroll 1
  for (int n = 0; n < STEPS; n++) {
    float d0[32], d1[32];
    PROF0();
    if (n > 0) bar_sync(B_V + WG, 256);
#pragma unroll
    for (int ch = 0; ch < 9; ch++) {
      mbar_wait(sb + G_BAR + ch * 8, n & 1);
      if (ch == 0) { PROF(1); }
      if (ch == 8 && (WG == 0 ? n > 0 : n + 1 < STEPS)) bar_arrive(B_V + (WG ^ 1), 256);
      wg_fence();
#pragma unroll
      for (int kk = 0; kk < 4; kk++) {
        const int ks = ch * 4 + kk;
        const uint64_t db = desc_sw128(G_RING + ch * 8192 + kk * 32);
        const uint64_t da = desc_sw128(G_W + WG * 73728 + ks * 2048);
        if (ks == 0) { wg_rs64<0>(d0, a, db); wg_ss64<0>(d1, da, db); }
        else if (ks < 34) { wg_rs64<1>(d0, a + ks * 4, db); wg_ss64<1>(d1, da, db); }
        else { wg_ss64<1>(d0, desc_sw128(G_W2 + WG * 4096 + (ks - 34) * 2048), db); wg_ss64<1>(d1, da, db); }
      }
      wg_commit();
      if (ch > 0) { wg_wait<1>(); if (lane == 0) mbar_arrive(sb + G_BAR + 128 + (ch - 1) * 8); }
    }
    wg_wait<0>();
    if (lane == 0) mbar_arrive(sb + G_BAR + 128 + 8 * 8);
    PROF(2);
    unsigned char* base = g_qkv + (size_t)(n & (RING - 1)) * (N_CHAIN * 24576);
#pragma unroll
    for (int i = 0; i < 8; i++) {
      const float* d = (i < 4 ? d0 : d1) + 8 * (i & 3);
      uint4 v = make_uint4(pack2(d[0], d[1]), pack2(d[2], d[3]), pack2(d[4], d[5]), pack2(d[6], d[7]));
      if (!isv) v = make_uint4(movmat(v.x), movmat(isq ? v.z : v.y), movmat(isq ? v.y : v.z), movmat(v.w));
      *(uint4*)(base + (off0 + (i >> 2) * half + ((i >> 1) & 1) * slot) + (i & 1) * 512) = v;
    }
    bar_arrive(B_M + WG, 160);
    PROF(3);
  }
}

__device__ __forceinline__ void fill16(void* p, uint32_t v) {
  asm volatile("st.global.v4.u32 [%0], {%1,%1,%1,%1};" :: "l"(p), "r"(v) : "memory");
}
__device__ __forceinline__ void g_load(const Params& P, uint32_t sb) {
  const int lane = threadIdx.x & 31, w = (threadIdx.x >> 5) & 3;
  if (w == 3) return;
  uint32_t fl = 0;
#pragma unroll 1
  for (int n = 0; n < STEPS; n++) {
    if (w == 0) {
      if (n == 0) wait_flag(g_lnflag + (lane & 1) * 8, 1);
      if ((n & 7) == 1 && n < 32) wait_flag(g_lnflag + ((n >> 3) * 32 + lane) * 8, 1);
      if (n == 1) fl = near_half(XB_F, blockIdx.x) * 1024;
      if (n >= LOCK0) {
        wait_flags(g_fl + fl + FL_TICK, n - LAG + 4);
        const uint32_t t0 = clk();
        if (n >= LAG) wait_flags(g_fl + fl + FL_F + (lane & 1) * 8, n - LAG + 1);
        wait_until(t0, DLYG);
      }
    }
    __syncwarp();
    bar_sync(B_X, 96);
    if (lane == 0) {
      if (w == 0) T3(4);
      fence_async_global();
      const uint32_t oa = min(n, NSEG - 1) * 36864, ob = n >= LAG ? (NSEG + n - LAG) * 36864 : 0;
#pragma unroll 1
      for (int ch = w; ch < 9; ch += 3) {
        const uint32_t full = sb + G_BAR + ch * 8;
        mbar_wait_guard(full + 128, (n & 1) ^ 1);
        mbar_expect(full, 8192);
        bulk_load(sb + G_RING + ch * 8192, g_lnimg + (oa + ch * 4096), 4096, full);
        bulk_load(sb + G_RING + ch * 8192 + 4096, g_lnimg + (ob + ch * 4096), 4096, full);
      }
    }
    __syncwarp();
  }
}

__device__ __forceinline__ void g_aux(uint32_t sb) {
  const int lane = threadIdx.x & 31, w = (threadIdx.x >> 5) & 3;
  if (w == 1 || w == 2) {
    const int q = g_unit(w - 1);
    uint32_t* f = g_fl + FL_G + q * 8;
#pragma unroll 1
    for (int n = 0; n < STEPS; n++) {
      const uint32_t ln = opaque_tid() & 31;
      uint4* z = (uint4*)g_oacc + (uint32_t)(((n + 2) % ARING) * (16 * DM) + q * 96 + ln);
      fill16(z, 0); fill16(z + 32, 0); fill16(z + 64, 0);
      if (n + 3 >= MRING && q < 80) fill16((uint4*)g_mimg + (uint32_t)(((n + 3) % MRING) * 2560 + q * 32 + ln), SENT);
      bar_sync(B_M + (w - 1), 160);
      if (lane == 0) { T3(w * 2 - 2); fence_async_global(); flag_release(f, n + 1); T3(w * 2 - 1); }
      __syncwarp();
    }
  }
}

template <int WG>
__device__ __forceinline__ void o_math(const Params& P, uint32_t sb) {
  const int ksl = (blockIdx.x - N_CHAIN - N_G) / 3;
  const int nc = ksl < 4 ? 11 : 10;
  const int lane = threadIdx.x & 31, w = (threadIdx.x >> 5) & 3, g = lane >> 2, tq = lane & 3;
  uint32_t a[96];
  {
    load_frags<24>(a, sb + WG * 49152);
    bar_sync(B_INIT, 416);
    load_wg(P, sb, false, WG);
    cp_async_wait_all();
    fence_async_smem();
    bar_sync(B_WG0 + WG, 128);
  }
  TS(4);
  const uint32_t st0 = sb + O_ST + tq * 512 + ((w * 16 + g) ^ (tq * 8)) * 4;
#pragma unroll 1
  for (int n = 0; n < STEPS; n++) {
    float d[32];
    PROF0();
    if (WG > 0 || n > 0) bar_sync(B_V + WG, 256);
#pragma unroll
    for (int gr = 0; gr < 5; gr++) {
      mbar_wait(sb + O_BAR + gr * 8, n & 1);
      if (gr == 0) { PROF(1); }
      if (gr == (WG == 0 ? OTURN : 4) && (WG < 2 || n + 1 < STEPS)) bar_arrive(B_V + (WG + 1) % 3, 256);
      wg_fence();
#pragma unroll
      for (int ks = gr * 8; ks < gr * 8 + 8; ks++) {
        const uint64_t db = desc_sw128(O_RING + (ks >> 2) * 8192 + (ks & 3) * 32);
        if (ks == 0) wg_rs64<0>(d, a, db);
        else if (ks < 24) wg_rs64<1>(d, a + ks * 4, db);
        else wg_ss64<1>(d, desc_sw128(O_W + WG * 40960 + (ks - 24) * 2048), db);
      }
      if (gr == 4 && nc == 11) {
#pragma unroll
        for (int ks = 40; ks < 44; ks++)
          wg_ss64<1>(d, desc_sw128(O_W + WG * 40960 + (ks - 24) * 2048), desc_sw128(O_RING + 10 * 8192 + (ks & 3) * 32));
      }
      wg_commit();
      if (gr > 0) { wg_wait<1>(); if (lane == 0) mbar_arrive(sb + O_BAR + 128 + (gr - 1) * 8); }
    }
    wg_wait<0>();
    if (lane == 0) mbar_arrive(sb + O_BAR + 128 + 4 * 8);
    PROF(2);
#pragma unroll
    for (int sl = 0; sl < 2; sl++) {
      mbar_wait(sb + OB_ST + WG * 16 + sl * 8, (n & 1) ^ (WG == 0));
#pragma unroll
      for (int nb = sl * 4; nb < sl * 4 + 4; nb++) {
        sts32(st0 + nb * 2048, __float_as_uint(d[nb * 4]));
        sts32(st0 + nb * 2048 + 256, __float_as_uint(d[nb * 4 + 1]));
        sts32((st0 ^ 32) + nb * 2048, __float_as_uint(d[nb * 4 + 2]));
        sts32((st0 ^ 32) + nb * 2048 + 256, __float_as_uint(d[nb * 4 + 3]));
      }
      fence_async_smem();
      bar_arrive((sl ? B_G : B_M) + WG, 160);
    }
    PROF(3);
  }
}

__device__ __forceinline__ void o_aux(const Params& P, uint32_t sb) {
  const int i = blockIdx.x - N_CHAIN - N_G, ksl = i / 3;
  const int c0 = ksl * 11 - max(ksl - 4, 0), nc = ksl < 4 ? 11 : 10;
  const int lane = threadIdx.x & 31, w = (threadIdx.x >> 5) & 3;
  if (w == 0) {
    bar_sync(B_INIT, 416);
    const uint32_t* f = g_fl + FL_O + near_half(XB_F + 1, blockIdx.x) * 1024 + min((c0 & ~1) + lane, (c0 + nc - 1) | 1);
#pragma unroll 1
    for (int n = 0; n < STEPS; n++) {
      wait_flags(f, n + 1);
      if (lane == 0) {
        T3(0);
        fence_async_global();
        const unsigned char* src = g_oimg + (size_t)((n % RING) * N_CHAIN + c0) * 8192;
#pragma unroll 1
        for (int gr = 0; gr < 5; gr++) {
          const uint32_t full = sb + O_BAR + gr * 8, bytes = (gr < 4 ? 2 : nc - 8) * 8192;
          mbar_wait_guard(full + 128, (n & 1) ^ 1);
          mbar_expect(full, bytes);
          bulk_load(sb + O_RING + gr * 16384, src + gr * 16384, bytes, full);
        }
      }
      __syncwarp();
    }
  } else {
#pragma unroll 1
    for (int n = 0; n < STEPS; n++) {
      float* dst = g_oacc + (uint32_t)((n % ARING) * (64 * DM) + ((i % 3) * 3 + (w - 1 + ksl) % 3) * 1024);
      bar_sync(B_M + (w - 1), 160);
      if (lane == 0) {
        T3(w * 2);
        if (n < NSEG) { bulk_reduce(dst, sb + O_ST, 4096); bulk_reduce(dst + 16 * DM, sb + O_ST + 4096, 4096); }
        asm volatile("cp.async.bulk.commit_group;" ::: "memory");
      }
      __syncwarp();
      bar_sync(B_G + (w - 1), 160);
      if (lane == 0) {
        if (n >= LAG) { bulk_reduce(dst + 32 * DM, sb + O_ST + 8192, 4096); bulk_reduce(dst + 48 * DM, sb + O_ST + 12288, 4096); }
        asm volatile("cp.async.bulk.commit_group;\ncp.async.bulk.wait_group.read 1;" ::: "memory");
        mbar_arrive(sb + OB_ST + (w % 3) * 16);
        asm volatile("cp.async.bulk.wait_group.read 0;" ::: "memory");
        mbar_arrive(sb + OB_ST + (w % 3) * 16 + 8);
        T3(8 + w);
        bulk_done_inc(g_fl + FL_OCNT + (n % OCRING) * 8);
        T3(w * 2 + 1);
      }
      __syncwarp();
    }
  }
}

__device__ __forceinline__ void f_role(const Params& P, uint32_t sb) {
  const int lane = threadIdx.x & 31, r0 = (blockIdx.x - N_CHAIN - N_G - N_O) * 16, r = r0 + (threadIdx.x >> 5);
  const uint32_t row = sb + (threadIdx.x >> 5) * 1152 + lane * 4;
  const uint32_t* fo = g_fl + FL_OCNT + near_half(XB_F, blockIdx.x) * 1024;
  if (threadIdx.x < 128) wait_flag(g_lnflag + threadIdx.x * 8, 2);
  __syncthreads();
  if (threadIdx.x == 0) {
    fence_async_global();
    mbar_expect(sb + F_BAR, 36864);
    bulk_load(sb + F_XY, g_x1 + (size_t)r0 * DM, 18432, sb + F_BAR);
    bulk_load(sb + F_XY + 18432, g_y + (size_t)r0 * DM, 18432, sb + F_BAR);
  }
#pragma unroll 1
  for (int n = 0; n < STEPS; n++) {
    uint32_t x[9], y[9];
    if (n < NSEG) {
      mbar_wait(sb + F_BAR, n & 1);
#pragma unroll
      for (int i = 0; i < 9; i++) { x[i] = lds32(row + F_XY + i * 128); y[i] = lds32(row + F_XY + 18432 + i * 128); }
    }
    PROF0();
    if (threadIdx.x == 0) { T3(1); wait_flag(fo + (n % OCRING) * 8, N_O * 3 * (n / OCRING + 1)); T3(0); }
    __syncthreads();
    PROF(1);
    const float* acc = g_oacc + (uint32_t)((n % ARING) * (64 * DM) + r0 * DM);
    const uint32_t col = (threadIdx.x >> 5) * 32 + (lane ^ ((r & 6) * 2));
    float2 a[9];
    if (n < NSEG) {
#pragma unroll
      for (int i = 0; i < 9; i++) a[i] = __ldcg((const float2*)acc + i * 512 + col);
    }
    if (threadIdx.x == 0) {
      fence_async_global();
      if (n >= LAG) {
        mbar_expect(sb + F_BAR + 8, 36864);
        bulk_load(sb + F_A, acc + 32 * DM, 36864, sb + F_BAR + 8);
      }
      if (n + 1 < NSEG) {
        mbar_expect(sb + F_BAR, 36864);
        bulk_load(sb + F_XY, g_x1 + (size_t)((n + 1) * 32 + r0) * DM, 18432, sb + F_BAR);
        bulk_load(sb + F_XY + 18432, g_y + (size_t)((n + 1) * 32 + r0) * DM, 18432, sb + F_BAR);
      }
    }
    __syncwarp();
    if (n < NSEG) {
      uint32_t l[9];
#pragma unroll
      for (int i = 0; i < 9; i++) x[i] = badd2(x[i], pack2(a[i].x, a[i].y));
      layernorm9(x, l);
#pragma unroll
      for (int i = 0; i < 9; i++) x[i] = badd2(x[i], bmul2(l[i], y[i]));
      layernorm9(x, l);
      store_ln_row(1, n * 32 + r, l);
      PROF(3);
      if (threadIdx.x < 480) bar_arrive(1, 512);
      else { bar_sync(1, 512); if (lane == 0) { T3(2); flag_release(g_fl + FL_F + (blockIdx.x & 1) * 8, n + 1); T3(3); } __syncwarp(); }
#pragma unroll
      for (int i = 0; i < 9; i++) sts32(row + (n % RING) * 18432 + i * 128, x[i]);
    }
    if (n >= LAG) {
      const uint32_t slot = ((n - LAG) % RING) * 18432;
      mbar_wait(sb + F_BAR + 8, (n - LAG) & 1);
#pragma unroll
      for (int i = 0; i < 9; i++) {
        const uint2 v = lds64(sb + F_A + i * 4096 + col * 8);
        sts32(row + slot + i * 128, badd2(lds32(row + slot + i * 128), pack2(__uint_as_float(v.x), __uint_as_float(v.y))));
      }
      fence_async_smem();
      if (threadIdx.x < 480) bar_arrive(2, 512);
      else {
        bar_sync(2, 512);
        if (lane == 0) {
          asm volatile("cp.async.bulk.global.shared::cta.bulk_group [%0], [%1], 18432;" :: "l"(P.out + (size_t)((n - LAG) * 32 + r0) * DM), "r"(sb + slot) : "memory");
          asm volatile("cp.async.bulk.commit_group;\ncp.async.bulk.wait_group.read 1;" ::: "memory");
        }
        __syncwarp();
      }
    }
  }
  if (threadIdx.x == 480) asm volatile("cp.async.bulk.wait_group 0;" ::: "memory");
}

constexpr uint32_t P_CH = 147456, P_CHSZ = 12800, P_H = 4352, P_Y = P_CH;
static_assert(P_CH + 5 * P_CHSZ + 8192 <= SMEM_BYTES, "prologue smem");

template <int N>
__device__ __forceinline__ void conv_fold(float (*acc)[4], bool hi, uint32_t mine, uint32_t theirs, int bar, int cnt) {
#pragma unroll
  for (int i = 0; i < N / 2; i++) {
    uint4 v;
    v.x = __float_as_uint(hi ? acc[i][0] : acc[i + N / 2][0]); v.y = __float_as_uint(hi ? acc[i][1] : acc[i + N / 2][1]);
    v.z = __float_as_uint(hi ? acc[i][2] : acc[i + N / 2][2]); v.w = __float_as_uint(hi ? acc[i][3] : acc[i + N / 2][3]);
    sts128(mine + i * 512, v);
  }
  bar_sync(bar, cnt);
#pragma unroll
  for (int i = 0; i < N / 2; i++) {
    const uint4 v = lds128(theirs + i * 512);
    acc[i][0] = (hi ? acc[i + N / 2][0] : acc[i][0]) + __uint_as_float(v.x); acc[i][1] = (hi ? acc[i + N / 2][1] : acc[i][1]) + __uint_as_float(v.y);
    acc[i][2] = (hi ? acc[i + N / 2][2] : acc[i][2]) + __uint_as_float(v.z); acc[i][3] = (hi ? acc[i + N / 2][3] : acc[i][3]) + __uint_as_float(v.w);
  }
}
template <int N>
__device__ __forceinline__ void conv_store(const float (*acc)[4], int tile0, uint32_t su, int d, uint32_t dd) {
  const int lane = threadIdx.x & 31, g = lane >> 2, tq = lane & 3;
#pragma unroll
  for (int i = 0; i < N; i++) {
    const uint32_t ad = su + (8 + (tile0 + i) * 8 + g) * 32 + tq * 4, sw = (g & 4) << 2;
    const uint32_t lo = badd2(movmat(pack2(acc[i][0], acc[i][1])), bmul2(lds32(ad + sw), dd));
    const uint32_t hi = badd2(movmat(pack2(acc[i][2], acc[i][3])), bmul2(lds32(ad + (sw ^ 16)), dd));
    ((uint2*)(g_yT + (size_t)d * SEQ))[(tile0 + i) * 32 + lane] = make_uint2(lo, hi);
  }
}

__device__ __forceinline__ void store_xy(uint32_t stage, int tile) {
  asm volatile("cp.async.bulk.global.shared::cta.bulk_group [%0], [%1], 18432;" :: "l"(g_y + (size_t)tile * 16 * DM), "r"(stage) : "memory");
  asm volatile("cp.async.bulk.global.shared::cta.bulk_group [%0], [%1], 18432;" :: "l"(g_x1 + (size_t)tile * 16 * DM), "r"(stage + 18432) : "memory");
  asm volatile("cp.async.bulk.commit_group;" ::: "memory");
}

__device__ __forceinline__ void prologue(const Params& P, uint32_t sb) {
  const int b = blockIdx.x, tid = threadIdx.x, lane = tid & 31, warp = tid >> 5, t0 = b * 16;
  const int chb = b, nch = chb < DM - 4 * N_CTA ? 5 : 4;
  if (tid < 288) {
    if (b < 128) {
      const int c = (tid >> 1) * 4, tt = t0 + (tid & 1) * 8;
      uint2 kr[11], vr[8];
#pragma unroll
      for (int i = 0; i < 11; i++) { const int t = tt + i - 3; kr[i] = t >= 0 ? __ldg((const uint2*)(P.K + (size_t)t * DM + c)) : make_uint2(0, 0); }
#pragma unroll
      for (int i = 0; i < 8; i++) vr[i] = __ldg((const uint2*)(P.V + (size_t)(tt + i) * DM + c));
#pragma unroll
      for (int e = 0; e < 2; e++) {
        const uint4 sh = __ldg((const uint4*)(P.shift + c * 4) + e);
        const uint32_t s0 = __byte_perm(sh.x, sh.z, 0x5410), s1 = __byte_perm(sh.x, sh.z, 0x7632);
        const uint32_t s2 = __byte_perm(sh.y, sh.w, 0x5410), s3 = __byte_perm(sh.y, sh.w, 0x7632);
        uint32_t v[8];
#pragma unroll
        for (int i = 0; i < 8; i++) {
          const uint32_t k3 = e ? kr[i].y : kr[i].x, k2 = e ? kr[i + 1].y : kr[i + 1].x, k1 = e ? kr[i + 2].y : kr[i + 2].x, k0 = e ? kr[i + 3].y : kr[i + 3].x;
          v[i] = bmul2(badd2(badd2(badd2(bmul2(k3, s3), bmul2(k2, s2)), bmul2(k1, s1)), bmul2(k0, s0)), e ? vr[i].y : vr[i].x);
        }
        *(uint4*)(g_kvT + (size_t)(c + 2 * e) * SEQ + tt) =
          make_uint4(__byte_perm(v[0], v[1], 0x5410), __byte_perm(v[2], v[3], 0x5410), __byte_perm(v[4], v[5], 0x5410), __byte_perm(v[6], v[7], 0x5410));
        *(uint4*)(g_kvT + (size_t)(c + 2 * e + 1) * SEQ + tt) =
          make_uint4(__byte_perm(v[0], v[1], 0x7632), __byte_perm(v[2], v[3], 0x7632), __byte_perm(v[4], v[5], 0x7632), __byte_perm(v[6], v[7], 0x7632));
      }
    }
  } else if (tid < 384) {
    const int t = tid - 288;
    for (int i = t; i < 32 * nch; i += 96) asm volatile("prefetch.global.L2 [%0];" :: "l"(P.Hk + (size_t)(chb + (i >> 5) * N_CTA) * SEQ + (i & 31) * 64));
    for (int i = b * 96 + t; i < 32 * DM; i += N_CTA * 96) ((uint4*)g_oacc)[i] = make_uint4(0, 0, 0, 0);
    if (b * 96 + t < 128 * 8) g_lnflag[b * 96 + t] = 0;
    if (t == 95) sts32(sb + S_GEN, ld_acquire(g_gbar));
  }
  if (warp < 12) {
    bar_sync(6, 384);
    if (tid == 128) TS(14);
    if (tid == 0) grid_arrive(0);
    if (tid == 0) TS(1);
  }
  if (warp < 12) {
    const bool quad = warp >= 8;
    const int ch = quad ? 4 : warp >> 1, sub = quad ? warp - 8 : warp & 1, nthr = quad ? 128 : 64, d = chb + ch * N_CTA;
    const uint32_t su = sb + P_CH + ch * P_CHSZ;
    if (ch < nch) {
      const uint32_t* hs = (const uint32_t*)(P.Hk + (size_t)d * SEQ);
#pragma unroll 4
      for (int q = sub * 32 + lane; q < 256; q += nthr) {
        const uint4 c = __ldg((const uint4*)hs + q);
        const uint32_t prev = q ? __ldg(hs + 4 * q - 1) : 0u;
        sts128(su + P_H + 32 + q * 16, make_uint4(__byte_perm(c.x, prev, 0x7610), __byte_perm(c.y, c.x, 0x7610), __byte_perm(c.z, c.y, 0x7610), __byte_perm(c.w, c.z, 0x7610)));
        sts128(su + P_H + 4224 + q * 16, make_uint4(__byte_perm(c.x, 0, 0x1032), __byte_perm(c.y, 0, 0x1032), __byte_perm(c.z, 0, 0x1032), __byte_perm(c.w, 0, 0x1032)));
      }
      if (sub == 1 && lane == 0) sts32(su + P_CHSZ - 16, __bfloat16_as_ushort(P.Dk[d]) * 0x10001u);
      if (sub == 0 && lane < 20) sts128(su + (lane < 16 ? lane * 16 : P_H + (lane & 2) * 2096 + (lane & 1) * 16), make_uint4(0, 0, 0, 0));
    }
    if (tid == 0) grid_wait(0, lds32(sb + S_GEN));
    bar_sync(6, 384);
    if (ch < nch) {
#pragma unroll 4
      for (int q = sub * 32 + lane; q < 256; q += nthr) {
        const int row = (q >> 1) + 8;
        sts128(su + row * 32 + (((q & 1) ^ ((row >> 2) & 1)) << 4), __ldcg((const uint4*)(g_kvT + (size_t)d * SEQ) + q));
      }
    }
    bar_arrive(8, 416);
    if (ch < nch) {
      bar_sync(1 + ch, nthr);
      if (tid == 0) TS(11);
      const int g = lane >> 2, tq = lane & 3;
      const uint32_t sh = su + P_H + (g & 1) * 4192 + (8 + (g >> 1) - tq) * 4;
      float acc[16][4];
#pragma unroll
      for (int i = 0; i < 16; i++) { acc[i][0] = acc[i][1] = acc[i][2] = acc[i][3] = 0.f; }
      const int nres = quad ? 2 : 4;
#pragma unroll 1
      for (int res = sub * nres; res < sub * nres + nres; res++) {
        uint32_t bf[16][2];
        const int row = 8 - res + ((lane >> 4) << 3) + (lane & 7);
        const uint32_t ad = su + row * 32 + ((((lane >> 3) & 1) ^ ((row >> 2) & 1)) << 4);
#pragma unroll
        for (int f = 0; f < 16; f += 2) ldsm4(bf[f][0], bf[f][1], bf[f + 1][0], bf[f + 1][1], ad + f * 256);
#pragma unroll
        for (int jj = 0; jj < 16; jj++) {
          const uint32_t ah = sh + (8 * jj + res) * 32;
          const uint32_t r0 = lds32(ah), r1 = lds32(ah + 16), rm = lds32(ah - 16);
#pragma unroll
          for (int i = jj; i < 16; i++) mma16(acc[i], r0, r1, rm, r0, bf[i - jj][0], bf[i - jj][1]);
        }
      }
      bar_sync(1 + ch, nthr);
      if (tid == 0) TS(12);
      const uint32_t xb = su + P_H + lane * 16, dd = lds32(su + P_CHSZ - 16);
      if (quad) bar_sync(1 + ch, nthr);
      conv_fold<16>(acc, sub & 1, xb + sub * 4096, xb + (sub ^ 1) * 4096, 1 + ch, nthr);
      if (quad) {
        bar_sync(1 + ch, nthr);
        conv_fold<8>(acc, sub & 2, xb + sub * 4096, xb + (sub ^ 2) * 4096, 1 + ch, nthr);
        conv_store<4>(acc, (sub & 1) * 8 + (sub & 2) * 2, su, d, dd);
      } else {
        conv_store<8>(acc, sub * 8, su, d, dd);
      }
    }
    bar_sync(9, 512);
    if (tid == 0) grid_arrive(1);
  } else {
    for (int blk = b; blk < XB_REF; blk += N_CTA) {
      const int n = (blk - XB_M) / 5, r = (blk - XB_M) % 5;
      const uint32_t fill = blk < XB_M ? 0u : SENT;
#pragma unroll
      for (int k = 0; k < 2; k++) {
        const int q = (tid & 127) + k * 128;
        uint4 v = make_uint4(fill, fill, fill, fill);
        if (blk >= XB_M && (n == 0 || (n <= LAG && ((q ^ (q >> 3)) & 1))) && (r < 4 || k == 0)) {
          const bf16* m = P.mem0 + (k * 20 + r * 4 + ((q >> 5) & 3)) * 16 + ((q >> 1) & 1) * 8 + ((q >> 2) & 7);
          v.x = pack2(__bfloat162float(m[0]), __bfloat162float(m[DM])); v.y = pack2(__bfloat162float(m[2 * DM]), __bfloat162float(m[3 * DM]));
          v.z = pack2(__bfloat162float(m[4 * DM]), __bfloat162float(m[5 * DM])); v.w = pack2(__bfloat162float(m[6 * DM]), __bfloat162float(m[7 * DM]));
        }
        g_xb[blk * 512 + q] = v;
        g_xb[blk * 512 + 256 + q] = v;
      }
    }
    if (tid < 388) g_xb[XB_REF * 512 + (tid & 2) * 128 + (b & ~1) + (tid & 1)] = make_uint4(0, 0, 0, 0);
    bar_sync(7, 128);
    TS(8);
    if (warp == 12) {
      bar_sync(8, 416);
      if (lane == 16 && b < 128) asm volatile("cp.async.bulk.prefetch.L2.global [%0], 18432;" :: "l"(P.X + (size_t)t0 * DM) : "memory");
      if (lane < 16 && b < 128) {
        const bf16* w = (lane & 12) == 0 ? P.Wk : (lane & 12) == 4 ? P.Wq : (lane & 12) == 8 ? P.Wv : P.Wo;
        asm volatile("cp.async.bulk.prefetch.L2.global [%0], 9216;" :: "l"(w + (size_t)(b * 4 + (lane & 3)) * 4608) : "memory");
      }
      wait_until(clk(), b >= N_CHAIN && b < N_CHAIN + N_G ? S1G : S1DLY);
    } else if (lane == 0) {
      const int blk = warp == 13 ? XB_REF : b + (warp - 14) * N_CTA;
      if (warp == 13 || blk < XB_REF) {
        uint32_t* p = (uint32_t*)(g_xb + blk * 512 + (warp == 13 ? b : 0));
        int votes = 0;
        for (int rep = 0; rep < 24 && abs(votes) < 7; rep++) {
          uint32_t v0, v1, c0, c1;
          asm volatile("atom.relaxed.gpu.global.add.u32 %0, [%4], 0;\n atom.relaxed.gpu.global.add.u32 %1, [%5], 0;\n"
                       "{.reg .pred p; setp.eq.u32 p, %0, 0x7ffffff3; @p trap; mov.u32 %2, %%clock; setp.eq.u32 p, %1, 0x7ffffff3; @p trap; mov.u32 %3, %%clock;}"
                       : "=&r"(v0), "=&r"(v1), "=&r"(c0), "=&r"(c1) : "l"(p + (rep & 1) * 1024), "l"(p + ((rep & 1) ^ 1) * 1024) : "memory");
          votes += ((c1 - c0 > 80u) == (rep & 1)) ? 1 : -1;
        }
        if (warp == 13) g_side[b] = votes > 0; else g_near[blk] = votes > 0;
      }
    }
    __syncwarp();
    bar_sync(7, 128);
    bar_arrive(9, 512);
    TS(9);
    const int nwg = b < N_CHAIN + N_G ? 2 : b < N_CTA - N_F ? 3 : 0;
    for (int k = 0; k < nwg; k++) load_wg(P, sb, true, k);
    TS(10);
  }
  if (tid == 0) TS(2);
  if (b < N_CHAIN || b >= N_CHAIN + N_G) {
    const bool isf = b >= N_CTA - N_F;
    const int first = b < N_CHAIN ? b + 2 : isf ? b - (N_CTA - N_F) : b - N_G + 2, last = isf ? 128 : 120;
    auto next = [&](int tile) { return b < N_CHAIN ? 128 : !isf ? tile + N_O : tile < 2 ? tile + 120 : tile + 2; };
    uint32_t st = sb + P_Y;
#pragma unroll 1
    for (int tile = first; tile < last; tile = next(tile), st = 2 * (sb + P_Y) + 36864 - st) {
      uint32_t x[9], l[9];
      const int tok = tile * 16 + warp;
#pragma unroll
      for (int i = 0; i < 9; i++) x[i] = __ldg((const uint32_t*)(P.X + (size_t)tok * DM) + i * 32 + lane);
      layernorm9(x, l);
      if (tile == first) { if (tid == 0) grid_wait(1, lds32(sb + S_GEN)); }
      else if (tid == 511) asm volatile("cp.async.bulk.wait_group.read 1;" ::: "memory");
      __syncthreads();
      if (tid == 0) TS(13);
      if (tid < 288) {
        uint4 y[4];
#pragma unroll
        for (int e = 0; e < 4; e++) y[e] = __ldcg((const uint4*)(g_yT + (size_t)((tid >> 1) * 4 + e) * SEQ + tile * 16) + (tid & 1));
#pragma unroll
        for (int i = 0; i < 4; i++) {
          const uint32_t w0 = ((const uint32_t*)&y[0])[i], w1 = ((const uint32_t*)&y[1])[i], w2 = ((const uint32_t*)&y[2])[i], w3 = ((const uint32_t*)&y[3])[i];
          const uint32_t ad = st + ((tid & 1) * 4 + (i >> 1) * 2 + (i & 1) * 8) * 1152 + (tid >> 1) * 8;
          sts64(ad, __byte_perm(w0, w1, 0x5410), __byte_perm(w2, w3, 0x5410));
          sts64(ad + 1152, __byte_perm(w0, w1, 0x7632), __byte_perm(w2, w3, 0x7632));
        }
      }
      __syncthreads();
#pragma unroll
      for (int i = 0; i < 9; i++) {
        x[i] = badd2(x[i], bmul2(l[i], lds32(st + warp * 1152 + i * 128 + lane * 4)));
        sts32(st + 18432 + warp * 1152 + i * 128 + lane * 4, x[i]);
      }
      layernorm9(x, l);
      store_ln_row(0, tok, l);
      fence_async_smem();
      __syncthreads();
      if (b >= N_CHAIN && tid == 511) { if (tile < 2) st_release(g_lnflag + tile * 8, 1); store_xy(st, tile); }
    }
    if (b >= N_CHAIN && tid == 511) {
      asm volatile("cp.async.bulk.wait_group 0;\nfence.acq_rel.gpu;" ::: "memory");
      for (int tile = first; tile < last; tile = next(tile)) st_relaxed_if(g_lnflag + tile * 8, 2, true);
    }
    if (tid == 0) TS(15);
  }
  cp_async_wait_all();
  __syncthreads();
}

__device__ __forceinline__ void publish_prologue(uint32_t sb) {
  if (threadIdx.x < 448) return;
  if (threadIdx.x < 448 + MRING) {
    uint32_t m = 0;
#pragma unroll
    for (int r = 0; r < 5; r++) m |= near_half(XB_M + (threadIdx.x - 448) * 5 + r, blockIdx.x) << r;
    sts32(sb + C_SEL + (threadIdx.x - 448) * 4, m);
  } else if (threadIdx.x == 448 + MRING) {
    sts32(sb + C_SEL + MRING * 4, near_half(XB_F, blockIdx.x) * 1024);
  }
  if (threadIdx.x == 511) {
    st_release(g_lnflag + (blockIdx.x + 2) * 8, 1);
    store_xy(sb + P_Y, blockIdx.x + 2);
    asm volatile("cp.async.bulk.wait_group.read 0;" ::: "memory");
  }
  __syncwarp();
  if (threadIdx.x >= 480) { bar_arrive(B_R, 64); bar_arrive(B_INIT, 320); } else bar_sync(B_INIT, 320);
  if (threadIdx.x == 511) asm volatile("cp.async.bulk.wait_group 0;" ::: "memory");
  if (threadIdx.x == 511) st_release(g_lnflag + (blockIdx.x + 2) * 8, 2);
  __syncwarp();
}

__global__ void __cluster_dims__(2, 1, 1) __launch_bounds__(512, 1) k_main(const Params P) {
  extern __shared__ __align__(1024) unsigned char smem[];
  const uint32_t sb = (uint32_t)__cvta_generic_to_shared(smem);
  const int b = blockIdx.x, wg = threadIdx.x >> 7;
  TS(0);
  prologue(P, sb);
  TS(3);
  if (threadIdx.x == 0) {
    if ((sb & 0xFFFFFF) != SBASE) __trap();
    if (b < N_CHAIN) {
      mbar_init(sb + CB_FULL, 1); mbar_init(sb + CB_FULL + 8, 1);
      mbar_init(sb + CB_EMPTY, 1); mbar_init(sb + CB_EMPTY + 8, 1);
      mbar_init(sb + CB_SX, 1); mbar_init(sb + CB_OX, 1); mbar_init(sb + CB_XX, 1); mbar_init(sb + CB_Q, 1); mbar_init(sb + CB_VF, 1); mbar_init(sb + CB_VF + 8, 1);
      for (int i = 0; i < 5; i++) mbar_init(sb + CB_M + i * 8, 1);
    } else if (b < N_CHAIN + N_G) {
      for (int i = 0; i < 9; i++) { mbar_init(sb + G_BAR + i * 8, 1); mbar_init(sb + G_BAR + 128 + i * 8, 8); }
    } else if (b < N_CHAIN + N_G + N_O) {
      for (int i = 0; i < 5; i++) { mbar_init(sb + O_BAR + i * 8, 1); mbar_init(sb + O_BAR + 128 + i * 8, 12); }
      for (int i = 0; i < 6; i++) mbar_init(sb + OB_ST + i * 8, 1);
    } else {
      mbar_init(sb + F_BAR, 1); mbar_init(sb + F_BAR + 8, 1);
    }
    asm volatile("fence.mbarrier_init.release.cluster;" ::: "memory");
  }
  fence_async_smem();
  __syncthreads();
  cluster_sync();
  if (b < N_CHAIN) {
    if (wg == 0) { reg_inc<192>(); chain_proj<0>(P, sb); PROF_DUMP(); }
    else if (wg == 1) { reg_inc<192>(); chain_proj<1>(P, sb); PROF_DUMP(); }
    else if (wg == 2) { reg_dec<88>(); chain_attn(P, sb); PROF_DUMP(); }
    else { reg_dec<40>(); publish_prologue(sb); chain_aux(P, sb); PROF_DUMP(); }
  } else if (b < N_CHAIN + N_G) {
    if (wg == 0) { reg_inc<232>(); g_math<0>(P, sb); PROF_DUMP(); }
    else if (wg == 1) { reg_inc<232>(); g_math<1>(P, sb); PROF_DUMP(); }
    else if (wg == 2) { reg_dec<24>(); g_aux(sb); }
    else { reg_dec<24>(); g_load(P, sb); }
  } else if (b < N_CHAIN + N_G + N_O) {
    if (wg == 0) { reg_inc<160>(); o_math<0>(P, sb); PROF_DUMP(); }
    else if (wg == 1) { reg_inc<160>(); o_math<1>(P, sb); PROF_DUMP(); }
    else if (wg == 2) { reg_inc<160>(); o_math<2>(P, sb); PROF_DUMP(); }
    else { reg_dec<32>(); o_aux(P, sb); }
  } else {

    f_role(P, sb); TS(7); PROF_DUMP();
  }
}

}

extern "C" void kernel_launch(void* const* d_in, const int* in_sizes, int n_in, void* d_out, int out_size) {
  Params P;
  P.X = (const bf16*)d_in[0]; P.K = (const bf16*)d_in[1]; P.V = (const bf16*)d_in[2];
  P.shift = (const bf16*)d_in[3]; P.Hk = (const bf16*)d_in[4]; P.Dk = (const bf16*)d_in[5];
  P.mem0 = (const bf16*)d_in[7];
  P.Wq = (const bf16*)d_in[8]; P.Wk = (const bf16*)d_in[9]; P.Wv = (const bf16*)d_in[10]; P.Wo = (const bf16*)d_in[11];
  P.out = (bf16*)d_out;
  for (int i = 0; i < 8; i++) P.dly[i] = h_dly[i];
  cudaFuncSetAttribute(k_main, cudaFuncAttributeMaxDynamicSharedMemorySize, SMEM_BYTES);
  k_main<<<N_CTA, 512, SMEM_BYTES>>>(P);
}
```

```cpp
#include <cuda_runtime.h>
#include <cuda_bf16.h>
#include <stdint.h>

namespace {

typedef __nv_bfloat16 bf16;

constexpr int SEQ = 2048, DM = 576, HD = 4096, NSEG = 64;
#define PLACE 1
#define LAGV 7
constexpr int LAG = LAGV, STEPS = NSEG + LAG, RING = 8;
static_assert(LAG < RING, "ring");
constexpr int N_CHAIN = 64, N_G = 48, N_O = 18, N_F = 2;
constexpr uint32_t SBASE = 1024;
constexpr uint32_t SENT = 0xFFFFFFFFu;
constexpr int SPIN_MAX = 1 << 22;

__device__ __forceinline__ uint32_t bid() {
  const uint32_t b = blockIdx.x;
  return b < 6 ? b + 106 : b < 8 ? b + 122 : b < 114 ? b - 8 : b < 130 ? b - 2 : b;
}
__device__ __forceinline__ uint32_t chain_id() { return blockIdx.x - (PLACE ? 8 : 0); }
__device__ __align__(1024) bf16 g_kvT[DM * SEQ];
__device__ __align__(1024) bf16 g_yT[DM * SEQ];
__device__ __align__(1024) bf16 g_y[SEQ * DM];
__device__ __align__(1024) bf16 g_x1[SEQ * DM];
__device__ __align__(1024) unsigned char g_lnimg[2 * NSEG * 9 * 4096];
__device__ __align__(1024) unsigned char g_qkv[RING * N_CHAIN * 24576];
__device__ __align__(1024) unsigned char g_oimg[RING * N_CHAIN * 8192];
constexpr int ARING = 16;
static_assert(ARING >= LAG + 9, "accumulator ring");
__device__ __align__(1024) float g_oacc[ARING * 64 * DM];
constexpr int MRING = LAG + 4, N_GRP = 32 + MRING + 1;
constexpr int XB_M = 256, XB_F = XB_M + MRING * 8, XB_REF = XB_F + 2, N_CTA = N_CHAIN + N_G + N_O + N_F;
__device__ __align__(65536) uint4 g_xb[N_GRP * 4096];
#define g_mimg ((uint32_t*)(g_xb + XB_M * 512))
__device__ uint32_t g_near[N_GRP];
__device__ uint32_t g_side[N_CTA];
__device__ __align__(128) uint32_t g_gbar[2 * 32];
constexpr int FL_G = 0, FL_F = 96 * 8, FL_OCNT = FL_F + 2 * 8, OCRING = 16, FL_TICK = 992, FL_O = 2048, FL_SYNC = FL_O + 128;
static_assert(FL_OCNT + OCRING * 8 <= FL_TICK, "flag block");
#define g_fl ((uint32_t*)(g_xb + XB_F * 512))
__device__ __align__(1024) uint32_t g_lnflag[128 * 8];
#define TS(slot)
constexpr int OBSW = 0;
#define PROF(slot)
#define PROF0()
#define PCNT(slot)
#define PROF_DUMP()

#define NSLEEP 0
#define INFL 8
#define S1DLY 2500
#define S1G 1500
#define OTURN 2
#define FENCE1 1
#define FENCE2 0
#define VMIX 23
#define MOFF 1
#define SORD 1
#define EARLYQ 1
#define LOCK0 3
#define MORD 0
#define FASTG 0
#define WSHFL 0
#define PGAP 40
#define NOBULK 0
#define VE 0
#define OGAP 2
#define KXW 0
#define NOCHAIN 0
#define BFENCE 2
#define ABL 0
#define QPRE 0
#define XGUARD 1
#define ATTR 80
#define MTMA 1
#define SEARLY 1
#define VEARLY 1
#define CNT(slot, tries)
#define T3(slot)
#define CK(i, dep)
#define CKW(i, dep)
#define CKDECL
#define CKOUT(base)
#define TR(slot)
#define TRV(slot, val)
#define TRD(slot, dep)
#define TRSYNC()
#define TRDUMP(n)
#define CLK(t) "{.reg .b64 x; .reg .b32 h; mov.u64 x, %%clock64; mov.b64 {" t ", h}, x;}"
__device__ __forceinline__ uint32_t clk() { uint32_t t; asm volatile(CLK("%0") : "=r"(t) :: "memory"); return t; }
__device__ __forceinline__ void wait_until(uint32_t t0, uint32_t d) {
  asm volatile("{.reg .pred p; .reg .u32 t;\n"
               "W: " CLK("t") " sub.u32 t, t, %0; setp.lt.s32 p, t, 0; @p bra.uni W;}"
               :: "r"(t0 + d) : "memory");
}
__device__ __forceinline__ uint32_t pack2(float lo, float hi) {
  uint32_t r; asm("cvt.rn.bf16x2.f32 %0, %1, %2;" : "=r"(r) : "f"(hi), "f"(lo)); return r;
}
__device__ __forceinline__ float bf_lo(uint32_t v) { return __uint_as_float(v << 16); }
__device__ __forceinline__ float bf_hi(uint32_t v) { return __uint_as_float(v & 0xFFFF0000u); }

__device__ __forceinline__ uint4 ld_relaxed4(const void* p) {
  uint4 v; asm volatile("ld.relaxed.gpu.global.v4.u32 {%0,%1,%2,%3}, [%4];" : "=r"(v.x), "=r"(v.y), "=r"(v.z), "=r"(v.w) : "l"(p) : "memory"); return v;
}
__device__ __forceinline__ void st_b128(void* p, uint32_t a, uint32_t b, uint32_t c, uint32_t d) {
  asm volatile("{.reg .b128 v; mov.b128 v, {%1,%2,%3,%4}; st.relaxed.gpu.global.b128 [%0], v;}" :: "l"(p), "r"(a), "r"(b), "r"(c), "r"(d) : "memory");
}
__device__ __forceinline__ void reload_b128(uint4& v, const void* p, uint32_t again) {
  asm volatile("{.reg .pred p; .reg .b128 v; setp.ne.u32 p, %5, 0; mov.b128 v, {%0,%1,%2,%3};\n"
               "@p ld.relaxed.gpu.global.b128 v, [%4]; mov.b128 {%0,%1,%2,%3}, v;}"
    : "+r"(v.x), "+r"(v.y), "+r"(v.z), "+r"(v.w) : "l"(p), "r"(again) : "memory");
}
__device__ __forceinline__ void reload4(uint4& v, const void* p, uint32_t again) {
  asm volatile("{.reg .pred p; setp.ne.u32 p, %5, 0; @p ld.relaxed.gpu.global.v4.u32 {%0,%1,%2,%3}, [%4];}"
    : "+r"(v.x), "+r"(v.y), "+r"(v.z), "+r"(v.w) : "l"(p), "r"(again) : "memory");
}
__device__ __forceinline__ void st_relaxed4(void* p, uint32_t a, uint32_t b, uint32_t c, uint32_t d) {
  asm volatile("st.relaxed.gpu.global.v4.u32 [%0], {%1,%2,%3,%4};" :: "l"(p), "r"(a), "r"(b), "r"(c), "r"(d) : "memory");
}
__device__ __forceinline__ void st_relaxed_if(void* p, uint32_t a, bool on) {
  asm volatile("{.reg .pred p; setp.ne.u32 p, %2, 0; @p st.relaxed.gpu.global.u32 [%0], %1;}" :: "l"(p), "r"(a), "r"((uint32_t)on) : "memory");
}
__device__ __forceinline__ uint32_t ld_acquire(const uint32_t* p) {
  uint32_t v; asm volatile("ld.acquire.gpu.global.u32 %0, [%1];" : "=r"(v) : "l"(p) : "memory"); return v;
}
__device__ __forceinline__ void st_release(uint32_t* p, uint32_t v) {
  asm volatile("st.release.gpu.global.u32 [%0], %1;" :: "l"(p), "r"(v) : "memory");
}
__device__ __forceinline__ void bulk_reduce(float* dst, uint32_t src, uint32_t bytes) {
  asm volatile("cp.reduce.async.bulk.global.shared::cta.bulk_group.add.f32 [%0], [%1], %2;" :: "l"(dst), "r"(src), "r"(bytes) : "memory");
}
__device__ __forceinline__ void bulk_done_inc(uint32_t* p) {
  asm volatile("cp.async.bulk.wait_group 0;\n"
               "fence.proxy.async.global;\nfence.release.gpu;\n"
               "red.relaxed.gpu.global.add.u32 [%0], 1;\nred.relaxed.gpu.global.add.u32 [%0+4096], 1;" :: "l"(p) : "memory");
}
__device__ __forceinline__ void flag_release(uint32_t* p, uint32_t v) {
  asm volatile("fence.release.gpu;\nst.relaxed.gpu.global.u32 [%0], %1;\nst.relaxed.gpu.global.u32 [%0+4096], %1;" :: "l"(p), "r"(v) : "memory");
}
__device__ __forceinline__ void spin_guard(int& it) {
  asm volatile("{.reg .pred p; add.s32 %0, %0, 1; setp.gt.s32 p, %0, %1; @p trap;}" : "+r"(it) : "n"(SPIN_MAX));
}
__device__ __forceinline__ void wait_flag(const uint32_t* p, uint32_t v) {
  int it = 0;
  while (ld_acquire(p) < v) { if (NSLEEP) __nanosleep(NSLEEP); spin_guard(it); }
}
__device__ __forceinline__ void wait_flags(const uint32_t* p, uint32_t v) {
  int it = 0;
  while (true) {
    uint32_t x; asm volatile("ld.relaxed.gpu.global.u32 %0, [%1];" : "=r"(x) : "l"(p) : "memory");
    if (__all_sync(~0u, x >= v)) break;
    spin_guard(it);
  }
  asm volatile("fence.acquire.gpu;" ::: "memory");
}
__device__ __forceinline__ uint32_t timer_offset() {
  uint32_t g0, g;
  asm volatile("mov.u32 %0, %%globaltimer_lo;" : "=r"(g0) :: "memory");
  do { asm volatile("mov.u32 %0, %%globaltimer_lo;" : "=r"(g) :: "memory"); } while (g == g0);
  return (g >> 5) * 58 - clk();
}
__device__ __forceinline__ void grid_arrive(int i) {
  asm volatile("red.release.gpu.global.add.u32 [%0], %1;" :: "l"(g_gbar + i * 32), "r"(bid() ? 1u : 257u - N_CTA) : "memory");
}
__device__ __forceinline__ void grid_wait(int i, uint32_t gen) {
  int it = 0;
  while (((ld_acquire(g_gbar + i * 32) ^ gen) >> 8) == 0) spin_guard(it);
}
__device__ __forceinline__ bool elect() {
  uint32_t r; asm volatile("{.reg .pred p; elect.sync _|p, -1; selp.u32 %0, 1, 0, p;}" : "=r"(r)); return r;
}
__device__ __forceinline__ void bar_sync(int id, int cnt) { asm volatile("bar.sync %0, %1;" :: "r"(id), "r"(cnt) : "memory"); }
__device__ __forceinline__ void bar_arrive(int id, int cnt) { asm volatile("bar.arrive %0, %1;" :: "r"(id), "r"(cnt) : "memory"); }
template <int id, int cnt> __device__ __forceinline__ void bar_arrive_after(uint32_t a, uint32_t b) {
  asm volatile("{.reg .pred p; setp.ne.u32 p, %2, 0xfff12345; setp.ne.and.u32 p, %3, 0xfff12345, p; @p bar.arrive %0, %1;}" :: "n"(id), "n"(cnt), "r"(a), "r"(b) : "memory");
}
template <int id, int cnt> __device__ __forceinline__ void bar_sync_after(uint32_t a) {
  asm volatile("{.reg .pred p; setp.ne.u32 p, %2, 0xfff12345; @p bar.sync %0, %1;}" :: "n"(id), "n"(cnt), "r"(a) : "memory");
}
__device__ __forceinline__ void fence_async_smem() { asm volatile("fence.proxy.async.shared::cta;" ::: "memory"); }
__device__ __forceinline__ void fence_async_global() { asm volatile("fence.proxy.async.global;" ::: "memory"); }
__device__ __forceinline__ void mbar_init(uint32_t mb, int cnt) { asm volatile("mbarrier.init.shared::cta.b64 [%0], %1;" :: "r"(mb), "r"(cnt) : "memory"); }
__device__ __forceinline__ void mbar_arrive(uint32_t mb) { asm volatile("mbarrier.arrive.shared::cta.b64 _, [%0];" :: "r"(mb) : "memory"); }
__device__ __forceinline__ void mbar_arrive_after(uint32_t mb, uint32_t a, uint32_t lane) {
  asm volatile("{.reg .pred p; setp.ne.u32 p, %1, 0xfff12345; setp.eq.and.u32 p, %2, 0, p; @p mbarrier.arrive.shared::cta.b64 _, [%0];}" :: "r"(mb), "r"(a), "r"(lane) : "memory");
}
__device__ __forceinline__ void mbar_expect(uint32_t mb, uint32_t bytes) {
  asm volatile("mbarrier.arrive.expect_tx.shared::cta.b64 _, [%0], %1;" :: "r"(mb), "r"(bytes) : "memory");
}
__device__ __forceinline__ void mbar_wait_guard(uint32_t mb, uint32_t parity) {
  uint32_t ok; int it = 0;
  while (true) {
    asm volatile("{.reg .pred p; mbarrier.try_wait.parity.shared::cta.b64 p, [%1], %2; selp.u32 %0, 1, 0, p;}" : "=r"(ok) : "r"(mb), "r"(parity) : "memory");
    if (ok) break;
    spin_guard(it);
  }
}
__device__ __forceinline__ void mbar_wait(uint32_t mb, uint32_t parity) {
  asm volatile("{.reg .pred p;\nW: mbarrier.try_wait.parity.shared::cta.b64 p, [%0], %1;\n@!p bra W;}" :: "r"(mb), "r"(parity) : "memory");
}
__device__ __forceinline__ void bulk_load(uint32_t dst, const void* src, uint32_t bytes, uint32_t mb) {
  asm volatile("cp.async.bulk.shared::cluster.global.mbarrier::complete_tx::bytes [%0], [%1], %2, [%3];" :: "r"(dst), "l"(src), "r"(bytes), "r"(mb) : "memory");
}
__device__ __forceinline__ void bulk_store(void* dst, uint32_t src, uint32_t bytes) {
  asm volatile("cp.async.bulk.global.shared::cta.bulk_group [%0], [%1], %2;" :: "l"(dst), "r"(src), "r"(bytes) : "memory");
}
__device__ __forceinline__ void cp_async16(uint32_t dst, const void* src) {
  asm volatile("cp.async.cg.shared.global [%0], [%1], 16;" :: "r"(dst), "l"(src) : "memory");
}
__device__ __forceinline__ void cp_async_wait_all() { asm volatile("cp.async.wait_all;" ::: "memory"); }
__device__ __forceinline__ uint32_t mapa(uint32_t a, uint32_t rank) {
  uint32_t r; asm("mapa.shared::cluster.u32 %0, %1, %2;" : "=r"(r) : "r"(a), "r"(rank)); return r;
}
__device__ __forceinline__ void st_async4(uint32_t dst, float a, float b, float c, float d, uint32_t mb) {
  asm volatile("st.async.shared::cluster.mbarrier::complete_tx::bytes.v4.f32 [%0], {%1,%2,%3,%4}, [%5];" :: "r"(dst), "f"(a), "f"(b), "f"(c), "f"(d), "r"(mb) : "memory");
}
__device__ __forceinline__ void st_async2(uint32_t dst, float a, float b, uint32_t mb) {
  asm volatile("st.async.shared::cluster.mbarrier::complete_tx::bytes.v2.f32 [%0], {%1,%2}, [%3];" :: "r"(dst), "f"(a), "f"(b), "r"(mb) : "memory");
}
__device__ __forceinline__ void st_async1(uint32_t dst, uint32_t a, uint32_t mb) {
  asm volatile("st.async.shared::cluster.mbarrier::complete_tx::bytes.u32 [%0], %1, [%2];" :: "r"(dst), "r"(a), "r"(mb) : "memory");
}
__device__ __forceinline__ uint4 lds128(uint32_t a) {
  uint4 v; asm volatile("ld.shared.v4.u32 {%0,%1,%2,%3}, [%4];" : "=r"(v.x), "=r"(v.y), "=r"(v.z), "=r"(v.w) : "r"(a) : "memory"); return v;
}
__device__ __forceinline__ uint2 lds64(uint32_t a) {
  uint2 v; asm volatile("ld.shared.v2.u32 {%0,%1}, [%2];" : "=r"(v.x), "=r"(v.y) : "r"(a) : "memory"); return v;
}
__device__ __forceinline__ uint32_t lds32(uint32_t a) {
  uint32_t v; asm volatile("ld.shared.u32 %0, [%1];" : "=r"(v) : "r"(a) : "memory"); return v;
}
__device__ __forceinline__ void sts128(uint32_t a, uint4 v) {
  asm volatile("st.shared.v4.u32 [%0], {%1,%2,%3,%4};" :: "r"(a), "r"(v.x), "r"(v.y), "r"(v.z), "r"(v.w) : "memory");
}
__device__ __forceinline__ void sts64(uint32_t a, uint32_t x, uint32_t y) {
  asm volatile("st.shared.v2.u32 [%0], {%1,%2};" :: "r"(a), "r"(x), "r"(y) : "memory");
}
__device__ __forceinline__ void sts32(uint32_t a, uint32_t x) { asm volatile("st.shared.u32 [%0], %1;" :: "r"(a), "r"(x) : "memory"); }
__device__ __forceinline__ void ldsm4(uint32_t& r0, uint32_t& r1, uint32_t& r2, uint32_t& r3, uint32_t a) {
  asm volatile("ldmatrix.sync.aligned.m8n8.x4.shared.b16 {%0,%1,%2,%3}, [%4];" : "=r"(r0), "=r"(r1), "=r"(r2), "=r"(r3) : "r"(a) : "memory");
}
__device__ __forceinline__ void ldsm4t(uint32_t& r0, uint32_t& r1, uint32_t& r2, uint32_t& r3, uint32_t a) {
  asm volatile("ldmatrix.sync.aligned.m8n8.x4.trans.shared.b16 {%0,%1,%2,%3}, [%4];" : "=r"(r0), "=r"(r1), "=r"(r2), "=r"(r3) : "r"(a) : "memory");
}
__device__ __forceinline__ void stsm4(uint32_t a, uint32_t r0, uint32_t r1, uint32_t r2, uint32_t r3) {
  asm volatile("stmatrix.sync.aligned.m8n8.x4.shared.b16 [%0], {%1,%2,%3,%4};" :: "r"(a), "r"(r0), "r"(r1), "r"(r2), "r"(r3) : "memory");
}
__device__ __forceinline__ uint32_t movmat(uint32_t a) {
  uint32_t d; asm volatile("movmatrix.sync.aligned.m8n8.trans.b16 %0, %1;" : "=r"(d) : "r"(a)); return d;
}
__device__ __forceinline__ void mma16(float* d, uint32_t a0, uint32_t a1, uint32_t a2, uint32_t a3, uint32_t b0, uint32_t b1) {
  asm volatile("mma.sync.aligned.m16n8k16.row.col.f32.bf16.bf16.f32 {%0,%1,%2,%3}, {%4,%5,%6,%7}, {%8,%9}, {%0,%1,%2,%3};"
    : "+f"(d[0]), "+f"(d[1]), "+f"(d[2]), "+f"(d[3]) : "r"(a0), "r"(a1), "r"(a2), "r"(a3), "r"(b0), "r"(b1));
}
__device__ __forceinline__ void mma8(float* d, uint32_t a0, uint32_t a1, uint32_t b0) {
  asm volatile("mma.sync.aligned.m16n8k8.row.col.f32.bf16.bf16.f32 {%0,%1,%2,%3}, {%4,%5}, {%6}, {%0,%1,%2,%3};"
    : "+f"(d[0]), "+f"(d[1]), "+f"(d[2]), "+f"(d[3]) : "r"(a0), "r"(a1), "r"(b0));
}
__device__ __forceinline__ float rcp(float x) { float r; asm("rcp.approx.ftz.f32 %0, %1;" : "=f"(r) : "f"(x)); return r; }
__device__ __forceinline__ float ex2(float x) { float r; asm("ex2.approx.ftz.f32 %0, %1;" : "=f"(r) : "f"(x)); return r; }

__host__ __device__ constexpr uint64_t mkdesc(uint32_t off, uint32_t lbo, uint32_t sbo, uint32_t swz) {
  return (uint64_t)((SBASE + off) >> 4) | ((uint64_t)(lbo >> 4) << 16) | ((uint64_t)(sbo >> 4) << 32) | ((uint64_t)swz << 62);
}
__host__ __device__ constexpr uint64_t desc_sw128(uint32_t off) { return mkdesc(off, 16, 1024, 1); }
__host__ __device__ constexpr uint64_t desc_n16(uint32_t off) { return mkdesc(off, 256, 128, 0); }
__host__ __device__ constexpr uint64_t desc_m(uint32_t off) { return mkdesc(off, 16, 256, 3); }

__host__ __device__ constexpr uint64_t desc_sw64(uint32_t off) { return mkdesc(off, 16, 512, 2); }

__device__ __forceinline__ void wg_fence() { asm volatile("wgmma.fence.sync.aligned;" ::: "memory"); }
__device__ __forceinline__ void wg_commit() { asm volatile("wgmma.commit_group.sync.aligned;" ::: "memory"); }
template <int N> __device__ __forceinline__ void wg_wait() { asm volatile("wgmma.wait_group.sync.aligned %0;" :: "n"(N) : "memory"); }

#define ACC8(d) "+f"(d[0]), "+f"(d[1]), "+f"(d[2]), "+f"(d[3]), "+f"(d[4]), "+f"(d[5]), "+f"(d[6]), "+f"(d[7])
#define ACC32(d) ACC8(d), ACC8((d + 8)), ACC8((d + 16)), ACC8((d + 24))
#define R8 "{%0,%1,%2,%3,%4,%5,%6,%7}"
#define R32 "{%0,%1,%2,%3,%4,%5,%6,%7,%8,%9,%10,%11,%12,%13,%14,%15,%16,%17,%18,%19,%20,%21,%22,%23,%24,%25,%26,%27,%28,%29,%30,%31}"
template <int SD> __device__ __forceinline__ void wg_rs16(float* d, const uint32_t* a, uint64_t db) {
  asm volatile("wgmma.mma_async.sync.aligned.m64n16k16.f32.bf16.bf16 " R8 ", {%8,%9,%10,%11}, %12, %13, 1, 1, 1;"
    : ACC8(d) : "r"(a[0]), "r"(a[1]), "r"(a[2]), "r"(a[3]), "l"(db), "n"(SD));
}
template <int SD> __device__ __forceinline__ void wg_ss16(float* d, uint64_t da, uint64_t db) {
  asm volatile("wgmma.mma_async.sync.aligned.m64n16k16.f32.bf16.bf16 " R8 ", %8, %9, %10, 1, 1, 1, 1;"
    : ACC8(d) : "l"(da), "l"(db), "n"(SD));
}
template <int SD, uint64_t DA, uint64_t DB> __device__ __forceinline__ void wg_ss16o(float* d, uint32_t oa, uint32_t ob) {
  asm volatile("{.reg .b32 x, y; .reg .b64 a, b; add.u32 x, %8, %10; add.u32 y, %9, %12; mov.b64 a, {x, %11}; mov.b64 b, {y, %13};\n"
               "wgmma.mma_async.sync.aligned.m64n16k16.f32.bf16.bf16 " R8 ", a, b, %14, 1, 1, 1, 1;}"
    : ACC8(d) : "r"(oa), "r"(ob), "n"((uint32_t)DA), "n"((uint32_t)(DA >> 32)), "n"((uint32_t)DB), "n"((uint32_t)(DB >> 32)), "n"(SD));
}
template <int SD> __device__ __forceinline__ void wg_rs64(float* d, const uint32_t* a, uint64_t db) {
  asm volatile("wgmma.mma_async.sync.aligned.m64n64k16.f32.bf16.bf16 " R32 ", {%32,%33,%34,%35}, %36, %37, 1, 1, 0;"
    : ACC32(d) : "r"(a[0]), "r"(a[1]), "r"(a[2]), "r"(a[3]), "l"(db), "n"(SD));
}
template <int SD> __device__ __forceinline__ void wg_ss64(float* d, uint64_t da, uint64_t db) {
  asm volatile("wgmma.mma_async.sync.aligned.m64n64k16.f32.bf16.bf16 " R32 ", %32, %33, %34, 1, 1, 1, 0;"
    : ACC32(d) : "l"(da), "l"(db), "n"(SD));
}
#define WG_RSO(NAME, SHAPE, REGS, ACC, A, TB) \
template <int SD, uint64_t DB> __device__ __forceinline__ void NAME(float* d, uint32_t a0, uint32_t a1, uint32_t a2, uint32_t a3, uint32_t ob) { \
  asm volatile("{.reg .b64 b; mov.b64 b, {" A(4) ", " A(5) "};\nwgmma.mma_async.sync.aligned." SHAPE ".f32.bf16.bf16 " REGS \
               ", {" A(0) "," A(1) "," A(2) "," A(3) "}, b, " A(6) ", 1, 1, " TB ";}" \
    : ACC(d) : "r"(a0), "r"(a1), "r"(a2), "r"(a3), "r"(ob + (uint32_t)DB), "n"((uint32_t)(DB >> 32)), "n"(SD)); \
}
#define ACC4(d) "+f"(d[0]), "+f"(d[1]), "+f"(d[2]), "+f"(d[3])
#define ACC16(d) ACC8(d), ACC8((d + 8))
#define OP4(i) OP4_##i
#define OP4_0 "%4"
#define OP4_1 "%5"
#define OP4_2 "%6"
#define OP4_3 "%7"
#define OP4_4 "%8"
#define OP4_5 "%9"
#define OP4_6 "%10"
#define OP16(i) OP16_##i
#define OP16_0 "%16"
#define OP16_1 "%17"
#define OP16_2 "%18"
#define OP16_3 "%19"
#define OP16_4 "%20"
#define OP16_5 "%21"
#define OP16_6 "%22"
#define OP32(i) OP32_##i
#define OP32_0 "%32"
#define OP32_1 "%33"
#define OP32_2 "%34"
#define OP32_3 "%35"
#define OP32_4 "%36"
#define OP32_5 "%37"
#define OP32_6 "%38"
WG_RSO(wg_rs8o, "m64n8k16", "{%0,%1,%2,%3}", ACC4, OP4, "1")
WG_RSO(wg_rs32o, "m64n32k16", "{%0,%1,%2,%3,%4,%5,%6,%7,%8,%9,%10,%11,%12,%13,%14,%15}", ACC16, OP16, "1")
WG_RSO(wg_rs64o, "m64n64k16", R32, ACC32, OP32, "0")
template <int N> __device__ __forceinline__ void reg_inc() { asm volatile("setmaxnreg.inc.sync.aligned.u32 %0;" :: "n"(N)); }
template <int N> __device__ __forceinline__ void reg_dec() { asm volatile("setmaxnreg.dec.sync.aligned.u32 %0;" :: "n"(N)); }
__device__ __forceinline__ void cluster_sync() {
  asm volatile("barrier.cluster.arrive.relaxed.aligned;\nbarrier.cluster.wait.aligned;" ::: "memory");
}

template <int KS>
__device__ __forceinline__ void load_frags(uint32_t* a, uint32_t src) {
  const int lane = threadIdx.x & 31, w = (threadIdx.x >> 5) & 3;
  const int k = ((lane >> 4) << 3) + (lane & 7), u = w * 2 + ((lane >> 3) & 1);
  const uint32_t base = src + k * 128 + ((u ^ (k & 7)) << 4);
#pragma unroll
  for (int ks = 0; ks < KS; ks++) ldsm4t(a[ks * 4], a[ks * 4 + 1], a[ks * 4 + 2], a[ks * 4 + 3], base + ks * 2048);
}

__device__ __forceinline__ uint32_t badd2(uint32_t a, uint32_t b) { uint32_t r; asm("add.rn.bf16x2 %0, %1, %2;" : "=r"(r) : "r"(a), "r"(b)); return r; }
__device__ __forceinline__ uint32_t bsub2(uint32_t a, uint32_t b) { uint32_t r; asm("sub.rn.bf16x2 %0, %1, %2;" : "=r"(r) : "r"(a), "r"(b)); return r; }
__device__ __forceinline__ uint32_t bmul2(uint32_t a, uint32_t b) { uint32_t r; asm("mul.rn.bf16x2 %0, %1, %2;" : "=r"(r) : "r"(a), "r"(b)); return r; }
__device__ __forceinline__ uint32_t bfma2(uint32_t a, uint32_t b, uint32_t c) { uint32_t r; asm("fma.rn.bf16x2 %0, %1, %2, %3;" : "=r"(r) : "r"(a), "r"(b), "r"(c)); return r; }
template <int R> __device__ __forceinline__ void layernorm9(const uint32_t* x, uint32_t* o) {
  const uint32_t ones = 0x3F803F80u;
  float a[R][3][4], q[R], s[R];
#pragma unroll
  for (int i = 0; i < 9 * R; i++) {
    float* d = a[i % R][i / R % 3];
    if (i < 3 * R) d[0] = d[1] = d[2] = d[3] = 0.f;
    mma8(d, x[i % R * 9 + i / R], ones, x[i % R * 9 + i / R]);
  }
#pragma unroll
  for (int r = 0; r < R; r++) {
    q[r] = threadIdx.x & 4 ? a[r][0][1] + a[r][1][1] + a[r][2][1] : a[r][0][0] + a[r][1][0] + a[r][2][0];
    s[r] = (a[r][0][2] + a[r][0][3]) + (a[r][1][2] + a[r][1][3]) + (a[r][2][2] + a[r][2][3]);
  }
#pragma unroll
  for (int r = 0; r < R; r++) { q[r] += __shfl_xor_sync(~0u, q[r], 4); s[r] += __shfl_xor_sync(~0u, s[r], 1); }
#pragma unroll
  for (int r = 0; r < R; r++) { q[r] += __shfl_xor_sync(~0u, q[r], 9); s[r] += __shfl_xor_sync(~0u, s[r], 2); }
#pragma unroll
  for (int r = 0; r < R; r++) q[r] = __shfl_sync(~0u, q[r], 0) + __shfl_sync(~0u, q[r], 18);
#pragma unroll
  for (int r = 0; r < R; r++) {
    const float mean = s[r] * (1.f / DM), var = fmaxf(fmaf(q[r], 1.f / DM, -mean * mean), 0.f);
    float sd;
    asm("sqrt.approx.ftz.f32 %0, %1;" : "=f"(sd) : "f"(bf_lo(pack2(bf_lo(pack2(var, 0.f)) + 1e-5f, 0.f))));
    const float inv = rcp(bf_lo(pack2(sd, 0.f)));
    const uint32_t mb = pack2(mean, mean), hi = pack2(inv, inv), lo = pack2(inv - bf_lo(hi), inv - bf_lo(hi));
#pragma unroll
    for (int i = r * 9; i < r * 9 + 9; i++) {
      const uint32_t d = bsub2(x[i], mb);
      o[i] = bfma2(d, hi, bmul2(d, lo));
    }
  }
}
__device__ __forceinline__ void store_ln_row(int layer, int tok, const uint32_t* o) {
  const int lane = threadIdx.x & 31, r = tok & 31;
  unsigned char* p = g_lnimg + (size_t)(layer * NSEG + (tok >> 5)) * (9 * 4096) + r * 128 + (((lane >> 2) ^ (r & 7)) << 4) + (lane & 3) * 4;
#pragma unroll
  for (int i = 0; i < 9; i++) *(uint32_t*)(p + i * 4096) = o[i];
}
struct Params { const bf16 *X, *K, *V, *shift, *Hk, *Dk, *mem0, *Wq, *Wk, *Wv, *Wo; bf16* out; uint32_t dly[20]; };
#define DLYS P.dly[0]
#define DLYW P.dly[1]
#define KLATE P.dly[2]
#define DLYQ P.dly[3]
#define DLYK P.dly[4]
#define DLYG P.dly[5]
#define KWIN P.dly[6]
#define KMIN P.dly[7]
uint32_t h_dly[20] = {800, 1100, 20, 0, 3650, 3200, 1800, 400, 1750, 1800, 2070, 2230, 2380, 2530, 3080, 3230, 3370, 3480, 3620};

constexpr uint32_t C_W = 0, C_M = 147456, C_KV = C_M + 18432, C_QM = C_KV + 32768, C_KM = C_QM + 2048,
                   C_VM = C_KM + 2048, C_OI = C_VM + 2048, C_SX = C_OI + 4096, C_KM2 = C_SX + 2560, C_VM2 = C_KM2 + 128,
                   C_KV2 = C_KM2 + 2048, C_Q = C_KV2 + 8192, C_BAR = C_Q + 8192;
constexpr uint32_t CB_FULL = C_BAR, CB_REF = C_BAR + 16, CB_SX = C_BAR + 32, CB_OX = C_BAR + 40, CB_XX = C_BAR + 48, CB_Q = C_BAR + 56, C_BAD = C_BAR + 64, S_GEN = C_BAR + 128, C_REF = C_BAR + 132, CB_VF = C_BAR + 144, CB_M = C_BAR + 160, CB_MV = C_BAR + 200;
constexpr uint32_t G_W = 0, G_RING = 147456, G_W2 = G_RING + 9 * 8192, G_BAR = G_W2 + 8192;
constexpr uint32_t O_W = 0, O_RING = 3 * 40960, O_ST = O_RING + 11 * 8192, O_BAR = O_ST + 16384, OB_ST = O_BAR + 64;
constexpr uint32_t F_A = 0, F_XY = 36864, F_L = F_XY + 36864, F_X = F_L + 18432, F_BAR = F_L + 2 * 36864;
constexpr uint32_t SMEM_BYTES = C_BAR + 256;
static_assert(G_BAR + 256 <= SMEM_BYTES && O_BAR + 256 <= SMEM_BYTES && F_BAR + 16 <= SMEM_BYTES && SMEM_BYTES <= 232448, "smem map");
enum { B_INIT = 1, B_M, B_QK, B_S, B_V, B_O, B_X, B_WG0, B_WG1, B_WG2, B_G, B_OE, B_T, B_R };

__device__ __forceinline__ uint4 pack_partial(const float* d, uint32_t tag) {
  uint32_t x;
  asm("lop3.b32 %0, %1, 1, %2, 0xb8;" : "=r"(x) : "r"(pack2(d[0], d[1])), "r"(tag));
  return make_uint4(x, pack2(d[4], d[5]), pack2(d[2], d[3]), pack2(d[6], d[7]));
}
__device__ __forceinline__ void store_partial(uint4* p, const uint4& v) { st_b128(p, v.x, v.y, v.z, v.w); }
__device__ __forceinline__ void gather_reduce(const uint32_t* p, uint32_t* dst, bool shared, uint32_t tag, uint32_t lane, uint32_t sb, int n, int TS0) {
  int tries = 0;
  float u, v;
  bool bad;
  TR(TS0);
  do {
    uint32_t x[16];
#pragma unroll
    for (int i = 0; i < 16; i++) asm volatile("ld.relaxed.gpu.global.u32 %0, [%1];" : "=r"(x[i]) : "l"(p + i * 64) : "memory");
    tries++;
    float a[2] = {bf_lo(x[0]), bf_lo(x[1])}, b[2] = {bf_hi(x[0]), bf_hi(x[1])};
    uint32_t t = 0;
#pragma unroll
    for (int i = 2; i < 16; i++) { a[i & 1] += bf_lo(x[i]); b[i & 1] += bf_hi(x[i]); }
#pragma unroll
    for (int i = 0; i < 16; i += 4)
      asm("{.reg .b32 y, z; lop3.b32 y, %1, %2, %5, 0x7e; lop3.b32 z, %3, %4, %5, 0x7e; lop3.b32 %0, %0, y, z, 0xfe;}"
          : "+r"(t) : "r"(x[i]), "r"(x[i + 1]), "r"(x[i + 2]), "r"(x[i + 3]), "r"(tag));
    u = a[0] + a[1]; v = b[0] + b[1];
    bad = __any_sync(~0u, (t & 1) && !(lane & 3));
    if (shared) { u += __shfl_xor_sync(~0u, u, 8); v += __shfl_xor_sync(~0u, v, 8); }
    u += __shfl_xor_sync(~0u, u, 16);
    v += __shfl_xor_sync(~0u, v, 16);
    st_relaxed_if(dst, pack2(u, v), !bad && (n >= LAG || !(lane & 1)));
  } while (bad);
  TR(TS0 + 3); TRV(TS0 + 2, tries);
  CNT((TS0 - 16) >> 2, tries);
}
__device__ __forceinline__ uint32_t sent_bad(const uint4& v) { return max(max(v.x, v.y), max(v.z, v.w)) == SENT; }

__host__ __device__ constexpr int o_ks(int s) { return s & (s < 8 ? 3 : 7); }
__host__ __device__ constexpr bool o_reg(int s) { return s < 8 ? (s & 3) != 3 : !(s & 1); }
__host__ __device__ constexpr int o_slot(int s) { return s < 8 ? (o_reg(s) ? s - (s >> 2) : s >> 2) : s & 1 ? (s - 5) >> 1 : (s + 4) >> 1; }
__device__ __forceinline__ int g_unit(int wg) {
  const int i = bid() - N_CHAIN;
  return i < 32 ? wg * 64 + i : 2 * i - 32 + wg;
}
__device__ __forceinline__ const bf16* slot_row(const Params& P, bool regs, int i, int r) {
  const int b = bid();
  if (b < N_CHAIN) {
    const int wg = i >= 36, col = b * 64;
    i -= wg * 36;
    if (wg || i < 18) {
      const bf16* w = !wg ? P.Wq : i < 18 ? P.Wk : P.Wv;
      return w + col + (size_t)(((i % 18) * 2 + !regs) * 16 + ((r & 1) << 3) + (r >> 1)) * HD;
    }
    i -= 18;
    if (!regs && i >= 14) return P.Wo + (size_t)(col + (i - 14) * 16 + r) * DM;
    const int st = regs ? (i < 6 ? i + i / 3 : 2 * i - 4) : i < 2 ? 4 * i + 3 : 2 * i + 5, ks = o_ks(st);
    const int f = 64 + (st < 8 ? (st >> 2) * 64 : (st >> 3) * 128 + (b & 1) * 64);
    return P.Wo + f + (size_t)((col ^ ((ks & 4) << 4)) + (ks & 3) * 16 + r) * DM;
  }
  if (b < N_CHAIN + N_G) {
    int wg = i >= 36, ks = i - wg * 36;
    if (i >= 72) { wg = (i - 72) >> 1; ks = 34 + (i & 1); regs = true; }
    const int q = g_unit(wg);
    const bf16* w = (q < 32 ? P.Wk : q < 64 ? P.Wv : P.Wq) + (q & 31) * 128 + (regs ? 0 : 64);
    return w + (size_t)(ks * 16 + r) * HD;
  }
  const int o = b - N_CHAIN - N_G, ksl = o / 3, per = regs ? 24 : 20, wg = i / per;
  i -= wg * per;
  const int k = (ksl * 11 - max(ksl - 4, 0)) * 64 + (regs ? i / 3 * 5 + i % 3 * 2 : i < 16 ? i / 2 * 5 + 1 + i % 2 * 2 : i + 24) * 16 + r;
  const int kk = (k & ~31) | (((k >> 1) & 3) << 3) | (((k >> 3) & 3) << 1) | (k & 1);
  return P.Wo + (size_t)kk * DM + ((o % 3) * 3 + (wg + ksl) % 3) * 64;
}
__device__ __forceinline__ void load_run(const Params& P, uint32_t dst, bool regs, int i0, int n) {
  const int r = (threadIdx.x & 127) >> 3, u = threadIdx.x & 7;
  const bf16* p0 = slot_row(P, regs, i0, r) + u * 8;
  const bf16* p1 = slot_row(P, regs, i0 + 1, r) + u * 8;
  const long step = n > 2 ? slot_row(P, regs, i0 + 2, r) + u * 8 - p0 : 0;
  dst += r * 128 + ((u ^ (r & 7)) << 4);
#pragma unroll 2
  for (int i = 0; i < n; i += 2, dst += 4096, p0 += step, p1 += step) {
    cp_async16(dst, p0);
    cp_async16(dst + 2048, p1);
    if (regs) asm volatile("cp.async.commit_group;\ncp.async.wait_group %0;" :: "n"(INFL) : "memory");
  }
}
__device__ __forceinline__ void load_wg(const Params& P, uint32_t sb, bool regs, int wg) {
  if (bid() < N_CHAIN) {
#pragma unroll 1
    for (int i0 = wg * 36, len = 18; i0 < wg * 36 + 36; i0 += len, len = wg ? 18 : 2) load_run(P, sb + i0 * 2048, regs, i0, len);
  } else if (bid() < N_CHAIN + N_G) {
    load_run(P, sb + wg * 73728, regs, wg * 36, regs ? 34 : 36);
    if (!regs) load_run(P, sb + G_W2 + wg * 4096, false, 72 + wg * 2, 2);
  } else {
    const int per = regs ? 24 : 20, cnt = regs || bid() < N_CHAIN + N_G + 12 ? per : 16;
#pragma unroll 1
    for (int i0 = wg * per; i0 < wg * per + cnt; i0 += 2) load_run(P, sb + i0 * 2048, regs, i0, 2);
  }
}
__device__ __forceinline__ uint32_t near_half(uint32_t blk, uint32_t reader) {
  return __ldcg(g_near + (blk >> 3)) ^ (~blk & 1) ^ __ldcg(g_side + (blk >> 3)) ^ __ldcg(g_side + reader);
}

__device__ __forceinline__ uint32_t opaque_tid() { uint32_t t; asm volatile("mov.u32 %0, %%tid.x;" : "=r"(t)); return t; }
__device__ __forceinline__ void m_fetch(uint32_t sb, uint32_t src, uint32_t b, uint32_t mb) {
  bulk_load(sb + C_M + (b ? b * 4096 - 2048 : 0), (const unsigned char*)g_mimg + ((src ^ ((b & 1) * 4096)) + b * 8192), b ? 4096 : 2048, mb);
}
__device__ __forceinline__ uint32_t pinned(uint32_t v) { return __shfl_sync(~0u, v, threadIdx.x & 31); }
template <class T> __device__ __forceinline__ T* pinned(T* p) { return (T*)__shfl_sync(~0u, (unsigned long long)p, threadIdx.x & 31); }
__device__ __forceinline__ uint32_t m_probe(uint32_t lane) { return lane * 32 + (lane & 4) * 4 + (lane >> 3) * 4; }
__device__ __forceinline__ uint32_t m_max(uint32_t a, uint32_t b) {
  return max(max(lds32(a), lds32(a + 1024)), max(lds32(b), lds32(b + 1024)));
}
template <int S0, int N> __device__ __forceinline__ void o_steps(float* d, const uint32_t* a) {
  constexpr int SD = o_ks(S0) != 0;
  if constexpr (o_reg(S0)) wg_rs16<SD>(d, a + (18 + o_slot(S0)) * 4, desc_n16(C_OI + o_ks(S0) * 512));
  else wg_ss16<SD>(d, desc_sw128(C_W + (18 + o_slot(S0)) * 2048), desc_n16(C_OI + o_ks(S0) * 512));
  if constexpr (N > 1) o_steps<S0 + 1, N - 1>(d, a);
}
template <int BASE, int KS, int N> __device__ __forceinline__ void m_steps(float* d, const uint32_t* a, uint32_t oa) {
  wg_rs16<KS != 0>(d, a + (BASE + KS / 2) * 4, desc_m(C_M + KS * 512));
  wg_ss16o<1, desc_sw128(C_W + (BASE + KS / 2) * 2048), desc_m(C_M + KS * 512 + 512)>(d, oa, 0);
  if constexpr (N > 2) m_steps<BASE, KS + 2, N - 2>(d, a, oa);
}

__device__ __forceinline__ void chain_proj(const Params& P, uint32_t sb) {
  const uint32_t c = chain_id(), h = c >> 1, j = c & 1, wid = __shfl_sync(~0u, threadIdx.x >> 5, 0), wg = wid >> 2, w = wid & 3;
  const uint32_t t = threadIdx.x & 127, lane = pinned(t & 31), mine = pinned(sb + t * 16), rb = mapa(sb, j ^ 1);
  const uint32_t theirs = pinned(rb + C_KM2 + w * 512 + lane * 4), oa = wg * 4608;
  uint32_t a[144];
  const uint32_t round = min(w, 2u) + (wg ? 0 : 3), gdly = P.dly[8 + round], ps = t >> 2, pf = j * 16 + (ps >> 1);
  uint4* const dsts = pinned(g_xb + (ps * 4096 + near_half(ps * 8, ps * 2) * 256 + c * 4 + (t & 3)));
  uint4* const dstf = pinned(g_xb + (pf * 4096 + 512 + near_half(pf * 8 + 1, pf * 2) * 256 + h * 8 + (t & 7)));
  const uint32_t* const gsrc = (const uint32_t*)g_xb + (h * 16384 + min(w, 2u) * 4096 + near_half(h * 8 + !wg, h * 2) * 1024 +
                               (wg ? (lane & 24) * 2 + j * 8 + (lane & 7) : 2048 + (lane & 16) * 2 + j * 16 + (lane & 15)));
  uint32_t* gdst = g_mimg + (16384 + (lane >> 4) * 1024 + (lane & 2) * 4 +
                   (wg ? (round ? 1536 + round * 512 : 0) + h * 16 + ((lane ^ (c >> 2)) & 1) * 4 + j * 2 + ((lane >> 2) & 1)
                       : (round - 1) * 2048 + c * 16 + ((lane ^ (c >> 1)) & 1) * 4 + ((lane >> 2) & 3)));
  load_frags<36>(a, sb + C_W + wg * 73728);
  bar_sync(B_WG0 + wg, 128);
  load_wg(P, sb, false, wg);
  cp_async_wait_all();
  fence_async_smem();
  bar_sync(B_INIT, 352);
  TS(4);

  uint32_t ring = 1;
#pragma unroll 1
  for (int n = 0; n < STEPS; n++) {
    float d[8], e[8];
    uint32_t redo = n + 1;
    do {
      mbar_wait(sb + CB_M, n & 1);
      wg_fence();
      m_steps<0, 0, 4>(d, a, oa);
      if (VE && wg) m_steps<18, 0, 4>(e, a, 4608);
      wg_commit();
      if (wid == 0) TR(8);
      mbar_wait(sb + CB_M + 8, n & 1);
      wg_fence();
      m_steps<0, 4, 8>(d, a, oa);
      if (VE > 4 && wg) m_steps<18, 4, (VE > 4 ? VE - 4 : 2)>(e, a, 4608);
      wg_commit();
      mbar_wait(sb + CB_MV, n & 1);
      redo = lds32(sb + C_BAD) == redo ? SENT : 0;
    } while (redo);
    mbar_wait(sb + CB_MV + 8, n & 1);
    wg_fence();
    m_steps<0, 12, 8>(d, a, oa);
    wg_commit();
    mbar_wait(sb + CB_MV + 16, n & 1);
    wg_fence();
    m_steps<0, 20, 8>(d, a, oa);
    wg_commit();
    mbar_wait(sb + CB_MV + 24, n & 1);
    wg_fence();
    m_steps<0, 28, 8>(d, a, oa);
    wg_commit();
    wg_wait<0>();
    if (w == 0) TR(6 + wg);
    const uint32_t f0 = pack2(d[0], d[1]), f1 = pack2(d[4], d[5]), f2 = pack2(d[2], d[3]), f3 = pack2(d[6], d[7]);
    stsm4(mine + C_QM + wg * 2048, f0, f1, f2, f3);
    bar_arrive(B_QK, 416);
    const uint32_t tag = (n & 1) ^ 1;
    if (wg) {
      if (n + 1 < STEPS) bar_sync(B_S, 256);
      wg_fence();
      m_steps<18, VE, 36 - VE>(e, a, 4608);
      wg_commit();
      st_async1(theirs, j ? f0 : f1, rb + CB_XX);
      st_async1(theirs + 256, j ? f2 : f3, rb + CB_XX);
      wg_wait<0>();
      if (w == 0) TR(11);
      const uint32_t v0 = pack2(e[0], e[1]), v1 = pack2(e[4], e[5]), v2 = pack2(e[2], e[3]), v3 = pack2(e[6], e[7]);
      stsm4(mine + C_VM, v0, v1, v2, v3);
      bar_arrive(B_V, 256);
      st_async1(theirs + 128, j ? v0 : v1, rb + CB_XX);
      st_async1(theirs + 384, j ? v2 : v3, rb + CB_XX);
      if (n + 1 == STEPS) break;
      bar_sync(B_O, 256);
      fence_async_smem();
      wg_fence();
#pragma unroll
      for (int ks = 0; ks < 4; ks++) {
        if (ks == 0) wg_ss16<0>(d, desc_sw128(C_W + 32 * 2048), desc_n16(C_OI));
        else wg_ss16<1>(d, desc_sw128(C_W + (32 + ks) * 2048), desc_n16(C_OI + ks * 512));
      }
      wg_commit();
      bar_arrive(B_X, 256);
      if (w == 0) TR(0);
      wg_wait<0>();
      store_partial(dsts, pack_partial(d, tag));
      bar_arrive(B_M, 160);
      if (w == 0) TR(1);
    } else {
      if (n + 1 == STEPS) break;
      bar_sync(B_X, 256);
      wg_fence();
      o_steps<0, 4>(d, a);
      wg_commit();
      o_steps<4, 4>(e, a);
      wg_commit();
      wg_wait<1>();
      store_partial(dsts + 1024, pack_partial(d, tag));
      if (w == 0) TR(2);
      if (OGAP == 0) { wg_fence(); o_steps<8, 4>(d, a); wg_commit(); wg_wait<1>(); } else wg_wait<0>();
      store_partial(dsts + 2048, pack_partial(e, tag));
      if (w == 0) TR(3);
      wg_fence();
      if (OGAP) o_steps<8, 4>(d, a);
      if (OGAP < 2) o_steps<16, 4>(e, a);
      wg_commit();
      bar_sync(B_T, 256);
      if (w == 0) { TRV(61, 0); TR(12); }
      wg_fence();
      o_steps<12, 4>(d, a);
      wg_commit();
      if (OGAP == 2) o_steps<16, 4>(e, a);
      o_steps<20, 4>(e, a);
      wg_commit();
      wg_wait<1>();
      store_partial(dstf, pack_partial(d, tag));
      if (w == 0) TR(4);
      wg_fence();
      o_steps<24, 8>(d, a);
      wg_commit();
      wg_wait<1>();
      store_partial(dstf + 1024, pack_partial(e, tag));
      bar_arrive(B_OE, 256);
      if (w == 0) TR(5);
      wg_wait<0>();
      store_partial(dstf + 2048, pack_partial(d, tag));
      if (w == 0) TR(15);
    }
    if (w < 3) {
      mbar_wait(sb + CB_REF, n & 1);
      wait_until(lds32(sb + C_REF), gdly);
      gather_reduce(gsrc, gdst, wg, tag, lane, sb, n, 16 + round * 4);
      if (++ring == MRING) { ring = 0; gdst -= MRING * 16384; }
      gdst += 16384;
    }
  }
}

template <int KS> __device__ __forceinline__ void x_scores(float* s, float* sm, const uint4* q, uint32_t ok, uint32_t om) {
  wg_rs32o<1, desc_sw64(C_KV + KS * 1024)>(s, q[KS].x, q[KS].y, q[KS].z, q[KS].w, ok);
  wg_rs8o<1, desc_n16(C_KM + KS * 512)>(sm, q[KS].x, q[KS].y, q[KS].z, q[KS].w, om);
  if constexpr (KS < 3) x_scores<KS + 1>(s, sm, q, ok, om);
}

__device__ __forceinline__ void chain_attn(const Params& P, uint32_t sb) {
  const int c = chain_id(), j = c & 1;
  const int tid = threadIdx.x, lane = tid & 31, w = __shfl_sync(~0u, (tid >> 5) & 3, 0);
  const int l = w >> 1, u = w & 1;
  const uint32_t rb = mapa(sb, j ^ 1);
  const float sc = 0.08838834764831845f * 1.4426950408889634f;
  const uint32_t ones = 0x3F803F80u;
  const uint32_t km_off = C_KM + (lane >> 3) * 256 + l * 128 + (lane & 7) * 16;
  const uint32_t qm_off = C_QM + (lane >> 4) * 256 + l * 128 + (lane & 7) * 16;
  const uint32_t kv_off = C_KV + l * 4096 + (lane & 15) * 64 + (((lane >> 4) ^ (u * 2) ^ ((lane >> 1) & 3)) << 4);

  if (lane == 0) mbar_arrive(sb + CB_M);
#pragma unroll 1
  for (int n = 0; n < STEPS; n++) {
    const uint32_t kvb = sb + kv_off + (n & 1) * 16384;
    if (w == 0 && elect()) { mbar_expect(sb + CB_SX, 2560); mbar_expect(sb + CB_OX, 2048); mbar_expect(sb + CB_XX, 2048); }
    mbar_wait(sb + CB_FULL + (n & 1) * 8, (n >> 1) & 1);
    if (n == 0) TS(5);
    __syncwarp();
    {
      uint32_t km[8];
      uint4 kx[8];
#pragma unroll
      for (int i = 0; i < 8; i++) ldsm4t(kx[i].x, kx[i].y, kx[i].z, kx[i].w, (kvb ^ ((i & 1) * 32)) + (i >> 1) * 1024);
      mbar_wait(sb + CB_VF, n & 1);
      if (w == 1) TRD(60, kx[7].x);
      bar_sync(B_QK, 416);
      if (n + 1 == STEPS) {
        bar_sync(B_V, 256);
      } else {
      uint32_t qm[16];
#pragma unroll
      for (int ks = 0; ks < 4; ks++) ldsm4t(qm[4 * ks], qm[4 * ks + 1], qm[4 * ks + 2], qm[4 * ks + 3], sb + qm_off + ks * 512);
      ldsm4t(km[0], km[1], km[2], km[3], sb + km_off);
      ldsm4t(km[4], km[5], km[6], km[7], sb + km_off + 1024);
      float s[5][4];
#pragma unroll
      for (int i = 0; i < 5; i++) { s[i][0] = s[i][1] = s[i][2] = s[i][3] = 0.f; }
#pragma unroll
      for (int ks = 0; ks < 4; ks++) {
        const uint32_t* q = qm + 4 * ks;
        mma16(s[1], q[0], q[1], q[2], q[3], kx[2 * ks].x, kx[2 * ks].y);
        mma16(s[2], q[0], q[1], q[2], q[3], kx[2 * ks].z, kx[2 * ks].w);
        mma16(s[0], q[0], q[1], q[2], q[3], km[2 * ks], km[2 * ks + 1]);
        mma16(s[3], q[0], q[1], q[2], q[3], kx[2 * ks + 1].x, kx[2 * ks + 1].y);
        mma16(s[4], q[0], q[1], q[2], q[3], kx[2 * ks + 1].z, kx[2 * ks + 1].w);
      }
      const uint32_t sx = C_SX + l * 1280;
      st_async4(rb + sx + u * 512 + lane * 16, s[1][0], s[1][1], s[2][0], s[2][1], rb + CB_SX);
      st_async1(rb + sx + 1024 + u * 128 + lane * 4, __float_as_uint(u ? s[0][1] : s[0][0]), rb + CB_SX);
      bar_arrive_after<B_S, 256>(__float_as_uint(s[3][0]), __float_as_uint(s[4][0]));
      uint4 vx[4];
#pragma unroll
      for (int i = 0; i < 4; i++) ldsm4(vx[i].x, vx[i].y, vx[i].z, vx[i].w, (kvb ^ ((i & 1) * 32)) + 8192 + (2 * u + (i >> 1)) * 1024);
      mbar_wait(sb + CB_SX, n & 1);
      const uint4 p0 = lds128(sb + sx + u * 512 + lane * 16), p1 = lds128(sb + sx + (u ^ 1) * 512 + lane * 16);
      const uint2 p2 = make_uint2(lds32(sb + sx + 1024 + lane * 4), lds32(sb + sx + 1152 + lane * 4));
      float t[10] = {s[0][0] + __uint_as_float(p2.x), s[0][1] + __uint_as_float(p2.y),
                     s[1][0] + __uint_as_float(p0.x), s[1][1] + __uint_as_float(p0.y),
                     s[2][0] + __uint_as_float(p0.z), s[2][1] + __uint_as_float(p0.w),
                     s[3][0] + __uint_as_float(p1.x), s[3][1] + __uint_as_float(p1.y),
                     s[4][0] + __uint_as_float(p1.z), s[4][1] + __uint_as_float(p1.w)};
      float mx = fmaxf(fmaxf(fmaxf(fmaxf(t[2], t[3]), fmaxf(t[4], t[5])), fmaxf(fmaxf(t[6], t[7]), fmaxf(t[8], t[9]))), fmaxf(t[0], t[1]));
      mx = fmaxf(fmaxf(mx, __shfl_xor_sync(~0u, mx, 1)), fmaxf(__shfl_xor_sync(~0u, mx, 2), __shfl_xor_sync(~0u, mx, 3)));
      const float ms = -mx * sc;
#pragma unroll
      for (int i = 0; i < 10; i++) t[i] = ex2(fmaf(t[i], sc, ms));
      uint32_t p[5];
#pragma unroll
      for (int i = 0; i < 5; i++) p[i] = pack2(t[2 * i], t[2 * i + 1]);
      p[1] |= (p[0] & p[3] & p[4]) & 0x80008000u;
      float o[2][4], z[4] = {0.f, 0.f, 0.f, 0.f};
      mma16(z, ones, ones, ones, ones, p[1], p[2]);
#pragma unroll
      for (int i = 0; i < 2; i++) {
        o[i][0] = o[i][1] = o[i][2] = o[i][3] = 0.f;
        mma16(o[i], vx[2 * i].x, vx[2 * i].y, vx[2 * i].z, vx[2 * i].w, p[1], p[2]);
      }
      mma16(z, ones, ones, ones, ones, p[3], p[4]);
#pragma unroll
      for (int i = 0; i < 2; i++) mma16(o[i], vx[2 * i + 1].x, vx[2 * i + 1].y, vx[2 * i + 1].z, vx[2 * i + 1].w, p[3], p[4]);
      mma8(z, ones, ones, p[0]);
      bar_sync_after<B_V, 256>(p[1]);
      ldsm4(km[0], km[1], km[2], km[3], sb + km_off + (C_VM - C_KM) + u * 1024);
      mma8(o[0], km[0], km[1], p[0]);
      mma8(o[1], km[2], km[3], p[0]);
      const float i0 = rcp(z[0]), i1 = rcp(z[1]);
      const uint32_t oo = C_OI + u * 1024 + l * 128 + lane * 4;
      uint32_t ow[4];
#pragma unroll
      for (int i = 0; i < 2; i++) { ow[2 * i] = pack2(o[i][0] * i0, o[i][1] * i1); ow[2 * i + 1] = pack2(o[i][2] * i0, o[i][3] * i1); }
#pragma unroll
      for (int i = 0; i < 4; i++) st_async1(rb + oo + 2048 + i * 256, ow[i], rb + CB_OX);
      stsm4(sb + C_OI + u * 1024 + l * 128 + (lane >> 3) * 256 + (lane & 7) * 16, ow[0], ow[1], ow[2], ow[3]);
      bar_arrive(B_O, 256);
      }
    }
    {
      const uint32_t lane = opaque_tid() & 31, own = ((n & 1) * 16384 + j * 4096) >> 4;
      float s[16], sm[4];
#pragma unroll
      for (int i = 0; i < 16; i++) s[i] = sm[i & 3] = 0.f;
      {
        uint4 q[4];
        mbar_wait(sb + CB_Q, n & 1);
#pragma unroll
        for (int ks = 0; ks < 4; ks++) q[ks] = lds128(sb + C_Q + (ks >> 1) * 4096 + w * 1024 + (ks & 1) * 512 + lane * 16);
        mbar_wait(sb + CB_XX, n & 1);
        if (n + 1 < STEPS) mbar_wait(sb + CB_OX, n & 1);
        fence_async_smem();
        if (n + 1 < STEPS) { bar_arrive(B_T, 256); bar_sync(B_OE, 256); }
        if (w == 1) { TRV(61, 0); TR(9); }
#pragma unroll 1
        for (uint32_t hf = 0; hf < 2; hf++) {
          wg_fence();
          x_scores<0>(s, sm, q, hf ? (C_KV2 - C_KV) >> 4 : own, hf ? (C_KM2 - C_KM) >> 4 : j * 8);
          wg_commit();
          wg_wait<0>();
#pragma unroll
          for (int ks = 0; ks < 4; ks++) asm volatile("mov.b32 %0, %1; mov.b32 %2, %3;" : "+r"(q[ks].x), "+r"(q[ks].y), "+r"(q[ks].z), "+r"(q[ks].w));
        }
      }
      const float neg = -1e9f * 11.313708498984761f;
      const int lim = 8 * (w - (int)(lane & 3)) + (int)(lane >> 2);
      float t[10] = {sm[0], sm[1]};
#pragma unroll
      for (int i = 0; i < 8; i++) t[2 + i] = i > lim ? neg : s[(i >> 1) * 4 + (i & 1)];
      float mx = fmaxf(fmaxf(fmaxf(fmaxf(t[2], t[3]), fmaxf(t[4], t[5])), fmaxf(fmaxf(t[6], t[7]), fmaxf(t[8], t[9]))), fmaxf(t[0], t[1]));
      mx = fmaxf(fmaxf(mx, __shfl_xor_sync(~0u, mx, 1)), fmaxf(__shfl_xor_sync(~0u, mx, 2), __shfl_xor_sync(~0u, mx, 3)));
      const float ms = -mx * sc;
#pragma unroll
      for (int i = 0; i < 10; i++) t[i] = ex2(fmaf(t[i], sc, ms));
      uint32_t p[5];
#pragma unroll
      for (int i = 0; i < 5; i++) p[i] = pack2(t[2 * i], t[2 * i + 1]);
      float z = ((t[0] + t[1]) + (t[2] + t[3])) + ((t[4] + t[5]) + (t[6] + t[7])) + (t[8] + t[9]);
      const uint32_t row = sb + C_Q + w * 1024 + (lane >> 2) * 128 + (((lane & 3) ^ (lane >> 2)) << 4);
#pragma unroll 1
      for (uint32_t hf = 0; hf < 2; hf++) {
        float o[32];
        const uint32_t vo = hf ? (C_KV2 + 4096 - C_KV - 8192) >> 4 : own;
        wg_fence();
        wg_rs64o<0, desc_sw64(C_KV + 8192)>(o, p[1], p[1], p[2], p[2], vo);
        wg_rs64o<1, desc_sw64(C_KV + 8192 + 32)>(o, p[3], p[3], p[4], p[4], vo);
        wg_rs64o<1, mkdesc(C_VM, 128, 256, 0)>(o, p[0], p[0], 0, 0, hf ? (C_VM2 - C_VM) >> 4 : j * 8);
        wg_commit();
        if (hf) {
          if (elect()) mbar_arrive(sb + CB_M);
        } else {
          z += __shfl_xor_sync(~0u, z, 1);
          z = rcp(z + __shfl_xor_sync(~0u, z, 2));
        }
        wg_wait<0>();
#pragma unroll
        for (int qq = 0; qq < 2; qq++) {
          const float* r = o + 16 * qq;
          sts128((row ^ (qq * 64)) + hf * 4096,
                 make_uint4(pack2(r[0] * z, r[1] * z), pack2(r[4] * z, r[5] * z), pack2(r[8] * z, r[9] * z), pack2(r[12] * z, r[13] * z)));
        }
      }
      bar_arrive(B_G, 160);
      if (w == 1) TR(10);
    }
  }
  TS(6);
}

__device__ __forceinline__ void chain_aux(const Params& P, uint32_t sb) {
  const uint32_t c = chain_id(), j = c & 1, lane = threadIdx.x & 31, w = __shfl_sync(~0u, (threadIdx.x >> 5) & 3, 0);
  if (w == 0) {
    bar_sync(B_R, 64);
    const uint32_t* fg = g_fl + FL_G + near_half(XB_F, c) * 1024 + (c >> 1) * 8;
#pragma unroll 1
    for (int n = 0; n < STEPS; n++) {
      const unsigned char* blk = g_qkv + (uint32_t)((n % RING) * (N_CHAIN * 24576));
      const uint32_t t1 = clk(), kb = sb + CB_FULL + (n & 1) * 8, kv = sb + C_KV + (n & 1) * 16384;
      uint32_t t0 = t1 - 100000, x = 0;
      if (n > 0) {
        wait_until(t1, KMIN);
        do asm volatile("ld.relaxed.gpu.global.u32 %0, [%1];" : "=r"(x) : "l"(fg) : "memory"); while (x <= n && clk() - t1 < KWIN);
        if (NOBULK) x = n + 1;
        if (x > n) {
          asm volatile("fence.acquire.gpu;" ::: "memory");
          fence_async_global();
          if (elect()) { mbar_expect(kb, 8192); bulk_load(kv, blk + c * 24576, 8192, kb); }
        }
        T3(0); CNT(12, 1 + (x <= n));
        mbar_wait(sb + CB_REF, (n - 1) & 1);
        t0 = lds32(sb + C_REF);
        wait_until(t0, DLYK - 500);
      }
      if (!NOBULK) wait_flags(fg + (lane & 1) * 256, n + 1);
      fence_async_global();
      wait_until(t0, DLYK);
      if (elect()) {
        if (x <= n) { mbar_expect(kb, 8192); bulk_load(kv, blk + c * 24576, 8192, kb); }
        mbar_expect(sb + CB_VF, 8192);
        bulk_load(kv + 8192, blk + (c * 24576 + 8192), 8192, sb + CB_VF);
      }
      T3(1);
      if (!NOBULK) wait_flags(fg + 512, n + 1);
      T3(2);
      fence_async_global();
      if (n > 0) bar_sync(B_R, 64);
      if (elect()) {
        mbar_expect(sb + CB_Q, 16384);
        bulk_load(sb + C_Q, blk + (c * 24576 + 16384), 8192, sb + CB_Q);
        bulk_load(sb + C_KV2, blk + ((c ^ 1) * 24576 + j * 4096), 4096, sb + CB_Q);
        bulk_load(sb + C_KV2 + 4096, blk + ((c ^ 1) * 24576 + 8192 + j * 4096), 4096, sb + CB_Q);
      }
      T3(3);
    }
  } else {
    const uint32_t near = __ballot_sync(~0u, near_half(XB_M + min(lane, MRING - 1u) * 8, c));
    uint32_t ring = 0;
    if (w > 1) {
      const uint32_t odd = w & 1, chk = pinned(sb + C_M + odd * 2048 + m_probe(lane)), again = sb + CB_MV + 32 + odd * 8;
      const bool one = elect();
      uint32_t mph = 0;
#pragma unroll 1
      for (int n = 0; n <= STEPS; n++) {
#pragma unroll
        for (int k = 0; k < 3; k++) {
          if (n == STEPS || (k == 2 && odd)) break;
          const uint32_t b = 2 * k + odd, at = chk + (k ? k * 8192 - 2048 + odd * 2048 : 0);
          uint32_t mb = sb + CB_M + b * 8, ph = n & 1;
          int it = 1;
          while (true) {
            mbar_wait(mb, ph);
            const bool bad = __any_sync(~0u, (k ? m_max(at, at + 2048) : max(m_max(at, at ^ 8), odd ? m_max(at + 2048, (at ^ 8) + 2048) : 0)) == SENT);
            if (one && !bad) mbar_arrive(sb + CB_MV + (k ? b * 8 - 8 : 0));
            if (!bad) break;
            mb = again; ph = mph; mph ^= 1;
            if (one) {
              if (k == 0) sts32(sb + C_BAD, n + 1);
              mbar_expect(mb, b ? 4096 : 2048);
              m_fetch(sb, ring * 65536 + ((near >> ring) & 1) * 4096, b, mb);
            }
            __syncwarp();
            spin_guard(it);
          }
          TR(41 + b * 4); CNT(6 + b, it);
        }
        ring = ring + 1 == MRING ? 0 : ring + 1;
        if (!odd) {
          if (n < STEPS) { TRSYNC(); TRDUMP(n - 2); }
        } else if (n > 0) {
          unsigned char* o = g_oimg + (uint32_t)(((n - 1) & (RING - 1)) * (N_CHAIN * 8192) + j * 4096);
          bar_sync(B_G, 160);
          fence_async_smem();
          if (one) {
            bulk_store(o + c * 8192, sb + C_Q, 4096);
            bulk_store(o + (c ^ 1) * 8192, sb + C_Q + 4096, 4096);
            asm volatile("cp.async.bulk.commit_group;\ncp.async.bulk.wait_group.read 0;" ::: "memory");
            { const int n_ = n - 1; { const int n = n_; T3(4); (void)n; } }
          }
          __syncwarp();
          if (n < STEPS) bar_arrive(B_R, 64);
          if (one) {
            bulk_done_inc(g_fl + FL_O + c);
            { const int n_ = n - 1; { const int n = n_; T3(5); (void)n; } }
          }
          __syncwarp();
        }
      }
    } else {
      const uint32_t* ts = g_fl + FL_SYNC + near_half(XB_F + 1, c) * 1024 + lane * 2;
      uint32_t t0 = clk() - 100000;
#pragma unroll 1
      for (int n = 0; n < STEPS; n++) {
        const uint32_t src = ring * 65536 + ((near >> ring) & 1) * 4096;
        if (lane < 5) mbar_expect(sb + CB_M + lane * 8, lane ? 4096 : 2048);
        __syncwarp();
        if (elect()) {
#pragma unroll
          for (int b = 0; b < 5; b++) {
            wait_until(t0, P.dly[14 + b]);
            m_fetch(sb, src, b, sb + CB_M + b * 8);
            TR(40 + b * 4);
          }
        }
        __syncwarp();
        ring = ring + 1 == MRING ? 0 : ring + 1;
        uint32_t va, vb;
        const uint32_t off = timer_offset(), tag = (uint32_t)(n + 1) << 24;
        bar_sync(B_QK, 416);
        if (n + 1 == STEPS) break;
        sts32(sb + C_REF + 4, 0);
        const uint32_t c0 = clk(), stamp = c0 + off;
        st_relaxed_if(g_fl + FL_SYNC + lane * 1024 + c, tag | (stamp & 0xFFFFFF), lane < 2);
        TR(13);
        wait_until(c0, DLYS);
        int it = 0;
        do {
          asm volatile("ld.relaxed.gpu.global.v2.u32 {%0,%1}, [%2];" : "=r"(va), "=r"(vb) : "l"(ts) : "memory");
          spin_guard(it);
        } while (__any_sync(~0u, ((va ^ tag) | (vb ^ tag)) >> 24));
        const int late = __reduce_max_sync(~0u, max((int)((va - stamp) << 8), (int)((vb - stamp) << 8))) >> 8;
        t0 = c0 + min((uint32_t)late, clk() - c0);
        if (elect()) {
          sts32(sb + C_REF, t0);
          mbar_arrive(sb + CB_REF);
        }
        st_relaxed_if(g_fl + FL_TICK + lane * 1024, tag | ((t0 + off) & 0xFFFFFF), c == 0 && lane < 2);
        TR(14); CNT(11, it);
        bar_sync(B_M, 160);
      }
    }
  }
}

template <int WG>
__device__ __forceinline__ void g_math(const Params& P, uint32_t sb) {
  const int q = g_unit(WG);
  const int lane = threadIdx.x & 31, w = (threadIdx.x >> 5) & 3;
  const bool isq = q >= 64;
  uint32_t a[136];
  {
    const uint32_t stage = sb + G_W + WG * 73728;
    load_frags<34>(a, stage);
    bar_sync(B_WG0 + WG, 128);
    load_wg(P, sb, false, WG);
    cp_async_wait_all();
    fence_async_smem();
    bar_sync(B_WG0 + WG, 128);
  }
  TS(4);
  const uint32_t off0 = (q & 31) * 49152 + (q >> 5) * 8192 +
                        (isq ? (w >> 1) * 4096 + (w & 1) * 512 + lane * 16 : w * 1024 + (lane >> 2) * 64 + (((lane ^ (lane >> 3)) & 3) << 4));
#pragma unroll 1
  for (int n = 0; n < STEPS; n++) {
    float d0[32], d1[32];
    PROF0();
    if (n > 0) bar_sync(B_V + WG, 256);
#pragma unroll
    for (int ch = 0; ch < 9; ch++) {
      mbar_wait(sb + G_BAR + ch * 8, n & 1);
      if (ch == 0) { PROF(1); if ((threadIdx.x & 127) == 0) T3(5 + WG * 3); __syncwarp(); }
      if (ch == 4) { if ((threadIdx.x & 127) == 0) T3(6 + WG * 3); __syncwarp(); }
      if (ch == 8 && (WG == 0 ? n > 0 : n + 1 < STEPS)) bar_arrive(B_V + (WG ^ 1), 256);
      wg_fence();
#pragma unroll
      for (int kk = 0; kk < 4 - FASTG; kk++) {
        const int ks = ch * 4 + kk;
        const uint64_t db = desc_sw128(G_RING + ch * 8192 + kk * 32);
        const uint64_t da = desc_sw128(G_W + WG * 73728 + ks * 2048);
        if (ks == 0) { wg_rs64<0>(d0, a, db); wg_ss64<0>(d1, da, db); }
        else if (ks < 34) { wg_rs64<1>(d0, a + ks * 4, db); wg_ss64<1>(d1, da, db); }
        else { wg_ss64<1>(d0, desc_sw128(G_W2 + WG * 4096 + (ks - 34) * 2048), db); wg_ss64<1>(d1, da, db); }
      }
      wg_commit();
      if (ch > 0) { wg_wait<1>(); if (lane == 0) mbar_arrive(sb + G_BAR + 128 + (ch - 1) * 8); }
    }
    wg_wait<0>();
    if (lane == 0) mbar_arrive(sb + G_BAR + 128 + 8 * 8);
    PROF(2);
    if ((threadIdx.x & 127) == 0) T3(7 + WG * 3);
    __syncwarp();
    uint32_t tw = clk() + (WG == 0 && n >= LOCK0 ? DLYW : 0);
    unsigned char* base = g_qkv + (size_t)(n & (RING - 1)) * (N_CHAIN * 24576);
    if ((ABL & 1) && d0[0] != 1234.5f) {
    } else if (isq) {
#pragma unroll
      for (int i = 0; i < 8; i++) {
        const float *d = (i < 4 ? d0 : d1) + 4 * i, *e = (i < 4 ? d1 : d0) + 4 * i;
        wait_until(tw, 0); tw += P.dly[2 + WG];
        *(uint4*)(base + off0 + (i >> 2) * 24576 + (i & 3) * 1024) =
          make_uint4(movmat(pack2(d[0], d[1])), movmat(pack2(e[0], e[1])), movmat(pack2(d[2], d[3])), movmat(pack2(e[2], e[3])));
      }
    } else {
#pragma unroll
      for (int i = 0; i < 8; i++) {
        const float* d = (i < 4 ? d0 : d1) + 8 * (i & 2) + 2 * (i & 1);
        wait_until(tw, 0); tw += P.dly[2 + WG];
        *(uint4*)(base + off0 + (i >> 2) * 24576 + (i & 2) * 2048 + (i & 1) * 512) =
          make_uint4(pack2(d[0], d[1]), pack2(d[4], d[5]), pack2(d[8], d[9]), pack2(d[12], d[13]));
      }
    }
    bar_arrive(B_M + WG, 160);
    PROF(3);
  }
}

__device__ __forceinline__ void fill16(void* p, uint32_t v) {
  asm volatile("st.global.v4.u32 [%0], {%1,%1,%1,%1};" :: "l"(p), "r"(v) : "memory");
}
__device__ __forceinline__ void g_load(const Params& P, uint32_t sb) {
  const int lane = threadIdx.x & 31, w = __shfl_sync(~0u, (threadIdx.x >> 5) & 3, 0);
  if (w == 2) return;
  uint32_t fl = 0;
#pragma unroll 1
  for (int n = 0; n < STEPS; n++) {
    if (w == 3) {
      if (n == 0) wait_flags(g_lnflag + (lane & 1) * 8, 1);
      if (n == 1) fl = near_half(XB_F, bid()) * 1024;
      if (!NOCHAIN && n >= LOCK0) {
        const uint32_t tag = (uint32_t)(n - LOCK0 + 1) << 24;
        uint32_t v; int it = 0;
        do { asm volatile("ld.relaxed.gpu.global.u32 %0, [%1];" : "=r"(v) : "l"(g_fl + fl + FL_TICK) : "memory"); spin_guard(it); } while (v < tag);
        const uint32_t off = timer_offset(), now = clk(), t0 = now - ((v ^ tag) >> 24 ? DLYG : (now + off - v) & 0xFFFFFF);
        asm volatile("fence.acquire.gpu;" ::: "memory");
        if (lane == 0) T3(11);
        if (n >= LAG) wait_flags(g_fl + fl + FL_F + (lane & 1) * 8, n - LAG + 1);
        if (lane == 0) T3(12);
        __syncwarp();
        wait_until(t0, DLYG);
      }
      bar_sync(B_X, 128);
      continue;
    }
    if (w == 0) {
      if (n == 0) wait_flags(g_lnflag + (lane & 1) * 8, 1);
      if ((n & 7) == 1 && n < 32) wait_flags(g_lnflag + ((n >> 3) * 32 + lane) * 8, 1);
    } else {
      bar_sync(B_X, 128);
      if (lane == 0) T3(4);
    }
    fence_async_global();
    const unsigned char* src = g_lnimg + (uint32_t)((w ? (n >= LAG ? NSEG + n - LAG : 0) : min(n, NSEG - 1)) * 36864);
#pragma unroll 1
    for (int ch = 0; ch < 9; ch++) {
      const uint32_t full = sb + G_BAR + ch * 8;
      mbar_wait(full + 128, (n & 1) ^ 1);
      if (elect()) {
        mbar_expect(full, ABL & 2 ? 16 : 4096);
        bulk_load(sb + G_RING + ch * 8192 + w * 4096, src + ch * 4096, ABL & 2 ? 16 : 4096, full);
      }
    }
  }
}

__device__ __forceinline__ void g_aux(const Params& P, uint32_t sb) {
  const int lane = threadIdx.x & 31, w = (threadIdx.x >> 5) & 3;
  if (w == 1 || w == 2) {
    const int q = g_unit(w - 1);
    uint32_t* f = g_fl + FL_G + q * 8;
#pragma unroll 1
    for (int n = 0; n < STEPS; n++) {
      const uint32_t ln = opaque_tid() & 31;
      uint4* z = (uint4*)g_oacc + (uint32_t)(((n + 1) % ARING) * (16 * DM) + q * 96 + ln);
      fill16(z, 0); fill16(z + 32, 0); fill16(z + 64, 0);
      if (n + 3 >= MRING && q < 80) fill16((uint4*)g_mimg + (uint32_t)(((n + 3) % MRING) * 4096 + q * 32 + ln), SENT);
      bar_sync(B_M + (w - 1), 160);
      if (lane == 0) { T3(w * 2 - 2); fence_async_global(); flag_release(f, n + 1); T3(w * 2 - 1); }
      __syncwarp();
    }
  } else {
    const uint32_t u = (bid() - N_CHAIN) * 2 + (w & 1), r = u / 36 * 16 + (u & 3) * 4 + (lane >> 3);
    uint32_t o = r * (DM / 8) + (u % 36 >> 2) * 8 + ((lane & 7) ^ ((r >> 1) & 3));
#pragma unroll 1
    for (int k = -LAG - 1; k < STEPS; k++) {
      if (k < NSEG - 1) bar_sync(B_X, 128);
      if (k < LAG || u >= 72) continue;
      if (k >= NSEG - 1) {
        const uint32_t* f = g_fl + near_half(XB_F, bid()) * 1024;
        if (k + 1 == STEPS) wait_flags(f + FL_F + (lane & 1) * 8, NSEG + 1);
        wait_flags(f + FL_OCNT + (max(k, NSEG) % OCRING) * 8, N_O * 3 * (max(k, NSEG) / OCRING + 1));
      }
      const float4* a = (const float4*)g_oacc + ((k % ARING) * (16 * DM) + 8 * DM + u * 64 + lane * 2);
      const float4 p = __ldcg(a), v = __ldcg(a + 1);
      const uint4 x = __ldcg((const uint4*)P.out + o);
      ((uint4*)P.out)[o] = make_uint4(badd2(x.x, pack2(p.x, p.y)), badd2(x.y, pack2(p.z, p.w)), badd2(x.z, pack2(v.x, v.y)), badd2(x.w, pack2(v.z, v.w)));
      o += 4 * DM;
    }
    TS(7);
  }
}

template <int WG>
__device__ __forceinline__ void o_math(const Params& P, uint32_t sb) {
  const int ksl = (bid() - N_CHAIN - N_G) / 3;
  const int nc = ksl < 4 ? 11 : 10;
  const int lane = threadIdx.x & 31, w = (threadIdx.x >> 5) & 3, g = lane >> 2, tq = lane & 3;
  uint32_t a[96];
  {
    load_frags<24>(a, sb + WG * 49152);
    bar_sync(B_INIT, 416);
    load_wg(P, sb, false, WG);
    cp_async_wait_all();
    fence_async_smem();
    bar_sync(B_WG0 + WG, 128);
  }
  TS(4);
  const uint32_t st0 = sb + O_ST + tq * 512 + ((w * 16 + g) ^ (tq * 8)) * 4;
#pragma unroll 1
  for (int n = 0; n < STEPS; n++) {
    float d[32];
    PROF0();
    if (WG > 0 || n > 0) bar_sync(B_V + WG, 256);
#pragma unroll
    for (int gr = 0; gr < 5; gr++) {
      mbar_wait(sb + O_BAR + gr * 8, n & 1);
      if (gr == 0) { PROF(1); if ((threadIdx.x & 127) == 0) T3(13 + WG); __syncwarp(); }
      if (gr == (WG == 0 ? OTURN : 4) && (WG < 2 || n + 1 < STEPS)) bar_arrive(B_V + (WG + 1) % 3, 256);
      wg_fence();
#pragma unroll
      for (int ks = gr * 8; ks < gr * 8 + 8 - 2 * FASTG; ks++) {
        const uint64_t db = desc_sw128(O_RING + (ks >> 2) * 8192 + (ks & 3) * 32);
        if (ks == 0) wg_rs64<0>(d, a, db);
        else if (!(ks % 5 & 1)) wg_rs64<1>(d, a + (ks / 5 * 3 + ks % 5 / 2) * 4, db);
        else wg_ss64<1>(d, desc_sw128(O_W + WG * 40960 + (ks / 5 * 2 + ks % 5 / 2) * 2048), db);
      }
      if (gr == 4 && nc == 11) {
#pragma unroll
        for (int ks = 40; ks < 44; ks++)
          wg_ss64<1>(d, desc_sw128(O_W + WG * 40960 + (ks - 24) * 2048), desc_sw128(O_RING + 10 * 8192 + (ks & 3) * 32));
      }
      wg_commit();
      if (gr > 0) { wg_wait<1>(); if (lane == 0) mbar_arrive(sb + O_BAR + 128 + (gr - 1) * 8); }
    }
    wg_wait<0>();
    if (lane == 0) mbar_arrive(sb + O_BAR + 128 + 4 * 8);
    if ((threadIdx.x & 127) == 0) T3(WG == 0 ? 1 : WG == 1 ? 8 : 12);
    __syncwarp();
    PROF(2);
#pragma unroll
    for (int sl = 0; sl < 2; sl++) {
      mbar_wait(sb + OB_ST + WG * 16 + sl * 8, (n & 1) ^ (WG == 0));
#pragma unroll
      for (int nb = sl * 4; nb < sl * 4 + 4; nb++) {
        sts32(st0 + nb * 2048, __float_as_uint(d[nb * 4]));
        sts32(st0 + nb * 2048 + 256, __float_as_uint(d[nb * 4 + 1]));
        sts32((st0 ^ 32) + nb * 2048, __float_as_uint(d[nb * 4 + 2]));
        sts32((st0 ^ 32) + nb * 2048 + 256, __float_as_uint(d[nb * 4 + 3]));
      }
      fence_async_smem();
      bar_arrive((sl ? B_G : B_M) + WG, 160);
    }
    PROF(3);
  }
}

__device__ __forceinline__ void o_aux(const Params& P, uint32_t sb) {
  const int i = bid() - N_CHAIN - N_G, ksl = i / 3;
  const int c0 = ksl * 11 - max(ksl - 4, 0), nc = ksl < 4 ? 11 : 10;
  const int lane = threadIdx.x & 31, w = __shfl_sync(~0u, (threadIdx.x >> 5) & 3, 0);
  if (w == 0) {
    bar_sync(B_INIT, 416);
    const uint32_t* f = g_fl + FL_O + near_half(XB_F + 1, bid()) * 1024 + min((c0 & ~1) + lane, (c0 + nc - 1) | 1);
#pragma unroll 1
    for (int n = 0; n < STEPS; n++) {
      const unsigned char* src = g_oimg + (uint32_t)(((n % RING) * N_CHAIN + c0) * 8192);
      if (!NOCHAIN) wait_flags(f, n + 1);
      fence_async_global();
      if (lane == 0) T3(0);
#pragma unroll
      for (int gr = 0; gr < 5; gr++) {
        const uint32_t full = sb + O_BAR + gr * 8, bytes = ABL & 4 ? 16 : (gr < 4 ? 2 : nc - 8) * 8192;
        mbar_wait(full + 128, (n & 1) ^ 1);
        if (elect()) {
          mbar_expect(full, bytes);
          bulk_load(sb + O_RING + gr * 16384, src + gr * 16384, bytes, full);
        }
      }
    }
  } else {
#pragma unroll 1
    for (int n = 0; n < STEPS; n++) {
      float* dst = g_oacc + (uint32_t)((n % ARING) * (64 * DM) + ((i % 3) * 3 + (w - 1 + ksl) % 3) * 1024);
      const bool early = w == 3 && n < NSEG;
      bar_sync(B_M + (w - 1), 160);
      if (lane == 0) {
        T3(w * 2);
        if (n < NSEG && !(ABL & 8)) { bulk_reduce(dst, sb + O_ST, 4096); bulk_reduce(dst + 16 * DM, sb + O_ST + 4096, 4096); }
        asm volatile("cp.async.bulk.commit_group;" ::: "memory");
        if (early) {
          asm volatile("cp.async.bulk.wait_group.read 0;" ::: "memory");
          mbar_arrive(sb + OB_ST);
          T3(8 + w);
          bulk_done_inc(g_fl + FL_OCNT + (n % OCRING) * 8);
          T3(w * 2 + 1);
        }
      }
      __syncwarp();
      bar_sync(B_G + (w - 1), 160);
      if (lane == 0) {
        if (n >= LAG && !(ABL & 8)) { bulk_reduce(dst + 32 * DM, sb + O_ST + 8192, 4096); bulk_reduce(dst + 48 * DM, sb + O_ST + 12288, 4096); }
        asm volatile("cp.async.bulk.commit_group;\ncp.async.bulk.wait_group.read 1;" ::: "memory");
        if (!early) mbar_arrive(sb + OB_ST + (w % 3) * 16);
        asm volatile("cp.async.bulk.wait_group.read 0;" ::: "memory");
        mbar_arrive(sb + OB_ST + (w % 3) * 16 + 8);
        if (!early) {
          T3(8 + w);
          bulk_done_inc(g_fl + FL_OCNT + (n % OCRING) * 8);
          T3(w * 2 + 1);
        }
      }
      __syncwarp();
    }
  }
}

__device__ __forceinline__ void f_role(const Params& P, uint32_t sb) {
  const int lane = threadIdx.x & 31, w = __shfl_sync(~0u, threadIdx.x >> 5, 0), r0 = (bid() - N_CHAIN - N_G - N_O) * 16;
  if (threadIdx.x < 128) wait_flag(g_lnflag + threadIdx.x * 8, 2);
  __syncthreads();
  if (w == 8) {
    const uint32_t* fo = g_fl + FL_OCNT + near_half(XB_F, bid()) * 1024;
    fence_async_global();
#pragma unroll 1
    for (int n = 0; n < NSEG; n++) {
      if (n > 0) bar_sync(2, 288);
      if (elect()) {
        mbar_expect(sb + F_BAR, 36864);
        bulk_load(sb + F_XY, g_x1 + (size_t)(n * 32 + r0) * DM, 18432, sb + F_BAR);
        bulk_load(sb + F_XY + 18432, g_y + (size_t)(n * 32 + r0) * DM, 18432, sb + F_BAR);
        mbar_expect(sb + F_BAR + 8, 36864);
        T3(1);
      }
      wait_flags(fo + (n % OCRING) * 8, NOCHAIN == 5 ? 0 : N_O * 3 * (n / OCRING + 1));
      fence_async_global();
      if (elect()) { bulk_load(sb + F_A, g_oacc + (uint32_t)((n % ARING) * (64 * DM) + r0 * DM), 36864, sb + F_BAR + 8); T3(0); }
    }
  } else if (w == 9) {
#pragma unroll 1
    for (int n = 0; n < NSEG; n++) {
      const uint32_t st = sb + (n & 1) * 36864;
      unsigned char* p = g_lnimg + (uint32_t)((NSEG + n) * 36864 + r0 * 128);
      bar_sync(1, 288);
      if (elect()) {
        T3(2);
#pragma unroll
        for (int i = 0; i < 9; i++) bulk_store(p + i * 4096, st + F_L + i * 2048, 2048);
        asm volatile("cp.async.bulk.commit_group;" ::: "memory");
        bulk_done_inc(g_fl + FL_F + (bid() & 1) * 8);
        T3(3);
        bulk_store(P.out + (size_t)(n * 32 + r0) * DM, st + F_X, 18432);
        asm volatile("cp.async.bulk.commit_group;\ncp.async.bulk.wait_group.read 0;" ::: "memory");
        if (n + 1 == NSEG) bulk_done_inc(g_fl + FL_F + (bid() & 1) * 8);
      }
      __syncwarp();
    }
  } else if (w < 8) {
    const uint32_t row = sb + w * 1152 + lane * 4, acc = sb + F_A + w * 256 + (lane ^ ((w & 6) * 2)) * 8;
    const uint32_t ln = sb + F_L + w * 128 + (((lane >> 2) ^ w) << 4) + (lane & 3) * 4;
#pragma unroll 1
    for (int n = 0; n < NSEG; n++) {
      const uint32_t st = (n & 1) * 36864;
      uint32_t x[18], y[18], l[18];
      mbar_wait(sb + F_BAR, n & 1);
#pragma unroll
      for (int i = 0; i < 18; i++) { x[i] = lds32(row + F_XY + i / 9 * 9216 + i % 9 * 128); y[i] = lds32(row + F_XY + 18432 + i / 9 * 9216 + i % 9 * 128); }
      mbar_wait(sb + F_BAR + 8, n & 1);
      if (threadIdx.x == 0) T3(4);
      __syncwarp();
      uint2 a[18];
#pragma unroll
      for (int i = 0; i < 18; i++) a[i] = lds64(acc + i / 9 * 2048 + i % 9 * 4096);
#pragma unroll
      for (int i = 0; i < 18; i++) x[i] = badd2(x[i], pack2(__uint_as_float(a[i].x), __uint_as_float(a[i].y)));
      if (n + 1 < NSEG) bar_arrive(2, 288);
      layernorm9<2>(x, l);
#pragma unroll
      for (int i = 0; i < 18; i++) { x[i] = badd2(x[i], bmul2(l[i], y[i])); sts32(row + st + F_X + i / 9 * 9216 + i % 9 * 128, x[i]); }
      layernorm9<2>(x, l);
#pragma unroll
      for (int i = 0; i < 18; i++) sts32(ln + st + i / 9 * 1024 + i % 9 * 2048, l[i]);
      fence_async_smem();
      bar_sync(1, 288);
    }
  }
}

constexpr uint32_t P_CH = 147456, P_CHSZ = 12800, P_H = 4352, P_Y = P_CH;
static_assert(P_CH + 5 * P_CHSZ + 8192 <= SMEM_BYTES, "prologue smem");

template <int N>
__device__ __forceinline__ void conv_fold(float (*acc)[4], bool hi, uint32_t mine, uint32_t theirs, int bar, int cnt) {
#pragma unroll
  for (int i = 0; i < N / 2; i++) {
    uint4 v;
    v.x = __float_as_uint(hi ? acc[i][0] : acc[i + N / 2][0]); v.y = __float_as_uint(hi ? acc[i][1] : acc[i + N / 2][1]);
    v.z = __float_as_uint(hi ? acc[i][2] : acc[i + N / 2][2]); v.w = __float_as_uint(hi ? acc[i][3] : acc[i + N / 2][3]);
    sts128(mine + i * 512, v);
  }
  bar_sync(bar, cnt);
#pragma unroll
  for (int i = 0; i < N / 2; i++) {
    const uint4 v = lds128(theirs + i * 512);
    acc[i][0] = (hi ? acc[i + N / 2][0] : acc[i][0]) + __uint_as_float(v.x); acc[i][1] = (hi ? acc[i + N / 2][1] : acc[i][1]) + __uint_as_float(v.y);
    acc[i][2] = (hi ? acc[i + N / 2][2] : acc[i][2]) + __uint_as_float(v.z); acc[i][3] = (hi ? acc[i + N / 2][3] : acc[i][3]) + __uint_as_float(v.w);
  }
}
template <int N>
__device__ __forceinline__ void conv_store(const float (*acc)[4], int tile0, uint32_t su, int d, uint32_t dd) {
  const int lane = threadIdx.x & 31, g = lane >> 2, tq = lane & 3;
#pragma unroll
  for (int i = 0; i < N; i++) {
    const uint32_t ad = su + (8 + (tile0 + i) * 8 + g) * 32 + tq * 4, sw = (g & 4) << 2;
    const uint32_t lo = badd2(movmat(pack2(acc[i][0], acc[i][1])), bmul2(lds32(ad + sw), dd));
    const uint32_t hi = badd2(movmat(pack2(acc[i][2], acc[i][3])), bmul2(lds32(ad + (sw ^ 16)), dd));
    ((uint2*)(g_yT + (size_t)d * SEQ))[(tile0 + i) * 32 + lane] = make_uint2(lo, hi);
  }
}

__device__ __forceinline__ void store_xy(uint32_t stage, int tile) {
  asm volatile("cp.async.bulk.global.shared::cta.bulk_group [%0], [%1], 18432;" :: "l"(g_y + (size_t)tile * 16 * DM), "r"(stage) : "memory");
  asm volatile("cp.async.bulk.global.shared::cta.bulk_group [%0], [%1], 18432;" :: "l"(g_x1 + (size_t)tile * 16 * DM), "r"(stage + 18432) : "memory");
  asm volatile("cp.async.bulk.commit_group;" ::: "memory");
}

__device__ __forceinline__ void prologue(const Params& P, uint32_t sb) {
  const int b = bid(), tid = threadIdx.x, lane = tid & 31, warp = tid >> 5, t0 = b * 16;
  const int chb = b, nch = chb < DM - 4 * N_CTA ? 5 : 4;
  if (tid < 288) {
    if (b < 128) {
      const int c = (tid >> 1) * 4, tt = t0 + (tid & 1) * 8;
      uint2 kr[11], vr[8];
#pragma unroll
      for (int i = 0; i < 11; i++) { const int t = tt + i - 3; kr[i] = t >= 0 ? __ldg((const uint2*)(P.K + (size_t)t * DM + c)) : make_uint2(0, 0); }
#pragma unroll
      for (int i = 0; i < 8; i++) vr[i] = __ldg((const uint2*)(P.V + (size_t)(tt + i) * DM + c));
#pragma unroll
      for (int e = 0; e < 2; e++) {
        const uint4 sh = __ldg((const uint4*)(P.shift + c * 4) + e);
        const uint32_t s0 = __byte_perm(sh.x, sh.z, 0x5410), s1 = __byte_perm(sh.x, sh.z, 0x7632);
        const uint32_t s2 = __byte_perm(sh.y, sh.w, 0x5410), s3 = __byte_perm(sh.y, sh.w, 0x7632);
        uint32_t v[8];
#pragma unroll
        for (int i = 0; i < 8; i++) {
          const uint32_t k3 = e ? kr[i].y : kr[i].x, k2 = e ? kr[i + 1].y : kr[i + 1].x, k1 = e ? kr[i + 2].y : kr[i + 2].x, k0 = e ? kr[i + 3].y : kr[i + 3].x;
          v[i] = bmul2(badd2(badd2(badd2(bmul2(k3, s3), bmul2(k2, s2)), bmul2(k1, s1)), bmul2(k0, s0)), e ? vr[i].y : vr[i].x);
        }
        *(uint4*)(g_kvT + (size_t)(c + 2 * e) * SEQ + tt) =
          make_uint4(__byte_perm(v[0], v[1], 0x5410), __byte_perm(v[2], v[3], 0x5410), __byte_perm(v[4], v[5], 0x5410), __byte_perm(v[6], v[7], 0x5410));
        *(uint4*)(g_kvT + (size_t)(c + 2 * e + 1) * SEQ + tt) =
          make_uint4(__byte_perm(v[0], v[1], 0x7632), __byte_perm(v[2], v[3], 0x7632), __byte_perm(v[4], v[5], 0x7632), __byte_perm(v[6], v[7], 0x7632));
      }
    }
  } else if (tid < 384) {
    const int t = tid - 288;
    for (int i = t; i < 32 * nch; i += 96) asm volatile("prefetch.global.L2 [%0];" :: "l"(P.Hk + (size_t)(chb + (i >> 5) * N_CTA) * SEQ + (i & 31) * 64));
    for (int i = b * 96 + t; i < 32 * DM; i += N_CTA * 96) ((uint4*)g_oacc)[i] = make_uint4(0, 0, 0, 0);
    if (b * 96 + t < 128 * 8) g_lnflag[b * 96 + t] = 0;
    if (t == 95) sts32(sb + S_GEN, ld_acquire(g_gbar));
  }
  if (warp < 12) {
    bar_sync(6, 384);
    if (tid == 128) TS(14);
    if (tid == 0) grid_arrive(0);
    if (tid == 0) TS(1);
  }
  if (warp < 12) {
    const bool quad = warp >= 8;
    const int ch = quad ? 4 : warp >> 1, sub = quad ? warp - 8 : warp & 1, nthr = quad ? 128 : 64, d = chb + ch * N_CTA;
    const uint32_t su = sb + P_CH + ch * P_CHSZ;
    if (ch < nch) {
      const uint32_t* hs = (const uint32_t*)(P.Hk + (size_t)d * SEQ);
#pragma unroll 4
      for (int q = sub * 32 + lane; q < 256; q += nthr) {
        const uint4 c = __ldg((const uint4*)hs + q);
        const uint32_t prev = q ? __ldg(hs + 4 * q - 1) : 0u;
        sts128(su + P_H + 32 + q * 16, make_uint4(__byte_perm(c.x, prev, 0x7610), __byte_perm(c.y, c.x, 0x7610), __byte_perm(c.z, c.y, 0x7610), __byte_perm(c.w, c.z, 0x7610)));
        sts128(su + P_H + 4224 + q * 16, make_uint4(__byte_perm(c.x, 0, 0x1032), __byte_perm(c.y, 0, 0x1032), __byte_perm(c.z, 0, 0x1032), __byte_perm(c.w, 0, 0x1032)));
      }
      if (sub == 1 && lane == 0) sts32(su + P_CHSZ - 16, __bfloat16_as_ushort(P.Dk[d]) * 0x10001u);
      if (sub == 0 && lane < 20) sts128(su + (lane < 16 ? lane * 16 : P_H + (lane & 2) * 2096 + (lane & 1) * 16), make_uint4(0, 0, 0, 0));
    }
    if (tid == 0) grid_wait(0, lds32(sb + S_GEN));
    bar_sync(6, 384);
    if (ch < nch) {
#pragma unroll 4
      for (int q = sub * 32 + lane; q < 256; q += nthr) {
        const int row = (q >> 1) + 8;
        sts128(su + row * 32 + (((q & 1) ^ ((row >> 2) & 1)) << 4), __ldcg((const uint4*)(g_kvT + (size_t)d * SEQ) + q));
      }
    }
    bar_arrive(8, 416);
    if (ch < nch) {
      bar_sync(1 + ch, nthr);
      if (tid == 0) TS(11);
      const int g = lane >> 2, tq = lane & 3;
      const uint32_t sh = su + P_H + (g & 1) * 4192 + (8 + (g >> 1) - tq) * 4;
      float acc[16][4];
#pragma unroll
      for (int i = 0; i < 16; i++) { acc[i][0] = acc[i][1] = acc[i][2] = acc[i][3] = 0.f; }
      const int nres = quad ? 2 : 4;
#pragma unroll 1
      for (int res = sub * nres; res < sub * nres + nres; res++) {
        uint32_t bf[16][2];
        const int row = 8 - res + ((lane >> 4) << 3) + (lane & 7);
        const uint32_t ad = su + row * 32 + ((((lane >> 3) & 1) ^ ((row >> 2) & 1)) << 4);
#pragma unroll
        for (int f = 0; f < 16; f += 2) ldsm4(bf[f][0], bf[f][1], bf[f + 1][0], bf[f + 1][1], ad + f * 256);
#pragma unroll
        for (int jj = 0; jj < 16; jj++) {
          const uint32_t ah = sh + (8 * jj + res) * 32;
          const uint32_t r0 = lds32(ah), r1 = lds32(ah + 16), rm = lds32(ah - 16);
#pragma unroll
          for (int i = jj; i < 16; i++) mma16(acc[i], r0, r1, rm, r0, bf[i - jj][0], bf[i - jj][1]);
        }
      }
      bar_sync(1 + ch, nthr);
      if (tid == 0) TS(12);
      const uint32_t xb = su + P_H + lane * 16, dd = lds32(su + P_CHSZ - 16);
      if (quad) bar_sync(1 + ch, nthr);
      conv_fold<16>(acc, sub & 1, xb + sub * 4096, xb + (sub ^ 1) * 4096, 1 + ch, nthr);
      if (quad) {
        bar_sync(1 + ch, nthr);
        conv_fold<8>(acc, sub & 2, xb + sub * 4096, xb + (sub ^ 2) * 4096, 1 + ch, nthr);
        conv_store<4>(acc, (sub & 1) * 8 + (sub & 2) * 2, su, d, dd);
      } else {
        conv_store<8>(acc, sub * 8, su, d, dd);
      }
    }
    bar_sync(9, 512);
    if (tid == 0) grid_arrive(1);
  } else {
    for (int i = b; i < 194 + MRING * 5; i += N_CTA) {
      const int n = (i - 194) / 5, r = (i - 194) % 5, blk = i < 192 ? i / 6 * 8 + i % 6 : i < 194 ? XB_F + i - 192 : XB_M + n * 8 + r;
      const uint32_t fill = i < 194 ? 0u : SENT;
#pragma unroll
      for (int k = 0; k < 2; k++) {
        const int q = (tid & 127) + k * 128;
        uint4 v = make_uint4(fill, fill, fill, fill);
        if (i >= 194 && (n == 0 || (n <= LAG && ((q ^ (q >> 3)) & 1))) && (r > 0 || k == 0)) {
          const bf16* m = P.mem0 + (max(r * 8 - 4, 0) + (q >> 5)) * 16 + ((q >> 1) & 1) * 8 + ((q >> 2) & 7);
          v.x = pack2(__bfloat162float(m[0]), __bfloat162float(m[DM])); v.y = pack2(__bfloat162float(m[2 * DM]), __bfloat162float(m[3 * DM]));
          v.z = pack2(__bfloat162float(m[4 * DM]), __bfloat162float(m[5 * DM])); v.w = pack2(__bfloat162float(m[6 * DM]), __bfloat162float(m[7 * DM]));
        }
        g_xb[blk * 512 + q] = v;
        g_xb[blk * 512 + 256 + q] = v;
      }
    }
    if (tid < 388) g_xb[XB_REF * 512 + (tid & 2) * 128 + (b & ~1) + (tid & 1)] = make_uint4(0, 0, 0, 0);
    else if (tid < 392 && b < N_GRP) g_xb[(b * 8 + 7) * 512 + (tid & 2) * 128 + (tid & 1)] = make_uint4(0, 0, 0, 0);
    bar_sync(7, 128);
    TS(8);
    if (warp == 12) {
      bar_sync(8, 416);
      if (lane == 16 && b < 128) asm volatile("cp.async.bulk.prefetch.L2.global [%0], 18432;" :: "l"(P.X + (size_t)t0 * DM) : "memory");
      if (lane < 16 && b < 128) {
        const bf16* w = (lane & 12) == 0 ? P.Wk : (lane & 12) == 4 ? P.Wq : (lane & 12) == 8 ? P.Wv : P.Wo;
        asm volatile("cp.async.bulk.prefetch.L2.global [%0], 9216;" :: "l"(w + (size_t)(b * 4 + (lane & 3)) * 4608) : "memory");
      }
      wait_until(clk(), b >= N_CHAIN && b < N_CHAIN + N_G ? S1G : S1DLY);
    } else if (lane == 0) {
      if (warp == 13 || (warp == 14 && b < N_GRP)) {
        uint32_t* p = (uint32_t*)(g_xb + (warp == 13 ? XB_REF * 512 + b : (b * 8 + 7) * 512));
        int votes = 0;
        for (int rep = 0; rep < 24 && abs(votes) < 7; rep++) {
          uint32_t v0, v1, c0, c1;
          asm volatile("atom.relaxed.gpu.global.add.u32 %0, [%4], 0;\n atom.relaxed.gpu.global.add.u32 %1, [%5], 0;\n"
                       "{.reg .pred p; setp.eq.u32 p, %0, 0x7ffffff3; @p trap; mov.u32 %2, %%clock; setp.eq.u32 p, %1, 0x7ffffff3; @p trap; mov.u32 %3, %%clock;}"
                       : "=&r"(v0), "=&r"(v1), "=&r"(c0), "=&r"(c1) : "l"(p + (rep & 1) * 1024), "l"(p + ((rep & 1) ^ 1) * 1024) : "memory");
          votes += ((c1 - c0 > 80u) == (rep & 1)) ? 1 : -1;
        }
        if (warp == 13) g_side[b] = votes > 0; else g_near[b] = votes > 0;
      }
    }
    __syncwarp();
    bar_sync(7, 128);
    bar_arrive(9, 512);
    TS(9);
    const int nwg = b < N_CHAIN + N_G ? 2 : b < N_CTA - N_F ? 3 : 0;
    for (int k = 0; k < nwg; k++) load_wg(P, sb, true, k);
    TS(10);
  }
  if (tid == 0) TS(2);
  if (b < N_CHAIN || b >= N_CHAIN + N_G) {
    const bool isf = b >= N_CTA - N_F;
    const int first = b < N_CHAIN ? b + 2 : isf ? b - (N_CTA - N_F) : b - N_G + 2, last = isf ? 128 : 120;
    auto next = [&](int tile) { return b < N_CHAIN ? 128 : !isf ? tile + N_O : tile < 2 ? tile + 120 : tile + 2; };
    uint32_t st = sb + P_Y;
#pragma unroll 1
    for (int tile = first; tile < last; tile = next(tile), st = 2 * (sb + P_Y) + 36864 - st) {
      uint32_t x[9], l[9];
      const int tok = tile * 16 + warp;
#pragma unroll
      for (int i = 0; i < 9; i++) x[i] = __ldg((const uint32_t*)(P.X + (size_t)tok * DM) + i * 32 + lane);
      layernorm9<1>(x, l);
      if (tile == first) { if (tid == 0) grid_wait(1, lds32(sb + S_GEN)); }
      else if (tid == 511) asm volatile("cp.async.bulk.wait_group.read 1;" ::: "memory");
      __syncthreads();
      if (tid == 0) TS(13);
      if (tid < 288) {
        uint4 y[4];
#pragma unroll
        for (int e = 0; e < 4; e++) y[e] = __ldcg((const uint4*)(g_yT + (size_t)((tid >> 1) * 4 + e) * SEQ + tile * 16) + (tid & 1));
#pragma unroll
        for (int i = 0; i < 4; i++) {
          const uint32_t w0 = ((const uint32_t*)&y[0])[i], w1 = ((const uint32_t*)&y[1])[i], w2 = ((const uint32_t*)&y[2])[i], w3 = ((const uint32_t*)&y[3])[i];
          const uint32_t ad = st + ((tid & 1) * 4 + (i >> 1) * 2 + (i & 1) * 8) * 1152 + (tid >> 1) * 8;
          sts64(ad, __byte_perm(w0, w1, 0x5410), __byte_perm(w2, w3, 0x5410));
          sts64(ad + 1152, __byte_perm(w0, w1, 0x7632), __byte_perm(w2, w3, 0x7632));
        }
      }
      __syncthreads();
#pragma unroll
      for (int i = 0; i < 9; i++) {
        x[i] = badd2(x[i], bmul2(l[i], lds32(st + warp * 1152 + i * 128 + lane * 4)));
        sts32(st + 18432 + warp * 1152 + i * 128 + lane * 4, x[i]);
      }
      layernorm9<1>(x, l);
      store_ln_row(0, tok, l);
      fence_async_smem();
      __syncthreads();
      if (b >= N_CHAIN && tid == 511) { if (tile < 2) st_release(g_lnflag + tile * 8, 1); store_xy(st, tile); }
    }
    if (b >= N_CHAIN && tid == 511) {
      asm volatile("cp.async.bulk.wait_group 0;\nfence.acq_rel.gpu;" ::: "memory");
      for (int tile = first; tile < last; tile = next(tile)) st_relaxed_if(g_lnflag + tile * 8, 2, true);
    }
    if (tid == 0) TS(15);
  }
  cp_async_wait_all();
  __syncthreads();
}

__device__ __forceinline__ void publish_prologue(uint32_t sb) {
  if (threadIdx.x < 416) return;
  if (threadIdx.x == 511) {
    st_release(g_lnflag + (bid() + 2) * 8, 1);
    store_xy(sb + P_Y, bid() + 2);
    asm volatile("cp.async.bulk.wait_group.read 0;" ::: "memory");
  }
  __syncwarp();
  if (threadIdx.x >= 480) bar_arrive(B_R, 64);
  bar_sync(B_INIT, 352);
  if (threadIdx.x == 511) asm volatile("cp.async.bulk.wait_group 0;" ::: "memory");
  if (threadIdx.x == 511) st_release(g_lnflag + (bid() + 2) * 8, 2);
  __syncwarp();
}

__global__ void __cluster_dims__(2, 1, 1) __launch_bounds__(512, 1) k_main(const Params P) {
  extern __shared__ __align__(1024) unsigned char smem[];
  const uint32_t sb = (uint32_t)__cvta_generic_to_shared(smem);
  const int b = bid(), wg = threadIdx.x >> 7;
  TS(0);
  prologue(P, sb);
  TS(3);
  if (threadIdx.x == 0) {
    if ((sb & 0xFFFFFF) != SBASE) __trap();
    if (b < N_CHAIN) {
      mbar_init(sb + CB_FULL, 1); mbar_init(sb + CB_FULL + 8, 1);
      mbar_init(sb + CB_REF, 1);
      mbar_init(sb + CB_SX, 1); mbar_init(sb + CB_OX, 1); mbar_init(sb + CB_XX, 1); mbar_init(sb + CB_Q, 1); mbar_init(sb + CB_VF, 1); mbar_init(sb + CB_VF + 8, 1);
      sts32(sb + C_BAD, 0);
      for (int i = 0; i < 11; i++) mbar_init(sb + CB_M + i * 8, i == 0 ? 5 : i == 5 ? 2 : 1);
    } else if (b < N_CHAIN + N_G) {
      for (int i = 0; i < 9; i++) { mbar_init(sb + G_BAR + i * 8, 2); mbar_init(sb + G_BAR + 128 + i * 8, 8); }
    } else if (b < N_CHAIN + N_G + N_O) {
      for (int i = 0; i < 5; i++) { mbar_init(sb + O_BAR + i * 8, 1); mbar_init(sb + O_BAR + 128 + i * 8, 12); }
      for (int i = 0; i < 6; i++) mbar_init(sb + OB_ST + i * 8, 1);
    } else {
      mbar_init(sb + F_BAR, 1); mbar_init(sb + F_BAR + 8, 1);
    }
    asm volatile("fence.mbarrier_init.release.cluster;" ::: "memory");
  }
  fence_async_smem();
  __syncthreads();
  cluster_sync();
  if (NOCHAIN && b < N_CHAIN) {
    if (threadIdx.x == 511) { store_xy(sb + P_Y, b + 2); asm volatile("cp.async.bulk.wait_group 0;" ::: "memory"); st_release(g_lnflag + (b + 2) * 8, 2); }
  } else if ((NOCHAIN == 2 && b >= N_CHAIN + N_G) || (NOCHAIN >= 3 && NOCHAIN < 6 && b < N_CHAIN + N_G) || ((NOCHAIN == 4 || NOCHAIN == 6) && b >= N_CTA - N_F) || (NOCHAIN == 5 && b < N_CTA - N_F)) {
  } else if (b < N_CHAIN) {
    if (wg < 2) { reg_inc<192>(); chain_proj(P, sb); }
    else if (wg == 2) { reg_dec<ATTR>(); chain_attn(P, sb); }
    else { reg_dec<128 - ATTR>(); publish_prologue(sb); chain_aux(P, sb); }
  } else if (NOBULK) {
    {
      if (wg == 0) {
        float d[4] = {0.f, 0.f, 0.f, 0.f};
        for (int n = 0; n < STEPS - 1; n++) {
          const uint32_t* f = g_fl + FL_TICK;
          uint32_t x;
          do { for (int k = 0; k < 16; k++) mma16(d, 0, 0, 0, 0, 0, 0); asm volatile("ld.relaxed.gpu.global.u32 %0, [%1];" : "=r"(x) : "l"(f) : "memory"); } while ((x >> 24) <= n);
          const int q = (b - N_CHAIN) * 4 + (threadIdx.x >> 5);
          if (n + 5 >= MRING && q < 80) fill16((uint4*)g_mimg + (uint32_t)(((n + 5) % MRING) * 4096 + q * 32 + (threadIdx.x & 31)), SENT);
        }
        if (d[0] == 1.f) P.out[0] = __float2bfloat16(0.f);
      }
    }
  } else if (b < N_CHAIN + N_G) {
    if (wg == 0) { reg_inc<232>(); g_math<0>(P, sb); PROF_DUMP(); }
    else if (wg == 1) { reg_inc<232>(); g_math<1>(P, sb); PROF_DUMP(); }
    else if (wg == 2) { reg_dec<24>(); g_aux(P, sb); }
    else { reg_dec<24>(); g_load(P, sb); }
  } else if (b < N_CHAIN + N_G + N_O) {
    if (wg == 0) { reg_inc<160>(); o_math<0>(P, sb); PROF_DUMP(); }
    else if (wg == 1) { reg_inc<160>(); o_math<1>(P, sb); PROF_DUMP(); }
    else if (wg == 2) { reg_inc<160>(); o_math<2>(P, sb); PROF_DUMP(); }
    else { reg_dec<32>(); o_aux(P, sb); }
  } else {

    f_role(P, sb);
  }
}

}

extern "C" void kernel_launch(void* const* d_in, const int* in_sizes, int n_in, void* d_out, int out_size) {
  Params P;
  P.X = (const bf16*)d_in[0]; P.K = (const bf16*)d_in[1]; P.V = (const bf16*)d_in[2];
  P.shift = (const bf16*)d_in[3]; P.Hk = (const bf16*)d_in[4]; P.Dk = (const bf16*)d_in[5];
  P.mem0 = (const bf16*)d_in[7];
  P.Wq = (const bf16*)d_in[8]; P.Wk = (const bf16*)d_in[9]; P.Wv = (const bf16*)d_in[10]; P.Wo = (const bf16*)d_in[11];
  P.out = (bf16*)d_out;
  for (int i = 0; i < 20; i++) P.dly[i] = h_dly[i];
  cudaFuncSetAttribute(k_main, cudaFuncAttributeMaxDynamicSharedMemorySize, SMEM_BYTES);
  k_main<<<N_CTA, 512, SMEM_BYTES>>>(P);
}
```

```cpp
#include <cuda.h>
#include <cuda_runtime.h>
#include <cuda_bf16.h>
#include <stdint.h>

namespace {

typedef __nv_bfloat16 bf16;

constexpr int SEQ = 2048, DM = 576, HD = 4096, NSEG = 64;
#define PLACE 1
#define LAGV 7
constexpr int LAG = LAGV, STEPS = NSEG + LAG, RING = 8;
static_assert(LAG < RING, "ring");
constexpr int N_CHAIN = 64, N_G = 48, N_O = 18, N_F = 2;
constexpr uint32_t SBASE = 1024;
constexpr uint32_t SENT = 0xFFFFFFFFu;
constexpr int SPIN_MAX = 1 << 22;

__device__ __forceinline__ uint32_t bid() {
  const uint32_t b = blockIdx.x;
  return b < 6 ? b + 106 : b < 8 ? b + 122 : b < 114 ? b - 8 : b < 130 ? b - 2 : b;
}
__device__ __forceinline__ uint32_t chain_id() { return blockIdx.x - (PLACE ? 8 : 0); }
__device__ __align__(1024) bf16 g_kvT[DM * SEQ];
__device__ __align__(1024) bf16 g_yT[DM * SEQ];
__device__ __align__(1024) bf16 g_y[SEQ * DM];
__device__ __align__(1024) bf16 g_x1[SEQ * DM];
__device__ __align__(1024) unsigned char g_lnimg[2 * NSEG * 9 * 4096];
__device__ __align__(1024) unsigned char g_qkv[RING * N_CHAIN * 24576];
__device__ __align__(1024) unsigned char g_oimg[RING * N_CHAIN * 8192];
constexpr int ARING = 16;
static_assert(ARING >= LAG + 9, "accumulator ring");
__device__ __align__(1024) float g_oacc[ARING * 64 * DM];
constexpr int MRING = LAG + 4, N_GRP = 32 + MRING + 1;
constexpr int XB_M = 256, XB_F = XB_M + MRING * 8, XB_REF = XB_F + 2, N_CTA = N_CHAIN + N_G + N_O + N_F;
__device__ __align__(65536) uint4 g_xb[N_GRP * 4096];
#define g_mimg ((uint32_t*)(g_xb + XB_M * 512))
__device__ uint32_t g_near[N_GRP];
__device__ uint32_t g_side[N_CTA];
__device__ __align__(128) uint32_t g_gbar[2 * 32];
constexpr int FL_G = 0, FL_F = 96 * 8, FL_OCNT = FL_F + 2 * 8, OCRING = 16, FL_TICK = 992, FL_O = 2048, FL_SYNC = FL_O + 128;
static_assert(FL_OCNT + OCRING * 8 <= FL_TICK, "flag block");
#define g_fl ((uint32_t*)(g_xb + XB_F * 512))
__device__ __align__(1024) uint32_t g_lnflag[128 * 8];
#define TS(slot)
constexpr int OBSW = 0;
#define PROF(slot)
#define PROF0()
#define PCNT(slot)
#define PROF_DUMP()

#define NSLEEP 0
#define INFL 8
#define S1DLY 2500
#define S1G 1500
#define OTURN 2
#define FENCE1 1
#define FENCE2 0
#define VMIX 23
#define MOFF 1
#define SORD 1
#define EARLYQ 1
#define LOCK0 3
#define MORD 0
#define FASTG 0
#define WSHFL 0
#define PGAP 40
#define NOBULK 0
#define VE 0
#define OGAP 2
#define KXW 0
#define NOCHAIN 0
#define BFENCE 2
#define ABL 0
#define QPRE 0
#define XGUARD 1
#define ATTR 80
#define MTMA 1
#define SEARLY 1
#define VEARLY 1
#define CNT(slot, tries)
#define T3(slot)
#define CK(i, dep)
#define CKW(i, dep)
#define CKDECL
#define CKOUT(base)
#define TR(slot)
#define TRV(slot, val)
#define TRD(slot, dep)
#define TRSYNC()
#define TRDUMP(n)
#define CLK(t) "{.reg .b64 x; .reg .b32 h; mov.u64 x, %%clock64; mov.b64 {" t ", h}, x;}"
__device__ __forceinline__ uint32_t clk() { uint32_t t; asm volatile(CLK("%0") : "=r"(t) :: "memory"); return t; }
__device__ __forceinline__ void wait_until(uint32_t t0, uint32_t d) {
  asm volatile("{.reg .pred p; .reg .u32 t;\n"
               "W: " CLK("t") " sub.u32 t, t, %0; setp.lt.s32 p, t, 0; @p bra.uni W;}"
               :: "r"(t0 + d) : "memory");
}
__device__ __forceinline__ uint32_t pack2(float lo, float hi) {
  uint32_t r; asm("cvt.rn.bf16x2.f32 %0, %1, %2;" : "=r"(r) : "f"(hi), "f"(lo)); return r;
}
__device__ __forceinline__ float bf_lo(uint32_t v) { return __uint_as_float(v << 16); }
__device__ __forceinline__ float bf_hi(uint32_t v) { return __uint_as_float(v & 0xFFFF0000u); }

__device__ __forceinline__ uint4 ld_relaxed4(const void* p) {
  uint4 v; asm volatile("ld.relaxed.gpu.global.v4.u32 {%0,%1,%2,%3}, [%4];" : "=r"(v.x), "=r"(v.y), "=r"(v.z), "=r"(v.w) : "l"(p) : "memory"); return v;
}
__device__ __forceinline__ void st_b128(void* p, uint32_t a, uint32_t b, uint32_t c, uint32_t d) {
  asm volatile("{.reg .b128 v; mov.b128 v, {%1,%2,%3,%4}; st.relaxed.gpu.global.b128 [%0], v;}" :: "l"(p), "r"(a), "r"(b), "r"(c), "r"(d) : "memory");
}
__device__ __forceinline__ void reload_b128(uint4& v, const void* p, uint32_t again) {
  asm volatile("{.reg .pred p; .reg .b128 v; setp.ne.u32 p, %5, 0; mov.b128 v, {%0,%1,%2,%3};\n"
               "@p ld.relaxed.gpu.global.b128 v, [%4]; mov.b128 {%0,%1,%2,%3}, v;}"
    : "+r"(v.x), "+r"(v.y), "+r"(v.z), "+r"(v.w) : "l"(p), "r"(again) : "memory");
}
__device__ __forceinline__ void reload4(uint4& v, const void* p, uint32_t again) {
  asm volatile("{.reg .pred p; setp.ne.u32 p, %5, 0; @p ld.relaxed.gpu.global.v4.u32 {%0,%1,%2,%3}, [%4];}"
    : "+r"(v.x), "+r"(v.y), "+r"(v.z), "+r"(v.w) : "l"(p), "r"(again) : "memory");
}
__device__ __forceinline__ void st_relaxed4(void* p, uint32_t a, uint32_t b, uint32_t c, uint32_t d) {
  asm volatile("st.relaxed.gpu.global.v4.u32 [%0], {%1,%2,%3,%4};" :: "l"(p), "r"(a), "r"(b), "r"(c), "r"(d) : "memory");
}
__device__ __forceinline__ void st_relaxed_if(void* p, uint32_t a, bool on) {
  asm volatile("{.reg .pred p; setp.ne.u32 p, %2, 0; @p st.relaxed.gpu.global.u32 [%0], %1;}" :: "l"(p), "r"(a), "r"((uint32_t)on) : "memory");
}
__device__ __forceinline__ uint32_t ld_acquire(const uint32_t* p) {
  uint32_t v; asm volatile("ld.acquire.gpu.global.u32 %0, [%1];" : "=r"(v) : "l"(p) : "memory"); return v;
}
__device__ __forceinline__ void st_release(uint32_t* p, uint32_t v) {
  asm volatile("st.release.gpu.global.u32 [%0], %1;" :: "l"(p), "r"(v) : "memory");
}
__device__ __forceinline__ void bulk_reduce(float* dst, uint32_t src, uint32_t bytes) {
  asm volatile("cp.reduce.async.bulk.global.shared::cta.bulk_group.add.f32 [%0], [%1], %2;" :: "l"(dst), "r"(src), "r"(bytes) : "memory");
}
__device__ __forceinline__ void bulk_done_inc(uint32_t* p) {
  asm volatile("cp.async.bulk.wait_group 0;\n"
               "fence.proxy.async.global;\nfence.release.gpu;\n"
               "red.relaxed.gpu.global.add.u32 [%0], 1;\nred.relaxed.gpu.global.add.u32 [%0+4096], 1;" :: "l"(p) : "memory");
}
__device__ __forceinline__ void flag_release(uint32_t* p, uint32_t v) {
  asm volatile("fence.release.gpu;\nst.relaxed.gpu.global.u32 [%0], %1;\nst.relaxed.gpu.global.u32 [%0+4096], %1;" :: "l"(p), "r"(v) : "memory");
}
__device__ __forceinline__ void spin_guard(int& it) {
  asm volatile("{.reg .pred p; add.s32 %0, %0, 1; setp.gt.s32 p, %0, %1; @p trap;}" : "+r"(it) : "n"(SPIN_MAX));
}
__device__ __forceinline__ void wait_flag(const uint32_t* p, uint32_t v) {
  int it = 0;
  while (ld_acquire(p) < v) { if (NSLEEP) __nanosleep(NSLEEP); spin_guard(it); }
}
__device__ __forceinline__ void wait_flags(const uint32_t* p, uint32_t v) {
  int it = 0;
  while (true) {
    uint32_t x; asm volatile("ld.relaxed.gpu.global.u32 %0, [%1];" : "=r"(x) : "l"(p) : "memory");
    if (__all_sync(~0u, x >= v)) break;
    spin_guard(it);
  }
  asm volatile("fence.acquire.gpu;" ::: "memory");
}
__device__ __forceinline__ uint32_t timer_offset() {
  uint32_t g0, g;
  asm volatile("mov.u32 %0, %%globaltimer_lo;" : "=r"(g0) :: "memory");
  do { asm volatile("mov.u32 %0, %%globaltimer_lo;" : "=r"(g) :: "memory"); } while (g == g0);
  return (g >> 5) * 58 - clk();
}
__device__ __forceinline__ void grid_arrive(int i) {
  asm volatile("red.release.gpu.global.add.u32 [%0], %1;" :: "l"(g_gbar + i * 32), "r"(bid() ? 1u : 257u - N_CTA) : "memory");
}
__device__ __forceinline__ void grid_wait(int i, uint32_t gen) {
  int it = 0;
  while (((ld_acquire(g_gbar + i * 32) ^ gen) >> 8) == 0) spin_guard(it);
}
__device__ __forceinline__ bool elect() {
  uint32_t r; asm volatile("{.reg .pred p; elect.sync _|p, -1; selp.u32 %0, 1, 0, p;}" : "=r"(r)); return r;
}
__device__ __forceinline__ void bar_sync(int id, int cnt) { asm volatile("bar.sync %0, %1;" :: "r"(id), "r"(cnt) : "memory"); }
__device__ __forceinline__ void bar_arrive(int id, int cnt) { asm volatile("bar.arrive %0, %1;" :: "r"(id), "r"(cnt) : "memory"); }
template <int id, int cnt> __device__ __forceinline__ void bar_arrive_after(uint32_t a, uint32_t b) {
  asm volatile("{.reg .pred p; setp.ne.u32 p, %2, 0xfff12345; setp.ne.and.u32 p, %3, 0xfff12345, p; @p bar.arrive %0, %1;}" :: "n"(id), "n"(cnt), "r"(a), "r"(b) : "memory");
}
template <int id, int cnt> __device__ __forceinline__ void bar_sync_after(uint32_t a) {
  asm volatile("{.reg .pred p; setp.ne.u32 p, %2, 0xfff12345; @p bar.sync %0, %1;}" :: "n"(id), "n"(cnt), "r"(a) : "memory");
}
__device__ __forceinline__ void fence_async_smem() { asm volatile("fence.proxy.async.shared::cta;" ::: "memory"); }
__device__ __forceinline__ void fence_async_global() { asm volatile("fence.proxy.async.global;" ::: "memory"); }
__device__ __forceinline__ void mbar_init(uint32_t mb, int cnt) { asm volatile("mbarrier.init.shared::cta.b64 [%0], %1;" :: "r"(mb), "r"(cnt) : "memory"); }
__device__ __forceinline__ void mbar_arrive(uint32_t mb) { asm volatile("mbarrier.arrive.shared::cta.b64 _, [%0];" :: "r"(mb) : "memory"); }
__device__ __forceinline__ void mbar_arrive_after(uint32_t mb, uint32_t a, uint32_t lane) {
  asm volatile("{.reg .pred p; setp.ne.u32 p, %1, 0xfff12345; setp.eq.and.u32 p, %2, 0, p; @p mbarrier.arrive.shared::cta.b64 _, [%0];}" :: "r"(mb), "r"(a), "r"(lane) : "memory");
}
__device__ __forceinline__ void mbar_expect(uint32_t mb, uint32_t bytes) {
  asm volatile("mbarrier.arrive.expect_tx.shared::cta.b64 _, [%0], %1;" :: "r"(mb), "r"(bytes) : "memory");
}
__device__ __forceinline__ void mbar_wait_guard(uint32_t mb, uint32_t parity) {
  uint32_t ok; int it = 0;
  while (true) {
    asm volatile("{.reg .pred p; mbarrier.try_wait.parity.shared::cta.b64 p, [%1], %2; selp.u32 %0, 1, 0, p;}" : "=r"(ok) : "r"(mb), "r"(parity) : "memory");
    if (ok) break;
    spin_guard(it);
  }
}
__device__ __forceinline__ void mbar_wait(uint32_t mb, uint32_t parity) {
  asm volatile("{.reg .pred p;\nW: mbarrier.try_wait.parity.shared::cta.b64 p, [%0], %1;\n@!p bra W;}" :: "r"(mb), "r"(parity) : "memory");
}
__device__ __forceinline__ void bulk_load(uint32_t dst, const void* src, uint32_t bytes, uint32_t mb) {
  asm volatile("cp.async.bulk.shared::cluster.global.mbarrier::complete_tx::bytes [%0], [%1], %2, [%3];" :: "r"(dst), "l"(src), "r"(bytes), "r"(mb) : "memory");
}
__device__ __forceinline__ void bulk_store(void* dst, uint32_t src, uint32_t bytes) {
  asm volatile("cp.async.bulk.global.shared::cta.bulk_group [%0], [%1], %2;" :: "l"(dst), "r"(src), "r"(bytes) : "memory");
}
__device__ __forceinline__ void cp_async16(uint32_t dst, const void* src) {
  asm volatile("cp.async.cg.shared.global [%0], [%1], 16;" :: "r"(dst), "l"(src) : "memory");
}
__device__ __forceinline__ void cp_async_wait_all() { asm volatile("cp.async.wait_all;" ::: "memory"); }
__device__ __forceinline__ uint32_t mapa(uint32_t a, uint32_t rank) {
  uint32_t r; asm("mapa.shared::cluster.u32 %0, %1, %2;" : "=r"(r) : "r"(a), "r"(rank)); return r;
}
__device__ __forceinline__ void st_async4(uint32_t dst, float a, float b, float c, float d, uint32_t mb) {
  asm volatile("st.async.shared::cluster.mbarrier::complete_tx::bytes.v4.f32 [%0], {%1,%2,%3,%4}, [%5];" :: "r"(dst), "f"(a), "f"(b), "f"(c), "f"(d), "r"(mb) : "memory");
}
__device__ __forceinline__ void st_async2(uint32_t dst, float a, float b, uint32_t mb) {
  asm volatile("st.async.shared::cluster.mbarrier::complete_tx::bytes.v2.f32 [%0], {%1,%2}, [%3];" :: "r"(dst), "f"(a), "f"(b), "r"(mb) : "memory");
}
__device__ __forceinline__ void st_async1(uint32_t dst, uint32_t a, uint32_t mb) {
  asm volatile("st.async.shared::cluster.mbarrier::complete_tx::bytes.u32 [%0], %1, [%2];" :: "r"(dst), "r"(a), "r"(mb) : "memory");
}
__device__ __forceinline__ uint4 lds128(uint32_t a) {
  uint4 v; asm volatile("ld.shared.v4.u32 {%0,%1,%2,%3}, [%4];" : "=r"(v.x), "=r"(v.y), "=r"(v.z), "=r"(v.w) : "r"(a) : "memory"); return v;
}
__device__ __forceinline__ uint2 lds64(uint32_t a) {
  uint2 v; asm volatile("ld.shared.v2.u32 {%0,%1}, [%2];" : "=r"(v.x), "=r"(v.y) : "r"(a) : "memory"); return v;
}
__device__ __forceinline__ uint32_t lds32(uint32_t a) {
  uint32_t v; asm volatile("ld.shared.u32 %0, [%1];" : "=r"(v) : "r"(a) : "memory"); return v;
}
__device__ __forceinline__ void sts128(uint32_t a, uint4 v) {
  asm volatile("st.shared.v4.u32 [%0], {%1,%2,%3,%4};" :: "r"(a), "r"(v.x), "r"(v.y), "r"(v.z), "r"(v.w) : "memory");
}
__device__ __forceinline__ void sts64(uint32_t a, uint32_t x, uint32_t y) {
  asm volatile("st.shared.v2.u32 [%0], {%1,%2};" :: "r"(a), "r"(x), "r"(y) : "memory");
}
__device__ __forceinline__ void sts32(uint32_t a, uint32_t x) { asm volatile("st.shared.u32 [%0], %1;" :: "r"(a), "r"(x) : "memory"); }
__device__ __forceinline__ void ldsm4(uint32_t& r0, uint32_t& r1, uint32_t& r2, uint32_t& r3, uint32_t a) {
  asm volatile("ldmatrix.sync.aligned.m8n8.x4.shared.b16 {%0,%1,%2,%3}, [%4];" : "=r"(r0), "=r"(r1), "=r"(r2), "=r"(r3) : "r"(a) : "memory");
}
__device__ __forceinline__ void ldsm4t(uint32_t& r0, uint32_t& r1, uint32_t& r2, uint32_t& r3, uint32_t a) {
  asm volatile("ldmatrix.sync.aligned.m8n8.x4.trans.shared.b16 {%0,%1,%2,%3}, [%4];" : "=r"(r0), "=r"(r1), "=r"(r2), "=r"(r3) : "r"(a) : "memory");
}
__device__ __forceinline__ void stsm4(uint32_t a, uint32_t r0, uint32_t r1, uint32_t r2, uint32_t r3) {
  asm volatile("stmatrix.sync.aligned.m8n8.x4.shared.b16 [%0], {%1,%2,%3,%4};" :: "r"(a), "r"(r0), "r"(r1), "r"(r2), "r"(r3) : "memory");
}
__device__ __forceinline__ uint32_t movmat(uint32_t a) {
  uint32_t d; asm volatile("movmatrix.sync.aligned.m8n8.trans.b16 %0, %1;" : "=r"(d) : "r"(a)); return d;
}
__device__ __forceinline__ void mma16(float* d, uint32_t a0, uint32_t a1, uint32_t a2, uint32_t a3, uint32_t b0, uint32_t b1) {
  asm volatile("mma.sync.aligned.m16n8k16.row.col.f32.bf16.bf16.f32 {%0,%1,%2,%3}, {%4,%5,%6,%7}, {%8,%9}, {%0,%1,%2,%3};"
    : "+f"(d[0]), "+f"(d[1]), "+f"(d[2]), "+f"(d[3]) : "r"(a0), "r"(a1), "r"(a2), "r"(a3), "r"(b0), "r"(b1));
}
__device__ __forceinline__ void mma8(float* d, uint32_t a0, uint32_t a1, uint32_t b0) {
  asm volatile("mma.sync.aligned.m16n8k8.row.col.f32.bf16.bf16.f32 {%0,%1,%2,%3}, {%4,%5}, {%6}, {%0,%1,%2,%3};"
    : "+f"(d[0]), "+f"(d[1]), "+f"(d[2]), "+f"(d[3]) : "r"(a0), "r"(a1), "r"(b0));
}
__device__ __forceinline__ float rcp(float x) { float r; asm("rcp.approx.ftz.f32 %0, %1;" : "=f"(r) : "f"(x)); return r; }
__device__ __forceinline__ float ex2(float x) { float r; asm("ex2.approx.ftz.f32 %0, %1;" : "=f"(r) : "f"(x)); return r; }

__host__ __device__ constexpr uint64_t mkdesc(uint32_t off, uint32_t lbo, uint32_t sbo, uint32_t swz) {
  return (uint64_t)((SBASE + off) >> 4) | ((uint64_t)(lbo >> 4) << 16) | ((uint64_t)(sbo >> 4) << 32) | ((uint64_t)swz << 62);
}
__host__ __device__ constexpr uint64_t desc_sw128(uint32_t off) { return mkdesc(off, 16, 1024, 1); }
__host__ __device__ constexpr uint64_t desc_n16(uint32_t off) { return mkdesc(off, 256, 128, 0); }
__host__ __device__ constexpr uint64_t desc_m(uint32_t off) { return mkdesc(off, 16, 256, 3); }

__host__ __device__ constexpr uint64_t desc_sw64(uint32_t off) { return mkdesc(off, 16, 512, 2); }

__device__ __forceinline__ void wg_fence() { asm volatile("wgmma.fence.sync.aligned;" ::: "memory"); }
__device__ __forceinline__ void wg_commit() { asm volatile("wgmma.commit_group.sync.aligned;" ::: "memory"); }
template <int N> __device__ __forceinline__ void wg_wait() { asm volatile("wgmma.wait_group.sync.aligned %0;" :: "n"(N) : "memory"); }

#define ACC8(d) "+f"(d[0]), "+f"(d[1]), "+f"(d[2]), "+f"(d[3]), "+f"(d[4]), "+f"(d[5]), "+f"(d[6]), "+f"(d[7])
#define ACC32(d) ACC8(d), ACC8((d + 8)), ACC8((d + 16)), ACC8((d + 24))
#define R8 "{%0,%1,%2,%3,%4,%5,%6,%7}"
#define R32 "{%0,%1,%2,%3,%4,%5,%6,%7,%8,%9,%10,%11,%12,%13,%14,%15,%16,%17,%18,%19,%20,%21,%22,%23,%24,%25,%26,%27,%28,%29,%30,%31}"
template <int SD> __device__ __forceinline__ void wg_rs16(float* d, const uint32_t* a, uint64_t db) {
  asm volatile("wgmma.mma_async.sync.aligned.m64n16k16.f32.bf16.bf16 " R8 ", {%8,%9,%10,%11}, %12, %13, 1, 1, 1;"
    : ACC8(d) : "r"(a[0]), "r"(a[1]), "r"(a[2]), "r"(a[3]), "l"(db), "n"(SD));
}
template <int SD> __device__ __forceinline__ void wg_ss16(float* d, uint64_t da, uint64_t db) {
  asm volatile("wgmma.mma_async.sync.aligned.m64n16k16.f32.bf16.bf16 " R8 ", %8, %9, %10, 1, 1, 1, 1;"
    : ACC8(d) : "l"(da), "l"(db), "n"(SD));
}
template <int SD, uint64_t DA, uint64_t DB> __device__ __forceinline__ void wg_ss16o(float* d, uint32_t oa, uint32_t ob) {
  asm volatile("{.reg .b32 x, y; .reg .b64 a, b; add.u32 x, %8, %10; add.u32 y, %9, %12; mov.b64 a, {x, %11}; mov.b64 b, {y, %13};\n"
               "wgmma.mma_async.sync.aligned.m64n16k16.f32.bf16.bf16 " R8 ", a, b, %14, 1, 1, 1, 1;}"
    : ACC8(d) : "r"(oa), "r"(ob), "n"((uint32_t)DA), "n"((uint32_t)(DA >> 32)), "n"((uint32_t)DB), "n"((uint32_t)(DB >> 32)), "n"(SD));
}
template <int SD> __device__ __forceinline__ void wg_rs64(float* d, const uint32_t* a, uint64_t db) {
  asm volatile("wgmma.mma_async.sync.aligned.m64n64k16.f32.bf16.bf16 " R32 ", {%32,%33,%34,%35}, %36, %37, 1, 1, 0;"
    : ACC32(d) : "r"(a[0]), "r"(a[1]), "r"(a[2]), "r"(a[3]), "l"(db), "n"(SD));
}
template <int SD> __device__ __forceinline__ void wg_ss64(float* d, uint64_t da, uint64_t db) {
  asm volatile("wgmma.mma_async.sync.aligned.m64n64k16.f32.bf16.bf16 " R32 ", %32, %33, %34, 1, 1, 1, 0;"
    : ACC32(d) : "l"(da), "l"(db), "n"(SD));
}
#define WG_RSO(NAME, SHAPE, REGS, ACC, A, TB) \
template <int SD, uint64_t DB> __device__ __forceinline__ void NAME(float* d, uint32_t a0, uint32_t a1, uint32_t a2, uint32_t a3, uint32_t ob) { \
  asm volatile("{.reg .b64 b; mov.b64 b, {" A(4) ", " A(5) "};\nwgmma.mma_async.sync.aligned." SHAPE ".f32.bf16.bf16 " REGS \
               ", {" A(0) "," A(1) "," A(2) "," A(3) "}, b, " A(6) ", 1, 1, " TB ";}" \
    : ACC(d) : "r"(a0), "r"(a1), "r"(a2), "r"(a3), "r"(ob + (uint32_t)DB), "n"((uint32_t)(DB >> 32)), "n"(SD)); \
}
#define ACC4(d) "+f"(d[0]), "+f"(d[1]), "+f"(d[2]), "+f"(d[3])
#define ACC16(d) ACC8(d), ACC8((d + 8))
#define OP4(i) OP4_##i
#define OP4_0 "%4"
#define OP4_1 "%5"
#define OP4_2 "%6"
#define OP4_3 "%7"
#define OP4_4 "%8"
#define OP4_5 "%9"
#define OP4_6 "%10"
#define OP16(i) OP16_##i
#define OP16_0 "%16"
#define OP16_1 "%17"
#define OP16_2 "%18"
#define OP16_3 "%19"
#define OP16_4 "%20"
#define OP16_5 "%21"
#define OP16_6 "%22"
#define OP32(i) OP32_##i
#define OP32_0 "%32"
#define OP32_1 "%33"
#define OP32_2 "%34"
#define OP32_3 "%35"
#define OP32_4 "%36"
#define OP32_5 "%37"
#define OP32_6 "%38"
WG_RSO(wg_rs8o, "m64n8k16", "{%0,%1,%2,%3}", ACC4, OP4, "1")
WG_RSO(wg_rs32o, "m64n32k16", "{%0,%1,%2,%3,%4,%5,%6,%7,%8,%9,%10,%11,%12,%13,%14,%15}", ACC16, OP16, "1")
WG_RSO(wg_rs64o, "m64n64k16", R32, ACC32, OP32, "0")
template <int N> __device__ __forceinline__ void reg_inc() { asm volatile("setmaxnreg.inc.sync.aligned.u32 %0;" :: "n"(N)); }
template <int N> __device__ __forceinline__ void reg_dec() { asm volatile("setmaxnreg.dec.sync.aligned.u32 %0;" :: "n"(N)); }
__device__ __forceinline__ void cluster_sync() {
  asm volatile("barrier.cluster.arrive.relaxed.aligned;\nbarrier.cluster.wait.aligned;" ::: "memory");
}

template <int KS>
__device__ __forceinline__ void load_frags(uint32_t* a, uint32_t src) {
  const int lane = threadIdx.x & 31, w = (threadIdx.x >> 5) & 3;
  const int k = ((lane >> 4) << 3) + (lane & 7), u = w * 2 + ((lane >> 3) & 1);
  const uint32_t base = src + k * 128 + ((u ^ (k & 7)) << 4);
#pragma unroll
  for (int ks = 0; ks < KS; ks++) ldsm4t(a[ks * 4], a[ks * 4 + 1], a[ks * 4 + 2], a[ks * 4 + 3], base + ks * 2048);
}

__device__ __forceinline__ uint32_t badd2(uint32_t a, uint32_t b) { uint32_t r; asm("add.rn.bf16x2 %0, %1, %2;" : "=r"(r) : "r"(a), "r"(b)); return r; }
__device__ __forceinline__ uint32_t bsub2(uint32_t a, uint32_t b) { uint32_t r; asm("sub.rn.bf16x2 %0, %1, %2;" : "=r"(r) : "r"(a), "r"(b)); return r; }
__device__ __forceinline__ uint32_t bmul2(uint32_t a, uint32_t b) { uint32_t r; asm("mul.rn.bf16x2 %0, %1, %2;" : "=r"(r) : "r"(a), "r"(b)); return r; }
__device__ __forceinline__ uint32_t bfma2(uint32_t a, uint32_t b, uint32_t c) { uint32_t r; asm("fma.rn.bf16x2 %0, %1, %2, %3;" : "=r"(r) : "r"(a), "r"(b), "r"(c)); return r; }
template <int R> __device__ __forceinline__ void layernorm9(const uint32_t* x, uint32_t* o) {
  const uint32_t ones = 0x3F803F80u;
  float a[R][3][4], q[R], s[R];
#pragma unroll
  for (int i = 0; i < 9 * R; i++) {
    float* d = a[i % R][i / R % 3];
    if (i < 3 * R) d[0] = d[1] = d[2] = d[3] = 0.f;
    mma8(d, x[i % R * 9 + i / R], ones, x[i % R * 9 + i / R]);
  }
#pragma unroll
  for (int r = 0; r < R; r++) {
    q[r] = threadIdx.x & 4 ? a[r][0][1] + a[r][1][1] + a[r][2][1] : a[r][0][0] + a[r][1][0] + a[r][2][0];
    s[r] = (a[r][0][2] + a[r][0][3]) + (a[r][1][2] + a[r][1][3]) + (a[r][2][2] + a[r][2][3]);
  }
#pragma unroll
  for (int r = 0; r < R; r++) { q[r] += __shfl_xor_sync(~0u, q[r], 4); s[r] += __shfl_xor_sync(~0u, s[r], 1); }
#pragma unroll
  for (int r = 0; r < R; r++) { q[r] += __shfl_xor_sync(~0u, q[r], 9); s[r] += __shfl_xor_sync(~0u, s[r], 2); }
#pragma unroll
  for (int r = 0; r < R; r++) q[r] = __shfl_sync(~0u, q[r], 0) + __shfl_sync(~0u, q[r], 18);
#pragma unroll
  for (int r = 0; r < R; r++) {
    const float mean = s[r] * (1.f / DM), var = fmaxf(fmaf(q[r], 1.f / DM, -mean * mean), 0.f);
    float sd;
    asm("sqrt.approx.ftz.f32 %0, %1;" : "=f"(sd) : "f"(bf_lo(pack2(bf_lo(pack2(var, 0.f)) + 1e-5f, 0.f))));
    const float inv = rcp(bf_lo(pack2(sd, 0.f)));
    const uint32_t mb = pack2(mean, mean), hi = pack2(inv, inv), lo = pack2(inv - bf_lo(hi), inv - bf_lo(hi));
#pragma unroll
    for (int i = r * 9; i < r * 9 + 9; i++) {
      const uint32_t d = bsub2(x[i], mb);
      o[i] = bfma2(d, hi, bmul2(d, lo));
    }
  }
}
__device__ __forceinline__ void store_ln_row(int layer, int tok, const uint32_t* o) {
  const int lane = threadIdx.x & 31, r = tok & 31;
  unsigned char* p = g_lnimg + (size_t)(layer * NSEG + (tok >> 5)) * (9 * 4096) + r * 128 + (((lane >> 2) ^ (r & 7)) << 4) + (lane & 3) * 4;
#pragma unroll
  for (int i = 0; i < 9; i++) *(uint32_t*)(p + i * 4096) = o[i];
}
struct Params { CUtensorMap map[8]; const bf16 *X, *K, *V, *shift, *Hk, *Dk, *mem0, *Wq, *Wk, *Wv, *Wo; bf16* out; uint32_t dly[20]; };
#define DLYS P.dly[0]
#define DLYW P.dly[1]
#define KLATE P.dly[2]
#define DLYQ P.dly[3]
#define DLYK P.dly[4]
#define DLYG P.dly[5]
#define KWIN P.dly[6]
#define KMIN P.dly[7]
uint32_t h_dly[20] = {800, 1100, 20, 0, 3650, 3200, 1800, 400, 1750, 1800, 2070, 2230, 2380, 2530, 3080, 3230, 3370, 3480, 3620};

constexpr uint32_t C_W = 0, C_M = 147456, C_KV = C_M + 18432, C_QM = C_KV + 32768, C_KM = C_QM + 2048,
                   C_VM = C_KM + 2048, C_OI = C_VM + 2048, C_SX = C_OI + 4096, C_KM2 = C_SX + 2560, C_VM2 = C_KM2 + 128,
                   C_KV2 = C_KM2 + 2048, C_Q = C_KV2 + 8192, C_BAR = C_Q + 8192;
constexpr uint32_t CB_FULL = C_BAR, CB_REF = C_BAR + 16, CB_SX = C_BAR + 32, CB_OX = C_BAR + 40, CB_XX = C_BAR + 48, CB_Q = C_BAR + 56, C_BAD = C_BAR + 64, W_BAR = C_BAR + 80, S_GEN = C_BAR + 128, C_REF = C_BAR + 132, CB_VF = C_BAR + 144, CB_M = C_BAR + 160, CB_MV = C_BAR + 200;
constexpr uint32_t G_W = 0, G_RING = 147456, G_W2 = G_RING + 9 * 8192, G_BAR = G_W2 + 8192;
constexpr uint32_t O_W = 0, O_RING = 3 * 40960, O_ST = O_RING + 11 * 8192, O_BAR = O_ST + 16384, OB_ST = O_BAR + 64;
constexpr uint32_t F_A = 0, F_XY = 36864, F_L = F_XY + 36864, F_X = F_L + 18432, F_BAR = F_L + 2 * 36864;
constexpr uint32_t SMEM_BYTES = C_BAR + 256;
static_assert(G_BAR + 256 <= SMEM_BYTES && O_BAR + 256 <= SMEM_BYTES && F_BAR + 16 <= SMEM_BYTES && SMEM_BYTES <= 232448, "smem map");
enum { B_INIT = 1, B_M, B_QK, B_S, B_V, B_O, B_X, B_WG0, B_WG1, B_WG2, B_G, B_OE, B_T, B_R };

__device__ __forceinline__ uint4 pack_partial(const float* d, uint32_t tag) {
  uint32_t x;
  asm("lop3.b32 %0, %1, 1, %2, 0xb8;" : "=r"(x) : "r"(pack2(d[0], d[1])), "r"(tag));
  return make_uint4(x, pack2(d[4], d[5]), pack2(d[2], d[3]), pack2(d[6], d[7]));
}
__device__ __forceinline__ void store_partial(uint4* p, const uint4& v) { st_b128(p, v.x, v.y, v.z, v.w); }
__device__ __forceinline__ void gather_reduce(const uint32_t* p, uint32_t* dst, bool shared, uint32_t tag, uint32_t lane, uint32_t sb, int n, int TS0) {
  int tries = 0;
  float u, v;
  bool bad;
  TR(TS0);
  do {
    uint32_t x[16];
#pragma unroll
    for (int i = 0; i < 16; i++) asm volatile("ld.relaxed.gpu.global.u32 %0, [%1];" : "=r"(x[i]) : "l"(p + i * 64) : "memory");
    tries++;
    float a[2] = {bf_lo(x[0]), bf_lo(x[1])}, b[2] = {bf_hi(x[0]), bf_hi(x[1])};
    uint32_t t = 0;
#pragma unroll
    for (int i = 2; i < 16; i++) { a[i & 1] += bf_lo(x[i]); b[i & 1] += bf_hi(x[i]); }
#pragma unroll
    for (int i = 0; i < 16; i += 4)
      asm("{.reg .b32 y, z; lop3.b32 y, %1, %2, %5, 0x7e; lop3.b32 z, %3, %4, %5, 0x7e; lop3.b32 %0, %0, y, z, 0xfe;}"
          : "+r"(t) : "r"(x[i]), "r"(x[i + 1]), "r"(x[i + 2]), "r"(x[i + 3]), "r"(tag));
    u = a[0] + a[1]; v = b[0] + b[1];
    bad = __any_sync(~0u, (t & 1) && !(lane & 3));
    if (shared) { u += __shfl_xor_sync(~0u, u, 8); v += __shfl_xor_sync(~0u, v, 8); }
    u += __shfl_xor_sync(~0u, u, 16);
    v += __shfl_xor_sync(~0u, v, 16);
    st_relaxed_if(dst, pack2(u, v), !bad && (n >= LAG || !(lane & 1)));
  } while (bad);
  TR(TS0 + 3); TRV(TS0 + 2, tries);
  CNT((TS0 - 16) >> 2, tries);
}
__device__ __forceinline__ uint32_t sent_bad(const uint4& v) { return max(max(v.x, v.y), max(v.z, v.w)) == SENT; }

__host__ __device__ constexpr int o_ks(int s) { return s & (s < 8 ? 3 : 7); }
__host__ __device__ constexpr bool o_reg(int s) { return s < 8 ? (s & 3) != 3 : !(s & 1); }
__host__ __device__ constexpr int o_slot(int s) { return s < 8 ? (o_reg(s) ? s - (s >> 2) : s >> 2) : s & 1 ? (s - 5) >> 1 : (s + 4) >> 1; }
__device__ __forceinline__ int g_unit(int wg) {
  const int i = bid() - N_CHAIN;
  return i < 32 ? wg * 64 + i : 2 * i - 32 + wg;
}
__device__ __forceinline__ void load_slot(const Params& P, uint32_t sb, bool regs, int wg, int i, uint32_t mb) {
  const int b = bid();
  int map, col, ks, c3 = 0;
  uint32_t dst = (wg * 36 + i) * 2048;
  if (b < N_CHAIN) {
    const int k = i - 18, st = regs ? (k < 6 ? k + k / 3 : 2 * k - 4) : k < 2 ? 4 * k + 3 : 2 * k + 5;
    if (wg || i < 18) { map = wg + (i >= 18); col = b * 64; ks = i % 18 * 2 + !regs; }
    else if (!regs && k >= 14) { map = 6; col = 0; ks = b * 4 + k - 14; }
    else { map = 6; col = 64 + (st < 8 ? (st >> 2) * 64 : (st >> 3) * 128 + (b & 1) * 64); ks = (b * 4) ^ o_ks(st); }
  } else if (b < N_CHAIN + N_G) {
    const int q = g_unit(wg);
    map = 3 + ((q >> 5) + 1) % 3; col = (q & 31) * 128 + (regs || i >= 36 ? 0 : 64); ks = i;
    if (i >= 36) { ks = i - 2; dst = G_W2 + wg * 4096 + (i - 36) * 2048; }
  } else {
    const int o = b - N_CHAIN - N_G, ksl = o / 3;
    map = 7; col = ((o % 3) * 3 + (wg + ksl) % 3) * 64; dst = (wg * (regs ? 24 : 20) + i) * 2048;
    ks = (ksl * 11 - max(ksl - 4, 0)) * 4 + (regs ? i / 3 * 5 + i % 3 * 2 : i < 16 ? i / 2 * 5 + 1 + i % 2 * 2 : i + 24);
    c3 = (ks & 1) * 2; ks >>= 1;
  }
  asm volatile("cp.async.bulk.tensor.5d.shared::cluster.global.tile.mbarrier::complete_tx::bytes [%0], [%1, {%2, %3, %3, %4, %5}], [%6];"
               :: "r"(sb + dst), "l"(&P.map[map]), "r"(col), "r"(0), "r"(c3), "r"(ks), "r"(mb) : "memory");
}
__device__ __forceinline__ void load_wg(const Params& P, uint32_t sb, bool regs, int wg) {
  const int b = bid(), i = (threadIdx.x & 31) * 4 + ((threadIdx.x >> 5) & 3);
  const int n = b < N_CHAIN ? 36 : b < N_CHAIN + N_G ? (regs ? 34 : 38) : regs ? 24 : b < N_CHAIN + N_G + 12 ? 20 : 16;
  if (i == 0) mbar_expect(sb + W_BAR + wg * 8, n * 2048);
  if (i < n) load_slot(P, sb, regs, wg, i, sb + W_BAR + wg * 8);
  __syncwarp();
}
__device__ __forceinline__ uint32_t near_half(uint32_t blk, uint32_t reader) {
  return __ldcg(g_near + (blk >> 3)) ^ (~blk & 1) ^ __ldcg(g_side + (blk >> 3)) ^ __ldcg(g_side + reader);
}

__device__ __forceinline__ uint32_t opaque_tid() { uint32_t t; asm volatile("mov.u32 %0, %%tid.x;" : "=r"(t)); return t; }
__device__ __forceinline__ void m_fetch(uint32_t sb, uint32_t src, uint32_t b, uint32_t mb) {
  bulk_load(sb + C_M + (b ? b * 4096 - 2048 : 0), (const unsigned char*)g_mimg + ((src ^ ((b & 1) * 4096)) + b * 8192), b ? 4096 : 2048, mb);
}
__device__ __forceinline__ uint32_t pinned(uint32_t v) { return __shfl_sync(~0u, v, threadIdx.x & 31); }
template <class T> __device__ __forceinline__ T* pinned(T* p) { return (T*)__shfl_sync(~0u, (unsigned long long)p, threadIdx.x & 31); }
__device__ __forceinline__ uint32_t m_probe(uint32_t lane) { return lane * 32 + (lane & 4) * 4 + (lane >> 3) * 4; }
__device__ __forceinline__ uint32_t m_max(uint32_t a, uint32_t b) {
  return max(max(lds32(a), lds32(a + 1024)), max(lds32(b), lds32(b + 1024)));
}
template <int S0, int N> __device__ __forceinline__ void o_steps(float* d, const uint32_t* a) {
  constexpr int SD = o_ks(S0) != 0;
  if constexpr (o_reg(S0)) wg_rs16<SD>(d, a + (18 + o_slot(S0)) * 4, desc_n16(C_OI + o_ks(S0) * 512));
  else wg_ss16<SD>(d, desc_sw128(C_W + (18 + o_slot(S0)) * 2048), desc_n16(C_OI + o_ks(S0) * 512));
  if constexpr (N > 1) o_steps<S0 + 1, N - 1>(d, a);
}
template <int BASE, int KS, int N> __device__ __forceinline__ void m_steps(float* d, const uint32_t* a, uint32_t oa) {
  wg_rs16<KS != 0>(d, a + (BASE + KS / 2) * 4, desc_m(C_M + KS * 512));
  wg_ss16o<1, desc_sw128(C_W + (BASE + KS / 2) * 2048), desc_m(C_M + KS * 512 + 512)>(d, oa, 0);
  if constexpr (N > 2) m_steps<BASE, KS + 2, N - 2>(d, a, oa);
}

__device__ __forceinline__ void chain_proj(const Params& P, uint32_t sb) {
  const uint32_t c = chain_id(), h = c >> 1, j = c & 1, wid = __shfl_sync(~0u, threadIdx.x >> 5, 0), wg = wid >> 2, w = wid & 3;
  const uint32_t t = threadIdx.x & 127, lane = pinned(t & 31), mine = pinned(sb + t * 16), rb = mapa(sb, j ^ 1);
  const uint32_t theirs = pinned(rb + C_KM2 + w * 512 + lane * 4), oa = wg * 4608;
  uint32_t a[144];
  const uint32_t round = min(w, 2u) + (wg ? 0 : 3), gdly = P.dly[8 + round], ps = t >> 2, pf = j * 16 + (ps >> 1);
  uint4* const dsts = pinned(g_xb + (ps * 4096 + near_half(ps * 8, ps * 2) * 256 + c * 4 + (t & 3)));
  uint4* const dstf = pinned(g_xb + (pf * 4096 + 512 + near_half(pf * 8 + 1, pf * 2) * 256 + h * 8 + (t & 7)));
  const uint32_t* const gsrc = (const uint32_t*)g_xb + (h * 16384 + min(w, 2u) * 4096 + near_half(h * 8 + !wg, h * 2) * 1024 +
                               (wg ? (lane & 24) * 2 + j * 8 + (lane & 7) : 2048 + (lane & 16) * 2 + j * 16 + (lane & 15)));
  uint32_t* gdst = g_mimg + (16384 + (lane >> 4) * 1024 + (lane & 2) * 4 +
                   (wg ? (round ? 1536 + round * 512 : 0) + h * 16 + ((lane ^ (c >> 2)) & 1) * 4 + j * 2 + ((lane >> 2) & 1)
                       : (round - 1) * 2048 + c * 16 + ((lane ^ (c >> 1)) & 1) * 4 + ((lane >> 2) & 3)));
  mbar_wait(sb + W_BAR + wg * 8, 0);
  load_frags<36>(a, sb + C_W + wg * 73728);
  fence_async_smem();
  bar_sync(B_WG0 + wg, 128);
  load_wg(P, sb, false, wg);
  mbar_wait(sb + W_BAR + wg * 8, 1);
  bar_sync(B_INIT, 352);
  TS(4);

  uint32_t ring = 1;
#pragma unroll 1
  for (int n = 0; n < STEPS; n++) {
    float d[8], e[8];
    uint32_t redo = n + 1;
    do {
      mbar_wait(sb + CB_M, n & 1);
      wg_fence();
      m_steps<0, 0, 4>(d, a, oa);
      if (VE && wg) m_steps<18, 0, 4>(e, a, 4608);
      wg_commit();
      if (wid == 0) TR(8);
      mbar_wait(sb + CB_M + 8, n & 1);
      wg_fence();
      m_steps<0, 4, 8>(d, a, oa);
      if (VE > 4 && wg) m_steps<18, 4, (VE > 4 ? VE - 4 : 2)>(e, a, 4608);
      wg_commit();
      mbar_wait(sb + CB_MV, n & 1);
      redo = lds32(sb + C_BAD) == redo ? SENT : 0;
    } while (redo);
    mbar_wait(sb + CB_MV + 8, n & 1);
    wg_fence();
    m_steps<0, 12, 8>(d, a, oa);
    wg_commit();
    mbar_wait(sb + CB_MV + 16, n & 1);
    wg_fence();
    m_steps<0, 20, 8>(d, a, oa);
    wg_commit();
    mbar_wait(sb + CB_MV + 24, n & 1);
    wg_fence();
    m_steps<0, 28, 8>(d, a, oa);
    wg_commit();
    wg_wait<0>();
    if (w == 0) TR(6 + wg);
    const uint32_t f0 = pack2(d[0], d[1]), f1 = pack2(d[4], d[5]), f2 = pack2(d[2], d[3]), f3 = pack2(d[6], d[7]);
    stsm4(mine + C_QM + wg * 2048, f0, f1, f2, f3);
    bar_arrive(B_QK, 416);
    const uint32_t tag = (n & 1) ^ 1;
    if (wg) {
      if (n + 1 < STEPS) bar_sync(B_S, 256);
      wg_fence();
      m_steps<18, VE, 36 - VE>(e, a, 4608);
      wg_commit();
      st_async1(theirs, j ? f0 : f1, rb + CB_XX);
      st_async1(theirs + 256, j ? f2 : f3, rb + CB_XX);
      wg_wait<0>();
      if (w == 0) TR(11);
      const uint32_t v0 = pack2(e[0], e[1]), v1 = pack2(e[4], e[5]), v2 = pack2(e[2], e[3]), v3 = pack2(e[6], e[7]);
      stsm4(mine + C_VM, v0, v1, v2, v3);
      bar_arrive(B_V, 256);
      st_async1(theirs + 128, j ? v0 : v1, rb + CB_XX);
      st_async1(theirs + 384, j ? v2 : v3, rb + CB_XX);
      if (n + 1 == STEPS) break;
      bar_sync(B_O, 256);
      fence_async_smem();
      wg_fence();
#pragma unroll
      for (int ks = 0; ks < 4; ks++) {
        if (ks == 0) wg_ss16<0>(d, desc_sw128(C_W + 32 * 2048), desc_n16(C_OI));
        else wg_ss16<1>(d, desc_sw128(C_W + (32 + ks) * 2048), desc_n16(C_OI + ks * 512));
      }
      wg_commit();
      bar_arrive(B_X, 256);
      if (w == 0) TR(0);
      wg_wait<0>();
      store_partial(dsts, pack_partial(d, tag));
      bar_arrive(B_M, 160);
      if (w == 0) TR(1);
    } else {
      if (n + 1 == STEPS) break;
      bar_sync(B_X, 256);
      wg_fence();
      o_steps<0, 4>(d, a);
      wg_commit();
      o_steps<4, 4>(e, a);
      wg_commit();
      wg_wait<1>();
      store_partial(dsts + 1024, pack_partial(d, tag));
      if (w == 0) TR(2);
      if (OGAP == 0) { wg_fence(); o_steps<8, 4>(d, a); wg_commit(); wg_wait<1>(); } else wg_wait<0>();
      store_partial(dsts + 2048, pack_partial(e, tag));
      if (w == 0) TR(3);
      wg_fence();
      if (OGAP) o_steps<8, 4>(d, a);
      if (OGAP < 2) o_steps<16, 4>(e, a);
      wg_commit();
      bar_sync(B_T, 256);
      if (w == 0) { TRV(61, 0); TR(12); }
      wg_fence();
      o_steps<12, 4>(d, a);
      wg_commit();
      if (OGAP == 2) o_steps<16, 4>(e, a);
      o_steps<20, 4>(e, a);
      wg_commit();
      wg_wait<1>();
      store_partial(dstf, pack_partial(d, tag));
      if (w == 0) TR(4);
      wg_fence();
      o_steps<24, 8>(d, a);
      wg_commit();
      wg_wait<1>();
      store_partial(dstf + 1024, pack_partial(e, tag));
      bar_arrive(B_OE, 256);
      if (w == 0) TR(5);
      wg_wait<0>();
      store_partial(dstf + 2048, pack_partial(d, tag));
      if (w == 0) TR(15);
    }
    if (w < 3) {
      mbar_wait(sb + CB_REF, n & 1);
      wait_until(lds32(sb + C_REF), gdly);
      gather_reduce(gsrc, gdst, wg, tag, lane, sb, n, 16 + round * 4);
      if (++ring == MRING) { ring = 0; gdst -= MRING * 16384; }
      gdst += 16384;
    }
  }
}

template <int KS> __device__ __forceinline__ void x_scores(float* s, float* sm, const uint4* q, uint32_t ok, uint32_t om) {
  wg_rs32o<1, desc_sw64(C_KV + KS * 1024)>(s, q[KS].x, q[KS].y, q[KS].z, q[KS].w, ok);
  wg_rs8o<1, desc_n16(C_KM + KS * 512)>(sm, q[KS].x, q[KS].y, q[KS].z, q[KS].w, om);
  if constexpr (KS < 3) x_scores<KS + 1>(s, sm, q, ok, om);
}

__device__ __forceinline__ void chain_attn(const Params& P, uint32_t sb) {
  const int c = chain_id(), j = c & 1;
  const int tid = threadIdx.x, lane = tid & 31, w = __shfl_sync(~0u, (tid >> 5) & 3, 0);
  const int l = w >> 1, u = w & 1;
  const uint32_t rb = mapa(sb, j ^ 1);
  const float sc = 0.08838834764831845f * 1.4426950408889634f;
  const uint32_t ones = 0x3F803F80u;
  const uint32_t km_off = C_KM + (lane >> 3) * 256 + l * 128 + (lane & 7) * 16;
  const uint32_t qm_off = C_QM + (lane >> 4) * 256 + l * 128 + (lane & 7) * 16;
  const uint32_t kv_off = C_KV + l * 4096 + (lane & 15) * 64 + (((lane >> 4) ^ (u * 2) ^ ((lane >> 1) & 3)) << 4);

  if (lane == 0) mbar_arrive(sb + CB_M);
#pragma unroll 1
  for (int n = 0; n < STEPS; n++) {
    const uint32_t kvb = sb + kv_off + (n & 1) * 16384;
    if (w == 0 && elect()) { mbar_expect(sb + CB_SX, 2560); mbar_expect(sb + CB_OX, 2048); mbar_expect(sb + CB_XX, 2048); }
    mbar_wait(sb + CB_FULL + (n & 1) * 8, (n >> 1) & 1);
    if (n == 0) TS(5);
    __syncwarp();
    {
      uint32_t km[8];
      uint4 kx[8];
#pragma unroll
      for (int i = 0; i < 8; i++) ldsm4t(kx[i].x, kx[i].y, kx[i].z, kx[i].w, (kvb ^ ((i & 1) * 32)) + (i >> 1) * 1024);
      mbar_wait(sb + CB_VF, n & 1);
      if (w == 1) TRD(60, kx[7].x);
      bar_sync(B_QK, 416);
      if (n + 1 == STEPS) {
        bar_sync(B_V, 256);
      } else {
      uint32_t qm[16];
#pragma unroll
      for (int ks = 0; ks < 4; ks++) ldsm4t(qm[4 * ks], qm[4 * ks + 1], qm[4 * ks + 2], qm[4 * ks + 3], sb + qm_off + ks * 512);
      ldsm4t(km[0], km[1], km[2], km[3], sb + km_off);
      ldsm4t(km[4], km[5], km[6], km[7], sb + km_off + 1024);
      float s[5][4];
#pragma unroll
      for (int i = 0; i < 5; i++) { s[i][0] = s[i][1] = s[i][2] = s[i][3] = 0.f; }
#pragma unroll
      for (int ks = 0; ks < 4; ks++) {
        const uint32_t* q = qm + 4 * ks;
        mma16(s[1], q[0], q[1], q[2], q[3], kx[2 * ks].x, kx[2 * ks].y);
        mma16(s[2], q[0], q[1], q[2], q[3], kx[2 * ks].z, kx[2 * ks].w);
        mma16(s[0], q[0], q[1], q[2], q[3], km[2 * ks], km[2 * ks + 1]);
        mma16(s[3], q[0], q[1], q[2], q[3], kx[2 * ks + 1].x, kx[2 * ks + 1].y);
        mma16(s[4], q[0], q[1], q[2], q[3], kx[2 * ks + 1].z, kx[2 * ks + 1].w);
      }
      const uint32_t sx = C_SX + l * 1280;
      st_async4(rb + sx + u * 512 + lane * 16, s[1][0], s[1][1], s[2][0], s[2][1], rb + CB_SX);
      st_async1(rb + sx + 1024 + u * 128 + lane * 4, __float_as_uint(u ? s[0][1] : s[0][0]), rb + CB_SX);
      bar_arrive_after<B_S, 256>(__float_as_uint(s[3][0]), __float_as_uint(s[4][0]));
      uint4 vx[4];
#pragma unroll
      for (int i = 0; i < 4; i++) ldsm4(vx[i].x, vx[i].y, vx[i].z, vx[i].w, (kvb ^ ((i & 1) * 32)) + 8192 + (2 * u + (i >> 1)) * 1024);
      mbar_wait(sb + CB_SX, n & 1);
      const uint4 p0 = lds128(sb + sx + u * 512 + lane * 16), p1 = lds128(sb + sx + (u ^ 1) * 512 + lane * 16);
      const uint2 p2 = make_uint2(lds32(sb + sx + 1024 + lane * 4), lds32(sb + sx + 1152 + lane * 4));
      float t[10] = {s[0][0] + __uint_as_float(p2.x), s[0][1] + __uint_as_float(p2.y),
                     s[1][0] + __uint_as_float(p0.x), s[1][1] + __uint_as_float(p0.y),
                     s[2][0] + __uint_as_float(p0.z), s[2][1] + __uint_as_float(p0.w),
                     s[3][0] + __uint_as_float(p1.x), s[3][1] + __uint_as_float(p1.y),
                     s[4][0] + __uint_as_float(p1.z), s[4][1] + __uint_as_float(p1.w)};
      float mx = fmaxf(fmaxf(fmaxf(fmaxf(t[2], t[3]), fmaxf(t[4], t[5])), fmaxf(fmaxf(t[6], t[7]), fmaxf(t[8], t[9]))), fmaxf(t[0], t[1]));
      mx = fmaxf(fmaxf(mx, __shfl_xor_sync(~0u, mx, 1)), fmaxf(__shfl_xor_sync(~0u, mx, 2), __shfl_xor_sync(~0u, mx, 3)));
      const float ms = -mx * sc;
#pragma unroll
      for (int i = 0; i < 10; i++) t[i] = ex2(fmaf(t[i], sc, ms));
      uint32_t p[5];
#pragma unroll
      for (int i = 0; i < 5; i++) p[i] = pack2(t[2 * i], t[2 * i + 1]);
      p[1] |= (p[0] & p[3] & p[4]) & 0x80008000u;
      float o[2][4], z[4] = {0.f, 0.f, 0.f, 0.f};
      mma16(z, ones, ones, ones, ones, p[1], p[2]);
#pragma unroll
      for (int i = 0; i < 2; i++) {
        o[i][0] = o[i][1] = o[i][2] = o[i][3] = 0.f;
        mma16(o[i], vx[2 * i].x, vx[2 * i].y, vx[2 * i].z, vx[2 * i].w, p[1], p[2]);
      }
      mma16(z, ones, ones, ones, ones, p[3], p[4]);
#pragma unroll
      for (int i = 0; i < 2; i++) mma16(o[i], vx[2 * i + 1].x, vx[2 * i + 1].y, vx[2 * i + 1].z, vx[2 * i + 1].w, p[3], p[4]);
      mma8(z, ones, ones, p[0]);
      bar_sync_after<B_V, 256>(p[1]);
      ldsm4(km[0], km[1], km[2], km[3], sb + km_off + (C_VM - C_KM) + u * 1024);
      mma8(o[0], km[0], km[1], p[0]);
      mma8(o[1], km[2], km[3], p[0]);
      const float i0 = rcp(z[0]), i1 = rcp(z[1]);
      const uint32_t oo = C_OI + u * 1024 + l * 128 + lane * 4;
      uint32_t ow[4];
#pragma unroll
      for (int i = 0; i < 2; i++) { ow[2 * i] = pack2(o[i][0] * i0, o[i][1] * i1); ow[2 * i + 1] = pack2(o[i][2] * i0, o[i][3] * i1); }
#pragma unroll
      for (int i = 0; i < 4; i++) st_async1(rb + oo + 2048 + i * 256, ow[i], rb + CB_OX);
      stsm4(sb + C_OI + u * 1024 + l * 128 + (lane >> 3) * 256 + (lane & 7) * 16, ow[0], ow[1], ow[2], ow[3]);
      bar_arrive(B_O, 256);
      }
    }
    {
      const uint32_t lane = opaque_tid() & 31, own = ((n & 1) * 16384 + j * 4096) >> 4;
      float s[16], sm[4];
#pragma unroll
      for (int i = 0; i < 16; i++) s[i] = sm[i & 3] = 0.f;
      {
        uint4 q[4];
        mbar_wait(sb + CB_Q, n & 1);
#pragma unroll
        for (int ks = 0; ks < 4; ks++) q[ks] = lds128(sb + C_Q + (ks >> 1) * 4096 + w * 1024 + (ks & 1) * 512 + lane * 16);
        mbar_wait(sb + CB_XX, n & 1);
        if (n + 1 < STEPS) mbar_wait(sb + CB_OX, n & 1);
        fence_async_smem();
        if (n + 1 < STEPS) { bar_arrive(B_T, 256); bar_sync(B_OE, 256); }
        if (w == 1) { TRV(61, 0); TR(9); }
#pragma unroll 1
        for (uint32_t hf = 0; hf < 2; hf++) {
          wg_fence();
          x_scores<0>(s, sm, q, hf ? (C_KV2 - C_KV) >> 4 : own, hf ? (C_KM2 - C_KM) >> 4 : j * 8);
          wg_commit();
          wg_wait<0>();
#pragma unroll
          for (int ks = 0; ks < 4; ks++) asm volatile("mov.b32 %0, %1; mov.b32 %2, %3;" : "+r"(q[ks].x), "+r"(q[ks].y), "+r"(q[ks].z), "+r"(q[ks].w));
        }
      }
      const float neg = -1e9f * 11.313708498984761f;
      const int lim = 8 * (w - (int)(lane & 3)) + (int)(lane >> 2);
      float t[10] = {sm[0], sm[1]};
#pragma unroll
      for (int i = 0; i < 8; i++) t[2 + i] = i > lim ? neg : s[(i >> 1) * 4 + (i & 1)];
      float mx = fmaxf(fmaxf(fmaxf(fmaxf(t[2], t[3]), fmaxf(t[4], t[5])), fmaxf(fmaxf(t[6], t[7]), fmaxf(t[8], t[9]))), fmaxf(t[0], t[1]));
      mx = fmaxf(fmaxf(mx, __shfl_xor_sync(~0u, mx, 1)), fmaxf(__shfl_xor_sync(~0u, mx, 2), __shfl_xor_sync(~0u, mx, 3)));
      const float ms = -mx * sc;
#pragma unroll
      for (int i = 0; i < 10; i++) t[i] = ex2(fmaf(t[i], sc, ms));
      uint32_t p[5];
#pragma unroll
      for (int i = 0; i < 5; i++) p[i] = pack2(t[2 * i], t[2 * i + 1]);
      float z = ((t[0] + t[1]) + (t[2] + t[3])) + ((t[4] + t[5]) + (t[6] + t[7])) + (t[8] + t[9]);
      const uint32_t row = sb + C_Q + w * 1024 + (lane >> 2) * 128 + (((lane & 3) ^ (lane >> 2)) << 4);
#pragma unroll 1
      for (uint32_t hf = 0; hf < 2; hf++) {
        float o[32];
        const uint32_t vo = hf ? (C_KV2 + 4096 - C_KV - 8192) >> 4 : own;
        wg_fence();
        wg_rs64o<0, desc_sw64(C_KV + 8192)>(o, p[1], p[1], p[2], p[2], vo);
        wg_rs64o<1, desc_sw64(C_KV + 8192 + 32)>(o, p[3], p[3], p[4], p[4], vo);
        wg_rs64o<1, mkdesc(C_VM, 128, 256, 0)>(o, p[0], p[0], 0, 0, hf ? (C_VM2 - C_VM) >> 4 : j * 8);
        wg_commit();
        if (hf) {
          if (elect()) mbar_arrive(sb + CB_M);
        } else {
          z += __shfl_xor_sync(~0u, z, 1);
          z = rcp(z + __shfl_xor_sync(~0u, z, 2));
        }
        wg_wait<0>();
#pragma unroll
        for (int qq = 0; qq < 2; qq++) {
          const float* r = o + 16 * qq;
          sts128((row ^ (qq * 64)) + hf * 4096,
                 make_uint4(pack2(r[0] * z, r[1] * z), pack2(r[4] * z, r[5] * z), pack2(r[8] * z, r[9] * z), pack2(r[12] * z, r[13] * z)));
        }
      }
      bar_arrive(B_G, 160);
      if (w == 1) TR(10);
    }
  }
  TS(6);
}

__device__ __forceinline__ void chain_aux(const Params& P, uint32_t sb) {
  const uint32_t c = chain_id(), j = c & 1, lane = threadIdx.x & 31, w = __shfl_sync(~0u, (threadIdx.x >> 5) & 3, 0);
  if (w == 0) {
    bar_sync(B_R, 64);
    const uint32_t* fg = g_fl + FL_G + near_half(XB_F, c) * 1024 + (c >> 1) * 8;
#pragma unroll 1
    for (int n = 0; n < STEPS; n++) {
      const unsigned char* blk = g_qkv + (uint32_t)((n % RING) * (N_CHAIN * 24576));
      const uint32_t t1 = clk(), kb = sb + CB_FULL + (n & 1) * 8, kv = sb + C_KV + (n & 1) * 16384;
      uint32_t t0 = t1 - 100000, x = 0;
      if (n > 0) {
        wait_until(t1, KMIN);
        do asm volatile("ld.relaxed.gpu.global.u32 %0, [%1];" : "=r"(x) : "l"(fg) : "memory"); while (x <= n && clk() - t1 < KWIN);
        if (NOBULK) x = n + 1;
        if (x > n) {
          asm volatile("fence.acquire.gpu;" ::: "memory");
          fence_async_global();
          if (elect()) { mbar_expect(kb, 8192); bulk_load(kv, blk + c * 24576, 8192, kb); }
        }
        T3(0); CNT(12, 1 + (x <= n));
        mbar_wait(sb + CB_REF, (n - 1) & 1);
        t0 = lds32(sb + C_REF);
        wait_until(t0, DLYK - 500);
      }
      if (!NOBULK) wait_flags(fg + (lane & 1) * 256, n + 1);
      fence_async_global();
      wait_until(t0, DLYK);
      if (elect()) {
        if (x <= n) { mbar_expect(kb, 8192); bulk_load(kv, blk + c * 24576, 8192, kb); }
        mbar_expect(sb + CB_VF, 8192);
        bulk_load(kv + 8192, blk + (c * 24576 + 8192), 8192, sb + CB_VF);
      }
      T3(1);
      if (!NOBULK) wait_flags(fg + 512, n + 1);
      T3(2);
      fence_async_global();
      if (n > 0) bar_sync(B_R, 64);
      if (elect()) {
        mbar_expect(sb + CB_Q, 16384);
        bulk_load(sb + C_Q, blk + (c * 24576 + 16384), 8192, sb + CB_Q);
        bulk_load(sb + C_KV2, blk + ((c ^ 1) * 24576 + j * 4096), 4096, sb + CB_Q);
        bulk_load(sb + C_KV2 + 4096, blk + ((c ^ 1) * 24576 + 8192 + j * 4096), 4096, sb + CB_Q);
      }
      T3(3);
    }
  } else {
    const uint32_t near = __ballot_sync(~0u, near_half(XB_M + min(lane, MRING - 1u) * 8, c));
    uint32_t ring = 0;
    if (w > 1) {
      const uint32_t odd = w & 1, chk = pinned(sb + C_M + odd * 2048 + m_probe(lane)), again = sb + CB_MV + 32 + odd * 8;
      const bool one = elect();
      uint32_t mph = 0;
#pragma unroll 1
      for (int n = 0; n <= STEPS; n++) {
#pragma unroll
        for (int k = 0; k < 3; k++) {
          if (n == STEPS || (k == 2 && odd)) break;
          const uint32_t b = 2 * k + odd, at = chk + (k ? k * 8192 - 2048 + odd * 2048 : 0);
          uint32_t mb = sb + CB_M + b * 8, ph = n & 1;
          int it = 1;
          while (true) {
            mbar_wait(mb, ph);
            const bool bad = __any_sync(~0u, (k ? m_max(at, at + 2048) : max(m_max(at, at ^ 8), odd ? m_max(at + 2048, (at ^ 8) + 2048) : 0)) == SENT);
            if (one && !bad) mbar_arrive(sb + CB_MV + (k ? b * 8 - 8 : 0));
            if (!bad) break;
            mb = again; ph = mph; mph ^= 1;
            if (one) {
              if (k == 0) sts32(sb + C_BAD, n + 1);
              mbar_expect(mb, b ? 4096 : 2048);
              m_fetch(sb, ring * 65536 + ((near >> ring) & 1) * 4096, b, mb);
            }
            __syncwarp();
            spin_guard(it);
          }
          TR(41 + b * 4); CNT(6 + b, it);
        }
        ring = ring + 1 == MRING ? 0 : ring + 1;
        if (!odd) {
          if (n < STEPS) { TRSYNC(); TRDUMP(n - 2); }
        } else if (n > 0) {
          unsigned char* o = g_oimg + (uint32_t)(((n - 1) & (RING - 1)) * (N_CHAIN * 8192) + j * 4096);
          bar_sync(B_G, 160);
          fence_async_smem();
          if (one) {
            bulk_store(o + c * 8192, sb + C_Q, 4096);
            bulk_store(o + (c ^ 1) * 8192, sb + C_Q + 4096, 4096);
            asm volatile("cp.async.bulk.commit_group;\ncp.async.bulk.wait_group.read 0;" ::: "memory");
            { const int n_ = n - 1; { const int n = n_; T3(4); (void)n; } }
          }
          __syncwarp();
          if (n < STEPS) bar_arrive(B_R, 64);
          if (one) {
            bulk_done_inc(g_fl + FL_O + c);
            { const int n_ = n - 1; { const int n = n_; T3(5); (void)n; } }
          }
          __syncwarp();
        }
      }
    } else {
      const uint32_t* ts = g_fl + FL_SYNC + near_half(XB_F + 1, c) * 1024 + lane * 2;
      uint32_t t0 = clk() - 100000;
#pragma unroll 1
      for (int n = 0; n < STEPS; n++) {
        const uint32_t src = ring * 65536 + ((near >> ring) & 1) * 4096;
        if (lane < 5) mbar_expect(sb + CB_M + lane * 8, lane ? 4096 : 2048);
        __syncwarp();
        if (elect()) {
#pragma unroll
          for (int b = 0; b < 5; b++) {
            wait_until(t0, P.dly[14 + b]);
            m_fetch(sb, src, b, sb + CB_M + b * 8);
            TR(40 + b * 4);
          }
        }
        __syncwarp();
        ring = ring + 1 == MRING ? 0 : ring + 1;
        uint32_t va, vb;
        const uint32_t off = timer_offset(), tag = (uint32_t)(n + 1) << 24;
        bar_sync(B_QK, 416);
        if (n + 1 == STEPS) break;
        sts32(sb + C_REF + 4, 0);
        const uint32_t c0 = clk(), stamp = c0 + off;
        st_relaxed_if(g_fl + FL_SYNC + lane * 1024 + c, tag | (stamp & 0xFFFFFF), lane < 2);
        TR(13);
        wait_until(c0, DLYS);
        int it = 0;
        do {
          asm volatile("ld.relaxed.gpu.global.v2.u32 {%0,%1}, [%2];" : "=r"(va), "=r"(vb) : "l"(ts) : "memory");
          spin_guard(it);
        } while (__any_sync(~0u, ((va ^ tag) | (vb ^ tag)) >> 24));
        const int late = __reduce_max_sync(~0u, max((int)((va - stamp) << 8), (int)((vb - stamp) << 8))) >> 8;
        t0 = c0 + min((uint32_t)late, clk() - c0);
        if (elect()) {
          sts32(sb + C_REF, t0);
          mbar_arrive(sb + CB_REF);
        }
        st_relaxed_if(g_fl + FL_TICK + lane * 1024, tag | ((t0 + off) & 0xFFFFFF), c == 0 && lane < 2);
        TR(14); CNT(11, it);
        bar_sync(B_M, 160);
      }
    }
  }
}

template <int WG>
__device__ __forceinline__ void g_math(const Params& P, uint32_t sb) {
  const int q = g_unit(WG);
  const int lane = threadIdx.x & 31, w = (threadIdx.x >> 5) & 3;
  const bool isq = q >= 64;
  uint32_t a[136];
  {
    const uint32_t stage = sb + G_W + WG * 73728;
    mbar_wait(sb + W_BAR + WG * 8, 0);
    load_frags<34>(a, stage);
    fence_async_smem();
    bar_sync(B_WG0 + WG, 128);
    load_wg(P, sb, false, WG);
    mbar_wait(sb + W_BAR + WG * 8, 1);
  }
  TS(4);
  const uint32_t off0 = (q & 31) * 49152 + (q >> 5) * 8192 +
                        (isq ? (w >> 1) * 4096 + (w & 1) * 512 + lane * 16 : w * 1024 + (lane >> 2) * 64 + (((lane ^ (lane >> 3)) & 3) << 4));
#pragma unroll 1
  for (int n = 0; n < STEPS; n++) {
    float d0[32], d1[32];
    PROF0();
    if (n > 0) bar_sync(B_V + WG, 256);
#pragma unroll
    for (int ch = 0; ch < 9; ch++) {
      mbar_wait(sb + G_BAR + ch * 8, n & 1);
      if (ch == 0) { PROF(1); if ((threadIdx.x & 127) == 0) T3(5 + WG * 3); __syncwarp(); }
      if (ch == 4) { if ((threadIdx.x & 127) == 0) T3(6 + WG * 3); __syncwarp(); }
      if (ch == 8 && (WG == 0 ? n > 0 : n + 1 < STEPS)) bar_arrive(B_V + (WG ^ 1), 256);
      wg_fence();
#pragma unroll
      for (int kk = 0; kk < 4 - FASTG; kk++) {
        const int ks = ch * 4 + kk;
        const uint64_t db = desc_sw128(G_RING + ch * 8192 + kk * 32);
        const uint64_t da = desc_sw128(G_W + WG * 73728 + ks * 2048);
        if (ks == 0) { wg_rs64<0>(d0, a, db); wg_ss64<0>(d1, da, db); }
        else if (ks < 34) { wg_rs64<1>(d0, a + ks * 4, db); wg_ss64<1>(d1, da, db); }
        else { wg_ss64<1>(d0, desc_sw128(G_W2 + WG * 4096 + (ks - 34) * 2048), db); wg_ss64<1>(d1, da, db); }
      }
      wg_commit();
      if (ch > 0) { wg_wait<1>(); if (lane == 0) mbar_arrive(sb + G_BAR + 128 + (ch - 1) * 8); }
    }
    wg_wait<0>();
    if (lane == 0) mbar_arrive(sb + G_BAR + 128 + 8 * 8);
    PROF(2);
    if ((threadIdx.x & 127) == 0) T3(7 + WG * 3);
    __syncwarp();
    uint32_t tw = clk() + (WG == 0 && n >= LOCK0 ? DLYW : 0);
    unsigned char* base = g_qkv + (size_t)(n & (RING - 1)) * (N_CHAIN * 24576);
    if ((ABL & 1) && d0[0] != 1234.5f) {
    } else if (isq) {
#pragma unroll
      for (int i = 0; i < 8; i++) {
        const float *d = (i < 4 ? d0 : d1) + 4 * i, *e = (i < 4 ? d1 : d0) + 4 * i;
        wait_until(tw, 0); tw += P.dly[2 + WG];
        *(uint4*)(base + off0 + (i >> 2) * 24576 + (i & 3) * 1024) =
          make_uint4(movmat(pack2(d[0], d[1])), movmat(pack2(e[0], e[1])), movmat(pack2(d[2], d[3])), movmat(pack2(e[2], e[3])));
      }
    } else {
#pragma unroll
      for (int i = 0; i < 8; i++) {
        const float* d = (i < 4 ? d0 : d1) + 8 * (i & 2) + 2 * (i & 1);
        wait_until(tw, 0); tw += P.dly[2 + WG];
        *(uint4*)(base + off0 + (i >> 2) * 24576 + (i & 2) * 2048 + (i & 1) * 512) =
          make_uint4(pack2(d[0], d[1]), pack2(d[4], d[5]), pack2(d[8], d[9]), pack2(d[12], d[13]));
      }
    }
    bar_arrive(B_M + WG, 160);
    PROF(3);
  }
}

__device__ __forceinline__ void fill16(void* p, uint32_t v) {
  asm volatile("st.global.v4.u32 [%0], {%1,%1,%1,%1};" :: "l"(p), "r"(v) : "memory");
}
__device__ __forceinline__ void g_load(const Params& P, uint32_t sb) {
  const int lane = threadIdx.x & 31, w = __shfl_sync(~0u, (threadIdx.x >> 5) & 3, 0);
  if (w == 2) return;
  uint32_t fl = 0;
#pragma unroll 1
  for (int n = 0; n < STEPS; n++) {
    if (w == 3) {
      if (n == 0) wait_flags(g_lnflag + (lane & 1) * 8, 1);
      if (n == 1) fl = near_half(XB_F, bid()) * 1024;
      if (!NOCHAIN && n >= LOCK0) {
        const uint32_t tag = (uint32_t)(n - LOCK0 + 1) << 24;
        uint32_t v; int it = 0;
        do { asm volatile("ld.relaxed.gpu.global.u32 %0, [%1];" : "=r"(v) : "l"(g_fl + fl + FL_TICK) : "memory"); spin_guard(it); } while (v < tag);
        const uint32_t off = timer_offset(), now = clk(), t0 = now - ((v ^ tag) >> 24 ? DLYG : (now + off - v) & 0xFFFFFF);
        asm volatile("fence.acquire.gpu;" ::: "memory");
        if (lane == 0) T3(11);
        if (n >= LAG) wait_flags(g_fl + fl + FL_F + (lane & 1) * 8, n - LAG + 1);
        if (lane == 0) T3(12);
        __syncwarp();
        wait_until(t0, DLYG);
      }
      bar_sync(B_X, 128);
      continue;
    }
    if (w == 0) {
      if (n == 0) wait_flags(g_lnflag + (lane & 1) * 8, 1);
      if ((n & 7) == 1 && n < 32) wait_flags(g_lnflag + ((n >> 3) * 32 + lane) * 8, 1);
    } else {
      bar_sync(B_X, 128);
      if (lane == 0) T3(4);
    }
    fence_async_global();
    const unsigned char* src = g_lnimg + (uint32_t)((w ? (n >= LAG ? NSEG + n - LAG : 0) : min(n, NSEG - 1)) * 36864);
#pragma unroll 1
    for (int ch = 0; ch < 9; ch++) {
      const uint32_t full = sb + G_BAR + ch * 8;
      mbar_wait(full + 128, (n & 1) ^ 1);
      if (elect()) {
        mbar_expect(full, ABL & 2 ? 16 : 4096);
        bulk_load(sb + G_RING + ch * 8192 + w * 4096, src + ch * 4096, ABL & 2 ? 16 : 4096, full);
      }
    }
  }
}

__device__ __forceinline__ void g_aux(const Params& P, uint32_t sb) {
  const int lane = threadIdx.x & 31, w = (threadIdx.x >> 5) & 3;
  if (w == 1 || w == 2) {
    const int q = g_unit(w - 1);
    uint32_t* f = g_fl + FL_G + q * 8;
#pragma unroll 1
    for (int n = 0; n < STEPS; n++) {
      const uint32_t ln = opaque_tid() & 31;
      uint4* z = (uint4*)g_oacc + (uint32_t)(((n + 1) % ARING) * (16 * DM) + q * 96 + ln);
      fill16(z, 0); fill16(z + 32, 0); fill16(z + 64, 0);
      if (n + 3 >= MRING && q < 80) fill16((uint4*)g_mimg + (uint32_t)(((n + 3) % MRING) * 4096 + q * 32 + ln), SENT);
      bar_sync(B_M + (w - 1), 160);
      if (lane == 0) { T3(w * 2 - 2); fence_async_global(); flag_release(f, n + 1); T3(w * 2 - 1); }
      __syncwarp();
    }
  } else {
    const uint32_t u = (bid() - N_CHAIN) * 2 + (w & 1), r = u / 36 * 16 + (u & 3) * 4 + (lane >> 3);
    uint32_t o = r * (DM / 8) + (u % 36 >> 2) * 8 + ((lane & 7) ^ ((r >> 1) & 3));
#pragma unroll 1
    for (int k = -LAG - 1; k < STEPS; k++) {
      if (k < NSEG - 1) bar_sync(B_X, 128);
      if (k < LAG || u >= 72) continue;
      if (k >= NSEG - 1) {
        const uint32_t* f = g_fl + near_half(XB_F, bid()) * 1024;
        if (k + 1 == STEPS) wait_flags(f + FL_F + (lane & 1) * 8, NSEG + 1);
        wait_flags(f + FL_OCNT + (max(k, NSEG) % OCRING) * 8, N_O * 3 * (max(k, NSEG) / OCRING + 1));
      }
      const float4* a = (const float4*)g_oacc + ((k % ARING) * (16 * DM) + 8 * DM + u * 64 + lane * 2);
      const float4 p = __ldcg(a), v = __ldcg(a + 1);
      const uint4 x = __ldcg((const uint4*)P.out + o);
      ((uint4*)P.out)[o] = make_uint4(badd2(x.x, pack2(p.x, p.y)), badd2(x.y, pack2(p.z, p.w)), badd2(x.z, pack2(v.x, v.y)), badd2(x.w, pack2(v.z, v.w)));
      o += 4 * DM;
    }
    TS(7);
  }
}

template <int WG>
__device__ __forceinline__ void o_math(const Params& P, uint32_t sb) {
  const int ksl = (bid() - N_CHAIN - N_G) / 3;
  const int nc = ksl < 4 ? 11 : 10;
  const int lane = threadIdx.x & 31, w = (threadIdx.x >> 5) & 3, g = lane >> 2, tq = lane & 3;
  uint32_t a[96];
  {
    mbar_wait(sb + W_BAR + WG * 8, 0);
    load_frags<24>(a, sb + WG * 49152);
    fence_async_smem();
    bar_sync(B_INIT, 416);
    load_wg(P, sb, false, WG);
    mbar_wait(sb + W_BAR + WG * 8, 1);
  }
  TS(4);
  const uint32_t st0 = sb + O_ST + tq * 512 + ((w * 16 + g) ^ (tq * 8)) * 4;
#pragma unroll 1
  for (int n = 0; n < STEPS; n++) {
    float d[32];
    PROF0();
    if (WG > 0 || n > 0) bar_sync(B_V + WG, 256);
#pragma unroll
    for (int gr = 0; gr < 5; gr++) {
      mbar_wait(sb + O_BAR + gr * 8, n & 1);
      if (gr == 0) { PROF(1); if ((threadIdx.x & 127) == 0) T3(13 + WG); __syncwarp(); }
      if (gr == (WG == 0 ? OTURN : 4) && (WG < 2 || n + 1 < STEPS)) bar_arrive(B_V + (WG + 1) % 3, 256);
      wg_fence();
#pragma unroll
      for (int ks = gr * 8; ks < gr * 8 + 8 - 2 * FASTG; ks++) {
        const uint64_t db = desc_sw128(O_RING + (ks >> 2) * 8192 + (ks & 3) * 32);
        if (ks == 0) wg_rs64<0>(d, a, db);
        else if (!(ks % 5 & 1)) wg_rs64<1>(d, a + (ks / 5 * 3 + ks % 5 / 2) * 4, db);
        else wg_ss64<1>(d, desc_sw128(O_W + WG * 40960 + (ks / 5 * 2 + ks % 5 / 2) * 2048), db);
      }
      if (gr == 4 && nc == 11) {
#pragma unroll
        for (int ks = 40; ks < 44; ks++)
          wg_ss64<1>(d, desc_sw128(O_W + WG * 40960 + (ks - 24) * 2048), desc_sw128(O_RING + 10 * 8192 + (ks & 3) * 32));
      }
      wg_commit();
      if (gr > 0) { wg_wait<1>(); if (lane == 0) mbar_arrive(sb + O_BAR + 128 + (gr - 1) * 8); }
    }
    wg_wait<0>();
    if (lane == 0) mbar_arrive(sb + O_BAR + 128 + 4 * 8);
    if ((threadIdx.x & 127) == 0) T3(WG == 0 ? 1 : WG == 1 ? 8 : 12);
    __syncwarp();
    PROF(2);
#pragma unroll
    for (int sl = 0; sl < 2; sl++) {
      mbar_wait(sb + OB_ST + WG * 16 + sl * 8, (n & 1) ^ (WG == 0));
#pragma unroll
      for (int nb = sl * 4; nb < sl * 4 + 4; nb++) {
        sts32(st0 + nb * 2048, __float_as_uint(d[nb * 4]));
        sts32(st0 + nb * 2048 + 256, __float_as_uint(d[nb * 4 + 1]));
        sts32((st0 ^ 32) + nb * 2048, __float_as_uint(d[nb * 4 + 2]));
        sts32((st0 ^ 32) + nb * 2048 + 256, __float_as_uint(d[nb * 4 + 3]));
      }
      fence_async_smem();
      bar_arrive((sl ? B_G : B_M) + WG, 160);
    }
    PROF(3);
  }
}

__device__ __forceinline__ void o_aux(const Params& P, uint32_t sb) {
  const int i = bid() - N_CHAIN - N_G, ksl = i / 3;
  const int c0 = ksl * 11 - max(ksl - 4, 0), nc = ksl < 4 ? 11 : 10;
  const int lane = threadIdx.x & 31, w = __shfl_sync(~0u, (threadIdx.x >> 5) & 3, 0);
  if (w == 0) {
    bar_sync(B_INIT, 416);
    const uint32_t* f = g_fl + FL_O + near_half(XB_F + 1, bid()) * 1024 + min((c0 & ~1) + lane, (c0 + nc - 1) | 1);
#pragma unroll 1
    for (int n = 0; n < STEPS; n++) {
      const unsigned char* src = g_oimg + (uint32_t)(((n % RING) * N_CHAIN + c0) * 8192);
      if (!NOCHAIN) wait_flags(f, n + 1);
      fence_async_global();
      if (lane == 0) T3(0);
#pragma unroll
      for (int gr = 0; gr < 5; gr++) {
        const uint32_t full = sb + O_BAR + gr * 8, bytes = ABL & 4 ? 16 : (gr < 4 ? 2 : nc - 8) * 8192;
        mbar_wait(full + 128, (n & 1) ^ 1);
        if (elect()) {
          mbar_expect(full, bytes);
          bulk_load(sb + O_RING + gr * 16384, src + gr * 16384, bytes, full);
        }
      }
    }
  } else {
#pragma unroll 1
    for (int n = 0; n < STEPS; n++) {
      float* dst = g_oacc + (uint32_t)((n % ARING) * (64 * DM) + ((i % 3) * 3 + (w - 1 + ksl) % 3) * 1024);
      const bool early = w == 3 && n < NSEG;
      bar_sync(B_M + (w - 1), 160);
      if (lane == 0) {
        T3(w * 2);
        if (n < NSEG && !(ABL & 8)) { bulk_reduce(dst, sb + O_ST, 4096); bulk_reduce(dst + 16 * DM, sb + O_ST + 4096, 4096); }
        asm volatile("cp.async.bulk.commit_group;" ::: "memory");
        if (early) {
          asm volatile("cp.async.bulk.wait_group.read 0;" ::: "memory");
          mbar_arrive(sb + OB_ST);
          T3(8 + w);
          bulk_done_inc(g_fl + FL_OCNT + (n % OCRING) * 8);
          T3(w * 2 + 1);
        }
      }
      __syncwarp();
      bar_sync(B_G + (w - 1), 160);
      if (lane == 0) {
        if (n >= LAG && !(ABL & 8)) { bulk_reduce(dst + 32 * DM, sb + O_ST + 8192, 4096); bulk_reduce(dst + 48 * DM, sb + O_ST + 12288, 4096); }
        asm volatile("cp.async.bulk.commit_group;\ncp.async.bulk.wait_group.read 1;" ::: "memory");
        if (!early) mbar_arrive(sb + OB_ST + (w % 3) * 16);
        asm volatile("cp.async.bulk.wait_group.read 0;" ::: "memory");
        mbar_arrive(sb + OB_ST + (w % 3) * 16 + 8);
        if (!early) {
          T3(8 + w);
          bulk_done_inc(g_fl + FL_OCNT + (n % OCRING) * 8);
          T3(w * 2 + 1);
        }
      }
      __syncwarp();
    }
  }
}

__device__ __forceinline__ void f_role(const Params& P, uint32_t sb) {
  const int lane = threadIdx.x & 31, w = __shfl_sync(~0u, threadIdx.x >> 5, 0), r0 = (bid() - N_CHAIN - N_G - N_O) * 16;
  if (threadIdx.x < 128) wait_flag(g_lnflag + threadIdx.x * 8, 2);
  __syncthreads();
  if (w == 8) {
    const uint32_t* fo = g_fl + FL_OCNT + near_half(XB_F, bid()) * 1024;
    fence_async_global();
#pragma unroll 1
    for (int n = 0; n < NSEG; n++) {
      if (n > 0) bar_sync(2, 288);
      if (elect()) {
        mbar_expect(sb + F_BAR, 36864);
        bulk_load(sb + F_XY, g_x1 + (size_t)(n * 32 + r0) * DM, 18432, sb + F_BAR);
        bulk_load(sb + F_XY + 18432, g_y + (size_t)(n * 32 + r0) * DM, 18432, sb + F_BAR);
        mbar_expect(sb + F_BAR + 8, 36864);
        T3(1);
      }
      wait_flags(fo + (n % OCRING) * 8, NOCHAIN == 5 ? 0 : N_O * 3 * (n / OCRING + 1));
      fence_async_global();
      if (elect()) { bulk_load(sb + F_A, g_oacc + (uint32_t)((n % ARING) * (64 * DM) + r0 * DM), 36864, sb + F_BAR + 8); T3(0); }
    }
  } else if (w == 9) {
#pragma unroll 1
    for (int n = 0; n < NSEG; n++) {
      const uint32_t st = sb + (n & 1) * 36864;
      unsigned char* p = g_lnimg + (uint32_t)((NSEG + n) * 36864 + r0 * 128);
      bar_sync(1, 288);
      if (elect()) {
        T3(2);
#pragma unroll
        for (int i = 0; i < 9; i++) bulk_store(p + i * 4096, st + F_L + i * 2048, 2048);
        asm volatile("cp.async.bulk.commit_group;" ::: "memory");
        bulk_done_inc(g_fl + FL_F + (bid() & 1) * 8);
        T3(3);
        bulk_store(P.out + (size_t)(n * 32 + r0) * DM, st + F_X, 18432);
        asm volatile("cp.async.bulk.commit_group;\ncp.async.bulk.wait_group.read 0;" ::: "memory");
        if (n + 1 == NSEG) bulk_done_inc(g_fl + FL_F + (bid() & 1) * 8);
      }
      __syncwarp();
    }
  } else if (w < 8) {
    const uint32_t row = sb + w * 1152 + lane * 4, acc = sb + F_A + w * 256 + (lane ^ ((w & 6) * 2)) * 8;
    const uint32_t ln = sb + F_L + w * 128 + (((lane >> 2) ^ w) << 4) + (lane & 3) * 4;
#pragma unroll 1
    for (int n = 0; n < NSEG; n++) {
      const uint32_t st = (n & 1) * 36864;
      uint32_t x[18], y[18], l[18];
      mbar_wait(sb + F_BAR, n & 1);
#pragma unroll
      for (int i = 0; i < 18; i++) { x[i] = lds32(row + F_XY + i / 9 * 9216 + i % 9 * 128); y[i] = lds32(row + F_XY + 18432 + i / 9 * 9216 + i % 9 * 128); }
      mbar_wait(sb + F_BAR + 8, n & 1);
      if (threadIdx.x == 0) T3(4);
      __syncwarp();
      uint2 a[18];
#pragma unroll
      for (int i = 0; i < 18; i++) a[i] = lds64(acc + i / 9 * 2048 + i % 9 * 4096);
#pragma unroll
      for (int i = 0; i < 18; i++) x[i] = badd2(x[i], pack2(__uint_as_float(a[i].x), __uint_as_float(a[i].y)));
      if (n + 1 < NSEG) bar_arrive(2, 288);
      layernorm9<2>(x, l);
#pragma unroll
      for (int i = 0; i < 18; i++) { x[i] = badd2(x[i], bmul2(l[i], y[i])); sts32(row + st + F_X + i / 9 * 9216 + i % 9 * 128, x[i]); }
      layernorm9<2>(x, l);
#pragma unroll
      for (int i = 0; i < 18; i++) sts32(ln + st + i / 9 * 1024 + i % 9 * 2048, l[i]);
      fence_async_smem();
      bar_sync(1, 288);
    }
  }
}

constexpr uint32_t P_CH = 147456, P_CHSZ = 12800, P_H = 4352, P_Y = P_CH;
static_assert(P_CH + 5 * P_CHSZ + 8192 <= SMEM_BYTES, "prologue smem");

template <int N>
__device__ __forceinline__ void conv_fold(float (*acc)[4], bool hi, uint32_t mine, uint32_t theirs, int bar, int cnt) {
#pragma unroll
  for (int i = 0; i < N / 2; i++) {
    uint4 v;
    v.x = __float_as_uint(hi ? acc[i][0] : acc[i + N / 2][0]); v.y = __float_as_uint(hi ? acc[i][1] : acc[i + N / 2][1]);
    v.z = __float_as_uint(hi ? acc[i][2] : acc[i + N / 2][2]); v.w = __float_as_uint(hi ? acc[i][3] : acc[i + N / 2][3]);
    sts128(mine + i * 512, v);
  }
  bar_sync(bar, cnt);
#pragma unroll
  for (int i = 0; i < N / 2; i++) {
    const uint4 v = lds128(theirs + i * 512);
    acc[i][0] = (hi ? acc[i + N / 2][0] : acc[i][0]) + __uint_as_float(v.x); acc[i][1] = (hi ? acc[i + N / 2][1] : acc[i][1]) + __uint_as_float(v.y);
    acc[i][2] = (hi ? acc[i + N / 2][2] : acc[i][2]) + __uint_as_float(v.z); acc[i][3] = (hi ? acc[i + N / 2][3] : acc[i][3]) + __uint_as_float(v.w);
  }
}
template <int N>
__device__ __forceinline__ void conv_store(const float (*acc)[4], int tile0, uint32_t su, int d, uint32_t dd) {
  const int lane = threadIdx.x & 31, g = lane >> 2, tq = lane & 3;
#pragma unroll
  for (int i = 0; i < N; i++) {
    const uint32_t ad = su + (8 + (tile0 + i) * 8 + g) * 32 + tq * 4, sw = (g & 4) << 2;
    const uint32_t lo = badd2(movmat(pack2(acc[i][0], acc[i][1])), bmul2(lds32(ad + sw), dd));
    const uint32_t hi = badd2(movmat(pack2(acc[i][2], acc[i][3])), bmul2(lds32(ad + (sw ^ 16)), dd));
    ((uint2*)(g_yT + (size_t)d * SEQ))[(tile0 + i) * 32 + lane] = make_uint2(lo, hi);
  }
}

__device__ __forceinline__ void store_xy(uint32_t stage, int tile) {
  asm volatile("cp.async.bulk.global.shared::cta.bulk_group [%0], [%1], 18432;" :: "l"(g_y + (size_t)tile * 16 * DM), "r"(stage) : "memory");
  asm volatile("cp.async.bulk.global.shared::cta.bulk_group [%0], [%1], 18432;" :: "l"(g_x1 + (size_t)tile * 16 * DM), "r"(stage + 18432) : "memory");
  asm volatile("cp.async.bulk.commit_group;" ::: "memory");
}

__device__ __forceinline__ void prologue(const Params& P, uint32_t sb) {
  const int b = bid(), tid = threadIdx.x, lane = tid & 31, warp = tid >> 5, t0 = b * 16;
  const int chb = b, nch = chb < DM - 4 * N_CTA ? 5 : 4;
  if (tid < 288) {
    if (b < 128) {
      const int c = (tid >> 1) * 4, tt = t0 + (tid & 1) * 8;
      uint2 kr[11], vr[8];
#pragma unroll
      for (int i = 0; i < 11; i++) { const int t = tt + i - 3; kr[i] = t >= 0 ? __ldg((const uint2*)(P.K + (size_t)t * DM + c)) : make_uint2(0, 0); }
#pragma unroll
      for (int i = 0; i < 8; i++) vr[i] = __ldg((const uint2*)(P.V + (size_t)(tt + i) * DM + c));
#pragma unroll
      for (int e = 0; e < 2; e++) {
        const uint4 sh = __ldg((const uint4*)(P.shift + c * 4) + e);
        const uint32_t s0 = __byte_perm(sh.x, sh.z, 0x5410), s1 = __byte_perm(sh.x, sh.z, 0x7632);
        const uint32_t s2 = __byte_perm(sh.y, sh.w, 0x5410), s3 = __byte_perm(sh.y, sh.w, 0x7632);
        uint32_t v[8];
#pragma unroll
        for (int i = 0; i < 8; i++) {
          const uint32_t k3 = e ? kr[i].y : kr[i].x, k2 = e ? kr[i + 1].y : kr[i + 1].x, k1 = e ? kr[i + 2].y : kr[i + 2].x, k0 = e ? kr[i + 3].y : kr[i + 3].x;
          v[i] = bmul2(badd2(badd2(badd2(bmul2(k3, s3), bmul2(k2, s2)), bmul2(k1, s1)), bmul2(k0, s0)), e ? vr[i].y : vr[i].x);
        }
        *(uint4*)(g_kvT + (size_t)(c + 2 * e) * SEQ + tt) =
          make_uint4(__byte_perm(v[0], v[1], 0x5410), __byte_perm(v[2], v[3], 0x5410), __byte_perm(v[4], v[5], 0x5410), __byte_perm(v[6], v[7], 0x5410));
        *(uint4*)(g_kvT + (size_t)(c + 2 * e + 1) * SEQ + tt) =
          make_uint4(__byte_perm(v[0], v[1], 0x7632), __byte_perm(v[2], v[3], 0x7632), __byte_perm(v[4], v[5], 0x7632), __byte_perm(v[6], v[7], 0x7632));
      }
    }
  } else if (tid < 384) {
    const int t = tid - 288;
    for (int i = t; i < 32 * nch; i += 96) asm volatile("prefetch.global.L2 [%0];" :: "l"(P.Hk + (size_t)(chb + (i >> 5) * N_CTA) * SEQ + (i & 31) * 64));
    for (int i = b * 96 + t; i < 32 * DM; i += N_CTA * 96) ((uint4*)g_oacc)[i] = make_uint4(0, 0, 0, 0);
    if (b * 96 + t < 128 * 8) g_lnflag[b * 96 + t] = 0;
    if (t == 95) sts32(sb + S_GEN, ld_acquire(g_gbar));
  }
  if (warp < 12) {
    bar_sync(6, 384);
    if (tid == 128) TS(14);
    if (tid == 0) grid_arrive(0);
    if (tid == 0) TS(1);
  }
  if (warp < 12) {
    const bool quad = warp >= 8;
    const int ch = quad ? 4 : warp >> 1, sub = quad ? warp - 8 : warp & 1, nthr = quad ? 128 : 64, d = chb + ch * N_CTA;
    const uint32_t su = sb + P_CH + ch * P_CHSZ;
    if (ch < nch) {
      const uint32_t* hs = (const uint32_t*)(P.Hk + (size_t)d * SEQ);
#pragma unroll 4
      for (int q = sub * 32 + lane; q < 256; q += nthr) {
        const uint4 c = __ldg((const uint4*)hs + q);
        const uint32_t prev = q ? __ldg(hs + 4 * q - 1) : 0u;
        sts128(su + P_H + 32 + q * 16, make_uint4(__byte_perm(c.x, prev, 0x7610), __byte_perm(c.y, c.x, 0x7610), __byte_perm(c.z, c.y, 0x7610), __byte_perm(c.w, c.z, 0x7610)));
        sts128(su + P_H + 4224 + q * 16, make_uint4(__byte_perm(c.x, 0, 0x1032), __byte_perm(c.y, 0, 0x1032), __byte_perm(c.z, 0, 0x1032), __byte_perm(c.w, 0, 0x1032)));
      }
      if (sub == 1 && lane == 0) sts32(su + P_CHSZ - 16, __bfloat16_as_ushort(P.Dk[d]) * 0x10001u);
      if (sub == 0 && lane < 20) sts128(su + (lane < 16 ? lane * 16 : P_H + (lane & 2) * 2096 + (lane & 1) * 16), make_uint4(0, 0, 0, 0));
    }
    if (tid == 0) grid_wait(0, lds32(sb + S_GEN));
    bar_sync(6, 384);
    if (ch < nch) {
#pragma unroll 4
      for (int q = sub * 32 + lane; q < 256; q += nthr) {
        const int row = (q >> 1) + 8;
        sts128(su + row * 32 + (((q & 1) ^ ((row >> 2) & 1)) << 4), __ldcg((const uint4*)(g_kvT + (size_t)d * SEQ) + q));
      }
    }
    bar_arrive(8, 416);
    if (ch < nch) {
      bar_sync(1 + ch, nthr);
      if (tid == 0) TS(11);
      const int g = lane >> 2, tq = lane & 3;
      const uint32_t sh = su + P_H + (g & 1) * 4192 + (8 + (g >> 1) - tq) * 4;
      float acc[16][4];
#pragma unroll
      for (int i = 0; i < 16; i++) { acc[i][0] = acc[i][1] = acc[i][2] = acc[i][3] = 0.f; }
      const int nres = quad ? 2 : 4;
#pragma unroll 1
      for (int res = sub * nres; res < sub * nres + nres; res++) {
        uint32_t bf[16][2];
        const int row = 8 - res + ((lane >> 4) << 3) + (lane & 7);
        const uint32_t ad = su + row * 32 + ((((lane >> 3) & 1) ^ ((row >> 2) & 1)) << 4);
#pragma unroll
        for (int f = 0; f < 16; f += 2) ldsm4(bf[f][0], bf[f][1], bf[f + 1][0], bf[f + 1][1], ad + f * 256);
#pragma unroll
        for (int jj = 0; jj < 16; jj++) {
          const uint32_t ah = sh + (8 * jj + res) * 32;
          const uint32_t r0 = lds32(ah), r1 = lds32(ah + 16), rm = lds32(ah - 16);
#pragma unroll
          for (int i = jj; i < 16; i++) mma16(acc[i], r0, r1, rm, r0, bf[i - jj][0], bf[i - jj][1]);
        }
      }
      bar_sync(1 + ch, nthr);
      if (tid == 0) TS(12);
      const uint32_t xb = su + P_H + lane * 16, dd = lds32(su + P_CHSZ - 16);
      if (quad) bar_sync(1 + ch, nthr);
      conv_fold<16>(acc, sub & 1, xb + sub * 4096, xb + (sub ^ 1) * 4096, 1 + ch, nthr);
      if (quad) {
        bar_sync(1 + ch, nthr);
        conv_fold<8>(acc, sub & 2, xb + sub * 4096, xb + (sub ^ 2) * 4096, 1 + ch, nthr);
        conv_store<4>(acc, (sub & 1) * 8 + (sub & 2) * 2, su, d, dd);
      } else {
        conv_store<8>(acc, sub * 8, su, d, dd);
      }
    }
    bar_sync(9, 512);
    if (tid == 0) grid_arrive(1);
  } else {
    for (int i = b; i < 194 + MRING * 5; i += N_CTA) {
      const int n = (i - 194) / 5, r = (i - 194) % 5, blk = i < 192 ? i / 6 * 8 + i % 6 : i < 194 ? XB_F + i - 192 : XB_M + n * 8 + r;
      const uint32_t fill = i < 194 ? 0u : SENT;
#pragma unroll
      for (int k = 0; k < 2; k++) {
        const int q = (tid & 127) + k * 128;
        uint4 v = make_uint4(fill, fill, fill, fill);
        if (i >= 194 && (n == 0 || (n <= LAG && ((q ^ (q >> 3)) & 1))) && (r > 0 || k == 0)) {
          const bf16* m = P.mem0 + (max(r * 8 - 4, 0) + (q >> 5)) * 16 + ((q >> 1) & 1) * 8 + ((q >> 2) & 7);
          v.x = pack2(__bfloat162float(m[0]), __bfloat162float(m[DM])); v.y = pack2(__bfloat162float(m[2 * DM]), __bfloat162float(m[3 * DM]));
          v.z = pack2(__bfloat162float(m[4 * DM]), __bfloat162float(m[5 * DM])); v.w = pack2(__bfloat162float(m[6 * DM]), __bfloat162float(m[7 * DM]));
        }
        g_xb[blk * 512 + q] = v;
        g_xb[blk * 512 + 256 + q] = v;
      }
    }
    if (tid >= 448 && tid < 451) { mbar_init(sb + W_BAR + (tid - 448) * 8, 1); fence_async_smem(); }
    if (tid < 388) g_xb[XB_REF * 512 + (tid & 2) * 128 + (b & ~1) + (tid & 1)] = make_uint4(0, 0, 0, 0);
    else if (tid < 392 && b < N_GRP) g_xb[(b * 8 + 7) * 512 + (tid & 2) * 128 + (tid & 1)] = make_uint4(0, 0, 0, 0);
    bar_sync(7, 128);
    TS(8);
    if (warp == 12) {
      bar_sync(8, 416);
      if (lane == 16 && b < 128) asm volatile("cp.async.bulk.prefetch.L2.global [%0], 18432;" :: "l"(P.X + (size_t)t0 * DM) : "memory");
      if (lane < 16 && b < 128) {
        const bf16* w = (lane & 12) == 0 ? P.Wk : (lane & 12) == 4 ? P.Wq : (lane & 12) == 8 ? P.Wv : P.Wo;
        asm volatile("cp.async.bulk.prefetch.L2.global [%0], 9216;" :: "l"(w + (size_t)(b * 4 + (lane & 3)) * 4608) : "memory");
      }
      wait_until(clk(), b >= N_CHAIN && b < N_CHAIN + N_G ? S1G : S1DLY);
    } else if (lane == 0) {
      if (warp == 13 || (warp == 14 && b < N_GRP)) {
        uint32_t* p = (uint32_t*)(g_xb + (warp == 13 ? XB_REF * 512 + b : (b * 8 + 7) * 512));
        int votes = 0;
        for (int rep = 0; rep < 24 && abs(votes) < 7; rep++) {
          uint32_t v0, v1, c0, c1;
          asm volatile("atom.relaxed.gpu.global.add.u32 %0, [%4], 0;\n atom.relaxed.gpu.global.add.u32 %1, [%5], 0;\n"
                       "{.reg .pred p; setp.eq.u32 p, %0, 0x7ffffff3; @p trap; mov.u32 %2, %%clock; setp.eq.u32 p, %1, 0x7ffffff3; @p trap; mov.u32 %3, %%clock;}"
                       : "=&r"(v0), "=&r"(v1), "=&r"(c0), "=&r"(c1) : "l"(p + (rep & 1) * 1024), "l"(p + ((rep & 1) ^ 1) * 1024) : "memory");
          votes += ((c1 - c0 > 80u) == (rep & 1)) ? 1 : -1;
        }
        if (warp == 13) g_side[b] = votes > 0; else g_near[b] = votes > 0;
      }
    }
    __syncwarp();
    bar_sync(7, 128);
    bar_arrive(9, 512);
    TS(9);
    const int nwg = b < N_CHAIN + N_G ? 2 : b < N_CTA - N_F ? 3 : 0;
    for (int k = 0; k < nwg; k++) load_wg(P, sb, true, k);
    TS(10);
  }
  if (tid == 0) TS(2);
  if (b < N_CHAIN || b >= N_CHAIN + N_G) {
    const bool isf = b >= N_CTA - N_F;
    const int first = b < N_CHAIN ? b + 2 : isf ? b - (N_CTA - N_F) : b - N_G + 2, last = isf ? 128 : 120;
    auto next = [&](int tile) { return b < N_CHAIN ? 128 : !isf ? tile + N_O : tile < 2 ? tile + 120 : tile + 2; };
    uint32_t st = sb + P_Y;
#pragma unroll 1
    for (int tile = first; tile < last; tile = next(tile), st = 2 * (sb + P_Y) + 36864 - st) {
      uint32_t x[9], l[9];
      const int tok = tile * 16 + warp;
#pragma unroll
      for (int i = 0; i < 9; i++) x[i] = __ldg((const uint32_t*)(P.X + (size_t)tok * DM) + i * 32 + lane);
      layernorm9<1>(x, l);
      if (tile == first) { if (tid == 0) grid_wait(1, lds32(sb + S_GEN)); }
      else if (tid == 511) asm volatile("cp.async.bulk.wait_group.read 1;" ::: "memory");
      __syncthreads();
      if (tid == 0) TS(13);
      if (tid < 288) {
        uint4 y[4];
#pragma unroll
        for (int e = 0; e < 4; e++) y[e] = __ldcg((const uint4*)(g_yT + (size_t)((tid >> 1) * 4 + e) * SEQ + tile * 16) + (tid & 1));
#pragma unroll
        for (int i = 0; i < 4; i++) {
          const uint32_t w0 = ((const uint32_t*)&y[0])[i], w1 = ((const uint32_t*)&y[1])[i], w2 = ((const uint32_t*)&y[2])[i], w3 = ((const uint32_t*)&y[3])[i];
          const uint32_t ad = st + ((tid & 1) * 4 + (i >> 1) * 2 + (i & 1) * 8) * 1152 + (tid >> 1) * 8;
          sts64(ad, __byte_perm(w0, w1, 0x5410), __byte_perm(w2, w3, 0x5410));
          sts64(ad + 1152, __byte_perm(w0, w1, 0x7632), __byte_perm(w2, w3, 0x7632));
        }
      }
      __syncthreads();
#pragma unroll
      for (int i = 0; i < 9; i++) {
        x[i] = badd2(x[i], bmul2(l[i], lds32(st + warp * 1152 + i * 128 + lane * 4)));
        sts32(st + 18432 + warp * 1152 + i * 128 + lane * 4, x[i]);
      }
      layernorm9<1>(x, l);
      store_ln_row(0, tok, l);
      fence_async_smem();
      __syncthreads();
      if (b >= N_CHAIN && tid == 511) { if (tile < 2) st_release(g_lnflag + tile * 8, 1); store_xy(st, tile); }
    }
    if (b >= N_CHAIN && tid == 511) {
      asm volatile("cp.async.bulk.wait_group 0;\nfence.acq_rel.gpu;" ::: "memory");
      for (int tile = first; tile < last; tile = next(tile)) st_relaxed_if(g_lnflag + tile * 8, 2, true);
    }
    if (tid == 0) TS(15);
  }
  __syncthreads();
}

__device__ __forceinline__ void publish_prologue(uint32_t sb) {
  if (threadIdx.x < 416) return;
  if (threadIdx.x == 511) {
    st_release(g_lnflag + (bid() + 2) * 8, 1);
    store_xy(sb + P_Y, bid() + 2);
    asm volatile("cp.async.bulk.wait_group.read 0;" ::: "memory");
  }
  __syncwarp();
  if (threadIdx.x >= 480) bar_arrive(B_R, 64);
  bar_sync(B_INIT, 352);
  if (threadIdx.x == 511) asm volatile("cp.async.bulk.wait_group 0;" ::: "memory");
  if (threadIdx.x == 511) st_release(g_lnflag + (bid() + 2) * 8, 2);
  __syncwarp();
}

__global__ void __cluster_dims__(2, 1, 1) __launch_bounds__(512, 1) k_main(const __grid_constant__ Params P) {
  extern __shared__ __align__(1024) unsigned char smem[];
  const uint32_t sb = (uint32_t)__cvta_generic_to_shared(smem);
  const int b = bid(), wg = threadIdx.x >> 7;
  TS(0);
  prologue(P, sb);
  TS(3);
  if (threadIdx.x == 0) {
    if ((sb & 0xFFFFFF) != SBASE) __trap();
    if (b < N_CHAIN) {
      mbar_init(sb + CB_FULL, 1); mbar_init(sb + CB_FULL + 8, 1);
      mbar_init(sb + CB_REF, 1);
      mbar_init(sb + CB_SX, 1); mbar_init(sb + CB_OX, 1); mbar_init(sb + CB_XX, 1); mbar_init(sb + CB_Q, 1); mbar_init(sb + CB_VF, 1); mbar_init(sb + CB_VF + 8, 1);
      sts32(sb + C_BAD, 0);
      for (int i = 0; i < 11; i++) mbar_init(sb + CB_M + i * 8, i == 0 ? 5 : i == 5 ? 2 : 1);
    } else if (b < N_CHAIN + N_G) {
      for (int i = 0; i < 9; i++) { mbar_init(sb + G_BAR + i * 8, 2); mbar_init(sb + G_BAR + 128 + i * 8, 8); }
    } else if (b < N_CHAIN + N_G + N_O) {
      for (int i = 0; i < 5; i++) { mbar_init(sb + O_BAR + i * 8, 1); mbar_init(sb + O_BAR + 128 + i * 8, 12); }
      for (int i = 0; i < 6; i++) mbar_init(sb + OB_ST + i * 8, 1);
    } else {
      mbar_init(sb + F_BAR, 1); mbar_init(sb + F_BAR + 8, 1);
    }
    asm volatile("fence.mbarrier_init.release.cluster;" ::: "memory");
  }
  fence_async_smem();
  __syncthreads();
  cluster_sync();
  if (NOCHAIN && b < N_CHAIN) {
    if (threadIdx.x == 511) { store_xy(sb + P_Y, b + 2); asm volatile("cp.async.bulk.wait_group 0;" ::: "memory"); st_release(g_lnflag + (b + 2) * 8, 2); }
  } else if ((NOCHAIN == 2 && b >= N_CHAIN + N_G) || (NOCHAIN >= 3 && NOCHAIN < 6 && b < N_CHAIN + N_G) || ((NOCHAIN == 4 || NOCHAIN == 6) && b >= N_CTA - N_F) || (NOCHAIN == 5 && b < N_CTA - N_F)) {
  } else if (b < N_CHAIN) {
    if (wg < 2) { reg_inc<192>(); chain_proj(P, sb); }
    else if (wg == 2) { reg_dec<ATTR>(); chain_attn(P, sb); }
    else { reg_dec<128 - ATTR>(); publish_prologue(sb); chain_aux(P, sb); }
  } else if (NOBULK) {
    {
      if (wg == 0) {
        float d[4] = {0.f, 0.f, 0.f, 0.f};
        for (int n = 0; n < STEPS - 1; n++) {
          const uint32_t* f = g_fl + FL_TICK;
          uint32_t x;
          do { for (int k = 0; k < 16; k++) mma16(d, 0, 0, 0, 0, 0, 0); asm volatile("ld.relaxed.gpu.global.u32 %0, [%1];" : "=r"(x) : "l"(f) : "memory"); } while ((x >> 24) <= n);
          const int q = (b - N_CHAIN) * 4 + (threadIdx.x >> 5);
          if (n + 5 >= MRING && q < 80) fill16((uint4*)g_mimg + (uint32_t)(((n + 5) % MRING) * 4096 + q * 32 + (threadIdx.x & 31)), SENT);
        }
        if (d[0] == 1.f) P.out[0] = __float2bfloat16(0.f);
      }
    }
  } else if (b < N_CHAIN + N_G) {
    if (wg == 0) { reg_inc<232>(); g_math<0>(P, sb); PROF_DUMP(); }
    else if (wg == 1) { reg_inc<232>(); g_math<1>(P, sb); PROF_DUMP(); }
    else if (wg == 2) { reg_dec<24>(); g_aux(P, sb); }
    else { reg_dec<24>(); g_load(P, sb); }
  } else if (b < N_CHAIN + N_G + N_O) {
    if (wg == 0) { reg_inc<160>(); o_math<0>(P, sb); PROF_DUMP(); }
    else if (wg == 1) { reg_inc<160>(); o_math<1>(P, sb); PROF_DUMP(); }
    else if (wg == 2) { reg_inc<160>(); o_math<2>(P, sb); PROF_DUMP(); }
    else { reg_dec<32>(); o_aux(P, sb); }
  } else {

    f_role(P, sb);
  }
}

}

extern "C" void kernel_launch(void* const* d_in, const int* in_sizes, int n_in, void* d_out, int out_size) {
  typedef CUresult (*Encode)(CUtensorMap*, CUtensorMapDataType, cuuint32_t, void*, const cuuint64_t*, const cuuint64_t*, const cuuint32_t*, const cuuint32_t*,
                             CUtensorMapInterleave, CUtensorMapSwizzle, CUtensorMapL2promotion, CUtensorMapFloatOOBfill);
  static Encode encode = nullptr;
  if (!encode) cudaGetDriverEntryPoint("cuTensorMapEncodeTiled", (void**)&encode, cudaEnableDefault);
  Params P;
  for (int i = 0; i < 8; i++) {
    const cuuint64_t cols = i < 6 ? HD : DM, rows = HD + DM - cols, pitch = cols * 2;
    const cuuint64_t dim[3][5] = {{cols, 2, 8, 1, rows / 16}, {cols, 16, 1, 1, rows / 16}, {cols, 2, 4, 4, rows / 32}};
    const cuuint64_t stride[3][4] = {{8 * pitch, pitch, pitch, 16 * pitch}, {pitch, pitch, pitch, 16 * pitch}, {pitch, 8 * pitch, 2 * pitch, 32 * pitch}};
    const cuuint32_t box[3][5] = {{64, 2, 8, 1, 1}, {64, 16, 1, 1, 1}, {64, 2, 4, 2, 1}}, one[5] = {1, 1, 1, 1, 1};
    const int k = i < 3 ? 0 : i < 7 ? 1 : 2;
    encode(&P.map[i], CU_TENSOR_MAP_DATA_TYPE_BFLOAT16, 5, d_in[i < 6 ? 8 + i % 3 : 11], dim[k], stride[k], box[k], one,
           CU_TENSOR_MAP_INTERLEAVE_NONE, CU_TENSOR_MAP_SWIZZLE_128B, CU_TENSOR_MAP_L2_PROMOTION_L2_128B, CU_TENSOR_MAP_FLOAT_OOB_FILL_NONE);
  }
  P.X = (const bf16*)d_in[0]; P.K = (const bf16*)d_in[1]; P.V = (const bf16*)d_in[2];
  P.shift = (const bf16*)d_in[3]; P.Hk = (const bf16*)d_in[4]; P.Dk = (const bf16*)d_in[5];
  P.mem0 = (const bf16*)d_in[7];
  P.Wq = (const bf16*)d_in[8]; P.Wk = (const bf16*)d_in[9]; P.Wv = (const bf16*)d_in[10]; P.Wo = (const bf16*)d_in[11];
  P.out = (bf16*)d_out;
  for (int i = 0; i < 20; i++) P.dly[i] = h_dly[i];
  cudaFuncSetAttribute(k_main, cudaFuncAttributeMaxDynamicSharedMemorySize, SMEM_BYTES);
  k_main<<<N_CTA, 512, SMEM_BYTES>>>(P);
}
```

```cpp
#include <cuda.h>
#include <cuda_runtime.h>
#include <cuda_bf16.h>
#include <stdint.h>

namespace {

typedef __nv_bfloat16 bf16;

constexpr int SEQ = 2048, DM = 576, HD = 4096, NSEG = 64;
#define PLACE 1
#define LAGV 7
constexpr int LAG = LAGV, STEPS = NSEG + LAG, RING = 8;
static_assert(LAG < RING, "ring");
constexpr int N_CHAIN = 64, N_G = 48, N_O = 18, N_F = 2;
constexpr uint32_t SBASE = 1024;
constexpr uint32_t SENT = 0xFFFFFFFFu;
constexpr int SPIN_MAX = 1 << 22;

__device__ __forceinline__ uint32_t bid() {
  const uint32_t b = blockIdx.x;
  return b < 6 ? b + 106 : b < 8 ? b + 122 : b < 114 ? b - 8 : b < 130 ? b - 2 : b;
}
__device__ __forceinline__ uint32_t chain_id() { return blockIdx.x - (PLACE ? 8 : 0); }
constexpr int KVP = SEQ + 64;
__device__ __align__(1024) bf16 g_kvT[DM * KVP];
__device__ __align__(1024) bf16 g_yT[DM * SEQ];
__device__ __align__(1024) unsigned char g_lnimg[2 * NSEG * 9 * 4096];
__device__ __align__(1024) unsigned char g_qkv[RING * N_CHAIN * 24576];
__device__ __align__(1024) unsigned char g_oimg[RING * N_CHAIN * 8192];
constexpr int ARING = 16;
static_assert(ARING >= LAG + 9, "accumulator ring");
__device__ __align__(1024) float g_oacc[ARING * 64 * DM];
constexpr int MRING = LAG + 4, N_GRP = 32 + MRING + 1;
constexpr int XB_M = 256, XB_F = XB_M + MRING * 8, XB_REF = XB_F + 2, N_CTA = N_CHAIN + N_G + N_O + N_F;
__device__ __align__(65536) uint4 g_xb[N_GRP * 4096];
#define g_mimg ((uint32_t*)(g_xb + XB_M * 512))
__device__ uint32_t g_near[N_GRP];
__device__ uint32_t g_side[N_CTA];
__device__ __align__(128) uint32_t g_gbar[3 * 32];
constexpr int FL_G = 0, FL_F = 96 * 8, FL_OCNT = FL_F + 2 * 8, OCRING = 16, FL_TICK = 992, FL_O = 2048, FL_SYNC = FL_O + 128;
static_assert(FL_OCNT + OCRING * 8 <= FL_TICK, "flag block");
#define g_fl ((uint32_t*)(g_xb + XB_F * 512))
__device__ __align__(1024) uint32_t g_lnflag[128 * 8];
#define TS(slot)

#define OTURN 2
#define LOCK0 3
#define FASTG 0
#define NOBULK 0
#define VE 0
#define OGAP 2
#define NOCHAIN 0
#define BFENCE 2
#define ABL 0
#define ATTR 80
#define CNT(slot, tries)
#define T3(slot)
#define TR(slot)
#define TRV(slot, val)
#define TRD(slot, dep)
#define TRSYNC()
#define TRDUMP(n)
#define CLK(t) "{.reg .b64 x; .reg .b32 h; mov.u64 x, %%clock64; mov.b64 {" t ", h}, x;}"
__device__ __forceinline__ uint32_t clk() { uint32_t t; asm volatile(CLK("%0") : "=r"(t) :: "memory"); return t; }
__device__ __forceinline__ void wait_until(uint32_t t0, uint32_t d) {
  asm volatile("{.reg .pred p; .reg .u32 t;\n"
               "W: " CLK("t") " sub.u32 t, t, %0; setp.lt.s32 p, t, 0; @p bra.uni W;}"
               :: "r"(t0 + d) : "memory");
}
__device__ __forceinline__ uint32_t pack2(float lo, float hi) {
  uint32_t r; asm("cvt.rn.bf16x2.f32 %0, %1, %2;" : "=r"(r) : "f"(hi), "f"(lo)); return r;
}
__device__ __forceinline__ float bf_lo(uint32_t v) { return __uint_as_float(v << 16); }
__device__ __forceinline__ float bf_hi(uint32_t v) { return __uint_as_float(v & 0xFFFF0000u); }

__device__ __forceinline__ uint4 ld_relaxed4(const void* p) {
  uint4 v; asm volatile("ld.relaxed.gpu.global.v4.u32 {%0,%1,%2,%3}, [%4];" : "=r"(v.x), "=r"(v.y), "=r"(v.z), "=r"(v.w) : "l"(p) : "memory"); return v;
}
__device__ __forceinline__ void st_b128(void* p, uint32_t a, uint32_t b, uint32_t c, uint32_t d) {
  asm volatile("{.reg .b128 v; mov.b128 v, {%1,%2,%3,%4}; st.relaxed.gpu.global.b128 [%0], v;}" :: "l"(p), "r"(a), "r"(b), "r"(c), "r"(d) : "memory");
}
__device__ __forceinline__ void reload_b128(uint4& v, const void* p, uint32_t again) {
  asm volatile("{.reg .pred p; .reg .b128 v; setp.ne.u32 p, %5, 0; mov.b128 v, {%0,%1,%2,%3};\n"
               "@p ld.relaxed.gpu.global.b128 v, [%4]; mov.b128 {%0,%1,%2,%3}, v;}"
    : "+r"(v.x), "+r"(v.y), "+r"(v.z), "+r"(v.w) : "l"(p), "r"(again) : "memory");
}
__device__ __forceinline__ void reload4(uint4& v, const void* p, uint32_t again) {
  asm volatile("{.reg .pred p; setp.ne.u32 p, %5, 0; @p ld.relaxed.gpu.global.v4.u32 {%0,%1,%2,%3}, [%4];}"
    : "+r"(v.x), "+r"(v.y), "+r"(v.z), "+r"(v.w) : "l"(p), "r"(again) : "memory");
}
__device__ __forceinline__ void st_relaxed4(void* p, uint32_t a, uint32_t b, uint32_t c, uint32_t d) {
  asm volatile("st.relaxed.gpu.global.v4.u32 [%0], {%1,%2,%3,%4};" :: "l"(p), "r"(a), "r"(b), "r"(c), "r"(d) : "memory");
}
__device__ __forceinline__ void st_relaxed_if(void* p, uint32_t a, bool on) {
  asm volatile("{.reg .pred p; setp.ne.u32 p, %2, 0; @p st.relaxed.gpu.global.u32 [%0], %1;}" :: "l"(p), "r"(a), "r"((uint32_t)on) : "memory");
}
__device__ __forceinline__ uint32_t ld_acquire(const uint32_t* p) {
  uint32_t v; asm volatile("ld.acquire.gpu.global.u32 %0, [%1];" : "=r"(v) : "l"(p) : "memory"); return v;
}
__device__ __forceinline__ void st_release(uint32_t* p, uint32_t v) {
  asm volatile("st.release.gpu.global.u32 [%0], %1;" :: "l"(p), "r"(v) : "memory");
}
__device__ __forceinline__ void bulk_reduce(float* dst, uint32_t src, uint32_t bytes) {
  asm volatile("cp.reduce.async.bulk.global.shared::cta.bulk_group.add.f32 [%0], [%1], %2;" :: "l"(dst), "r"(src), "r"(bytes) : "memory");
}
__device__ __forceinline__ void bulk_done_inc(uint32_t* p) {
  asm volatile("cp.async.bulk.wait_group 0;\n"
               "fence.proxy.async.global;\nfence.release.gpu;\n"
               "red.relaxed.gpu.global.add.u32 [%0], 1;\nred.relaxed.gpu.global.add.u32 [%0+4096], 1;" :: "l"(p) : "memory");
}
__device__ __forceinline__ void flag_release(uint32_t* p, uint32_t v) {
  asm volatile("fence.release.gpu;\nst.relaxed.gpu.global.u32 [%0], %1;\nst.relaxed.gpu.global.u32 [%0+4096], %1;" :: "l"(p), "r"(v) : "memory");
}
__device__ __forceinline__ void spin_guard(int& it) {
  asm volatile("{.reg .pred p; add.s32 %0, %0, 1; setp.gt.s32 p, %0, %1; @p trap;}" : "+r"(it) : "n"(SPIN_MAX));
}
__device__ __forceinline__ void wait_flag(const uint32_t* p, uint32_t v) {
  int it = 0;
  while (ld_acquire(p) < v) spin_guard(it);
}
__device__ __forceinline__ void wait_flags(const uint32_t* p, uint32_t v) {
  int it = 0;
  while (true) {
    uint32_t x; asm volatile("ld.relaxed.gpu.global.u32 %0, [%1];" : "=r"(x) : "l"(p) : "memory");
    if (__all_sync(~0u, x >= v)) break;
    spin_guard(it);
  }
  asm volatile("fence.acquire.gpu;" ::: "memory");
}
__device__ __forceinline__ uint32_t timer_offset() {
  uint32_t g0, g;
  asm volatile("mov.u32 %0, %%globaltimer_lo;" : "=r"(g0) :: "memory");
  do { asm volatile("mov.u32 %0, %%globaltimer_lo;" : "=r"(g) :: "memory"); } while (g == g0);
  return (g >> 5) * 58 - clk();
}
__device__ __forceinline__ void grid_arrive(int i) {
  asm volatile("red.release.gpu.global.add.u32 [%0], %1;" :: "l"(g_gbar + i * 32), "r"(bid() ? 1u : 257u - N_CTA) : "memory");
}
__device__ __forceinline__ void grid_wait(int i, uint32_t gen) {
  int it = 0;
  while (((ld_acquire(g_gbar + i * 32) ^ gen) >> 8) == 0) spin_guard(it);
}
__device__ __forceinline__ bool elect() {
  uint32_t r; asm volatile("{.reg .pred p; elect.sync _|p, -1; selp.u32 %0, 1, 0, p;}" : "=r"(r)); return r;
}
__device__ __forceinline__ void bar_sync(int id, int cnt) { asm volatile("bar.sync %0, %1;" :: "r"(id), "r"(cnt) : "memory"); }
__device__ __forceinline__ void bar_arrive(int id, int cnt) { asm volatile("bar.arrive %0, %1;" :: "r"(id), "r"(cnt) : "memory"); }
template <int id, int cnt> __device__ __forceinline__ void bar_arrive_after(uint32_t a, uint32_t b) {
  asm volatile("{.reg .pred p; setp.ne.u32 p, %2, 0xfff12345; setp.ne.and.u32 p, %3, 0xfff12345, p; @p bar.arrive %0, %1;}" :: "n"(id), "n"(cnt), "r"(a), "r"(b) : "memory");
}
template <int id, int cnt> __device__ __forceinline__ void bar_sync_after(uint32_t a) {
  asm volatile("{.reg .pred p; setp.ne.u32 p, %2, 0xfff12345; @p bar.sync %0, %1;}" :: "n"(id), "n"(cnt), "r"(a) : "memory");
}
__device__ __forceinline__ void fence_async_smem() { asm volatile("fence.proxy.async.shared::cta;" ::: "memory"); }
__device__ __forceinline__ void fence_async_global() { asm volatile("fence.proxy.async.global;" ::: "memory"); }
__device__ __forceinline__ void mbar_init(uint32_t mb, int cnt) { asm volatile("mbarrier.init.shared::cta.b64 [%0], %1;" :: "r"(mb), "r"(cnt) : "memory"); }
__device__ __forceinline__ void mbar_arrive(uint32_t mb) { asm volatile("mbarrier.arrive.shared::cta.b64 _, [%0];" :: "r"(mb) : "memory"); }
__device__ __forceinline__ void mbar_arrive_after(uint32_t mb, uint32_t a, uint32_t lane) {
  asm volatile("{.reg .pred p; setp.ne.u32 p, %1, 0xfff12345; setp.eq.and.u32 p, %2, 0, p; @p mbarrier.arrive.shared::cta.b64 _, [%0];}" :: "r"(mb), "r"(a), "r"(lane) : "memory");
}
__device__ __forceinline__ void mbar_expect(uint32_t mb, uint32_t bytes) {
  asm volatile("mbarrier.arrive.expect_tx.shared::cta.b64 _, [%0], %1;" :: "r"(mb), "r"(bytes) : "memory");
}
__device__ __forceinline__ void mbar_wait_guard(uint32_t mb, uint32_t parity) {
  uint32_t ok; int it = 0;
  while (true) {
    asm volatile("{.reg .pred p; mbarrier.try_wait.parity.shared::cta.b64 p, [%1], %2; selp.u32 %0, 1, 0, p;}" : "=r"(ok) : "r"(mb), "r"(parity) : "memory");
    if (ok) break;
    spin_guard(it);
  }
}
__device__ __forceinline__ void mbar_wait(uint32_t mb, uint32_t parity) {
  asm volatile("{.reg .pred p;\nW: mbarrier.try_wait.parity.shared::cta.b64 p, [%0], %1;\n@!p bra W;}" :: "r"(mb), "r"(parity) : "memory");
}
__device__ __forceinline__ void bulk_load(uint32_t dst, const void* src, uint32_t bytes, uint32_t mb) {
  asm volatile("cp.async.bulk.shared::cluster.global.mbarrier::complete_tx::bytes [%0], [%1], %2, [%3];" :: "r"(dst), "l"(src), "r"(bytes), "r"(mb) : "memory");
}
__device__ __forceinline__ void bulk_store(void* dst, uint32_t src, uint32_t bytes) {
  asm volatile("cp.async.bulk.global.shared::cta.bulk_group [%0], [%1], %2;" :: "l"(dst), "r"(src), "r"(bytes) : "memory");
}
__device__ __forceinline__ void cp_async16(uint32_t dst, const void* src) {
  asm volatile("cp.async.cg.shared.global [%0], [%1], 16;" :: "r"(dst), "l"(src) : "memory");
}
__device__ __forceinline__ void cp_async_wait_all() { asm volatile("cp.async.wait_all;" ::: "memory"); }
__device__ __forceinline__ uint32_t mapa(uint32_t a, uint32_t rank) {
  uint32_t r; asm("mapa.shared::cluster.u32 %0, %1, %2;" : "=r"(r) : "r"(a), "r"(rank)); return r;
}
__device__ __forceinline__ void st_async4(uint32_t dst, float a, float b, float c, float d, uint32_t mb) {
  asm volatile("st.async.shared::cluster.mbarrier::complete_tx::bytes.v4.f32 [%0], {%1,%2,%3,%4}, [%5];" :: "r"(dst), "f"(a), "f"(b), "f"(c), "f"(d), "r"(mb) : "memory");
}
__device__ __forceinline__ void st_async2(uint32_t dst, float a, float b, uint32_t mb) {
  asm volatile("st.async.shared::cluster.mbarrier::complete_tx::bytes.v2.f32 [%0], {%1,%2}, [%3];" :: "r"(dst), "f"(a), "f"(b), "r"(mb) : "memory");
}
__device__ __forceinline__ void st_async1(uint32_t dst, uint32_t a, uint32_t mb) {
  asm volatile("st.async.shared::cluster.mbarrier::complete_tx::bytes.u32 [%0], %1, [%2];" :: "r"(dst), "r"(a), "r"(mb) : "memory");
}
__device__ __forceinline__ uint4 lds128(uint32_t a) {
  uint4 v; asm volatile("ld.shared.v4.u32 {%0,%1,%2,%3}, [%4];" : "=r"(v.x), "=r"(v.y), "=r"(v.z), "=r"(v.w) : "r"(a) : "memory"); return v;
}
__device__ __forceinline__ uint2 lds64(uint32_t a) {
  uint2 v; asm volatile("ld.shared.v2.u32 {%0,%1}, [%2];" : "=r"(v.x), "=r"(v.y) : "r"(a) : "memory"); return v;
}
__device__ __forceinline__ uint32_t lds32(uint32_t a) {
  uint32_t v; asm volatile("ld.shared.u32 %0, [%1];" : "=r"(v) : "r"(a) : "memory"); return v;
}
__device__ __forceinline__ void sts128(uint32_t a, uint4 v) {
  asm volatile("st.shared.v4.u32 [%0], {%1,%2,%3,%4};" :: "r"(a), "r"(v.x), "r"(v.y), "r"(v.z), "r"(v.w) : "memory");
}
__device__ __forceinline__ void sts64(uint32_t a, uint32_t x, uint32_t y) {
  asm volatile("st.shared.v2.u32 [%0], {%1,%2};" :: "r"(a), "r"(x), "r"(y) : "memory");
}
__device__ __forceinline__ void sts32(uint32_t a, uint32_t x) { asm volatile("st.shared.u32 [%0], %1;" :: "r"(a), "r"(x) : "memory"); }
__device__ __forceinline__ void ldsm4(uint32_t& r0, uint32_t& r1, uint32_t& r2, uint32_t& r3, uint32_t a) {
  asm volatile("ldmatrix.sync.aligned.m8n8.x4.shared.b16 {%0,%1,%2,%3}, [%4];" : "=r"(r0), "=r"(r1), "=r"(r2), "=r"(r3) : "r"(a) : "memory");
}
__device__ __forceinline__ void ldsm4t(uint32_t& r0, uint32_t& r1, uint32_t& r2, uint32_t& r3, uint32_t a) {
  asm volatile("ldmatrix.sync.aligned.m8n8.x4.trans.shared.b16 {%0,%1,%2,%3}, [%4];" : "=r"(r0), "=r"(r1), "=r"(r2), "=r"(r3) : "r"(a) : "memory");
}
__device__ __forceinline__ void stsm4(uint32_t a, uint32_t r0, uint32_t r1, uint32_t r2, uint32_t r3) {
  asm volatile("stmatrix.sync.aligned.m8n8.x4.shared.b16 [%0], {%1,%2,%3,%4};" :: "r"(a), "r"(r0), "r"(r1), "r"(r2), "r"(r3) : "memory");
}
__device__ __forceinline__ uint32_t movmat(uint32_t a) {
  uint32_t d; asm volatile("movmatrix.sync.aligned.m8n8.trans.b16 %0, %1;" : "=r"(d) : "r"(a)); return d;
}
__device__ __forceinline__ void mma16(float* d, uint32_t a0, uint32_t a1, uint32_t a2, uint32_t a3, uint32_t b0, uint32_t b1) {
  asm volatile("mma.sync.aligned.m16n8k16.row.col.f32.bf16.bf16.f32 {%0,%1,%2,%3}, {%4,%5,%6,%7}, {%8,%9}, {%0,%1,%2,%3};"
    : "+f"(d[0]), "+f"(d[1]), "+f"(d[2]), "+f"(d[3]) : "r"(a0), "r"(a1), "r"(a2), "r"(a3), "r"(b0), "r"(b1));
}
__device__ __forceinline__ void mma8(float* d, uint32_t a0, uint32_t a1, uint32_t b0) {
  asm volatile("mma.sync.aligned.m16n8k8.row.col.f32.bf16.bf16.f32 {%0,%1,%2,%3}, {%4,%5}, {%6}, {%0,%1,%2,%3};"
    : "+f"(d[0]), "+f"(d[1]), "+f"(d[2]), "+f"(d[3]) : "r"(a0), "r"(a1), "r"(b0));
}
__device__ __forceinline__ float rcp(float x) { float r; asm("rcp.approx.ftz.f32 %0, %1;" : "=f"(r) : "f"(x)); return r; }
__device__ __forceinline__ float ex2(float x) { float r; asm("ex2.approx.ftz.f32 %0, %1;" : "=f"(r) : "f"(x)); return r; }

__host__ __device__ constexpr uint64_t mkdesc(uint32_t off, uint32_t lbo, uint32_t sbo, uint32_t swz) {
  return (uint64_t)((SBASE + off) >> 4) | ((uint64_t)(lbo >> 4) << 16) | ((uint64_t)(sbo >> 4) << 32) | ((uint64_t)swz << 62);
}
__host__ __device__ constexpr uint64_t desc_sw128(uint32_t off) { return mkdesc(off, 16, 1024, 1); }
__host__ __device__ constexpr uint64_t desc_n16(uint32_t off) { return mkdesc(off, 256, 128, 0); }
__host__ __device__ constexpr uint64_t desc_m(uint32_t off) { return mkdesc(off, 16, 256, 3); }

__host__ __device__ constexpr uint64_t desc_sw64(uint32_t off) { return mkdesc(off, 16, 512, 2); }

__device__ __forceinline__ void wg_fence() { asm volatile("wgmma.fence.sync.aligned;" ::: "memory"); }
__device__ __forceinline__ void wg_commit() { asm volatile("wgmma.commit_group.sync.aligned;" ::: "memory"); }
template <int N> __device__ __forceinline__ void wg_wait() { asm volatile("wgmma.wait_group.sync.aligned %0;" :: "n"(N) : "memory"); }

#define ACC8(d) "+f"(d[0]), "+f"(d[1]), "+f"(d[2]), "+f"(d[3]), "+f"(d[4]), "+f"(d[5]), "+f"(d[6]), "+f"(d[7])
#define ACC32(d) ACC8(d), ACC8((d + 8)), ACC8((d + 16)), ACC8((d + 24))
#define R8 "{%0,%1,%2,%3,%4,%5,%6,%7}"
#define R32 "{%0,%1,%2,%3,%4,%5,%6,%7,%8,%9,%10,%11,%12,%13,%14,%15,%16,%17,%18,%19,%20,%21,%22,%23,%24,%25,%26,%27,%28,%29,%30,%31}"
template <int SD> __device__ __forceinline__ void wg_rs16(float* d, const uint32_t* a, uint64_t db) {
  asm volatile("wgmma.mma_async.sync.aligned.m64n16k16.f32.bf16.bf16 " R8 ", {%8,%9,%10,%11}, %12, %13, 1, 1, 1;"
    : ACC8(d) : "r"(a[0]), "r"(a[1]), "r"(a[2]), "r"(a[3]), "l"(db), "n"(SD));
}
template <int SD> __device__ __forceinline__ void wg_ss16(float* d, uint64_t da, uint64_t db) {
  asm volatile("wgmma.mma_async.sync.aligned.m64n16k16.f32.bf16.bf16 " R8 ", %8, %9, %10, 1, 1, 1, 1;"
    : ACC8(d) : "l"(da), "l"(db), "n"(SD));
}
template <int SD, uint64_t DA, uint64_t DB> __device__ __forceinline__ void wg_ss16o(float* d, uint32_t oa, uint32_t ob) {
  asm volatile("{.reg .b32 x, y; .reg .b64 a, b; add.u32 x, %8, %10; add.u32 y, %9, %12; mov.b64 a, {x, %11}; mov.b64 b, {y, %13};\n"
               "wgmma.mma_async.sync.aligned.m64n16k16.f32.bf16.bf16 " R8 ", a, b, %14, 1, 1, 1, 1;}"
    : ACC8(d) : "r"(oa), "r"(ob), "n"((uint32_t)DA), "n"((uint32_t)(DA >> 32)), "n"((uint32_t)DB), "n"((uint32_t)(DB >> 32)), "n"(SD));
}
template <int SD> __device__ __forceinline__ void wg_rs64(float* d, const uint32_t* a, uint64_t db) {
  asm volatile("wgmma.mma_async.sync.aligned.m64n64k16.f32.bf16.bf16 " R32 ", {%32,%33,%34,%35}, %36, %37, 1, 1, 0;"
    : ACC32(d) : "r"(a[0]), "r"(a[1]), "r"(a[2]), "r"(a[3]), "l"(db), "n"(SD));
}
template <int SD> __device__ __forceinline__ void wg_ss64(float* d, uint64_t da, uint64_t db) {
  asm volatile("wgmma.mma_async.sync.aligned.m64n64k16.f32.bf16.bf16 " R32 ", %32, %33, %34, 1, 1, 1, 0;"
    : ACC32(d) : "l"(da), "l"(db), "n"(SD));
}
#define WG_RSO(NAME, SHAPE, REGS, ACC, A, TB) \
template <int SD, uint64_t DB> __device__ __forceinline__ void NAME(float* d, uint32_t a0, uint32_t a1, uint32_t a2, uint32_t a3, uint32_t ob) { \
  asm volatile("{.reg .b64 b; mov.b64 b, {" A(4) ", " A(5) "};\nwgmma.mma_async.sync.aligned." SHAPE ".f32.bf16.bf16 " REGS \
               ", {" A(0) "," A(1) "," A(2) "," A(3) "}, b, " A(6) ", 1, 1, " TB ";}" \
    : ACC(d) : "r"(a0), "r"(a1), "r"(a2), "r"(a3), "r"(ob + (uint32_t)DB), "n"((uint32_t)(DB >> 32)), "n"(SD)); \
}
#define ACC4(d) "+f"(d[0]), "+f"(d[1]), "+f"(d[2]), "+f"(d[3])
#define ACC16(d) ACC8(d), ACC8((d + 8))
#define OP4(i) OP4_##i
#define OP4_0 "%4"
#define OP4_1 "%5"
#define OP4_2 "%6"
#define OP4_3 "%7"
#define OP4_4 "%8"
#define OP4_5 "%9"
#define OP4_6 "%10"
#define OP16(i) OP16_##i
#define OP16_0 "%16"
#define OP16_1 "%17"
#define OP16_2 "%18"
#define OP16_3 "%19"
#define OP16_4 "%20"
#define OP16_5 "%21"
#define OP16_6 "%22"
#define OP32(i) OP32_##i
#define OP32_0 "%32"
#define OP32_1 "%33"
#define OP32_2 "%34"
#define OP32_3 "%35"
#define OP32_4 "%36"
#define OP32_5 "%37"
#define OP32_6 "%38"
WG_RSO(wg_rs8o, "m64n8k16", "{%0,%1,%2,%3}", ACC4, OP4, "1")
WG_RSO(wg_rs32o, "m64n32k16", "{%0,%1,%2,%3,%4,%5,%6,%7,%8,%9,%10,%11,%12,%13,%14,%15}", ACC16, OP16, "1")
WG_RSO(wg_rs64o, "m64n64k16", R32, ACC32, OP32, "0")
template <int N> __device__ __forceinline__ void reg_inc() { asm volatile("setmaxnreg.inc.sync.aligned.u32 %0;" :: "n"(N)); }
template <int N> __device__ __forceinline__ void reg_dec() { asm volatile("setmaxnreg.dec.sync.aligned.u32 %0;" :: "n"(N)); }
__device__ __forceinline__ void cluster_sync() {
  asm volatile("barrier.cluster.arrive.relaxed.aligned;\nbarrier.cluster.wait.aligned;" ::: "memory");
}

template <int KS>
__device__ __forceinline__ void load_frags(uint32_t* a, uint32_t src) {
  const int lane = threadIdx.x & 31, w = (threadIdx.x >> 5) & 3;
  const int k = ((lane >> 4) << 3) + (lane & 7), u = w * 2 + ((lane >> 3) & 1);
  const uint32_t base = src + k * 128 + ((u ^ (k & 7)) << 4);
#pragma unroll
  for (int ks = 0; ks < KS; ks++) ldsm4t(a[ks * 4], a[ks * 4 + 1], a[ks * 4 + 2], a[ks * 4 + 3], base + ks * 2048);
}

__device__ __forceinline__ uint32_t badd2(uint32_t a, uint32_t b) { uint32_t r; asm("add.rn.bf16x2 %0, %1, %2;" : "=r"(r) : "r"(a), "r"(b)); return r; }
__device__ __forceinline__ uint32_t bsub2(uint32_t a, uint32_t b) { uint32_t r; asm("sub.rn.bf16x2 %0, %1, %2;" : "=r"(r) : "r"(a), "r"(b)); return r; }
__device__ __forceinline__ uint32_t bmul2(uint32_t a, uint32_t b) { uint32_t r; asm("mul.rn.bf16x2 %0, %1, %2;" : "=r"(r) : "r"(a), "r"(b)); return r; }
__device__ __forceinline__ uint32_t bfma2(uint32_t a, uint32_t b, uint32_t c) { uint32_t r; asm("fma.rn.bf16x2 %0, %1, %2, %3;" : "=r"(r) : "r"(a), "r"(b), "r"(c)); return r; }
template <int R> __device__ __forceinline__ void layernorm9(const uint32_t* x, uint32_t* o) {
  const uint32_t ones = 0x3F803F80u;
  float a[R][3][4], q[R], s[R];
#pragma unroll
  for (int i = 0; i < 9 * R; i++) {
    float* d = a[i % R][i / R % 3];
    if (i < 3 * R) d[0] = d[1] = d[2] = d[3] = 0.f;
    mma8(d, x[i % R * 9 + i / R], ones, x[i % R * 9 + i / R]);
  }
#pragma unroll
  for (int r = 0; r < R; r++) {
    q[r] = threadIdx.x & 4 ? a[r][0][1] + a[r][1][1] + a[r][2][1] : a[r][0][0] + a[r][1][0] + a[r][2][0];
    s[r] = (a[r][0][2] + a[r][0][3]) + (a[r][1][2] + a[r][1][3]) + (a[r][2][2] + a[r][2][3]);
  }
#pragma unroll
  for (int r = 0; r < R; r++) { q[r] += __shfl_xor_sync(~0u, q[r], 4); s[r] += __shfl_xor_sync(~0u, s[r], 1); }
#pragma unroll
  for (int r = 0; r < R; r++) { q[r] += __shfl_xor_sync(~0u, q[r], 9); s[r] += __shfl_xor_sync(~0u, s[r], 2); }
#pragma unroll
  for (int r = 0; r < R; r++) q[r] = __shfl_sync(~0u, q[r], 0) + __shfl_sync(~0u, q[r], 18);
#pragma unroll
  for (int r = 0; r < R; r++) {
    const float mean = s[r] * (1.f / DM), var = fmaxf(fmaf(q[r], 1.f / DM, -mean * mean), 0.f);
    float sd;
    asm("sqrt.approx.ftz.f32 %0, %1;" : "=f"(sd) : "f"(bf_lo(pack2(bf_lo(pack2(var, 0.f)) + 1e-5f, 0.f))));
    const float inv = rcp(bf_lo(pack2(sd, 0.f)));
    const uint32_t mb = pack2(mean, mean), hi = pack2(inv, inv), lo = pack2(inv - bf_lo(hi), inv - bf_lo(hi));
#pragma unroll
    for (int i = r * 9; i < r * 9 + 9; i++) {
      const uint32_t d = bsub2(x[i], mb);
      o[i] = bfma2(d, hi, bmul2(d, lo));
    }
  }
}
__device__ __forceinline__ void store_ln_row(int layer, int tok, const uint32_t* o) {
  const int lane = threadIdx.x & 31, r = tok & 31;
  unsigned char* p = g_lnimg + (size_t)(layer * NSEG + (tok >> 5)) * (9 * 4096) + r * 128 + (((lane >> 2) ^ (r & 7)) << 4) + (lane & 3) * 4;
#pragma unroll
  for (int i = 0; i < 9; i++) *(uint32_t*)(p + i * 4096) = o[i];
}
struct Params { CUtensorMap map[11]; const bf16 *X, *K, *V, *shift, *Hk, *Dk, *mem0, *Wq, *Wk, *Wv, *Wo; bf16* out; uint32_t dly[24]; };
#define PACE P.dly[20]
#define S1G P.dly[21]
#define S1DLY P.dly[22]
#define DLYS P.dly[0]
#define DLYW P.dly[1]
#define KLATE P.dly[2]
#define DLYQ P.dly[3]
#define DLYK P.dly[4]
#define DLYG P.dly[5]
#define KWIN P.dly[6]
#define KMIN P.dly[7]
uint32_t h_dly[24] = {800, 1100, 20, 0, 3650, 3200, 1800, 400, 1750, 1800, 2070, 2230, 2380, 2530, 3080, 3230, 3370, 3480, 3620, 0, 200, 14000, 17000};

constexpr uint32_t C_W = 0, C_M = 147456, C_KV = C_M + 18432, C_QM = C_KV + 32768, C_KM = C_QM + 2048,
                   C_VM = C_KM + 2048, C_OI = C_VM + 2048, C_SX = C_OI + 4096, C_KM2 = C_SX + 2560, C_VM2 = C_KM2 + 128,
                   C_KV2 = C_KM2 + 2048, C_Q = C_KV2 + 8192, C_BAR = C_Q + 8192;
constexpr uint32_t CB_FULL = C_BAR, CB_REF = C_BAR + 16, CB_SX = C_BAR + 32, CB_OX = C_BAR + 40, CB_XX = C_BAR + 48, CB_Q = C_BAR + 56, C_BAD = C_BAR + 64, W_BAR = C_BAR + 80, T_BAR = W_BAR + 24, S_GEN = C_BAR + 128, C_REF = C_BAR + 132, CB_VF = C_BAR + 144, CB_M = C_BAR + 160, CB_MV = C_BAR + 200;
constexpr uint32_t G_W = 0, G_RING = 147456, G_W2 = G_RING + 9 * 8192, G_BAR = G_W2 + 8192;
constexpr uint32_t O_W = 0, O_RING = 3 * 40960, O_ST = O_RING + 11 * 8192, O_BAR = O_ST + 16384, OB_ST = O_BAR + 64;
constexpr uint32_t F_A = 0, F_XY = 36864, F_L = F_XY + 36864, F_X = F_L + 18432, F_Y = F_L + 2 * 36864, F_BAR = C_BAR;
constexpr uint32_t SMEM_BYTES = C_BAR + 256;
static_assert(G_BAR + 256 <= SMEM_BYTES && O_BAR + 256 <= SMEM_BYTES && F_BAR + 16 <= SMEM_BYTES && SMEM_BYTES <= 232448, "smem map");
enum { B_INIT = 1, B_M, B_QK, B_S, B_V, B_O, B_X, B_WG0, B_WG1, B_WG2, B_G, B_OE, B_T, B_R };

__device__ __forceinline__ uint4 pack_partial(const float* d, uint32_t tag) {
  uint32_t x;
  asm("lop3.b32 %0, %1, 1, %2, 0xb8;" : "=r"(x) : "r"(pack2(d[0], d[1])), "r"(tag));
  return make_uint4(x, pack2(d[4], d[5]), pack2(d[2], d[3]), pack2(d[6], d[7]));
}
__device__ __forceinline__ void store_partial(uint4* p, const uint4& v) { st_b128(p, v.x, v.y, v.z, v.w); }
__device__ __forceinline__ void gather_reduce(const uint32_t* p, uint32_t* dst, bool shared, uint32_t tag, uint32_t lane, uint32_t sb, int n, int TS0) {
  int tries = 0;
  float u, v;
  bool bad;
  TR(TS0);
  do {
    uint32_t x[16];
#pragma unroll
    for (int i = 0; i < 16; i++) asm volatile("ld.relaxed.gpu.global.u32 %0, [%1];" : "=r"(x[i]) : "l"(p + i * 64) : "memory");
    tries++;
    float a[2] = {bf_lo(x[0]), bf_lo(x[1])}, b[2] = {bf_hi(x[0]), bf_hi(x[1])};
    uint32_t t = 0;
#pragma unroll
    for (int i = 2; i < 16; i++) { a[i & 1] += bf_lo(x[i]); b[i & 1] += bf_hi(x[i]); }
#pragma unroll
    for (int i = 0; i < 16; i += 4)
      asm("{.reg .b32 y, z; lop3.b32 y, %1, %2, %5, 0x7e; lop3.b32 z, %3, %4, %5, 0x7e; lop3.b32 %0, %0, y, z, 0xfe;}"
          : "+r"(t) : "r"(x[i]), "r"(x[i + 1]), "r"(x[i + 2]), "r"(x[i + 3]), "r"(tag));
    u = a[0] + a[1]; v = b[0] + b[1];
    bad = __any_sync(~0u, (t & 1) && !(lane & 3));
    if (shared) { u += __shfl_xor_sync(~0u, u, 8); v += __shfl_xor_sync(~0u, v, 8); }
    u += __shfl_xor_sync(~0u, u, 16);
    v += __shfl_xor_sync(~0u, v, 16);
    st_relaxed_if(dst, pack2(u, v), !bad && (n >= LAG || !(lane & 1)));
  } while (bad);
  TR(TS0 + 3); TRV(TS0 + 2, tries);
  CNT((TS0 - 16) >> 2, tries);
}
__device__ __forceinline__ uint32_t sent_bad(const uint4& v) { return max(max(v.x, v.y), max(v.z, v.w)) == SENT; }

__host__ __device__ constexpr int o_ks(int s) { return s & (s < 8 ? 3 : 7); }
__host__ __device__ constexpr bool o_reg(int s) { return s < 8 ? (s & 3) != 3 : !(s & 1); }
__host__ __device__ constexpr int o_slot(int s) { return s < 8 ? (o_reg(s) ? s - (s >> 2) : s >> 2) : s & 1 ? (s - 5) >> 1 : (s + 4) >> 1; }
__device__ __forceinline__ int g_unit(int wg) {
  const int i = bid() - N_CHAIN;
  return i < 32 ? wg * 64 + i : 2 * i - 32 + wg;
}
__device__ __forceinline__ void load_box(const Params& P, uint32_t sb, bool regs, int wg, int i, uint32_t mb) {
  const int b = bid();
  int map, col = 0, ks = 0, c2 = 0, c3 = 0;
  uint32_t dst = wg * 73728;
  if (b < N_CHAIN) {
    const int k = i - 1, st = regs ? (k < 6 ? k + k / 3 : 2 * k - 4) : k < 2 ? 4 * k + 3 : 2 * k + 5;
    dst += i ? (17 + i) * 2048 : 0;
    if (wg || i == 0) { map = wg + i; col = b * 64; c3 = !regs; }
    else if (!regs && k >= 14) { map = 6; ks = b * 4 + k - 14; }
    else { map = 6; col = 64 + (st < 8 ? (st >> 2) * 64 : (st >> 3) * 128 + (b & 1) * 64); ks = (b * 4) ^ o_ks(st); }
  } else if (b < N_CHAIN + N_G) {
    const int q = g_unit(wg);
    map = ((q >> 5) + 1) % 3;
    if (i) { map += 3; col = (q & 31) * 128 + (i - 1) * 64; ks = 34; dst = G_W2 + wg * 4096 + (i - 1) * 2048; }
    else { map += 8; c2 = (q & 31) * 2; c3 = !regs; }
  } else {
    const int o = b - N_CHAIN - N_G, ksl = o / 3;
    map = 7; col = ((o % 3) * 3 + (wg + ksl) % 3) * 64; dst = (wg * (regs ? 24 : 20) + i) * 2048;
    ks = (ksl * 11 - max(ksl - 4, 0)) * 4 + (regs ? i / 3 * 5 + i % 3 * 2 : i < 16 ? i / 2 * 5 + 1 + i % 2 * 2 : i + 24);
    c3 = (ks & 1) * 2; ks >>= 1;
  }
  asm volatile("cp.async.bulk.tensor.5d.shared::cluster.global.tile.mbarrier::complete_tx::bytes [%0], [%1, {%2, %3, %4, %5, %6}], [%7];"
               :: "r"(sb + dst), "l"(&P.map[map]), "r"(col), "r"(0), "r"(c2), "r"(c3), "r"(ks), "r"(mb) : "memory");
}
__device__ __forceinline__ void load_wg(const Params& P, uint32_t sb, bool regs, int wg, int quarter) {
  const int b = bid(), i = (threadIdx.x & 31) * 4 + quarter;
  const int n = b < N_CHAIN ? 36 : b < N_CHAIN + N_G ? (regs ? 38 : 36) : regs ? 24 : b < N_CHAIN + N_G + 12 ? 20 : 16;
  if (i == 0) mbar_expect(sb + W_BAR + wg * 8, n * 2048);
  if (i < (b < N_CHAIN ? (wg ? 2 : 19) : b < N_CHAIN + N_G ? n - 35 : n)) load_box(P, sb, regs, wg, i, sb + W_BAR + wg * 8);
  __syncwarp();
}
__device__ __forceinline__ uint32_t near_half(uint32_t blk, uint32_t reader) {
  return __ldcg(g_near + (blk >> 3)) ^ (~blk & 1) ^ __ldcg(g_side + (blk >> 3)) ^ __ldcg(g_side + reader);
}

__device__ __forceinline__ uint32_t opaque_tid() { uint32_t t; asm volatile("mov.u32 %0, %%tid.x;" : "=r"(t)); return t; }
__device__ __forceinline__ void m_fetch(uint32_t sb, uint32_t src, uint32_t b, uint32_t mb) {
  bulk_load(sb + C_M + (b ? b * 4096 - 2048 : 0), (const unsigned char*)g_mimg + ((src ^ ((b & 1) * 4096)) + b * 8192), b ? 4096 : 2048, mb);
}
__device__ __forceinline__ uint32_t pinned(uint32_t v) { return __shfl_sync(~0u, v, threadIdx.x & 31); }
template <class T> __device__ __forceinline__ T* pinned(T* p) { return (T*)__shfl_sync(~0u, (unsigned long long)p, threadIdx.x & 31); }
__device__ __forceinline__ uint32_t m_probe(uint32_t lane) { return lane * 32 + (lane & 4) * 4 + (lane >> 3) * 4; }
__device__ __forceinline__ uint32_t m_max(uint32_t a, uint32_t b) {
  return max(max(lds32(a), lds32(a + 1024)), max(lds32(b), lds32(b + 1024)));
}
template <int S0, int N> __device__ __forceinline__ void o_steps(float* d, const uint32_t* a) {
  constexpr int SD = o_ks(S0) != 0;
  if constexpr (o_reg(S0)) wg_rs16<SD>(d, a + (18 + o_slot(S0)) * 4, desc_n16(C_OI + o_ks(S0) * 512));
  else wg_ss16<SD>(d, desc_sw128(C_W + (18 + o_slot(S0)) * 2048), desc_n16(C_OI + o_ks(S0) * 512));
  if constexpr (N > 1) o_steps<S0 + 1, N - 1>(d, a);
}
template <int BASE, int KS, int N> __device__ __forceinline__ void m_steps(float* d, const uint32_t* a, uint32_t oa) {
  wg_rs16<KS != 0>(d, a + (BASE + KS / 2) * 4, desc_m(C_M + KS * 512));
  wg_ss16o<1, desc_sw128(C_W + (BASE + KS / 2) * 2048), desc_m(C_M + KS * 512 + 512)>(d, oa, 0);
  if constexpr (N > 2) m_steps<BASE, KS + 2, N - 2>(d, a, oa);
}

__device__ __forceinline__ void chain_proj(const Params& P, uint32_t sb) {
  const uint32_t c = chain_id(), h = c >> 1, j = c & 1, wid = __shfl_sync(~0u, threadIdx.x >> 5, 0), wg = wid >> 2, w = wid & 3;
  const uint32_t t = threadIdx.x & 127, lane = pinned(t & 31), mine = pinned(sb + t * 16), rb = mapa(sb, j ^ 1);
  const uint32_t theirs = pinned(rb + C_KM2 + w * 512 + lane * 4), oa = wg * 4608;
  uint32_t a[144];
  mbar_wait(sb + W_BAR + wg * 8, 0);
  load_frags<36>(a, sb + C_W + wg * 73728);
  fence_async_smem();
  bar_sync(B_WG0 + wg, 128);
  load_wg(P, sb, false, wg, w);
  bar_sync(B_WG2, 384);
  const uint32_t round = min(w, 2u) + (wg ? 0 : 3), gdly = P.dly[8 + round], ps = t >> 2, pf = j * 16 + (ps >> 1);
  uint4* const dsts = pinned(g_xb + (ps * 4096 + near_half(ps * 8, ps * 2) * 256 + c * 4 + (t & 3)));
  uint4* const dstf = pinned(g_xb + (pf * 4096 + 512 + near_half(pf * 8 + 1, pf * 2) * 256 + h * 8 + (t & 7)));
  const uint32_t* const gsrc = (const uint32_t*)g_xb + (h * 16384 + min(w, 2u) * 4096 + near_half(h * 8 + !wg, h * 2) * 1024 +
                               (wg ? (lane & 24) * 2 + j * 8 + (lane & 7) : 2048 + (lane & 16) * 2 + j * 16 + (lane & 15)));
  uint32_t* gdst = g_mimg + (16384 + (lane >> 4) * 1024 + (lane & 2) * 4 +
                   (wg ? (round ? 1536 + round * 512 : 0) + h * 16 + ((lane ^ (c >> 2)) & 1) * 4 + j * 2 + ((lane >> 2) & 1)
                       : (round - 1) * 2048 + c * 16 + ((lane ^ (c >> 1)) & 1) * 4 + ((lane >> 2) & 3)));
  mbar_wait(sb + W_BAR + wg * 8, 1);
  bar_sync(B_INIT, 256);
  if ((threadIdx.x & 127) == 0) TS(4);

  uint32_t ring = 1;
#pragma unroll 1
  for (int n = 0; n < STEPS; n++) {
    float d[8], e[8];
    uint32_t redo = n + 1;
    do {
      mbar_wait(sb + CB_M, n & 1);
      wg_fence();
      m_steps<0, 0, 4>(d, a, oa);
      if (VE && wg) m_steps<18, 0, 4>(e, a, 4608);
      wg_commit();
      if (wid == 0) TR(8);
      mbar_wait(sb + CB_M + 8, n & 1);
      wg_fence();
      m_steps<0, 4, 8>(d, a, oa);
      if (VE > 4 && wg) m_steps<18, 4, (VE > 4 ? VE - 4 : 2)>(e, a, 4608);
      wg_commit();
      mbar_wait(sb + CB_MV, n & 1);
      redo = lds32(sb + C_BAD) == redo ? SENT : 0;
    } while (redo);
    mbar_wait(sb + CB_MV + 8, n & 1);
    wg_fence();
    m_steps<0, 12, 8>(d, a, oa);
    wg_commit();
    mbar_wait(sb + CB_MV + 16, n & 1);
    wg_fence();
    m_steps<0, 20, 8>(d, a, oa);
    wg_commit();
    mbar_wait(sb + CB_MV + 24, n & 1);
    wg_fence();
    m_steps<0, 28, 8>(d, a, oa);
    wg_commit();
    wg_wait<0>();
    if (w == 0) TR(6 + wg);
    const uint32_t f0 = pack2(d[0], d[1]), f1 = pack2(d[4], d[5]), f2 = pack2(d[2], d[3]), f3 = pack2(d[6], d[7]);
    stsm4(mine + C_QM + wg * 2048, f0, f1, f2, f3);
    bar_arrive(B_QK, 416);
    const uint32_t tag = (n & 1) ^ 1;
    if (wg) {
      if (n + 1 < STEPS) bar_sync(B_S, 256);
      wg_fence();
      m_steps<18, VE, 36 - VE>(e, a, 4608);
      wg_commit();
      st_async1(theirs, j ? f0 : f1, rb + CB_XX);
      st_async1(theirs + 256, j ? f2 : f3, rb + CB_XX);
      wg_wait<0>();
      if (w == 0) TR(11);
      const uint32_t v0 = pack2(e[0], e[1]), v1 = pack2(e[4], e[5]), v2 = pack2(e[2], e[3]), v3 = pack2(e[6], e[7]);
      stsm4(mine + C_VM, v0, v1, v2, v3);
      bar_arrive(B_V, 256);
      st_async1(theirs + 128, j ? v0 : v1, rb + CB_XX);
      st_async1(theirs + 384, j ? v2 : v3, rb + CB_XX);
      if (n + 1 == STEPS) break;
      bar_sync(B_O, 256);
      fence_async_smem();
      wg_fence();
#pragma unroll
      for (int ks = 0; ks < 4; ks++) {
        if (ks == 0) wg_ss16<0>(d, desc_sw128(C_W + 32 * 2048), desc_n16(C_OI));
        else wg_ss16<1>(d, desc_sw128(C_W + (32 + ks) * 2048), desc_n16(C_OI + ks * 512));
      }
      wg_commit();
      bar_arrive(B_X, 256);
      if (w == 0) TR(0);
      wg_wait<0>();
      store_partial(dsts, pack_partial(d, tag));
      bar_arrive(B_M, 160);
      if (w == 0) TR(1);
    } else {
      if (n + 1 == STEPS) break;
      bar_sync(B_X, 256);
      wg_fence();
      o_steps<0, 4>(d, a);
      wg_commit();
      o_steps<4, 4>(e, a);
      wg_commit();
      wg_wait<1>();
      store_partial(dsts + 1024, pack_partial(d, tag));
      if (w == 0) TR(2);
      if (OGAP == 0) { wg_fence(); o_steps<8, 4>(d, a); wg_commit(); wg_wait<1>(); } else wg_wait<0>();
      store_partial(dsts + 2048, pack_partial(e, tag));
      if (w == 0) TR(3);
      wg_fence();
      if (OGAP) o_steps<8, 4>(d, a);
      if (OGAP < 2) o_steps<16, 4>(e, a);
      wg_commit();
      bar_sync(B_T, 256);
      if (w == 0) { TRV(61, 0); TR(12); }
      wg_fence();
      o_steps<12, 4>(d, a);
      wg_commit();
      if (OGAP == 2) o_steps<16, 4>(e, a);
      o_steps<20, 4>(e, a);
      wg_commit();
      wg_wait<1>();
      store_partial(dstf, pack_partial(d, tag));
      if (w == 0) TR(4);
      wg_fence();
      o_steps<24, 8>(d, a);
      wg_commit();
      wg_wait<1>();
      store_partial(dstf + 1024, pack_partial(e, tag));
      bar_arrive(B_OE, 256);
      if (w == 0) TR(5);
      wg_wait<0>();
      store_partial(dstf + 2048, pack_partial(d, tag));
      if (w == 0) TR(15);
    }
    if (w < 3) {
      mbar_wait(sb + CB_REF, n & 1);
      wait_until(lds32(sb + C_REF), gdly);
      gather_reduce(gsrc, gdst, wg, tag, lane, sb, n, 16 + round * 4);
      if (++ring == MRING) { ring = 0; gdst -= MRING * 16384; }
      gdst += 16384;
    }
  }
}

template <int KS> __device__ __forceinline__ void x_scores(float* s, float* sm, const uint4* q, uint32_t ok, uint32_t om) {
  wg_rs32o<1, desc_sw64(C_KV + KS * 1024)>(s, q[KS].x, q[KS].y, q[KS].z, q[KS].w, ok);
  wg_rs8o<1, desc_n16(C_KM + KS * 512)>(sm, q[KS].x, q[KS].y, q[KS].z, q[KS].w, om);
  if constexpr (KS < 3) x_scores<KS + 1>(s, sm, q, ok, om);
}

__device__ __forceinline__ void chain_attn(const Params& P, uint32_t sb) {
  const int c = chain_id(), j = c & 1;
  const int tid = threadIdx.x, lane = tid & 31, w = __shfl_sync(~0u, (tid >> 5) & 3, 0);
  const int l = w >> 1, u = w & 1;
  const uint32_t rb = mapa(sb, j ^ 1);
  const float sc = 0.08838834764831845f * 1.4426950408889634f;
  const uint32_t ones = 0x3F803F80u;
  const uint32_t km_off = C_KM + (lane >> 3) * 256 + l * 128 + (lane & 7) * 16;
  const uint32_t qm_off = C_QM + (lane >> 4) * 256 + l * 128 + (lane & 7) * 16;
  const uint32_t kv_off = C_KV + l * 4096 + (lane & 15) * 64 + (((lane >> 4) ^ (u * 2) ^ ((lane >> 1) & 3)) << 4);

  if (lane == 0) mbar_arrive(sb + CB_M);
#pragma unroll 1
  for (int n = 0; n < STEPS; n++) {
    const uint32_t kvb = sb + kv_off + (n & 1) * 16384;
    if (w == 0 && elect()) { mbar_expect(sb + CB_SX, 2560); mbar_expect(sb + CB_OX, 2048); mbar_expect(sb + CB_XX, 2048); }
    mbar_wait(sb + CB_FULL + (n & 1) * 8, (n >> 1) & 1);
    if (n < 3 && tid == 256) TS(n ? 20 + n : 5);
    __syncwarp();
    {
      uint32_t km[8];
      uint4 kx[8];
#pragma unroll
      for (int i = 0; i < 8; i++) ldsm4t(kx[i].x, kx[i].y, kx[i].z, kx[i].w, (kvb ^ ((i & 1) * 32)) + (i >> 1) * 1024);
      mbar_wait(sb + CB_VF, n & 1);
      if (w == 1) TRD(60, kx[7].x);
      bar_sync(B_QK, 416);
      if (n + 1 == STEPS) {
        bar_sync(B_V, 256);
      } else {
      uint32_t qm[16];
#pragma unroll
      for (int ks = 0; ks < 4; ks++) ldsm4t(qm[4 * ks], qm[4 * ks + 1], qm[4 * ks + 2], qm[4 * ks + 3], sb + qm_off + ks * 512);
      ldsm4t(km[0], km[1], km[2], km[3], sb + km_off);
      ldsm4t(km[4], km[5], km[6], km[7], sb + km_off + 1024);
      float s[5][4];
#pragma unroll
      for (int i = 0; i < 5; i++) { s[i][0] = s[i][1] = s[i][2] = s[i][3] = 0.f; }
#pragma unroll
      for (int ks = 0; ks < 4; ks++) {
        const uint32_t* q = qm + 4 * ks;
        mma16(s[1], q[0], q[1], q[2], q[3], kx[2 * ks].x, kx[2 * ks].y);
        mma16(s[2], q[0], q[1], q[2], q[3], kx[2 * ks].z, kx[2 * ks].w);
        mma16(s[0], q[0], q[1], q[2], q[3], km[2 * ks], km[2 * ks + 1]);
        mma16(s[3], q[0], q[1], q[2], q[3], kx[2 * ks + 1].x, kx[2 * ks + 1].y);
        mma16(s[4], q[0], q[1], q[2], q[3], kx[2 * ks + 1].z, kx[2 * ks + 1].w);
      }
      const uint32_t sx = C_SX + l * 1280;
      st_async4(rb + sx + u * 512 + lane * 16, s[1][0], s[1][1], s[2][0], s[2][1], rb + CB_SX);
      st_async1(rb + sx + 1024 + u * 128 + lane * 4, __float_as_uint(u ? s[0][1] : s[0][0]), rb + CB_SX);
      bar_arrive_after<B_S, 256>(__float_as_uint(s[3][0]), __float_as_uint(s[4][0]));
      uint4 vx[4];
#pragma unroll
      for (int i = 0; i < 4; i++) ldsm4(vx[i].x, vx[i].y, vx[i].z, vx[i].w, (kvb ^ ((i & 1) * 32)) + 8192 + (2 * u + (i >> 1)) * 1024);
      mbar_wait(sb + CB_SX, n & 1);
      const uint4 p0 = lds128(sb + sx + u * 512 + lane * 16), p1 = lds128(sb + sx + (u ^ 1) * 512 + lane * 16);
      const uint2 p2 = make_uint2(lds32(sb + sx + 1024 + lane * 4), lds32(sb + sx + 1152 + lane * 4));
      float t[10] = {s[0][0] + __uint_as_float(p2.x), s[0][1] + __uint_as_float(p2.y),
                     s[1][0] + __uint_as_float(p0.x), s[1][1] + __uint_as_float(p0.y),
                     s[2][0] + __uint_as_float(p0.z), s[2][1] + __uint_as_float(p0.w),
                     s[3][0] + __uint_as_float(p1.x), s[3][1] + __uint_as_float(p1.y),
                     s[4][0] + __uint_as_float(p1.z), s[4][1] + __uint_as_float(p1.w)};
      float mx = fmaxf(fmaxf(fmaxf(fmaxf(t[2], t[3]), fmaxf(t[4], t[5])), fmaxf(fmaxf(t[6], t[7]), fmaxf(t[8], t[9]))), fmaxf(t[0], t[1]));
      mx = fmaxf(fmaxf(mx, __shfl_xor_sync(~0u, mx, 1)), fmaxf(__shfl_xor_sync(~0u, mx, 2), __shfl_xor_sync(~0u, mx, 3)));
      const float ms = -mx * sc;
#pragma unroll
      for (int i = 0; i < 10; i++) t[i] = ex2(fmaf(t[i], sc, ms));
      uint32_t p[5];
#pragma unroll
      for (int i = 0; i < 5; i++) p[i] = pack2(t[2 * i], t[2 * i + 1]);
      p[1] |= (p[0] & p[3] & p[4]) & 0x80008000u;
      float o[2][4], z[4] = {0.f, 0.f, 0.f, 0.f};
      mma16(z, ones, ones, ones, ones, p[1], p[2]);
#pragma unroll
      for (int i = 0; i < 2; i++) {
        o[i][0] = o[i][1] = o[i][2] = o[i][3] = 0.f;
        mma16(o[i], vx[2 * i].x, vx[2 * i].y, vx[2 * i].z, vx[2 * i].w, p[1], p[2]);
      }
      mma16(z, ones, ones, ones, ones, p[3], p[4]);
#pragma unroll
      for (int i = 0; i < 2; i++) mma16(o[i], vx[2 * i + 1].x, vx[2 * i + 1].y, vx[2 * i + 1].z, vx[2 * i + 1].w, p[3], p[4]);
      mma8(z, ones, ones, p[0]);
      bar_sync_after<B_V, 256>(p[1]);
      ldsm4(km[0], km[1], km[2], km[3], sb + km_off + (C_VM - C_KM) + u * 1024);
      mma8(o[0], km[0], km[1], p[0]);
      mma8(o[1], km[2], km[3], p[0]);
      const float i0 = rcp(z[0]), i1 = rcp(z[1]);
      const uint32_t oo = C_OI + u * 1024 + l * 128 + lane * 4;
      uint32_t ow[4];
#pragma unroll
      for (int i = 0; i < 2; i++) { ow[2 * i] = pack2(o[i][0] * i0, o[i][1] * i1); ow[2 * i + 1] = pack2(o[i][2] * i0, o[i][3] * i1); }
#pragma unroll
      for (int i = 0; i < 4; i++) st_async1(rb + oo + 2048 + i * 256, ow[i], rb + CB_OX);
      stsm4(sb + C_OI + u * 1024 + l * 128 + (lane >> 3) * 256 + (lane & 7) * 16, ow[0], ow[1], ow[2], ow[3]);
      bar_arrive(B_O, 256);
      }
    }
    {
      const uint32_t lane = opaque_tid() & 31, own = ((n & 1) * 16384 + j * 4096) >> 4;
      float s[16], sm[4];
#pragma unroll
      for (int i = 0; i < 16; i++) s[i] = sm[i & 3] = 0.f;
      {
        uint4 q[4];
        mbar_wait(sb + CB_Q, n & 1);
#pragma unroll
        for (int ks = 0; ks < 4; ks++) q[ks] = lds128(sb + C_Q + (ks >> 1) * 4096 + w * 1024 + (ks & 1) * 512 + lane * 16);
        mbar_wait(sb + CB_XX, n & 1);
        if (n + 1 < STEPS) mbar_wait(sb + CB_OX, n & 1);
        fence_async_smem();
        if (n + 1 < STEPS) { bar_arrive(B_T, 256); bar_sync(B_OE, 256); }
        if (w == 1) { TRV(61, 0); TR(9); }
#pragma unroll 1
        for (uint32_t hf = 0; hf < 2; hf++) {
          wg_fence();
          x_scores<0>(s, sm, q, hf ? (C_KV2 - C_KV) >> 4 : own, hf ? (C_KM2 - C_KM) >> 4 : j * 8);
          wg_commit();
          wg_wait<0>();
#pragma unroll
          for (int ks = 0; ks < 4; ks++) asm volatile("mov.b32 %0, %1; mov.b32 %2, %3;" : "+r"(q[ks].x), "+r"(q[ks].y), "+r"(q[ks].z), "+r"(q[ks].w));
        }
      }
      const float neg = -1e9f * 11.313708498984761f;
      const int lim = 8 * (w - (int)(lane & 3)) + (int)(lane >> 2);
      float t[10] = {sm[0], sm[1]};
#pragma unroll
      for (int i = 0; i < 8; i++) t[2 + i] = i > lim ? neg : s[(i >> 1) * 4 + (i & 1)];
      float mx = fmaxf(fmaxf(fmaxf(fmaxf(t[2], t[3]), fmaxf(t[4], t[5])), fmaxf(fmaxf(t[6], t[7]), fmaxf(t[8], t[9]))), fmaxf(t[0], t[1]));
      mx = fmaxf(fmaxf(mx, __shfl_xor_sync(~0u, mx, 1)), fmaxf(__shfl_xor_sync(~0u, mx, 2), __shfl_xor_sync(~0u, mx, 3)));
      const float ms = -mx * sc;
#pragma unroll
      for (int i = 0; i < 10; i++) t[i] = ex2(fmaf(t[i], sc, ms));
      uint32_t p[5];
#pragma unroll
      for (int i = 0; i < 5; i++) p[i] = pack2(t[2 * i], t[2 * i + 1]);
      float z = ((t[0] + t[1]) + (t[2] + t[3])) + ((t[4] + t[5]) + (t[6] + t[7])) + (t[8] + t[9]);
      const uint32_t row = sb + C_Q + w * 1024 + (lane >> 2) * 128 + (((lane & 3) ^ (lane >> 2)) << 4);
#pragma unroll 1
      for (uint32_t hf = 0; hf < 2; hf++) {
        float o[32];
        const uint32_t vo = hf ? (C_KV2 + 4096 - C_KV - 8192) >> 4 : own;
        wg_fence();
        wg_rs64o<0, desc_sw64(C_KV + 8192)>(o, p[1], p[1], p[2], p[2], vo);
        wg_rs64o<1, desc_sw64(C_KV + 8192 + 32)>(o, p[3], p[3], p[4], p[4], vo);
        wg_rs64o<1, mkdesc(C_VM, 128, 256, 0)>(o, p[0], p[0], 0, 0, hf ? (C_VM2 - C_VM) >> 4 : j * 8);
        wg_commit();
        if (hf) {
          if (elect()) mbar_arrive(sb + CB_M);
        } else {
          z += __shfl_xor_sync(~0u, z, 1);
          z = rcp(z + __shfl_xor_sync(~0u, z, 2));
        }
        wg_wait<0>();
#pragma unroll
        for (int qq = 0; qq < 2; qq++) {
          const float* r = o + 16 * qq;
          sts128((row ^ (qq * 64)) + hf * 4096,
                 make_uint4(pack2(r[0] * z, r[1] * z), pack2(r[4] * z, r[5] * z), pack2(r[8] * z, r[9] * z), pack2(r[12] * z, r[13] * z)));
        }
      }
      bar_arrive(B_G, 160);
      if (w == 1) TR(10);
    }
  }
  if ((threadIdx.x & 127) == 0) TS(6);
}

__device__ __forceinline__ void chain_aux(const Params& P, uint32_t sb) {
  const uint32_t c = chain_id(), j = c & 1, lane = threadIdx.x & 31, w = __shfl_sync(~0u, (threadIdx.x >> 5) & 3, 0);
  if (threadIdx.x == 384) grid_wait(1, lds32(sb + S_GEN));
  bar_sync(B_WG2, 384);
  if (threadIdx.x == 384) TS(13);
  if (w == 0) {
    const uint32_t* fg = g_fl + FL_G + near_half(XB_F, c) * 1024 + (c >> 1) * 8;
#pragma unroll 1
    for (int n = 0; n < STEPS; n++) {
      const unsigned char* blk = g_qkv + (uint32_t)((n % RING) * (N_CHAIN * 24576));
      const uint32_t t1 = clk(), kb = sb + CB_FULL + (n & 1) * 8, kv = sb + C_KV + (n & 1) * 16384;
      uint32_t t0 = t1 - 100000, x = 0;
      if (n > 0) {
        wait_until(t1, KMIN);
        do asm volatile("ld.relaxed.gpu.global.u32 %0, [%1];" : "=r"(x) : "l"(fg) : "memory"); while (x <= n && clk() - t1 < KWIN);
        if (NOBULK) x = n + 1;
        if (x > n) {
          asm volatile("fence.acquire.gpu;" ::: "memory");
          fence_async_global();
          if (elect()) { mbar_expect(kb, 8192); bulk_load(kv, blk + c * 24576, 8192, kb); }
        }
        T3(0); CNT(12, 1 + (x <= n));
        mbar_wait(sb + CB_REF, (n - 1) & 1);
        t0 = lds32(sb + C_REF);
        wait_until(t0, DLYK - 500);
      }
      if (!NOBULK) wait_flags(fg + (lane & 1) * 256, n + 1);
      fence_async_global();
      wait_until(t0, DLYK);
      if (elect()) {
        if (x <= n) { mbar_expect(kb, 8192); bulk_load(kv, blk + c * 24576, 8192, kb); }
        mbar_expect(sb + CB_VF, 8192);
        bulk_load(kv + 8192, blk + (c * 24576 + 8192), 8192, sb + CB_VF);
      }
      T3(1);
      if (!NOBULK) wait_flags(fg + 512, n + 1);
      T3(2);
      fence_async_global();
      if (n > 0) bar_sync(B_R, 64);
      if (elect()) {
        mbar_expect(sb + CB_Q, 16384);
        bulk_load(sb + C_Q, blk + (c * 24576 + 16384), 8192, sb + CB_Q);
        bulk_load(sb + C_KV2, blk + ((c ^ 1) * 24576 + j * 4096), 4096, sb + CB_Q);
        bulk_load(sb + C_KV2 + 4096, blk + ((c ^ 1) * 24576 + 8192 + j * 4096), 4096, sb + CB_Q);
      }
      T3(3);
    }
  } else {
    const uint32_t near = __ballot_sync(~0u, near_half(XB_M + min(lane, MRING - 1u) * 8, c));
    uint32_t ring = 0;
    if (w > 1) {
      const uint32_t odd = w & 1, chk = pinned(sb + C_M + odd * 2048 + m_probe(lane)), again = sb + CB_MV + 32 + odd * 8;
      const bool one = elect();
      uint32_t mph = 0;
#pragma unroll 1
      for (int n = 0; n <= STEPS; n++) {
#pragma unroll
        for (int k = 0; k < 3; k++) {
          if (n == STEPS || (k == 2 && odd)) break;
          const uint32_t b = 2 * k + odd, at = chk + (k ? k * 8192 - 2048 + odd * 2048 : 0);
          uint32_t mb = sb + CB_M + b * 8, ph = n & 1;
          int it = 1;
          while (true) {
            mbar_wait(mb, ph);
            const bool bad = __any_sync(~0u, (k ? m_max(at, at + 2048) : max(m_max(at, at ^ 8), odd ? m_max(at + 2048, (at ^ 8) + 2048) : 0)) == SENT);
            if (one && !bad) mbar_arrive(sb + CB_MV + (k ? b * 8 - 8 : 0));
            if (!bad) break;
            mb = again; ph = mph; mph ^= 1;
            if (one) {
              if (k == 0) sts32(sb + C_BAD, n + 1);
              mbar_expect(mb, b ? 4096 : 2048);
              m_fetch(sb, ring * 65536 + ((near >> ring) & 1) * 4096, b, mb);
            }
            __syncwarp();
            spin_guard(it);
          }
          TR(41 + b * 4); CNT(6 + b, it);
        }
        ring = ring + 1 == MRING ? 0 : ring + 1;
        if (!odd) {
          if (n < STEPS) { TRSYNC(); TRDUMP(n - 2); }
        } else if (n > 0) {
          unsigned char* o = g_oimg + (uint32_t)(((n - 1) & (RING - 1)) * (N_CHAIN * 8192) + j * 4096);
          bar_sync(B_G, 160);
          fence_async_smem();
          if (one) {
            bulk_store(o + c * 8192, sb + C_Q, 4096);
            bulk_store(o + (c ^ 1) * 8192, sb + C_Q + 4096, 4096);
            asm volatile("cp.async.bulk.commit_group;\ncp.async.bulk.wait_group.read 0;" ::: "memory");
            { const int n_ = n - 1; { const int n = n_; T3(4); (void)n; } }
          }
          __syncwarp();
          if (n < STEPS) bar_arrive(B_R, 64);
          if (one) {
            bulk_done_inc(g_fl + FL_O + c);
            { const int n_ = n - 1; { const int n = n_; T3(5); (void)n; } }
          }
          __syncwarp();
        }
      }
    } else {
      const uint32_t* ts = g_fl + FL_SYNC + near_half(XB_F + 1, c) * 1024 + lane * 2;
      uint32_t t0 = clk() - 100000;
#pragma unroll 1
      for (int n = 0; n < STEPS; n++) {
        const uint32_t src = ring * 65536 + ((near >> ring) & 1) * 4096;
        if (lane < 5) mbar_expect(sb + CB_M + lane * 8, lane ? 4096 : 2048);
        __syncwarp();
        if (elect()) {
#pragma unroll
          for (int b = 0; b < 5; b++) {
            wait_until(t0, P.dly[14 + b]);
            m_fetch(sb, src, b, sb + CB_M + b * 8);
            TR(40 + b * 4);
          }
        }
        __syncwarp();
        ring = ring + 1 == MRING ? 0 : ring + 1;
        uint32_t va, vb;
        const uint32_t off = timer_offset(), tag = (uint32_t)(n + 1) << 24;
        bar_sync(B_QK, 416);
        if (n + 1 == STEPS) break;
        sts32(sb + C_REF + 4, 0);
        const uint32_t c0 = clk(), stamp = c0 + off;
        st_relaxed_if(g_fl + FL_SYNC + lane * 1024 + c, tag | (stamp & 0xFFFFFF), lane < 2);
        TR(13);
        wait_until(c0, DLYS);
        int it = 0;
        do {
          asm volatile("ld.relaxed.gpu.global.v2.u32 {%0,%1}, [%2];" : "=r"(va), "=r"(vb) : "l"(ts) : "memory");
          spin_guard(it);
        } while (__any_sync(~0u, ((va ^ tag) | (vb ^ tag)) >> 24));
        const int late = __reduce_max_sync(~0u, max((int)((va - stamp) << 8), (int)((vb - stamp) << 8))) >> 8;
        t0 = c0 + min((uint32_t)late, clk() - c0);
        if (elect()) {
          sts32(sb + C_REF, t0);
          mbar_arrive(sb + CB_REF);
        }
        st_relaxed_if(g_fl + FL_TICK + lane * 1024, tag | ((t0 + off) & 0xFFFFFF), c == 0 && lane < 2);
        TR(14); CNT(11, it);
        bar_sync(B_M, 160);
      }
    }
  }
}

template <int WG>
__device__ __forceinline__ void g_math(const Params& P, uint32_t sb) {
  const int q = g_unit(WG);
  const int lane = threadIdx.x & 31, w = (threadIdx.x >> 5) & 3;
  const bool isq = q >= 64;
  uint32_t a[136];
  {
    const uint32_t stage = sb + G_W + WG * 73728;
    mbar_wait(sb + W_BAR + WG * 8, 0);
    if (threadIdx.x == 0) TS(23);
    load_frags<34>(a, stage);
    fence_async_smem();
    bar_sync(B_WG0 + WG, 128);
    if (threadIdx.x == 0) TS(24);
    load_wg(P, sb, false, WG, w);
    if (threadIdx.x == 0) TS(25);
    mbar_wait(sb + W_BAR + WG * 8, 1);
  }
  if ((threadIdx.x & 127) == 0) TS(4);
  const uint32_t off0 = (q & 31) * 49152 + (q >> 5) * 8192 +
                        (isq ? (w >> 1) * 4096 + (w & 1) * 512 + lane * 16 : w * 1024 + (lane >> 2) * 64 + (((lane ^ (lane >> 3)) & 3) << 4));
#pragma unroll 1
  for (int n = 0; n < STEPS; n++) {
    float d0[32], d1[32];
    if (n > 0) bar_sync(B_V + WG, 256);
#pragma unroll
    for (int ch = 0; ch < 9; ch++) {
      mbar_wait(sb + G_BAR + ch * 8, n & 1);
      if (ch == 0) { if ((threadIdx.x & 127) == 0) T3(5 + WG * 3); __syncwarp(); }
      if (ch == 4) { if ((threadIdx.x & 127) == 0) T3(6 + WG * 3); __syncwarp(); }
      if (ch == 8 && (WG == 0 ? n > 0 : n + 1 < STEPS)) bar_arrive(B_V + (WG ^ 1), 256);
      wg_fence();
#pragma unroll
      for (int kk = 0; kk < 4 - FASTG; kk++) {
        const int i = ch * 4 + kk;
        float* d = i & 1 ? d1 : d0;
        const uint64_t db = desc_sw128(G_RING + ch * 8192 + (kk & 2) * 32);
        if (i < 2) wg_rs64<0>(d, a + i * 4, db);
        else if (i < 34) wg_rs64<1>(d, a + i * 4, db);
        else wg_ss64<1>(d, desc_sw128(G_W2 + WG * 4096 + (i - 34) * 2048), db);
        wg_ss64<1>(d, desc_sw128(G_W + WG * 73728 + i * 2048), db + 2);
      }
      wg_commit();
      if (ch > 0) { wg_wait<1>(); if (lane == 0) mbar_arrive(sb + G_BAR + 128 + (ch - 1) * 8); }
    }
    wg_wait<0>();
    if (lane == 0) mbar_arrive(sb + G_BAR + 128 + 8 * 8);
    if ((threadIdx.x & 127) == 0) T3(7 + WG * 3);
    __syncwarp();
    uint32_t tw = clk() + (WG == 0 && n >= LOCK0 ? DLYW : 0);
    unsigned char* base = g_qkv + (size_t)(n & (RING - 1)) * (N_CHAIN * 24576);
    if ((ABL & 1) && d0[0] != 1234.5f) {
    } else if (isq) {
#pragma unroll
      for (int i = 0; i < 8; i++) {
        const float *d = (i < 4 ? d0 : d1) + 4 * i, *e = (i < 4 ? d1 : d0) + 4 * i;
        wait_until(tw, 0); tw += P.dly[2 + WG];
        *(uint4*)(base + off0 + (i >> 2) * 24576 + (i & 3) * 1024) =
          make_uint4(movmat(pack2(d[0], d[1])), movmat(pack2(e[0], e[1])), movmat(pack2(d[2], d[3])), movmat(pack2(e[2], e[3])));
      }
    } else {
#pragma unroll
      for (int i = 0; i < 8; i++) {
        const float* d = (i < 4 ? d0 : d1) + 8 * (i & 2) + 2 * (i & 1);
        wait_until(tw, 0); tw += P.dly[2 + WG];
        *(uint4*)(base + off0 + (i >> 2) * 24576 + (i & 2) * 2048 + (i & 1) * 512) =
          make_uint4(pack2(d[0], d[1]), pack2(d[4], d[5]), pack2(d[8], d[9]), pack2(d[12], d[13]));
      }
    }
    bar_arrive(B_M + WG, 160);
  }
}

__device__ __forceinline__ void fill16(void* p, uint32_t v) {
  asm volatile("st.global.v4.u32 [%0], {%1,%1,%1,%1};" :: "l"(p), "r"(v) : "memory");
}
__device__ __forceinline__ void g_load(const Params& P, uint32_t sb) {
  const int lane = threadIdx.x & 31, w = __shfl_sync(~0u, (threadIdx.x >> 5) & 3, 0);
  if (w == 2) return;
  uint32_t fl = 0;
#pragma unroll 1
  for (int n = 0; n < STEPS; n++) {
    if (w == 3) {
      if (n == 0) wait_flags(g_lnflag + (lane & 1) * 8, 1);
      if (n == LOCK0) { grid_wait(1, lds32(sb + S_GEN)); fl = near_half(XB_F, bid()) * 1024; }
      if (!NOCHAIN && n >= LOCK0) {
        const uint32_t tag = (uint32_t)(n - LOCK0 + 1) << 24;
        uint32_t v; int it = 0;
        do { asm volatile("ld.relaxed.gpu.global.u32 %0, [%1];" : "=r"(v) : "l"(g_fl + fl + FL_TICK) : "memory"); spin_guard(it); } while (v < tag);
        const uint32_t off = timer_offset(), now = clk(), t0 = now - ((v ^ tag) >> 24 ? DLYG : (now + off - v) & 0xFFFFFF);
        asm volatile("fence.acquire.gpu;" ::: "memory");
        if (lane == 0) T3(11);
        if (n >= LAG) wait_flags(g_fl + fl + FL_F + (lane & 1) * 8, n - LAG + 1);
        if (lane == 0) T3(12);
        __syncwarp();
        wait_until(t0, DLYG);
      }
      bar_sync(B_X, 128);
      continue;
    }
    if (w == 0) {
      if (n < NSEG) wait_flags(g_lnflag + n * 16 + (lane & 1) * 8, 1);
    } else {
      bar_sync(B_X, 128);
      if (lane == 0) T3(4);
    }
    fence_async_global();
    const unsigned char* src = g_lnimg + (uint32_t)((w ? (n >= LAG ? NSEG + n - LAG : 0) : min(n, NSEG - 1)) * 36864);
#pragma unroll 1
    for (int ch = 0; ch < 9; ch++) {
      const uint32_t full = sb + G_BAR + ch * 8;
      mbar_wait(full + 128, (n & 1) ^ 1);
      if (elect()) {
        mbar_expect(full, ABL & 2 ? 16 : 4096);
        bulk_load(sb + G_RING + ch * 8192 + w * 4096, src + ch * 4096, ABL & 2 ? 16 : 4096, full);
      }
    }
  }
}

__device__ __forceinline__ void g_aux(const Params& P, uint32_t sb) {
  const int lane = threadIdx.x & 31, w = (threadIdx.x >> 5) & 3;
  if (w == 1 || w == 2) {
    const int q = g_unit(w - 1);
    uint32_t* f = g_fl + FL_G + q * 8;
#pragma unroll 1
    for (int n = 0; n < STEPS; n++) {
      const uint32_t ln = opaque_tid() & 31;
      uint4* z = (uint4*)g_oacc + (uint32_t)(((n + 1) % ARING) * (16 * DM) + q * 96 + ln);
      fill16(z, 0); fill16(z + 32, 0); fill16(z + 64, 0);
      if (n + 3 >= MRING && q < 80) fill16((uint4*)g_mimg + (uint32_t)(((n + 3) % MRING) * 4096 + q * 32 + ln), SENT);
      bar_sync(B_M + (w - 1), 160);
      if (lane == 0) { T3(w * 2 - 2); fence_async_global(); flag_release(f, n + 1); T3(w * 2 - 1); }
      __syncwarp();
    }
  } else {
    const uint32_t u = (bid() - N_CHAIN) * 2 + (w & 1), r = u / 36 * 16 + (u & 3) * 4 + (lane >> 3);
    uint32_t o = r * (DM / 8) + (u % 36 >> 2) * 8 + ((lane & 7) ^ ((r >> 1) & 3));
#pragma unroll 1
    for (int k = -LAG - 1; k < STEPS; k++) {
      if (k < NSEG - 1) bar_sync(B_X, 128);
      if (k < LAG || u >= 72) continue;
      if (k >= NSEG - 1) {
        const uint32_t* f = g_fl + near_half(XB_F, bid()) * 1024;
        if (k + 1 == STEPS) wait_flags(f + FL_F + (lane & 1) * 8, NSEG + 1);
        wait_flags(f + FL_OCNT + (max(k, NSEG) % OCRING) * 8, N_O * 3 * (max(k, NSEG) / OCRING + 1));
      }
      const float4* a = (const float4*)g_oacc + ((k % ARING) * (16 * DM) + 8 * DM + u * 64 + lane * 2);
      const float4 p = __ldcg(a), v = __ldcg(a + 1);
      const uint4 x = __ldcg((const uint4*)P.out + o);
      ((uint4*)P.out)[o] = make_uint4(badd2(x.x, pack2(p.x, p.y)), badd2(x.y, pack2(p.z, p.w)), badd2(x.z, pack2(v.x, v.y)), badd2(x.w, pack2(v.z, v.w)));
      o += 4 * DM;
    }
    if ((threadIdx.x & 127) == 0) TS(7);
  }
}

template <int WG>
__device__ __forceinline__ void o_math(const Params& P, uint32_t sb) {
  const int ksl = (bid() - N_CHAIN - N_G) / 3;
  const int nc = ksl < 4 ? 11 : 10;
  const int lane = threadIdx.x & 31, w = (threadIdx.x >> 5) & 3, g = lane >> 2, tq = lane & 3;
  uint32_t a[96];
  {
    mbar_wait(sb + W_BAR + WG * 8, 0);
    load_frags<24>(a, sb + WG * 49152);
    fence_async_smem();
    bar_sync(B_INIT, 416);
    load_wg(P, sb, false, WG, w);
    mbar_wait(sb + W_BAR + WG * 8, 1);
  }
  if ((threadIdx.x & 127) == 0) TS(4);
  const uint32_t st0 = sb + O_ST + tq * 512 + ((w * 16 + g) ^ (tq * 8)) * 4;
#pragma unroll 1
  for (int n = 0; n < STEPS; n++) {
    float d[32];
    if (WG > 0 || n > 0) bar_sync(B_V + WG, 256);
#pragma unroll
    for (int gr = 0; gr < 5; gr++) {
      mbar_wait(sb + O_BAR + gr * 8, n & 1);
      if (gr == 0) { if ((threadIdx.x & 127) == 0) T3(13 + WG); __syncwarp(); }
      if (gr == (WG == 0 ? OTURN : 4) && (WG < 2 || n + 1 < STEPS)) bar_arrive(B_V + (WG + 1) % 3, 256);
      wg_fence();
#pragma unroll
      for (int ks = gr * 8; ks < gr * 8 + 8 - 2 * FASTG; ks++) {
        const uint64_t db = desc_sw128(O_RING + (ks >> 2) * 8192 + (ks & 3) * 32);
        if (ks == 0) wg_rs64<0>(d, a, db);
        else if (!(ks % 5 & 1)) wg_rs64<1>(d, a + (ks / 5 * 3 + ks % 5 / 2) * 4, db);
        else wg_ss64<1>(d, desc_sw128(O_W + WG * 40960 + (ks / 5 * 2 + ks % 5 / 2) * 2048), db);
      }
      if (gr == 4 && nc == 11) {
#pragma unroll
        for (int ks = 40; ks < 44; ks++)
          wg_ss64<1>(d, desc_sw128(O_W + WG * 40960 + (ks - 24) * 2048), desc_sw128(O_RING + 10 * 8192 + (ks & 3) * 32));
      }
      wg_commit();
      if (gr > 0) { wg_wait<1>(); if (lane == 0) mbar_arrive(sb + O_BAR + 128 + (gr - 1) * 8); }
    }
    wg_wait<0>();
    if (lane == 0) mbar_arrive(sb + O_BAR + 128 + 4 * 8);
    if ((threadIdx.x & 127) == 0) T3(WG == 0 ? 1 : WG == 1 ? 8 : 12);
    __syncwarp();
#pragma unroll
    for (int sl = 0; sl < 2; sl++) {
      mbar_wait(sb + OB_ST + WG * 16 + sl * 8, (n & 1) ^ (WG == 0));
#pragma unroll
      for (int nb = sl * 4; nb < sl * 4 + 4; nb++) {
        sts32(st0 + nb * 2048, __float_as_uint(d[nb * 4]));
        sts32(st0 + nb * 2048 + 256, __float_as_uint(d[nb * 4 + 1]));
        sts32((st0 ^ 32) + nb * 2048, __float_as_uint(d[nb * 4 + 2]));
        sts32((st0 ^ 32) + nb * 2048 + 256, __float_as_uint(d[nb * 4 + 3]));
      }
      fence_async_smem();
      bar_arrive((sl ? B_G : B_M) + WG, 160);
    }
  }
}

__device__ __forceinline__ void o_aux(const Params& P, uint32_t sb) {
  const int i = bid() - N_CHAIN - N_G, ksl = i / 3;
  const int c0 = ksl * 11 - max(ksl - 4, 0), nc = ksl < 4 ? 11 : 10;
  const int lane = threadIdx.x & 31, w = __shfl_sync(~0u, (threadIdx.x >> 5) & 3, 0);
  if (w == 0) {
    bar_sync(B_INIT, 416);
    const uint32_t* f = g_fl + FL_O + near_half(XB_F + 1, bid()) * 1024 + min((c0 & ~1) + lane, (c0 + nc - 1) | 1);
#pragma unroll 1
    for (int n = 0; n < STEPS; n++) {
      const unsigned char* src = g_oimg + (uint32_t)(((n % RING) * N_CHAIN + c0) * 8192);
      if (!NOCHAIN) wait_flags(f, n + 1);
      fence_async_global();
      if (lane == 0) T3(0);
#pragma unroll
      for (int gr = 0; gr < 5; gr++) {
        const uint32_t full = sb + O_BAR + gr * 8, bytes = ABL & 4 ? 16 : (gr < 4 ? 2 : nc - 8) * 8192;
        mbar_wait(full + 128, (n & 1) ^ 1);
        if (elect()) {
          mbar_expect(full, bytes);
          bulk_load(sb + O_RING + gr * 16384, src + gr * 16384, bytes, full);
        }
      }
    }
  } else {
#pragma unroll 1
    for (int n = 0; n < STEPS; n++) {
      float* dst = g_oacc + (uint32_t)((n % ARING) * (64 * DM) + ((i % 3) * 3 + (w - 1 + ksl) % 3) * 1024);
      const bool early = w == 3 && n < NSEG;
      bar_sync(B_M + (w - 1), 160);
      if (lane == 0) {
        T3(w * 2);
        if (n < NSEG && !(ABL & 8)) { bulk_reduce(dst, sb + O_ST, 4096); bulk_reduce(dst + 16 * DM, sb + O_ST + 4096, 4096); }
        asm volatile("cp.async.bulk.commit_group;" ::: "memory");
        if (early) {
          asm volatile("cp.async.bulk.wait_group.read 0;" ::: "memory");
          mbar_arrive(sb + OB_ST);
          T3(8 + w);
          bulk_done_inc(g_fl + FL_OCNT + (n % OCRING) * 8);
          T3(w * 2 + 1);
        }
      }
      __syncwarp();
      bar_sync(B_G + (w - 1), 160);
      if (lane == 0) {
        if (n >= LAG && !(ABL & 8)) { bulk_reduce(dst + 32 * DM, sb + O_ST + 8192, 4096); bulk_reduce(dst + 48 * DM, sb + O_ST + 12288, 4096); }
        asm volatile("cp.async.bulk.commit_group;\ncp.async.bulk.wait_group.read 1;" ::: "memory");
        if (!early) mbar_arrive(sb + OB_ST + (w % 3) * 16);
        asm volatile("cp.async.bulk.wait_group.read 0;" ::: "memory");
        mbar_arrive(sb + OB_ST + (w % 3) * 16 + 8);
        if (!early) {
          T3(8 + w);
          bulk_done_inc(g_fl + FL_OCNT + (n % OCRING) * 8);
          T3(w * 2 + 1);
        }
      }
      __syncwarp();
    }
  }
}

constexpr uint32_t Y_PITCH = 1168, Y_ROWS = 16 * Y_PITCH;
template <int R> __device__ __forceinline__ void y_rows(uint32_t* y, uint32_t src, uint32_t dst, int w, int bar) {
  const int lane = threadIdx.x & 31;
#pragma unroll
  for (int k = 0; k < 2 * R + 1; k++) {
    const int op = w + k * (16 / R);
    if (k == 2 * R && w >= 4) break;
    uint32_t a, b, c, d;
    ldsm4t(a, b, c, d, src + op * 512 + (lane & 16) * 16 + (lane & 7) * 32 + (lane & 8) * 2);
    stsm4(dst + (lane & 15) * Y_PITCH + op * 32 + (lane & 16), a, b, c, d);
  }
  bar_sync(bar, 512 / R);
  const uint32_t row = dst + ((w & 6) * 2 + (w >> 3) * 2 + (w & 1)) * Y_PITCH + lane * 4;
#pragma unroll
  for (int i = 0; i < 9 * R; i++) y[i] = lds32(row + i / 9 * 2 * Y_PITCH + i % 9 * 128);
}

__device__ __forceinline__ void f_role(const Params& P, uint32_t sb) {
  const int lane = threadIdx.x & 31, w = __shfl_sync(~0u, threadIdx.x >> 5, 0), r0 = (bid() - N_CHAIN - N_G - N_O) * 16;
  if (w == 8) {
    const uint32_t* fo = g_fl + FL_OCNT + near_half(XB_F, bid()) * 1024;
    fence_async_global();
#pragma unroll 1
    for (int n = 0; n < NSEG; n++) {
      if (n > 0) bar_sync(2, 288);
      if (elect()) {
        mbar_expect(sb + F_BAR, 36864);
        bulk_load(sb + F_XY, P.X + (size_t)(n * 32 + r0) * DM, 18432, sb + F_BAR);
        bulk_load(sb + F_XY + 18432, g_yT + (size_t)(n * 32 + r0) * DM, 18432, sb + F_BAR);
        mbar_expect(sb + F_BAR + 8, 36864);
        T3(1);
      }
      wait_flags(fo + (n % OCRING) * 8, NOCHAIN == 5 ? 0 : N_O * 3 * (n / OCRING + 1));
      fence_async_global();
      if (elect()) { bulk_load(sb + F_A, g_oacc + (uint32_t)((n % ARING) * (64 * DM) + r0 * DM), 36864, sb + F_BAR + 8); T3(0); }
    }
  } else if (w == 9) {
#pragma unroll 1
    for (int n = 0; n < NSEG; n++) {
      const uint32_t st = sb + (n & 1) * 36864;
      unsigned char* p = g_lnimg + (uint32_t)((NSEG + n) * 36864 + r0 * 128);
      bar_sync(1, 288);
      if (elect()) {
        T3(2);
#pragma unroll
        for (int i = 0; i < 9; i++) bulk_store(p + i * 4096, st + F_L + i * 2048, 2048);
        asm volatile("cp.async.bulk.commit_group;" ::: "memory");
        bulk_done_inc(g_fl + FL_F + (bid() & 1) * 8);
        T3(3);
        bulk_store(P.out + (size_t)(n * 32 + r0) * DM, st + F_X, 18432);
        asm volatile("cp.async.bulk.commit_group;\ncp.async.bulk.wait_group.read 0;" ::: "memory");
        if (n + 1 == NSEG) bulk_done_inc(g_fl + FL_F + (bid() & 1) * 8);
      }
      __syncwarp();
    }
  } else if (w < 8) {
    const uint32_t row = sb + w * 1152 + lane * 4, acc = sb + F_A + w * 256 + (lane ^ ((w & 6) * 2)) * 8;
    const uint32_t ln = sb + F_L + w * 128 + (((lane >> 2) ^ w) << 4) + (lane & 3) * 4;
#pragma unroll 1
    for (int n = 0; n < NSEG; n++) {
      const uint32_t st = (n & 1) * 36864;
      uint32_t x[18], y[18], l[18];
      mbar_wait(sb + F_BAR, n & 1);
#pragma unroll
      for (int i = 0; i < 18; i++) x[i] = lds32(row + F_XY + i / 9 * 9216 + i % 9 * 128);
      y_rows<2>(y, sb + F_XY + 18432, sb + F_Y, w, 3);
      layernorm9<2>(x, l);
#pragma unroll
      for (int i = 0; i < 18; i++) x[i] = badd2(x[i], bmul2(l[i], y[i]));
      mbar_wait(sb + F_BAR + 8, n & 1);
      if (threadIdx.x == 0) T3(4);
      __syncwarp();
      uint2 a[18];
#pragma unroll
      for (int i = 0; i < 18; i++) a[i] = lds64(acc + i / 9 * 2048 + i % 9 * 4096);
#pragma unroll
      for (int i = 0; i < 18; i++) x[i] = badd2(x[i], pack2(__uint_as_float(a[i].x), __uint_as_float(a[i].y)));
      if (n + 1 < NSEG) bar_arrive(2, 288);
      layernorm9<2>(x, l);
#pragma unroll
      for (int i = 0; i < 18; i++) { x[i] = badd2(x[i], bmul2(l[i], y[i])); sts32(row + st + F_X + i / 9 * 9216 + i % 9 * 128, x[i]); }
      layernorm9<2>(x, l);
#pragma unroll
      for (int i = 0; i < 18; i++) sts32(ln + st + i / 9 * 1024 + i % 9 * 2048, l[i]);
      fence_async_smem();
      bar_sync(1, 288);
    }
  }
}

constexpr uint32_t P_CH = 147456, P_CHSZ = 12800, P_H = 4352;
static_assert(P_CH + 6 * P_CHSZ <= G_BAR, "prologue smem");

template <int N>
__device__ __forceinline__ void conv_fold(float (*acc)[4], bool hi, uint32_t mine, uint32_t theirs, int bar, int cnt) {
#pragma unroll
  for (int i = 0; i < N / 2; i++) {
    uint4 v;
    v.x = __float_as_uint(hi ? acc[i][0] : acc[i + N / 2][0]); v.y = __float_as_uint(hi ? acc[i][1] : acc[i + N / 2][1]);
    v.z = __float_as_uint(hi ? acc[i][2] : acc[i + N / 2][2]); v.w = __float_as_uint(hi ? acc[i][3] : acc[i + N / 2][3]);
    sts128(mine + i * 512, v);
  }
  bar_sync(bar, cnt);
#pragma unroll
  for (int i = 0; i < N / 2; i++) {
    const uint4 v = lds128(theirs + i * 512);
    acc[i][0] = (hi ? acc[i + N / 2][0] : acc[i][0]) + __uint_as_float(v.x); acc[i][1] = (hi ? acc[i + N / 2][1] : acc[i][1]) + __uint_as_float(v.y);
    acc[i][2] = (hi ? acc[i + N / 2][2] : acc[i][2]) + __uint_as_float(v.z); acc[i][3] = (hi ? acc[i + N / 2][3] : acc[i][3]) + __uint_as_float(v.w);
  }
}
template <int N>
__device__ __forceinline__ void conv_store(const float (*acc)[4], int tile0, uint32_t su, int d, uint32_t dd) {
  const int lane = threadIdx.x & 31, g = lane >> 2, tq = lane & 3;
#pragma unroll
  for (int i = 0; i < N; i++) {
    const uint32_t ad = su + (8 + (tile0 + i) * 8 + g) * 32 + tq * 4, sw = (g & 4) << 2;
    const uint32_t lo = badd2(movmat(pack2(acc[i][0], acc[i][1])), bmul2(lds32(ad + sw), dd));
    const uint32_t hi = badd2(movmat(pack2(acc[i][2], acc[i][3])), bmul2(lds32(ad + (sw ^ 16)), dd));
    ((uint2*)g_yT)[(((tile0 + i) * 8 + g) * DM + d) * 4 + tq] = make_uint2(lo, hi);
  }
}

__device__ __forceinline__ void prologue(const Params& P, uint32_t sb) {
  const int b = bid(), tid = threadIdx.x, lane = tid & 31, warp = tid >> 5, t0 = b * 16;
  const bool isg = b >= N_CHAIN && b < N_CHAIN + N_G;
  const int nch = isg ? 2 : b < 128 ? 6 : 0, chb = b < N_CHAIN ? b * 6 : isg ? b * 2 + 256 : b * 6 - 192;
  const uint32_t tstart = clk();
  if (tid < 288) {
    if (b < 128) {
      const int c = (tid >> 1) * 4, tt = t0 + (tid & 1) * 8;
      uint2 kr[11], vr[8];
#pragma unroll
      for (int i = 0; i < 11; i++) { const int t = tt + i - 3; kr[i] = t >= 0 ? __ldg((const uint2*)(P.K + (size_t)t * DM + c)) : make_uint2(0, 0); }
#pragma unroll
      for (int i = 0; i < 8; i++) vr[i] = __ldg((const uint2*)(P.V + (size_t)(tt + i) * DM + c));
#pragma unroll
      for (int e = 0; e < 2; e++) {
        const uint4 sh = __ldg((const uint4*)(P.shift + c * 4) + e);
        const uint32_t s0 = __byte_perm(sh.x, sh.z, 0x5410), s1 = __byte_perm(sh.x, sh.z, 0x7632);
        const uint32_t s2 = __byte_perm(sh.y, sh.w, 0x5410), s3 = __byte_perm(sh.y, sh.w, 0x7632);
        uint32_t v[8];
#pragma unroll
        for (int i = 0; i < 8; i++) {
          const uint32_t k3 = e ? kr[i].y : kr[i].x, k2 = e ? kr[i + 1].y : kr[i + 1].x, k1 = e ? kr[i + 2].y : kr[i + 2].x, k0 = e ? kr[i + 3].y : kr[i + 3].x;
          v[i] = bmul2(badd2(badd2(badd2(bmul2(k3, s3), bmul2(k2, s2)), bmul2(k1, s1)), bmul2(k0, s0)), e ? vr[i].y : vr[i].x);
        }
        *(uint4*)(g_kvT + (size_t)(c + 2 * e) * KVP + tt) =
          make_uint4(__byte_perm(v[0], v[1], 0x5410), __byte_perm(v[2], v[3], 0x5410), __byte_perm(v[4], v[5], 0x5410), __byte_perm(v[6], v[7], 0x5410));
        *(uint4*)(g_kvT + (size_t)(c + 2 * e + 1) * KVP + tt) =
          make_uint4(__byte_perm(v[0], v[1], 0x7632), __byte_perm(v[2], v[3], 0x7632), __byte_perm(v[4], v[5], 0x7632), __byte_perm(v[6], v[7], 0x7632));
      }
    }
  } else if (tid < 384) {
    const int t = tid - 288;
    for (int i = t; i < 32 * nch; i += 96) asm volatile("prefetch.global.L2 [%0];" :: "l"(P.Hk + (size_t)chb * SEQ + i * 64));
    for (int i = b * 96 + t; i < 32 * DM; i += N_CTA * 96) ((uint4*)g_oacc)[i] = make_uint4(0, 0, 0, 0);
    if (b * 96 + t < 128 * 8) g_lnflag[b * 96 + t] = 0;
    if (t == 95) sts32(sb + S_GEN, ld_acquire(g_gbar));
  }
  if (warp < 12) {
    bar_arrive(10, 448);
    if (tid == 128) TS(14);
    const int ch = warp >> 1, sub = warp & 1, d = chb + ch;
    const uint32_t su = sb + P_CH + ch * P_CHSZ;
    if (ch < nch) {
      const uint32_t* hs = (const uint32_t*)(P.Hk + (size_t)d * SEQ);
#pragma unroll
      for (int q = sub * 32 + lane; q < 256; q += 64) {
        const uint4 c = __ldg((const uint4*)hs + q);
        const uint32_t prev = q ? __ldg(hs + 4 * q - 1) : 0u;
        sts128(su + P_H + 32 + q * 16, make_uint4(__byte_perm(c.x, prev, 0x7610), __byte_perm(c.y, c.x, 0x7610), __byte_perm(c.z, c.y, 0x7610), __byte_perm(c.w, c.z, 0x7610)));
        sts128(su + P_H + 4224 + q * 16, make_uint4(__byte_perm(c.x, 0, 0x1032), __byte_perm(c.y, 0, 0x1032), __byte_perm(c.z, 0, 0x1032), __byte_perm(c.w, 0, 0x1032)));
      }
      if (sub == 1 && lane == 0) sts32(su + P_CHSZ - 16, __bfloat16_as_ushort(P.Dk[d]) * 0x10001u);
      if (sub == 0 && lane < 20) sts128(su + (lane < 16 ? lane * 16 : P_H + (lane & 2) * 2096 + (lane & 1) * 16), make_uint4(0, 0, 0, 0));
    }
    bar_sync(11, 416);
    if (ch < nch) {
#pragma unroll
      for (int q = sub * 32 + lane; q < 256; q += 64) {
        const int row = (q >> 1) + 8;
        sts128(su + row * 32 + (((q & 1) ^ ((row >> 2) & 1)) << 4), __ldcg((const uint4*)(g_kvT + (size_t)d * KVP) + q));
      }
    }
    const int g = lane >> 2, tq = lane & 3;
    const uint32_t sh = su + P_H + (g & 1) * 4192 + (8 + (g >> 1) - tq) * 4;
    float acc[16][4];
#pragma unroll
    for (int i = 0; i < 16; i++) { acc[i][0] = acc[i][1] = acc[i][2] = acc[i][3] = 0.f; }
    auto u_addr = [&](int res) {
      const int row = 8 - res + ((lane >> 4) << 3) + (lane & 7);
      return su + row * 32 + ((((lane >> 3) & 1) ^ ((row >> 2) & 1)) << 4);
    };
    if (ch < nch) {
      bar_sync(1 + ch, 64);
      if (tid == 0) TS(11);
      if (sub) {
#pragma unroll 4
        for (int res = 0; res < 8; res++) {
          uint32_t b0, b1, b2, b3;
          ldsm4(b0, b1, b2, b3, u_addr(res));
          const uint32_t r0 = lds32(sh + res * 32);
          mma16(acc[0], r0, lds32(sh + res * 32 + 16), lds32(sh + res * 32 - 16), r0, b0, b1);
        }
        conv_store<1>(acc, 0, su, d, lds32(su + P_CHSZ - 16));
      }
    }
    bar_arrive(12, 416);
    if (isg && warp >= 4) { wait_until(tstart, S1G); load_wg(P, sb, true, warp >> 3, warp & 3); }
    if (ch < nch) {
#pragma unroll 1
      for (int res = sub * 4; res < sub * 4 + 4; res++) {
        uint32_t bf[16][2];
        const uint32_t ad = u_addr(res);
#pragma unroll
        for (int f = 0; f < 16; f += 2) ldsm4(bf[f][0], bf[f][1], bf[f + 1][0], bf[f + 1][1], ad + f * 256);
#pragma unroll
        for (int jj = 0; jj < 16; jj++) {
          const uint32_t ah = sh + (8 * jj + res) * 32;
          const uint32_t r0 = lds32(ah), r1 = lds32(ah + 16), rm = lds32(ah - 16);
#pragma unroll
          for (int i = max(jj, 1); i < 16; i++) mma16(acc[i], r0, r1, rm, r0, bf[i - jj][0], bf[i - jj][1]);
        }
      }
      bar_sync(1 + ch, 64);
      if (tid == 0) TS(12);
      const uint32_t xb = su + P_H + lane * 16, dd = lds32(su + P_CHSZ - 16);
      conv_fold<16>(acc, sub, xb + sub * 4096, xb + (sub ^ 1) * 4096, 1 + ch, 64);
      conv_store<8>(acc, sub * 8, su, d, dd);
    }
  } else {
    for (int i = b; i < 194 + MRING * 5; i += N_CTA) {
      const int n = (i - 194) / 5, r = (i - 194) % 5, blk = i < 192 ? i / 6 * 8 + i % 6 : i < 194 ? XB_F + i - 192 : XB_M + n * 8 + r;
      const uint32_t fill = i < 194 ? 0u : SENT;
#pragma unroll 1
      for (int q = tid - 384; q < 256 && warp < 15; q += 96) {
        uint4 v = make_uint4(fill, fill, fill, fill);
        if (i >= 194 && (n == 0 || (n <= LAG && ((q ^ (q >> 3)) & 1))) && (r > 0 || q < 128)) {
          const bf16* m = P.mem0 + (max(r * 8 - 4, 0) + (q >> 5)) * 16 + ((q >> 1) & 1) * 8 + ((q >> 2) & 7);
          v.x = pack2(__bfloat162float(m[0]), __bfloat162float(m[DM])); v.y = pack2(__bfloat162float(m[2 * DM]), __bfloat162float(m[3 * DM]));
          v.z = pack2(__bfloat162float(m[4 * DM]), __bfloat162float(m[5 * DM])); v.w = pack2(__bfloat162float(m[6 * DM]), __bfloat162float(m[7 * DM]));
        }
        g_xb[blk * 512 + q] = v;
        g_xb[blk * 512 + 256 + q] = v;
      }
    }
    if (tid < 388) g_xb[XB_REF * 512 + (tid & 2) * 128 + (b & ~1) + (tid & 1)] = make_uint4(0, 0, 0, 0);
    else if (tid < 392 && b < N_GRP) g_xb[(b * 8 + 7) * 512 + (tid & 2) * 128 + (tid & 1)] = make_uint4(0, 0, 0, 0);
    if (warp < 15) { bar_arrive(9, 128); bar_sync(7, 96); }
    if (tid == 384) TS(8);
    if (warp == 12) {
      const bf16* w = lane < 6 ? (lane % 3 == 0 ? P.Wk : lane % 3 == 1 ? P.Wv : P.Wq) + (((b >> 5) * 2 + lane / 3) * 32 + (b & 31)) * 2048
                               : (lane < 8 ? P.Wo + (lane - 6) * (9 * 131072) : P.X) + b * 2048;
      bar_sync(10, 448);
      uint32_t t = clk() + P.dly[19];
#pragma unroll 1
      for (int st = 0; st < 9 && b < N_CHAIN; st++) {
#pragma unroll 1
        for (int i = 0; i < 9; i++, t += PACE) {
          wait_until(t, 0);
          if (lane == st) asm volatile("cp.async.bulk.prefetch.L2.global [%0], 4096;" :: "l"(w + i * (lane < 6 ? 262144 : 131072)) : "memory");
        }
      }
      if (lane == 0) TS(10);
    } else if (warp == 15) {
      bar_sync(10, 448);
      if (lane == 0) { grid_arrive(0); if (nch) grid_wait(0, lds32(sb + S_GEN)); }
      __syncwarp();
      bar_arrive(11, 416);
      if (lane == 0) TS(1);
      bar_sync(9, 128);
      bar_sync(12, 416);
      if (lane == 0) { TS(16); grid_arrive(2); TS(17); }
    } else if (lane == 0) {
      if (warp == 13 || (warp == 14 && b < N_GRP)) {
        uint32_t* p = (uint32_t*)(g_xb + (warp == 13 ? XB_REF * 512 + b : (b * 8 + 7) * 512));
        int votes = 0;
        for (int rep = 0; rep < 24 && abs(votes) < 7; rep++) {
          uint32_t v0, v1, c0, c1;
          asm volatile("atom.relaxed.gpu.global.add.u32 %0, [%4], 0;\n atom.relaxed.gpu.global.add.u32 %1, [%5], 0;\n"
                       "{.reg .pred p; setp.eq.u32 p, %0, 0x7ffffff3; @p trap; mov.u32 %2, %%clock; setp.eq.u32 p, %1, 0x7ffffff3; @p trap; mov.u32 %3, %%clock;}"
                       : "=&r"(v0), "=&r"(v1), "=&r"(c0), "=&r"(c1) : "l"(p + (rep & 1) * 1024), "l"(p + ((rep & 1) ^ 1) * 1024) : "memory");
          votes += ((c1 - c0 > 80u) == (rep & 1)) ? 1 : -1;
        }
        if (warp == 13) { g_side[b] = votes > 0; TS(9); } else g_near[b] = votes > 0;
      }
    }
    __syncwarp();
    if (warp > 12 && b < N_CHAIN) {
      wait_until(tstart, S1DLY);
      for (int k = warp - 13; k < 8; k += 3) load_wg(P, sb, true, 1 - k / 4, k & 3);
    }
  }
  __syncthreads();
  if (tid == 511) { grid_arrive(1); TS(18); }
  if (tid == 0) TS(2);
}

template <int R> __device__ __forceinline__ void ln_tiles(const Params& P, uint32_t sb) {
  const int lane = threadIdx.x & 31, w = (threadIdx.x >> 5) & (16 / R - 1), half = R == 1 ? 0 : threadIdx.x >> 8, u = N_CTA - 1 - bid();
  const int first = R == 1 ? u : 46 - 2 * u + half, step = R == 1 ? 4 : 40, last = R == 1 ? 8 : 128;
  const uint32_t raw = sb + P_CH + half * (18432 + Y_ROWS), mb = sb + T_BAR + (R - 1 + half) * 8;
  const bool lead = w == 16 / R - 1 && lane == 0;
  auto load_y = [&](const bf16* src, int tile) {
    fence_async_global();
    mbar_expect(mb, 18432);
    bulk_load(raw, src + (size_t)tile * 16 * DM, 18432, mb);
  };
  if (R == 2 && u >= N_F && w < 6) load_wg(P, sb, true, w >> 1, half * 2 + (w & 1));
#pragma unroll 1
  for (int tile = first, real = R - 1, ph = 0; tile < last; tile += real * step, real = 1, ph ^= 1) {
    uint32_t x[9 * R], l[9 * R], y[9 * R];
    const bool ts = threadIdx.x == 0 && (R == 1 ? tile == first : u > 3 && tile == first + step);
    if (ts) TS(26);
#pragma unroll
    for (int i = 0; i < 9 * R; i++) x[i] = __ldg((const uint32_t*)(P.X + (size_t)(tile * 16 + w + i / 9 * 8) * DM) + i % 9 * 32 + lane);
    layernorm9<R>(x, l);
    if (tile == first && lead) {
      if (real) grid_wait(3 - R, lds32(sb + S_GEN));
      if (R == 1 || u > 3) TS(13);
      load_y(real ? g_yT : P.Hk, tile);
    }
    bar_sync(13 + half, 512 / R);
    mbar_wait(mb, ph);
    if (ts) TS(28);
    y_rows<R>(y, raw, raw + 18432, w, 13 + half);
    if (ts) TS(29);
    if (lead && real && tile + step < last) { fence_async_smem(); load_y(g_yT, tile + step); }
    __syncwarp();
#pragma unroll
    for (int i = 0; i < 9 * R; i++) x[i] = badd2(x[i], bmul2(l[i], y[i]));
    layernorm9<R>(x, l);
    if (ts && l[0] != 0x12345) TS(30);
#pragma unroll
    for (int r = 0; r < R; r++) store_ln_row(0, tile * 16 + w + r * 8, l + r * 9);
    if (R == 1) {
      __syncthreads();
      if (threadIdx.x == 32 && real) { if (tile < 4) TS(19); st_release(g_lnflag + tile * 8, 1); if (tile < 4) TS(20); }
      __syncwarp();
    }
    if (ts) TS(31);
  }
  if (R == 2) {
    __syncthreads();
    if (threadIdx.x >= 506) {
      asm volatile("fence.acq_rel.gpu;" ::: "memory");
      st_relaxed_if(g_lnflag + ((first ^ (lane & 1)) + (lane - 26) / 2 * step) * 8, 1, true);
    }
    __syncwarp();
    fence_async_smem();
    if (threadIdx.x == 0) TS(15);
  }
}

__global__ void __cluster_dims__(2, 1, 1) __launch_bounds__(512, 1) k_main(const __grid_constant__ Params P) {
  extern __shared__ __align__(1024) unsigned char smem[];
  const uint32_t sb = (uint32_t)__cvta_generic_to_shared(smem);
  const int b = bid(), wg = threadIdx.x >> 7;
  if ((threadIdx.x & 127) == 0) TS(0);
  if (threadIdx.x == 480) {
    if ((sb & 0xFFFFFF) != SBASE) __trap();
    for (int i = 0; i < 6; i++) mbar_init(sb + W_BAR + i * 8, 1);
    if (b < N_CHAIN) {
      mbar_init(sb + CB_FULL, 1); mbar_init(sb + CB_FULL + 8, 1);
      mbar_init(sb + CB_REF, 1);
      mbar_init(sb + CB_SX, 1); mbar_init(sb + CB_OX, 1); mbar_init(sb + CB_XX, 1); mbar_init(sb + CB_Q, 1); mbar_init(sb + CB_VF, 1); mbar_init(sb + CB_VF + 8, 1);
      sts32(sb + C_BAD, 0);
      for (int i = 0; i < 11; i++) mbar_init(sb + CB_M + i * 8, i == 0 ? 5 : i == 5 ? 2 : 1);
    } else if (b < N_CHAIN + N_G) {
      for (int i = 0; i < 9; i++) { mbar_init(sb + G_BAR + i * 8, 2); mbar_init(sb + G_BAR + 128 + i * 8, 8); }
    } else if (b < N_CHAIN + N_G + N_O) {
      for (int i = 0; i < 5; i++) { mbar_init(sb + O_BAR + i * 8, 1); mbar_init(sb + O_BAR + 128 + i * 8, 12); }
      for (int i = 0; i < 6; i++) mbar_init(sb + OB_ST + i * 8, 1);
    } else {
      mbar_init(sb + F_BAR, 1); mbar_init(sb + F_BAR + 8, 1);
    }
    asm volatile("fence.mbarrier_init.release.cluster;" ::: "memory");
    fence_async_smem();
  }
  __syncwarp();
  asm volatile("barrier.cluster.arrive.relaxed.aligned;" ::: "memory");
  prologue(P, sb);
  asm volatile("barrier.cluster.wait.aligned;" ::: "memory");
  fence_async_smem();
  if (b >= 128) ln_tiles<1>(P, sb);
  if (b >= N_CHAIN + N_G) ln_tiles<2>(P, sb);
  if ((threadIdx.x & 127) == 0) TS(3);
  if (b < N_CHAIN) {
    if (wg < 2) { reg_inc<192>(); chain_proj(P, sb); }
    else if (wg == 2) { reg_dec<ATTR>(); chain_attn(P, sb); }
    else { reg_dec<128 - ATTR>(); chain_aux(P, sb); }
  } else if (NOBULK) {
    {
      if (wg == 0) {
        float d[4] = {0.f, 0.f, 0.f, 0.f};
        for (int n = 0; n < STEPS - 1; n++) {
          const uint32_t* f = g_fl + FL_TICK;
          uint32_t x;
          do { for (int k = 0; k < 16; k++) mma16(d, 0, 0, 0, 0, 0, 0); asm volatile("ld.relaxed.gpu.global.u32 %0, [%1];" : "=r"(x) : "l"(f) : "memory"); } while ((x >> 24) <= n);
          const int q = (b - N_CHAIN) * 4 + (threadIdx.x >> 5);
          if (n + 5 >= MRING && q < 80) fill16((uint4*)g_mimg + (uint32_t)(((n + 5) % MRING) * 4096 + q * 32 + (threadIdx.x & 31)), SENT);
        }
        if (d[0] == 1.f) P.out[0] = __float2bfloat16(0.f);
      }
    }
  } else if (b < N_CHAIN + N_G) {
    if (wg == 0) { reg_inc<232>(); g_math<0>(P, sb); }
    else if (wg == 1) { reg_inc<232>(); g_math<1>(P, sb); }
    else if (wg == 2) { reg_dec<24>(); g_aux(P, sb); }
    else { reg_dec<24>(); g_load(P, sb); }
  } else if (b < N_CHAIN + N_G + N_O) {
    if (wg == 0) { reg_inc<160>(); o_math<0>(P, sb); }
    else if (wg == 1) { reg_inc<160>(); o_math<1>(P, sb); }
    else if (wg == 2) { reg_inc<160>(); o_math<2>(P, sb); }
    else { reg_dec<32>(); o_aux(P, sb); }
  } else {
    f_role(P, sb);
  }
}

}

extern "C" void kernel_launch(void* const* d_in, const int* in_sizes, int n_in, void* d_out, int out_size) {
  typedef CUresult (*Encode)(CUtensorMap*, CUtensorMapDataType, cuuint32_t, void*, const cuuint64_t*, const cuuint64_t*, const cuuint32_t*, const cuuint32_t*,
                             CUtensorMapInterleave, CUtensorMapSwizzle, CUtensorMapL2promotion, CUtensorMapFloatOOBfill);
  static Encode encode = nullptr;
  if (!encode) cudaGetDriverEntryPoint("cuTensorMapEncodeTiled", (void**)&encode, cudaEnableDefault);
  Params P;
  for (int i = 0; i < 11; i++) {
    const bool wo = i == 6 || i == 7;
    const cuuint64_t cols = wo ? DM : HD, rows = HD + DM - cols, pitch = cols * 2;
    const cuuint64_t dim[4][5] = {{cols, 2, 8, 2, 18}, {cols, 16, 1, 1, rows / 16}, {cols, 2, 4, 4, rows / 32}, {64, 16, 64, 2, 18}};
    const cuuint64_t stride[4][4] = {{8 * pitch, pitch, 16 * pitch, 32 * pitch}, {pitch, pitch, pitch, 16 * pitch},
                                     {pitch, 8 * pitch, 2 * pitch, 32 * pitch}, {pitch, 128, 16 * pitch, 32 * pitch}};
    const cuuint32_t box[4][5] = {{64, 2, 8, 1, 18}, {64, 16, 1, 1, 1}, {64, 2, 4, 2, 1}, {64, 16, 2, 1, 18}}, one[5] = {1, 1, 1, 1, 1};
    const int k = i < 3 ? 0 : i < 7 ? 1 : i < 8 ? 2 : 3;
    encode(&P.map[i], CU_TENSOR_MAP_DATA_TYPE_BFLOAT16, 5, d_in[wo ? 11 : 8 + (i & 7) % 3], dim[k], stride[k], box[k], one,
           CU_TENSOR_MAP_INTERLEAVE_NONE, CU_TENSOR_MAP_SWIZZLE_128B, CU_TENSOR_MAP_L2_PROMOTION_L2_128B, CU_TENSOR_MAP_FLOAT_OOB_FILL_NONE);
  }
  P.X = (const bf16*)d_in[0]; P.K = (const bf16*)d_in[1]; P.V = (const bf16*)d_in[2];
  P.shift = (const bf16*)d_in[3]; P.Hk = (const bf16*)d_in[4]; P.Dk = (const bf16*)d_in[5];
  P.mem0 = (const bf16*)d_in[7];
  P.Wq = (const bf16*)d_in[8]; P.Wk = (const bf16*)d_in[9]; P.Wv = (const bf16*)d_in[10]; P.Wo = (const bf16*)d_in[11];
  P.out = (bf16*)d_out;
  for (int i = 0; i < 24; i++) P.dly[i] = h_dly[i];
  cudaFuncSetAttribute(k_main, cudaFuncAttributeMaxDynamicSharedMemorySize, SMEM_BYTES);
  k_main<<<N_CTA, 512, SMEM_BYTES>>>(P);
}
```

```cpp
#include <cuda.h>
#include <cuda_runtime.h>
#include <cuda_bf16.h>
#include <stdint.h>

namespace {

typedef __nv_bfloat16 bf16;

constexpr int SEQ = 2048, DM = 576, HD = 4096, NSEG = 64;
#define PLACE 1
#define LAGV 7
constexpr int LAG = LAGV, STEPS = NSEG + LAG, RING = 8;
static_assert(LAG < RING, "ring");
constexpr int N_CHAIN = 64, N_G = 48, N_O = 18, N_F = 2;
constexpr uint32_t SBASE = 1024;
constexpr uint32_t SENT = 0xFFFFFFFFu;
constexpr int SPIN_MAX = 1 << 22;

__device__ __forceinline__ uint32_t bid() {
  const uint32_t b = blockIdx.x;
  return b < 6 ? b + 106 : b < 8 ? b + 122 : b < 114 ? b - 8 : b < 130 ? b - 2 : b;
}
__device__ __forceinline__ uint32_t chain_id() { return blockIdx.x - (PLACE ? 8 : 0); }
constexpr int KVP = SEQ + 64;
__device__ __align__(1024) bf16 g_kvT[DM * KVP];
__device__ __align__(1024) bf16 g_yT[DM * SEQ];
__device__ __align__(1024) unsigned char g_lnimg[2 * NSEG * 9 * 4096];
__device__ __align__(1024) unsigned char g_qkv[RING * N_CHAIN * 24576];
__device__ __align__(1024) unsigned char g_oimg[RING * N_CHAIN * 8192];
constexpr int ARING = 16;
static_assert(ARING >= LAG + 9, "accumulator ring");
__device__ __align__(1024) float g_oacc[ARING * 64 * DM];
constexpr int MRING = LAG + 4, N_GRP = 32 + MRING + 1;
constexpr int XB_M = 256, XB_F = XB_M + MRING * 8, XB_REF = XB_F + 2, N_CTA = N_CHAIN + N_G + N_O + N_F;
__device__ __align__(65536) uint4 g_xb[N_GRP * 4096];
#define g_mimg ((uint32_t*)(g_xb + XB_M * 512))
__device__ uint32_t g_near[N_GRP];
__device__ uint32_t g_side[N_CTA];
__device__ __align__(128) uint32_t g_gbar[3 * 32];
constexpr int FL_G = 0, FL_F = 96 * 8, FL_OCNT = FL_F + 2 * 8, OCRING = 16, FL_TICK = 992, FL_O = 2048, FL_SYNC = FL_O + 128;
static_assert(FL_OCNT + OCRING * 8 <= FL_TICK, "flag block");
#define g_fl ((uint32_t*)(g_xb + XB_F * 512))
__device__ __align__(1024) uint32_t g_lnflag[128 * 8];
#define TS(slot)

#define OTURN 2
#define LOCK0 3
#define FASTG 0
#define NOBULK 0
#define WFENCE 0
#define QPOS 0
#define VE 4
#define OGAP 2
#define NOCHAIN 0
#define BFENCE 2
#define ABL 0
#define ATTR 80
#define CNT(slot, tries)
#define T3(slot)
#define TR(slot)
#define TRV(slot, val)
#define TRD(slot, dep)
#define TRSYNC()
#define TRDUMP(n)
#define CLK(t) "{.reg .b64 x; .reg .b32 h; mov.u64 x, %%clock64; mov.b64 {" t ", h}, x;}"
__device__ __forceinline__ uint32_t clk() { uint32_t t; asm volatile(CLK("%0") : "=r"(t) :: "memory"); return t; }
__device__ __forceinline__ void wait_until(uint32_t t0, uint32_t d) {
  asm volatile("{.reg .pred p; .reg .u32 t;\n"
               "W: " CLK("t") " sub.u32 t, t, %0; setp.lt.s32 p, t, 0; @p bra.uni W;}"
               :: "r"(t0 + d) : "memory");
}
__device__ __forceinline__ uint32_t pack2(float lo, float hi) {
  uint32_t r; asm("cvt.rn.bf16x2.f32 %0, %1, %2;" : "=r"(r) : "f"(hi), "f"(lo)); return r;
}
__device__ __forceinline__ float bf_lo(uint32_t v) { return __uint_as_float(v << 16); }
__device__ __forceinline__ float bf_hi(uint32_t v) { return __uint_as_float(v & 0xFFFF0000u); }

__device__ __forceinline__ uint4 ld_relaxed4(const void* p) {
  uint4 v; asm volatile("ld.relaxed.gpu.global.v4.u32 {%0,%1,%2,%3}, [%4];" : "=r"(v.x), "=r"(v.y), "=r"(v.z), "=r"(v.w) : "l"(p) : "memory"); return v;
}
__device__ __forceinline__ void st_b128(void* p, uint32_t a, uint32_t b, uint32_t c, uint32_t d) {
  asm volatile("{.reg .b128 v; mov.b128 v, {%1,%2,%3,%4}; st.relaxed.gpu.global.b128 [%0], v;}" :: "l"(p), "r"(a), "r"(b), "r"(c), "r"(d) : "memory");
}
__device__ __forceinline__ void reload_b128(uint4& v, const void* p, uint32_t again) {
  asm volatile("{.reg .pred p; .reg .b128 v; setp.ne.u32 p, %5, 0; mov.b128 v, {%0,%1,%2,%3};\n"
               "@p ld.relaxed.gpu.global.b128 v, [%4]; mov.b128 {%0,%1,%2,%3}, v;}"
    : "+r"(v.x), "+r"(v.y), "+r"(v.z), "+r"(v.w) : "l"(p), "r"(again) : "memory");
}
__device__ __forceinline__ void reload4(uint4& v, const void* p, uint32_t again) {
  asm volatile("{.reg .pred p; setp.ne.u32 p, %5, 0; @p ld.relaxed.gpu.global.v4.u32 {%0,%1,%2,%3}, [%4];}"
    : "+r"(v.x), "+r"(v.y), "+r"(v.z), "+r"(v.w) : "l"(p), "r"(again) : "memory");
}
__device__ __forceinline__ void st_relaxed4(void* p, uint32_t a, uint32_t b, uint32_t c, uint32_t d) {
  asm volatile("st.relaxed.gpu.global.v4.u32 [%0], {%1,%2,%3,%4};" :: "l"(p), "r"(a), "r"(b), "r"(c), "r"(d) : "memory");
}
__device__ __forceinline__ void st_relaxed_if(void* p, uint32_t a, bool on) {
  asm volatile("{.reg .pred p; setp.ne.u32 p, %2, 0; @p st.relaxed.gpu.global.u32 [%0], %1;}" :: "l"(p), "r"(a), "r"((uint32_t)on) : "memory");
}
__device__ __forceinline__ uint32_t ld_acquire(const uint32_t* p) {
  uint32_t v; asm volatile("ld.acquire.gpu.global.u32 %0, [%1];" : "=r"(v) : "l"(p) : "memory"); return v;
}
__device__ __forceinline__ void st_release(uint32_t* p, uint32_t v) {
  asm volatile("st.release.gpu.global.u32 [%0], %1;" :: "l"(p), "r"(v) : "memory");
}
__device__ __forceinline__ void bulk_reduce(float* dst, uint32_t src, uint32_t bytes) {
  asm volatile("cp.reduce.async.bulk.global.shared::cta.bulk_group.add.f32 [%0], [%1], %2;" :: "l"(dst), "r"(src), "r"(bytes) : "memory");
}
__device__ __forceinline__ void bulk_done_inc(uint32_t* p) {
  asm volatile("cp.async.bulk.wait_group 0;\n"
               "fence.proxy.async.global;\nfence.release.gpu;\n"
               "red.relaxed.gpu.global.add.u32 [%0], 1;\nred.relaxed.gpu.global.add.u32 [%0+4096], 1;" :: "l"(p) : "memory");
}
__device__ __forceinline__ void flag_release(uint32_t* p, uint32_t v) {
  asm volatile("fence.release.gpu;\nst.relaxed.gpu.global.u32 [%0], %1;\nst.relaxed.gpu.global.u32 [%0+4096], %1;" :: "l"(p), "r"(v) : "memory");
}
__device__ __forceinline__ void spin_guard(int& it) {
  asm volatile("{.reg .pred p; add.s32 %0, %0, 1; setp.gt.s32 p, %0, %1; @p trap;}" : "+r"(it) : "n"(SPIN_MAX));
}
__device__ __forceinline__ void wait_flag(const uint32_t* p, uint32_t v) {
  int it = 0;
  while (ld_acquire(p) < v) spin_guard(it);
}
__device__ __forceinline__ void wait_flags(const uint32_t* p, uint32_t v) {
  int it = 0;
  while (true) {
    uint32_t x; asm volatile("ld.relaxed.gpu.global.u32 %0, [%1];" : "=r"(x) : "l"(p) : "memory");
    if (__all_sync(~0u, x >= v)) break;
    spin_guard(it);
  }
  asm volatile("fence.acquire.gpu;" ::: "memory");
}
__device__ __forceinline__ uint32_t timer_offset() {
  uint32_t g0, g;
  asm volatile("mov.u32 %0, %%globaltimer_lo;" : "=r"(g0) :: "memory");
  do { asm volatile("mov.u32 %0, %%globaltimer_lo;" : "=r"(g) :: "memory"); } while (g == g0);
  return (g >> 5) * 58 - clk();
}
__device__ __forceinline__ void grid_arrive(int i) {
  asm volatile("red.release.gpu.global.add.u32 [%0], %1;" :: "l"(g_gbar + i * 32), "r"(bid() ? 1u : 257u - N_CTA) : "memory");
}
__device__ __forceinline__ void grid_wait(int i, uint32_t gen) {
  int it = 0;
  while (((ld_acquire(g_gbar + i * 32) ^ gen) >> 8) == 0) spin_guard(it);
}
__device__ __forceinline__ bool elect() {
  uint32_t r; asm volatile("{.reg .pred p; elect.sync _|p, -1; selp.u32 %0, 1, 0, p;}" : "=r"(r)); return r;
}
__device__ __forceinline__ void bar_sync(int id, int cnt) { asm volatile("bar.sync %0, %1;" :: "r"(id), "r"(cnt) : "memory"); }
__device__ __forceinline__ void bar_arrive(int id, int cnt) { asm volatile("bar.arrive %0, %1;" :: "r"(id), "r"(cnt) : "memory"); }
template <int id, int cnt> __device__ __forceinline__ void bar_arrive_after(uint32_t a, uint32_t b) {
  asm volatile("{.reg .pred p; setp.ne.u32 p, %2, 0xfff12345; setp.ne.and.u32 p, %3, 0xfff12345, p; @p bar.arrive %0, %1;}" :: "n"(id), "n"(cnt), "r"(a), "r"(b) : "memory");
}
template <int id, int cnt> __device__ __forceinline__ void bar_sync_after(uint32_t a) {
  asm volatile("{.reg .pred p; setp.ne.u32 p, %2, 0xfff12345; @p bar.sync %0, %1;}" :: "n"(id), "n"(cnt), "r"(a) : "memory");
}
__device__ __forceinline__ void fence_async_smem() { asm volatile("fence.proxy.async.shared::cta;" ::: "memory"); }
__device__ __forceinline__ void fence_async_global() { asm volatile("fence.proxy.async.global;" ::: "memory"); }
__device__ __forceinline__ void mbar_init(uint32_t mb, int cnt) { asm volatile("mbarrier.init.shared::cta.b64 [%0], %1;" :: "r"(mb), "r"(cnt) : "memory"); }
__device__ __forceinline__ void mbar_arrive(uint32_t mb) { asm volatile("mbarrier.arrive.shared::cta.b64 _, [%0];" :: "r"(mb) : "memory"); }
__device__ __forceinline__ void mbar_arrive_after(uint32_t mb, uint32_t a, uint32_t lane) {
  asm volatile("{.reg .pred p; setp.ne.u32 p, %1, 0xfff12345; setp.eq.and.u32 p, %2, 0, p; @p mbarrier.arrive.shared::cta.b64 _, [%0];}" :: "r"(mb), "r"(a), "r"(lane) : "memory");
}
__device__ __forceinline__ void mbar_expect(uint32_t mb, uint32_t bytes) {
  asm volatile("mbarrier.arrive.expect_tx.shared::cta.b64 _, [%0], %1;" :: "r"(mb), "r"(bytes) : "memory");
}
__device__ __forceinline__ void mbar_wait_guard(uint32_t mb, uint32_t parity) {
  uint32_t ok; int it = 0;
  while (true) {
    asm volatile("{.reg .pred p; mbarrier.try_wait.parity.shared::cta.b64 p, [%1], %2; selp.u32 %0, 1, 0, p;}" : "=r"(ok) : "r"(mb), "r"(parity) : "memory");
    if (ok) break;
    spin_guard(it);
  }
}
__device__ __forceinline__ void mbar_wait(uint32_t mb, uint32_t parity) {
  asm volatile("{.reg .pred p;\nW: mbarrier.try_wait.parity.shared::cta.b64 p, [%0], %1;\n@!p bra W;}" :: "r"(mb), "r"(parity) : "memory");
}
__device__ __forceinline__ void bulk_load(uint32_t dst, const void* src, uint32_t bytes, uint32_t mb) {
  asm volatile("cp.async.bulk.shared::cluster.global.mbarrier::complete_tx::bytes [%0], [%1], %2, [%3];" :: "r"(dst), "l"(src), "r"(bytes), "r"(mb) : "memory");
}
__device__ __forceinline__ void bulk_store(void* dst, uint32_t src, uint32_t bytes) {
  asm volatile("cp.async.bulk.global.shared::cta.bulk_group [%0], [%1], %2;" :: "l"(dst), "r"(src), "r"(bytes) : "memory");
}
__device__ __forceinline__ void cp_async16(uint32_t dst, const void* src) {
  asm volatile("cp.async.cg.shared.global [%0], [%1], 16;" :: "r"(dst), "l"(src) : "memory");
}
__device__ __forceinline__ void cp_async_wait_all() { asm volatile("cp.async.wait_all;" ::: "memory"); }
__device__ __forceinline__ uint32_t mapa(uint32_t a, uint32_t rank) {
  uint32_t r; asm("mapa.shared::cluster.u32 %0, %1, %2;" : "=r"(r) : "r"(a), "r"(rank)); return r;
}
__device__ __forceinline__ void st_async4(uint32_t dst, float a, float b, float c, float d, uint32_t mb) {
  asm volatile("st.async.shared::cluster.mbarrier::complete_tx::bytes.v4.f32 [%0], {%1,%2,%3,%4}, [%5];" :: "r"(dst), "f"(a), "f"(b), "f"(c), "f"(d), "r"(mb) : "memory");
}
__device__ __forceinline__ void st_async2(uint32_t dst, float a, float b, uint32_t mb) {
  asm volatile("st.async.shared::cluster.mbarrier::complete_tx::bytes.v2.f32 [%0], {%1,%2}, [%3];" :: "r"(dst), "f"(a), "f"(b), "r"(mb) : "memory");
}
__device__ __forceinline__ void st_async1(uint32_t dst, uint32_t a, uint32_t mb) {
  asm volatile("st.async.shared::cluster.mbarrier::complete_tx::bytes.u32 [%0], %1, [%2];" :: "r"(dst), "r"(a), "r"(mb) : "memory");
}
__device__ __forceinline__ uint4 lds128(uint32_t a) {
  uint4 v; asm volatile("ld.shared.v4.u32 {%0,%1,%2,%3}, [%4];" : "=r"(v.x), "=r"(v.y), "=r"(v.z), "=r"(v.w) : "r"(a) : "memory"); return v;
}
__device__ __forceinline__ uint2 lds64(uint32_t a) {
  uint2 v; asm volatile("ld.shared.v2.u32 {%0,%1}, [%2];" : "=r"(v.x), "=r"(v.y) : "r"(a) : "memory"); return v;
}
__device__ __forceinline__ uint32_t lds32(uint32_t a) {
  uint32_t v; asm volatile("ld.shared.u32 %0, [%1];" : "=r"(v) : "r"(a) : "memory"); return v;
}
__device__ __forceinline__ void sts128(uint32_t a, uint4 v) {
  asm volatile("st.shared.v4.u32 [%0], {%1,%2,%3,%4};" :: "r"(a), "r"(v.x), "r"(v.y), "r"(v.z), "r"(v.w) : "memory");
}
__device__ __forceinline__ void sts64(uint32_t a, uint32_t x, uint32_t y) {
  asm volatile("st.shared.v2.u32 [%0], {%1,%2};" :: "r"(a), "r"(x), "r"(y) : "memory");
}
__device__ __forceinline__ void sts32(uint32_t a, uint32_t x) { asm volatile("st.shared.u32 [%0], %1;" :: "r"(a), "r"(x) : "memory"); }
__device__ __forceinline__ void ldsm4(uint32_t& r0, uint32_t& r1, uint32_t& r2, uint32_t& r3, uint32_t a) {
  asm volatile("ldmatrix.sync.aligned.m8n8.x4.shared.b16 {%0,%1,%2,%3}, [%4];" : "=r"(r0), "=r"(r1), "=r"(r2), "=r"(r3) : "r"(a) : "memory");
}
__device__ __forceinline__ void ldsm4t(uint32_t& r0, uint32_t& r1, uint32_t& r2, uint32_t& r3, uint32_t a) {
  asm volatile("ldmatrix.sync.aligned.m8n8.x4.trans.shared.b16 {%0,%1,%2,%3}, [%4];" : "=r"(r0), "=r"(r1), "=r"(r2), "=r"(r3) : "r"(a) : "memory");
}
__device__ __forceinline__ void stsm4(uint32_t a, uint32_t r0, uint32_t r1, uint32_t r2, uint32_t r3) {
  asm volatile("stmatrix.sync.aligned.m8n8.x4.shared.b16 [%0], {%1,%2,%3,%4};" :: "r"(a), "r"(r0), "r"(r1), "r"(r2), "r"(r3) : "memory");
}
__device__ __forceinline__ uint32_t movmat(uint32_t a) {
  uint32_t d; asm volatile("movmatrix.sync.aligned.m8n8.trans.b16 %0, %1;" : "=r"(d) : "r"(a)); return d;
}
__device__ __forceinline__ void mma16(float* d, uint32_t a0, uint32_t a1, uint32_t a2, uint32_t a3, uint32_t b0, uint32_t b1) {
  asm volatile("mma.sync.aligned.m16n8k16.row.col.f32.bf16.bf16.f32 {%0,%1,%2,%3}, {%4,%5,%6,%7}, {%8,%9}, {%0,%1,%2,%3};"
    : "+f"(d[0]), "+f"(d[1]), "+f"(d[2]), "+f"(d[3]) : "r"(a0), "r"(a1), "r"(a2), "r"(a3), "r"(b0), "r"(b1));
}
__device__ __forceinline__ void mma8(float* d, uint32_t a0, uint32_t a1, uint32_t b0) {
  asm volatile("mma.sync.aligned.m16n8k8.row.col.f32.bf16.bf16.f32 {%0,%1,%2,%3}, {%4,%5}, {%6}, {%0,%1,%2,%3};"
    : "+f"(d[0]), "+f"(d[1]), "+f"(d[2]), "+f"(d[3]) : "r"(a0), "r"(a1), "r"(b0));
}
__device__ __forceinline__ float rcp(float x) { float r; asm("rcp.approx.ftz.f32 %0, %1;" : "=f"(r) : "f"(x)); return r; }
__device__ __forceinline__ float ex2(float x) { float r; asm("ex2.approx.ftz.f32 %0, %1;" : "=f"(r) : "f"(x)); return r; }

__host__ __device__ constexpr uint64_t mkdesc(uint32_t off, uint32_t lbo, uint32_t sbo, uint32_t swz) {
  return (uint64_t)((SBASE + off) >> 4) | ((uint64_t)(lbo >> 4) << 16) | ((uint64_t)(sbo >> 4) << 32) | ((uint64_t)swz << 62);
}
__host__ __device__ constexpr uint64_t desc_sw128(uint32_t off) { return mkdesc(off, 16, 1024, 1); }
__host__ __device__ constexpr uint64_t desc_n16(uint32_t off) { return mkdesc(off, 256, 128, 0); }
__host__ __device__ constexpr uint64_t desc_m(uint32_t off) { return mkdesc(off, 16, 256, 3); }

__host__ __device__ constexpr uint64_t desc_sw64(uint32_t off) { return mkdesc(off, 16, 512, 2); }

__device__ __forceinline__ void wg_fence() { asm volatile("wgmma.fence.sync.aligned;" ::: "memory"); }
__device__ __forceinline__ void wg_commit() { asm volatile("wgmma.commit_group.sync.aligned;" ::: "memory"); }
template <int N> __device__ __forceinline__ void wg_wait() { asm volatile("wgmma.wait_group.sync.aligned %0;" :: "n"(N) : "memory"); }

#define ACC8(d) "+f"(d[0]), "+f"(d[1]), "+f"(d[2]), "+f"(d[3]), "+f"(d[4]), "+f"(d[5]), "+f"(d[6]), "+f"(d[7])
#define ACC32(d) ACC8(d), ACC8((d + 8)), ACC8((d + 16)), ACC8((d + 24))
#define R8 "{%0,%1,%2,%3,%4,%5,%6,%7}"
#define R32 "{%0,%1,%2,%3,%4,%5,%6,%7,%8,%9,%10,%11,%12,%13,%14,%15,%16,%17,%18,%19,%20,%21,%22,%23,%24,%25,%26,%27,%28,%29,%30,%31}"
template <int SD> __device__ __forceinline__ void wg_rs16(float* d, const uint32_t* a, uint64_t db) {
  asm volatile("wgmma.mma_async.sync.aligned.m64n16k16.f32.bf16.bf16 " R8 ", {%8,%9,%10,%11}, %12, %13, 1, 1, 1;"
    : ACC8(d) : "r"(a[0]), "r"(a[1]), "r"(a[2]), "r"(a[3]), "l"(db), "n"(SD));
}
template <int SD> __device__ __forceinline__ void wg_ss16(float* d, uint64_t da, uint64_t db) {
  asm volatile("wgmma.mma_async.sync.aligned.m64n16k16.f32.bf16.bf16 " R8 ", %8, %9, %10, 1, 1, 1, 1;"
    : ACC8(d) : "l"(da), "l"(db), "n"(SD));
}
template <int SD, uint64_t DA, uint64_t DB> __device__ __forceinline__ void wg_ss16o(float* d, uint32_t oa, uint32_t ob) {
  asm volatile("{.reg .b32 x, y; .reg .b64 a, b; add.u32 x, %8, %10; add.u32 y, %9, %12; mov.b64 a, {x, %11}; mov.b64 b, {y, %13};\n"
               "wgmma.mma_async.sync.aligned.m64n16k16.f32.bf16.bf16 " R8 ", a, b, %14, 1, 1, 1, 1;}"
    : ACC8(d) : "r"(oa), "r"(ob), "n"((uint32_t)DA), "n"((uint32_t)(DA >> 32)), "n"((uint32_t)DB), "n"((uint32_t)(DB >> 32)), "n"(SD));
}
template <int SD> __device__ __forceinline__ void wg_rs64(float* d, const uint32_t* a, uint64_t db) {
  asm volatile("wgmma.mma_async.sync.aligned.m64n64k16.f32.bf16.bf16 " R32 ", {%32,%33,%34,%35}, %36, %37, 1, 1, 0;"
    : ACC32(d) : "r"(a[0]), "r"(a[1]), "r"(a[2]), "r"(a[3]), "l"(db), "n"(SD));
}
template <int SD> __device__ __forceinline__ void wg_ss64(float* d, uint64_t da, uint64_t db) {
  asm volatile("wgmma.mma_async.sync.aligned.m64n64k16.f32.bf16.bf16 " R32 ", %32, %33, %34, 1, 1, 1, 0;"
    : ACC32(d) : "l"(da), "l"(db), "n"(SD));
}
#define WG_RSO(NAME, SHAPE, REGS, ACC, A, TB) \
template <int SD, uint64_t DB> __device__ __forceinline__ void NAME(float* d, uint32_t a0, uint32_t a1, uint32_t a2, uint32_t a3, uint32_t ob) { \
  asm volatile("{.reg .b64 b; mov.b64 b, {" A(4) ", " A(5) "};\nwgmma.mma_async.sync.aligned." SHAPE ".f32.bf16.bf16 " REGS \
               ", {" A(0) "," A(1) "," A(2) "," A(3) "}, b, " A(6) ", 1, 1, " TB ";}" \
    : ACC(d) : "r"(a0), "r"(a1), "r"(a2), "r"(a3), "r"(ob + (uint32_t)DB), "n"((uint32_t)(DB >> 32)), "n"(SD)); \
}
#define ACC4(d) "+f"(d[0]), "+f"(d[1]), "+f"(d[2]), "+f"(d[3])
#define ACC16(d) ACC8(d), ACC8((d + 8))
#define OP4(i) OP4_##i
#define OP4_0 "%4"
#define OP4_1 "%5"
#define OP4_2 "%6"
#define OP4_3 "%7"
#define OP4_4 "%8"
#define OP4_5 "%9"
#define OP4_6 "%10"
#define OP16(i) OP16_##i
#define OP16_0 "%16"
#define OP16_1 "%17"
#define OP16_2 "%18"
#define OP16_3 "%19"
#define OP16_4 "%20"
#define OP16_5 "%21"
#define OP16_6 "%22"
#define OP32(i) OP32_##i
#define OP32_0 "%32"
#define OP32_1 "%33"
#define OP32_2 "%34"
#define OP32_3 "%35"
#define OP32_4 "%36"
#define OP32_5 "%37"
#define OP32_6 "%38"
WG_RSO(wg_rs8o, "m64n8k16", "{%0,%1,%2,%3}", ACC4, OP4, "1")
WG_RSO(wg_rs32o, "m64n32k16", "{%0,%1,%2,%3,%4,%5,%6,%7,%8,%9,%10,%11,%12,%13,%14,%15}", ACC16, OP16, "1")
WG_RSO(wg_rs64o, "m64n64k16", R32, ACC32, OP32, "0")
template <int N> __device__ __forceinline__ void reg_inc() { asm volatile("setmaxnreg.inc.sync.aligned.u32 %0;" :: "n"(N)); }
template <int N> __device__ __forceinline__ void reg_dec() { asm volatile("setmaxnreg.dec.sync.aligned.u32 %0;" :: "n"(N)); }
__device__ __forceinline__ void cluster_sync() {
  asm volatile("barrier.cluster.arrive.relaxed.aligned;\nbarrier.cluster.wait.aligned;" ::: "memory");
}

template <int KS>
__device__ __forceinline__ void load_frags(uint32_t* a, uint32_t src) {
  const int lane = threadIdx.x & 31, w = (threadIdx.x >> 5) & 3;
  const int k = ((lane >> 4) << 3) + (lane & 7), u = w * 2 + ((lane >> 3) & 1);
  const uint32_t base = src + k * 128 + ((u ^ (k & 7)) << 4);
#pragma unroll
  for (int ks = 0; ks < KS; ks++) ldsm4t(a[ks * 4], a[ks * 4 + 1], a[ks * 4 + 2], a[ks * 4 + 3], base + ks * 2048);
}

__device__ __forceinline__ uint32_t badd2(uint32_t a, uint32_t b) { uint32_t r; asm("add.rn.bf16x2 %0, %1, %2;" : "=r"(r) : "r"(a), "r"(b)); return r; }
__device__ __forceinline__ uint32_t bsub2(uint32_t a, uint32_t b) { uint32_t r; asm("sub.rn.bf16x2 %0, %1, %2;" : "=r"(r) : "r"(a), "r"(b)); return r; }
__device__ __forceinline__ uint32_t bmul2(uint32_t a, uint32_t b) { uint32_t r; asm("mul.rn.bf16x2 %0, %1, %2;" : "=r"(r) : "r"(a), "r"(b)); return r; }
__device__ __forceinline__ uint32_t bfma2(uint32_t a, uint32_t b, uint32_t c) { uint32_t r; asm("fma.rn.bf16x2 %0, %1, %2, %3;" : "=r"(r) : "r"(a), "r"(b), "r"(c)); return r; }
template <int R> __device__ __forceinline__ void layernorm9(const uint32_t* x, uint32_t* o) {
  const uint32_t ones = 0x3F803F80u;
  float a[R][3][4], q[R], s[R];
#pragma unroll
  for (int i = 0; i < 9 * R; i++) {
    float* d = a[i % R][i / R % 3];
    if (i < 3 * R) d[0] = d[1] = d[2] = d[3] = 0.f;
    mma8(d, x[i % R * 9 + i / R], ones, x[i % R * 9 + i / R]);
  }
#pragma unroll
  for (int r = 0; r < R; r++) {
    q[r] = threadIdx.x & 4 ? a[r][0][1] + a[r][1][1] + a[r][2][1] : a[r][0][0] + a[r][1][0] + a[r][2][0];
    s[r] = (a[r][0][2] + a[r][0][3]) + (a[r][1][2] + a[r][1][3]) + (a[r][2][2] + a[r][2][3]);
  }
#pragma unroll
  for (int r = 0; r < R; r++) { q[r] += __shfl_xor_sync(~0u, q[r], 4); s[r] += __shfl_xor_sync(~0u, s[r], 1); }
#pragma unroll
  for (int r = 0; r < R; r++) { q[r] += __shfl_xor_sync(~0u, q[r], 9); s[r] += __shfl_xor_sync(~0u, s[r], 2); }
#pragma unroll
  for (int r = 0; r < R; r++) q[r] = __shfl_sync(~0u, q[r], 0) + __shfl_sync(~0u, q[r], 18);
#pragma unroll
  for (int r = 0; r < R; r++) {
    const float mean = s[r] * (1.f / DM), var = fmaxf(fmaf(q[r], 1.f / DM, -mean * mean), 0.f);
    float sd;
    asm("sqrt.approx.ftz.f32 %0, %1;" : "=f"(sd) : "f"(bf_lo(pack2(bf_lo(pack2(var, 0.f)) + 1e-5f, 0.f))));
    const float inv = rcp(bf_lo(pack2(sd, 0.f)));
    const uint32_t mb = pack2(mean, mean), hi = pack2(inv, inv), lo = pack2(inv - bf_lo(hi), inv - bf_lo(hi));
#pragma unroll
    for (int i = r * 9; i < r * 9 + 9; i++) {
      const uint32_t d = bsub2(x[i], mb);
      o[i] = bfma2(d, hi, bmul2(d, lo));
    }
  }
}
__device__ __forceinline__ void store_ln_row(int layer, int tok, const uint32_t* o) {
  const int lane = threadIdx.x & 31, r = tok & 31;
  unsigned char* p = g_lnimg + (size_t)(layer * NSEG + (tok >> 5)) * (9 * 4096) + r * 128 + (((lane >> 2) ^ (r & 7)) << 4) + (lane & 3) * 4;
#pragma unroll
  for (int i = 0; i < 9; i++) *(uint32_t*)(p + i * 4096) = o[i];
}
struct Params { CUtensorMap map[11]; const bf16 *X, *K, *V, *shift, *Hk, *Dk, *mem0, *Wq, *Wk, *Wv, *Wo; bf16* out; uint32_t dly[24]; };
#define PACE P.dly[20]
#define S1G P.dly[21]
#define S1DLY P.dly[22]
#define DLYS P.dly[0]
#define DLYW P.dly[1]
#define KLATE P.dly[2]
#define DLYQ P.dly[3]
#define DLYK P.dly[4]
#define DLYG P.dly[5]
#define KWIN P.dly[6]
#define KMIN P.dly[7]
uint32_t h_dly[24] = {1000, 200, 0, 0, 3600, 4900, 1750, 300, 1720, 1810, 1900, 2220, 2350, 2460, 3050, 3120, 3340, 3410, 3560, 0, 180, 12000, 16000};

constexpr uint32_t C_W = 0, C_M = 147456, C_KV = C_M + 18432, C_QM = C_KV + 32768, C_KM = C_QM + 2048,
                   C_VM = C_KM + 2048, C_OI = C_VM + 2048, C_SX = C_OI + 4096, C_KM2 = C_SX + 2560, C_VM2 = C_KM2 + 128,
                   C_KV2 = C_KM2 + 2048, C_Q = C_KV2 + 8192, C_BAR = C_Q + 8192;
constexpr uint32_t CB_FULL = C_BAR, CB_REF = C_BAR + 16, CB_SX = C_BAR + 32, CB_OX = C_BAR + 40, CB_XX = C_BAR + 48, CB_Q = C_BAR + 56, C_BAD = C_BAR + 64, W_BAR = C_BAR + 80, T_BAR = W_BAR + 24, S_GEN = C_BAR + 128, C_REF = C_BAR + 132, CB_VF = C_BAR + 144, CB_M = C_BAR + 160, CB_MV = C_BAR + 200;
constexpr uint32_t G_W = 0, G_RING = 147456, G_W2 = G_RING + 9 * 8192, G_BAR = G_W2 + 8192;
constexpr uint32_t O_W = 0, O_RING = 3 * 40960, O_ST = O_RING + 11 * 8192, O_BAR = O_ST + 16384, OB_ST = O_BAR + 64;
constexpr uint32_t F_A = 0, F_XY = 36864, F_L = F_XY + 36864, F_X = F_L + 18432, F_Y = F_L + 2 * 36864, F_BAR = C_BAR;
constexpr uint32_t SMEM_BYTES = C_BAR + 256;
static_assert(G_BAR + 256 <= SMEM_BYTES && O_BAR + 256 <= SMEM_BYTES && F_BAR + 16 <= SMEM_BYTES && SMEM_BYTES <= 232448, "smem map");
enum { B_INIT = 1, B_M, B_QK, B_S, B_V, B_O, B_X, B_WG0, B_WG1, B_WG2, B_G, B_OE, B_T, B_R };

__device__ __forceinline__ uint4 pack_partial(const float* d, uint32_t tag) {
  uint32_t x;
  asm("lop3.b32 %0, %1, 1, %2, 0xb8;" : "=r"(x) : "r"(pack2(d[0], d[1])), "r"(tag));
  return make_uint4(x, pack2(d[4], d[5]), pack2(d[2], d[3]), pack2(d[6], d[7]));
}
__device__ __forceinline__ void store_partial(uint4* p, const uint4& v) { st_b128(p, v.x, v.y, v.z, v.w); }
__device__ __forceinline__ void gather_reduce(const uint32_t* p, uint32_t* dst, bool shared, uint32_t tag, uint32_t lane, uint32_t sb, int n, int TS0) {
  int tries = 0;
  float u, v;
  bool bad;
  TR(TS0);
  do {
    uint32_t x[16];
#pragma unroll
    for (int i = 0; i < 16; i++) asm volatile("ld.relaxed.gpu.global.u32 %0, [%1];" : "=r"(x[i]) : "l"(p + i * 64) : "memory");
    tries++;
    float a[2] = {bf_lo(x[0]), bf_lo(x[1])}, b[2] = {bf_hi(x[0]), bf_hi(x[1])};
    uint32_t t = 0;
#pragma unroll
    for (int i = 2; i < 16; i++) { a[i & 1] += bf_lo(x[i]); b[i & 1] += bf_hi(x[i]); }
#pragma unroll
    for (int i = 0; i < 16; i += 4)
      asm("{.reg .b32 y, z; lop3.b32 y, %1, %2, %5, 0x7e; lop3.b32 z, %3, %4, %5, 0x7e; lop3.b32 %0, %0, y, z, 0xfe;}"
          : "+r"(t) : "r"(x[i]), "r"(x[i + 1]), "r"(x[i + 2]), "r"(x[i + 3]), "r"(tag));
    u = a[0] + a[1]; v = b[0] + b[1];
    bad = __any_sync(~0u, (t & 1) && !(lane & 3));
    if (shared) { u += __shfl_xor_sync(~0u, u, 8); v += __shfl_xor_sync(~0u, v, 8); }
    u += __shfl_xor_sync(~0u, u, 16);
    v += __shfl_xor_sync(~0u, v, 16);
    st_relaxed_if(dst, pack2(u, v), !bad && (n >= LAG || !(lane & 1)));
  } while (bad);
  TR(TS0 + 3); TRV(TS0 + 2, tries);
  CNT((TS0 - 16) >> 2, tries);
}
__device__ __forceinline__ uint32_t sent_bad(const uint4& v) { return max(max(v.x, v.y), max(v.z, v.w)) == SENT; }

__host__ __device__ constexpr int o_ks(int s) { return s & (s < 8 ? 3 : 7); }
__host__ __device__ constexpr bool o_reg(int s) { return s < 8 ? (s & 3) != 3 : !(s & 1); }
__host__ __device__ constexpr int o_slot(int s) { return s < 8 ? (o_reg(s) ? s - (s >> 2) : s >> 2) : s & 1 ? (s - 5) >> 1 : (s + 4) >> 1; }
__device__ __forceinline__ int g_unit(int wg) {
  const int i = bid() - N_CHAIN;
  return i < 32 ? wg * 64 + i : 2 * i - 32 + wg;
}
__device__ __forceinline__ void load_box(const Params& P, uint32_t sb, bool regs, int wg, int i, uint32_t mb) {
  const int b = bid();
  int map, col = 0, ks = 0, c2 = 0, c3 = 0;
  uint32_t dst = wg * 73728;
  if (b < N_CHAIN) {
    const int k = i - 1, st = regs ? (k < 6 ? k + k / 3 : 2 * k - 4) : k < 2 ? 4 * k + 3 : 2 * k + 5;
    dst += i ? (17 + i) * 2048 : 0;
    if (wg || i == 0) { map = wg + i; col = b * 64; c3 = !regs; }
    else if (!regs && k >= 14) { map = 6; ks = b * 4 + k - 14; }
    else { map = 6; col = 64 + (st < 8 ? (st >> 2) * 64 : (st >> 3) * 128 + (b & 1) * 64); ks = (b * 4) ^ o_ks(st); }
  } else if (b < N_CHAIN + N_G) {
    const int q = g_unit(wg);
    map = ((q >> 5) + 1) % 3;
    if (i) { map += 3; col = (q & 31) * 128 + (i - 1) * 64; ks = 34; dst = G_W2 + wg * 4096 + (i - 1) * 2048; }
    else { map += 8; c2 = (q & 31) * 2; c3 = !regs; }
  } else {
    const int o = b - N_CHAIN - N_G, ksl = o / 3;
    map = 7; col = ((o % 3) * 3 + (wg + ksl) % 3) * 64; dst = (wg * (regs ? 24 : 20) + i) * 2048;
    ks = (ksl * 11 - max(ksl - 4, 0)) * 4 + (regs ? i / 3 * 5 + i % 3 * 2 : i < 16 ? i / 2 * 5 + 1 + i % 2 * 2 : i + 24);
    c3 = (ks & 1) * 2; ks >>= 1;
  }
  asm volatile("cp.async.bulk.tensor.5d.shared::cluster.global.tile.mbarrier::complete_tx::bytes [%0], [%1, {%2, %3, %4, %5, %6}], [%7];"
               :: "r"(sb + dst), "l"(&P.map[map]), "r"(col), "r"(0), "r"(c2), "r"(c3), "r"(ks), "r"(mb) : "memory");
}
__device__ __forceinline__ void load_wg(const Params& P, uint32_t sb, bool regs, int wg, int quarter) {
  const int b = bid(), i = (threadIdx.x & 31) * 4 + quarter;
  const int n = b < N_CHAIN ? 36 : b < N_CHAIN + N_G ? (regs ? 38 : 36) : regs ? 24 : b < N_CHAIN + N_G + 12 ? 20 : 16;
  if (i == 0) mbar_expect(sb + W_BAR + wg * 8, n * 2048);
  if (i < (b < N_CHAIN ? (wg ? 2 : 19) : b < N_CHAIN + N_G ? n - 35 : n)) load_box(P, sb, regs, wg, i, sb + W_BAR + wg * 8);
  __syncwarp();
}
__device__ __forceinline__ uint32_t near_half(uint32_t blk, uint32_t reader) {
  return __ldcg(g_near + (blk >> 3)) ^ (~blk & 1) ^ __ldcg(g_side + (blk >> 3)) ^ __ldcg(g_side + reader);
}

__device__ __forceinline__ uint32_t opaque_tid() { uint32_t t; asm volatile("mov.u32 %0, %%tid.x;" : "=r"(t)); return t; }
__device__ __forceinline__ void m_fetch(uint32_t sb, uint32_t src, uint32_t b, uint32_t mb) {
  bulk_load(sb + C_M + (b ? b * 4096 - 2048 : 0), (const unsigned char*)g_mimg + ((src ^ ((b & 1) * 4096)) + b * 8192), b ? 4096 : 2048, mb);
}
__device__ __forceinline__ uint32_t pinned(uint32_t v) { return __shfl_sync(~0u, v, threadIdx.x & 31); }
template <class T> __device__ __forceinline__ T* pinned(T* p) { return (T*)__shfl_sync(~0u, (unsigned long long)p, threadIdx.x & 31); }
__device__ __forceinline__ uint32_t m_probe(uint32_t lane) { return lane * 32 + (lane & 4) * 4 + (lane >> 3) * 4; }
__device__ __forceinline__ uint32_t m_max(uint32_t a, uint32_t b) {
  return max(max(lds32(a), lds32(a + 1024)), max(lds32(b), lds32(b + 1024)));
}
template <int S0, int N> __device__ __forceinline__ void o_steps(float* d, const uint32_t* a) {
  constexpr int SD = o_ks(S0) != 0;
  if constexpr (o_reg(S0)) wg_rs16<SD>(d, a + (18 + o_slot(S0)) * 4, desc_n16(C_OI + o_ks(S0) * 512));
  else wg_ss16<SD>(d, desc_sw128(C_W + (18 + o_slot(S0)) * 2048), desc_n16(C_OI + o_ks(S0) * 512));
  if constexpr (N > 1) o_steps<S0 + 1, N - 1>(d, a);
}
template <int BASE, int KS, int N> __device__ __forceinline__ void m_steps(float* d, const uint32_t* a, uint32_t oa) {
  wg_rs16<KS != 0>(d, a + (BASE + KS / 2) * 4, desc_m(C_M + KS * 512));
  wg_ss16o<1, desc_sw128(C_W + (BASE + KS / 2) * 2048), desc_m(C_M + KS * 512 + 512)>(d, oa, 0);
  if constexpr (N > 2) m_steps<BASE, KS + 2, N - 2>(d, a, oa);
}

__device__ __forceinline__ void chain_proj(const Params& P, uint32_t sb) {
  const uint32_t c = chain_id(), h = c >> 1, j = c & 1, wid = __shfl_sync(~0u, threadIdx.x >> 5, 0), wg = wid >> 2, w = wid & 3;
  const uint32_t t = threadIdx.x & 127, lane = pinned(t & 31), mine = pinned(sb + t * 16), rb = mapa(sb, j ^ 1);
  const uint32_t theirs = pinned(rb + C_KM2 + w * 512 + lane * 4), oa = wg * 4608;
  uint32_t a[144];
  mbar_wait(sb + W_BAR + wg * 8, 0);
  if (threadIdx.x == 0) TS(23);
  load_frags<36>(a, sb + C_W + wg * 73728);
  fence_async_smem();
  bar_sync(B_WG0 + wg, 128);
  if (threadIdx.x == 0) TS(24);
  load_wg(P, sb, false, wg, w);
  if (threadIdx.x == 0) TS(25);
  bar_sync(B_WG2, 384);
  const uint32_t round = min(w, 2u) + (wg ? 0 : 3), gdly = P.dly[8 + round], ps = t >> 2, pf = j * 16 + (ps >> 1);
  uint4* const dsts = pinned(g_xb + (ps * 4096 + near_half(ps * 8, ps * 2) * 256 + c * 4 + (t & 3)));
  uint4* const dstf = pinned(g_xb + (pf * 4096 + 512 + near_half(pf * 8 + 1, pf * 2) * 256 + h * 8 + (t & 7)));
  const uint32_t* const gsrc = (const uint32_t*)g_xb + (h * 16384 + min(w, 2u) * 4096 + near_half(h * 8 + !wg, h * 2) * 1024 +
                               (wg ? (lane & 24) * 2 + j * 8 + (lane & 7) : 2048 + (lane & 16) * 2 + j * 16 + (lane & 15)));
  uint32_t* gdst = g_mimg + (16384 + (lane >> 4) * 1024 + (lane & 2) * 4 +
                   (wg ? (round ? 1536 + round * 512 : 0) + h * 16 + ((lane ^ (c >> 2)) & 1) * 4 + j * 2 + ((lane >> 2) & 1)
                       : (round - 1) * 2048 + c * 16 + ((lane ^ (c >> 1)) & 1) * 4 + ((lane >> 2) & 3)));
  mbar_wait(sb + W_BAR + wg * 8, 1);
  bar_sync(B_INIT, 256);
  if ((threadIdx.x & 127) == 0) TS(4);

  uint32_t ring = 1;
#pragma unroll 1
  for (int n = 0; n < STEPS; n++) {
    float d[8], e[8];
    uint32_t redo = n + 1;
    do {
      mbar_wait(sb + CB_M, n & 1);
      wg_fence();
      m_steps<0, 0, 4>(d, a, oa);
      if (VE && wg) m_steps<18, 0, 4>(e, a, 4608);
      wg_commit();
      if (wid == 0) TR(8);
      mbar_wait(sb + CB_M + 8, n & 1);
      wg_fence();
      m_steps<0, 4, 8>(d, a, oa);
      if (VE > 4 && wg) m_steps<18, 4, (VE > 4 ? VE - 4 : 2)>(e, a, 4608);
      wg_commit();
      mbar_wait(sb + CB_MV, n & 1);
      redo = lds32(sb + C_BAD) == redo ? SENT : 0;
    } while (redo);
    mbar_wait(sb + CB_MV + 8, n & 1);
    wg_fence();
    m_steps<0, 12, 8>(d, a, oa);
    wg_commit();
    mbar_wait(sb + CB_MV + 16, n & 1);
    wg_fence();
    m_steps<0, 20, 8>(d, a, oa);
    wg_commit();
    mbar_wait(sb + CB_MV + 24, n & 1);
    wg_fence();
    m_steps<0, 28, 8>(d, a, oa);
    wg_commit();
    wg_wait<0>();
    if (w == 0) TR(6 + wg);
    const uint32_t f0 = pack2(d[0], d[1]), f1 = pack2(d[4], d[5]), f2 = pack2(d[2], d[3]), f3 = pack2(d[6], d[7]);
    stsm4(mine + C_QM + wg * 2048, f0, f1, f2, f3);
    bar_arrive(B_QK, 416);
    const uint32_t tag = (n & 1) ^ 1;
    if (wg) {
      if (n + 1 < STEPS) bar_sync(B_S, 256);
      wg_fence();
      m_steps<18, VE, 36 - VE>(e, a, 4608);
      wg_commit();
      st_async1(theirs, j ? f0 : f1, rb + CB_XX);
      st_async1(theirs + 256, j ? f2 : f3, rb + CB_XX);
      wg_wait<0>();
      if (w == 0) TR(11);
      const uint32_t v0 = pack2(e[0], e[1]), v1 = pack2(e[4], e[5]), v2 = pack2(e[2], e[3]), v3 = pack2(e[6], e[7]);
      stsm4(mine + C_VM, v0, v1, v2, v3);
      bar_arrive(B_V, 256);
      st_async1(theirs + 128, j ? v0 : v1, rb + CB_XX);
      st_async1(theirs + 384, j ? v2 : v3, rb + CB_XX);
      if (n + 1 == STEPS) break;
      bar_sync(B_O, 256);
      if (!WFENCE) fence_async_smem();
      wg_fence();
#pragma unroll
      for (int ks = 0; ks < 4; ks++) {
        if (ks == 0) wg_ss16<0>(d, desc_sw128(C_W + 32 * 2048), desc_n16(C_OI));
        else wg_ss16<1>(d, desc_sw128(C_W + (32 + ks) * 2048), desc_n16(C_OI + ks * 512));
      }
      wg_commit();
      bar_arrive(B_X, 256);
      if (w == 0) TR(0);
      wg_wait<0>();
      store_partial(dsts, pack_partial(d, tag));
      bar_arrive(B_M, 160);
      if (w == 0) TR(1);
    } else {
      if (n + 1 == STEPS) break;
      bar_sync(B_X, 256);
      wg_fence();
      o_steps<0, 4>(d, a);
      wg_commit();
      o_steps<4, 4>(e, a);
      wg_commit();
      wg_wait<1>();
      store_partial(dsts + 1024, pack_partial(d, tag));
      if (w == 0) TR(2);
      if (OGAP == 0) { wg_fence(); o_steps<8, 4>(d, a); wg_commit(); wg_wait<1>(); } else wg_wait<0>();
      store_partial(dsts + 2048, pack_partial(e, tag));
      if (w == 0) TR(3);
      wg_fence();
      if (OGAP) o_steps<8, 4>(d, a);
      if (OGAP < 2) o_steps<16, 4>(e, a);
      wg_commit();
      bar_sync(B_T, 256);
      if (w == 0) { TRV(61, 0); TR(12); }
      wg_fence();
      o_steps<12, 4>(d, a);
      wg_commit();
      if (OGAP == 2) o_steps<16, 4>(e, a);
      o_steps<20, 4>(e, a);
      wg_commit();
      wg_wait<1>();
      store_partial(dstf, pack_partial(d, tag));
      if (w == 0) TR(4);
      wg_fence();
      o_steps<24, 8>(d, a);
      wg_commit();
      wg_wait<1>();
      store_partial(dstf + 1024, pack_partial(e, tag));
      bar_arrive(B_OE, 256);
      if (w == 0) TR(5);
      wg_wait<0>();
      store_partial(dstf + 2048, pack_partial(d, tag));
      if (w == 0) TR(15);
    }
    if (w < 3) {
      mbar_wait(sb + CB_REF, n & 1);
      wait_until(lds32(sb + C_REF), gdly);
      gather_reduce(gsrc, gdst, wg, tag, lane, sb, n, 16 + round * 4);
      if (++ring == MRING) { ring = 0; gdst -= MRING * 16384; }
      gdst += 16384;
    }
  }
}

template <int KS> __device__ __forceinline__ void x_scores(float* s, float* sm, const uint4* q, uint32_t ok, uint32_t om) {
  wg_rs32o<1, desc_sw64(C_KV + KS * 1024)>(s, q[KS].x, q[KS].y, q[KS].z, q[KS].w, ok);
  wg_rs8o<1, desc_n16(C_KM + KS * 512)>(sm, q[KS].x, q[KS].y, q[KS].z, q[KS].w, om);
  if constexpr (KS < 3) x_scores<KS + 1>(s, sm, q, ok, om);
}

__device__ __forceinline__ void chain_attn(const Params& P, uint32_t sb) {
  const int c = chain_id(), j = c & 1;
  const int tid = threadIdx.x, lane = tid & 31, w = __shfl_sync(~0u, (tid >> 5) & 3, 0);
  const int l = w >> 1, u = w & 1;
  const uint32_t rb = mapa(sb, j ^ 1);
  const float sc = 0.08838834764831845f * 1.4426950408889634f;
  const uint32_t ones = 0x3F803F80u;
  const uint32_t km_off = C_KM + (lane >> 3) * 256 + l * 128 + (lane & 7) * 16;
  const uint32_t qm_off = C_QM + (lane >> 4) * 256 + l * 128 + (lane & 7) * 16;
  const uint32_t kv_off = C_KV + l * 4096 + (lane & 15) * 64 + (((lane >> 4) ^ (u * 2) ^ ((lane >> 1) & 3)) << 4);

  if (lane == 0) mbar_arrive(sb + CB_M);
#pragma unroll 1
  for (int n = 0; n < STEPS; n++) {
    const uint32_t kvb = sb + kv_off + (n & 1) * 16384;
    if (w == 0 && elect()) { mbar_expect(sb + CB_SX, 2560); mbar_expect(sb + CB_OX, 2048); mbar_expect(sb + CB_XX, 2048); }
    mbar_wait(sb + CB_FULL + (n & 1) * 8, (n >> 1) & 1);
    if (n < 3 && tid == 256) TS(n ? 20 + n : 5);
    __syncwarp();
    {
      uint32_t km[8];
      uint4 kx[8];
#pragma unroll
      for (int i = 0; i < 8; i++) ldsm4t(kx[i].x, kx[i].y, kx[i].z, kx[i].w, (kvb ^ ((i & 1) * 32)) + (i >> 1) * 1024);
      mbar_wait(sb + CB_VF, n & 1);
      if (w == 1) TRD(60, kx[7].x);
      bar_sync(B_QK, 416);
      if (n + 1 == STEPS) {
        bar_sync(B_V, 256);
      } else {
      uint32_t qm[16];
#pragma unroll
      for (int ks = 0; ks < 4; ks++) ldsm4t(qm[4 * ks], qm[4 * ks + 1], qm[4 * ks + 2], qm[4 * ks + 3], sb + qm_off + ks * 512);
      ldsm4t(km[0], km[1], km[2], km[3], sb + km_off);
      ldsm4t(km[4], km[5], km[6], km[7], sb + km_off + 1024);
      float s[5][4];
#pragma unroll
      for (int i = 0; i < 5; i++) { s[i][0] = s[i][1] = s[i][2] = s[i][3] = 0.f; }
#pragma unroll
      for (int ks = 0; ks < 4; ks++) {
        const uint32_t* q = qm + 4 * ks;
        mma16(s[1], q[0], q[1], q[2], q[3], kx[2 * ks].x, kx[2 * ks].y);
        mma16(s[2], q[0], q[1], q[2], q[3], kx[2 * ks].z, kx[2 * ks].w);
        mma16(s[0], q[0], q[1], q[2], q[3], km[2 * ks], km[2 * ks + 1]);
        mma16(s[3], q[0], q[1], q[2], q[3], kx[2 * ks + 1].x, kx[2 * ks + 1].y);
        mma16(s[4], q[0], q[1], q[2], q[3], kx[2 * ks + 1].z, kx[2 * ks + 1].w);
      }
      const uint32_t sx = C_SX + l * 1280;
      st_async4(rb + sx + u * 512 + lane * 16, s[1][0], s[1][1], s[2][0], s[2][1], rb + CB_SX);
      st_async1(rb + sx + 1024 + u * 128 + lane * 4, __float_as_uint(u ? s[0][1] : s[0][0]), rb + CB_SX);
      bar_arrive_after<B_S, 256>(__float_as_uint(s[3][0]), __float_as_uint(s[4][0]));
      uint4 vx[4];
#pragma unroll
      for (int i = 0; i < 4; i++) ldsm4(vx[i].x, vx[i].y, vx[i].z, vx[i].w, (kvb ^ ((i & 1) * 32)) + 8192 + (2 * u + (i >> 1)) * 1024);
      mbar_wait(sb + CB_SX, n & 1);
      const uint4 p0 = lds128(sb + sx + u * 512 + lane * 16), p1 = lds128(sb + sx + (u ^ 1) * 512 + lane * 16);
      const uint2 p2 = make_uint2(lds32(sb + sx + 1024 + lane * 4), lds32(sb + sx + 1152 + lane * 4));
      float t[10] = {s[0][0] + __uint_as_float(p2.x), s[0][1] + __uint_as_float(p2.y),
                     s[1][0] + __uint_as_float(p0.x), s[1][1] + __uint_as_float(p0.y),
                     s[2][0] + __uint_as_float(p0.z), s[2][1] + __uint_as_float(p0.w),
                     s[3][0] + __uint_as_float(p1.x), s[3][1] + __uint_as_float(p1.y),
                     s[4][0] + __uint_as_float(p1.z), s[4][1] + __uint_as_float(p1.w)};
      float mx = fmaxf(fmaxf(fmaxf(fmaxf(t[2], t[3]), fmaxf(t[4], t[5])), fmaxf(fmaxf(t[6], t[7]), fmaxf(t[8], t[9]))), fmaxf(t[0], t[1]));
      mx = fmaxf(fmaxf(mx, __shfl_xor_sync(~0u, mx, 1)), fmaxf(__shfl_xor_sync(~0u, mx, 2), __shfl_xor_sync(~0u, mx, 3)));
      const float ms = -mx * sc;
#pragma unroll
      for (int i = 0; i < 10; i++) t[i] = ex2(fmaf(t[i], sc, ms));
      uint32_t p[5];
#pragma unroll
      for (int i = 0; i < 5; i++) p[i] = pack2(t[2 * i], t[2 * i + 1]);
      p[1] |= (p[0] & p[3] & p[4]) & 0x80008000u;
      float o[2][4], z[4] = {0.f, 0.f, 0.f, 0.f};
      mma16(z, ones, ones, ones, ones, p[1], p[2]);
#pragma unroll
      for (int i = 0; i < 2; i++) {
        o[i][0] = o[i][1] = o[i][2] = o[i][3] = 0.f;
        mma16(o[i], vx[2 * i].x, vx[2 * i].y, vx[2 * i].z, vx[2 * i].w, p[1], p[2]);
      }
      mma16(z, ones, ones, ones, ones, p[3], p[4]);
#pragma unroll
      for (int i = 0; i < 2; i++) mma16(o[i], vx[2 * i + 1].x, vx[2 * i + 1].y, vx[2 * i + 1].z, vx[2 * i + 1].w, p[3], p[4]);
      mma8(z, ones, ones, p[0]);
      bar_sync_after<B_V, 256>(p[1]);
      ldsm4(km[0], km[1], km[2], km[3], sb + km_off + (C_VM - C_KM) + u * 1024);
      mma8(o[0], km[0], km[1], p[0]);
      mma8(o[1], km[2], km[3], p[0]);
      const float i0 = rcp(z[0]), i1 = rcp(z[1]);
      const uint32_t oo = C_OI + u * 1024 + l * 128 + lane * 4;
      uint32_t ow[4];
#pragma unroll
      for (int i = 0; i < 2; i++) { ow[2 * i] = pack2(o[i][0] * i0, o[i][1] * i1); ow[2 * i + 1] = pack2(o[i][2] * i0, o[i][3] * i1); }
      stsm4(sb + C_OI + u * 1024 + l * 128 + (lane >> 3) * 256 + (lane & 7) * 16, ow[0], ow[1], ow[2], ow[3]);
      if (WFENCE) fence_async_smem();
      bar_arrive(B_O, 256);
#pragma unroll
      for (int i = 0; i < 4; i++) st_async1(rb + oo + 2048 + i * 256, ow[i], rb + CB_OX);
      }
    }
    {
      const uint32_t lane = opaque_tid() & 31, own = ((n & 1) * 16384 + j * 4096) >> 4;
      float s[16], sm[4];
#pragma unroll
      for (int i = 0; i < 16; i++) s[i] = sm[i & 3] = 0.f;
      {
        uint4 q[4];
        mbar_wait(sb + CB_Q, n & 1);
        auto load_q = [&]() {
#pragma unroll
          for (int ks = 0; ks < 4; ks++) q[ks] = lds128(sb + C_Q + (ks >> 1) * 4096 + w * 1024 + (ks & 1) * 512 + lane * 16);
        };
        if (QPOS == 0) load_q();
        mbar_wait(sb + CB_XX, n & 1);
        if (n + 1 < STEPS) mbar_wait(sb + CB_OX, n & 1);
        fence_async_smem();
        if (n + 1 < STEPS) bar_arrive(B_T, 256);
        if (QPOS == 1) load_q();
        if (n + 1 < STEPS) bar_sync(B_OE, 256);
        if (QPOS == 2) load_q();
        if (w == 1) { TRV(61, 0); TR(9); }
#pragma unroll 1
        for (uint32_t hf = 0; hf < 2; hf++) {
          wg_fence();
          x_scores<0>(s, sm, q, hf ? (C_KV2 - C_KV) >> 4 : own, hf ? (C_KM2 - C_KM) >> 4 : j * 8);
          wg_commit();
          wg_wait<0>();
#pragma unroll
          for (int ks = 0; ks < 4; ks++) asm volatile("mov.b32 %0, %1; mov.b32 %2, %3;" : "+r"(q[ks].x), "+r"(q[ks].y), "+r"(q[ks].z), "+r"(q[ks].w));
        }
      }
      const float neg = -1e9f * 11.313708498984761f;
      const int lim = 8 * (w - (int)(lane & 3)) + (int)(lane >> 2);
      float t[10] = {sm[0], sm[1]};
#pragma unroll
      for (int i = 0; i < 8; i++) t[2 + i] = i > lim ? neg : s[(i >> 1) * 4 + (i & 1)];
      float mx = fmaxf(fmaxf(fmaxf(fmaxf(t[2], t[3]), fmaxf(t[4], t[5])), fmaxf(fmaxf(t[6], t[7]), fmaxf(t[8], t[9]))), fmaxf(t[0], t[1]));
      mx = fmaxf(fmaxf(mx, __shfl_xor_sync(~0u, mx, 1)), fmaxf(__shfl_xor_sync(~0u, mx, 2), __shfl_xor_sync(~0u, mx, 3)));
      const float ms = -mx * sc;
#pragma unroll
      for (int i = 0; i < 10; i++) t[i] = ex2(fmaf(t[i], sc, ms));
      uint32_t p[5];
#pragma unroll
      for (int i = 0; i < 5; i++) p[i] = pack2(t[2 * i], t[2 * i + 1]);
      float z = ((t[0] + t[1]) + (t[2] + t[3])) + ((t[4] + t[5]) + (t[6] + t[7])) + (t[8] + t[9]);
      const uint32_t row = sb + C_Q + w * 1024 + (lane >> 2) * 128 + (((lane & 3) ^ (lane >> 2)) << 4);
#pragma unroll 1
      for (uint32_t hf = 0; hf < 2; hf++) {
        float o[32];
        const uint32_t vo = hf ? (C_KV2 + 4096 - C_KV - 8192) >> 4 : own;
        wg_fence();
        wg_rs64o<0, desc_sw64(C_KV + 8192)>(o, p[1], p[1], p[2], p[2], vo);
        wg_rs64o<1, desc_sw64(C_KV + 8192 + 32)>(o, p[3], p[3], p[4], p[4], vo);
        wg_rs64o<1, mkdesc(C_VM, 128, 256, 0)>(o, p[0], p[0], 0, 0, hf ? (C_VM2 - C_VM) >> 4 : j * 8);
        wg_commit();
        if (hf) {
          if (elect()) mbar_arrive(sb + CB_M);
        } else {
          z += __shfl_xor_sync(~0u, z, 1);
          z = rcp(z + __shfl_xor_sync(~0u, z, 2));
        }
        wg_wait<0>();
#pragma unroll
        for (int qq = 0; qq < 2; qq++) {
          const float* r = o + 16 * qq;
          sts128((row ^ (qq * 64)) + hf * 4096,
                 make_uint4(pack2(r[0] * z, r[1] * z), pack2(r[4] * z, r[5] * z), pack2(r[8] * z, r[9] * z), pack2(r[12] * z, r[13] * z)));
        }
      }
      bar_arrive(B_G, 160);
      if (w == 1) TR(10);
    }
  }
  if ((threadIdx.x & 127) == 0) TS(6);
}

__device__ __forceinline__ void chain_aux(const Params& P, uint32_t sb) {
  const uint32_t c = chain_id(), j = c & 1, lane = threadIdx.x & 31, w = __shfl_sync(~0u, (threadIdx.x >> 5) & 3, 0);
  if (threadIdx.x == 384) grid_wait(1, lds32(sb + S_GEN));
  bar_sync(B_WG2, 384);
  if (threadIdx.x == 384) TS(13);
  if (w == 0) {
    const uint32_t* fg = g_fl + FL_G + near_half(XB_F, c) * 1024 + (c >> 1) * 8;
#pragma unroll 1
    for (int n = 0; n < STEPS; n++) {
      const unsigned char* blk = g_qkv + (uint32_t)((n % RING) * (N_CHAIN * 24576));
      const uint32_t t1 = clk(), kb = sb + CB_FULL + (n & 1) * 8, kv = sb + C_KV + (n & 1) * 16384;
      uint32_t t0 = t1 - 100000, x = 0;
      if (n > 0) {
        wait_until(t1, KMIN);
        do asm volatile("ld.relaxed.gpu.global.u32 %0, [%1];" : "=r"(x) : "l"(fg) : "memory"); while (x <= n && clk() - t1 < KWIN);
        if (NOBULK) x = n + 1;
        if (x > n) {
          asm volatile("fence.acquire.gpu;" ::: "memory");
          fence_async_global();
          if (elect()) { mbar_expect(kb, 8192); bulk_load(kv, blk + c * 24576, 8192, kb); }
        }
        T3(0); CNT(12, 1 + (x <= n));
        mbar_wait(sb + CB_REF, (n - 1) & 1);
        t0 = lds32(sb + C_REF);
        wait_until(t0, DLYK - 500);
      }
      if (!NOBULK) wait_flags(fg + (lane & 1) * 256, n + 1);
      fence_async_global();
      wait_until(t0, DLYK);
      if (elect()) {
        if (x <= n) { mbar_expect(kb, 8192); bulk_load(kv, blk + c * 24576, 8192, kb); }
        mbar_expect(sb + CB_VF, 8192);
        bulk_load(kv + 8192, blk + (c * 24576 + 8192), 8192, sb + CB_VF);
      }
      T3(1);
      if (!NOBULK) wait_flags(fg + 512, n + 1);
      T3(2);
      fence_async_global();
      if (n > 0) bar_sync(B_R, 64);
      if (elect()) {
        mbar_expect(sb + CB_Q, 16384);
        bulk_load(sb + C_Q, blk + (c * 24576 + 16384), 8192, sb + CB_Q);
        bulk_load(sb + C_KV2, blk + ((c ^ 1) * 24576 + j * 4096), 4096, sb + CB_Q);
        bulk_load(sb + C_KV2 + 4096, blk + ((c ^ 1) * 24576 + 8192 + j * 4096), 4096, sb + CB_Q);
      }
      T3(3);
    }
  } else {
    const uint32_t near = __ballot_sync(~0u, near_half(XB_M + min(lane, MRING - 1u) * 8, c));
    uint32_t ring = 0;
    if (w > 1) {
      const uint32_t odd = w & 1, chk = pinned(sb + C_M + odd * 2048 + m_probe(lane)), again = sb + CB_MV + 32 + odd * 8;
      const bool one = elect();
      uint32_t mph = 0;
#pragma unroll 1
      for (int n = 0; n <= STEPS; n++) {
#pragma unroll
        for (int k = 0; k < 3; k++) {
          if (n == STEPS || (k == 2 && odd)) break;
          const uint32_t b = 2 * k + odd, at = chk + (k ? k * 8192 - 2048 + odd * 2048 : 0);
          uint32_t mb = sb + CB_M + b * 8, ph = n & 1;
          int it = 1;
          while (true) {
            mbar_wait(mb, ph);
            const bool bad = __any_sync(~0u, (k ? m_max(at, at + 2048) : max(m_max(at, at ^ 8), odd ? m_max(at + 2048, (at ^ 8) + 2048) : 0)) == SENT);
            if (one && !bad) mbar_arrive(sb + CB_MV + (k ? b * 8 - 8 : 0));
            if (!bad) break;
            mb = again; ph = mph; mph ^= 1;
            if (one) {
              if (k == 0) sts32(sb + C_BAD, n + 1);
              mbar_expect(mb, b ? 4096 : 2048);
              m_fetch(sb, ring * 65536 + ((near >> ring) & 1) * 4096, b, mb);
            }
            __syncwarp();
            spin_guard(it);
          }
          TR(41 + b * 4); CNT(6 + b, it);
        }
        ring = ring + 1 == MRING ? 0 : ring + 1;
        if (!odd) {
          if (n < STEPS) { TRSYNC(); TRDUMP(n - 2); }
        } else if (n > 0) {
          unsigned char* o = g_oimg + (uint32_t)(((n - 1) & (RING - 1)) * (N_CHAIN * 8192) + j * 4096);
          bar_sync(B_G, 160);
          fence_async_smem();
          if (one) {
            bulk_store(o + c * 8192, sb + C_Q, 4096);
            bulk_store(o + (c ^ 1) * 8192, sb + C_Q + 4096, 4096);
            asm volatile("cp.async.bulk.commit_group;\ncp.async.bulk.wait_group.read 0;" ::: "memory");
            { const int n_ = n - 1; { const int n = n_; T3(4); (void)n; } }
          }
          __syncwarp();
          if (n < STEPS) bar_arrive(B_R, 64);
          if (one) {
            bulk_done_inc(g_fl + FL_O + c);
            { const int n_ = n - 1; { const int n = n_; T3(5); (void)n; } }
          }
          __syncwarp();
        }
      }
    } else {
      const uint32_t* ts = g_fl + FL_SYNC + near_half(XB_F + 1, c) * 1024 + lane * 2;
      uint32_t t0 = clk() - 100000;
#pragma unroll 1
      for (int n = 0; n < STEPS; n++) {
        const uint32_t src = ring * 65536 + ((near >> ring) & 1) * 4096;
        if (lane < 5) mbar_expect(sb + CB_M + lane * 8, lane ? 4096 : 2048);
        __syncwarp();
        if (elect()) {
#pragma unroll
          for (int b = 0; b < 5; b++) {
            wait_until(t0, P.dly[14 + b]);
            m_fetch(sb, src, b, sb + CB_M + b * 8);
            TR(40 + b * 4);
          }
        }
        __syncwarp();
        ring = ring + 1 == MRING ? 0 : ring + 1;
        uint32_t va, vb;
        const uint32_t off = timer_offset(), tag = (uint32_t)(n + 1) << 24;
        bar_sync(B_QK, 416);
        if (n + 1 == STEPS) break;
        sts32(sb + C_REF + 4, 0);
        const uint32_t c0 = clk(), stamp = c0 + off;
        st_relaxed_if(g_fl + FL_SYNC + lane * 1024 + c, tag | (stamp & 0xFFFFFF), lane < 2);
        TR(13);
        wait_until(c0, DLYS);
        int it = 0;
        do {
          asm volatile("ld.relaxed.gpu.global.v2.u32 {%0,%1}, [%2];" : "=r"(va), "=r"(vb) : "l"(ts) : "memory");
          spin_guard(it);
        } while (__any_sync(~0u, ((va ^ tag) | (vb ^ tag)) >> 24));
        const int late = __reduce_max_sync(~0u, max((int)((va - stamp) << 8), (int)((vb - stamp) << 8))) >> 8;
        t0 = c0 + min((uint32_t)late, clk() - c0);
        if (elect()) {
          sts32(sb + C_REF, t0);
          mbar_arrive(sb + CB_REF);
        }
        st_relaxed_if(g_fl + FL_TICK + lane * 1024, tag | ((t0 + off) & 0xFFFFFF), c == 0 && lane < 2);
        TR(14); CNT(11, it);
        bar_sync(B_M, 160);
      }
    }
  }
}

template <int WG>
__device__ __forceinline__ void g_math(const Params& P, uint32_t sb) {
  const int q = g_unit(WG);
  const int lane = threadIdx.x & 31, w = (threadIdx.x >> 5) & 3;
  const bool isq = q >= 64;
  uint32_t a[136];
  {
    const uint32_t stage = sb + G_W + WG * 73728;
    mbar_wait(sb + W_BAR + WG * 8, 0);
    if (threadIdx.x == 0) TS(23);
    load_frags<34>(a, stage);
    fence_async_smem();
    bar_sync(B_WG0 + WG, 128);
    if (threadIdx.x == 0) TS(24);
    load_wg(P, sb, false, WG, w);
    if (threadIdx.x == 0) TS(25);
    mbar_wait(sb + W_BAR + WG * 8, 1);
  }
  if ((threadIdx.x & 127) == 0) TS(4);
  const uint32_t off0 = (q & 31) * 49152 + (q >> 5) * 8192 +
                        (isq ? (w >> 1) * 4096 + (w & 1) * 512 + lane * 16 : w * 1024 + (lane >> 2) * 64 + (((lane ^ (lane >> 3)) & 3) << 4));
#pragma unroll 1
  for (int n = 0; n < STEPS; n++) {
    float d0[32], d1[32];
    if (WG == 0 && n >= LOCK0) bar_sync(B_OE, 160);
    if (n > 0) bar_sync(B_V + WG, 256);
#pragma unroll
    for (int ch = 0; ch < 9; ch++) {
      mbar_wait(sb + G_BAR + ch * 8, n & 1);
      if (ch == 0) { if ((threadIdx.x & 127) == 0) T3(5 + WG * 3); __syncwarp(); }
      if (ch == 4) { if ((threadIdx.x & 127) == 0) T3(6 + WG * 3); __syncwarp(); }
      if (ch == 8 && (WG == 0 ? n > 0 : n + 1 < STEPS)) bar_arrive(B_V + (WG ^ 1), 256);
      wg_fence();
#pragma unroll
      for (int kk = 0; kk < 4 - FASTG; kk++) {
        const int i = ch * 4 + kk;
        float* d = i & 1 ? d1 : d0;
        const uint64_t db = desc_sw128(G_RING + ch * 8192 + (kk & 2) * 32);
        if (i < 2) wg_rs64<0>(d, a + i * 4, db);
        else if (i < 34) wg_rs64<1>(d, a + i * 4, db);
        else wg_ss64<1>(d, desc_sw128(G_W2 + WG * 4096 + (i - 34) * 2048), db);
        wg_ss64<1>(d, desc_sw128(G_W + WG * 73728 + i * 2048), db + 2);
      }
      wg_commit();
      if (ch > 0) { wg_wait<1>(); if (lane == 0) mbar_arrive(sb + G_BAR + 128 + (ch - 1) * 8); }
    }
    wg_wait<0>();
    if (lane == 0) mbar_arrive(sb + G_BAR + 128 + 8 * 8);
    if ((threadIdx.x & 127) == 0) T3(7 + WG * 3);
    __syncwarp();
    if (WG == 0) wait_until(clk(), DLYW);
    unsigned char* base = g_qkv + (size_t)(n & (RING - 1)) * (N_CHAIN * 24576);
    if ((ABL & 1) && d0[0] != 1234.5f) {
    } else if (isq) {
#pragma unroll
      for (int i = 0; i < 8; i++) {
        const float *d = (i < 4 ? d0 : d1) + 4 * i, *e = (i < 4 ? d1 : d0) + 4 * i;
        *(uint4*)(base + off0 + (i >> 2) * 24576 + (i & 3) * 1024) =
          make_uint4(movmat(pack2(d[0], d[1])), movmat(pack2(e[0], e[1])), movmat(pack2(d[2], d[3])), movmat(pack2(e[2], e[3])));
      }
    } else {
#pragma unroll
      for (int i = 0; i < 8; i++) {
        const float* d = (i < 4 ? d0 : d1) + 8 * (i & 2) + 2 * (i & 1);
        *(uint4*)(base + off0 + (i >> 2) * 24576 + (i & 2) * 2048 + (i & 1) * 512) =
          make_uint4(pack2(d[0], d[1]), pack2(d[4], d[5]), pack2(d[8], d[9]), pack2(d[12], d[13]));
      }
    }
    bar_arrive(B_M + WG, 160);
  }
}

__device__ __forceinline__ void fill16(void* p, uint32_t v) {
  asm volatile("st.global.v4.u32 [%0], {%1,%1,%1,%1};" :: "l"(p), "r"(v) : "memory");
}
__device__ __forceinline__ void g_load(const Params& P, uint32_t sb) {
  const int lane = threadIdx.x & 31, w = __shfl_sync(~0u, (threadIdx.x >> 5) & 3, 0);
  if (w == 2) return;
  uint32_t fl = 0;
#pragma unroll 1
  for (int n = w == 3 ? LOCK0 : 0; n < STEPS; n++) {
    if (w && n == LOCK0) { grid_wait(1, lds32(sb + S_GEN)); fl = near_half(XB_F, bid()) * 1024; }
    if (w == 3) {
      const uint32_t tag = (uint32_t)(n - LOCK0 + 1) << 24;
      uint32_t v; int it = 0;
      do { asm volatile("ld.relaxed.gpu.global.u32 %0, [%1];" : "=r"(v) : "l"(g_fl + fl + FL_TICK) : "memory"); spin_guard(it); } while (!NOCHAIN && v < tag);
      const uint32_t off = timer_offset(), now = clk(), t0 = now - ((v ^ tag) >> 24 ? DLYG : (now + off - v) & 0xFFFFFF);
      asm volatile("fence.acquire.gpu;" ::: "memory");
      if (lane == 0) T3(11);
      __syncwarp();
      wait_until(t0, DLYG);
      if (lane == 0) T3(4);
      bar_sync(B_OE, 160);
      continue;
    }
    if (w == 0 || n == 0) {
      if (n < NSEG) wait_flags(g_lnflag + n * 16 + (lane & 1) * 8, 1);
    } else if (!NOCHAIN && n >= LAG) {
      wait_flags(g_fl + fl + FL_F + (lane & 1) * 8, n - LAG + 1);
    }
    if (w) { if (lane == 0) T3(12); bar_sync(B_X, 96); }
    fence_async_global();
    const unsigned char* src = g_lnimg + (uint32_t)((w ? (n >= LAG ? NSEG + n - LAG : 0) : min(n, NSEG - 1)) * 36864);
#pragma unroll 1
    for (int ch = 0; ch < 9; ch++) {
      const uint32_t full = sb + G_BAR + ch * 8;
      mbar_wait(full + 128, (n & 1) ^ 1);
      if (elect()) {
        mbar_expect(full, ABL & 2 ? 16 : 4096);
        bulk_load(sb + G_RING + ch * 8192 + w * 4096, src + ch * 4096, ABL & 2 ? 16 : 4096, full);
      }
    }
  }
}

__device__ __forceinline__ void g_aux(const Params& P, uint32_t sb) {
  const int lane = threadIdx.x & 31, w = (threadIdx.x >> 5) & 3;
  if (w == 1 || w == 2) {
    const int q = g_unit(w - 1);
    uint32_t* f = g_fl + FL_G + q * 8;
#pragma unroll 1
    for (int n = 0; n < STEPS; n++) {
      const uint32_t ln = opaque_tid() & 31;
      uint4* z = (uint4*)g_oacc + (uint32_t)(((n + 1) % ARING) * (16 * DM) + q * 96 + ln);
      if (!(ABL & 16)) { fill16(z, 0); fill16(z + 32, 0); fill16(z + 64, 0); }
      if (n + 3 >= MRING && q < 80) fill16((uint4*)g_mimg + (uint32_t)(((n + 3) % MRING) * 4096 + q * 32 + ln), SENT);
      bar_sync(B_M + (w - 1), 160);
      if (lane == 0) { T3(w * 2 - 2); fence_async_global(); flag_release(f, n + 1); T3(w * 2 - 1); }
      __syncwarp();
    }
  } else {
    const uint32_t u = (bid() - N_CHAIN) * 2 + (w & 1), r = u / 36 * 16 + (u & 3) * 4 + (lane >> 3);
    uint32_t o = r * (DM / 8) + (u % 36 >> 2) * 8 + ((lane & 7) ^ ((r >> 1) & 3));
#pragma unroll 1
    for (int k = -LAG - 1; k < STEPS; k++) {
      if (k < NSEG - 1) bar_sync(B_X, 96);
      if (k < LAG || u >= 72) continue;
      if (k >= NSEG - 1) {
        const uint32_t* f = g_fl + near_half(XB_F, bid()) * 1024;
        if (k + 1 == STEPS) wait_flags(f + FL_F + (lane & 1) * 8, NSEG + 1);
        wait_flags(f + FL_OCNT + (max(k, NSEG) % OCRING) * 8, N_O * 3 * (max(k, NSEG) / OCRING + 1));
      }
      const float4* a = (const float4*)g_oacc + ((k % ARING) * (16 * DM) + 8 * DM + u * 64 + lane * 2);
      const float4 p = __ldcg(a), v = __ldcg(a + 1);
      const uint4 x = __ldcg((const uint4*)P.out + o);
      ((uint4*)P.out)[o] = make_uint4(badd2(x.x, pack2(p.x, p.y)), badd2(x.y, pack2(p.z, p.w)), badd2(x.z, pack2(v.x, v.y)), badd2(x.w, pack2(v.z, v.w)));
      o += 4 * DM;
    }
    if ((threadIdx.x & 127) == 0) TS(7);
  }
}

template <int WG>
__device__ __forceinline__ void o_math(const Params& P, uint32_t sb) {
  const int ksl = (bid() - N_CHAIN - N_G) / 3;
  const int nc = ksl < 4 ? 11 : 10;
  const int lane = threadIdx.x & 31, w = (threadIdx.x >> 5) & 3, g = lane >> 2, tq = lane & 3;
  uint32_t a[96];
  {
    mbar_wait(sb + W_BAR + WG * 8, 0);
    load_frags<24>(a, sb + WG * 49152);
    fence_async_smem();
    bar_sync(B_INIT, 416);
    load_wg(P, sb, false, WG, w);
    mbar_wait(sb + W_BAR + WG * 8, 1);
  }
  if ((threadIdx.x & 127) == 0) TS(4);
  const uint32_t st0 = sb + O_ST + tq * 512 + ((w * 16 + g) ^ (tq * 8)) * 4;
#pragma unroll 1
  for (int n = 0; n < STEPS; n++) {
    float d[32];
    if (WG > 0 || n > 0) bar_sync(B_V + WG, 256);
#pragma unroll
    for (int gr = 0; gr < 5; gr++) {
      mbar_wait(sb + O_BAR + gr * 8, n & 1);
      if (gr == 0) { if ((threadIdx.x & 127) == 0) T3(13 + WG); __syncwarp(); }
      if (gr == (WG == 0 ? OTURN : 4) && (WG < 2 || n + 1 < STEPS)) bar_arrive(B_V + (WG + 1) % 3, 256);
      wg_fence();
#pragma unroll
      for (int ks = gr * 8; ks < gr * 8 + 8 - 2 * FASTG; ks++) {
        const uint64_t db = desc_sw128(O_RING + (ks >> 2) * 8192 + (ks & 3) * 32);
        if (ks == 0) wg_rs64<0>(d, a, db);
        else if (!(ks % 5 & 1)) wg_rs64<1>(d, a + (ks / 5 * 3 + ks % 5 / 2) * 4, db);
        else wg_ss64<1>(d, desc_sw128(O_W + WG * 40960 + (ks / 5 * 2 + ks % 5 / 2) * 2048), db);
      }
      if (gr == 4 && nc == 11) {
#pragma unroll
        for (int ks = 40; ks < 44; ks++)
          wg_ss64<1>(d, desc_sw128(O_W + WG * 40960 + (ks - 24) * 2048), desc_sw128(O_RING + 10 * 8192 + (ks & 3) * 32));
      }
      wg_commit();
      if (gr > 0) { wg_wait<1>(); if (lane == 0) mbar_arrive(sb + O_BAR + 128 + (gr - 1) * 8); }
    }
    wg_wait<0>();
    if (lane == 0) mbar_arrive(sb + O_BAR + 128 + 4 * 8);
    if ((threadIdx.x & 127) == 0) T3(WG == 0 ? 1 : WG == 1 ? 8 : 12);
    __syncwarp();
#pragma unroll
    for (int sl = 0; sl < 2; sl++) {
      mbar_wait(sb + OB_ST + WG * 16 + sl * 8, (n & 1) ^ (WG == 0));
#pragma unroll
      for (int nb = sl * 4; nb < sl * 4 + 4; nb++) {
        sts32(st0 + nb * 2048, __float_as_uint(d[nb * 4]));
        sts32(st0 + nb * 2048 + 256, __float_as_uint(d[nb * 4 + 1]));
        sts32((st0 ^ 32) + nb * 2048, __float_as_uint(d[nb * 4 + 2]));
        sts32((st0 ^ 32) + nb * 2048 + 256, __float_as_uint(d[nb * 4 + 3]));
      }
      fence_async_smem();
      bar_arrive((sl ? B_G : B_M) + WG, 160);
    }
  }
}

__device__ __forceinline__ void o_aux(const Params& P, uint32_t sb) {
  const int i = bid() - N_CHAIN - N_G, ksl = i / 3;
  const int c0 = ksl * 11 - max(ksl - 4, 0), nc = ksl < 4 ? 11 : 10;
  const int lane = threadIdx.x & 31, w = __shfl_sync(~0u, (threadIdx.x >> 5) & 3, 0);
  if (w == 0) {
    bar_sync(B_INIT, 416);
    const uint32_t* f = g_fl + FL_O + near_half(XB_F + 1, bid()) * 1024 + min((c0 & ~1) + lane, (c0 + nc - 1) | 1);
#pragma unroll 1
    for (int n = 0; n < STEPS; n++) {
      const unsigned char* src = g_oimg + (uint32_t)(((n % RING) * N_CHAIN + c0) * 8192);
      if (!NOCHAIN) wait_flags(f, n + 1);
      fence_async_global();
      if (lane == 0) T3(0);
#pragma unroll
      for (int gr = 0; gr < 5; gr++) {
        const uint32_t full = sb + O_BAR + gr * 8, bytes = ABL & 4 ? 16 : (gr < 4 ? 2 : nc - 8) * 8192;
        mbar_wait(full + 128, (n & 1) ^ 1);
        if (elect()) {
          mbar_expect(full, bytes);
          bulk_load(sb + O_RING + gr * 16384, src + gr * 16384, bytes, full);
        }
      }
    }
  } else {
#pragma unroll 1
    for (int n = 0; n < STEPS; n++) {
      float* dst = g_oacc + (uint32_t)((n % ARING) * (64 * DM) + ((i % 3) * 3 + (w - 1 + ksl) % 3) * 1024);
      const bool early = w == 3 && n < NSEG;
      bar_sync(B_M + (w - 1), 160);
      if (lane == 0) {
        T3(w * 2);
        if (n < NSEG && !(ABL & 8)) { bulk_reduce(dst, sb + O_ST, 4096); bulk_reduce(dst + 16 * DM, sb + O_ST + 4096, 4096); }
        asm volatile("cp.async.bulk.commit_group;" ::: "memory");
        if (early) {
          asm volatile("cp.async.bulk.wait_group.read 0;" ::: "memory");
          mbar_arrive(sb + OB_ST);
          T3(8 + w);
          bulk_done_inc(g_fl + FL_OCNT + (n % OCRING) * 8);
          T3(w * 2 + 1);
        }
      }
      __syncwarp();
      bar_sync(B_G + (w - 1), 160);
      if (lane == 0) {
        if (n >= LAG && !(ABL & 8)) { bulk_reduce(dst + 32 * DM, sb + O_ST + 8192, 4096); bulk_reduce(dst + 48 * DM, sb + O_ST + 12288, 4096); }
        asm volatile("cp.async.bulk.commit_group;\ncp.async.bulk.wait_group.read 1;" ::: "memory");
        if (!early) mbar_arrive(sb + OB_ST + (w % 3) * 16);
        asm volatile("cp.async.bulk.wait_group.read 0;" ::: "memory");
        mbar_arrive(sb + OB_ST + (w % 3) * 16 + 8);
        if (!early) {
          T3(8 + w);
          bulk_done_inc(g_fl + FL_OCNT + (n % OCRING) * 8);
          T3(w * 2 + 1);
        }
      }
      __syncwarp();
    }
  }
}

constexpr uint32_t Y_PITCH = 1168, Y_ROWS = 16 * Y_PITCH;
template <int R> __device__ __forceinline__ void y_rows(uint32_t* y, uint32_t src, uint32_t dst, int w, int bar) {
  const int lane = threadIdx.x & 31;
#pragma unroll
  for (int k = 0; k < 2 * R + 1; k++) {
    const int op = w + k * (16 / R);
    if (k == 2 * R && w >= 4) break;
    uint32_t a, b, c, d;
    ldsm4t(a, b, c, d, src + op * 512 + (lane & 16) * 16 + (lane & 7) * 32 + (lane & 8) * 2);
    stsm4(dst + (lane & 15) * Y_PITCH + op * 32 + (lane & 16), a, b, c, d);
  }
  bar_sync(bar, 512 / R);
  const uint32_t row = dst + ((w & 6) * 2 + (w >> 3) * 2 + (w & 1)) * Y_PITCH + lane * 4;
#pragma unroll
  for (int i = 0; i < 9 * R; i++) y[i] = lds32(row + i / 9 * 2 * Y_PITCH + i % 9 * 128);
}

__device__ __forceinline__ void f_role(const Params& P, uint32_t sb) {
  const int lane = threadIdx.x & 31, w = __shfl_sync(~0u, threadIdx.x >> 5, 0), r0 = (bid() - N_CHAIN - N_G - N_O) * 16;
  if (w == 8) {
    const uint32_t* fo = g_fl + FL_OCNT + near_half(XB_F, bid()) * 1024;
    fence_async_global();
#pragma unroll 1
    for (int n = 0; n < NSEG; n++) {
      if (n > 0) bar_sync(2, 288);
      if (elect()) {
        mbar_expect(sb + F_BAR, 36864);
        bulk_load(sb + F_XY, P.X + (size_t)(n * 32 + r0) * DM, 18432, sb + F_BAR);
        bulk_load(sb + F_XY + 18432, g_yT + (size_t)(n * 32 + r0) * DM, 18432, sb + F_BAR);
        mbar_expect(sb + F_BAR + 8, 36864);
        T3(1);
      }
      wait_flags(fo + (n % OCRING) * 8, NOCHAIN == 5 ? 0 : N_O * 3 * (n / OCRING + 1));
      fence_async_global();
      if (elect()) { bulk_load(sb + F_A, g_oacc + (uint32_t)((n % ARING) * (64 * DM) + r0 * DM), 36864, sb + F_BAR + 8); T3(0); }
    }
  } else if (w == 9) {
#pragma unroll 1
    for (int n = 0; n < NSEG; n++) {
      const uint32_t st = sb + (n & 1) * 36864;
      unsigned char* p = g_lnimg + (uint32_t)((NSEG + n) * 36864 + r0 * 128);
      bar_sync(1, 288);
      if (elect()) {
        T3(2);
#pragma unroll
        for (int i = 0; i < 9; i++) bulk_store(p + i * 4096, st + F_L + i * 2048, 2048);
        asm volatile("cp.async.bulk.commit_group;" ::: "memory");
        bulk_done_inc(g_fl + FL_F + (bid() & 1) * 8);
        T3(3);
        bulk_store(P.out + (size_t)(n * 32 + r0) * DM, st + F_X, 18432);
        asm volatile("cp.async.bulk.commit_group;\ncp.async.bulk.wait_group.read 0;" ::: "memory");
        if (n + 1 == NSEG) bulk_done_inc(g_fl + FL_F + (bid() & 1) * 8);
      }
      __syncwarp();
    }
  } else if (w < 8) {
    const uint32_t row = sb + w * 1152 + lane * 4, acc = sb + F_A + w * 256 + (lane ^ ((w & 6) * 2)) * 8;
    const uint32_t ln = sb + F_L + w * 128 + (((lane >> 2) ^ w) << 4) + (lane & 3) * 4;
#pragma unroll 1
    for (int n = 0; n < NSEG; n++) {
      const uint32_t st = (n & 1) * 36864;
      uint32_t x[18], y[18], l[18];
      mbar_wait(sb + F_BAR, n & 1);
#pragma unroll
      for (int i = 0; i < 18; i++) x[i] = lds32(row + F_XY + i / 9 * 9216 + i % 9 * 128);
      y_rows<2>(y, sb + F_XY + 18432, sb + F_Y, w, 3);
      layernorm9<2>(x, l);
#pragma unroll
      for (int i = 0; i < 18; i++) x[i] = badd2(x[i], bmul2(l[i], y[i]));
      mbar_wait(sb + F_BAR + 8, n & 1);
      if (threadIdx.x == 0) T3(4);
      __syncwarp();
      uint2 a[18];
#pragma unroll
      for (int i = 0; i < 18; i++) a[i] = lds64(acc + i / 9 * 2048 + i % 9 * 4096);
#pragma unroll
      for (int i = 0; i < 18; i++) x[i] = badd2(x[i], pack2(__uint_as_float(a[i].x), __uint_as_float(a[i].y)));
      if (n + 1 < NSEG) bar_arrive(2, 288);
      layernorm9<2>(x, l);
#pragma unroll
      for (int i = 0; i < 18; i++) { x[i] = badd2(x[i], bmul2(l[i], y[i])); sts32(row + st + F_X + i / 9 * 9216 + i % 9 * 128, x[i]); }
      layernorm9<2>(x, l);
#pragma unroll
      for (int i = 0; i < 18; i++) sts32(ln + st + i / 9 * 1024 + i % 9 * 2048, l[i]);
      fence_async_smem();
      bar_sync(1, 288);
    }
  }
}

constexpr uint32_t P_CH = 147456, P_CHSZ = 12800, P_H = 4352;
static_assert(P_CH + 6 * P_CHSZ <= G_BAR, "prologue smem");

template <int N>
__device__ __forceinline__ void conv_fold(float (*acc)[4], bool hi, uint32_t mine, uint32_t theirs, int bar, int cnt) {
#pragma unroll
  for (int i = 0; i < N / 2; i++) {
    uint4 v;
    v.x = __float_as_uint(hi ? acc[i][0] : acc[i + N / 2][0]); v.y = __float_as_uint(hi ? acc[i][1] : acc[i + N / 2][1]);
    v.z = __float_as_uint(hi ? acc[i][2] : acc[i + N / 2][2]); v.w = __float_as_uint(hi ? acc[i][3] : acc[i + N / 2][3]);
    sts128(mine + i * 512, v);
  }
  bar_sync(bar, cnt);
#pragma unroll
  for (int i = 0; i < N / 2; i++) {
    const uint4 v = lds128(theirs + i * 512);
    acc[i][0] = (hi ? acc[i + N / 2][0] : acc[i][0]) + __uint_as_float(v.x); acc[i][1] = (hi ? acc[i + N / 2][1] : acc[i][1]) + __uint_as_float(v.y);
    acc[i][2] = (hi ? acc[i + N / 2][2] : acc[i][2]) + __uint_as_float(v.z); acc[i][3] = (hi ? acc[i + N / 2][3] : acc[i][3]) + __uint_as_float(v.w);
  }
}
template <int N>
__device__ __forceinline__ void conv_store(const float (*acc)[4], int tile0, uint32_t su, int d, uint32_t dd) {
  const int lane = threadIdx.x & 31, g = lane >> 2, tq = lane & 3;
#pragma unroll
  for (int i = 0; i < N; i++) {
    const uint32_t ad = su + (8 + (tile0 + i) * 8 + g) * 32 + tq * 4, sw = (g & 4) << 2;
    const uint32_t lo = badd2(movmat(pack2(acc[i][0], acc[i][1])), bmul2(lds32(ad + sw), dd));
    const uint32_t hi = badd2(movmat(pack2(acc[i][2], acc[i][3])), bmul2(lds32(ad + (sw ^ 16)), dd));
    ((uint2*)g_yT)[(((tile0 + i) * 8 + g) * DM + d) * 4 + tq] = make_uint2(lo, hi);
  }
}

__device__ __forceinline__ void prologue(const Params& P, uint32_t sb) {
  const int b = bid(), tid = threadIdx.x, lane = tid & 31, warp = tid >> 5, t0 = b * 16;
  const bool isg = b >= N_CHAIN && b < N_CHAIN + N_G;
  const int nch = isg ? 2 : b < 128 ? 6 : 0, chb = b < N_CHAIN ? b * 6 : isg ? b * 2 + 256 : b * 6 - 192;
  const uint32_t tstart = clk();
  if (tid < 288) {
    if (b < 128) {
      const int c = (tid >> 1) * 4, tt = t0 + (tid & 1) * 8;
      uint2 kr[11], vr[8];
#pragma unroll
      for (int i = 0; i < 11; i++) { const int t = tt + i - 3; kr[i] = t >= 0 ? __ldg((const uint2*)(P.K + (size_t)t * DM + c)) : make_uint2(0, 0); }
#pragma unroll
      for (int i = 0; i < 8; i++) vr[i] = __ldg((const uint2*)(P.V + (size_t)(tt + i) * DM + c));
#pragma unroll
      for (int e = 0; e < 2; e++) {
        const uint4 sh = __ldg((const uint4*)(P.shift + c * 4) + e);
        const uint32_t s0 = __byte_perm(sh.x, sh.z, 0x5410), s1 = __byte_perm(sh.x, sh.z, 0x7632);
        const uint32_t s2 = __byte_perm(sh.y, sh.w, 0x5410), s3 = __byte_perm(sh.y, sh.w, 0x7632);
        uint32_t v[8];
#pragma unroll
        for (int i = 0; i < 8; i++) {
          const uint32_t k3 = e ? kr[i].y : kr[i].x, k2 = e ? kr[i + 1].y : kr[i + 1].x, k1 = e ? kr[i + 2].y : kr[i + 2].x, k0 = e ? kr[i + 3].y : kr[i + 3].x;
          v[i] = bmul2(badd2(badd2(badd2(bmul2(k3, s3), bmul2(k2, s2)), bmul2(k1, s1)), bmul2(k0, s0)), e ? vr[i].y : vr[i].x);
        }
        *(uint4*)(g_kvT + (size_t)(c + 2 * e) * KVP + tt) =
          make_uint4(__byte_perm(v[0], v[1], 0x5410), __byte_perm(v[2], v[3], 0x5410), __byte_perm(v[4], v[5], 0x5410), __byte_perm(v[6], v[7], 0x5410));
        *(uint4*)(g_kvT + (size_t)(c + 2 * e + 1) * KVP + tt) =
          make_uint4(__byte_perm(v[0], v[1], 0x7632), __byte_perm(v[2], v[3], 0x7632), __byte_perm(v[4], v[5], 0x7632), __byte_perm(v[6], v[7], 0x7632));
      }
    }
  } else if (tid < 384) {
    const int t = tid - 288;
    for (int i = t; i < 32 * nch; i += 96) asm volatile("prefetch.global.L2 [%0];" :: "l"(P.Hk + (size_t)chb * SEQ + i * 64));
    for (int i = b * 96 + t; i < 32 * DM; i += N_CTA * 96) ((uint4*)g_oacc)[i] = make_uint4(0, 0, 0, 0);
    if (b * 96 + t < 128 * 8) g_lnflag[b * 96 + t] = 0;
    if (t == 95) sts32(sb + S_GEN, ld_acquire(g_gbar));
  }
  if (warp < 12) {
    bar_arrive(10, 448);
    if (tid == 128) TS(14);
    const int ch = warp >> 1, sub = warp & 1, d = chb + ch;
    const uint32_t su = sb + P_CH + ch * P_CHSZ;
    if (ch < nch) {
      const uint32_t* hs = (const uint32_t*)(P.Hk + (size_t)d * SEQ);
#pragma unroll
      for (int q = sub * 32 + lane; q < 256; q += 64) {
        const uint4 c = __ldg((const uint4*)hs + q);
        const uint32_t prev = q ? __ldg(hs + 4 * q - 1) : 0u;
        sts128(su + P_H + 32 + q * 16, make_uint4(__byte_perm(c.x, prev, 0x7610), __byte_perm(c.y, c.x, 0x7610), __byte_perm(c.z, c.y, 0x7610), __byte_perm(c.w, c.z, 0x7610)));
        sts128(su + P_H + 4224 + q * 16, make_uint4(__byte_perm(c.x, 0, 0x1032), __byte_perm(c.y, 0, 0x1032), __byte_perm(c.z, 0, 0x1032), __byte_perm(c.w, 0, 0x1032)));
      }
      if (sub == 1 && lane == 0) sts32(su + P_CHSZ - 16, __bfloat16_as_ushort(P.Dk[d]) * 0x10001u);
      if (sub == 0 && lane < 20) sts128(su + (lane < 16 ? lane * 16 : P_H + (lane & 2) * 2096 + (lane & 1) * 16), make_uint4(0, 0, 0, 0));
    }
    bar_sync(11, 416);
    if (ch < nch) {
#pragma unroll
      for (int q = sub * 32 + lane; q < 256; q += 64) {
        const int row = (q >> 1) + 8;
        sts128(su + row * 32 + (((q & 1) ^ ((row >> 2) & 1)) << 4), __ldcg((const uint4*)(g_kvT + (size_t)d * KVP) + q));
      }
    }
    const int g = lane >> 2, tq = lane & 3;
    const uint32_t sh = su + P_H + (g & 1) * 4192 + (8 + (g >> 1) - tq) * 4;
    float acc[16][4];
#pragma unroll
    for (int i = 0; i < 16; i++) { acc[i][0] = acc[i][1] = acc[i][2] = acc[i][3] = 0.f; }
    auto u_addr = [&](int res) {
      const int row = 8 - res + ((lane >> 4) << 3) + (lane & 7);
      return su + row * 32 + ((((lane >> 3) & 1) ^ ((row >> 2) & 1)) << 4);
    };
    if (ch < nch) {
      bar_sync(1 + ch, 64);
      if (tid == 0) TS(11);
      if (sub) {
#pragma unroll 4
        for (int res = 0; res < 8; res++) {
          uint32_t b0, b1, b2, b3;
          ldsm4(b0, b1, b2, b3, u_addr(res));
          const uint32_t r0 = lds32(sh + res * 32);
          mma16(acc[0], r0, lds32(sh + res * 32 + 16), lds32(sh + res * 32 - 16), r0, b0, b1);
        }
        conv_store<1>(acc, 0, su, d, lds32(su + P_CHSZ - 16));
      }
    }
    bar_arrive(12, 416);
    if (isg && warp >= 4) { while ((int)(clk() - tstart - S1G) < 0) __nanosleep(200); load_wg(P, sb, true, warp >> 3, warp & 3); }
    if (ch < nch) {
#pragma unroll 1
      for (int res = sub * 4; res < sub * 4 + 4; res++) {
        uint32_t bf[16][2];
        const uint32_t ad = u_addr(res);
#pragma unroll
        for (int f = 0; f < 16; f += 2) ldsm4(bf[f][0], bf[f][1], bf[f + 1][0], bf[f + 1][1], ad + f * 256);
#pragma unroll
        for (int k = 0; k < 16; k++) {
          const int jj = k & 1 ? k >> 1 : 15 - (k >> 1);
          const uint32_t ah = sh + (8 * jj + res) * 32;
          const uint32_t r0 = lds32(ah), r1 = lds32(ah + 16), rm = lds32(ah - 16);
#pragma unroll
          for (int i = max(jj, 1); i < 16; i++) mma16(acc[i], r0, r1, rm, r0, bf[i - jj][0], bf[i - jj][1]);
        }
      }
      bar_sync(1 + ch, 64);
      if (tid == 0) TS(12);
      const uint32_t xb = su + P_H + lane * 16, dd = lds32(su + P_CHSZ - 16);
      conv_fold<16>(acc, sub, xb + sub * 4096, xb + (sub ^ 1) * 4096, 1 + ch, 64);
      conv_store<8>(acc, sub * 8, su, d, dd);
    }
  } else {
    for (int i = b; i < 194 + MRING * 5; i += N_CTA) {
      const int n = (i - 194) / 5, r = (i - 194) % 5, blk = i < 192 ? i / 6 * 8 + i % 6 : i < 194 ? XB_F + i - 192 : XB_M + n * 8 + r;
      const uint32_t fill = i < 194 ? 0u : SENT;
#pragma unroll 1
      for (int q = tid - 384; q < 256 && warp < 15; q += 96) {
        uint4 v = make_uint4(fill, fill, fill, fill);
        if (i >= 194 && (n == 0 || (n <= LAG && ((q ^ (q >> 3)) & 1))) && (r > 0 || q < 128)) {
          const bf16* m = P.mem0 + (max(r * 8 - 4, 0) + (q >> 5)) * 16 + ((q >> 1) & 1) * 8 + ((q >> 2) & 7);
          v.x = pack2(__bfloat162float(m[0]), __bfloat162float(m[DM])); v.y = pack2(__bfloat162float(m[2 * DM]), __bfloat162float(m[3 * DM]));
          v.z = pack2(__bfloat162float(m[4 * DM]), __bfloat162float(m[5 * DM])); v.w = pack2(__bfloat162float(m[6 * DM]), __bfloat162float(m[7 * DM]));
        }
        g_xb[blk * 512 + q] = v;
        g_xb[blk * 512 + 256 + q] = v;
      }
    }
    if (tid < 388) g_xb[XB_REF * 512 + (tid & 2) * 128 + (b & ~1) + (tid & 1)] = make_uint4(0, 0, 0, 0);
    else if (tid < 392 && b < N_GRP) g_xb[(b * 8 + 7) * 512 + (tid & 2) * 128 + (tid & 1)] = make_uint4(0, 0, 0, 0);
    if (warp < 15) { bar_arrive(9, 128); bar_sync(7, 96); }
    if (tid == 384) TS(8);
    if (warp == 12) {
      const bf16* w = lane < 6 ? (lane % 3 == 0 ? P.Wk : lane % 3 == 1 ? P.Wv : P.Wq) + (((b >> 5) * 2 + lane / 3) * 32 + (b & 31)) * 2048
                               : (lane < 8 ? P.Wo + (lane - 6) * (9 * 131072) : P.X) + b * 2048;
      bar_sync(10, 448);
      uint32_t t = clk() + P.dly[19];
#pragma unroll 1
      for (int st = 0; st < 9 && b < N_CHAIN; st++) {
#pragma unroll 1
        for (int i = 0; i < 9; i++, t += PACE) {
          wait_until(t, 0);
          if (lane == st) asm volatile("cp.async.bulk.prefetch.L2.global [%0], 4096;" :: "l"(w + i * (lane < 6 ? 262144 : 131072)) : "memory");
        }
      }
      if (lane == 0) TS(10);
    } else if (warp == 15) {
      bar_sync(10, 448);
      if (lane == 0) { grid_arrive(0); if (nch) grid_wait(0, lds32(sb + S_GEN)); }
      __syncwarp();
      bar_arrive(11, 416);
      if (lane == 0) TS(1);
      bar_sync(9, 128);
      bar_sync(12, 416);
      if (lane == 0) { TS(16); grid_arrive(2); TS(17); }
    } else if (lane == 0) {
      if (warp == 13 || (warp == 14 && b < N_GRP)) {
        uint32_t* p = (uint32_t*)(g_xb + (warp == 13 ? XB_REF * 512 + b : (b * 8 + 7) * 512));
        int votes = 0;
        for (int rep = 0; rep < 24 && abs(votes) < 7; rep++) {
          uint32_t v0, v1, c0, c1;
          asm volatile("atom.relaxed.gpu.global.add.u32 %0, [%4], 0;\n atom.relaxed.gpu.global.add.u32 %1, [%5], 0;\n"
                       "{.reg .pred p; setp.eq.u32 p, %0, 0x7ffffff3; @p trap; mov.u32 %2, %%clock; setp.eq.u32 p, %1, 0x7ffffff3; @p trap; mov.u32 %3, %%clock;}"
                       : "=&r"(v0), "=&r"(v1), "=&r"(c0), "=&r"(c1) : "l"(p + (rep & 1) * 1024), "l"(p + ((rep & 1) ^ 1) * 1024) : "memory");
          votes += ((c1 - c0 > 80u) == (rep & 1)) ? 1 : -1;
        }
        if (warp == 13) { g_side[b] = votes > 0; TS(9); } else g_near[b] = votes > 0;
      }
    }
    __syncwarp();
    if (warp > 12 && b < N_CHAIN) {
      while ((int)(clk() - tstart - S1DLY) < 0) __nanosleep(200);
      for (int k = warp - 13; k < 8; k += 3) load_wg(P, sb, true, 1 - k / 4, k & 3);
    }
  }
  __syncthreads();
  if (tid == 511) { grid_arrive(1); TS(18); }
  if (tid == 0) TS(2);
}

template <int R> __device__ __forceinline__ void ln_tiles(const Params& P, uint32_t sb) {
  const int lane = threadIdx.x & 31, w = (threadIdx.x >> 5) & (16 / R - 1), half = R == 1 ? 0 : threadIdx.x >> 8, u = N_CTA - 1 - bid();
  const int first = R == 1 ? u : 46 - 2 * u + half, step = R == 1 ? 4 : 40, last = R == 1 ? 8 : 128;
  const uint32_t raw = sb + P_CH + half * (18432 + Y_ROWS), mb = sb + T_BAR + (R - 1 + half) * 8;
  const bool lead = w == 16 / R - 1 && lane == 0;
  auto load_y = [&](const bf16* src, int tile) {
    fence_async_global();
    mbar_expect(mb, 18432);
    bulk_load(raw, src + (size_t)tile * 16 * DM, 18432, mb);
  };
  if (R == 2 && u >= N_F && w < 6) load_wg(P, sb, true, w >> 1, half * 2 + (w & 1));
#pragma unroll 1
  for (int tile = first, real = R - 1, ph = 0; tile < last; tile += real * step, real = 1, ph ^= 1) {
    uint32_t x[9 * R], l[9 * R], y[9 * R];
    const bool ts = threadIdx.x == 0 && (R == 1 ? tile == first : u > 3 && tile == first + step);
    if (ts) TS(26);
#pragma unroll
    for (int i = 0; i < 9 * R; i++) x[i] = __ldg((const uint32_t*)(P.X + (size_t)(tile * 16 + w + i / 9 * 8) * DM) + i % 9 * 32 + lane);
    layernorm9<R>(x, l);
    if (tile == first && lead) {
      if (real) grid_wait(3 - R, lds32(sb + S_GEN));
      if (R == 1 || u > 3) TS(13);
      load_y(real ? g_yT : P.Hk, tile);
    }
    bar_sync(13 + half, 512 / R);
    mbar_wait(mb, ph);
    if (ts) TS(28);
    y_rows<R>(y, raw, raw + 18432, w, 13 + half);
    if (ts) TS(29);
    if (lead && real && tile + step < last) { fence_async_smem(); load_y(g_yT, tile + step); }
    __syncwarp();
#pragma unroll
    for (int i = 0; i < 9 * R; i++) x[i] = badd2(x[i], bmul2(l[i], y[i]));
    layernorm9<R>(x, l);
    if (ts && l[0] != 0x12345) TS(30);
#pragma unroll
    for (int r = 0; r < R; r++) store_ln_row(0, tile * 16 + w + r * 8, l + r * 9);
    if (R == 1) {
      __syncthreads();
      if (threadIdx.x == 32 && real) { if (tile < 4) TS(19); st_release(g_lnflag + tile * 8, 1); if (tile < 4) TS(20); }
      __syncwarp();
    }
    if (ts) TS(31);
  }
  if (R == 2) {
    __syncthreads();
    if (threadIdx.x >= 506) {
      asm volatile("fence.acq_rel.gpu;" ::: "memory");
      st_relaxed_if(g_lnflag + ((first ^ (lane & 1)) + (lane - 26) / 2 * step) * 8, 1, true);
    }
    __syncwarp();
    fence_async_smem();
    if (threadIdx.x == 0) TS(15);
  }
}

__global__ void __cluster_dims__(2, 1, 1) __launch_bounds__(512, 1) k_main(const __grid_constant__ Params P) {
  extern __shared__ __align__(1024) unsigned char smem[];
  const uint32_t sb = (uint32_t)__cvta_generic_to_shared(smem);
  const int b = bid(), wg = threadIdx.x >> 7;
  if ((threadIdx.x & 127) == 0) TS(0);
  if (threadIdx.x == 480) {
    if ((sb & 0xFFFFFF) != SBASE) __trap();
    for (int i = 0; i < 6; i++) mbar_init(sb + W_BAR + i * 8, 1);
    if (b < N_CHAIN) {
      mbar_init(sb + CB_FULL, 1); mbar_init(sb + CB_FULL + 8, 1);
      mbar_init(sb + CB_REF, 1);
      mbar_init(sb + CB_SX, 1); mbar_init(sb + CB_OX, 1); mbar_init(sb + CB_XX, 1); mbar_init(sb + CB_Q, 1); mbar_init(sb + CB_VF, 1); mbar_init(sb + CB_VF + 8, 1);
      sts32(sb + C_BAD, 0);
      for (int i = 0; i < 11; i++) mbar_init(sb + CB_M + i * 8, i == 0 ? 5 : i == 5 ? 2 : 1);
    } else if (b < N_CHAIN + N_G) {
      for (int i = 0; i < 9; i++) { mbar_init(sb + G_BAR + i * 8, 2); mbar_init(sb + G_BAR + 128 + i * 8, 8); }
    } else if (b < N_CHAIN + N_G + N_O) {
      for (int i = 0; i < 5; i++) { mbar_init(sb + O_BAR + i * 8, 1); mbar_init(sb + O_BAR + 128 + i * 8, 12); }
      for (int i = 0; i < 6; i++) mbar_init(sb + OB_ST + i * 8, 1);
    } else {
      mbar_init(sb + F_BAR, 1); mbar_init(sb + F_BAR + 8, 1);
    }
    asm volatile("fence.mbarrier_init.release.cluster;" ::: "memory");
    fence_async_smem();
  }
  __syncwarp();
  asm volatile("barrier.cluster.arrive.relaxed.aligned;" ::: "memory");
  prologue(P, sb);
  asm volatile("barrier.cluster.wait.aligned;" ::: "memory");
  fence_async_smem();
  if (b >= 128) ln_tiles<1>(P, sb);
  if (b >= N_CHAIN + N_G) ln_tiles<2>(P, sb);
  if ((threadIdx.x & 127) == 0) TS(3);
  if (b < N_CHAIN) {
    if (wg < 2) { reg_inc<192>(); chain_proj(P, sb); }
    else if (wg == 2) { reg_dec<ATTR>(); chain_attn(P, sb); }
    else { reg_dec<128 - ATTR>(); chain_aux(P, sb); }
  } else if (NOBULK) {
    {
      if (wg == 0) {
        float d[4] = {0.f, 0.f, 0.f, 0.f};
        for (int n = 0; n < STEPS - 1; n++) {
          const uint32_t* f = g_fl + FL_TICK;
          uint32_t x;
          do { for (int k = 0; k < 16; k++) mma16(d, 0, 0, 0, 0, 0, 0); asm volatile("ld.relaxed.gpu.global.u32 %0, [%1];" : "=r"(x) : "l"(f) : "memory"); } while ((x >> 24) <= n);
          const int q = (b - N_CHAIN) * 4 + (threadIdx.x >> 5);
          if (n + 5 >= MRING && q < 80) fill16((uint4*)g_mimg + (uint32_t)(((n + 5) % MRING) * 4096 + q * 32 + (threadIdx.x & 31)), SENT);
        }
        if (d[0] == 1.f) P.out[0] = __float2bfloat16(0.f);
      }
    }
  } else if (b < N_CHAIN + N_G) {
    if (wg == 0) { reg_inc<232>(); g_math<0>(P, sb); }
    else if (wg == 1) { reg_inc<232>(); g_math<1>(P, sb); }
    else if (wg == 2) { reg_dec<24>(); g_aux(P, sb); }
    else { reg_dec<24>(); g_load(P, sb); }
  } else if (b < N_CHAIN + N_G + N_O) {
    if (wg == 0) { reg_inc<160>(); o_math<0>(P, sb); }
    else if (wg == 1) { reg_inc<160>(); o_math<1>(P, sb); }
    else if (wg == 2) { reg_inc<160>(); o_math<2>(P, sb); }
    else { reg_dec<32>(); o_aux(P, sb); }
  } else {
    f_role(P, sb);
  }
}

}

extern "C" void kernel_launch(void* const* d_in, const int* in_sizes, int n_in, void* d_out, int out_size) {
  typedef CUresult (*Encode)(CUtensorMap*, CUtensorMapDataType, cuuint32_t, void*, const cuuint64_t*, const cuuint64_t*, const cuuint32_t*, const cuuint32_t*,
                             CUtensorMapInterleave, CUtensorMapSwizzle, CUtensorMapL2promotion, CUtensorMapFloatOOBfill);
  static Encode encode = nullptr;
  if (!encode) cudaGetDriverEntryPoint("cuTensorMapEncodeTiled", (void**)&encode, cudaEnableDefault);
  Params P;
  for (int i = 0; i < 11; i++) {
    const bool wo = i == 6 || i == 7;
    const cuuint64_t cols = wo ? DM : HD, rows = HD + DM - cols, pitch = cols * 2;
    const cuuint64_t dim[4][5] = {{cols, 2, 8, 2, 18}, {cols, 16, 1, 1, rows / 16}, {cols, 2, 4, 4, rows / 32}, {64, 16, 64, 2, 18}};
    const cuuint64_t stride[4][4] = {{8 * pitch, pitch, 16 * pitch, 32 * pitch}, {pitch, pitch, pitch, 16 * pitch},
                                     {pitch, 8 * pitch, 2 * pitch, 32 * pitch}, {pitch, 128, 16 * pitch, 32 * pitch}};
    const cuuint32_t box[4][5] = {{64, 2, 8, 1, 18}, {64, 16, 1, 1, 1}, {64, 2, 4, 2, 1}, {64, 16, 2, 1, 18}}, one[5] = {1, 1, 1, 1, 1};
    const int k = i < 3 ? 0 : i < 7 ? 1 : i < 8 ? 2 : 3;
    encode(&P.map[i], CU_TENSOR_MAP_DATA_TYPE_BFLOAT16, 5, d_in[wo ? 11 : 8 + (i & 7) % 3], dim[k], stride[k], box[k], one,
           CU_TENSOR_MAP_INTERLEAVE_NONE, CU_TENSOR_MAP_SWIZZLE_128B, CU_TENSOR_MAP_L2_PROMOTION_L2_128B, CU_TENSOR_MAP_FLOAT_OOB_FILL_NONE);
  }
  P.X = (const bf16*)d_in[0]; P.K = (const bf16*)d_in[1]; P.V = (const bf16*)d_in[2];
  P.shift = (const bf16*)d_in[3]; P.Hk = (const bf16*)d_in[4]; P.Dk = (const bf16*)d_in[5];
  P.mem0 = (const bf16*)d_in[7];
  P.Wq = (const bf16*)d_in[8]; P.Wk = (const bf16*)d_in[9]; P.Wv = (const bf16*)d_in[10]; P.Wo = (const bf16*)d_in[11];
  P.out = (bf16*)d_out;
  for (int i = 0; i < 24; i++) P.dly[i] = h_dly[i];
  cudaFuncSetAttribute(k_main, cudaFuncAttributeMaxDynamicSharedMemorySize, SMEM_BYTES);
  k_main<<<N_CTA, 512, SMEM_BYTES>>>(P);
}
```

```cpp
#include <cuda.h>
#include <cuda_runtime.h>
#include <cuda_bf16.h>
#include <stdint.h>

namespace {

typedef __nv_bfloat16 bf16;

constexpr int SEQ = 2048, DM = 576, HD = 4096, NSEG = 64;
#define PLACE 1
#define LAGV 7
constexpr int LAG = LAGV, STEPS = NSEG + LAG, RING = 8;
static_assert(LAG < RING, "ring");
constexpr int N_CHAIN = 64, N_G = 48, N_O = 18, N_F = 2;
constexpr uint32_t SBASE = 1024;
constexpr uint32_t SENT = 0xFFFFFFFFu;
constexpr int SPIN_MAX = 1 << 22;

__device__ __forceinline__ uint32_t bid() {
  const uint32_t b = blockIdx.x;
  return b < 6 ? b + 106 : b < 8 ? b + 122 : b < 114 ? b - 8 : b < 130 ? b - 2 : b;
}
__device__ __forceinline__ uint32_t chain_id() { return blockIdx.x - (PLACE ? 8 : 0); }
constexpr int KVP = SEQ + 64;
__device__ __align__(1024) bf16 g_kvT[DM * KVP];
__device__ __align__(1024) bf16 g_yT[DM * SEQ];
__device__ __align__(1024) unsigned char g_lnimg[2 * NSEG * 9 * 4096];
__device__ __align__(1024) unsigned char g_qkv[RING * N_CHAIN * 24576];
__device__ __align__(1024) unsigned char g_oimg[RING * N_CHAIN * 8192];
constexpr int ARING = 16;
static_assert(ARING >= LAG + 9, "accumulator ring");
__device__ __align__(1024) float g_oacc[ARING * 64 * DM];
constexpr int MRING = LAG + 4, N_GRP = 32 + MRING + 1;
constexpr int XB_M = 256, XB_F = XB_M + MRING * 8, XB_REF = XB_F + 2, N_CTA = N_CHAIN + N_G + N_O + N_F;
__device__ __align__(65536) uint4 g_xb[N_GRP * 4096];
#define g_mimg ((uint32_t*)(g_xb + XB_M * 512))
__device__ uint32_t g_near[N_GRP];
__device__ uint32_t g_side[N_CTA];
__device__ __align__(128) uint32_t g_gbar[3 * 32];
constexpr int FL_G = 0, FL_F = 96 * 8, FL_OCNT = FL_F + 2 * 8, OCRING = 16, FL_TICK = 992, FL_O = 2048, FL_SYNC = FL_O + 128;
static_assert(FL_OCNT + OCRING * 8 <= FL_TICK, "flag block");
#define g_fl ((uint32_t*)(g_xb + XB_F * 512))
__device__ __align__(1024) uint32_t g_lnflag[128 * 8];
#define TS(slot)

#define OTURN 2
#define LOCK0 3
#define FASTG 0
#define NOBULK 0
#define WFENCE 0
#define QPOS 0
#define VE 4
#define OGAP 2
#define NOCHAIN 0
#define BFENCE 2
#define ABL 0
#define ATTR 80
#define CNT(slot, tries)
#define T3(slot)
#define TR(slot)
#define TRV(slot, val)
#define TRD(slot, dep)
#define TRSYNC()
#define TRDUMP(n)
#define CLK(t) "{.reg .b64 x; .reg .b32 h; mov.u64 x, %%clock64; mov.b64 {" t ", h}, x;}"
__device__ __forceinline__ uint32_t clk() { uint32_t t; asm volatile(CLK("%0") : "=r"(t) :: "memory"); return t; }
__device__ __forceinline__ void wait_until(uint32_t t0, uint32_t d) {
  asm volatile("{.reg .pred p; .reg .u32 t;\n"
               "W: " CLK("t") " sub.u32 t, t, %0; setp.lt.s32 p, t, 0; @p bra.uni W;}"
               :: "r"(t0 + d) : "memory");
}
__device__ __forceinline__ uint32_t pack2(float lo, float hi) {
  uint32_t r; asm("cvt.rn.bf16x2.f32 %0, %1, %2;" : "=r"(r) : "f"(hi), "f"(lo)); return r;
}
__device__ __forceinline__ float bf_lo(uint32_t v) { return __uint_as_float(v << 16); }
__device__ __forceinline__ float bf_hi(uint32_t v) { return __uint_as_float(v & 0xFFFF0000u); }

__device__ __forceinline__ uint4 ld_relaxed4(const void* p) {
  uint4 v; asm volatile("ld.relaxed.gpu.global.v4.u32 {%0,%1,%2,%3}, [%4];" : "=r"(v.x), "=r"(v.y), "=r"(v.z), "=r"(v.w) : "l"(p) : "memory"); return v;
}
__device__ __forceinline__ void st_b128(void* p, uint32_t a, uint32_t b, uint32_t c, uint32_t d) {
  asm volatile("{.reg .b128 v; mov.b128 v, {%1,%2,%3,%4}; st.relaxed.gpu.global.b128 [%0], v;}" :: "l"(p), "r"(a), "r"(b), "r"(c), "r"(d) : "memory");
}
__device__ __forceinline__ void reload_b128(uint4& v, const void* p, uint32_t again) {
  asm volatile("{.reg .pred p; .reg .b128 v; setp.ne.u32 p, %5, 0; mov.b128 v, {%0,%1,%2,%3};\n"
               "@p ld.relaxed.gpu.global.b128 v, [%4]; mov.b128 {%0,%1,%2,%3}, v;}"
    : "+r"(v.x), "+r"(v.y), "+r"(v.z), "+r"(v.w) : "l"(p), "r"(again) : "memory");
}
__device__ __forceinline__ void reload4(uint4& v, const void* p, uint32_t again) {
  asm volatile("{.reg .pred p; setp.ne.u32 p, %5, 0; @p ld.relaxed.gpu.global.v4.u32 {%0,%1,%2,%3}, [%4];}"
    : "+r"(v.x), "+r"(v.y), "+r"(v.z), "+r"(v.w) : "l"(p), "r"(again) : "memory");
}
__device__ __forceinline__ void st_relaxed4(void* p, uint32_t a, uint32_t b, uint32_t c, uint32_t d) {
  asm volatile("st.relaxed.gpu.global.v4.u32 [%0], {%1,%2,%3,%4};" :: "l"(p), "r"(a), "r"(b), "r"(c), "r"(d) : "memory");
}
__device__ __forceinline__ void st_relaxed_if(void* p, uint32_t a, bool on) {
  asm volatile("{.reg .pred p; setp.ne.u32 p, %2, 0; @p st.relaxed.gpu.global.u32 [%0], %1;}" :: "l"(p), "r"(a), "r"((uint32_t)on) : "memory");
}
__device__ __forceinline__ uint32_t ld_acquire(const uint32_t* p) {
  uint32_t v; asm volatile("ld.acquire.gpu.global.u32 %0, [%1];" : "=r"(v) : "l"(p) : "memory"); return v;
}
__device__ __forceinline__ void st_release(uint32_t* p, uint32_t v) {
  asm volatile("st.release.gpu.global.u32 [%0], %1;" :: "l"(p), "r"(v) : "memory");
}
__device__ __forceinline__ void bulk_reduce(float* dst, uint32_t src, uint32_t bytes) {
  asm volatile("cp.reduce.async.bulk.global.shared::cta.bulk_group.add.f32 [%0], [%1], %2;" :: "l"(dst), "r"(src), "r"(bytes) : "memory");
}
__device__ __forceinline__ void bulk_done_inc(uint32_t* p) {
  asm volatile("cp.async.bulk.wait_group 0;\n"
               "fence.proxy.async.global;\nfence.release.gpu;\n"
               "red.relaxed.gpu.global.add.u32 [%0], 1;\nred.relaxed.gpu.global.add.u32 [%0+4096], 1;" :: "l"(p) : "memory");
}
__device__ __forceinline__ void flag_release(uint32_t* p, uint32_t v) {
  asm volatile("fence.release.gpu;\nst.relaxed.gpu.global.u32 [%0], %1;\nst.relaxed.gpu.global.u32 [%0+4096], %1;" :: "l"(p), "r"(v) : "memory");
}
__device__ __forceinline__ void spin_guard(int& it) {
  asm volatile("{.reg .pred p; add.s32 %0, %0, 1; setp.gt.s32 p, %0, %1; @p trap;}" : "+r"(it) : "n"(SPIN_MAX));
}
__device__ __forceinline__ void wait_flag(const uint32_t* p, uint32_t v) {
  int it = 0;
  while (ld_acquire(p) < v) spin_guard(it);
}
__device__ __forceinline__ void wait_flags(const uint32_t* p, uint32_t v) {
  int it = 0;
  while (true) {
    uint32_t x; asm volatile("ld.relaxed.gpu.global.u32 %0, [%1];" : "=r"(x) : "l"(p) : "memory");
    if (__all_sync(~0u, x >= v)) break;
    spin_guard(it);
  }
  asm volatile("fence.acquire.gpu;" ::: "memory");
}
__device__ __forceinline__ uint32_t timer_offset() {
  uint32_t g0, g;
  asm volatile("mov.u32 %0, %%globaltimer_lo;" : "=r"(g0) :: "memory");
  do { asm volatile("mov.u32 %0, %%globaltimer_lo;" : "=r"(g) :: "memory"); } while (g == g0);
  return (g >> 5) * 58 - clk();
}
__device__ __forceinline__ void grid_arrive(int i) {
  asm volatile("red.release.gpu.global.add.u32 [%0], %1;" :: "l"(g_gbar + i * 32), "r"(bid() ? 1u : 257u - N_CTA) : "memory");
}
__device__ __forceinline__ void grid_wait(int i, uint32_t gen) {
  int it = 0;
  while (((ld_acquire(g_gbar + i * 32) ^ gen) >> 8) == 0) spin_guard(it);
}
__device__ __forceinline__ bool elect() {
  uint32_t r; asm volatile("{.reg .pred p; elect.sync _|p, -1; selp.u32 %0, 1, 0, p;}" : "=r"(r)); return r;
}
__device__ __forceinline__ void bar_sync(int id, int cnt) { asm volatile("bar.sync %0, %1;" :: "r"(id), "r"(cnt) : "memory"); }
__device__ __forceinline__ void bar_arrive(int id, int cnt) { asm volatile("bar.arrive %0, %1;" :: "r"(id), "r"(cnt) : "memory"); }
template <int id, int cnt> __device__ __forceinline__ void bar_arrive_after(uint32_t a, uint32_t b) {
  asm volatile("{.reg .pred p; setp.ne.u32 p, %2, 0xfff12345; setp.ne.and.u32 p, %3, 0xfff12345, p; @p bar.arrive %0, %1;}" :: "n"(id), "n"(cnt), "r"(a), "r"(b) : "memory");
}
template <int id, int cnt> __device__ __forceinline__ void bar_sync_after(uint32_t a) {
  asm volatile("{.reg .pred p; setp.ne.u32 p, %2, 0xfff12345; @p bar.sync %0, %1;}" :: "n"(id), "n"(cnt), "r"(a) : "memory");
}
__device__ __forceinline__ void fence_async_smem() { asm volatile("fence.proxy.async.shared::cta;" ::: "memory"); }
__device__ __forceinline__ void fence_async_global() { asm volatile("fence.proxy.async.global;" ::: "memory"); }
__device__ __forceinline__ void mbar_init(uint32_t mb, int cnt) { asm volatile("mbarrier.init.shared::cta.b64 [%0], %1;" :: "r"(mb), "r"(cnt) : "memory"); }
__device__ __forceinline__ void mbar_arrive(uint32_t mb) { asm volatile("mbarrier.arrive.shared::cta.b64 _, [%0];" :: "r"(mb) : "memory"); }
__device__ __forceinline__ void mbar_arrive_after(uint32_t mb, uint32_t a, uint32_t lane) {
  asm volatile("{.reg .pred p; setp.ne.u32 p, %1, 0xfff12345; setp.eq.and.u32 p, %2, 0, p; @p mbarrier.arrive.shared::cta.b64 _, [%0];}" :: "r"(mb), "r"(a), "r"(lane) : "memory");
}
__device__ __forceinline__ void mbar_expect(uint32_t mb, uint32_t bytes) {
  asm volatile("mbarrier.arrive.expect_tx.shared::cta.b64 _, [%0], %1;" :: "r"(mb), "r"(bytes) : "memory");
}
__device__ __forceinline__ void mbar_wait_guard(uint32_t mb, uint32_t parity) {
  uint32_t ok; int it = 0;
  while (true) {
    asm volatile("{.reg .pred p; mbarrier.try_wait.parity.shared::cta.b64 p, [%1], %2; selp.u32 %0, 1, 0, p;}" : "=r"(ok) : "r"(mb), "r"(parity) : "memory");
    if (ok) break;
    spin_guard(it);
  }
}
__device__ __forceinline__ void mbar_wait(uint32_t mb, uint32_t parity) {
  asm volatile("{.reg .pred p;\nW: mbarrier.try_wait.parity.shared::cta.b64 p, [%0], %1;\n@!p bra W;}" :: "r"(mb), "r"(parity) : "memory");
}
__device__ __forceinline__ void bulk_load(uint32_t dst, const void* src, uint32_t bytes, uint32_t mb) {
  asm volatile("cp.async.bulk.shared::cluster.global.mbarrier::complete_tx::bytes [%0], [%1], %2, [%3];" :: "r"(dst), "l"(src), "r"(bytes), "r"(mb) : "memory");
}
__device__ __forceinline__ void bulk_store(void* dst, uint32_t src, uint32_t bytes) {
  asm volatile("cp.async.bulk.global.shared::cta.bulk_group [%0], [%1], %2;" :: "l"(dst), "r"(src), "r"(bytes) : "memory");
}
__device__ __forceinline__ void cp_async16(uint32_t dst, const void* src) {
  asm volatile("cp.async.cg.shared.global [%0], [%1], 16;" :: "r"(dst), "l"(src) : "memory");
}
__device__ __forceinline__ void cp_async_wait_all() { asm volatile("cp.async.wait_all;" ::: "memory"); }
__device__ __forceinline__ uint32_t mapa(uint32_t a, uint32_t rank) {
  uint32_t r; asm("mapa.shared::cluster.u32 %0, %1, %2;" : "=r"(r) : "r"(a), "r"(rank)); return r;
}
__device__ __forceinline__ void st_async4(uint32_t dst, float a, float b, float c, float d, uint32_t mb) {
  asm volatile("st.async.shared::cluster.mbarrier::complete_tx::bytes.v4.f32 [%0], {%1,%2,%3,%4}, [%5];" :: "r"(dst), "f"(a), "f"(b), "f"(c), "f"(d), "r"(mb) : "memory");
}
__device__ __forceinline__ void st_async2(uint32_t dst, float a, float b, uint32_t mb) {
  asm volatile("st.async.shared::cluster.mbarrier::complete_tx::bytes.v2.f32 [%0], {%1,%2}, [%3];" :: "r"(dst), "f"(a), "f"(b), "r"(mb) : "memory");
}
__device__ __forceinline__ void st_async1(uint32_t dst, uint32_t a, uint32_t mb) {
  asm volatile("st.async.shared::cluster.mbarrier::complete_tx::bytes.u32 [%0], %1, [%2];" :: "r"(dst), "r"(a), "r"(mb) : "memory");
}
__device__ __forceinline__ uint4 lds128(uint32_t a) {
  uint4 v; asm volatile("ld.shared.v4.u32 {%0,%1,%2,%3}, [%4];" : "=r"(v.x), "=r"(v.y), "=r"(v.z), "=r"(v.w) : "r"(a) : "memory"); return v;
}
__device__ __forceinline__ uint2 lds64(uint32_t a) {
  uint2 v; asm volatile("ld.shared.v2.u32 {%0,%1}, [%2];" : "=r"(v.x), "=r"(v.y) : "r"(a) : "memory"); return v;
}
__device__ __forceinline__ uint32_t lds32(uint32_t a) {
  uint32_t v; asm volatile("ld.shared.u32 %0, [%1];" : "=r"(v) : "r"(a) : "memory"); return v;
}
__device__ __forceinline__ void sts128(uint32_t a, uint4 v) {
  asm volatile("st.shared.v4.u32 [%0], {%1,%2,%3,%4};" :: "r"(a), "r"(v.x), "r"(v.y), "r"(v.z), "r"(v.w) : "memory");
}
__device__ __forceinline__ void sts64(uint32_t a, uint32_t x, uint32_t y) {
  asm volatile("st.shared.v2.u32 [%0], {%1,%2};" :: "r"(a), "r"(x), "r"(y) : "memory");
}
__device__ __forceinline__ void sts32(uint32_t a, uint32_t x) { asm volatile("st.shared.u32 [%0], %1;" :: "r"(a), "r"(x) : "memory"); }
__device__ __forceinline__ void ldsm4(uint32_t& r0, uint32_t& r1, uint32_t& r2, uint32_t& r3, uint32_t a) {
  asm volatile("ldmatrix.sync.aligned.m8n8.x4.shared.b16 {%0,%1,%2,%3}, [%4];" : "=r"(r0), "=r"(r1), "=r"(r2), "=r"(r3) : "r"(a) : "memory");
}
__device__ __forceinline__ void ldsm4t(uint32_t& r0, uint32_t& r1, uint32_t& r2, uint32_t& r3, uint32_t a) {
  asm volatile("ldmatrix.sync.aligned.m8n8.x4.trans.shared.b16 {%0,%1,%2,%3}, [%4];" : "=r"(r0), "=r"(r1), "=r"(r2), "=r"(r3) : "r"(a) : "memory");
}
__device__ __forceinline__ void stsm4(uint32_t a, uint32_t r0, uint32_t r1, uint32_t r2, uint32_t r3) {
  asm volatile("stmatrix.sync.aligned.m8n8.x4.shared.b16 [%0], {%1,%2,%3,%4};" :: "r"(a), "r"(r0), "r"(r1), "r"(r2), "r"(r3) : "memory");
}
__device__ __forceinline__ uint32_t movmat(uint32_t a) {
  uint32_t d; asm volatile("movmatrix.sync.aligned.m8n8.trans.b16 %0, %1;" : "=r"(d) : "r"(a)); return d;
}
__device__ __forceinline__ void mma16(float* d, uint32_t a0, uint32_t a1, uint32_t a2, uint32_t a3, uint32_t b0, uint32_t b1) {
  asm volatile("mma.sync.aligned.m16n8k16.row.col.f32.bf16.bf16.f32 {%0,%1,%2,%3}, {%4,%5,%6,%7}, {%8,%9}, {%0,%1,%2,%3};"
    : "+f"(d[0]), "+f"(d[1]), "+f"(d[2]), "+f"(d[3]) : "r"(a0), "r"(a1), "r"(a2), "r"(a3), "r"(b0), "r"(b1));
}
__device__ __forceinline__ void mma8(float* d, uint32_t a0, uint32_t a1, uint32_t b0) {
  asm volatile("mma.sync.aligned.m16n8k8.row.col.f32.bf16.bf16.f32 {%0,%1,%2,%3}, {%4,%5}, {%6}, {%0,%1,%2,%3};"
    : "+f"(d[0]), "+f"(d[1]), "+f"(d[2]), "+f"(d[3]) : "r"(a0), "r"(a1), "r"(b0));
}
__device__ __forceinline__ float rcp(float x) { float r; asm("rcp.approx.ftz.f32 %0, %1;" : "=f"(r) : "f"(x)); return r; }
__device__ __forceinline__ float ex2(float x) { float r; asm("ex2.approx.ftz.f32 %0, %1;" : "=f"(r) : "f"(x)); return r; }

__host__ __device__ constexpr uint64_t mkdesc(uint32_t off, uint32_t lbo, uint32_t sbo, uint32_t swz) {
  return (uint64_t)((SBASE + off) >> 4) | ((uint64_t)(lbo >> 4) << 16) | ((uint64_t)(sbo >> 4) << 32) | ((uint64_t)swz << 62);
}
__host__ __device__ constexpr uint64_t desc_sw128(uint32_t off) { return mkdesc(off, 16, 1024, 1); }
__host__ __device__ constexpr uint64_t desc_n16(uint32_t off) { return mkdesc(off, 256, 128, 0); }
__host__ __device__ constexpr uint64_t desc_m(uint32_t off) { return mkdesc(off, 16, 256, 3); }

__host__ __device__ constexpr uint64_t desc_sw64(uint32_t off) { return mkdesc(off, 16, 512, 2); }

__device__ __forceinline__ void wg_fence() { asm volatile("wgmma.fence.sync.aligned;" ::: "memory"); }
__device__ __forceinline__ void wg_commit() { asm volatile("wgmma.commit_group.sync.aligned;" ::: "memory"); }
template <int N> __device__ __forceinline__ void wg_wait() { asm volatile("wgmma.wait_group.sync.aligned %0;" :: "n"(N) : "memory"); }

#define ACC8(d) "+f"(d[0]), "+f"(d[1]), "+f"(d[2]), "+f"(d[3]), "+f"(d[4]), "+f"(d[5]), "+f"(d[6]), "+f"(d[7])
#define ACC32(d) ACC8(d), ACC8((d + 8)), ACC8((d + 16)), ACC8((d + 24))
#define R8 "{%0,%1,%2,%3,%4,%5,%6,%7}"
#define R32 "{%0,%1,%2,%3,%4,%5,%6,%7,%8,%9,%10,%11,%12,%13,%14,%15,%16,%17,%18,%19,%20,%21,%22,%23,%24,%25,%26,%27,%28,%29,%30,%31}"
template <int SD> __device__ __forceinline__ void wg_rs16(float* d, const uint32_t* a, uint64_t db) {
  asm volatile("wgmma.mma_async.sync.aligned.m64n16k16.f32.bf16.bf16 " R8 ", {%8,%9,%10,%11}, %12, %13, 1, 1, 1;"
    : ACC8(d) : "r"(a[0]), "r"(a[1]), "r"(a[2]), "r"(a[3]), "l"(db), "n"(SD));
}
template <int SD> __device__ __forceinline__ void wg_ss16(float* d, uint64_t da, uint64_t db) {
  asm volatile("wgmma.mma_async.sync.aligned.m64n16k16.f32.bf16.bf16 " R8 ", %8, %9, %10, 1, 1, 1, 1;"
    : ACC8(d) : "l"(da), "l"(db), "n"(SD));
}
template <int SD, uint64_t DA, uint64_t DB> __device__ __forceinline__ void wg_ss16o(float* d, uint32_t oa, uint32_t ob) {
  asm volatile("{.reg .b32 x, y; .reg .b64 a, b; add.u32 x, %8, %10; add.u32 y, %9, %12; mov.b64 a, {x, %11}; mov.b64 b, {y, %13};\n"
               "wgmma.mma_async.sync.aligned.m64n16k16.f32.bf16.bf16 " R8 ", a, b, %14, 1, 1, 1, 1;}"
    : ACC8(d) : "r"(oa), "r"(ob), "n"((uint32_t)DA), "n"((uint32_t)(DA >> 32)), "n"((uint32_t)DB), "n"((uint32_t)(DB >> 32)), "n"(SD));
}
template <int SD> __device__ __forceinline__ void wg_rs64(float* d, const uint32_t* a, uint64_t db) {
  asm volatile("wgmma.mma_async.sync.aligned.m64n64k16.f32.bf16.bf16 " R32 ", {%32,%33,%34,%35}, %36, %37, 1, 1, 0;"
    : ACC32(d) : "r"(a[0]), "r"(a[1]), "r"(a[2]), "r"(a[3]), "l"(db), "n"(SD));
}
template <int SD> __device__ __forceinline__ void wg_ss64(float* d, uint64_t da, uint64_t db) {
  asm volatile("wgmma.mma_async.sync.aligned.m64n64k16.f32.bf16.bf16 " R32 ", %32, %33, %34, 1, 1, 1, 0;"
    : ACC32(d) : "l"(da), "l"(db), "n"(SD));
}
#define WG_RSO(NAME, SHAPE, REGS, ACC, A, TB) \
template <int SD, uint64_t DB> __device__ __forceinline__ void NAME(float* d, uint32_t a0, uint32_t a1, uint32_t a2, uint32_t a3, uint32_t ob) { \
  asm volatile("{.reg .b64 b; mov.b64 b, {" A(4) ", " A(5) "};\nwgmma.mma_async.sync.aligned." SHAPE ".f32.bf16.bf16 " REGS \
               ", {" A(0) "," A(1) "," A(2) "," A(3) "}, b, " A(6) ", 1, 1, " TB ";}" \
    : ACC(d) : "r"(a0), "r"(a1), "r"(a2), "r"(a3), "r"(ob + (uint32_t)DB), "n"((uint32_t)(DB >> 32)), "n"(SD)); \
}
#define ACC4(d) "+f"(d[0]), "+f"(d[1]), "+f"(d[2]), "+f"(d[3])
#define ACC16(d) ACC8(d), ACC8((d + 8))
#define OP4(i) OP4_##i
#define OP4_0 "%4"
#define OP4_1 "%5"
#define OP4_2 "%6"
#define OP4_3 "%7"
#define OP4_4 "%8"
#define OP4_5 "%9"
#define OP4_6 "%10"
#define OP16(i) OP16_##i
#define OP16_0 "%16"
#define OP16_1 "%17"
#define OP16_2 "%18"
#define OP16_3 "%19"
#define OP16_4 "%20"
#define OP16_5 "%21"
#define OP16_6 "%22"
#define OP32(i) OP32_##i
#define OP32_0 "%32"
#define OP32_1 "%33"
#define OP32_2 "%34"
#define OP32_3 "%35"
#define OP32_4 "%36"
#define OP32_5 "%37"
#define OP32_6 "%38"
WG_RSO(wg_rs8o, "m64n8k16", "{%0,%1,%2,%3}", ACC4, OP4, "1")
#define R16 "{%0,%1,%2,%3,%4,%5,%6,%7,%8,%9,%10,%11,%12,%13,%14,%15}"
WG_RSO(wg_rs32o, "m64n32k16", R16, ACC16, OP16, "1")
WG_RSO(wg_rs64o, "m64n64k16", R32, ACC32, OP32, "0")
WG_RSO(wg_rs32k, "m64n32k16", R16, ACC16, OP16, "0")
template <uint64_t DA, uint64_t DB> __device__ __forceinline__ void wg_ss32k(float* d, uint32_t ob) {
  asm volatile("{.reg .b64 b; mov.b64 b, {%17, %18};\nwgmma.mma_async.sync.aligned.m64n32k16.f32.bf16.bf16 " R16 ", %16, b, 1, 1, 1, 1, 0;}"
    : ACC16(d) : "l"(DA), "r"(ob + (uint32_t)DB), "n"((uint32_t)(DB >> 32)));
}
template <int N> __device__ __forceinline__ void reg_inc() { asm volatile("setmaxnreg.inc.sync.aligned.u32 %0;" :: "n"(N)); }
template <int N> __device__ __forceinline__ void reg_dec() { asm volatile("setmaxnreg.dec.sync.aligned.u32 %0;" :: "n"(N)); }
__device__ __forceinline__ void cluster_sync() {
  asm volatile("barrier.cluster.arrive.relaxed.aligned;\nbarrier.cluster.wait.aligned;" ::: "memory");
}

template <int KS>
__device__ __forceinline__ void load_frags(uint32_t* a, uint32_t src) {
  const int lane = threadIdx.x & 31, w = (threadIdx.x >> 5) & 3;
  const int k = ((lane >> 4) << 3) + (lane & 7), u = w * 2 + ((lane >> 3) & 1);
  const uint32_t base = src + k * 128 + ((u ^ (k & 7)) << 4);
#pragma unroll
  for (int ks = 0; ks < KS; ks++) ldsm4t(a[ks * 4], a[ks * 4 + 1], a[ks * 4 + 2], a[ks * 4 + 3], base + ks * 2048);
}

__device__ __forceinline__ uint32_t badd2(uint32_t a, uint32_t b) { uint32_t r; asm("add.rn.bf16x2 %0, %1, %2;" : "=r"(r) : "r"(a), "r"(b)); return r; }
__device__ __forceinline__ uint32_t bsub2(uint32_t a, uint32_t b) { uint32_t r; asm("sub.rn.bf16x2 %0, %1, %2;" : "=r"(r) : "r"(a), "r"(b)); return r; }
__device__ __forceinline__ uint32_t bmul2(uint32_t a, uint32_t b) { uint32_t r; asm("mul.rn.bf16x2 %0, %1, %2;" : "=r"(r) : "r"(a), "r"(b)); return r; }
__device__ __forceinline__ uint32_t bfma2(uint32_t a, uint32_t b, uint32_t c) { uint32_t r; asm("fma.rn.bf16x2 %0, %1, %2, %3;" : "=r"(r) : "r"(a), "r"(b), "r"(c)); return r; }
template <int R> __device__ __forceinline__ void layernorm9(const uint32_t* x, uint32_t* o) {
  const uint32_t ones = 0x3F803F80u;
  float a[R][3][4], q[R], s[R];
#pragma unroll
  for (int i = 0; i < 9 * R; i++) {
    float* d = a[i % R][i / R % 3];
    if (i < 3 * R) d[0] = d[1] = d[2] = d[3] = 0.f;
    mma8(d, x[i % R * 9 + i / R], ones, x[i % R * 9 + i / R]);
  }
#pragma unroll
  for (int r = 0; r < R; r++) {
    q[r] = threadIdx.x & 4 ? a[r][0][1] + a[r][1][1] + a[r][2][1] : a[r][0][0] + a[r][1][0] + a[r][2][0];
    s[r] = (a[r][0][2] + a[r][0][3]) + (a[r][1][2] + a[r][1][3]) + (a[r][2][2] + a[r][2][3]);
  }
#pragma unroll
  for (int r = 0; r < R; r++) { q[r] += __shfl_xor_sync(~0u, q[r], 4); s[r] += __shfl_xor_sync(~0u, s[r], 1); }
#pragma unroll
  for (int r = 0; r < R; r++) { q[r] += __shfl_xor_sync(~0u, q[r], 9); s[r] += __shfl_xor_sync(~0u, s[r], 2); }
#pragma unroll
  for (int r = 0; r < R; r++) q[r] = __shfl_sync(~0u, q[r], 0) + __shfl_sync(~0u, q[r], 18);
#pragma unroll
  for (int r = 0; r < R; r++) {
    const float mean = s[r] * (1.f / DM), var = fmaxf(fmaf(q[r], 1.f / DM, -mean * mean), 0.f);
    float sd;
    asm("sqrt.approx.ftz.f32 %0, %1;" : "=f"(sd) : "f"(bf_lo(pack2(bf_lo(pack2(var, 0.f)) + 1e-5f, 0.f))));
    const float inv = rcp(bf_lo(pack2(sd, 0.f)));
    const uint32_t mb = pack2(mean, mean), hi = pack2(inv, inv), lo = pack2(inv - bf_lo(hi), inv - bf_lo(hi));
#pragma unroll
    for (int i = r * 9; i < r * 9 + 9; i++) {
      const uint32_t d = bsub2(x[i], mb);
      o[i] = bfma2(d, hi, bmul2(d, lo));
    }
  }
}
__device__ __forceinline__ void store_ln_row(int layer, int tok, const uint32_t* o) {
  const int lane = threadIdx.x & 31, r = tok & 31;
  unsigned char* p = g_lnimg + (size_t)(layer * NSEG + (tok >> 5)) * (9 * 4096) + r * 128 + (((lane >> 2) ^ (r & 7)) << 4) + (lane & 3) * 4;
#pragma unroll
  for (int i = 0; i < 9; i++) *(uint32_t*)(p + i * 4096) = o[i];
}
struct Params { CUtensorMap map[11]; const bf16 *X, *K, *V, *shift, *Hk, *Dk, *mem0, *Wq, *Wk, *Wv, *Wo; bf16* out; uint32_t dly[24]; };
#define PACE P.dly[20]
#define S1G P.dly[21]
#define S1DLY P.dly[22]
#define DLYS P.dly[0]
#define DLYW P.dly[1]
#define KLATE P.dly[2]
#define DLYQ P.dly[3]
#define DLYK P.dly[4]
#define DLYG P.dly[5]
#define KWIN P.dly[6]
#define KMIN P.dly[7]
uint32_t h_dly[24] = {900, 150, 100, 40, 3650, 4900, 1750, 300, 1740, 1840, 1900, 2230, 2340, 2430, 3080, 3170, 3380, 3460, 3580, 0, 180, 12000, 16000};

constexpr uint32_t C_W = 0, C_M = 147456, C_KV = C_M + 18432, C_QM = C_KV + 32768, C_KM = C_QM + 2048,
                   C_VM = C_KM + 2048, C_OI = C_VM + 2048, C_SX = C_OI + 4096, C_KM2 = C_SX + 2560, C_VM2 = C_KM2 + 128,
                   C_KV2 = C_KM2 + 2048, C_Q = C_KV2 + 8192, C_BAR = C_Q + 8192;
constexpr uint32_t CB_FULL = C_BAR, CB_REF = C_BAR + 16, CB_SX = C_BAR + 32, CB_OX = C_BAR + 40, CB_XX = C_BAR + 48, CB_Q = C_BAR + 56, C_BAD = C_BAR + 64, W_BAR = C_BAR + 80, T_BAR = W_BAR + 24, S_GEN = C_BAR + 128, C_REF = C_BAR + 132, CB_VF = C_BAR + 144, CB_M = C_BAR + 160, CB_MV = C_BAR + 200;
constexpr uint32_t G_W = 0, G_RING = 147456, G_W2 = G_RING + 9 * 8192, G_BAR = G_W2 + 8192;
constexpr uint32_t O_W = 0, O_RING = 3 * 40960, O_ST = O_RING + 11 * 8192, O_BAR = O_ST + 16384, OB_ST = O_BAR + 64;
constexpr uint32_t F_A = 0, F_XY = 36864, F_L = F_XY + 36864, F_X = F_L + 18432, F_Y = F_L + 2 * 36864, F_BAR = C_BAR;
constexpr uint32_t SMEM_BYTES = C_BAR + 256;
static_assert(G_BAR + 256 <= SMEM_BYTES && O_BAR + 256 <= SMEM_BYTES && F_BAR + 16 <= SMEM_BYTES && SMEM_BYTES <= 232448, "smem map");
enum { B_INIT = 1, B_M, B_QK, B_S, B_V, B_O, B_X, B_WG0, B_WG1, B_WG2, B_G, B_OE, B_T, B_R };

__device__ __forceinline__ uint4 pack_partial(const float* d, uint32_t tag) {
  uint32_t x;
  asm("lop3.b32 %0, %1, 1, %2, 0xb8;" : "=r"(x) : "r"(pack2(d[0], d[1])), "r"(tag));
  return make_uint4(x, pack2(d[4], d[5]), pack2(d[2], d[3]), pack2(d[6], d[7]));
}
__device__ __forceinline__ void store_partial(uint4* p, const uint4& v) { st_b128(p, v.x, v.y, v.z, v.w); }
__device__ __forceinline__ void gather_reduce(const uint32_t* p, uint32_t* dst, bool shared, uint32_t tag, uint32_t lane, uint32_t sb, int n, int TS0) {
  int tries = 0;
  float u, v;
  bool bad;
  TR(TS0);
  do {
    uint32_t x[16];
#pragma unroll
    for (int i = 0; i < 16; i++) asm volatile("ld.relaxed.gpu.global.u32 %0, [%1];" : "=r"(x[i]) : "l"(p + i * 64) : "memory");
    tries++;
    float a[2] = {bf_lo(x[0]), bf_lo(x[1])}, b[2] = {bf_hi(x[0]), bf_hi(x[1])};
    uint32_t t = 0;
#pragma unroll
    for (int i = 2; i < 16; i++) { a[i & 1] += bf_lo(x[i]); b[i & 1] += bf_hi(x[i]); }
#pragma unroll
    for (int i = 0; i < 16; i += 4)
      asm("{.reg .b32 y, z; lop3.b32 y, %1, %2, %5, 0x7e; lop3.b32 z, %3, %4, %5, 0x7e; lop3.b32 %0, %0, y, z, 0xfe;}"
          : "+r"(t) : "r"(x[i]), "r"(x[i + 1]), "r"(x[i + 2]), "r"(x[i + 3]), "r"(tag));
    u = a[0] + a[1]; v = b[0] + b[1];
    bad = __any_sync(~0u, (t & 1) && !(lane & 3));
    if (shared) { u += __shfl_xor_sync(~0u, u, 8); v += __shfl_xor_sync(~0u, v, 8); }
    u += __shfl_xor_sync(~0u, u, 16);
    v += __shfl_xor_sync(~0u, v, 16);
    st_relaxed_if(dst, pack2(u, v), !bad && (n >= LAG || !(lane & 1)));
  } while (bad);
  TR(TS0 + 3); TRV(TS0 + 2, tries);
  CNT((TS0 - 16) >> 2, tries);
}
__device__ __forceinline__ uint32_t sent_bad(const uint4& v) { return max(max(v.x, v.y), max(v.z, v.w)) == SENT; }

__host__ __device__ constexpr int o_ks(int s) { return s & (s < 8 ? 3 : 7); }
__host__ __device__ constexpr bool o_reg(int s) { return s < 8 ? (s & 3) != 3 : !(s & 1); }
__host__ __device__ constexpr int o_slot(int s) { return s < 8 ? (o_reg(s) ? s - (s >> 2) : s >> 2) : s & 1 ? (s - 5) >> 1 : (s + 4) >> 1; }
__device__ __forceinline__ int g_unit(int wg) {
  const int i = bid() - N_CHAIN;
  return i < 32 ? wg * 64 + i : 2 * i - 32 + wg;
}
__device__ __forceinline__ void load_box(const Params& P, uint32_t sb, bool regs, int wg, int i, uint32_t mb) {
  const int b = bid();
  int map, col = 0, ks = 0, c2 = 0, c3 = 0;
  uint32_t dst = wg * 73728;
  if (b < N_CHAIN) {
    const int k = i - 1, st = regs ? (k < 6 ? k + k / 3 : 2 * k - 4) : k < 2 ? 4 * k + 3 : 2 * k + 5;
    dst += i ? (17 + i) * 2048 : 0;
    if (wg || i == 0) { map = wg + i; col = b * 64; c3 = !regs; }
    else if (!regs && k >= 14) { map = 6; ks = b * 4 + k - 14; }
    else { map = 6; col = 64 + (st < 8 ? (st >> 2) * 64 : (st >> 3) * 128 + (b & 1) * 64); ks = (b * 4) ^ o_ks(st); }
  } else if (b < N_CHAIN + N_G) {
    const int q = g_unit(wg);
    map = ((q >> 5) + 1) % 3;
    if (i) { map += 3; col = (q & 31) * 128 + (i - 1) * 64; ks = 34; dst = G_W2 + wg * 4096 + (i - 1) * 2048; }
    else { map += 8; c2 = (q & 31) * 2; c3 = !regs; }
  } else {
    const int o = b - N_CHAIN - N_G, ksl = o / 3;
    map = 7; col = ((o % 3) * 3 + (wg + ksl) % 3) * 64; dst = (wg * (regs ? 24 : 20) + i) * 2048;
    ks = (ksl * 11 - max(ksl - 4, 0)) * 4 + (regs ? i / 3 * 5 + i % 3 * 2 : i < 16 ? i / 2 * 5 + 1 + i % 2 * 2 : i + 24);
    c3 = (ks & 1) * 2; ks >>= 1;
  }
  asm volatile("cp.async.bulk.tensor.5d.shared::cluster.global.tile.mbarrier::complete_tx::bytes [%0], [%1, {%2, %3, %4, %5, %6}], [%7];"
               :: "r"(sb + dst), "l"(&P.map[map]), "r"(col), "r"(0), "r"(c2), "r"(c3), "r"(ks), "r"(mb) : "memory");
}
__device__ __forceinline__ void load_wg(const Params& P, uint32_t sb, bool regs, int wg, int quarter) {
  const int b = bid(), i = (threadIdx.x & 31) * 4 + quarter;
  const int n = b < N_CHAIN ? 36 : b < N_CHAIN + N_G ? (regs ? 38 : 36) : regs ? 24 : b < N_CHAIN + N_G + 12 ? 20 : 16;
  if (i == 0) mbar_expect(sb + W_BAR + wg * 8, n * 2048);
  if (i < (b < N_CHAIN ? (wg ? 2 : 19) : b < N_CHAIN + N_G ? n - 35 : n)) load_box(P, sb, regs, wg, i, sb + W_BAR + wg * 8);
  __syncwarp();
}
__device__ __forceinline__ uint32_t near_half(uint32_t blk, uint32_t reader) {
  return __ldcg(g_near + (blk >> 3)) ^ (~blk & 1) ^ __ldcg(g_side + (blk >> 3)) ^ __ldcg(g_side + reader);
}

__device__ __forceinline__ uint32_t opaque_tid() { uint32_t t; asm volatile("mov.u32 %0, %%tid.x;" : "=r"(t)); return t; }
__device__ __forceinline__ void m_fetch(uint32_t sb, uint32_t src, uint32_t b, uint32_t mb) {
  bulk_load(sb + C_M + (b ? b * 4096 - 2048 : 0), (const unsigned char*)g_mimg + ((src ^ ((b & 1) * 4096)) + b * 8192), b ? 4096 : 2048, mb);
}
__device__ __forceinline__ uint32_t pinned(uint32_t v) { return __shfl_sync(~0u, v, threadIdx.x & 31); }
template <class T> __device__ __forceinline__ T* pinned(T* p) { return (T*)__shfl_sync(~0u, (unsigned long long)p, threadIdx.x & 31); }
__device__ __forceinline__ uint32_t m_probe(uint32_t lane) { return lane * 32 + (lane & 4) * 4 + (lane >> 3) * 4; }
__device__ __forceinline__ uint32_t m_max(uint32_t a, uint32_t b) {
  return max(max(lds32(a), lds32(a + 1024)), max(lds32(b), lds32(b + 1024)));
}
template <int S0, int N> __device__ __forceinline__ void o_steps(float* d, const uint32_t* a) {
  constexpr int SD = o_ks(S0) != 0;
  if constexpr (o_reg(S0)) wg_rs16<SD>(d, a + (18 + o_slot(S0)) * 4, desc_n16(C_OI + o_ks(S0) * 512));
  else wg_ss16<SD>(d, desc_sw128(C_W + (18 + o_slot(S0)) * 2048), desc_n16(C_OI + o_ks(S0) * 512));
  if constexpr (N > 1) o_steps<S0 + 1, N - 1>(d, a);
}
template <int BASE, int KS, int N> __device__ __forceinline__ void m_steps(float* d, const uint32_t* a, uint32_t oa) {
  wg_rs16<KS != 0>(d, a + (BASE + KS / 2) * 4, desc_m(C_M + KS * 512));
  wg_ss16o<1, desc_sw128(C_W + (BASE + KS / 2) * 2048), desc_m(C_M + KS * 512 + 512)>(d, oa, 0);
  if constexpr (N > 2) m_steps<BASE, KS + 2, N - 2>(d, a, oa);
}

__device__ __forceinline__ void chain_proj(const Params& P, uint32_t sb) {
  const uint32_t c = chain_id(), h = c >> 1, j = c & 1, wid = __shfl_sync(~0u, threadIdx.x >> 5, 0), wg = wid >> 2, w = wid & 3;
  const uint32_t t = threadIdx.x & 127, lane = pinned(t & 31), mine = pinned(sb + t * 16), rb = mapa(sb, j ^ 1);
  const uint32_t theirs = pinned(rb + C_KM2 + w * 512 + lane * 4), oa = wg * 4608;
  uint32_t a[144];
  mbar_wait(sb + W_BAR + wg * 8, 0);
  if (threadIdx.x == 0) TS(23);
  load_frags<36>(a, sb + C_W + wg * 73728);
  fence_async_smem();
  bar_sync(B_WG0 + wg, 128);
  if (threadIdx.x == 0) TS(24);
  load_wg(P, sb, false, wg, w);
  if (threadIdx.x == 0) TS(25);
  bar_sync(B_WG2, 384);
  const uint32_t round = min(w, 2u) + (wg ? 0 : 3), gdly = P.dly[8 + round], ps = t >> 2, pf = j * 16 + (ps >> 1);
  uint4* const dsts = pinned(g_xb + (ps * 4096 + near_half(ps * 8, ps * 2) * 256 + c * 4 + (t & 3)));
  uint4* const dstf = pinned(g_xb + (pf * 4096 + 512 + near_half(pf * 8 + 1, pf * 2) * 256 + h * 8 + (t & 7)));
  const uint32_t* const gsrc = (const uint32_t*)g_xb + (h * 16384 + min(w, 2u) * 4096 + near_half(h * 8 + !wg, h * 2) * 1024 +
                               (wg ? (lane & 24) * 2 + j * 8 + (lane & 7) : 2048 + (lane & 16) * 2 + j * 16 + (lane & 15)));
  uint32_t* gdst = g_mimg + (16384 + (lane >> 4) * 1024 + (lane & 2) * 4 +
                   (wg ? (round ? 1536 + round * 512 : 0) + h * 16 + ((lane ^ (c >> 2)) & 1) * 4 + j * 2 + ((lane >> 2) & 1)
                       : (round - 1) * 2048 + c * 16 + ((lane ^ (c >> 1)) & 1) * 4 + ((lane >> 2) & 3)));
  mbar_wait(sb + W_BAR + wg * 8, 1);
  bar_sync(B_INIT, 256);
  if ((threadIdx.x & 127) == 0) TS(4);

  uint32_t ring = 1;
#pragma unroll 1
  for (int n = 0; n < STEPS; n++) {
    float d[8], e[8];
    uint32_t redo = n + 1;
    do {
      mbar_wait(sb + CB_M, n & 1);
      wg_fence();
      m_steps<0, 0, 4>(d, a, oa);
      if (VE && wg) m_steps<18, 0, 4>(e, a, 4608);
      wg_commit();
      if (wid == 0) TR(8);
      mbar_wait(sb + CB_M + 8, n & 1);
      wg_fence();
      m_steps<0, 4, 8>(d, a, oa);
      if (VE > 4 && wg) m_steps<18, 4, (VE > 4 ? VE - 4 : 2)>(e, a, 4608);
      wg_commit();
      mbar_wait(sb + CB_MV, n & 1);
      redo = lds32(sb + C_BAD) == redo ? SENT : 0;
    } while (redo);
    mbar_wait(sb + CB_MV + 8, n & 1);
    wg_fence();
    m_steps<0, 12, 8>(d, a, oa);
    wg_commit();
    mbar_wait(sb + CB_MV + 16, n & 1);
    wg_fence();
    m_steps<0, 20, 8>(d, a, oa);
    wg_commit();
    mbar_wait(sb + CB_MV + 24, n & 1);
    wg_fence();
    m_steps<0, 28, 8>(d, a, oa);
    wg_commit();
    wg_wait<0>();
    if (w == 0) TR(6 + wg);
    const uint32_t f0 = pack2(d[0], d[1]), f1 = pack2(d[4], d[5]), f2 = pack2(d[2], d[3]), f3 = pack2(d[6], d[7]);
    stsm4(mine + C_QM + wg * 2048, f0, f1, f2, f3);
    bar_arrive(B_QK, 416);
    const uint32_t tag = (n & 1) ^ 1;
    if (wg) {
      if (n + 1 < STEPS) bar_sync(B_S, 256);
      wg_fence();
      m_steps<18, VE, 36 - VE>(e, a, 4608);
      wg_commit();
      st_async1(theirs, j ? f0 : f1, rb + CB_XX);
      st_async1(theirs + 256, j ? f2 : f3, rb + CB_XX);
      wg_wait<0>();
      if (w == 0) TR(11);
      const uint32_t v0 = pack2(e[0], e[1]), v1 = pack2(e[4], e[5]), v2 = pack2(e[2], e[3]), v3 = pack2(e[6], e[7]);
      stsm4(mine + C_VM, v0, v1, v2, v3);
      bar_arrive(B_V, 256);
      st_async1(theirs + 128, j ? v0 : v1, rb + CB_XX);
      st_async1(theirs + 384, j ? v2 : v3, rb + CB_XX);
      if (n + 1 == STEPS) break;
      bar_sync(B_O, 256);
      if (!WFENCE) fence_async_smem();
      wg_fence();
#pragma unroll
      for (int ks = 0; ks < 4; ks++) {
        if (ks == 0) wg_ss16<0>(d, desc_sw128(C_W + 32 * 2048), desc_n16(C_OI));
        else wg_ss16<1>(d, desc_sw128(C_W + (32 + ks) * 2048), desc_n16(C_OI + ks * 512));
      }
      wg_commit();
      bar_arrive(B_X, 256);
      if (w == 0) TR(0);
      wg_wait<0>();
      store_partial(dsts, pack_partial(d, tag));
      bar_arrive(B_M, 160);
      if (w == 0) TR(1);
    } else {
      if (n + 1 == STEPS) break;
      bar_sync(B_X, 256);
      wg_fence();
      o_steps<0, 4>(d, a);
      wg_commit();
      o_steps<4, 4>(e, a);
      wg_commit();
      wg_wait<1>();
      store_partial(dsts + 1024, pack_partial(d, tag));
      if (w == 0) TR(2);
      if (OGAP == 0) { wg_fence(); o_steps<8, 4>(d, a); wg_commit(); wg_wait<1>(); } else wg_wait<0>();
      store_partial(dsts + 2048, pack_partial(e, tag));
      if (w == 0) TR(3);
      wg_fence();
      if (OGAP) o_steps<8, 4>(d, a);
      if (OGAP < 2) o_steps<16, 4>(e, a);
      wg_commit();
      bar_sync(B_T, 256);
      if (w == 0) { TRV(61, 0); TR(12); }
      wg_fence();
      o_steps<12, 4>(d, a);
      wg_commit();
      if (OGAP == 2) o_steps<16, 4>(e, a);
      o_steps<20, 4>(e, a);
      wg_commit();
      wg_wait<1>();
      store_partial(dstf, pack_partial(d, tag));
      if (w == 0) TR(4);
      wg_fence();
      o_steps<24, 8>(d, a);
      wg_commit();
      wg_wait<1>();
      store_partial(dstf + 1024, pack_partial(e, tag));
      bar_arrive(B_OE, 256);
      if (w == 0) TR(5);
      wg_wait<0>();
      store_partial(dstf + 2048, pack_partial(d, tag));
      if (w == 0) TR(15);
    }
    if (w < 3) {
      mbar_wait(sb + CB_REF, n & 1);
      wait_until(lds32(sb + C_REF), gdly);
      gather_reduce(gsrc, gdst, wg, tag, lane, sb, n, 16 + round * 4);
      if (++ring == MRING) { ring = 0; gdst -= MRING * 16384; }
      gdst += 16384;
    }
  }
}

template <int KS> __device__ __forceinline__ void x_scores(float* s, float* sm, const uint4* q, uint32_t ok, uint32_t om) {
  wg_rs32o<1, desc_sw64(C_KV + KS * 1024)>(s, q[KS].x, q[KS].y, q[KS].z, q[KS].w, ok);
  wg_rs8o<1, desc_n16(C_KM + KS * 512)>(sm, q[KS].x, q[KS].y, q[KS].z, q[KS].w, om);
  if constexpr (KS < 3) x_scores<KS + 1>(s, sm, q, ok, om);
}

__device__ __forceinline__ void chain_attn(const Params& P, uint32_t sb) {
  const int c = chain_id(), j = c & 1;
  const int tid = threadIdx.x, lane = tid & 31, w = __shfl_sync(~0u, (tid >> 5) & 3, 0);
  const int l = w >> 1, u = w & 1;
  const uint32_t rb = mapa(sb, j ^ 1);
  const float sc = 0.08838834764831845f * 1.4426950408889634f;
  const uint32_t ones = 0x3F803F80u;
  const uint32_t km_off = C_KM + (lane >> 3) * 256 + l * 128 + (lane & 7) * 16;
  const uint32_t qm_off = C_QM + (lane >> 4) * 256 + l * 128 + (lane & 7) * 16;
  const uint32_t kv_off = C_KV + l * 4096 + (lane & 15) * 64 + (((lane >> 4) ^ (u * 2) ^ ((lane >> 1) & 3)) << 4);

  if (lane == 0) mbar_arrive(sb + CB_M);
#pragma unroll 1
  for (int n = 0; n < STEPS; n++) {
    const uint32_t kvb = sb + kv_off + (n & 1) * 16384;
    if (w == 0 && elect()) { mbar_expect(sb + CB_SX, 2560); mbar_expect(sb + CB_OX, 2048); mbar_expect(sb + CB_XX, 2048); }
    mbar_wait(sb + CB_FULL + (n & 1) * 8, (n >> 1) & 1);
    if (n < 3 && tid == 256) TS(n ? 20 + n : 5);
    __syncwarp();
    {
      uint32_t km[8];
      uint4 kx[8];
#pragma unroll
      for (int i = 0; i < 8; i++) ldsm4t(kx[i].x, kx[i].y, kx[i].z, kx[i].w, (kvb ^ ((i & 1) * 32)) + (i >> 1) * 1024);
      mbar_wait(sb + CB_VF, n & 1);
      if (w == 1) TRD(60, kx[7].x);
      bar_sync(B_QK, 416);
      if (n + 1 == STEPS) {
        bar_sync(B_V, 256);
      } else {
      uint32_t qm[16];
#pragma unroll
      for (int ks = 0; ks < 4; ks++) ldsm4t(qm[4 * ks], qm[4 * ks + 1], qm[4 * ks + 2], qm[4 * ks + 3], sb + qm_off + ks * 512);
      ldsm4t(km[0], km[1], km[2], km[3], sb + km_off);
      ldsm4t(km[4], km[5], km[6], km[7], sb + km_off + 1024);
      float s[5][4];
#pragma unroll
      for (int i = 0; i < 5; i++) { s[i][0] = s[i][1] = s[i][2] = s[i][3] = 0.f; }
#pragma unroll
      for (int ks = 0; ks < 4; ks++) {
        const uint32_t* q = qm + 4 * ks;
        mma16(s[1], q[0], q[1], q[2], q[3], kx[2 * ks].x, kx[2 * ks].y);
        mma16(s[2], q[0], q[1], q[2], q[3], kx[2 * ks].z, kx[2 * ks].w);
        mma16(s[0], q[0], q[1], q[2], q[3], km[2 * ks], km[2 * ks + 1]);
        mma16(s[3], q[0], q[1], q[2], q[3], kx[2 * ks + 1].x, kx[2 * ks + 1].y);
        mma16(s[4], q[0], q[1], q[2], q[3], kx[2 * ks + 1].z, kx[2 * ks + 1].w);
      }
      const uint32_t sx = C_SX + l * 1280;
      st_async4(rb + sx + u * 512 + lane * 16, s[1][0], s[1][1], s[2][0], s[2][1], rb + CB_SX);
      st_async1(rb + sx + 1024 + u * 128 + lane * 4, __float_as_uint(u ? s[0][1] : s[0][0]), rb + CB_SX);
      bar_arrive_after<B_S, 256>(__float_as_uint(s[3][0]), __float_as_uint(s[4][0]));
      uint4 vx[4];
#pragma unroll
      for (int i = 0; i < 4; i++) ldsm4(vx[i].x, vx[i].y, vx[i].z, vx[i].w, (kvb ^ ((i & 1) * 32)) + 8192 + (2 * u + (i >> 1)) * 1024);
      mbar_wait(sb + CB_SX, n & 1);
      const uint4 p0 = lds128(sb + sx + u * 512 + lane * 16), p1 = lds128(sb + sx + (u ^ 1) * 512 + lane * 16);
      const uint2 p2 = make_uint2(lds32(sb + sx + 1024 + lane * 4), lds32(sb + sx + 1152 + lane * 4));
      float t[10] = {s[0][0] + __uint_as_float(p2.x), s[0][1] + __uint_as_float(p2.y),
                     s[1][0] + __uint_as_float(p0.x), s[1][1] + __uint_as_float(p0.y),
                     s[2][0] + __uint_as_float(p0.z), s[2][1] + __uint_as_float(p0.w),
                     s[3][0] + __uint_as_float(p1.x), s[3][1] + __uint_as_float(p1.y),
                     s[4][0] + __uint_as_float(p1.z), s[4][1] + __uint_as_float(p1.w)};
      float mx = fmaxf(fmaxf(fmaxf(fmaxf(t[2], t[3]), fmaxf(t[4], t[5])), fmaxf(fmaxf(t[6], t[7]), fmaxf(t[8], t[9]))), fmaxf(t[0], t[1]));
      mx = fmaxf(fmaxf(mx, __shfl_xor_sync(~0u, mx, 1)), fmaxf(__shfl_xor_sync(~0u, mx, 2), __shfl_xor_sync(~0u, mx, 3)));
      const float ms = -mx * sc;
#pragma unroll
      for (int i = 0; i < 10; i++) t[i] = ex2(fmaf(t[i], sc, ms));
      uint32_t p[5];
#pragma unroll
      for (int i = 0; i < 5; i++) p[i] = pack2(t[2 * i], t[2 * i + 1]);
      p[1] |= (p[0] & p[3] & p[4]) & 0x80008000u;
      float o[2][4], z[4] = {0.f, 0.f, 0.f, 0.f};
      mma16(z, ones, ones, ones, ones, p[1], p[2]);
#pragma unroll
      for (int i = 0; i < 2; i++) {
        o[i][0] = o[i][1] = o[i][2] = o[i][3] = 0.f;
        mma16(o[i], vx[2 * i].x, vx[2 * i].y, vx[2 * i].z, vx[2 * i].w, p[1], p[2]);
      }
      mma16(z, ones, ones, ones, ones, p[3], p[4]);
#pragma unroll
      for (int i = 0; i < 2; i++) mma16(o[i], vx[2 * i + 1].x, vx[2 * i + 1].y, vx[2 * i + 1].z, vx[2 * i + 1].w, p[3], p[4]);
      mma8(z, ones, ones, p[0]);
      bar_sync_after<B_V, 256>(p[1]);
      ldsm4(km[0], km[1], km[2], km[3], sb + km_off + (C_VM - C_KM) + u * 1024);
      mma8(o[0], km[0], km[1], p[0]);
      mma8(o[1], km[2], km[3], p[0]);
      const float i0 = rcp(z[0]), i1 = rcp(z[1]);
      const uint32_t oo = C_OI + u * 1024 + l * 128 + lane * 4;
      uint32_t ow[4];
#pragma unroll
      for (int i = 0; i < 2; i++) { ow[2 * i] = pack2(o[i][0] * i0, o[i][1] * i1); ow[2 * i + 1] = pack2(o[i][2] * i0, o[i][3] * i1); }
      stsm4(sb + C_OI + u * 1024 + l * 128 + (lane >> 3) * 256 + (lane & 7) * 16, ow[0], ow[1], ow[2], ow[3]);
      if (WFENCE) fence_async_smem();
      bar_arrive(B_O, 256);
#pragma unroll
      for (int i = 0; i < 4; i++) st_async1(rb + oo + 2048 + i * 256, ow[i], rb + CB_OX);
      }
    }
    {
      const uint32_t lane = opaque_tid() & 31, own = ((n & 1) * 16384 + j * 4096) >> 4;
      float s[16], sm[4];
#pragma unroll
      for (int i = 0; i < 16; i++) s[i] = sm[i & 3] = 0.f;
      {
        uint4 q[4];
        mbar_wait(sb + CB_Q, n & 1);
        auto load_q = [&]() {
#pragma unroll
          for (int ks = 0; ks < 4; ks++) q[ks] = lds128(sb + C_Q + (ks >> 1) * 4096 + w * 1024 + (ks & 1) * 512 + lane * 16);
        };
        if (QPOS == 0) load_q();
        mbar_wait(sb + CB_XX, n & 1);
        if (n + 1 < STEPS) mbar_wait(sb + CB_OX, n & 1);
        fence_async_smem();
        if (n + 1 < STEPS) bar_arrive(B_T, 256);
        if (QPOS == 1) load_q();
        if (n + 1 < STEPS) bar_sync(B_OE, 256);
        if (QPOS == 2) load_q();
        if (w == 1) { TRV(61, 0); TR(9); }
#pragma unroll 1
        for (uint32_t hf = 0; hf < 2; hf++) {
          wg_fence();
          x_scores<0>(s, sm, q, hf ? (C_KV2 - C_KV) >> 4 : own, hf ? (C_KM2 - C_KM) >> 4 : j * 8);
          wg_commit();
          wg_wait<0>();
#pragma unroll
          for (int ks = 0; ks < 4; ks++) asm volatile("mov.b32 %0, %1; mov.b32 %2, %3;" : "+r"(q[ks].x), "+r"(q[ks].y), "+r"(q[ks].z), "+r"(q[ks].w));
        }
      }
      const float neg = -1e9f * 11.313708498984761f;
      const int lim = 8 * (w - (int)(lane & 3)) + (int)(lane >> 2);
      float t[10] = {sm[0], sm[1]};
#pragma unroll
      for (int i = 0; i < 8; i++) t[2 + i] = i > lim ? neg : s[(i >> 1) * 4 + (i & 1)];
      float mx = fmaxf(fmaxf(fmaxf(fmaxf(t[2], t[3]), fmaxf(t[4], t[5])), fmaxf(fmaxf(t[6], t[7]), fmaxf(t[8], t[9]))), fmaxf(t[0], t[1]));
      mx = fmaxf(fmaxf(mx, __shfl_xor_sync(~0u, mx, 1)), fmaxf(__shfl_xor_sync(~0u, mx, 2), __shfl_xor_sync(~0u, mx, 3)));
      const float ms = -mx * sc;
#pragma unroll
      for (int i = 0; i < 10; i++) t[i] = ex2(fmaf(t[i], sc, ms));
      uint32_t p[5];
#pragma unroll
      for (int i = 0; i < 5; i++) p[i] = pack2(t[2 * i], t[2 * i + 1]);
      float z = ((t[0] + t[1]) + (t[2] + t[3])) + ((t[4] + t[5]) + (t[6] + t[7])) + (t[8] + t[9]);
      const uint32_t row = sb + C_Q + w * 1024 + (lane >> 2) * 128 + (((lane & 3) ^ (lane >> 2)) << 4);
#pragma unroll 1
      for (uint32_t hf = 0; hf < 2; hf++) {
        float o[32];
        const uint32_t vo = hf ? (C_KV2 + 4096 - C_KV - 8192) >> 4 : own;
        wg_fence();
        wg_rs64o<0, desc_sw64(C_KV + 8192)>(o, p[1], p[1], p[2], p[2], vo);
        wg_rs64o<1, desc_sw64(C_KV + 8192 + 32)>(o, p[3], p[3], p[4], p[4], vo);
        wg_rs64o<1, mkdesc(C_VM, 128, 256, 0)>(o, p[0], p[0], 0, 0, hf ? (C_VM2 - C_VM) >> 4 : j * 8);
        wg_commit();
        if (hf) {
          if (elect()) mbar_arrive(sb + CB_M);
        } else {
          z += __shfl_xor_sync(~0u, z, 1);
          z = rcp(z + __shfl_xor_sync(~0u, z, 2));
        }
        wg_wait<0>();
#pragma unroll
        for (int qq = 0; qq < 2; qq++) {
          const float* r = o + 16 * qq;
          sts128((row ^ (qq * 64)) + hf * 4096,
                 make_uint4(pack2(r[0] * z, r[1] * z), pack2(r[4] * z, r[5] * z), pack2(r[8] * z, r[9] * z), pack2(r[12] * z, r[13] * z)));
        }
      }
      bar_arrive(B_G, 160);
      if (w == 1) TR(10);
    }
  }
  if ((threadIdx.x & 127) == 0) TS(6);
}

__device__ __forceinline__ void chain_aux(const Params& P, uint32_t sb) {
  const uint32_t c = chain_id(), j = c & 1, lane = threadIdx.x & 31, w = __shfl_sync(~0u, (threadIdx.x >> 5) & 3, 0);
  if (threadIdx.x == 384) grid_wait(1, lds32(sb + S_GEN));
  bar_sync(B_WG2, 384);
  if (threadIdx.x == 384) TS(13);
  if (w == 0) {
    const uint32_t* fg = g_fl + FL_G + near_half(XB_F, c) * 1024 + (c >> 1) * 8;
#pragma unroll 1
    for (int n = 0; n < STEPS; n++) {
      const unsigned char* blk = g_qkv + (uint32_t)((n % RING) * (N_CHAIN * 24576));
      const uint32_t t1 = clk(), kb = sb + CB_FULL + (n & 1) * 8, kv = sb + C_KV + (n & 1) * 16384;
      uint32_t t0 = t1 - 100000, x = 0;
      if (n > 0) {
        wait_until(t1, KMIN);
        do asm volatile("ld.relaxed.gpu.global.u32 %0, [%1];" : "=r"(x) : "l"(fg) : "memory"); while (x <= n && clk() - t1 < KWIN);
        if (NOBULK) x = n + 1;
        if (x > n) {
          asm volatile("fence.acquire.gpu;" ::: "memory");
          fence_async_global();
          if (elect()) { mbar_expect(kb, 8192); bulk_load(kv, blk + c * 24576, 8192, kb); }
        }
        T3(0); CNT(12, 1 + (x <= n));
        mbar_wait(sb + CB_REF, (n - 1) & 1);
        t0 = lds32(sb + C_REF);
        wait_until(t0, DLYK - 500);
      }
      if (!NOBULK) wait_flags(fg + (lane & 1) * 256, n + 1);
      fence_async_global();
      wait_until(t0, DLYK);
      if (elect()) {
        if (x <= n) { mbar_expect(kb, 8192); bulk_load(kv, blk + c * 24576, 8192, kb); }
        mbar_expect(sb + CB_VF, 8192);
        bulk_load(kv + 8192, blk + (c * 24576 + 8192), 8192, sb + CB_VF);
      }
      T3(1);
      if (!NOBULK) wait_flags(fg + 512, n + 1);
      T3(2);
      fence_async_global();
      if (n > 0) bar_sync(B_R, 64);
      if (elect()) {
        mbar_expect(sb + CB_Q, 16384);
        bulk_load(sb + C_Q, blk + (c * 24576 + 16384), 8192, sb + CB_Q);
        bulk_load(sb + C_KV2, blk + ((c ^ 1) * 24576 + j * 4096), 4096, sb + CB_Q);
        bulk_load(sb + C_KV2 + 4096, blk + ((c ^ 1) * 24576 + 8192 + j * 4096), 4096, sb + CB_Q);
      }
      T3(3);
    }
  } else {
    const uint32_t near = __ballot_sync(~0u, near_half(XB_M + min(lane, MRING - 1u) * 8, c));
    uint32_t ring = 0;
    if (w > 1) {
      const uint32_t odd = w & 1, chk = pinned(sb + C_M + odd * 2048 + m_probe(lane)), again = sb + CB_MV + 32 + odd * 8;
      const bool one = elect();
      uint32_t mph = 0;
#pragma unroll 1
      for (int n = 0; n <= STEPS; n++) {
#pragma unroll
        for (int k = 0; k < 3; k++) {
          if (n == STEPS || (k == 2 && odd)) break;
          const uint32_t b = 2 * k + odd, at = chk + (k ? k * 8192 - 2048 + odd * 2048 : 0);
          uint32_t mb = sb + CB_M + b * 8, ph = n & 1;
          int it = 1;
          while (true) {
            mbar_wait(mb, ph);
            const bool bad = __any_sync(~0u, (k ? m_max(at, at + 2048) : max(m_max(at, at ^ 8), odd ? m_max(at + 2048, (at ^ 8) + 2048) : 0)) == SENT);
            if (one && !bad) mbar_arrive(sb + CB_MV + (k ? b * 8 - 8 : 0));
            if (!bad) break;
            mb = again; ph = mph; mph ^= 1;
            if (one) {
              if (k == 0) sts32(sb + C_BAD, n + 1);
              mbar_expect(mb, b ? 4096 : 2048);
              m_fetch(sb, ring * 65536 + ((near >> ring) & 1) * 4096, b, mb);
            }
            __syncwarp();
            spin_guard(it);
          }
          TR(41 + b * 4); CNT(6 + b, it);
        }
        ring = ring + 1 == MRING ? 0 : ring + 1;
        if (!odd) {
          if (n < STEPS) { TRSYNC(); TRDUMP(n - 2); }
        } else if (n > 0) {
          unsigned char* o = g_oimg + (uint32_t)(((n - 1) & (RING - 1)) * (N_CHAIN * 8192) + j * 4096);
          bar_sync(B_G, 160);
          fence_async_smem();
          if (one) {
            bulk_store(o + c * 8192, sb + C_Q, 4096);
            bulk_store(o + (c ^ 1) * 8192, sb + C_Q + 4096, 4096);
            asm volatile("cp.async.bulk.commit_group;\ncp.async.bulk.wait_group.read 0;" ::: "memory");
            { const int n_ = n - 1; { const int n = n_; T3(4); (void)n; } }
          }
          __syncwarp();
          if (n < STEPS) bar_arrive(B_R, 64);
          if (one) {
            bulk_done_inc(g_fl + FL_O + c);
            { const int n_ = n - 1; { const int n = n_; T3(5); (void)n; } }
          }
          __syncwarp();
        }
      }
    } else {
      const uint32_t* ts = g_fl + FL_SYNC + near_half(XB_F + 1, c) * 1024 + lane * 2;
      uint32_t t0 = clk() - 100000;
#pragma unroll 1
      for (int n = 0; n < STEPS; n++) {
        const uint32_t src = ring * 65536 + ((near >> ring) & 1) * 4096;
        if (lane < 5) mbar_expect(sb + CB_M + lane * 8, lane ? 4096 : 2048);
        __syncwarp();
        if (elect()) {
#pragma unroll
          for (int b = 0; b < 5; b++) {
            wait_until(t0, P.dly[14 + b]);
            m_fetch(sb, src, b, sb + CB_M + b * 8);
            TR(40 + b * 4);
          }
        }
        __syncwarp();
        ring = ring + 1 == MRING ? 0 : ring + 1;
        uint32_t va, vb;
        const uint32_t off = timer_offset(), tag = (uint32_t)(n + 1) << 24;
        bar_sync(B_QK, 416);
        if (n + 1 == STEPS) break;
        sts32(sb + C_REF + 4, 0);
        const uint32_t c0 = clk(), stamp = c0 + off;
        st_relaxed_if(g_fl + FL_SYNC + lane * 1024 + c, tag | (stamp & 0xFFFFFF), lane < 2);
        TR(13);
        wait_until(c0, DLYS);
        int it = 0;
        do {
          asm volatile("ld.relaxed.gpu.global.v2.u32 {%0,%1}, [%2];" : "=r"(va), "=r"(vb) : "l"(ts) : "memory");
          spin_guard(it);
        } while (__any_sync(~0u, ((va ^ tag) | (vb ^ tag)) >> 24));
        const int late = __reduce_max_sync(~0u, max((int)((va - stamp) << 8), (int)((vb - stamp) << 8))) >> 8;
        t0 = c0 + min((uint32_t)late, clk() - c0);
        if (elect()) {
          sts32(sb + C_REF, t0);
          mbar_arrive(sb + CB_REF);
        }
        st_relaxed_if(g_fl + FL_TICK + lane * 1024, tag | ((t0 + off) & 0xFFFFFF), c == 0 && lane < 2);
        TR(14); CNT(11, it);
        bar_sync(B_M, 160);
      }
    }
  }
}

template <int WG>
__device__ __forceinline__ void g_math(const Params& P, uint32_t sb) {
  const int q = g_unit(WG);
  const int lane = threadIdx.x & 31, w = (threadIdx.x >> 5) & 3;
  const bool isq = q >= 64;
  uint32_t a[136];
  {
    const uint32_t stage = sb + G_W + WG * 73728;
    mbar_wait(sb + W_BAR + WG * 8, 0);
    if (threadIdx.x == 0) TS(23);
    load_frags<34>(a, stage);
    fence_async_smem();
    bar_sync(B_WG0 + WG, 128);
    if (threadIdx.x == 0) TS(24);
    load_wg(P, sb, false, WG, w);
    if (threadIdx.x == 0) TS(25);
    mbar_wait(sb + W_BAR + WG * 8, 1);
  }
  if ((threadIdx.x & 127) == 0) TS(4);
  const uint32_t off0 = (q & 31) * 49152 + (q >> 5) * 8192 +
                        (isq ? (w >> 1) * 4096 + (w & 1) * 512 + lane * 16 : w * 1024 + (lane >> 2) * 64 + (((lane ^ (lane >> 3)) & 3) << 4));
#pragma unroll 1
  for (int n = 0; n < STEPS; n++) {
    float d0[32], d1[32];
    if (WG == 0 && n >= LOCK0) bar_sync(B_OE, 160);
    if (n > 0) bar_sync(B_V + WG, 256);
#pragma unroll
    for (int ch = 0; ch < 9; ch++) {
      mbar_wait(sb + G_BAR + ch * 8, n & 1);
      if (ch == 0) { if ((threadIdx.x & 127) == 0) T3(5 + WG * 3); __syncwarp(); }
      if (ch == 4) { if ((threadIdx.x & 127) == 0) T3(6 + WG * 3); __syncwarp(); }
      if (ch == 8 && (WG == 0 ? n > 0 : n + 1 < STEPS)) bar_arrive(B_V + (WG ^ 1), 256);
      wg_fence();
#pragma unroll
      for (int kk = 0; kk < 4 - FASTG; kk++) {
        const int i = ch * 4 + kk;
        float* d = i & 1 ? d1 : d0;
        const uint64_t db = desc_sw128(G_RING + ch * 8192 + (kk & 2) * 32);
        if (i < 2) wg_rs64<0>(d, a + i * 4, db);
        else if (i < 34) wg_rs64<1>(d, a + i * 4, db);
        else wg_ss64<1>(d, desc_sw128(G_W2 + WG * 4096 + (i - 34) * 2048), db);
        wg_ss64<1>(d, desc_sw128(G_W + WG * 73728 + i * 2048), db + 2);
      }
      wg_commit();
      if (ch > 0) { wg_wait<1>(); if (lane == 0) mbar_arrive(sb + G_BAR + 128 + (ch - 1) * 8); }
    }
    wg_wait<0>();
    if (lane == 0) mbar_arrive(sb + G_BAR + 128 + 8 * 8);
    if ((threadIdx.x & 127) == 0) T3(7 + WG * 3);
    __syncwarp();
    uint32_t tw = clk() + (WG ? 0 : DLYW);
    unsigned char* base = g_qkv + (size_t)(n & (RING - 1)) * (N_CHAIN * 24576);
    if ((ABL & 1) && d0[0] != 1234.5f) {
    } else if (isq) {
#pragma unroll
      for (int i = 0; i < 8; i++) {
        const float *d = (i < 4 ? d0 : d1) + 4 * i, *e = (i < 4 ? d1 : d0) + 4 * i;
        wait_until(tw, 0); tw += P.dly[2 + WG];
        *(uint4*)(base + off0 + (i >> 2) * 24576 + (i & 3) * 1024) =
          make_uint4(movmat(pack2(d[0], d[1])), movmat(pack2(e[0], e[1])), movmat(pack2(d[2], d[3])), movmat(pack2(e[2], e[3])));
      }
    } else {
#pragma unroll
      for (int i = 0; i < 8; i++) {
        const float* d = (i < 4 ? d0 : d1) + 8 * (i & 2) + 2 * (i & 1);
        wait_until(tw, 0); tw += P.dly[2 + WG];
        *(uint4*)(base + off0 + (i >> 2) * 24576 + (i & 2) * 2048 + (i & 1) * 512) =
          make_uint4(pack2(d[0], d[1]), pack2(d[4], d[5]), pack2(d[8], d[9]), pack2(d[12], d[13]));
      }
    }
    bar_arrive(B_M + WG, 160);
  }
}

__device__ __forceinline__ void fill16(void* p, uint32_t v) {
  asm volatile("st.global.v4.u32 [%0], {%1,%1,%1,%1};" :: "l"(p), "r"(v) : "memory");
}
__device__ __forceinline__ void g_load(const Params& P, uint32_t sb) {
  const int lane = threadIdx.x & 31, w = __shfl_sync(~0u, (threadIdx.x >> 5) & 3, 0);
  if (w == 2) return;
  uint32_t fl = 0;
#pragma unroll 1
  for (int n = w == 3 ? LOCK0 : 0; n < STEPS; n++) {
    if (w && n == LOCK0) { grid_wait(1, lds32(sb + S_GEN)); fl = near_half(XB_F, bid()) * 1024; }
    if (w == 3) {
      const uint32_t tag = (uint32_t)(n - LOCK0 + 1) << 24;
      uint32_t v; int it = 0;
      do { asm volatile("ld.relaxed.gpu.global.u32 %0, [%1];" : "=r"(v) : "l"(g_fl + fl + FL_TICK) : "memory"); spin_guard(it); } while (!NOCHAIN && v < tag);
      const uint32_t off = timer_offset(), now = clk(), t0 = now - ((v ^ tag) >> 24 ? DLYG : (now + off - v) & 0xFFFFFF);
      asm volatile("fence.acquire.gpu;" ::: "memory");
      if (lane == 0) T3(11);
      __syncwarp();
      wait_until(t0, DLYG);
      if (lane == 0) T3(4);
      bar_sync(B_OE, 160);
      continue;
    }
    if (w == 0 || n == 0) {
      if (n < NSEG) wait_flags(g_lnflag + n * 16 + (lane & 1) * 8, 1);
    } else if (!NOCHAIN && n >= LAG) {
      wait_flags(g_fl + fl + FL_F + (lane & 1) * 8, n - LAG + 1);
    }
    if (w) { if (lane == 0) T3(12); bar_sync(B_X, 96); }
    fence_async_global();
    const unsigned char* src = g_lnimg + (uint32_t)((w ? (n >= LAG ? NSEG + n - LAG : 0) : min(n, NSEG - 1)) * 36864);
#pragma unroll 1
    for (int ch = 0; ch < 9; ch++) {
      const uint32_t full = sb + G_BAR + ch * 8;
      mbar_wait(full + 128, (n & 1) ^ 1);
      if (elect()) {
        mbar_expect(full, ABL & 2 ? 16 : 4096);
        bulk_load(sb + G_RING + ch * 8192 + w * 4096, src + ch * 4096, ABL & 2 ? 16 : 4096, full);
      }
    }
  }
}

__device__ __forceinline__ void g_aux(const Params& P, uint32_t sb) {
  const int lane = threadIdx.x & 31, w = (threadIdx.x >> 5) & 3;
  if (w == 1 || w == 2) {
    const int q = g_unit(w - 1);
    uint32_t* f = g_fl + FL_G + q * 8;
#pragma unroll 1
    for (int n = 0; n < STEPS; n++) {
      const uint32_t ln = opaque_tid() & 31;
      uint4* z = (uint4*)g_oacc + (uint32_t)(((n + 1) % ARING) * (16 * DM) + q * 96 + ln);
      if (!(ABL & 16)) { fill16(z, 0); fill16(z + 32, 0); fill16(z + 64, 0); }
      if (n + 3 >= MRING && q < 80) fill16((uint4*)g_mimg + (uint32_t)(((n + 3) % MRING) * 4096 + q * 32 + ln), SENT);
      bar_sync(B_M + (w - 1), 160);
      if (lane == 0) { T3(w * 2 - 2); fence_async_global(); flag_release(f, n + 1); T3(w * 2 - 1); }
      __syncwarp();
    }
  } else {
    const uint32_t u = (bid() - N_CHAIN) * 2 + (w & 1), r = u / 36 * 16 + (u & 3) * 4 + (lane >> 3);
    uint32_t o = r * (DM / 8) + (u % 36 >> 2) * 8 + ((lane & 7) ^ ((r >> 1) & 3)), fl = 0;
#pragma unroll 1
    for (int k = -LAG - 1; k < STEPS; k++) {
      if (k < NSEG - 1) bar_sync(B_X, 96);
      if (k < LAG || u >= 72) continue;
      if (k == NSEG - 1) { fl = near_half(XB_F, bid()) * 1024; wait_flags(g_fl + fl + FL_F + (lane & 1) * 8, NSEG + 1); }
      const uint4 x = __ldcg((const uint4*)P.out + o);
      if (k >= NSEG - 1) wait_flags(g_fl + fl + FL_OCNT + (max(k, NSEG) % OCRING) * 8, N_O * 3 * (max(k, NSEG) / OCRING + 1));
      const float4* a = (const float4*)g_oacc + ((k % ARING) * (16 * DM) + 8 * DM + u * 64 + lane * 2);
      const float4 p = __ldcg(a), v = __ldcg(a + 1);
      ((uint4*)P.out)[o] = make_uint4(badd2(x.x, pack2(p.x, p.y)), badd2(x.y, pack2(p.z, p.w)), badd2(x.z, pack2(v.x, v.y)), badd2(x.w, pack2(v.z, v.w)));
      o += 4 * DM;
    }
    if ((threadIdx.x & 127) == 0) TS(7);
  }
}

template <int WG, bool HALF, int KS, int N> __device__ __forceinline__ void o_mma(float* d, const uint32_t* a, uint32_t ob) {
  constexpr uint64_t db = desc_sw128(O_RING + (KS >> 2) * 8192 + (KS & 3) * 32);
  constexpr uint64_t da = desc_sw128(O_W + WG * 40960 + (KS < 40 ? KS / 5 * 2 + KS % 5 / 2 : KS - 24) * 2048);
  if constexpr (KS < 40 && !(KS % 5 & 1)) {
    const uint32_t* r = a + (KS / 5 * 3 + KS % 5 / 2) * 4;
    if constexpr (HALF) wg_rs32k<KS != 0, db>(d, r[0], r[1], r[2], r[3], ob); else wg_rs64<KS != 0>(d, r, db);
  } else {
    if constexpr (HALF) wg_ss32k<da, db>(d, ob); else wg_ss64<1>(d, da, db);
  }
  if constexpr (N > 1) o_mma<WG, HALF, KS + 1, N - 1>(d, a, ob);
}
template <int WG, bool HALF, int GR> __device__ __forceinline__ void o_groups(float* d, const uint32_t* a, uint32_t sb, int n, bool more) {
  const uint32_t ob = n < NSEG ? 0 : 256;
  mbar_wait(sb + O_BAR + GR * 8, n & 1);
  if (GR == 0) { if ((threadIdx.x & 127) == 0) T3(13 + WG); __syncwarp(); }
  if (GR == (WG == 0 ? OTURN : 4) && (WG < 2 || n + 1 < STEPS)) bar_arrive(B_V + (WG + 1) % 3, 256);
  wg_fence();
  o_mma<WG, HALF, GR * 8, 8 - 2 * FASTG>(d, a, ob);
  if (GR == 4 && more) o_mma<WG, HALF, 40, 4>(d, a, ob);
  wg_commit();
  if (GR > 0) { wg_wait<1>(); if ((threadIdx.x & 31) == 0) mbar_arrive(sb + O_BAR + 128 + (GR - 1) * 8); }
  if constexpr (GR < 4) o_groups<WG, HALF, GR + 1>(d, a, sb, n, more);
}
template <int WG, bool HALF> __device__ __forceinline__ void o_step(const uint32_t* a, uint32_t sb, uint32_t st0, int n, bool more) {
  float d[HALF ? 16 : 32];
  if (WG > 0 || n > 0) bar_sync(B_V + WG, 256);
  o_groups<WG, HALF, 0>(d, a, sb, n, more);
  wg_wait<0>();
  if ((threadIdx.x & 31) == 0) mbar_arrive(sb + O_BAR + 128 + 4 * 8);
  if ((threadIdx.x & 127) == 0) T3(WG == 0 ? 1 : WG == 1 ? 8 : 12);
  __syncwarp();
#pragma unroll(HALF ? 1 : 2)
  for (int sl = 0; sl < 2; sl++) {
    mbar_wait(sb + OB_ST + WG * 16 + sl * 8, (n & 1) ^ (WG == 0));
    if (!HALF || sl == (n >= NSEG)) {
#pragma unroll
      for (int nb = 0; nb < 4; nb++) {
        const float* r = d + (HALF ? 0 : sl * 16) + nb * 4;
        const uint32_t ad = st0 + sl * 8192 + nb * 2048;
        sts32(ad, __float_as_uint(r[0]));
        sts32(ad + 256, __float_as_uint(r[1]));
        sts32(ad ^ 32, __float_as_uint(r[2]));
        sts32((ad ^ 32) + 256, __float_as_uint(r[3]));
      }
      fence_async_smem();
    }
    bar_arrive((sl ? B_G : B_M) + WG, 160);
  }
}
template <int WG>
__device__ __forceinline__ void o_math(const Params& P, uint32_t sb) {
  const bool more = bid() < N_CHAIN + N_G + 12;
  const int lane = threadIdx.x & 31, w = (threadIdx.x >> 5) & 3, g = lane >> 2, tq = lane & 3;
  uint32_t a[96];
  mbar_wait(sb + W_BAR + WG * 8, 0);
  load_frags<24>(a, sb + WG * 49152);
  fence_async_smem();
  bar_sync(B_INIT, 416);
  load_wg(P, sb, false, WG, w);
  mbar_wait(sb + W_BAR + WG * 8, 1);
  if ((threadIdx.x & 127) == 0) TS(4);
  const uint32_t st0 = sb + O_ST + tq * 512 + ((w * 16 + g) ^ (tq * 8)) * 4;
#pragma unroll 1
  for (int n = 0; n < STEPS; n++) {
    if (n < LAG || n >= NSEG) o_step<WG, true>(a, sb, st0, n, more); else o_step<WG, false>(a, sb, st0, n, more);
  }
}

__device__ __forceinline__ void o_aux(const Params& P, uint32_t sb) {
  const int i = bid() - N_CHAIN - N_G, ksl = i / 3;
  const int c0 = ksl * 11 - max(ksl - 4, 0), nc = ksl < 4 ? 11 : 10;
  const int lane = threadIdx.x & 31, w = __shfl_sync(~0u, (threadIdx.x >> 5) & 3, 0);
  if (w == 0) {
    bar_sync(B_INIT, 416);
    const uint32_t* f = g_fl + FL_O + near_half(XB_F + 1, bid()) * 1024 + min((c0 & ~1) + lane, (c0 + nc - 1) | 1);
#pragma unroll 1
    for (int n = 0; n < STEPS; n++) {
      const unsigned char* src = g_oimg + (uint32_t)(((n % RING) * N_CHAIN + c0) * 8192);
      if (!NOCHAIN) wait_flags(f, n + 1);
      fence_async_global();
      if (lane == 0) T3(0);
#pragma unroll
      for (int gr = 0; gr < 5; gr++) {
        const uint32_t full = sb + O_BAR + gr * 8, bytes = ABL & 4 ? 16 : (gr < 4 ? 2 : nc - 8) * 8192;
        mbar_wait(full + 128, (n & 1) ^ 1);
        if (elect()) {
          if (n < LAG || n >= NSEG) {
            mbar_expect(full, bytes >> 1);
            for (uint32_t o = gr * 16384 + (n < LAG ? 0 : 4096); o < gr * 16384 + bytes; o += 8192) bulk_load(sb + O_RING + o, src + o, 4096, full);
          } else {
            mbar_expect(full, bytes);
            bulk_load(sb + O_RING + gr * 16384, src + gr * 16384, bytes, full);
          }
        }
      }
    }
  } else {
#pragma unroll 1
    for (int n = 0; n < STEPS; n++) {
      float* dst = g_oacc + (uint32_t)((n % ARING) * (64 * DM) + ((i % 3) * 3 + (w - 1 + ksl) % 3) * 1024);
      const bool early = w == 3 && n < NSEG;
      bar_sync(B_M + (w - 1), 160);
      if (lane == 0) {
        T3(w * 2);
        if (n < NSEG && !(ABL & 8)) { bulk_reduce(dst, sb + O_ST, 4096); bulk_reduce(dst + 16 * DM, sb + O_ST + 4096, 4096); }
        asm volatile("cp.async.bulk.commit_group;" ::: "memory");
        if (early) {
          asm volatile("cp.async.bulk.wait_group.read 0;" ::: "memory");
          mbar_arrive(sb + OB_ST);
          T3(8 + w);
          bulk_done_inc(g_fl + FL_OCNT + (n % OCRING) * 8);
          T3(w * 2 + 1);
        }
      }
      __syncwarp();
      bar_sync(B_G + (w - 1), 160);
      if (lane == 0) {
        if (n >= LAG && !(ABL & 8)) { bulk_reduce(dst + 32 * DM, sb + O_ST + 8192, 4096); bulk_reduce(dst + 48 * DM, sb + O_ST + 12288, 4096); }
        asm volatile("cp.async.bulk.commit_group;\ncp.async.bulk.wait_group.read 1;" ::: "memory");
        if (!early) mbar_arrive(sb + OB_ST + (w % 3) * 16);
        asm volatile("cp.async.bulk.wait_group.read 0;" ::: "memory");
        mbar_arrive(sb + OB_ST + (w % 3) * 16 + 8);
        if (!early) {
          T3(8 + w);
          bulk_done_inc(g_fl + FL_OCNT + (n % OCRING) * 8);
          T3(w * 2 + 1);
        }
      }
      __syncwarp();
    }
  }
}

constexpr uint32_t Y_PITCH = 1168, Y_ROWS = 16 * Y_PITCH;
template <int R> __device__ __forceinline__ void y_rows(uint32_t* y, uint32_t src, uint32_t dst, int w, int bar) {
  const int lane = threadIdx.x & 31;
#pragma unroll
  for (int k = 0; k < 2 * R + 1; k++) {
    const int op = w + k * (16 / R);
    if (k == 2 * R && w >= 4) break;
    uint32_t a, b, c, d;
    ldsm4t(a, b, c, d, src + op * 512 + (lane & 16) * 16 + (lane & 7) * 32 + (lane & 8) * 2);
    stsm4(dst + (lane & 15) * Y_PITCH + op * 32 + (lane & 16), a, b, c, d);
  }
  bar_sync(bar, 512 / R);
  const uint32_t row = dst + ((w & 6) * 2 + (w >> 3) * 2 + (w & 1)) * Y_PITCH + lane * 4;
#pragma unroll
  for (int i = 0; i < 9 * R; i++) y[i] = lds32(row + i / 9 * 2 * Y_PITCH + i % 9 * 128);
}

__device__ __forceinline__ void f_role(const Params& P, uint32_t sb) {
  const int lane = threadIdx.x & 31, w = __shfl_sync(~0u, threadIdx.x >> 5, 0), r0 = (bid() - N_CHAIN - N_G - N_O) * 16;
  if (w == 8) {
    const uint32_t* fo = g_fl + FL_OCNT + near_half(XB_F, bid()) * 1024;
    fence_async_global();
#pragma unroll 1
    for (int n = 0; n < NSEG; n++) {
      if (n > 0) bar_sync(2, 288);
      if (elect()) {
        mbar_expect(sb + F_BAR, 36864);
        bulk_load(sb + F_XY, P.X + (size_t)(n * 32 + r0) * DM, 18432, sb + F_BAR);
        bulk_load(sb + F_XY + 18432, g_yT + (size_t)(n * 32 + r0) * DM, 18432, sb + F_BAR);
        mbar_expect(sb + F_BAR + 8, 36864);
        T3(1);
      }
      wait_flags(fo + (n % OCRING) * 8, NOCHAIN == 5 ? 0 : N_O * 3 * (n / OCRING + 1));
      fence_async_global();
      if (elect()) { bulk_load(sb + F_A, g_oacc + (uint32_t)((n % ARING) * (64 * DM) + r0 * DM), 36864, sb + F_BAR + 8); T3(0); }
    }
  } else if (w == 9) {
#pragma unroll 1
    for (int n = 0; n < NSEG; n++) {
      const uint32_t st = sb + (n & 1) * 36864;
      unsigned char* p = g_lnimg + (uint32_t)((NSEG + n) * 36864 + r0 * 128);
      bar_sync(1, 288);
      if (elect()) {
        T3(2);
#pragma unroll
        for (int i = 0; i < 9; i++) bulk_store(p + i * 4096, st + F_L + i * 2048, 2048);
        asm volatile("cp.async.bulk.commit_group;" ::: "memory");
        bulk_done_inc(g_fl + FL_F + (bid() & 1) * 8);
        T3(3);
        bulk_store(P.out + (size_t)(n * 32 + r0) * DM, st + F_X, 18432);
        asm volatile("cp.async.bulk.commit_group;\ncp.async.bulk.wait_group.read 0;" ::: "memory");
        if (n + 1 == NSEG) bulk_done_inc(g_fl + FL_F + (bid() & 1) * 8);
      }
      __syncwarp();
    }
  } else if (w < 8) {
    const uint32_t row = sb + w * 1152 + lane * 4, acc = sb + F_A + w * 256 + (lane ^ ((w & 6) * 2)) * 8;
    const uint32_t ln = sb + F_L + w * 128 + (((lane >> 2) ^ w) << 4) + (lane & 3) * 4;
#pragma unroll 1
    for (int n = 0; n < NSEG; n++) {
      const uint32_t st = (n & 1) * 36864;
      uint32_t x[18], y[18], l[18];
      mbar_wait(sb + F_BAR, n & 1);
#pragma unroll
      for (int i = 0; i < 18; i++) x[i] = lds32(row + F_XY + i / 9 * 9216 + i % 9 * 128);
      y_rows<2>(y, sb + F_XY + 18432, sb + F_Y, w, 3);
      layernorm9<2>(x, l);
#pragma unroll
      for (int i = 0; i < 18; i++) x[i] = badd2(x[i], bmul2(l[i], y[i]));
      mbar_wait(sb + F_BAR + 8, n & 1);
      if (threadIdx.x == 0) T3(4);
      __syncwarp();
      uint2 a[18];
#pragma unroll
      for (int i = 0; i < 18; i++) a[i] = lds64(acc + i / 9 * 2048 + i % 9 * 4096);
#pragma unroll
      for (int i = 0; i < 18; i++) x[i] = badd2(x[i], pack2(__uint_as_float(a[i].x), __uint_as_float(a[i].y)));
      if (n + 1 < NSEG) bar_arrive(2, 288);
      layernorm9<2>(x, l);
#pragma unroll
      for (int i = 0; i < 18; i++) { x[i] = badd2(x[i], bmul2(l[i], y[i])); sts32(row + st + F_X + i / 9 * 9216 + i % 9 * 128, x[i]); }
      layernorm9<2>(x, l);
#pragma unroll
      for (int i = 0; i < 18; i++) sts32(ln + st + i / 9 * 1024 + i % 9 * 2048, l[i]);
      fence_async_smem();
      bar_sync(1, 288);
    }
  }
}

constexpr uint32_t P_CH = 147456, P_CHSZ = 12800, P_H = 4352;
static_assert(P_CH + 6 * P_CHSZ <= G_BAR, "prologue smem");

template <int N>
__device__ __forceinline__ void conv_fold(float (*acc)[4], bool hi, uint32_t mine, uint32_t theirs, int bar, int cnt) {
#pragma unroll
  for (int i = 0; i < N / 2; i++) {
    uint4 v;
    v.x = __float_as_uint(hi ? acc[i][0] : acc[i + N / 2][0]); v.y = __float_as_uint(hi ? acc[i][1] : acc[i + N / 2][1]);
    v.z = __float_as_uint(hi ? acc[i][2] : acc[i + N / 2][2]); v.w = __float_as_uint(hi ? acc[i][3] : acc[i + N / 2][3]);
    sts128(mine + i * 512, v);
  }
  bar_sync(bar, cnt);
#pragma unroll
  for (int i = 0; i < N / 2; i++) {
    const uint4 v = lds128(theirs + i * 512);
    acc[i][0] = (hi ? acc[i + N / 2][0] : acc[i][0]) + __uint_as_float(v.x); acc[i][1] = (hi ? acc[i + N / 2][1] : acc[i][1]) + __uint_as_float(v.y);
    acc[i][2] = (hi ? acc[i + N / 2][2] : acc[i][2]) + __uint_as_float(v.z); acc[i][3] = (hi ? acc[i + N / 2][3] : acc[i][3]) + __uint_as_float(v.w);
  }
}
template <int N>
__device__ __forceinline__ void conv_store(const float (*acc)[4], int tile0, uint32_t su, int d, uint32_t dd) {
  const int lane = threadIdx.x & 31, g = lane >> 2, tq = lane & 3;
#pragma unroll
  for (int i = 0; i < N; i++) {
    const uint32_t ad = su + (8 + (tile0 + i) * 8 + g) * 32 + tq * 4, sw = (g & 4) << 2;
    const uint32_t lo = badd2(movmat(pack2(acc[i][0], acc[i][1])), bmul2(lds32(ad + sw), dd));
    const uint32_t hi = badd2(movmat(pack2(acc[i][2], acc[i][3])), bmul2(lds32(ad + (sw ^ 16)), dd));
    ((uint2*)g_yT)[(((tile0 + i) * 8 + g) * DM + d) * 4 + tq] = make_uint2(lo, hi);
  }
}

__device__ __forceinline__ void prologue(const Params& P, uint32_t sb) {
  const int b = bid(), tid = threadIdx.x, lane = tid & 31, warp = tid >> 5, t0 = b * 16;
  const bool isg = b >= N_CHAIN && b < N_CHAIN + N_G;
  const int nch = isg ? 2 : b < 128 ? 6 : 0, chb = b < N_CHAIN ? b * 6 : isg ? b * 2 + 256 : b * 6 - 192;
  const uint32_t tstart = clk();
  if (tid < 288) {
    if (b < 128) {
      const int c = (tid >> 1) * 4, tt = t0 + (tid & 1) * 8;
      uint2 kr[11], vr[8];
#pragma unroll
      for (int i = 0; i < 11; i++) { const int t = tt + i - 3; kr[i] = t >= 0 ? __ldg((const uint2*)(P.K + (size_t)t * DM + c)) : make_uint2(0, 0); }
#pragma unroll
      for (int i = 0; i < 8; i++) vr[i] = __ldg((const uint2*)(P.V + (size_t)(tt + i) * DM + c));
#pragma unroll
      for (int e = 0; e < 2; e++) {
        const uint4 sh = __ldg((const uint4*)(P.shift + c * 4) + e);
        const uint32_t s0 = __byte_perm(sh.x, sh.z, 0x5410), s1 = __byte_perm(sh.x, sh.z, 0x7632);
        const uint32_t s2 = __byte_perm(sh.y, sh.w, 0x5410), s3 = __byte_perm(sh.y, sh.w, 0x7632);
        uint32_t v[8];
#pragma unroll
        for (int i = 0; i < 8; i++) {
          const uint32_t k3 = e ? kr[i].y : kr[i].x, k2 = e ? kr[i + 1].y : kr[i + 1].x, k1 = e ? kr[i + 2].y : kr[i + 2].x, k0 = e ? kr[i + 3].y : kr[i + 3].x;
          v[i] = bmul2(badd2(badd2(badd2(bmul2(k3, s3), bmul2(k2, s2)), bmul2(k1, s1)), bmul2(k0, s0)), e ? vr[i].y : vr[i].x);
        }
        *(uint4*)(g_kvT + (size_t)(c + 2 * e) * KVP + tt) =
          make_uint4(__byte_perm(v[0], v[1], 0x5410), __byte_perm(v[2], v[3], 0x5410), __byte_perm(v[4], v[5], 0x5410), __byte_perm(v[6], v[7], 0x5410));
        *(uint4*)(g_kvT + (size_t)(c + 2 * e + 1) * KVP + tt) =
          make_uint4(__byte_perm(v[0], v[1], 0x7632), __byte_perm(v[2], v[3], 0x7632), __byte_perm(v[4], v[5], 0x7632), __byte_perm(v[6], v[7], 0x7632));
      }
    }
  } else if (tid < 384) {
    const int t = tid - 288;
    for (int i = t; i < 32 * nch; i += 96) asm volatile("prefetch.global.L2 [%0];" :: "l"(P.Hk + (size_t)chb * SEQ + i * 64));
    for (int i = b * 96 + t; i < 32 * DM; i += N_CTA * 96) ((uint4*)g_oacc)[i] = make_uint4(0, 0, 0, 0);
    if (b * 96 + t < 128 * 8) g_lnflag[b * 96 + t] = 0;
    if (t == 95) sts32(sb + S_GEN, ld_acquire(g_gbar));
  }
  if (warp < 12) {
    bar_arrive(10, 448);
    if (tid == 128) TS(14);
    const int ch = warp >> 1, sub = warp & 1, d = chb + ch;
    const uint32_t su = sb + P_CH + ch * P_CHSZ;
    if (ch < nch) {
      const uint32_t* hs = (const uint32_t*)(P.Hk + (size_t)d * SEQ);
#pragma unroll
      for (int q = sub * 32 + lane; q < 256; q += 64) {
        const uint4 c = __ldg((const uint4*)hs + q);
        const uint32_t prev = q ? __ldg(hs + 4 * q - 1) : 0u;
        sts128(su + P_H + 32 + q * 16, make_uint4(__byte_perm(c.x, prev, 0x7610), __byte_perm(c.y, c.x, 0x7610), __byte_perm(c.z, c.y, 0x7610), __byte_perm(c.w, c.z, 0x7610)));
        sts128(su + P_H + 4224 + q * 16, make_uint4(__byte_perm(c.x, 0, 0x1032), __byte_perm(c.y, 0, 0x1032), __byte_perm(c.z, 0, 0x1032), __byte_perm(c.w, 0, 0x1032)));
      }
      if (sub == 1 && lane == 0) sts32(su + P_CHSZ - 16, __bfloat16_as_ushort(P.Dk[d]) * 0x10001u);
      if (sub == 0 && lane < 20) sts128(su + (lane < 16 ? lane * 16 : P_H + (lane & 2) * 2096 + (lane & 1) * 16), make_uint4(0, 0, 0, 0));
    }
    bar_sync(11, 416);
    if (ch < nch) {
#pragma unroll
      for (int q = sub * 32 + lane; q < 256; q += 64) {
        const int row = (q >> 1) + 8;
        sts128(su + row * 32 + (((q & 1) ^ ((row >> 2) & 1)) << 4), __ldcg((const uint4*)(g_kvT + (size_t)d * KVP) + q));
      }
    }
    const int g = lane >> 2, tq = lane & 3;
    const uint32_t sh = su + P_H + (g & 1) * 4192 + (8 + (g >> 1) - tq) * 4;
    float acc[16][4];
#pragma unroll
    for (int i = 0; i < 16; i++) { acc[i][0] = acc[i][1] = acc[i][2] = acc[i][3] = 0.f; }
    auto u_addr = [&](int res) {
      const int row = 8 - res + ((lane >> 4) << 3) + (lane & 7);
      return su + row * 32 + ((((lane >> 3) & 1) ^ ((row >> 2) & 1)) << 4);
    };
    if (ch < nch) {
      bar_sync(1 + ch, 64);
      if (tid == 0) TS(11);
      if (sub) {
#pragma unroll 4
        for (int res = 0; res < 8; res++) {
          uint32_t b0, b1, b2, b3;
          ldsm4(b0, b1, b2, b3, u_addr(res));
          const uint32_t r0 = lds32(sh + res * 32);
          mma16(acc[0], r0, lds32(sh + res * 32 + 16), lds32(sh + res * 32 - 16), r0, b0, b1);
        }
        conv_store<1>(acc, 0, su, d, lds32(su + P_CHSZ - 16));
      }
    }
    bar_arrive(12, 416);
    if (isg && warp >= 4) { while ((int)(clk() - tstart - S1G) < 0) __nanosleep(200); load_wg(P, sb, true, warp >> 3, warp & 3); }
    if (ch < nch) {
#pragma unroll 1
      for (int res = sub * 4; res < sub * 4 + 4; res++) {
        uint32_t bf[16][2];
        const uint32_t ad = u_addr(res);
#pragma unroll
        for (int f = 0; f < 16; f += 2) ldsm4(bf[f][0], bf[f][1], bf[f + 1][0], bf[f + 1][1], ad + f * 256);
#pragma unroll
        for (int k = 0; k < 16; k++) {
          const int jj = k & 1 ? k >> 1 : 15 - (k >> 1);
          const uint32_t ah = sh + (8 * jj + res) * 32;
          const uint32_t r0 = lds32(ah), r1 = lds32(ah + 16), rm = lds32(ah - 16);
#pragma unroll
          for (int i = max(jj, 1); i < 16; i++) mma16(acc[i], r0, r1, rm, r0, bf[i - jj][0], bf[i - jj][1]);
        }
      }
      bar_sync(1 + ch, 64);
      if (tid == 0) TS(12);
      const uint32_t xb = su + P_H + lane * 16, dd = lds32(su + P_CHSZ - 16);
      conv_fold<16>(acc, sub, xb + sub * 4096, xb + (sub ^ 1) * 4096, 1 + ch, 64);
      conv_store<8>(acc, sub * 8, su, d, dd);
    }
  } else {
    for (int i = b; i < 194 + MRING * 5; i += N_CTA) {
      const int n = (i - 194) / 5, r = (i - 194) % 5, blk = i < 192 ? i / 6 * 8 + i % 6 : i < 194 ? XB_F + i - 192 : XB_M + n * 8 + r;
      const uint32_t fill = i < 194 ? 0u : SENT;
#pragma unroll 1
      for (int q = tid - 384; q < 256 && warp < 15; q += 96) {
        uint4 v = make_uint4(fill, fill, fill, fill);
        if (i >= 194 && (n == 0 || (n <= LAG && ((q ^ (q >> 3)) & 1))) && (r > 0 || q < 128)) {
          const bf16* m = P.mem0 + (max(r * 8 - 4, 0) + (q >> 5)) * 16 + ((q >> 1) & 1) * 8 + ((q >> 2) & 7);
          v.x = pack2(__bfloat162float(m[0]), __bfloat162float(m[DM])); v.y = pack2(__bfloat162float(m[2 * DM]), __bfloat162float(m[3 * DM]));
          v.z = pack2(__bfloat162float(m[4 * DM]), __bfloat162float(m[5 * DM])); v.w = pack2(__bfloat162float(m[6 * DM]), __bfloat162float(m[7 * DM]));
        }
        g_xb[blk * 512 + q] = v;
        g_xb[blk * 512 + 256 + q] = v;
      }
    }
    if (tid < 388) g_xb[XB_REF * 512 + (tid & 2) * 128 + (b & ~1) + (tid & 1)] = make_uint4(0, 0, 0, 0);
    else if (tid < 392 && b < N_GRP) g_xb[(b * 8 + 7) * 512 + (tid & 2) * 128 + (tid & 1)] = make_uint4(0, 0, 0, 0);
    if (warp < 15) { bar_arrive(9, 128); bar_sync(7, 96); }
    if (tid == 384) TS(8);
    if (warp == 12) {
      const bf16* w = lane < 6 ? (lane % 3 == 0 ? P.Wk : lane % 3 == 1 ? P.Wv : P.Wq) + (((b >> 5) * 2 + lane / 3) * 32 + (b & 31)) * 2048
                               : (lane < 8 ? P.Wo + (lane - 6) * (9 * 131072) : P.X) + b * 2048;
      bar_sync(10, 448);
      uint32_t t = clk() + P.dly[19];
#pragma unroll 1
      for (int st = 0; st < 9 && b < N_CHAIN; st++) {
#pragma unroll 1
        for (int i = 0; i < 9; i++, t += PACE) {
          wait_until(t, 0);
          if (lane == st) asm volatile("cp.async.bulk.prefetch.L2.global [%0], 4096;" :: "l"(w + i * (lane < 6 ? 262144 : 131072)) : "memory");
        }
      }
      if (lane == 0) TS(10);
    } else if (warp == 15) {
      bar_sync(10, 448);
      if (lane == 0) { grid_arrive(0); if (nch) grid_wait(0, lds32(sb + S_GEN)); }
      __syncwarp();
      bar_arrive(11, 416);
      if (lane == 0) TS(1);
      bar_sync(9, 128);
      bar_sync(12, 416);
      if (lane == 0) { TS(16); grid_arrive(2); TS(17); }
    } else if (lane == 0) {
      if (warp == 13 || (warp == 14 && b < N_GRP)) {
        uint32_t* p = (uint32_t*)(g_xb + (warp == 13 ? XB_REF * 512 + b : (b * 8 + 7) * 512));
        int votes = 0;
        for (int rep = 0; rep < 24 && abs(votes) < 7; rep++) {
          uint32_t v0, v1, c0, c1;
          asm volatile("atom.relaxed.gpu.global.add.u32 %0, [%4], 0;\n atom.relaxed.gpu.global.add.u32 %1, [%5], 0;\n"
                       "{.reg .pred p; setp.eq.u32 p, %0, 0x7ffffff3; @p trap; mov.u32 %2, %%clock; setp.eq.u32 p, %1, 0x7ffffff3; @p trap; mov.u32 %3, %%clock;}"
                       : "=&r"(v0), "=&r"(v1), "=&r"(c0), "=&r"(c1) : "l"(p + (rep & 1) * 1024), "l"(p + ((rep & 1) ^ 1) * 1024) : "memory");
          votes += ((c1 - c0 > 80u) == (rep & 1)) ? 1 : -1;
        }
        if (warp == 13) { g_side[b] = votes > 0; TS(9); } else g_near[b] = votes > 0;
      }
    }
    __syncwarp();
    if (warp > 12 && b < N_CHAIN) {
      while ((int)(clk() - tstart - S1DLY) < 0) __nanosleep(200);
      for (int k = warp - 13; k < 8; k += 3) load_wg(P, sb, true, 1 - k / 4, k & 3);
    }
  }
  __syncthreads();
  if (tid == 511) { grid_arrive(1); TS(18); }
  if (tid == 0) TS(2);
}

template <int R> __device__ __forceinline__ void ln_tiles(const Params& P, uint32_t sb) {
  const int lane = threadIdx.x & 31, w = (threadIdx.x >> 5) & (16 / R - 1), half = R == 1 ? 0 : threadIdx.x >> 8, u = N_CTA - 1 - bid();
  const int first = R == 1 ? u : 46 - 2 * u + half, step = R == 1 ? 4 : 40, last = R == 1 ? 8 : 128;
  const uint32_t raw = sb + P_CH + half * (18432 + Y_ROWS), mb = sb + T_BAR + (R - 1 + half) * 8;
  const bool lead = w == 16 / R - 1 && lane == 0;
  auto load_y = [&](const bf16* src, int tile) {
    fence_async_global();
    mbar_expect(mb, 18432);
    bulk_load(raw, src + (size_t)tile * 16 * DM, 18432, mb);
  };
  if (R == 2 && u >= N_F && w < 6) load_wg(P, sb, true, w >> 1, half * 2 + (w & 1));
#pragma unroll 1
  for (int tile = first, real = R - 1, ph = 0; tile < last; tile += real * step, real = 1, ph ^= 1) {
    uint32_t x[9 * R], l[9 * R], y[9 * R];
    const bool ts = threadIdx.x == 0 && (R == 1 ? tile == first : u > 3 && tile == first + step);
    if (ts) TS(26);
#pragma unroll
    for (int i = 0; i < 9 * R; i++) x[i] = __ldg((const uint32_t*)(P.X + (size_t)(tile * 16 + w + i / 9 * 8) * DM) + i % 9 * 32 + lane);
    layernorm9<R>(x, l);
    if (tile == first && lead) {
      if (real) grid_wait(3 - R, lds32(sb + S_GEN));
      if (R == 1 || u > 3) TS(13);
      load_y(real ? g_yT : P.Hk, tile);
    }
    bar_sync(13 + half, 512 / R);
    mbar_wait(mb, ph);
    if (ts) TS(28);
    y_rows<R>(y, raw, raw + 18432, w, 13 + half);
    if (ts) TS(29);
    if (lead && real && tile + step < last) { fence_async_smem(); load_y(g_yT, tile + step); }
    __syncwarp();
#pragma unroll
    for (int i = 0; i < 9 * R; i++) x[i] = badd2(x[i], bmul2(l[i], y[i]));
    layernorm9<R>(x, l);
    if (ts && l[0] != 0x12345) TS(30);
#pragma unroll
    for (int r = 0; r < R; r++) store_ln_row(0, tile * 16 + w + r * 8, l + r * 9);
    if (R == 1) {
      __syncthreads();
      if (threadIdx.x == 32 && real) { if (tile < 4) TS(19); st_release(g_lnflag + tile * 8, 1); if (tile < 4) TS(20); }
      __syncwarp();
    }
    if (ts) TS(31);
  }
  if (R == 2) {
    __syncthreads();
    if (threadIdx.x >= 506) {
      asm volatile("fence.acq_rel.gpu;" ::: "memory");
      st_relaxed_if(g_lnflag + ((first ^ (lane & 1)) + (lane - 26) / 2 * step) * 8, 1, true);
    }
    __syncwarp();
    fence_async_smem();
    if (threadIdx.x == 0) TS(15);
  }
}

__global__ void __cluster_dims__(2, 1, 1) __launch_bounds__(512, 1) k_main(const __grid_constant__ Params P) {
  extern __shared__ __align__(1024) unsigned char smem[];
  const uint32_t sb = (uint32_t)__cvta_generic_to_shared(smem);
  const int b = bid(), wg = threadIdx.x >> 7;
  if ((threadIdx.x & 127) == 0) TS(0);
  if (threadIdx.x == 480) {
    if ((sb & 0xFFFFFF) != SBASE) __trap();
    for (int i = 0; i < 6; i++) mbar_init(sb + W_BAR + i * 8, 1);
    if (b < N_CHAIN) {
      mbar_init(sb + CB_FULL, 1); mbar_init(sb + CB_FULL + 8, 1);
      mbar_init(sb + CB_REF, 1);
      mbar_init(sb + CB_SX, 1); mbar_init(sb + CB_OX, 1); mbar_init(sb + CB_XX, 1); mbar_init(sb + CB_Q, 1); mbar_init(sb + CB_VF, 1); mbar_init(sb + CB_VF + 8, 1);
      sts32(sb + C_BAD, 0);
      for (int i = 0; i < 11; i++) mbar_init(sb + CB_M + i * 8, i == 0 ? 5 : i == 5 ? 2 : 1);
    } else if (b < N_CHAIN + N_G) {
      for (int i = 0; i < 9; i++) { mbar_init(sb + G_BAR + i * 8, 2); mbar_init(sb + G_BAR + 128 + i * 8, 8); }
    } else if (b < N_CHAIN + N_G + N_O) {
      for (int i = 0; i < 5; i++) { mbar_init(sb + O_BAR + i * 8, 1); mbar_init(sb + O_BAR + 128 + i * 8, 12); }
      for (int i = 0; i < 6; i++) mbar_init(sb + OB_ST + i * 8, 1);
    } else {
      mbar_init(sb + F_BAR, 1); mbar_init(sb + F_BAR + 8, 1);
    }
    asm volatile("fence.mbarrier_init.release.cluster;" ::: "memory");
    fence_async_smem();
  }
  __syncwarp();
  asm volatile("barrier.cluster.arrive.relaxed.aligned;" ::: "memory");
  prologue(P, sb);
  asm volatile("barrier.cluster.wait.aligned;" ::: "memory");
  fence_async_smem();
  if (b >= 128) ln_tiles<1>(P, sb);
  if (b >= N_CHAIN + N_G) ln_tiles<2>(P, sb);
  if ((threadIdx.x & 127) == 0) TS(3);
  if (b < N_CHAIN) {
    if (wg < 2) { reg_inc<200>(); chain_proj(P, sb); }
    else if (wg == 2) { reg_dec<ATTR>(); chain_attn(P, sb); }
    else { reg_dec<112 - ATTR>(); chain_aux(P, sb); }
  } else if (NOBULK) {
    {
      if (wg == 0) {
        float d[4] = {0.f, 0.f, 0.f, 0.f};
        for (int n = 0; n < STEPS - 1; n++) {
          const uint32_t* f = g_fl + FL_TICK;
          uint32_t x;
          do { for (int k = 0; k < 16; k++) mma16(d, 0, 0, 0, 0, 0, 0); asm volatile("ld.relaxed.gpu.global.u32 %0, [%1];" : "=r"(x) : "l"(f) : "memory"); } while ((x >> 24) <= n);
          const int q = (b - N_CHAIN) * 4 + (threadIdx.x >> 5);
          if (n + 5 >= MRING && q < 80) fill16((uint4*)g_mimg + (uint32_t)(((n + 5) % MRING) * 4096 + q * 32 + (threadIdx.x & 31)), SENT);
        }
        if (d[0] == 1.f) P.out[0] = __float2bfloat16(0.f);
      }
    }
  } else if (b < N_CHAIN + N_G) {
    if (wg == 0) { reg_inc<232>(); g_math<0>(P, sb); }
    else if (wg == 1) { reg_inc<232>(); g_math<1>(P, sb); }
    else if (wg == 2) { reg_dec<24>(); g_aux(P, sb); }
    else { reg_dec<24>(); g_load(P, sb); }
  } else if (b < N_CHAIN + N_G + N_O) {
    if (wg == 0) { reg_inc<160>(); o_math<0>(P, sb); }
    else if (wg == 1) { reg_inc<160>(); o_math<1>(P, sb); }
    else if (wg == 2) { reg_inc<160>(); o_math<2>(P, sb); }
    else { reg_dec<32>(); o_aux(P, sb); }
  } else {
    f_role(P, sb);
  }
}

}

extern "C" void kernel_launch(void* const* d_in, const int* in_sizes, int n_in, void* d_out, int out_size) {
  typedef CUresult (*Encode)(CUtensorMap*, CUtensorMapDataType, cuuint32_t, void*, const cuuint64_t*, const cuuint64_t*, const cuuint32_t*, const cuuint32_t*,
                             CUtensorMapInterleave, CUtensorMapSwizzle, CUtensorMapL2promotion, CUtensorMapFloatOOBfill);
  static Encode encode = nullptr;
  if (!encode) cudaGetDriverEntryPoint("cuTensorMapEncodeTiled", (void**)&encode, cudaEnableDefault);
  Params P;
  for (int i = 0; i < 11; i++) {
    const bool wo = i == 6 || i == 7;
    const cuuint64_t cols = wo ? DM : HD, rows = HD + DM - cols, pitch = cols * 2;
    const cuuint64_t dim[4][5] = {{cols, 2, 8, 2, 18}, {cols, 16, 1, 1, rows / 16}, {cols, 2, 4, 4, rows / 32}, {64, 16, 64, 2, 18}};
    const cuuint64_t stride[4][4] = {{8 * pitch, pitch, 16 * pitch, 32 * pitch}, {pitch, pitch, pitch, 16 * pitch},
                                     {pitch, 8 * pitch, 2 * pitch, 32 * pitch}, {pitch, 128, 16 * pitch, 32 * pitch}};
    const cuuint32_t box[4][5] = {{64, 2, 8, 1, 18}, {64, 16, 1, 1, 1}, {64, 2, 4, 2, 1}, {64, 16, 2, 1, 18}}, one[5] = {1, 1, 1, 1, 1};
    const int k = i < 3 ? 0 : i < 7 ? 1 : i < 8 ? 2 : 3;
    encode(&P.map[i], CU_TENSOR_MAP_DATA_TYPE_BFLOAT16, 5, d_in[wo ? 11 : 8 + (i & 7) % 3], dim[k], stride[k], box[k], one,
           CU_TENSOR_MAP_INTERLEAVE_NONE, CU_TENSOR_MAP_SWIZZLE_128B, CU_TENSOR_MAP_L2_PROMOTION_L2_128B, CU_TENSOR_MAP_FLOAT_OOB_FILL_NONE);
  }
  P.X = (const bf16*)d_in[0]; P.K = (const bf16*)d_in[1]; P.V = (const bf16*)d_in[2];
  P.shift = (const bf16*)d_in[3]; P.Hk = (const bf16*)d_in[4]; P.Dk = (const bf16*)d_in[5];
  P.mem0 = (const bf16*)d_in[7];
  P.Wq = (const bf16*)d_in[8]; P.Wk = (const bf16*)d_in[9]; P.Wv = (const bf16*)d_in[10]; P.Wo = (const bf16*)d_in[11];
  P.out = (bf16*)d_out;
  for (int i = 0; i < 24; i++) P.dly[i] = h_dly[i];
  cudaFuncSetAttribute(k_main, cudaFuncAttributeMaxDynamicSharedMemorySize, SMEM_BYTES);
  k_main<<<N_CTA, 512, SMEM_BYTES>>>(P);
}
```

```cpp
#include <cuda.h>
#include <cuda_runtime.h>
#include <cuda_bf16.h>
#include <stdint.h>

namespace {

typedef __nv_bfloat16 bf16;

constexpr int SEQ = 2048, DM = 576, HD = 4096, NSEG = 64;
#define PLACE 1
#define LAGV 7
constexpr int LAG = LAGV, STEPS = NSEG + LAG, RING = 8, QRING = 4;
static_assert(LAG < RING, "ring");
constexpr int N_CHAIN = 64, N_G = 48, N_O = 18, N_F = 2;
constexpr uint32_t SBASE = 1024;
constexpr uint32_t SENT = 0xFFFFFFFFu;
constexpr int SPIN_MAX = 1 << 22;

__device__ __forceinline__ uint32_t bid() {
  const uint32_t b = blockIdx.x;
  return b < 6 ? b + 106 : b < 8 ? b + 122 : b < 114 ? b - 8 : b < 130 ? b - 2 : b;
}
__device__ __forceinline__ uint32_t chain_id() { return blockIdx.x - (PLACE ? 8 : 0); }
constexpr int KVP = SEQ + 64;
__device__ __align__(1024) bf16 g_kvT[DM * KVP];
__device__ __align__(1024) bf16 g_yT[DM * SEQ];
__device__ __align__(1024) unsigned char g_lnimg[2 * NSEG * 9 * 4096];
__device__ __align__(1024) unsigned char g_qkv[QRING * N_CHAIN * 24576];
__device__ __align__(1024) unsigned char g_oimg[RING * N_CHAIN * 8192];
constexpr int ARING = 16;
static_assert(ARING >= LAG + 9, "accumulator ring");
__device__ __align__(1024) float g_oacc[ARING * 64 * DM];
constexpr int MRING = LAG + 4, N_GRP = 32 + MRING + 1;
constexpr int XB_M = 256, XB_F = XB_M + MRING * 8, XB_REF = XB_F + 2, N_CTA = N_CHAIN + N_G + N_O + N_F;
__device__ __align__(65536) uint4 g_xb[N_GRP * 4096];
#define g_mimg ((uint32_t*)(g_xb + XB_M * 512))
__device__ uint32_t g_near[N_GRP];
__device__ uint32_t g_side[N_CTA];
__device__ __align__(128) uint32_t g_gbar[3 * 32];
constexpr int FL_G = 0, FL_F = 96 * 8, FL_OCNT = FL_F + 2 * 8, OCRING = 16, FL_TICK = 992, FL_O = 2048, FL_SYNC = FL_O + 128;
static_assert(FL_OCNT + OCRING * 8 <= FL_TICK, "flag block");
#define g_fl ((uint32_t*)(g_xb + XB_F * 512))
__device__ __align__(1024) uint32_t g_lnflag[128 * 8];
#define TS(slot)

#define OTURN 2
#define LOCK0 3
#define FASTG 0
#define NOBULK 0
#define WFENCE 0
#define QPOS 0
#define VE 4
#define OGAP 2
#define NOCHAIN 0
#define BFENCE 2
#define ABL 0
#define ATTR 80
#define CNT(slot, tries)
#define T3(slot)
#define TR(slot)
#define TRV(slot, val)
#define TRD(slot, dep)
#define TRSYNC()
#define TRDUMP(n)
#define CLK(t) "{.reg .b64 x; .reg .b32 h; mov.u64 x, %%clock64; mov.b64 {" t ", h}, x;}"
__device__ __forceinline__ uint32_t clk() { uint32_t t; asm volatile(CLK("%0") : "=r"(t) :: "memory"); return t; }
__device__ __forceinline__ void wait_until(uint32_t t0, uint32_t d) {
  asm volatile("{.reg .pred p; .reg .u32 t;\n"
               "W: " CLK("t") " sub.u32 t, t, %0; setp.lt.s32 p, t, 0; @p bra.uni W;}"
               :: "r"(t0 + d) : "memory");
}
__device__ __forceinline__ uint32_t pack2(float lo, float hi) {
  uint32_t r; asm("cvt.rn.bf16x2.f32 %0, %1, %2;" : "=r"(r) : "f"(hi), "f"(lo)); return r;
}
__device__ __forceinline__ float bf_lo(uint32_t v) { return __uint_as_float(v << 16); }
__device__ __forceinline__ float bf_hi(uint32_t v) { return __uint_as_float(v & 0xFFFF0000u); }

__device__ __forceinline__ uint4 ld_relaxed4(const void* p) {
  uint4 v; asm volatile("ld.relaxed.gpu.global.v4.u32 {%0,%1,%2,%3}, [%4];" : "=r"(v.x), "=r"(v.y), "=r"(v.z), "=r"(v.w) : "l"(p) : "memory"); return v;
}
__device__ __forceinline__ void st_b128(void* p, uint32_t a, uint32_t b, uint32_t c, uint32_t d) {
  asm volatile("{.reg .b128 v; mov.b128 v, {%1,%2,%3,%4}; st.relaxed.gpu.global.b128 [%0], v;}" :: "l"(p), "r"(a), "r"(b), "r"(c), "r"(d) : "memory");
}
__device__ __forceinline__ void reload_b128(uint4& v, const void* p, uint32_t again) {
  asm volatile("{.reg .pred p; .reg .b128 v; setp.ne.u32 p, %5, 0; mov.b128 v, {%0,%1,%2,%3};\n"
               "@p ld.relaxed.gpu.global.b128 v, [%4]; mov.b128 {%0,%1,%2,%3}, v;}"
    : "+r"(v.x), "+r"(v.y), "+r"(v.z), "+r"(v.w) : "l"(p), "r"(again) : "memory");
}
__device__ __forceinline__ void reload4(uint4& v, const void* p, uint32_t again) {
  asm volatile("{.reg .pred p; setp.ne.u32 p, %5, 0; @p ld.relaxed.gpu.global.v4.u32 {%0,%1,%2,%3}, [%4];}"
    : "+r"(v.x), "+r"(v.y), "+r"(v.z), "+r"(v.w) : "l"(p), "r"(again) : "memory");
}
__device__ __forceinline__ void st_relaxed4(void* p, uint32_t a, uint32_t b, uint32_t c, uint32_t d) {
  asm volatile("st.relaxed.gpu.global.v4.u32 [%0], {%1,%2,%3,%4};" :: "l"(p), "r"(a), "r"(b), "r"(c), "r"(d) : "memory");
}
__device__ __forceinline__ void st_relaxed_if(void* p, uint32_t a, bool on) {
  asm volatile("{.reg .pred p; setp.ne.u32 p, %2, 0; @p st.relaxed.gpu.global.u32 [%0], %1;}" :: "l"(p), "r"(a), "r"((uint32_t)on) : "memory");
}
__device__ __forceinline__ uint32_t ld_acquire(const uint32_t* p) {
  uint32_t v; asm volatile("ld.acquire.gpu.global.u32 %0, [%1];" : "=r"(v) : "l"(p) : "memory"); return v;
}
__device__ __forceinline__ void st_release(uint32_t* p, uint32_t v) {
  asm volatile("st.release.gpu.global.u32 [%0], %1;" :: "l"(p), "r"(v) : "memory");
}
__device__ __forceinline__ void bulk_reduce(float* dst, uint32_t src, uint32_t bytes) {
  asm volatile("cp.reduce.async.bulk.global.shared::cta.bulk_group.add.f32 [%0], [%1], %2;" :: "l"(dst), "r"(src), "r"(bytes) : "memory");
}
__device__ __forceinline__ void bulk_done_inc(uint32_t* p) {
  asm volatile("cp.async.bulk.wait_group 0;\n"
               "fence.proxy.async.global;\nfence.release.gpu;\n"
               "red.relaxed.gpu.global.add.u32 [%0], 1;\nred.relaxed.gpu.global.add.u32 [%0+4096], 1;" :: "l"(p) : "memory");
}
__device__ __forceinline__ void flag_release(uint32_t* p, uint32_t v) {
  asm volatile("fence.release.gpu;\nst.relaxed.gpu.global.u32 [%0], %1;\nst.relaxed.gpu.global.u32 [%0+4096], %1;" :: "l"(p), "r"(v) : "memory");
}
__device__ __forceinline__ void spin_guard(int& it) {
  asm volatile("{.reg .pred p; add.s32 %0, %0, 1; setp.gt.s32 p, %0, %1; @p trap;}" : "+r"(it) : "n"(SPIN_MAX));
}
__device__ __forceinline__ void wait_flag(const uint32_t* p, uint32_t v) {
  int it = 0;
  while (ld_acquire(p) < v) spin_guard(it);
}
__device__ __forceinline__ void wait_flags(const uint32_t* p, uint32_t v) {
  int it = 0;
  while (true) {
    uint32_t x; asm volatile("ld.relaxed.gpu.global.u32 %0, [%1];" : "=r"(x) : "l"(p) : "memory");
    if (__all_sync(~0u, x >= v)) break;
    spin_guard(it);
  }
  asm volatile("fence.acquire.gpu;" ::: "memory");
}
__device__ __forceinline__ uint32_t timer_offset() {
  uint32_t g0, g;
  asm volatile("mov.u32 %0, %%globaltimer_lo;" : "=r"(g0) :: "memory");
  do { asm volatile("mov.u32 %0, %%globaltimer_lo;" : "=r"(g) :: "memory"); } while (g == g0);
  return (g >> 5) * 58 - clk();
}
__device__ __forceinline__ void grid_arrive(int i) {
  asm volatile("red.release.gpu.global.add.u32 [%0], %1;" :: "l"(g_gbar + i * 32), "r"(bid() ? 1u : 257u - N_CTA) : "memory");
}
__device__ __forceinline__ void grid_wait(int i, uint32_t gen) {
  int it = 0;
  while (((ld_acquire(g_gbar + i * 32) ^ gen) >> 8) == 0) spin_guard(it);
}
__device__ __forceinline__ bool elect() {
  uint32_t r; asm volatile("{.reg .pred p; elect.sync _|p, -1; selp.u32 %0, 1, 0, p;}" : "=r"(r)); return r;
}
__device__ __forceinline__ void bar_sync(int id, int cnt) { asm volatile("bar.sync %0, %1;" :: "r"(id), "r"(cnt) : "memory"); }
__device__ __forceinline__ void bar_arrive(int id, int cnt) { asm volatile("bar.arrive %0, %1;" :: "r"(id), "r"(cnt) : "memory"); }
template <int id, int cnt> __device__ __forceinline__ void bar_arrive_after(uint32_t a, uint32_t b) {
  asm volatile("{.reg .pred p; setp.ne.u32 p, %2, 0xfff12345; setp.ne.and.u32 p, %3, 0xfff12345, p; @p bar.arrive %0, %1;}" :: "n"(id), "n"(cnt), "r"(a), "r"(b) : "memory");
}
template <int id, int cnt> __device__ __forceinline__ void bar_sync_after(uint32_t a) {
  asm volatile("{.reg .pred p; setp.ne.u32 p, %2, 0xfff12345; @p bar.sync %0, %1;}" :: "n"(id), "n"(cnt), "r"(a) : "memory");
}
__device__ __forceinline__ void fence_async_smem() { asm volatile("fence.proxy.async.shared::cta;" ::: "memory"); }
__device__ __forceinline__ void fence_async_global() { asm volatile("fence.proxy.async.global;" ::: "memory"); }
__device__ __forceinline__ void mbar_init(uint32_t mb, int cnt) { asm volatile("mbarrier.init.shared::cta.b64 [%0], %1;" :: "r"(mb), "r"(cnt) : "memory"); }
__device__ __forceinline__ void mbar_arrive(uint32_t mb) { asm volatile("mbarrier.arrive.shared::cta.b64 _, [%0];" :: "r"(mb) : "memory"); }
__device__ __forceinline__ void mbar_arrive_after(uint32_t mb, uint32_t a, uint32_t lane) {
  asm volatile("{.reg .pred p; setp.ne.u32 p, %1, 0xfff12345; setp.eq.and.u32 p, %2, 0, p; @p mbarrier.arrive.shared::cta.b64 _, [%0];}" :: "r"(mb), "r"(a), "r"(lane) : "memory");
}
__device__ __forceinline__ void mbar_expect(uint32_t mb, uint32_t bytes) {
  asm volatile("mbarrier.arrive.expect_tx.shared::cta.b64 _, [%0], %1;" :: "r"(mb), "r"(bytes) : "memory");
}
__device__ __forceinline__ void mbar_wait_guard(uint32_t mb, uint32_t parity) {
  uint32_t ok; int it = 0;
  while (true) {
    asm volatile("{.reg .pred p; mbarrier.try_wait.parity.shared::cta.b64 p, [%1], %2; selp.u32 %0, 1, 0, p;}" : "=r"(ok) : "r"(mb), "r"(parity) : "memory");
    if (ok) break;
    spin_guard(it);
  }
}
__device__ __forceinline__ void mbar_wait(uint32_t mb, uint32_t parity) {
  asm volatile("{.reg .pred p;\nW: mbarrier.try_wait.parity.shared::cta.b64 p, [%0], %1;\n@!p bra W;}" :: "r"(mb), "r"(parity) : "memory");
}
__device__ __forceinline__ void bulk_load(uint32_t dst, const void* src, uint32_t bytes, uint32_t mb) {
  asm volatile("cp.async.bulk.shared::cluster.global.mbarrier::complete_tx::bytes [%0], [%1], %2, [%3];" :: "r"(dst), "l"(src), "r"(bytes), "r"(mb) : "memory");
}
__device__ __forceinline__ void bulk_store(void* dst, uint32_t src, uint32_t bytes) {
  asm volatile("cp.async.bulk.global.shared::cta.bulk_group [%0], [%1], %2;" :: "l"(dst), "r"(src), "r"(bytes) : "memory");
}
__device__ __forceinline__ void cp_async16(uint32_t dst, const void* src) {
  asm volatile("cp.async.cg.shared.global [%0], [%1], 16;" :: "r"(dst), "l"(src) : "memory");
}
__device__ __forceinline__ void cp_async_wait_all() { asm volatile("cp.async.wait_all;" ::: "memory"); }
__device__ __forceinline__ uint32_t mapa(uint32_t a, uint32_t rank) {
  uint32_t r; asm("mapa.shared::cluster.u32 %0, %1, %2;" : "=r"(r) : "r"(a), "r"(rank)); return r;
}
__device__ __forceinline__ void st_async4(uint32_t dst, float a, float b, float c, float d, uint32_t mb) {
  asm volatile("st.async.shared::cluster.mbarrier::complete_tx::bytes.v4.f32 [%0], {%1,%2,%3,%4}, [%5];" :: "r"(dst), "f"(a), "f"(b), "f"(c), "f"(d), "r"(mb) : "memory");
}
__device__ __forceinline__ void st_async2(uint32_t dst, float a, float b, uint32_t mb) {
  asm volatile("st.async.shared::cluster.mbarrier::complete_tx::bytes.v2.f32 [%0], {%1,%2}, [%3];" :: "r"(dst), "f"(a), "f"(b), "r"(mb) : "memory");
}
__device__ __forceinline__ void st_async1(uint32_t dst, uint32_t a, uint32_t mb) {
  asm volatile("st.async.shared::cluster.mbarrier::complete_tx::bytes.u32 [%0], %1, [%2];" :: "r"(dst), "r"(a), "r"(mb) : "memory");
}
__device__ __forceinline__ uint4 lds128(uint32_t a) {
  uint4 v; asm volatile("ld.shared.v4.u32 {%0,%1,%2,%3}, [%4];" : "=r"(v.x), "=r"(v.y), "=r"(v.z), "=r"(v.w) : "r"(a) : "memory"); return v;
}
__device__ __forceinline__ uint2 lds64(uint32_t a) {
  uint2 v; asm volatile("ld.shared.v2.u32 {%0,%1}, [%2];" : "=r"(v.x), "=r"(v.y) : "r"(a) : "memory"); return v;
}
__device__ __forceinline__ uint32_t lds32(uint32_t a) {
  uint32_t v; asm volatile("ld.shared.u32 %0, [%1];" : "=r"(v) : "r"(a) : "memory"); return v;
}
__device__ __forceinline__ void sts128(uint32_t a, uint4 v) {
  asm volatile("st.shared.v4.u32 [%0], {%1,%2,%3,%4};" :: "r"(a), "r"(v.x), "r"(v.y), "r"(v.z), "r"(v.w) : "memory");
}
__device__ __forceinline__ void sts64(uint32_t a, uint32_t x, uint32_t y) {
  asm volatile("st.shared.v2.u32 [%0], {%1,%2};" :: "r"(a), "r"(x), "r"(y) : "memory");
}
__device__ __forceinline__ void sts32(uint32_t a, uint32_t x) { asm volatile("st.shared.u32 [%0], %1;" :: "r"(a), "r"(x) : "memory"); }
__device__ __forceinline__ void ldsm4(uint32_t& r0, uint32_t& r1, uint32_t& r2, uint32_t& r3, uint32_t a) {
  asm volatile("ldmatrix.sync.aligned.m8n8.x4.shared.b16 {%0,%1,%2,%3}, [%4];" : "=r"(r0), "=r"(r1), "=r"(r2), "=r"(r3) : "r"(a) : "memory");
}
__device__ __forceinline__ void ldsm4t(uint32_t& r0, uint32_t& r1, uint32_t& r2, uint32_t& r3, uint32_t a) {
  asm volatile("ldmatrix.sync.aligned.m8n8.x4.trans.shared.b16 {%0,%1,%2,%3}, [%4];" : "=r"(r0), "=r"(r1), "=r"(r2), "=r"(r3) : "r"(a) : "memory");
}
__device__ __forceinline__ void stsm4(uint32_t a, uint32_t r0, uint32_t r1, uint32_t r2, uint32_t r3) {
  asm volatile("stmatrix.sync.aligned.m8n8.x4.shared.b16 [%0], {%1,%2,%3,%4};" :: "r"(a), "r"(r0), "r"(r1), "r"(r2), "r"(r3) : "memory");
}
__device__ __forceinline__ uint32_t movmat(uint32_t a) {
  uint32_t d; asm volatile("movmatrix.sync.aligned.m8n8.trans.b16 %0, %1;" : "=r"(d) : "r"(a)); return d;
}
__device__ __forceinline__ void mma16(float* d, uint32_t a0, uint32_t a1, uint32_t a2, uint32_t a3, uint32_t b0, uint32_t b1) {
  asm volatile("mma.sync.aligned.m16n8k16.row.col.f32.bf16.bf16.f32 {%0,%1,%2,%3}, {%4,%5,%6,%7}, {%8,%9}, {%0,%1,%2,%3};"
    : "+f"(d[0]), "+f"(d[1]), "+f"(d[2]), "+f"(d[3]) : "r"(a0), "r"(a1), "r"(a2), "r"(a3), "r"(b0), "r"(b1));
}
__device__ __forceinline__ void mma8(float* d, uint32_t a0, uint32_t a1, uint32_t b0) {
  asm volatile("mma.sync.aligned.m16n8k8.row.col.f32.bf16.bf16.f32 {%0,%1,%2,%3}, {%4,%5}, {%6}, {%0,%1,%2,%3};"
    : "+f"(d[0]), "+f"(d[1]), "+f"(d[2]), "+f"(d[3]) : "r"(a0), "r"(a1), "r"(b0));
}
__device__ __forceinline__ float rcp(float x) { float r; asm("rcp.approx.ftz.f32 %0, %1;" : "=f"(r) : "f"(x)); return r; }
__device__ __forceinline__ float ex2(float x) { float r; asm("ex2.approx.ftz.f32 %0, %1;" : "=f"(r) : "f"(x)); return r; }

__host__ __device__ constexpr uint64_t mkdesc(uint32_t off, uint32_t lbo, uint32_t sbo, uint32_t swz) {
  return (uint64_t)((SBASE + off) >> 4) | ((uint64_t)(lbo >> 4) << 16) | ((uint64_t)(sbo >> 4) << 32) | ((uint64_t)swz << 62);
}
__host__ __device__ constexpr uint64_t desc_sw128(uint32_t off) { return mkdesc(off, 16, 1024, 1); }
__host__ __device__ constexpr uint64_t desc_n16(uint32_t off) { return mkdesc(off, 256, 128, 0); }
__host__ __device__ constexpr uint64_t desc_m(uint32_t off) { return mkdesc(off, 16, 256, 3); }

__host__ __device__ constexpr uint64_t desc_sw64(uint32_t off) { return mkdesc(off, 16, 512, 2); }

__device__ __forceinline__ void wg_fence() { asm volatile("wgmma.fence.sync.aligned;" ::: "memory"); }
__device__ __forceinline__ void wg_commit() { asm volatile("wgmma.commit_group.sync.aligned;" ::: "memory"); }
template <int N> __device__ __forceinline__ void wg_wait() { asm volatile("wgmma.wait_group.sync.aligned %0;" :: "n"(N) : "memory"); }

#define ACC8(d) "+f"(d[0]), "+f"(d[1]), "+f"(d[2]), "+f"(d[3]), "+f"(d[4]), "+f"(d[5]), "+f"(d[6]), "+f"(d[7])
#define ACC32(d) ACC8(d), ACC8((d + 8)), ACC8((d + 16)), ACC8((d + 24))
#define R8 "{%0,%1,%2,%3,%4,%5,%6,%7}"
#define R32 "{%0,%1,%2,%3,%4,%5,%6,%7,%8,%9,%10,%11,%12,%13,%14,%15,%16,%17,%18,%19,%20,%21,%22,%23,%24,%25,%26,%27,%28,%29,%30,%31}"
template <int SD> __device__ __forceinline__ void wg_rs16(float* d, const uint32_t* a, uint64_t db) {
  asm volatile("wgmma.mma_async.sync.aligned.m64n16k16.f32.bf16.bf16 " R8 ", {%8,%9,%10,%11}, %12, %13, 1, 1, 1;"
    : ACC8(d) : "r"(a[0]), "r"(a[1]), "r"(a[2]), "r"(a[3]), "l"(db), "n"(SD));
}
template <int SD> __device__ __forceinline__ void wg_ss16(float* d, uint64_t da, uint64_t db) {
  asm volatile("wgmma.mma_async.sync.aligned.m64n16k16.f32.bf16.bf16 " R8 ", %8, %9, %10, 1, 1, 1, 1;"
    : ACC8(d) : "l"(da), "l"(db), "n"(SD));
}
template <int SD, uint64_t DA, uint64_t DB> __device__ __forceinline__ void wg_ss16o(float* d, uint32_t oa, uint32_t ob) {
  asm volatile("{.reg .b32 x, y; .reg .b64 a, b; add.u32 x, %8, %10; add.u32 y, %9, %12; mov.b64 a, {x, %11}; mov.b64 b, {y, %13};\n"
               "wgmma.mma_async.sync.aligned.m64n16k16.f32.bf16.bf16 " R8 ", a, b, %14, 1, 1, 1, 1;}"
    : ACC8(d) : "r"(oa), "r"(ob), "n"((uint32_t)DA), "n"((uint32_t)(DA >> 32)), "n"((uint32_t)DB), "n"((uint32_t)(DB >> 32)), "n"(SD));
}
template <int SD> __device__ __forceinline__ void wg_rs64(float* d, const uint32_t* a, uint64_t db) {
  asm volatile("wgmma.mma_async.sync.aligned.m64n64k16.f32.bf16.bf16 " R32 ", {%32,%33,%34,%35}, %36, %37, 1, 1, 0;"
    : ACC32(d) : "r"(a[0]), "r"(a[1]), "r"(a[2]), "r"(a[3]), "l"(db), "n"(SD));
}
template <int SD> __device__ __forceinline__ void wg_ss64(float* d, uint64_t da, uint64_t db) {
  asm volatile("wgmma.mma_async.sync.aligned.m64n64k16.f32.bf16.bf16 " R32 ", %32, %33, %34, 1, 1, 1, 0;"
    : ACC32(d) : "l"(da), "l"(db), "n"(SD));
}
#define WG_RSO(NAME, SHAPE, REGS, ACC, A, TB) \
template <int SD, uint64_t DB> __device__ __forceinline__ void NAME(float* d, uint32_t a0, uint32_t a1, uint32_t a2, uint32_t a3, uint32_t ob) { \
  asm volatile("{.reg .b64 b; mov.b64 b, {" A(4) ", " A(5) "};\nwgmma.mma_async.sync.aligned." SHAPE ".f32.bf16.bf16 " REGS \
               ", {" A(0) "," A(1) "," A(2) "," A(3) "}, b, " A(6) ", 1, 1, " TB ";}" \
    : ACC(d) : "r"(a0), "r"(a1), "r"(a2), "r"(a3), "r"(ob + (uint32_t)DB), "n"((uint32_t)(DB >> 32)), "n"(SD)); \
}
#define ACC4(d) "+f"(d[0]), "+f"(d[1]), "+f"(d[2]), "+f"(d[3])
#define ACC16(d) ACC8(d), ACC8((d + 8))
#define OP4(i) OP4_##i
#define OP4_0 "%4"
#define OP4_1 "%5"
#define OP4_2 "%6"
#define OP4_3 "%7"
#define OP4_4 "%8"
#define OP4_5 "%9"
#define OP4_6 "%10"
#define OP16(i) OP16_##i
#define OP16_0 "%16"
#define OP16_1 "%17"
#define OP16_2 "%18"
#define OP16_3 "%19"
#define OP16_4 "%20"
#define OP16_5 "%21"
#define OP16_6 "%22"
#define OP32(i) OP32_##i
#define OP32_0 "%32"
#define OP32_1 "%33"
#define OP32_2 "%34"
#define OP32_3 "%35"
#define OP32_4 "%36"
#define OP32_5 "%37"
#define OP32_6 "%38"
WG_RSO(wg_rs8o, "m64n8k16", "{%0,%1,%2,%3}", ACC4, OP4, "1")
#define R16 "{%0,%1,%2,%3,%4,%5,%6,%7,%8,%9,%10,%11,%12,%13,%14,%15}"
WG_RSO(wg_rs32o, "m64n32k16", R16, ACC16, OP16, "1")
WG_RSO(wg_rs64o, "m64n64k16", R32, ACC32, OP32, "0")
WG_RSO(wg_rs32k, "m64n32k16", R16, ACC16, OP16, "0")
template <uint64_t DA, uint64_t DB> __device__ __forceinline__ void wg_ss32k(float* d, uint32_t ob) {
  asm volatile("{.reg .b64 b; mov.b64 b, {%17, %18};\nwgmma.mma_async.sync.aligned.m64n32k16.f32.bf16.bf16 " R16 ", %16, b, 1, 1, 1, 1, 0;}"
    : ACC16(d) : "l"(DA), "r"(ob + (uint32_t)DB), "n"((uint32_t)(DB >> 32)));
}
template <int N> __device__ __forceinline__ void reg_inc() { asm volatile("setmaxnreg.inc.sync.aligned.u32 %0;" :: "n"(N)); }
template <int N> __device__ __forceinline__ void reg_dec() { asm volatile("setmaxnreg.dec.sync.aligned.u32 %0;" :: "n"(N)); }
__device__ __forceinline__ void cluster_sync() {
  asm volatile("barrier.cluster.arrive.relaxed.aligned;\nbarrier.cluster.wait.aligned;" ::: "memory");
}

template <int KS>
__device__ __forceinline__ void load_frags(uint32_t* a, uint32_t src) {
  const int lane = threadIdx.x & 31, w = (threadIdx.x >> 5) & 3;
  const int k = ((lane >> 4) << 3) + (lane & 7), u = w * 2 + ((lane >> 3) & 1);
  const uint32_t base = src + k * 128 + ((u ^ (k & 7)) << 4);
#pragma unroll
  for (int ks = 0; ks < KS; ks++) ldsm4t(a[ks * 4], a[ks * 4 + 1], a[ks * 4 + 2], a[ks * 4 + 3], base + ks * 2048);
}

__device__ __forceinline__ uint32_t badd2(uint32_t a, uint32_t b) { uint32_t r; asm("add.rn.bf16x2 %0, %1, %2;" : "=r"(r) : "r"(a), "r"(b)); return r; }
__device__ __forceinline__ uint32_t bsub2(uint32_t a, uint32_t b) { uint32_t r; asm("sub.rn.bf16x2 %0, %1, %2;" : "=r"(r) : "r"(a), "r"(b)); return r; }
__device__ __forceinline__ uint32_t bmul2(uint32_t a, uint32_t b) { uint32_t r; asm("mul.rn.bf16x2 %0, %1, %2;" : "=r"(r) : "r"(a), "r"(b)); return r; }
__device__ __forceinline__ uint32_t bfma2(uint32_t a, uint32_t b, uint32_t c) { uint32_t r; asm("fma.rn.bf16x2 %0, %1, %2, %3;" : "=r"(r) : "r"(a), "r"(b), "r"(c)); return r; }
template <int R> __device__ __forceinline__ void layernorm9(const uint32_t* x, uint32_t* o) {
  const uint32_t ones = 0x3F803F80u;
  float a[R][3][4], q[R], s[R];
#pragma unroll
  for (int i = 0; i < 9 * R; i++) {
    float* d = a[i % R][i / R % 3];
    if (i < 3 * R) d[0] = d[1] = d[2] = d[3] = 0.f;
    mma8(d, x[i % R * 9 + i / R], ones, x[i % R * 9 + i / R]);
  }
#pragma unroll
  for (int r = 0; r < R; r++) {
    q[r] = threadIdx.x & 4 ? a[r][0][1] + a[r][1][1] + a[r][2][1] : a[r][0][0] + a[r][1][0] + a[r][2][0];
    s[r] = (a[r][0][2] + a[r][0][3]) + (a[r][1][2] + a[r][1][3]) + (a[r][2][2] + a[r][2][3]);
  }
#pragma unroll
  for (int r = 0; r < R; r++) { q[r] += __shfl_xor_sync(~0u, q[r], 4); s[r] += __shfl_xor_sync(~0u, s[r], 1); }
#pragma unroll
  for (int r = 0; r < R; r++) { q[r] += __shfl_xor_sync(~0u, q[r], 9); s[r] += __shfl_xor_sync(~0u, s[r], 2); }
#pragma unroll
  for (int r = 0; r < R; r++) q[r] = __shfl_sync(~0u, q[r], 0) + __shfl_sync(~0u, q[r], 18);
#pragma unroll
  for (int r = 0; r < R; r++) {
    const float mean = s[r] * (1.f / DM), var = fmaxf(fmaf(q[r], 1.f / DM, -mean * mean), 0.f);
    float sd;
    asm("sqrt.approx.ftz.f32 %0, %1;" : "=f"(sd) : "f"(bf_lo(pack2(bf_lo(pack2(var, 0.f)) + 1e-5f, 0.f))));
    const float inv = rcp(bf_lo(pack2(sd, 0.f)));
    const uint32_t mb = pack2(mean, mean), hi = pack2(inv, inv), lo = pack2(inv - bf_lo(hi), inv - bf_lo(hi));
#pragma unroll
    for (int i = r * 9; i < r * 9 + 9; i++) {
      const uint32_t d = bsub2(x[i], mb);
      o[i] = bfma2(d, hi, bmul2(d, lo));
    }
  }
}
__device__ __forceinline__ void store_ln_row(int layer, int tok, const uint32_t* o) {
  const int lane = threadIdx.x & 31, r = tok & 31;
  unsigned char* p = g_lnimg + (size_t)(layer * NSEG + (tok >> 5)) * (9 * 4096) + r * 128 + (((lane >> 2) ^ (r & 7)) << 4) + (lane & 3) * 4;
#pragma unroll
  for (int i = 0; i < 9; i++) *(uint32_t*)(p + i * 4096) = o[i];
}
struct Params { CUtensorMap map[11]; const bf16 *X, *K, *V, *shift, *Hk, *Dk, *mem0, *Wq, *Wk, *Wv, *Wo; bf16* out; uint32_t dly[24]; };
#define PACE P.dly[20]
#define S1G P.dly[21]
#define S1DLY P.dly[22]
#define DLYS P.dly[0]
#define DLYW P.dly[1]
#define KLATE P.dly[2]
#define DLYQ P.dly[3]
#define DLYK P.dly[4]
#define DLYG P.dly[5]
#define KWIN P.dly[6]
#define KMIN P.dly[7]
uint32_t h_dly[24] = {900, 150, 100, 40, 3650, 4900, 1750, 300, 1740, 1840, 1900, 2230, 2340, 2430, 3080, 3170, 3380, 3460, 3580, 0, 180, 12000, 16000};

constexpr uint32_t C_W = 0, C_M = 147456, C_KV = C_M + 18432, C_QM = C_KV + 32768, C_KM = C_QM + 2048,
                   C_VM = C_KM + 2048, C_OI = C_VM + 2048, C_SX = C_OI + 4096, C_KM2 = C_SX + 2560, C_VM2 = C_KM2 + 128,
                   C_KV2 = C_KM2 + 2048, C_Q = C_KV2 + 8192, C_BAR = C_Q + 8192;
constexpr uint32_t CB_FULL = C_BAR, CB_REF = C_BAR + 16, CB_SX = C_BAR + 32, CB_OX = C_BAR + 40, CB_XX = C_BAR + 48, CB_Q = C_BAR + 56, C_BAD = C_BAR + 64, W_BAR = C_BAR + 80, T_BAR = W_BAR + 24, S_GEN = C_BAR + 128, C_REF = C_BAR + 132, CB_VF = C_BAR + 144, CB_M = C_BAR + 160, CB_MV = C_BAR + 200;
constexpr uint32_t G_W = 0, G_RING = 147456, G_W2 = G_RING + 9 * 8192, G_BAR = G_W2 + 8192;
constexpr uint32_t O_W = 0, O_RING = 3 * 40960, O_ST = O_RING + 11 * 8192, O_BAR = O_ST + 16384, OB_ST = O_BAR + 64;
constexpr uint32_t F_A = 0, F_XY = 36864, F_L = F_XY + 36864, F_X = F_L + 18432, F_Y = F_L + 2 * 36864, F_BAR = C_BAR;
constexpr uint32_t SMEM_BYTES = C_BAR + 256;
static_assert(G_BAR + 256 <= SMEM_BYTES && O_BAR + 256 <= SMEM_BYTES && F_BAR + 16 <= SMEM_BYTES && SMEM_BYTES <= 232448, "smem map");
enum { B_INIT = 1, B_M, B_QK, B_S, B_V, B_O, B_X, B_WG0, B_WG1, B_WG2, B_G, B_OE, B_T, B_R };

__device__ __forceinline__ uint4 pack_partial(const float* d, uint32_t tag) {
  uint32_t x;
  asm("lop3.b32 %0, %1, 1, %2, 0xb8;" : "=r"(x) : "r"(pack2(d[0], d[1])), "r"(tag));
  return make_uint4(x, pack2(d[4], d[5]), pack2(d[2], d[3]), pack2(d[6], d[7]));
}
__device__ __forceinline__ void store_partial(uint4* p, const uint4& v) { st_b128(p, v.x, v.y, v.z, v.w); }
__device__ __forceinline__ void gather_reduce(const uint32_t* p, uint32_t* dst, uint32_t m0, bool shared, uint32_t tag, uint32_t lane, uint32_t sb, int n, int TS0) {
  int tries = 0;
  float u, v;
  bool bad;
  TR(TS0);
  do {
    uint32_t x[16];
#pragma unroll
    for (int i = 0; i < 16; i++) asm volatile("ld.relaxed.gpu.global.u32 %0, [%1];" : "=r"(x[i]) : "l"(p + i * 64) : "memory");
    tries++;
    float a[2] = {bf_lo(x[0]), bf_lo(x[1])}, b[2] = {bf_hi(x[0]), bf_hi(x[1])};
    uint32_t t = 0;
#pragma unroll
    for (int i = 2; i < 16; i++) { a[i & 1] += bf_lo(x[i]); b[i & 1] += bf_hi(x[i]); }
#pragma unroll
    for (int i = 0; i < 16; i += 4)
      asm("{.reg .b32 y, z; lop3.b32 y, %1, %2, %5, 0x7e; lop3.b32 z, %3, %4, %5, 0x7e; lop3.b32 %0, %0, y, z, 0xfe;}"
          : "+r"(t) : "r"(x[i]), "r"(x[i + 1]), "r"(x[i + 2]), "r"(x[i + 3]), "r"(tag));
    u = a[0] + a[1]; v = b[0] + b[1];
    bad = __any_sync(~0u, (t & 1) && !(lane & 3));
    if (shared) { u += __shfl_xor_sync(~0u, u, 8); v += __shfl_xor_sync(~0u, v, 8); }
    u += __shfl_xor_sync(~0u, u, 16);
    v += __shfl_xor_sync(~0u, v, 16);
    st_relaxed_if(dst, n < LAG && (lane & 1) ? m0 : pack2(u, v), !bad);
  } while (bad);
  TR(TS0 + 3); TRV(TS0 + 2, tries);
  CNT((TS0 - 16) >> 2, tries);
}
__device__ __forceinline__ uint32_t sent_bad(const uint4& v) { return max(max(v.x, v.y), max(v.z, v.w)) == SENT; }

__host__ __device__ constexpr int o_ks(int s) { return s & (s < 8 ? 3 : 7); }
__host__ __device__ constexpr bool o_reg(int s) { return s < 8 ? (s & 3) != 3 : !(s & 1); }
__host__ __device__ constexpr int o_slot(int s) { return s < 8 ? (o_reg(s) ? s - (s >> 2) : s >> 2) : s & 1 ? (s - 5) >> 1 : (s + 4) >> 1; }
__device__ __forceinline__ int g_unit(int wg) {
  const int i = bid() - N_CHAIN;
  return i < 32 ? wg * 64 + i : 2 * i - 32 + wg;
}
__device__ __forceinline__ void load_box(const Params& P, uint32_t sb, bool regs, int wg, int i, uint32_t mb) {
  const int b = bid();
  int map, col = 0, ks = 0, c2 = 0, c3 = 0;
  uint32_t dst = wg * 73728;
  if (b < N_CHAIN) {
    const int k = i - 1, st = regs ? (k < 6 ? k + k / 3 : 2 * k - 4) : k < 2 ? 4 * k + 3 : 2 * k + 5;
    dst += i ? (17 + i) * 2048 : 0;
    if (wg || i == 0) { map = wg + i; col = b * 64; c3 = !regs; }
    else if (!regs && k >= 14) { map = 6; ks = b * 4 + k - 14; }
    else { map = 6; col = 64 + (st < 8 ? (st >> 2) * 64 : (st >> 3) * 128 + (b & 1) * 64); ks = (b * 4) ^ o_ks(st); }
  } else if (b < N_CHAIN + N_G) {
    const int q = g_unit(wg);
    map = ((q >> 5) + 1) % 3;
    if (i) { map += 3; col = (q & 31) * 128 + (i - 1) * 64; ks = 34; dst = G_W2 + wg * 4096 + (i - 1) * 2048; }
    else { map += 8; c2 = (q & 31) * 2; c3 = !regs; }
  } else {
    const int o = b - N_CHAIN - N_G, ksl = o / 3;
    map = 7; col = ((o % 3) * 3 + (wg + ksl) % 3) * 64; dst = (wg * (regs ? 24 : 20) + i) * 2048;
    ks = (ksl * 11 - max(ksl - 4, 0)) * 4 + (regs ? i / 3 * 5 + i % 3 * 2 : i < 16 ? i / 2 * 5 + 1 + i % 2 * 2 : i + 24);
    c3 = (ks & 1) * 2; ks >>= 1;
  }
  asm volatile("cp.async.bulk.tensor.5d.shared::cluster.global.tile.mbarrier::complete_tx::bytes [%0], [%1, {%2, %3, %4, %5, %6}], [%7];"
               :: "r"(sb + dst), "l"(&P.map[map]), "r"(col), "r"(0), "r"(c2), "r"(c3), "r"(ks), "r"(mb) : "memory");
}
__device__ __forceinline__ void load_wg(const Params& P, uint32_t sb, bool regs, int wg, int quarter) {
  const int b = bid(), i = (threadIdx.x & 31) * 4 + quarter;
  const int n = b < N_CHAIN ? 36 : b < N_CHAIN + N_G ? (regs ? 38 : 36) : regs ? 24 : b < N_CHAIN + N_G + 12 ? 20 : 16;
  if (i == 0) mbar_expect(sb + W_BAR + wg * 8, n * 2048);
  if (i < (b < N_CHAIN ? (wg ? 2 : 19) : b < N_CHAIN + N_G ? n - 35 : n)) load_box(P, sb, regs, wg, i, sb + W_BAR + wg * 8);
  __syncwarp();
}
__device__ __forceinline__ uint32_t near_half(uint32_t blk, uint32_t reader) {
  return __ldcg(g_near + (blk >> 3)) ^ (~blk & 1) ^ __ldcg(g_side + (blk >> 3)) ^ __ldcg(g_side + reader);
}

__device__ __forceinline__ uint32_t opaque_tid() { uint32_t t; asm volatile("mov.u32 %0, %%tid.x;" : "=r"(t)); return t; }
__device__ __forceinline__ void m_fetch(uint32_t sb, uint32_t src, uint32_t b, uint32_t mb) {
  bulk_load(sb + C_M + (b ? b * 4096 - 2048 : 0), (const unsigned char*)g_mimg + ((src ^ ((b & 1) * 4096)) + b * 8192), b ? 4096 : 2048, mb);
}
__device__ __forceinline__ uint32_t pinned(uint32_t v) { return __shfl_sync(~0u, v, threadIdx.x & 31); }
template <class T> __device__ __forceinline__ T* pinned(T* p) { return (T*)__shfl_sync(~0u, (unsigned long long)p, threadIdx.x & 31); }
__device__ __forceinline__ uint32_t m_probe(uint32_t lane) { return lane * 32 + (lane & 4) * 4 + (lane >> 3) * 4; }
__device__ __forceinline__ uint32_t m_max(uint32_t a, uint32_t b) {
  return max(max(lds32(a), lds32(a + 1024)), max(lds32(b), lds32(b + 1024)));
}
template <int S0, int N> __device__ __forceinline__ void o_steps(float* d, const uint32_t* a) {
  constexpr int SD = o_ks(S0) != 0;
  if constexpr (o_reg(S0)) wg_rs16<SD>(d, a + (18 + o_slot(S0)) * 4, desc_n16(C_OI + o_ks(S0) * 512));
  else wg_ss16<SD>(d, desc_sw128(C_W + (18 + o_slot(S0)) * 2048), desc_n16(C_OI + o_ks(S0) * 512));
  if constexpr (N > 1) o_steps<S0 + 1, N - 1>(d, a);
}
template <int BASE, int KS, int N> __device__ __forceinline__ void m_steps(float* d, const uint32_t* a, uint32_t oa) {
  wg_rs16<KS != 0>(d, a + (BASE + KS / 2) * 4, desc_m(C_M + KS * 512));
  wg_ss16o<1, desc_sw128(C_W + (BASE + KS / 2) * 2048), desc_m(C_M + KS * 512 + 512)>(d, oa, 0);
  if constexpr (N > 2) m_steps<BASE, KS + 2, N - 2>(d, a, oa);
}

__device__ __forceinline__ void chain_proj(const Params& P, uint32_t sb) {
  const uint32_t c = chain_id(), h = c >> 1, j = c & 1, wid = __shfl_sync(~0u, threadIdx.x >> 5, 0), wg = wid >> 2, w = wid & 3;
  const uint32_t t = threadIdx.x & 127, lane = pinned(t & 31), mine = pinned(sb + t * 16), rb = mapa(sb, j ^ 1);
  const uint32_t theirs = pinned(rb + C_KM2 + w * 512 + lane * 4), oa = wg * 4608;
  uint32_t a[144];
  mbar_wait(sb + W_BAR + wg * 8, 0);
  if (threadIdx.x == 0) TS(23);
  load_frags<36>(a, sb + C_W + wg * 73728);
  fence_async_smem();
  bar_sync(B_WG0 + wg, 128);
  if (threadIdx.x == 0) TS(24);
  load_wg(P, sb, false, wg, w);
  if (threadIdx.x == 0) TS(25);
  bar_sync(B_WG2, 384);
  const uint32_t round = min(w, 2u) + (wg ? 0 : 3), gdly = P.dly[8 + round], ps = t >> 2, pf = j * 16 + (ps >> 1);
  uint4* const dsts = pinned(g_xb + (ps * 4096 + near_half(ps * 8, ps * 2) * 256 + c * 4 + (t & 3)));
  uint4* const dstf = pinned(g_xb + (pf * 4096 + 512 + near_half(pf * 8 + 1, pf * 2) * 256 + h * 8 + (t & 7)));
  const uint32_t* const gsrc = (const uint32_t*)g_xb + (h * 16384 + min(w, 2u) * 4096 + near_half(h * 8 + !wg, h * 2) * 1024 +
                               (wg ? (lane & 24) * 2 + j * 8 + (lane & 7) : 2048 + (lane & 16) * 2 + j * 16 + (lane & 15)));
  uint32_t* gdst = g_mimg + (16384 + (lane >> 4) * 1024 + (lane & 2) * 4 +
                   (wg ? (round ? 1536 + round * 512 : 0) + h * 16 + ((lane ^ (c >> 2)) & 1) * 4 + j * 2 + ((lane >> 2) & 1)
                       : (round - 1) * 2048 + c * 16 + ((lane ^ (c >> 1)) & 1) * 4 + ((lane >> 2) & 3)));
  const uint32_t m0 = __ldcg(gdst - 16384);
  mbar_wait(sb + W_BAR + wg * 8, 1);
  bar_sync(B_INIT, 256);
  if ((threadIdx.x & 127) == 0) TS(4);

  uint32_t ring = 1;
#pragma unroll 1
  for (int n = 0; n < STEPS; n++) {
    float d[8], e[8];
    uint32_t redo = n + 1;
    do {
      mbar_wait(sb + CB_M, n & 1);
      wg_fence();
      m_steps<0, 0, 4>(d, a, oa);
      if (VE && wg) m_steps<18, 0, 4>(e, a, 4608);
      wg_commit();
      if (wid == 0) TR(8);
      mbar_wait(sb + CB_M + 8, n & 1);
      wg_fence();
      m_steps<0, 4, 8>(d, a, oa);
      if (VE > 4 && wg) m_steps<18, 4, (VE > 4 ? VE - 4 : 2)>(e, a, 4608);
      wg_commit();
      mbar_wait(sb + CB_MV, n & 1);
      redo = lds32(sb + C_BAD) == redo ? SENT : 0;
    } while (redo);
    mbar_wait(sb + CB_MV + 8, n & 1);
    wg_fence();
    m_steps<0, 12, 8>(d, a, oa);
    wg_commit();
    mbar_wait(sb + CB_MV + 16, n & 1);
    wg_fence();
    m_steps<0, 20, 8>(d, a, oa);
    wg_commit();
    mbar_wait(sb + CB_MV + 24, n & 1);
    wg_fence();
    m_steps<0, 28, 8>(d, a, oa);
    wg_commit();
    wg_wait<0>();
    if (w == 0) TR(6 + wg);
    const uint32_t f0 = pack2(d[0], d[1]), f1 = pack2(d[4], d[5]), f2 = pack2(d[2], d[3]), f3 = pack2(d[6], d[7]);
    stsm4(mine + C_QM + wg * 2048, f0, f1, f2, f3);
    bar_arrive(B_QK, 416);
    const uint32_t tag = (n & 1) ^ 1;
    if (wg) {
      if (n + 1 < STEPS) bar_sync(B_S, 256);
      wg_fence();
      m_steps<18, VE, 36 - VE>(e, a, 4608);
      wg_commit();
      st_async1(theirs, j ? f0 : f1, rb + CB_XX);
      st_async1(theirs + 256, j ? f2 : f3, rb + CB_XX);
      wg_wait<0>();
      if (w == 0) TR(11);
      const uint32_t v0 = pack2(e[0], e[1]), v1 = pack2(e[4], e[5]), v2 = pack2(e[2], e[3]), v3 = pack2(e[6], e[7]);
      stsm4(mine + C_VM, v0, v1, v2, v3);
      bar_arrive(B_V, 256);
      st_async1(theirs + 128, j ? v0 : v1, rb + CB_XX);
      st_async1(theirs + 384, j ? v2 : v3, rb + CB_XX);
      if (n + 1 == STEPS) break;
      bar_sync(B_O, 256);
      if (!WFENCE) fence_async_smem();
      wg_fence();
#pragma unroll
      for (int ks = 0; ks < 4; ks++) {
        if (ks == 0) wg_ss16<0>(d, desc_sw128(C_W + 32 * 2048), desc_n16(C_OI));
        else wg_ss16<1>(d, desc_sw128(C_W + (32 + ks) * 2048), desc_n16(C_OI + ks * 512));
      }
      wg_commit();
      bar_arrive(B_X, 256);
      if (w == 0) TR(0);
      wg_wait<0>();
      store_partial(dsts, pack_partial(d, tag));
      bar_arrive(B_M, 160);
      if (w == 0) TR(1);
    } else {
      if (n + 1 == STEPS) break;
      bar_sync(B_X, 256);
      wg_fence();
      o_steps<0, 4>(d, a);
      wg_commit();
      o_steps<4, 4>(e, a);
      wg_commit();
      wg_wait<1>();
      store_partial(dsts + 1024, pack_partial(d, tag));
      if (w == 0) TR(2);
      if (OGAP == 0) { wg_fence(); o_steps<8, 4>(d, a); wg_commit(); wg_wait<1>(); } else wg_wait<0>();
      store_partial(dsts + 2048, pack_partial(e, tag));
      if (w == 0) TR(3);
      wg_fence();
      if (OGAP) o_steps<8, 4>(d, a);
      if (OGAP < 2) o_steps<16, 4>(e, a);
      wg_commit();
      bar_sync(B_T, 256);
      if (w == 0) { TRV(61, 0); TR(12); }
      wg_fence();
      o_steps<12, 4>(d, a);
      wg_commit();
      if (OGAP == 2) o_steps<16, 4>(e, a);
      o_steps<20, 4>(e, a);
      wg_commit();
      wg_wait<1>();
      store_partial(dstf, pack_partial(d, tag));
      if (w == 0) TR(4);
      wg_fence();
      o_steps<24, 8>(d, a);
      wg_commit();
      wg_wait<1>();
      store_partial(dstf + 1024, pack_partial(e, tag));
      bar_arrive(B_OE, 256);
      if (w == 0) TR(5);
      wg_wait<0>();
      store_partial(dstf + 2048, pack_partial(d, tag));
      if (w == 0) TR(15);
    }
    if (w < 3) {
      mbar_wait(sb + CB_REF, n & 1);
      wait_until(lds32(sb + C_REF), gdly);
      gather_reduce(gsrc, gdst, m0, wg, tag, lane, sb, n, 16 + round * 4);
      if (++ring == MRING) { ring = 0; gdst -= MRING * 16384; }
      gdst += 16384;
    }
  }
}

template <int KS> __device__ __forceinline__ void x_scores(float* s, float* sm, const uint4* q, uint32_t ok, uint32_t om) {
  wg_rs32o<1, desc_sw64(C_KV + KS * 1024)>(s, q[KS].x, q[KS].y, q[KS].z, q[KS].w, ok);
  wg_rs8o<1, desc_n16(C_KM + KS * 512)>(sm, q[KS].x, q[KS].y, q[KS].z, q[KS].w, om);
  if constexpr (KS < 3) x_scores<KS + 1>(s, sm, q, ok, om);
}

__device__ __forceinline__ void chain_attn(const Params& P, uint32_t sb) {
  const int c = chain_id(), j = c & 1;
  const int tid = threadIdx.x, lane = tid & 31, w = __shfl_sync(~0u, (tid >> 5) & 3, 0);
  const int l = w >> 1, u = w & 1;
  const uint32_t rb = mapa(sb, j ^ 1);
  const float sc = 0.08838834764831845f * 1.4426950408889634f;
  const uint32_t ones = 0x3F803F80u;
  const uint32_t km_off = C_KM + (lane >> 3) * 256 + l * 128 + (lane & 7) * 16;
  const uint32_t qm_off = C_QM + (lane >> 4) * 256 + l * 128 + (lane & 7) * 16;
  const uint32_t kv_off = C_KV + l * 4096 + (lane & 15) * 64 + (((lane >> 4) ^ (u * 2) ^ ((lane >> 1) & 3)) << 4);

  if (lane == 0) mbar_arrive(sb + CB_M);
#pragma unroll 1
  for (int n = 0; n < STEPS; n++) {
    const uint32_t kvb = sb + kv_off + (n & 1) * 16384;
    if (w == 0 && elect()) { mbar_expect(sb + CB_SX, 2560); mbar_expect(sb + CB_OX, 2048); mbar_expect(sb + CB_XX, 2048); }
    mbar_wait(sb + CB_FULL + (n & 1) * 8, (n >> 1) & 1);
    if (n < 3 && tid == 256) TS(n ? 20 + n : 5);
    __syncwarp();
    {
      uint32_t km[8];
      uint4 kx[8];
#pragma unroll
      for (int i = 0; i < 8; i++) ldsm4t(kx[i].x, kx[i].y, kx[i].z, kx[i].w, (kvb ^ ((i & 1) * 32)) + (i >> 1) * 1024);
      mbar_wait(sb + CB_VF, n & 1);
      if (w == 1) TRD(60, kx[7].x);
      bar_sync(B_QK, 416);
      if (n + 1 == STEPS) {
        bar_sync(B_V, 256);
      } else {
      uint32_t qm[16];
#pragma unroll
      for (int ks = 0; ks < 4; ks++) ldsm4t(qm[4 * ks], qm[4 * ks + 1], qm[4 * ks + 2], qm[4 * ks + 3], sb + qm_off + ks * 512);
      ldsm4t(km[0], km[1], km[2], km[3], sb + km_off);
      ldsm4t(km[4], km[5], km[6], km[7], sb + km_off + 1024);
      float s[5][4];
#pragma unroll
      for (int i = 0; i < 5; i++) { s[i][0] = s[i][1] = s[i][2] = s[i][3] = 0.f; }
#pragma unroll
      for (int ks = 0; ks < 4; ks++) {
        const uint32_t* q = qm + 4 * ks;
        mma16(s[1], q[0], q[1], q[2], q[3], kx[2 * ks].x, kx[2 * ks].y);
        mma16(s[2], q[0], q[1], q[2], q[3], kx[2 * ks].z, kx[2 * ks].w);
        mma16(s[0], q[0], q[1], q[2], q[3], km[2 * ks], km[2 * ks + 1]);
        mma16(s[3], q[0], q[1], q[2], q[3], kx[2 * ks + 1].x, kx[2 * ks + 1].y);
        mma16(s[4], q[0], q[1], q[2], q[3], kx[2 * ks + 1].z, kx[2 * ks + 1].w);
      }
      const uint32_t sx = C_SX + l * 1280;
      st_async4(rb + sx + u * 512 + lane * 16, s[1][0], s[1][1], s[2][0], s[2][1], rb + CB_SX);
      st_async1(rb + sx + 1024 + u * 128 + lane * 4, __float_as_uint(u ? s[0][1] : s[0][0]), rb + CB_SX);
      bar_arrive_after<B_S, 256>(__float_as_uint(s[3][0]), __float_as_uint(s[4][0]));
      uint4 vx[4];
#pragma unroll
      for (int i = 0; i < 4; i++) ldsm4(vx[i].x, vx[i].y, vx[i].z, vx[i].w, (kvb ^ ((i & 1) * 32)) + 8192 + (2 * u + (i >> 1)) * 1024);
      mbar_wait(sb + CB_SX, n & 1);
      const uint4 p0 = lds128(sb + sx + u * 512 + lane * 16), p1 = lds128(sb + sx + (u ^ 1) * 512 + lane * 16);
      const uint2 p2 = make_uint2(lds32(sb + sx + 1024 + lane * 4), lds32(sb + sx + 1152 + lane * 4));
      float t[10] = {s[0][0] + __uint_as_float(p2.x), s[0][1] + __uint_as_float(p2.y),
                     s[1][0] + __uint_as_float(p0.x), s[1][1] + __uint_as_float(p0.y),
                     s[2][0] + __uint_as_float(p0.z), s[2][1] + __uint_as_float(p0.w),
                     s[3][0] + __uint_as_float(p1.x), s[3][1] + __uint_as_float(p1.y),
                     s[4][0] + __uint_as_float(p1.z), s[4][1] + __uint_as_float(p1.w)};
      float mx = fmaxf(fmaxf(fmaxf(fmaxf(t[2], t[3]), fmaxf(t[4], t[5])), fmaxf(fmaxf(t[6], t[7]), fmaxf(t[8], t[9]))), fmaxf(t[0], t[1]));
      mx = fmaxf(fmaxf(mx, __shfl_xor_sync(~0u, mx, 1)), fmaxf(__shfl_xor_sync(~0u, mx, 2), __shfl_xor_sync(~0u, mx, 3)));
      const float ms = -mx * sc;
#pragma unroll
      for (int i = 0; i < 10; i++) t[i] = ex2(fmaf(t[i], sc, ms));
      uint32_t p[5];
#pragma unroll
      for (int i = 0; i < 5; i++) p[i] = pack2(t[2 * i], t[2 * i + 1]);
      p[1] |= (p[0] & p[3] & p[4]) & 0x80008000u;
      float o[2][4], z[4] = {0.f, 0.f, 0.f, 0.f};
      mma16(z, ones, ones, ones, ones, p[1], p[2]);
#pragma unroll
      for (int i = 0; i < 2; i++) {
        o[i][0] = o[i][1] = o[i][2] = o[i][3] = 0.f;
        mma16(o[i], vx[2 * i].x, vx[2 * i].y, vx[2 * i].z, vx[2 * i].w, p[1], p[2]);
      }
      mma16(z, ones, ones, ones, ones, p[3], p[4]);
#pragma unroll
      for (int i = 0; i < 2; i++) mma16(o[i], vx[2 * i + 1].x, vx[2 * i + 1].y, vx[2 * i + 1].z, vx[2 * i + 1].w, p[3], p[4]);
      mma8(z, ones, ones, p[0]);
      bar_sync_after<B_V, 256>(p[1]);
      ldsm4(km[0], km[1], km[2], km[3], sb + km_off + (C_VM - C_KM) + u * 1024);
      mma8(o[0], km[0], km[1], p[0]);
      mma8(o[1], km[2], km[3], p[0]);
      const float i0 = rcp(z[0]), i1 = rcp(z[1]);
      const uint32_t oo = C_OI + u * 1024 + l * 128 + lane * 4;
      uint32_t ow[4];
#pragma unroll
      for (int i = 0; i < 2; i++) { ow[2 * i] = pack2(o[i][0] * i0, o[i][1] * i1); ow[2 * i + 1] = pack2(o[i][2] * i0, o[i][3] * i1); }
      stsm4(sb + C_OI + u * 1024 + l * 128 + (lane >> 3) * 256 + (lane & 7) * 16, ow[0], ow[1], ow[2], ow[3]);
      if (WFENCE) fence_async_smem();
      bar_arrive(B_O, 256);
#pragma unroll
      for (int i = 0; i < 4; i++) st_async1(rb + oo + 2048 + i * 256, ow[i], rb + CB_OX);
      }
    }
    {
      const uint32_t lane = opaque_tid() & 31, own = ((n & 1) * 16384 + j * 4096) >> 4;
      float s[16], sm[4];
#pragma unroll
      for (int i = 0; i < 16; i++) s[i] = sm[i & 3] = 0.f;
      {
        uint4 q[4];
        mbar_wait(sb + CB_Q, n & 1);
        auto load_q = [&]() {
#pragma unroll
          for (int ks = 0; ks < 4; ks++) q[ks] = lds128(sb + C_Q + (ks >> 1) * 4096 + w * 1024 + (ks & 1) * 512 + lane * 16);
        };
        if (QPOS == 0) load_q();
        mbar_wait(sb + CB_XX, n & 1);
        if (n + 1 < STEPS) mbar_wait(sb + CB_OX, n & 1);
        fence_async_smem();
        if (n + 1 < STEPS) bar_arrive(B_T, 256);
        if (QPOS == 1) load_q();
        if (n + 1 < STEPS) bar_sync(B_OE, 256);
        if (QPOS == 2) load_q();
        if (w == 1) { TRV(61, 0); TR(9); }
#pragma unroll 1
        for (uint32_t hf = 0; hf < 2; hf++) {
          wg_fence();
          x_scores<0>(s, sm, q, hf ? (C_KV2 - C_KV) >> 4 : own, hf ? (C_KM2 - C_KM) >> 4 : j * 8);
          wg_commit();
          wg_wait<0>();
#pragma unroll
          for (int ks = 0; ks < 4; ks++) asm volatile("mov.b32 %0, %1; mov.b32 %2, %3;" : "+r"(q[ks].x), "+r"(q[ks].y), "+r"(q[ks].z), "+r"(q[ks].w));
        }
      }
      const float neg = -1e9f * 11.313708498984761f;
      const int lim = 8 * (w - (int)(lane & 3)) + (int)(lane >> 2);
      float t[10] = {sm[0], sm[1]};
#pragma unroll
      for (int i = 0; i < 8; i++) t[2 + i] = i > lim ? neg : s[(i >> 1) * 4 + (i & 1)];
      float mx = fmaxf(fmaxf(fmaxf(fmaxf(t[2], t[3]), fmaxf(t[4], t[5])), fmaxf(fmaxf(t[6], t[7]), fmaxf(t[8], t[9]))), fmaxf(t[0], t[1]));
      mx = fmaxf(fmaxf(mx, __shfl_xor_sync(~0u, mx, 1)), fmaxf(__shfl_xor_sync(~0u, mx, 2), __shfl_xor_sync(~0u, mx, 3)));
      const float ms = -mx * sc;
#pragma unroll
      for (int i = 0; i < 10; i++) t[i] = ex2(fmaf(t[i], sc, ms));
      uint32_t p[5];
#pragma unroll
      for (int i = 0; i < 5; i++) p[i] = pack2(t[2 * i], t[2 * i + 1]);
      float z = ((t[0] + t[1]) + (t[2] + t[3])) + ((t[4] + t[5]) + (t[6] + t[7])) + (t[8] + t[9]);
      const uint32_t row = sb + C_Q + w * 1024 + (lane >> 2) * 128 + (((lane & 3) ^ (lane >> 2)) << 4);
#pragma unroll 1
      for (uint32_t hf = 0; hf < 2; hf++) {
        float o[32];
        const uint32_t vo = hf ? (C_KV2 + 4096 - C_KV - 8192) >> 4 : own;
        wg_fence();
        wg_rs64o<0, desc_sw64(C_KV + 8192)>(o, p[1], p[1], p[2], p[2], vo);
        wg_rs64o<1, desc_sw64(C_KV + 8192 + 32)>(o, p[3], p[3], p[4], p[4], vo);
        wg_rs64o<1, mkdesc(C_VM, 128, 256, 0)>(o, p[0], p[0], 0, 0, hf ? (C_VM2 - C_VM) >> 4 : j * 8);
        wg_commit();
        if (hf) {
          if (elect()) mbar_arrive(sb + CB_M);
        } else {
          z += __shfl_xor_sync(~0u, z, 1);
          z = rcp(z + __shfl_xor_sync(~0u, z, 2));
        }
        wg_wait<0>();
#pragma unroll
        for (int qq = 0; qq < 2; qq++) {
          const float* r = o + 16 * qq;
          sts128((row ^ (qq * 64)) + hf * 4096,
                 make_uint4(pack2(r[0] * z, r[1] * z), pack2(r[4] * z, r[5] * z), pack2(r[8] * z, r[9] * z), pack2(r[12] * z, r[13] * z)));
        }
      }
      bar_arrive(B_G, 160);
      if (w == 1) TR(10);
    }
  }
  if ((threadIdx.x & 127) == 0) TS(6);
}

__device__ __forceinline__ void chain_aux(const Params& P, uint32_t sb) {
  const uint32_t c = chain_id(), j = c & 1, lane = threadIdx.x & 31, w = __shfl_sync(~0u, (threadIdx.x >> 5) & 3, 0);
  if (threadIdx.x == 384) grid_wait(1, lds32(sb + S_GEN));
  bar_sync(B_WG2, 384);
  if (threadIdx.x == 384) TS(13);
  if (w == 0) {
    const uint32_t* fg = g_fl + FL_G + near_half(XB_F, c) * 1024 + (c >> 1) * 8;
#pragma unroll 1
    for (int n = 0; n < STEPS; n++) {
      const unsigned char* blk = g_qkv + (uint32_t)((n % QRING) * (N_CHAIN * 24576));
      const uint32_t t1 = clk(), kb = sb + CB_FULL + (n & 1) * 8, kv = sb + C_KV + (n & 1) * 16384;
      uint32_t t0 = t1 - 100000, x = 0;
      if (n > 0) {
        wait_until(t1, KMIN);
        do asm volatile("ld.relaxed.gpu.global.u32 %0, [%1];" : "=r"(x) : "l"(fg) : "memory"); while (x <= n && clk() - t1 < KWIN);
        if (NOBULK) x = n + 1;
        if (x > n) {
          asm volatile("fence.acquire.gpu;" ::: "memory");
          fence_async_global();
          if (elect()) { mbar_expect(kb, 8192); bulk_load(kv, blk + c * 24576, 8192, kb); }
        }
        T3(0); CNT(12, 1 + (x <= n));
        mbar_wait(sb + CB_REF, (n - 1) & 1);
        t0 = lds32(sb + C_REF);
        wait_until(t0, DLYK - 500);
      }
      if (!NOBULK) wait_flags(fg + (lane & 1) * 256, n + 1);
      fence_async_global();
      wait_until(t0, DLYK);
      if (elect()) {
        if (x <= n) { mbar_expect(kb, 8192); bulk_load(kv, blk + c * 24576, 8192, kb); }
        mbar_expect(sb + CB_VF, 8192);
        bulk_load(kv + 8192, blk + (c * 24576 + 8192), 8192, sb + CB_VF);
      }
      T3(1);
      if (!NOBULK) wait_flags(fg + 512, n + 1);
      T3(2);
      fence_async_global();
      if (n > 0) bar_sync(B_R, 64);
      if (elect()) {
        mbar_expect(sb + CB_Q, 16384);
        bulk_load(sb + C_Q, blk + (c * 24576 + 16384), 8192, sb + CB_Q);
        bulk_load(sb + C_KV2, blk + ((c ^ 1) * 24576 + j * 4096), 4096, sb + CB_Q);
        bulk_load(sb + C_KV2 + 4096, blk + ((c ^ 1) * 24576 + 8192 + j * 4096), 4096, sb + CB_Q);
      }
      T3(3);
    }
  } else {
    const uint32_t near = __ballot_sync(~0u, near_half(XB_M + min(lane, MRING - 1u) * 8, c));
    uint32_t ring = 0;
    if (w > 1) {
      const uint32_t odd = w & 1, chk = pinned(sb + C_M + odd * 2048 + m_probe(lane)), again = sb + CB_MV + 32 + odd * 8;
      const bool one = elect();
      uint32_t mph = 0;
#pragma unroll 1
      for (int n = 0; n <= STEPS; n++) {
#pragma unroll
        for (int k = 0; k < 3; k++) {
          if (n == STEPS || (k == 2 && odd)) break;
          const uint32_t b = 2 * k + odd, at = chk + (k ? k * 8192 - 2048 + odd * 2048 : 0);
          uint32_t mb = sb + CB_M + b * 8, ph = n & 1;
          int it = 1;
          while (true) {
            mbar_wait(mb, ph);
            const bool bad = __any_sync(~0u, (k ? m_max(at, at + 2048) : max(m_max(at, at ^ 8), odd ? m_max(at + 2048, (at ^ 8) + 2048) : 0)) == SENT);
            if (one && !bad) mbar_arrive(sb + CB_MV + (k ? b * 8 - 8 : 0));
            if (!bad) break;
            mb = again; ph = mph; mph ^= 1;
            if (one) {
              if (k == 0) sts32(sb + C_BAD, n + 1);
              mbar_expect(mb, b ? 4096 : 2048);
              m_fetch(sb, ring * 65536 + ((near >> ring) & 1) * 4096, b, mb);
            }
            __syncwarp();
            spin_guard(it);
          }
          TR(41 + b * 4); CNT(6 + b, it);
        }
        ring = ring + 1 == MRING ? 0 : ring + 1;
        if (!odd) {
          if (n < STEPS) { TRSYNC(); TRDUMP(n - 2); }
        } else if (n > 0) {
          unsigned char* o = g_oimg + (uint32_t)(((n - 1) & (RING - 1)) * (N_CHAIN * 8192) + j * 4096);
          bar_sync(B_G, 160);
          fence_async_smem();
          if (one) {
            bulk_store(o + c * 8192, sb + C_Q, 4096);
            bulk_store(o + (c ^ 1) * 8192, sb + C_Q + 4096, 4096);
            asm volatile("cp.async.bulk.commit_group;\ncp.async.bulk.wait_group.read 0;" ::: "memory");
            { const int n_ = n - 1; { const int n = n_; T3(4); (void)n; } }
          }
          __syncwarp();
          if (n < STEPS) bar_arrive(B_R, 64);
          if (one) {
            bulk_done_inc(g_fl + FL_O + c);
            { const int n_ = n - 1; { const int n = n_; T3(5); (void)n; } }
          }
          __syncwarp();
        }
      }
    } else {
      const uint32_t* ts = g_fl + FL_SYNC + near_half(XB_F + 1, c) * 1024 + lane * 2;
      uint32_t t0 = clk() - 100000;
#pragma unroll 1
      for (int n = 0; n < STEPS; n++) {
        const uint32_t src = ring * 65536 + ((near >> ring) & 1) * 4096;
        if (lane < 5) mbar_expect(sb + CB_M + lane * 8, lane ? 4096 : 2048);
        __syncwarp();
        if (elect()) {
#pragma unroll
          for (int b = 0; b < 5; b++) {
            wait_until(t0, P.dly[14 + b]);
            m_fetch(sb, src, b, sb + CB_M + b * 8);
            TR(40 + b * 4);
          }
        }
        __syncwarp();
        ring = ring + 1 == MRING ? 0 : ring + 1;
        uint32_t va, vb;
        const uint32_t off = timer_offset(), tag = (uint32_t)(n + 1) << 24;
        bar_sync(B_QK, 416);
        if (n + 1 == STEPS) break;
        sts32(sb + C_REF + 4, 0);
        const uint32_t c0 = clk(), stamp = c0 + off;
        st_relaxed_if(g_fl + FL_SYNC + lane * 1024 + c, tag | (stamp & 0xFFFFFF), lane < 2);
        TR(13);
        wait_until(c0, DLYS);
        int it = 0;
        do {
          asm volatile("ld.relaxed.gpu.global.v2.u32 {%0,%1}, [%2];" : "=r"(va), "=r"(vb) : "l"(ts) : "memory");
          spin_guard(it);
        } while (__any_sync(~0u, ((va ^ tag) | (vb ^ tag)) >> 24));
        const int late = __reduce_max_sync(~0u, max((int)((va - stamp) << 8), (int)((vb - stamp) << 8))) >> 8;
        t0 = c0 + min((uint32_t)late, clk() - c0);
        if (elect()) {
          sts32(sb + C_REF, t0);
          mbar_arrive(sb + CB_REF);
        }
        st_relaxed_if(g_fl + FL_TICK + lane * 1024, tag | ((t0 + off) & 0xFFFFFF), c == 0 && lane < 2);
        TR(14); CNT(11, it);
        bar_sync(B_M, 160);
      }
    }
  }
}

template <int WG>
__device__ __forceinline__ void g_math(const Params& P, uint32_t sb) {
  const int q = g_unit(WG);
  const int lane = threadIdx.x & 31, w = (threadIdx.x >> 5) & 3;
  const bool isq = q >= 64;
  uint32_t a[136];
  {
    const uint32_t stage = sb + G_W + WG * 73728;
    mbar_wait(sb + W_BAR + WG * 8, 0);
    if (threadIdx.x == 0) TS(23);
    load_frags<34>(a, stage);
    fence_async_smem();
    bar_sync(B_WG0 + WG, 128);
    if (threadIdx.x == 0) TS(24);
    load_wg(P, sb, false, WG, w);
    if (threadIdx.x == 0) TS(25);
    mbar_wait(sb + W_BAR + WG * 8, 1);
  }
  if ((threadIdx.x & 127) == 0) TS(4);
  const uint32_t off0 = (q & 31) * 49152 + (q >> 5) * 8192 +
                        (isq ? (w >> 1) * 4096 + (w & 1) * 512 + lane * 16 : w * 1024 + (lane >> 2) * 64 + (((lane ^ (lane >> 3)) & 3) << 4));
#pragma unroll 1
  for (int n = 0; n < STEPS; n++) {
    float d0[32], d1[32];
    if (WG == 0 && n >= LOCK0) bar_sync(B_OE, 160);
    if (n > 0) bar_sync(B_V + WG, 256);
#pragma unroll
    for (int ch = 0; ch < 9; ch++) {
      mbar_wait(sb + G_BAR + ch * 8, n & 1);
      if (ch == 0) { if ((threadIdx.x & 127) == 0) T3(5 + WG * 3); __syncwarp(); }
      if (ch == 4) { if ((threadIdx.x & 127) == 0) T3(6 + WG * 3); __syncwarp(); }
      if (ch == 8 && (WG == 0 ? n > 0 : n + 1 < STEPS)) bar_arrive(B_V + (WG ^ 1), 256);
      wg_fence();
#pragma unroll
      for (int kk = 0; kk < 4 - FASTG; kk++) {
        const int i = ch * 4 + kk;
        float* d = i & 1 ? d1 : d0;
        const uint64_t db = desc_sw128(G_RING + ch * 8192 + (kk & 2) * 32);
        if (i < 2) wg_rs64<0>(d, a + i * 4, db);
        else if (i < 34) wg_rs64<1>(d, a + i * 4, db);
        else wg_ss64<1>(d, desc_sw128(G_W2 + WG * 4096 + (i - 34) * 2048), db);
        wg_ss64<1>(d, desc_sw128(G_W + WG * 73728 + i * 2048), db + 2);
      }
      wg_commit();
      if (ch > 0) { wg_wait<1>(); if (lane == 0) mbar_arrive(sb + G_BAR + 128 + (ch - 1) * 8); }
    }
    wg_wait<0>();
    if (lane == 0) mbar_arrive(sb + G_BAR + 128 + 8 * 8);
    if ((threadIdx.x & 127) == 0) T3(7 + WG * 3);
    __syncwarp();
    uint32_t tw = clk() + (WG ? 0 : DLYW);
    unsigned char* base = g_qkv + (size_t)(n & (QRING - 1)) * (N_CHAIN * 24576);
    if ((ABL & 1) && d0[0] != 1234.5f) {
    } else if (isq) {
#pragma unroll
      for (int i = 0; i < 8; i++) {
        const float *d = (i < 4 ? d0 : d1) + 4 * i, *e = (i < 4 ? d1 : d0) + 4 * i;
        wait_until(tw, 0); tw += P.dly[2 + WG];
        *(uint4*)(base + off0 + (i >> 2) * 24576 + (i & 3) * 1024) =
          make_uint4(movmat(pack2(d[0], d[1])), movmat(pack2(e[0], e[1])), movmat(pack2(d[2], d[3])), movmat(pack2(e[2], e[3])));
      }
    } else {
#pragma unroll
      for (int i = 0; i < 8; i++) {
        const float* d = (i < 4 ? d0 : d1) + 8 * (i & 2) + 2 * (i & 1);
        wait_until(tw, 0); tw += P.dly[2 + WG];
        *(uint4*)(base + off0 + (i >> 2) * 24576 + (i & 2) * 2048 + (i & 1) * 512) =
          make_uint4(pack2(d[0], d[1]), pack2(d[4], d[5]), pack2(d[8], d[9]), pack2(d[12], d[13]));
      }
    }
    bar_arrive(B_M + WG, 160);
  }
}

__device__ __forceinline__ void fill16(void* p, uint32_t v) {
  asm volatile("st.global.v4.u32 [%0], {%1,%1,%1,%1};" :: "l"(p), "r"(v) : "memory");
}
__device__ __forceinline__ void g_load(const Params& P, uint32_t sb) {
  const int lane = threadIdx.x & 31, w = __shfl_sync(~0u, (threadIdx.x >> 5) & 3, 0);
  if (w == 2) return;
  uint32_t fl = 0;
#pragma unroll 1
  for (int n = w == 3 ? LOCK0 : 0; n < STEPS; n++) {
    if (w && n == LOCK0) { grid_wait(1, lds32(sb + S_GEN)); fl = near_half(XB_F, bid()) * 1024; }
    if (w == 3) {
      const uint32_t tag = (uint32_t)(n - LOCK0 + 1) << 24;
      uint32_t v; int it = 0;
      do { asm volatile("ld.relaxed.gpu.global.u32 %0, [%1];" : "=r"(v) : "l"(g_fl + fl + FL_TICK) : "memory"); spin_guard(it); } while (!NOCHAIN && v < tag);
      const uint32_t off = timer_offset(), now = clk(), t0 = now - ((v ^ tag) >> 24 ? DLYG : (now + off - v) & 0xFFFFFF);
      asm volatile("fence.acquire.gpu;" ::: "memory");
      if (lane == 0) T3(11);
      __syncwarp();
      wait_until(t0, DLYG);
      if (lane == 0) T3(4);
      bar_sync(B_OE, 160);
      continue;
    }
    if (w == 0 || n == 0) {
      if (n < NSEG) wait_flags(g_lnflag + n * 16 + (lane & 1) * 8, 1);
    } else if (!NOCHAIN && n >= LAG) {
      wait_flags(g_fl + fl + FL_F + (lane & 1) * 8, n - LAG + 1);
    }
    if (w) { if (lane == 0) T3(12); bar_sync(B_X, 96); }
    fence_async_global();
    const unsigned char* src = g_lnimg + (uint32_t)((w ? (n >= LAG ? NSEG + n - LAG : 0) : min(n, NSEG - 1)) * 36864);
#pragma unroll 1
    for (int ch = 0; ch < 9; ch++) {
      const uint32_t full = sb + G_BAR + ch * 8;
      mbar_wait(full + 128, (n & 1) ^ 1);
      if (elect()) {
        mbar_expect(full, ABL & 2 ? 16 : 4096);
        bulk_load(sb + G_RING + ch * 8192 + w * 4096, src + ch * 4096, ABL & 2 ? 16 : 4096, full);
      }
    }
  }
}

__device__ __forceinline__ void g_aux(const Params& P, uint32_t sb) {
  const int lane = threadIdx.x & 31, w = (threadIdx.x >> 5) & 3;
  if (w == 1 || w == 2) {
    const int q = g_unit(w - 1);
    uint32_t* f = g_fl + FL_G + q * 8;
#pragma unroll 1
    for (int n = 0; n < STEPS; n++) {
      const uint32_t ln = opaque_tid() & 31;
      uint4* z = (uint4*)g_oacc + (uint32_t)(((n + 1) % ARING) * (16 * DM) + q * 96 + ln);
      if (!(ABL & 16)) { fill16(z, 0); fill16(z + 32, 0); fill16(z + 64, 0); }
      if (n + 3 >= MRING && q < 80) fill16((uint4*)g_mimg + (uint32_t)(((n + 3) % MRING) * 4096 + q * 32 + ln), SENT);
      bar_sync(B_M + (w - 1), 160);
      if (lane == 0) { T3(w * 2 - 2); fence_async_global(); flag_release(f, n + 1); T3(w * 2 - 1); }
      __syncwarp();
    }
  } else {
    const uint32_t u = (bid() - N_CHAIN) * 2 + (w & 1), r = u / 36 * 16 + (u & 3) * 4 + (lane >> 3);
    uint32_t o = r * (DM / 8) + (u % 36 >> 2) * 8 + ((lane & 7) ^ ((r >> 1) & 3)), fl = 0;
#pragma unroll 1
    for (int k = -LAG - 1; k < STEPS; k++) {
      if (k < NSEG - 1) bar_sync(B_X, 96);
      if (k < LAG || u >= 72) continue;
      if (k == NSEG - 1) { fl = near_half(XB_F, bid()) * 1024; wait_flags(g_fl + fl + FL_F + (lane & 1) * 8, NSEG + 1); }
      const uint4 x = __ldcg((const uint4*)P.out + o);
      if (k >= NSEG - 1) wait_flags(g_fl + fl + FL_OCNT + (max(k, NSEG) % OCRING) * 8, N_O * 3 * (max(k, NSEG) / OCRING + 1));
      const float4* a = (const float4*)g_oacc + ((k % ARING) * (16 * DM) + 8 * DM + u * 64 + lane * 2);
      const float4 p = __ldcg(a), v = __ldcg(a + 1);
      ((uint4*)P.out)[o] = make_uint4(badd2(x.x, pack2(p.x, p.y)), badd2(x.y, pack2(p.z, p.w)), badd2(x.z, pack2(v.x, v.y)), badd2(x.w, pack2(v.z, v.w)));
      o += 4 * DM;
    }
    if ((threadIdx.x & 127) == 0) TS(7);
  }
}

template <int WG, bool HALF, int KS, int N> __device__ __forceinline__ void o_mma(float* d, const uint32_t* a, uint32_t ob) {
  constexpr uint64_t db = desc_sw128(O_RING + (KS >> 2) * 8192 + (KS & 3) * 32);
  constexpr uint64_t da = desc_sw128(O_W + WG * 40960 + (KS < 40 ? KS / 5 * 2 + KS % 5 / 2 : KS - 24) * 2048);
  if constexpr (KS < 40 && !(KS % 5 & 1)) {
    const uint32_t* r = a + (KS / 5 * 3 + KS % 5 / 2) * 4;
    if constexpr (HALF) wg_rs32k<KS != 0, db>(d, r[0], r[1], r[2], r[3], ob); else wg_rs64<KS != 0>(d, r, db);
  } else {
    if constexpr (HALF) wg_ss32k<da, db>(d, ob); else wg_ss64<1>(d, da, db);
  }
  if constexpr (N > 1) o_mma<WG, HALF, KS + 1, N - 1>(d, a, ob);
}
template <int WG, bool HALF, int GR> __device__ __forceinline__ void o_groups(float* d, const uint32_t* a, uint32_t sb, int n, bool more) {
  const uint32_t ob = n < NSEG ? 0 : 256;
  mbar_wait(sb + O_BAR + GR * 8, n & 1);
  if (GR == 0) { if ((threadIdx.x & 127) == 0) T3(13 + WG); __syncwarp(); }
  if (GR == (WG == 0 ? OTURN : 4) && (WG < 2 || n + 1 < STEPS)) bar_arrive(B_V + (WG + 1) % 3, 256);
  wg_fence();
  o_mma<WG, HALF, GR * 8, 8 - 2 * FASTG>(d, a, ob);
  if (GR == 4 && more) o_mma<WG, HALF, 40, 4>(d, a, ob);
  wg_commit();
  if (GR > 0) { wg_wait<1>(); if ((threadIdx.x & 31) == 0) mbar_arrive(sb + O_BAR + 128 + (GR - 1) * 8); }
  if constexpr (GR < 4) o_groups<WG, HALF, GR + 1>(d, a, sb, n, more);
}
template <int WG, bool HALF> __device__ __forceinline__ void o_step(const uint32_t* a, uint32_t sb, uint32_t st0, int n, bool more) {
  float d[HALF ? 16 : 32];
  if (WG > 0 || n > 0) bar_sync(B_V + WG, 256);
  o_groups<WG, HALF, 0>(d, a, sb, n, more);
  wg_wait<0>();
  if ((threadIdx.x & 31) == 0) mbar_arrive(sb + O_BAR + 128 + 4 * 8);
  if ((threadIdx.x & 127) == 0) T3(WG == 0 ? 1 : WG == 1 ? 8 : 12);
  __syncwarp();
#pragma unroll(HALF ? 1 : 2)
  for (int sl = 0; sl < 2; sl++) {
    mbar_wait(sb + OB_ST + WG * 16 + sl * 8, (n & 1) ^ (WG == 0));
    if (!HALF || sl == (n >= NSEG)) {
#pragma unroll
      for (int nb = 0; nb < 4; nb++) {
        const float* r = d + (HALF ? 0 : sl * 16) + nb * 4;
        const uint32_t ad = st0 + sl * 8192 + nb * 2048;
        sts32(ad, __float_as_uint(r[0]));
        sts32(ad + 256, __float_as_uint(r[1]));
        sts32(ad ^ 32, __float_as_uint(r[2]));
        sts32((ad ^ 32) + 256, __float_as_uint(r[3]));
      }
      fence_async_smem();
    }
    bar_arrive((sl ? B_G : B_M) + WG, 160);
  }
}
template <int WG>
__device__ __forceinline__ void o_math(const Params& P, uint32_t sb) {
  const bool more = bid() < N_CHAIN + N_G + 12;
  const int lane = threadIdx.x & 31, w = (threadIdx.x >> 5) & 3, g = lane >> 2, tq = lane & 3;
  uint32_t a[96];
  mbar_wait(sb + W_BAR + WG * 8, 0);
  load_frags<24>(a, sb + WG * 49152);
  fence_async_smem();
  bar_sync(B_INIT, 416);
  load_wg(P, sb, false, WG, w);
  mbar_wait(sb + W_BAR + WG * 8, 1);
  if ((threadIdx.x & 127) == 0) TS(4);
  const uint32_t st0 = sb + O_ST + tq * 512 + ((w * 16 + g) ^ (tq * 8)) * 4;
#pragma unroll 1
  for (int n = 0; n < STEPS; n++) {
    if (n < LAG || n >= NSEG) o_step<WG, true>(a, sb, st0, n, more); else o_step<WG, false>(a, sb, st0, n, more);
  }
}

__device__ __forceinline__ void o_aux(const Params& P, uint32_t sb) {
  const int i = bid() - N_CHAIN - N_G, ksl = i / 3;
  const int c0 = ksl * 11 - max(ksl - 4, 0), nc = ksl < 4 ? 11 : 10;
  const int lane = threadIdx.x & 31, w = __shfl_sync(~0u, (threadIdx.x >> 5) & 3, 0);
  if (w == 0) {
    bar_sync(B_INIT, 416);
    const uint32_t* f = g_fl + FL_O + near_half(XB_F + 1, bid()) * 1024 + min((c0 & ~1) + lane, (c0 + nc - 1) | 1);
#pragma unroll 1
    for (int n = 0; n < STEPS; n++) {
      const unsigned char* src = g_oimg + (uint32_t)(((n % RING) * N_CHAIN + c0) * 8192);
      if (!NOCHAIN) wait_flags(f, n + 1);
      fence_async_global();
      if (lane == 0) T3(0);
#pragma unroll
      for (int gr = 0; gr < 5; gr++) {
        const uint32_t full = sb + O_BAR + gr * 8, bytes = ABL & 4 ? 16 : (gr < 4 ? 2 : nc - 8) * 8192;
        mbar_wait(full + 128, (n & 1) ^ 1);
        if (elect()) {
          if (n < LAG || n >= NSEG) {
            mbar_expect(full, bytes >> 1);
            for (uint32_t o = gr * 16384 + (n < LAG ? 0 : 4096); o < gr * 16384 + bytes; o += 8192) bulk_load(sb + O_RING + o, src + o, 4096, full);
          } else {
            mbar_expect(full, bytes);
            bulk_load(sb + O_RING + gr * 16384, src + gr * 16384, bytes, full);
          }
        }
      }
    }
  } else {
#pragma unroll 1
    for (int n = 0; n < STEPS; n++) {
      float* dst = g_oacc + (uint32_t)((n % ARING) * (64 * DM) + ((i % 3) * 3 + (w - 1 + ksl) % 3) * 1024);
      const bool early = w == 3 && n < NSEG;
      bar_sync(B_M + (w - 1), 160);
      if (lane == 0) {
        T3(w * 2);
        if (n < NSEG && !(ABL & 8)) { bulk_reduce(dst, sb + O_ST, 4096); bulk_reduce(dst + 16 * DM, sb + O_ST + 4096, 4096); }
        asm volatile("cp.async.bulk.commit_group;" ::: "memory");
        if (early) {
          asm volatile("cp.async.bulk.wait_group.read 0;" ::: "memory");
          mbar_arrive(sb + OB_ST);
          T3(8 + w);
          bulk_done_inc(g_fl + FL_OCNT + (n % OCRING) * 8);
          T3(w * 2 + 1);
        }
      }
      __syncwarp();
      bar_sync(B_G + (w - 1), 160);
      if (lane == 0) {
        if (n >= LAG && !(ABL & 8)) { bulk_reduce(dst + 32 * DM, sb + O_ST + 8192, 4096); bulk_reduce(dst + 48 * DM, sb + O_ST + 12288, 4096); }
        asm volatile("cp.async.bulk.commit_group;\ncp.async.bulk.wait_group.read 1;" ::: "memory");
        if (!early) mbar_arrive(sb + OB_ST + (w % 3) * 16);
        asm volatile("cp.async.bulk.wait_group.read 0;" ::: "memory");
        mbar_arrive(sb + OB_ST + (w % 3) * 16 + 8);
        if (!early) {
          T3(8 + w);
          bulk_done_inc(g_fl + FL_OCNT + (n % OCRING) * 8);
          T3(w * 2 + 1);
        }
      }
      __syncwarp();
    }
  }
}

constexpr uint32_t Y_PITCH = 1168, Y_ROWS = 16 * Y_PITCH;
template <int R> __device__ __forceinline__ void y_rows(uint32_t* y, uint32_t src, uint32_t dst, int w, int bar) {
  const int lane = threadIdx.x & 31;
#pragma unroll
  for (int k = 0; k < 2 * R + 1; k++) {
    const int op = w + k * (16 / R);
    if (k == 2 * R && w >= 4) break;
    uint32_t a, b, c, d;
    ldsm4t(a, b, c, d, src + op * 512 + (lane & 16) * 16 + (lane & 7) * 32 + (lane & 8) * 2);
    stsm4(dst + (lane & 15) * Y_PITCH + op * 32 + (lane & 16), a, b, c, d);
  }
  bar_sync(bar, 512 / R);
  const uint32_t row = dst + ((w & 6) * 2 + (w >> 3) * 2 + (w & 1)) * Y_PITCH + lane * 4;
#pragma unroll
  for (int i = 0; i < 9 * R; i++) y[i] = lds32(row + i / 9 * 2 * Y_PITCH + i % 9 * 128);
}

__device__ __forceinline__ void f_role(const Params& P, uint32_t sb) {
  const int lane = threadIdx.x & 31, w = __shfl_sync(~0u, threadIdx.x >> 5, 0), r0 = (bid() - N_CHAIN - N_G - N_O) * 16;
  if (w == 8) {
    const uint32_t* fo = g_fl + FL_OCNT + near_half(XB_F, bid()) * 1024;
    fence_async_global();
#pragma unroll 1
    for (int n = 0; n < NSEG; n++) {
      bar_sync(2, 288);
      if (elect()) {
        mbar_expect(sb + F_BAR, 36864);
        bulk_load(sb + F_XY, P.X + (size_t)(n * 32 + r0) * DM, 18432, sb + F_BAR);
        bulk_load(sb + F_XY + 18432, g_yT + (size_t)(n * 32 + r0) * DM, 18432, sb + F_BAR);
        mbar_expect(sb + F_BAR + 8, 36864);
        T3(1);
      }
      wait_flags(fo + (n % OCRING) * 8, NOCHAIN == 5 ? 0 : N_O * 3 * (n / OCRING + 1));
      fence_async_global();
      if (elect()) { bulk_load(sb + F_A, g_oacc + (uint32_t)((n % ARING) * (64 * DM) + r0 * DM), 36864, sb + F_BAR + 8); T3(0); }
    }
  } else if (w == 9) {
#pragma unroll 1
    for (int n = 0; n < NSEG; n++) {
      const uint32_t st = sb + (n & 1) * 36864;
      unsigned char* p = g_lnimg + (uint32_t)((NSEG + n) * 36864 + r0 * 128);
      bar_sync(1, 288);
      if (elect()) {
        T3(2);
#pragma unroll
        for (int i = 0; i < 9; i++) bulk_store(p + i * 4096, st + F_L + i * 2048, 2048);
        asm volatile("cp.async.bulk.commit_group;" ::: "memory");
        bulk_done_inc(g_fl + FL_F + (bid() & 1) * 8);
        T3(3);
        bulk_store(P.out + (size_t)(n * 32 + r0) * DM, st + F_X, 18432);
        asm volatile("cp.async.bulk.commit_group;\ncp.async.bulk.wait_group.read 0;" ::: "memory");
        if (n + 1 == NSEG) bulk_done_inc(g_fl + FL_F + (bid() & 1) * 8);
      }
      __syncwarp();
    }
  } else if (w < 8) {
    const uint32_t row = sb + w * 1152 + lane * 4, acc = sb + F_A + w * 256 + (lane ^ ((w & 6) * 2)) * 8;
    const uint32_t ln = sb + F_L + w * 128 + (((lane >> 2) ^ w) << 4) + (lane & 3) * 4;
#pragma unroll 1
    for (int n = -1; n < NSEG; n++) {
      const uint32_t st = (n & 1) * 36864;
      uint32_t x[18], y[18], l[18];
      if (n >= 0) mbar_wait(sb + F_BAR, n & 1);
#pragma unroll
      for (int i = 0; i < 18; i++) x[i] = lds32(row + F_XY + i / 9 * 9216 + i % 9 * 128);
      y_rows<2>(y, sb + F_XY + 18432, sb + F_Y, w, 3);
      layernorm9<2>(x, l);
#pragma unroll
      for (int i = 0; i < 18; i++) x[i] = badd2(x[i], bmul2(l[i], y[i]));
      if (n >= 0) mbar_wait(sb + F_BAR + 8, n & 1);
      if (threadIdx.x == 0 && n >= 0) T3(4);
      __syncwarp();
      uint2 a[18];
#pragma unroll
      for (int i = 0; i < 18; i++) a[i] = lds64(acc + i / 9 * 2048 + i % 9 * 4096);
#pragma unroll
      for (int i = 0; i < 18; i++) x[i] = badd2(x[i], pack2(__uint_as_float(a[i].x), __uint_as_float(a[i].y)));
      if (n + 1 < NSEG) bar_arrive(2, 288);
      layernorm9<2>(x, l);
#pragma unroll
      for (int i = 0; i < 18; i++) { x[i] = badd2(x[i], bmul2(l[i], y[i])); sts32(row + st + F_X + i / 9 * 9216 + i % 9 * 128, x[i]); }
      layernorm9<2>(x, l);
#pragma unroll
      for (int i = 0; i < 18; i++) sts32(ln + st + i / 9 * 1024 + i % 9 * 2048, l[i]);
      fence_async_smem();
      if (n >= 0) bar_sync(1, 288); else bar_sync(3, 256);
    }
  }
}

constexpr uint32_t P_CH = 147456, P_CHSZ = 12800, P_H = 4352;
static_assert(P_CH + 6 * P_CHSZ <= G_BAR, "prologue smem");

template <int N>
__device__ __forceinline__ void conv_fold(float (*acc)[4], bool hi, uint32_t mine, uint32_t theirs, int bar, int cnt) {
#pragma unroll
  for (int i = 0; i < N / 2; i++) {
    uint4 v;
    v.x = __float_as_uint(hi ? acc[i][0] : acc[i + N / 2][0]); v.y = __float_as_uint(hi ? acc[i][1] : acc[i + N / 2][1]);
    v.z = __float_as_uint(hi ? acc[i][2] : acc[i + N / 2][2]); v.w = __float_as_uint(hi ? acc[i][3] : acc[i + N / 2][3]);
    sts128(mine + i * 512, v);
  }
  bar_sync(bar, cnt);
#pragma unroll
  for (int i = 0; i < N / 2; i++) {
    const uint4 v = lds128(theirs + i * 512);
    acc[i][0] = (hi ? acc[i + N / 2][0] : acc[i][0]) + __uint_as_float(v.x); acc[i][1] = (hi ? acc[i + N / 2][1] : acc[i][1]) + __uint_as_float(v.y);
    acc[i][2] = (hi ? acc[i + N / 2][2] : acc[i][2]) + __uint_as_float(v.z); acc[i][3] = (hi ? acc[i + N / 2][3] : acc[i][3]) + __uint_as_float(v.w);
  }
}
template <int N>
__device__ __forceinline__ void conv_store(const float (*acc)[4], int tile0, uint32_t su, int d, uint32_t dd) {
  const int lane = threadIdx.x & 31, g = lane >> 2, tq = lane & 3;
#pragma unroll
  for (int i = 0; i < N; i++) {
    const uint32_t ad = su + (8 + (tile0 + i) * 8 + g) * 32 + tq * 4, sw = (g & 4) << 2;
    const uint32_t lo = badd2(movmat(pack2(acc[i][0], acc[i][1])), bmul2(lds32(ad + sw), dd));
    const uint32_t hi = badd2(movmat(pack2(acc[i][2], acc[i][3])), bmul2(lds32(ad + (sw ^ 16)), dd));
    ((uint2*)g_yT)[(((tile0 + i) * 8 + g) * DM + d) * 4 + tq] = make_uint2(lo, hi);
  }
}

__device__ __forceinline__ void prologue(const Params& P, uint32_t sb) {
  const int b = bid(), tid = threadIdx.x, lane = tid & 31, warp = tid >> 5, t0 = b * 16;
  const bool isg = b >= N_CHAIN && b < N_CHAIN + N_G;
  const int nch = isg ? 2 : b < 128 ? 6 : 0, chb = b < N_CHAIN ? b * 6 : isg ? b * 2 + 256 : b * 6 - 192;
  const uint32_t tstart = clk();
  if (tid < 288) {
    if (b < 128) {
      const int c = (tid >> 1) * 4, tt = t0 + (tid & 1) * 8;
      uint2 kr[11], vr[8];
#pragma unroll
      for (int i = 0; i < 11; i++) { const int t = tt + i - 3; kr[i] = t >= 0 ? __ldg((const uint2*)(P.K + (size_t)t * DM + c)) : make_uint2(0, 0); }
#pragma unroll
      for (int i = 0; i < 8; i++) vr[i] = __ldg((const uint2*)(P.V + (size_t)(tt + i) * DM + c));
#pragma unroll
      for (int e = 0; e < 2; e++) {
        const uint4 sh = __ldg((const uint4*)(P.shift + c * 4) + e);
        const uint32_t s0 = __byte_perm(sh.x, sh.z, 0x5410), s1 = __byte_perm(sh.x, sh.z, 0x7632);
        const uint32_t s2 = __byte_perm(sh.y, sh.w, 0x5410), s3 = __byte_perm(sh.y, sh.w, 0x7632);
        uint32_t v[8];
#pragma unroll
        for (int i = 0; i < 8; i++) {
          const uint32_t k3 = e ? kr[i].y : kr[i].x, k2 = e ? kr[i + 1].y : kr[i + 1].x, k1 = e ? kr[i + 2].y : kr[i + 2].x, k0 = e ? kr[i + 3].y : kr[i + 3].x;
          v[i] = bmul2(badd2(badd2(badd2(bmul2(k3, s3), bmul2(k2, s2)), bmul2(k1, s1)), bmul2(k0, s0)), e ? vr[i].y : vr[i].x);
        }
        *(uint4*)(g_kvT + (size_t)(c + 2 * e) * KVP + tt) =
          make_uint4(__byte_perm(v[0], v[1], 0x5410), __byte_perm(v[2], v[3], 0x5410), __byte_perm(v[4], v[5], 0x5410), __byte_perm(v[6], v[7], 0x5410));
        *(uint4*)(g_kvT + (size_t)(c + 2 * e + 1) * KVP + tt) =
          make_uint4(__byte_perm(v[0], v[1], 0x7632), __byte_perm(v[2], v[3], 0x7632), __byte_perm(v[4], v[5], 0x7632), __byte_perm(v[6], v[7], 0x7632));
      }
    }
  } else if (tid < 384) {
    const int t = tid - 288;
    for (int i = t; i < 32 * nch; i += 96) asm volatile("prefetch.global.L2 [%0];" :: "l"(P.Hk + (size_t)chb * SEQ + i * 64));
    for (int i = b * 96 + t; i < 32 * DM; i += N_CTA * 96) ((uint4*)g_oacc)[i] = make_uint4(0, 0, 0, 0);
    if (b * 96 + t < 128 * 8) g_lnflag[b * 96 + t] = 0;
    if (t == 95) sts32(sb + S_GEN, ld_acquire(g_gbar));
  }
  if (warp < 12) {
    bar_arrive(10, 448);
    if (tid == 128) TS(14);
    const int ch = warp >> 1, sub = warp & 1, d = chb + ch;
    const uint32_t su = sb + P_CH + ch * P_CHSZ;
    if (ch < nch) {
      const uint32_t* hs = (const uint32_t*)(P.Hk + (size_t)d * SEQ);
#pragma unroll
      for (int q = sub * 32 + lane; q < 256; q += 64) {
        const uint4 c = __ldg((const uint4*)hs + q);
        const uint32_t prev = q ? __ldg(hs + 4 * q - 1) : 0u;
        sts128(su + P_H + 32 + q * 16, make_uint4(__byte_perm(c.x, prev, 0x7610), __byte_perm(c.y, c.x, 0x7610), __byte_perm(c.z, c.y, 0x7610), __byte_perm(c.w, c.z, 0x7610)));
        sts128(su + P_H + 4224 + q * 16, make_uint4(__byte_perm(c.x, 0, 0x1032), __byte_perm(c.y, 0, 0x1032), __byte_perm(c.z, 0, 0x1032), __byte_perm(c.w, 0, 0x1032)));
      }
      if (sub == 1 && lane == 0) sts32(su + P_CHSZ - 16, __bfloat16_as_ushort(P.Dk[d]) * 0x10001u);
      if (sub == 0 && lane < 20) sts128(su + (lane < 16 ? lane * 16 : P_H + (lane & 2) * 2096 + (lane & 1) * 16), make_uint4(0, 0, 0, 0));
    }
    bar_sync(11, 416);
    if (ch < nch) {
#pragma unroll
      for (int q = sub * 32 + lane; q < 256; q += 64) {
        const int row = (q >> 1) + 8;
        sts128(su + row * 32 + (((q & 1) ^ ((row >> 2) & 1)) << 4), __ldcg((const uint4*)(g_kvT + (size_t)d * KVP) + q));
      }
    }
    const int g = lane >> 2, tq = lane & 3;
    const uint32_t sh = su + P_H + (g & 1) * 4192 + (8 + (g >> 1) - tq) * 4;
    float acc[16][4];
#pragma unroll
    for (int i = 0; i < 16; i++) { acc[i][0] = acc[i][1] = acc[i][2] = acc[i][3] = 0.f; }
    auto u_addr = [&](int res) {
      const int row = 8 - res + ((lane >> 4) << 3) + (lane & 7);
      return su + row * 32 + ((((lane >> 3) & 1) ^ ((row >> 2) & 1)) << 4);
    };
    if (ch < nch) {
      bar_sync(1 + ch, 64);
      if (tid == 0) TS(11);
      if (sub) {
#pragma unroll 4
        for (int res = 0; res < 8; res++) {
          uint32_t b0, b1, b2, b3;
          ldsm4(b0, b1, b2, b3, u_addr(res));
          const uint32_t r0 = lds32(sh + res * 32);
          mma16(acc[0], r0, lds32(sh + res * 32 + 16), lds32(sh + res * 32 - 16), r0, b0, b1);
        }
        conv_store<1>(acc, 0, su, d, lds32(su + P_CHSZ - 16));
      }
    }
    bar_arrive(12, 416);
    if (isg && warp >= 4) { while ((int)(clk() - tstart - S1G) < 0) __nanosleep(200); load_wg(P, sb, true, warp >> 3, warp & 3); }
    if (ch < nch) {
#pragma unroll 1
      for (int res = sub * 4; res < sub * 4 + 4; res++) {
        uint32_t bf[16][2];
        const uint32_t ad = u_addr(res);
#pragma unroll
        for (int f = 0; f < 16; f += 2) ldsm4(bf[f][0], bf[f][1], bf[f + 1][0], bf[f + 1][1], ad + f * 256);
#pragma unroll
        for (int k = 0; k < 16; k++) {
          const int jj = k & 1 ? k >> 1 : 15 - (k >> 1);
          const uint32_t ah = sh + (8 * jj + res) * 32;
          const uint32_t r0 = lds32(ah), r1 = lds32(ah + 16), rm = lds32(ah - 16);
#pragma unroll
          for (int i = max(jj, 1); i < 16; i++) mma16(acc[i], r0, r1, rm, r0, bf[i - jj][0], bf[i - jj][1]);
        }
      }
      bar_sync(1 + ch, 64);
      if (tid == 0) TS(12);
      const uint32_t xb = su + P_H + lane * 16, dd = lds32(su + P_CHSZ - 16);
      conv_fold<16>(acc, sub, xb + sub * 4096, xb + (sub ^ 1) * 4096, 1 + ch, 64);
      conv_store<8>(acc, sub * 8, su, d, dd);
    }
  } else {
    for (int i = b; i < 194 + MRING * 5; i += N_CTA) {
      const int n = (i - 194) / 5, r = (i - 194) % 5, blk = i < 192 ? i / 6 * 8 + i % 6 : i < 194 ? XB_F + i - 192 : XB_M + n * 8 + r;
      const uint32_t fill = i < 194 ? 0u : SENT;
#pragma unroll 1
      for (int q = tid - 384; q < 256 && warp < 15; q += 96) {
        uint4 v = make_uint4(fill, fill, fill, fill);
        if (i >= 194 && n == 0 && (r > 0 || q < 128)) {
          const bf16* m = P.mem0 + (max(r * 8 - 4, 0) + (q >> 5)) * 16 + ((q >> 1) & 1) * 8 + ((q >> 2) & 7);
          v.x = pack2(__bfloat162float(m[0]), __bfloat162float(m[DM])); v.y = pack2(__bfloat162float(m[2 * DM]), __bfloat162float(m[3 * DM]));
          v.z = pack2(__bfloat162float(m[4 * DM]), __bfloat162float(m[5 * DM])); v.w = pack2(__bfloat162float(m[6 * DM]), __bfloat162float(m[7 * DM]));
        }
        g_xb[blk * 512 + q] = v;
        g_xb[blk * 512 + 256 + q] = v;
      }
    }
    if (tid < 388) g_xb[XB_REF * 512 + (tid & 2) * 128 + (b & ~1) + (tid & 1)] = make_uint4(0, 0, 0, 0);
    else if (tid < 392 && b < N_GRP) g_xb[(b * 8 + 7) * 512 + (tid & 2) * 128 + (tid & 1)] = make_uint4(0, 0, 0, 0);
    if (warp < 15) { bar_arrive(9, 128); bar_sync(7, 96); }
    if (tid == 384) TS(8);
    if (warp == 12) {
      const bf16* w = lane < 6 ? (lane % 3 == 0 ? P.Wk : lane % 3 == 1 ? P.Wv : P.Wq) + (((b >> 5) * 2 + lane / 3) * 32 + (b & 31)) * 2048
                               : (lane < 8 ? P.Wo + (lane - 6) * (9 * 131072) : P.X) + b * 2048;
      bar_sync(10, 448);
      uint32_t t = clk() + P.dly[19];
#pragma unroll 1
      for (int st = 0; st < 9 && b < N_CHAIN; st++) {
#pragma unroll 1
        for (int i = 0; i < 9; i++, t += PACE) {
          wait_until(t, 0);
          if (lane == st) asm volatile("cp.async.bulk.prefetch.L2.global [%0], 4096;" :: "l"(w + i * (lane < 6 ? 262144 : 131072)) : "memory");
        }
      }
      if (lane == 0) TS(10);
    } else if (warp == 15) {
      bar_sync(10, 448);
      if (lane == 0) { grid_arrive(0); if (nch) grid_wait(0, lds32(sb + S_GEN)); }
      __syncwarp();
      bar_arrive(11, 416);
      if (lane == 0) TS(1);
      bar_sync(9, 128);
      bar_sync(12, 416);
      if (lane == 0) { TS(16); grid_arrive(2); TS(17); }
    } else if (lane == 0) {
      if (warp == 13 || (warp == 14 && b < N_GRP)) {
        uint32_t* p = (uint32_t*)(g_xb + (warp == 13 ? XB_REF * 512 + b : (b * 8 + 7) * 512));
        int votes = 0;
        for (int rep = 0; rep < 24 && abs(votes) < 7; rep++) {
          uint32_t v0, v1, c0, c1;
          asm volatile("atom.relaxed.gpu.global.add.u32 %0, [%4], 0;\n atom.relaxed.gpu.global.add.u32 %1, [%5], 0;\n"
                       "{.reg .pred p; setp.eq.u32 p, %0, 0x7ffffff3; @p trap; mov.u32 %2, %%clock; setp.eq.u32 p, %1, 0x7ffffff3; @p trap; mov.u32 %3, %%clock;}"
                       : "=&r"(v0), "=&r"(v1), "=&r"(c0), "=&r"(c1) : "l"(p + (rep & 1) * 1024), "l"(p + ((rep & 1) ^ 1) * 1024) : "memory");
          votes += ((c1 - c0 > 80u) == (rep & 1)) ? 1 : -1;
        }
        if (warp == 13) { g_side[b] = votes > 0; TS(9); } else g_near[b] = votes > 0;
      }
    }
    __syncwarp();
    if (warp > 12 && b < N_CHAIN) {
      while ((int)(clk() - tstart - S1DLY) < 0) __nanosleep(200);
      for (int k = warp - 13; k < 8; k += 3) load_wg(P, sb, true, 1 - k / 4, k & 3);
    }
  }
  __syncthreads();
  if (tid == 511) { grid_arrive(1); TS(18); }
  if (tid == 0) TS(2);
}

template <int R> __device__ __forceinline__ void ln_tiles(const Params& P, uint32_t sb) {
  const int lane = threadIdx.x & 31, w = (threadIdx.x >> 5) & (16 / R - 1), half = R == 1 ? 0 : threadIdx.x >> 8, u = N_CTA - 1 - bid();
  const int first = R == 1 ? u : 46 - 2 * u + half, step = R == 1 ? 4 : 40, last = R == 1 ? 8 : 128;
  const uint32_t raw = sb + P_CH + half * (18432 + Y_ROWS), mb = sb + T_BAR + (R - 1 + half) * 8;
  const bool lead = w == 16 / R - 1 && lane == 0;
  auto load_y = [&](const bf16* src, int tile) {
    fence_async_global();
    mbar_expect(mb, 18432);
    bulk_load(raw, src + (size_t)tile * 16 * DM, 18432, mb);
  };
  uint32_t nx[9 * R];
  auto load_x = [&](int tile) {
#pragma unroll
    for (int i = 0; i < 9 * R; i++) nx[i] = __ldg((const uint32_t*)(P.X + (size_t)(tile * 16 + w + i / 9 * 8) * DM) + i % 9 * 32 + lane);
  };
  load_x(first);
  if (R == 2) {
    if (lead) { grid_wait(1, lds32(sb + S_GEN)); if (u > 3) TS(13); load_y(g_yT, first); }
    if (u >= N_F && w < 6) load_wg(P, sb, true, w >> 1, half * 2 + (w & 1));
    __syncwarp();
  }
#pragma unroll 1
  for (int tile = first, real = R - 1, ph = 0; tile < last; tile += real * step, real = 1, ph ^= 1) {
    uint32_t x[9 * R], l[9 * R], y[9 * R];
    const bool ts = threadIdx.x == 0 && (R == 1 ? tile == first : u > 3 && tile == first + step);
    if (ts) TS(26);
#pragma unroll
    for (int i = 0; i < 9 * R; i++) x[i] = nx[i];
    layernorm9<R>(x, l);
    if (real && tile + step < last) load_x(tile + step);
    if (R == 1 && tile == first && lead) {
      if (real) grid_wait(2, lds32(sb + S_GEN));
      TS(13);
      load_y(real ? g_yT : P.Hk, tile);
    }
    bar_sync(13 + half, 512 / R);
    mbar_wait(mb, ph);
    if (ts) TS(28);
    y_rows<R>(y, raw, raw + 18432, w, 13 + half);
    if (ts) TS(29);
    if (lead && real && tile + step < last) { fence_async_smem(); load_y(g_yT, tile + step); }
    __syncwarp();
#pragma unroll
    for (int i = 0; i < 9 * R; i++) x[i] = badd2(x[i], bmul2(l[i], y[i]));
    layernorm9<R>(x, l);
    if (ts && l[0] != 0x12345) TS(30);
#pragma unroll
    for (int r = 0; r < R; r++) store_ln_row(0, tile * 16 + w + r * 8, l + r * 9);
    if (R == 1) {
      __syncthreads();
      if (threadIdx.x == 32 && real) { if (tile < 4) TS(19); st_release(g_lnflag + tile * 8, 1); if (tile < 4) TS(20); }
      __syncwarp();
    }
    if (ts) TS(31);
  }
  if (R == 2) {
    __syncthreads();
    if (threadIdx.x >= 506) {
      asm volatile("fence.acq_rel.gpu;" ::: "memory");
      st_relaxed_if(g_lnflag + ((first ^ (lane & 1)) + (lane - 26) / 2 * step) * 8, 1, true);
    }
    __syncwarp();
    fence_async_smem();
    if (threadIdx.x == 0) TS(15);
  }
}

__global__ void __cluster_dims__(2, 1, 1) __launch_bounds__(512, 1) k_main(const __grid_constant__ Params P) {
  extern __shared__ __align__(1024) unsigned char smem[];
  const uint32_t sb = (uint32_t)__cvta_generic_to_shared(smem);
  const int b = bid(), wg = threadIdx.x >> 7;
  if ((threadIdx.x & 127) == 0) TS(0);
  if (threadIdx.x == 480) {
    if ((sb & 0xFFFFFF) != SBASE) __trap();
    for (int i = 0; i < 6; i++) mbar_init(sb + W_BAR + i * 8, 1);
    if (b < N_CHAIN) {
      mbar_init(sb + CB_FULL, 1); mbar_init(sb + CB_FULL + 8, 1);
      mbar_init(sb + CB_REF, 1);
      mbar_init(sb + CB_SX, 1); mbar_init(sb + CB_OX, 1); mbar_init(sb + CB_XX, 1); mbar_init(sb + CB_Q, 1); mbar_init(sb + CB_VF, 1); mbar_init(sb + CB_VF + 8, 1);
      sts32(sb + C_BAD, 0);
      for (int i = 0; i < 11; i++) mbar_init(sb + CB_M + i * 8, i == 0 ? 5 : i == 5 ? 2 : 1);
    } else if (b < N_CHAIN + N_G) {
      for (int i = 0; i < 9; i++) { mbar_init(sb + G_BAR + i * 8, 2); mbar_init(sb + G_BAR + 128 + i * 8, 8); }
    } else if (b < N_CHAIN + N_G + N_O) {
      for (int i = 0; i < 5; i++) { mbar_init(sb + O_BAR + i * 8, 1); mbar_init(sb + O_BAR + 128 + i * 8, 12); }
      for (int i = 0; i < 6; i++) mbar_init(sb + OB_ST + i * 8, 1);
    } else {
      mbar_init(sb + F_BAR, 1); mbar_init(sb + F_BAR + 8, 1);
    }
    asm volatile("fence.mbarrier_init.release.cluster;" ::: "memory");
    fence_async_smem();
  }
  __syncwarp();
  asm volatile("barrier.cluster.arrive.relaxed.aligned;" ::: "memory");
  prologue(P, sb);
  asm volatile("barrier.cluster.wait.aligned;" ::: "memory");
  fence_async_smem();
  if (b >= 128) ln_tiles<1>(P, sb);
  if (b >= N_CHAIN + N_G) ln_tiles<2>(P, sb);
  if ((threadIdx.x & 127) == 0) TS(3);
  if (b < N_CHAIN) {
    if (wg < 2) { reg_inc<200>(); chain_proj(P, sb); }
    else if (wg == 2) { reg_dec<ATTR>(); chain_attn(P, sb); }
    else { reg_dec<112 - ATTR>(); chain_aux(P, sb); }
  } else if (NOBULK) {
    {
      if (wg == 0) {
        float d[4] = {0.f, 0.f, 0.f, 0.f};
        for (int n = 0; n < STEPS - 1; n++) {
          const uint32_t* f = g_fl + FL_TICK;
          uint32_t x;
          do { for (int k = 0; k < 16; k++) mma16(d, 0, 0, 0, 0, 0, 0); asm volatile("ld.relaxed.gpu.global.u32 %0, [%1];" : "=r"(x) : "l"(f) : "memory"); } while ((x >> 24) <= n);
          const int q = (b - N_CHAIN) * 4 + (threadIdx.x >> 5);
          if (n + 5 >= MRING && q < 80) fill16((uint4*)g_mimg + (uint32_t)(((n + 5) % MRING) * 4096 + q * 32 + (threadIdx.x & 31)), SENT);
        }
        if (d[0] == 1.f) P.out[0] = __float2bfloat16(0.f);
      }
    }
  } else if (b < N_CHAIN + N_G) {
    if (wg == 0) { reg_inc<232>(); g_math<0>(P, sb); }
    else if (wg == 1) { reg_inc<232>(); g_math<1>(P, sb); }
    else if (wg == 2) { reg_dec<24>(); g_aux(P, sb); }
    else { reg_dec<24>(); g_load(P, sb); }
  } else if (b < N_CHAIN + N_G + N_O) {
    if (wg == 0) { reg_inc<160>(); o_math<0>(P, sb); }
    else if (wg == 1) { reg_inc<160>(); o_math<1>(P, sb); }
    else if (wg == 2) { reg_inc<160>(); o_math<2>(P, sb); }
    else { reg_dec<32>(); o_aux(P, sb); }
  } else {
    f_role(P, sb);
  }
}

}

extern "C" void kernel_launch(void* const* d_in, const int* in_sizes, int n_in, void* d_out, int out_size) {
  typedef CUresult (*Encode)(CUtensorMap*, CUtensorMapDataType, cuuint32_t, void*, const cuuint64_t*, const cuuint64_t*, const cuuint32_t*, const cuuint32_t*,
                             CUtensorMapInterleave, CUtensorMapSwizzle, CUtensorMapL2promotion, CUtensorMapFloatOOBfill);
  static Encode encode = nullptr;
  if (!encode) cudaGetDriverEntryPoint("cuTensorMapEncodeTiled", (void**)&encode, cudaEnableDefault);
  Params P;
  for (int i = 0; i < 11; i++) {
    const bool wo = i == 6 || i == 7;
    const cuuint64_t cols = wo ? DM : HD, rows = HD + DM - cols, pitch = cols * 2;
    const cuuint64_t dim[4][5] = {{cols, 2, 8, 2, 18}, {cols, 16, 1, 1, rows / 16}, {cols, 2, 4, 4, rows / 32}, {64, 16, 64, 2, 18}};
    const cuuint64_t stride[4][4] = {{8 * pitch, pitch, 16 * pitch, 32 * pitch}, {pitch, pitch, pitch, 16 * pitch},
                                     {pitch, 8 * pitch, 2 * pitch, 32 * pitch}, {pitch, 128, 16 * pitch, 32 * pitch}};
    const cuuint32_t box[4][5] = {{64, 2, 8, 1, 18}, {64, 16, 1, 1, 1}, {64, 2, 4, 2, 1}, {64, 16, 2, 1, 18}}, one[5] = {1, 1, 1, 1, 1};
    const int k = i < 3 ? 0 : i < 7 ? 1 : i < 8 ? 2 : 3;
    encode(&P.map[i], CU_TENSOR_MAP_DATA_TYPE_BFLOAT16, 5, d_in[wo ? 11 : 8 + (i & 7) % 3], dim[k], stride[k], box[k], one,
           CU_TENSOR_MAP_INTERLEAVE_NONE, CU_TENSOR_MAP_SWIZZLE_128B, CU_TENSOR_MAP_L2_PROMOTION_L2_128B, CU_TENSOR_MAP_FLOAT_OOB_FILL_NONE);
  }
  P.X = (const bf16*)d_in[0]; P.K = (const bf16*)d_in[1]; P.V = (const bf16*)d_in[2];
  P.shift = (const bf16*)d_in[3]; P.Hk = (const bf16*)d_in[4]; P.Dk = (const bf16*)d_in[5];
  P.mem0 = (const bf16*)d_in[7];
  P.Wq = (const bf16*)d_in[8]; P.Wk = (const bf16*)d_in[9]; P.Wv = (const bf16*)d_in[10]; P.Wo = (const bf16*)d_in[11];
  P.out = (bf16*)d_out;
  for (int i = 0; i < 24; i++) P.dly[i] = h_dly[i];
  cudaFuncSetAttribute(k_main, cudaFuncAttributeMaxDynamicSharedMemorySize, SMEM_BYTES);
  k_main<<<N_CTA, 512, SMEM_BYTES>>>(P);
}
```

```cpp
#include <cuda.h>
#include <cuda_runtime.h>
#include <cuda_bf16.h>
#include <stdint.h>

namespace {

typedef __nv_bfloat16 bf16;

constexpr int SEQ = 2048, DM = 576, HD = 4096, NSEG = 64;
#define PLACE 1
#define LAGV 7
constexpr int LAG = LAGV, STEPS = NSEG + LAG, RING = 8, QRING = 4;
static_assert(LAG < RING, "ring");
constexpr int N_CHAIN = 64, N_G = 48, N_O = 18, N_F = 2;
constexpr uint32_t SBASE = 1024;
constexpr uint32_t SENT = 0xFFFFFFFFu;
constexpr int SPIN_MAX = 1 << 22;

__device__ __forceinline__ uint32_t bid() {
  uint32_t b;
  asm volatile("mov.u32 %0, %%ctaid.x;" : "=r"(b));
  return b < 6 ? b + 106 : b < 8 ? b + 122 : b < 114 ? b - 8 : b < 130 ? b - 2 : b;
}
__device__ __forceinline__ uint32_t chain_id() { return blockIdx.x - (PLACE ? 8 : 0); }
constexpr int KVP = SEQ + 64;
__device__ __align__(1024) bf16 g_kvT[DM * KVP];
__device__ __align__(1024) bf16 g_yT[DM * SEQ];
__device__ __align__(1024) unsigned char g_lnimg[2 * NSEG * 9 * 4096];
__device__ __align__(1024) unsigned char g_qkv[QRING * N_CHAIN * 24576];
__device__ __align__(1024) unsigned char g_oimg[RING * N_CHAIN * 8192];
constexpr int ARING = 16;
static_assert(ARING >= LAG + 9, "accumulator ring");
__device__ __align__(1024) float g_oacc[ARING * 64 * DM];
constexpr int MRING = LAG + 4, N_GRP = 32 + MRING + 1;
constexpr int XB_M = 256, XB_F = XB_M + MRING * 8, XB_REF = XB_F + 2, N_CTA = N_CHAIN + N_G + N_O + N_F;
__device__ __align__(65536) uint4 g_xb[N_GRP * 4096];
#define g_mimg ((uint32_t*)(g_xb + XB_M * 512))
__device__ uint32_t g_near[N_GRP];
__device__ uint32_t g_side[N_CTA];
__device__ __align__(128) uint32_t g_gbar[3 * 32];
constexpr int FL_G = 0, FL_F = 96 * 8, FL_OCNT = FL_F + 2 * 8, OCRING = 16, FL_TICK = 992, FL_O = 2048, FL_SYNC = FL_O + 128;
static_assert(FL_OCNT + OCRING * 8 <= FL_TICK, "flag block");
#define g_fl ((uint32_t*)(g_xb + XB_F * 512))
__device__ __align__(1024) uint32_t g_lnflag[128 * 8];
#define TS(slot)

#define OTURN 2
#define LOCK0 3
#define FASTG 0
#define NOBULK 0
#define WFENCE 0
#define QPOS 0
#define VE 4
#define OGAP 2
#define NOCHAIN 0
#define BFENCE 2
#define ABL 0
#define ATTR 80
#define CNT(slot, tries)
#define T3(slot)
#define TR(slot)
#define TRV(slot, val)
#define TRD(slot, dep)
#define TRSYNC()
#define TRDUMP(n)
#define CLK(t) "{.reg .b64 x; .reg .b32 h; mov.u64 x, %%clock64; mov.b64 {" t ", h}, x;}"
__device__ __forceinline__ uint32_t clk() { uint32_t t; asm volatile(CLK("%0") : "=r"(t) :: "memory"); return t; }
__device__ __forceinline__ void wait_until(uint32_t t0, uint32_t d) {
  asm volatile("{.reg .pred p; .reg .u32 t;\n"
               "W: " CLK("t") " sub.u32 t, t, %0; setp.lt.s32 p, t, 0; @p bra.uni W;}"
               :: "r"(t0 + d) : "memory");
}
__device__ __forceinline__ uint32_t pack2(float lo, float hi) {
  uint32_t r; asm("cvt.rn.bf16x2.f32 %0, %1, %2;" : "=r"(r) : "f"(hi), "f"(lo)); return r;
}
__device__ __forceinline__ float bf_lo(uint32_t v) { return __uint_as_float(v << 16); }
__device__ __forceinline__ float bf_hi(uint32_t v) { return __uint_as_float(v & 0xFFFF0000u); }

__device__ __forceinline__ uint4 ld_relaxed4(const void* p) {
  uint4 v; asm volatile("ld.relaxed.gpu.global.v4.u32 {%0,%1,%2,%3}, [%4];" : "=r"(v.x), "=r"(v.y), "=r"(v.z), "=r"(v.w) : "l"(p) : "memory"); return v;
}
__device__ __forceinline__ void st_b128(void* p, uint32_t a, uint32_t b, uint32_t c, uint32_t d) {
  asm volatile("{.reg .b128 v; mov.b128 v, {%1,%2,%3,%4}; st.relaxed.gpu.global.b128 [%0], v;}" :: "l"(p), "r"(a), "r"(b), "r"(c), "r"(d) : "memory");
}
__device__ __forceinline__ void reload_b128(uint4& v, const void* p, uint32_t again) {
  asm volatile("{.reg .pred p; .reg .b128 v; setp.ne.u32 p, %5, 0; mov.b128 v, {%0,%1,%2,%3};\n"
               "@p ld.relaxed.gpu.global.b128 v, [%4]; mov.b128 {%0,%1,%2,%3}, v;}"
    : "+r"(v.x), "+r"(v.y), "+r"(v.z), "+r"(v.w) : "l"(p), "r"(again) : "memory");
}
__device__ __forceinline__ void reload4(uint4& v, const void* p, uint32_t again) {
  asm volatile("{.reg .pred p; setp.ne.u32 p, %5, 0; @p ld.relaxed.gpu.global.v4.u32 {%0,%1,%2,%3}, [%4];}"
    : "+r"(v.x), "+r"(v.y), "+r"(v.z), "+r"(v.w) : "l"(p), "r"(again) : "memory");
}
__device__ __forceinline__ void st_relaxed4(void* p, uint32_t a, uint32_t b, uint32_t c, uint32_t d) {
  asm volatile("st.relaxed.gpu.global.v4.u32 [%0], {%1,%2,%3,%4};" :: "l"(p), "r"(a), "r"(b), "r"(c), "r"(d) : "memory");
}
__device__ __forceinline__ void st_relaxed_if(void* p, uint32_t a, bool on) {
  asm volatile("{.reg .pred p; setp.ne.u32 p, %2, 0; @p st.relaxed.gpu.global.u32 [%0], %1;}" :: "l"(p), "r"(a), "r"((uint32_t)on) : "memory");
}
__device__ __forceinline__ uint32_t ld_acquire(const uint32_t* p) {
  uint32_t v; asm volatile("ld.acquire.gpu.global.u32 %0, [%1];" : "=r"(v) : "l"(p) : "memory"); return v;
}
__device__ __forceinline__ void st_release(uint32_t* p, uint32_t v) {
  asm volatile("st.release.gpu.global.u32 [%0], %1;" :: "l"(p), "r"(v) : "memory");
}
__device__ __forceinline__ void bulk_reduce(float* dst, uint32_t src, uint32_t bytes) {
  asm volatile("cp.reduce.async.bulk.global.shared::cta.bulk_group.add.f32 [%0], [%1], %2;" :: "l"(dst), "r"(src), "r"(bytes) : "memory");
}
__device__ __forceinline__ void bulk_done_inc(uint32_t* p) {
  asm volatile("cp.async.bulk.wait_group 0;\n"
               "fence.proxy.async.global;\nfence.release.gpu;\n"
               "red.relaxed.gpu.global.add.u32 [%0], 1;\nred.relaxed.gpu.global.add.u32 [%0+4096], 1;" :: "l"(p) : "memory");
}
__device__ __forceinline__ void flag_release(uint32_t* p, uint32_t v) {
  asm volatile("fence.release.gpu;\nst.relaxed.gpu.global.u32 [%0], %1;\nst.relaxed.gpu.global.u32 [%0+4096], %1;" :: "l"(p), "r"(v) : "memory");
}
__device__ __forceinline__ void spin_guard(int& it) {
  asm volatile("{.reg .pred p; add.s32 %0, %0, 1; setp.gt.s32 p, %0, %1; @p trap;}" : "+r"(it) : "n"(SPIN_MAX));
}
__device__ __forceinline__ void wait_flag(const uint32_t* p, uint32_t v) {
  int it = 0;
  while (ld_acquire(p) < v) spin_guard(it);
}
__device__ __forceinline__ void wait_flags(const uint32_t* p, uint32_t v) {
  int it = 0;
  while (true) {
    uint32_t x; asm volatile("ld.relaxed.gpu.global.u32 %0, [%1];" : "=r"(x) : "l"(p) : "memory");
    if (__all_sync(~0u, x >= v)) break;
    spin_guard(it);
  }
  asm volatile("fence.acquire.gpu;" ::: "memory");
}
__device__ __forceinline__ uint32_t timer_offset() {
  uint32_t g0, g;
  asm volatile("mov.u32 %0, %%globaltimer_lo;" : "=r"(g0) :: "memory");
  do { asm volatile("mov.u32 %0, %%globaltimer_lo;" : "=r"(g) :: "memory"); } while (g == g0);
  return (g >> 5) * 58 - clk();
}
__device__ __forceinline__ void grid_arrive(int i) {
  asm volatile("red.release.gpu.global.add.u32 [%0], %1;" :: "l"(g_gbar + i * 32), "r"(bid() ? 1u : 257u - N_CTA) : "memory");
}
__device__ __forceinline__ void grid_wait(int i, uint32_t gen) {
  int it = 0;
  while (((ld_acquire(g_gbar + i * 32) ^ gen) >> 8) == 0) spin_guard(it);
}
__device__ __forceinline__ bool elect() {
  uint32_t r; asm volatile("{.reg .pred p; elect.sync _|p, -1; selp.u32 %0, 1, 0, p;}" : "=r"(r)); return r;
}
__device__ __forceinline__ void bar_sync(int id, int cnt) { asm volatile("bar.sync %0, %1;" :: "r"(id), "r"(cnt) : "memory"); }
__device__ __forceinline__ void bar_arrive(int id, int cnt) { asm volatile("bar.arrive %0, %1;" :: "r"(id), "r"(cnt) : "memory"); }
template <int id, int cnt> __device__ __forceinline__ void bar_arrive_after(uint32_t a, uint32_t b) {
  asm volatile("{.reg .pred p; setp.ne.u32 p, %2, 0xfff12345; setp.ne.and.u32 p, %3, 0xfff12345, p; @p bar.arrive %0, %1;}" :: "n"(id), "n"(cnt), "r"(a), "r"(b) : "memory");
}
template <int id, int cnt> __device__ __forceinline__ void bar_sync_after(uint32_t a) {
  asm volatile("{.reg .pred p; setp.ne.u32 p, %2, 0xfff12345; @p bar.sync %0, %1;}" :: "n"(id), "n"(cnt), "r"(a) : "memory");
}
__device__ __forceinline__ void fence_async_smem() { asm volatile("fence.proxy.async.shared::cta;" ::: "memory"); }
__device__ __forceinline__ void fence_async_global() { asm volatile("fence.proxy.async.global;" ::: "memory"); }
__device__ __forceinline__ void mbar_init(uint32_t mb, int cnt) { asm volatile("mbarrier.init.shared::cta.b64 [%0], %1;" :: "r"(mb), "r"(cnt) : "memory"); }
__device__ __forceinline__ void mbar_arrive(uint32_t mb) { asm volatile("mbarrier.arrive.shared::cta.b64 _, [%0];" :: "r"(mb) : "memory"); }
__device__ __forceinline__ void mbar_arrive_after(uint32_t mb, uint32_t a, uint32_t lane) {
  asm volatile("{.reg .pred p; setp.ne.u32 p, %1, 0xfff12345; setp.eq.and.u32 p, %2, 0, p; @p mbarrier.arrive.shared::cta.b64 _, [%0];}" :: "r"(mb), "r"(a), "r"(lane) : "memory");
}
__device__ __forceinline__ void mbar_expect(uint32_t mb, uint32_t bytes) {
  asm volatile("mbarrier.arrive.expect_tx.shared::cta.b64 _, [%0], %1;" :: "r"(mb), "r"(bytes) : "memory");
}
__device__ __forceinline__ void mbar_wait_guard(uint32_t mb, uint32_t parity) {
  uint32_t ok; int it = 0;
  while (true) {
    asm volatile("{.reg .pred p; mbarrier.try_wait.parity.shared::cta.b64 p, [%1], %2; selp.u32 %0, 1, 0, p;}" : "=r"(ok) : "r"(mb), "r"(parity) : "memory");
    if (ok) break;
    spin_guard(it);
  }
}
__device__ __forceinline__ void mbar_wait(uint32_t mb, uint32_t parity) {
  asm volatile("{.reg .pred p;\nW: mbarrier.try_wait.parity.shared::cta.b64 p, [%0], %1;\n@!p bra W;}" :: "r"(mb), "r"(parity) : "memory");
}
__device__ __forceinline__ void bulk_load(uint32_t dst, const void* src, uint32_t bytes, uint32_t mb) {
  asm volatile("cp.async.bulk.shared::cluster.global.mbarrier::complete_tx::bytes [%0], [%1], %2, [%3];" :: "r"(dst), "l"(src), "r"(bytes), "r"(mb) : "memory");
}
__device__ __forceinline__ void bulk_store(void* dst, uint32_t src, uint32_t bytes) {
  asm volatile("cp.async.bulk.global.shared::cta.bulk_group [%0], [%1], %2;" :: "l"(dst), "r"(src), "r"(bytes) : "memory");
}
__device__ __forceinline__ void cp_async16(uint32_t dst, const void* src) {
  asm volatile("cp.async.cg.shared.global [%0], [%1], 16;" :: "r"(dst), "l"(src) : "memory");
}
__device__ __forceinline__ void cp_async_wait_all() { asm volatile("cp.async.wait_all;" ::: "memory"); }
__device__ __forceinline__ uint32_t mapa(uint32_t a, uint32_t rank) {
  uint32_t r; asm("mapa.shared::cluster.u32 %0, %1, %2;" : "=r"(r) : "r"(a), "r"(rank)); return r;
}
__device__ __forceinline__ void st_async4(uint32_t dst, float a, float b, float c, float d, uint32_t mb) {
  asm volatile("st.async.shared::cluster.mbarrier::complete_tx::bytes.v4.f32 [%0], {%1,%2,%3,%4}, [%5];" :: "r"(dst), "f"(a), "f"(b), "f"(c), "f"(d), "r"(mb) : "memory");
}
__device__ __forceinline__ void st_async2(uint32_t dst, float a, float b, uint32_t mb) {
  asm volatile("st.async.shared::cluster.mbarrier::complete_tx::bytes.v2.f32 [%0], {%1,%2}, [%3];" :: "r"(dst), "f"(a), "f"(b), "r"(mb) : "memory");
}
__device__ __forceinline__ void st_async1(uint32_t dst, uint32_t a, uint32_t mb) {
  asm volatile("st.async.shared::cluster.mbarrier::complete_tx::bytes.u32 [%0], %1, [%2];" :: "r"(dst), "r"(a), "r"(mb) : "memory");
}
__device__ __forceinline__ uint4 lds128(uint32_t a) {
  uint4 v; asm volatile("ld.shared.v4.u32 {%0,%1,%2,%3}, [%4];" : "=r"(v.x), "=r"(v.y), "=r"(v.z), "=r"(v.w) : "r"(a) : "memory"); return v;
}
__device__ __forceinline__ uint2 lds64(uint32_t a) {
  uint2 v; asm volatile("ld.shared.v2.u32 {%0,%1}, [%2];" : "=r"(v.x), "=r"(v.y) : "r"(a) : "memory"); return v;
}
__device__ __forceinline__ uint32_t lds32(uint32_t a) {
  uint32_t v; asm volatile("ld.shared.u32 %0, [%1];" : "=r"(v) : "r"(a) : "memory"); return v;
}
__device__ __forceinline__ void sts128(uint32_t a, uint4 v) {
  asm volatile("st.shared.v4.u32 [%0], {%1,%2,%3,%4};" :: "r"(a), "r"(v.x), "r"(v.y), "r"(v.z), "r"(v.w) : "memory");
}
__device__ __forceinline__ void sts64(uint32_t a, uint32_t x, uint32_t y) {
  asm volatile("st.shared.v2.u32 [%0], {%1,%2};" :: "r"(a), "r"(x), "r"(y) : "memory");
}
__device__ __forceinline__ void sts32(uint32_t a, uint32_t x) { asm volatile("st.shared.u32 [%0], %1;" :: "r"(a), "r"(x) : "memory"); }
__device__ __forceinline__ void ldsm4(uint32_t& r0, uint32_t& r1, uint32_t& r2, uint32_t& r3, uint32_t a) {
  asm volatile("ldmatrix.sync.aligned.m8n8.x4.shared.b16 {%0,%1,%2,%3}, [%4];" : "=r"(r0), "=r"(r1), "=r"(r2), "=r"(r3) : "r"(a) : "memory");
}
__device__ __forceinline__ void ldsm4t(uint32_t& r0, uint32_t& r1, uint32_t& r2, uint32_t& r3, uint32_t a) {
  asm volatile("ldmatrix.sync.aligned.m8n8.x4.trans.shared.b16 {%0,%1,%2,%3}, [%4];" : "=r"(r0), "=r"(r1), "=r"(r2), "=r"(r3) : "r"(a) : "memory");
}
__device__ __forceinline__ void stsm4(uint32_t a, uint32_t r0, uint32_t r1, uint32_t r2, uint32_t r3) {
  asm volatile("stmatrix.sync.aligned.m8n8.x4.shared.b16 [%0], {%1,%2,%3,%4};" :: "r"(a), "r"(r0), "r"(r1), "r"(r2), "r"(r3) : "memory");
}
__device__ __forceinline__ uint32_t movmat(uint32_t a) {
  uint32_t d; asm volatile("movmatrix.sync.aligned.m8n8.trans.b16 %0, %1;" : "=r"(d) : "r"(a)); return d;
}
__device__ __forceinline__ void mma16(float* d, uint32_t a0, uint32_t a1, uint32_t a2, uint32_t a3, uint32_t b0, uint32_t b1) {
  asm volatile("mma.sync.aligned.m16n8k16.row.col.f32.bf16.bf16.f32 {%0,%1,%2,%3}, {%4,%5,%6,%7}, {%8,%9}, {%0,%1,%2,%3};"
    : "+f"(d[0]), "+f"(d[1]), "+f"(d[2]), "+f"(d[3]) : "r"(a0), "r"(a1), "r"(a2), "r"(a3), "r"(b0), "r"(b1));
}
__device__ __forceinline__ void mma8(float* d, uint32_t a0, uint32_t a1, uint32_t b0) {
  asm volatile("mma.sync.aligned.m16n8k8.row.col.f32.bf16.bf16.f32 {%0,%1,%2,%3}, {%4,%5}, {%6}, {%0,%1,%2,%3};"
    : "+f"(d[0]), "+f"(d[1]), "+f"(d[2]), "+f"(d[3]) : "r"(a0), "r"(a1), "r"(b0));
}
__device__ __forceinline__ float rcp(float x) { float r; asm("rcp.approx.ftz.f32 %0, %1;" : "=f"(r) : "f"(x)); return r; }
__device__ __forceinline__ float ex2(float x) { float r; asm("ex2.approx.ftz.f32 %0, %1;" : "=f"(r) : "f"(x)); return r; }

__host__ __device__ constexpr uint64_t mkdesc(uint32_t off, uint32_t lbo, uint32_t sbo, uint32_t swz) {
  return (uint64_t)((SBASE + off) >> 4) | ((uint64_t)(lbo >> 4) << 16) | ((uint64_t)(sbo >> 4) << 32) | ((uint64_t)swz << 62);
}
__host__ __device__ constexpr uint64_t desc_sw128(uint32_t off) { return mkdesc(off, 16, 1024, 1); }
__host__ __device__ constexpr uint64_t desc_n16(uint32_t off) { return mkdesc(off, 256, 128, 0); }
__host__ __device__ constexpr uint64_t desc_m(uint32_t off) { return mkdesc(off, 16, 256, 3); }

__host__ __device__ constexpr uint64_t desc_sw64(uint32_t off) { return mkdesc(off, 16, 512, 2); }

__device__ __forceinline__ void wg_fence() { asm volatile("wgmma.fence.sync.aligned;" ::: "memory"); }
__device__ __forceinline__ void wg_commit() { asm volatile("wgmma.commit_group.sync.aligned;" ::: "memory"); }
template <int N> __device__ __forceinline__ void wg_wait() { asm volatile("wgmma.wait_group.sync.aligned %0;" :: "n"(N) : "memory"); }

#define ACC8(d) "+f"(d[0]), "+f"(d[1]), "+f"(d[2]), "+f"(d[3]), "+f"(d[4]), "+f"(d[5]), "+f"(d[6]), "+f"(d[7])
#define ACC32(d) ACC8(d), ACC8((d + 8)), ACC8((d + 16)), ACC8((d + 24))
#define R8 "{%0,%1,%2,%3,%4,%5,%6,%7}"
#define R32 "{%0,%1,%2,%3,%4,%5,%6,%7,%8,%9,%10,%11,%12,%13,%14,%15,%16,%17,%18,%19,%20,%21,%22,%23,%24,%25,%26,%27,%28,%29,%30,%31}"
template <int SD> __device__ __forceinline__ void wg_rs16(float* d, const uint32_t* a, uint64_t db) {
  asm volatile("wgmma.mma_async.sync.aligned.m64n16k16.f32.bf16.bf16 " R8 ", {%8,%9,%10,%11}, %12, %13, 1, 1, 1;"
    : ACC8(d) : "r"(a[0]), "r"(a[1]), "r"(a[2]), "r"(a[3]), "l"(db), "n"(SD));
}
template <int SD> __device__ __forceinline__ void wg_ss16(float* d, uint64_t da, uint64_t db) {
  asm volatile("wgmma.mma_async.sync.aligned.m64n16k16.f32.bf16.bf16 " R8 ", %8, %9, %10, 1, 1, 1, 1;"
    : ACC8(d) : "l"(da), "l"(db), "n"(SD));
}
template <int SD, uint64_t DA, uint64_t DB> __device__ __forceinline__ void wg_ss16o(float* d, uint32_t oa, uint32_t ob) {
  asm volatile("{.reg .b32 x, y; .reg .b64 a, b; add.u32 x, %8, %10; add.u32 y, %9, %12; mov.b64 a, {x, %11}; mov.b64 b, {y, %13};\n"
               "wgmma.mma_async.sync.aligned.m64n16k16.f32.bf16.bf16 " R8 ", a, b, %14, 1, 1, 1, 1;}"
    : ACC8(d) : "r"(oa), "r"(ob), "n"((uint32_t)DA), "n"((uint32_t)(DA >> 32)), "n"((uint32_t)DB), "n"((uint32_t)(DB >> 32)), "n"(SD));
}
template <int SD> __device__ __forceinline__ void wg_rs64(float* d, const uint32_t* a, uint64_t db) {
  asm volatile("wgmma.mma_async.sync.aligned.m64n64k16.f32.bf16.bf16 " R32 ", {%32,%33,%34,%35}, %36, %37, 1, 1, 0;"
    : ACC32(d) : "r"(a[0]), "r"(a[1]), "r"(a[2]), "r"(a[3]), "l"(db), "n"(SD));
}
template <int SD> __device__ __forceinline__ void wg_ss64(float* d, uint64_t da, uint64_t db) {
  asm volatile("wgmma.mma_async.sync.aligned.m64n64k16.f32.bf16.bf16 " R32 ", %32, %33, %34, 1, 1, 1, 0;"
    : ACC32(d) : "l"(da), "l"(db), "n"(SD));
}
#define WG_RSO(NAME, SHAPE, REGS, ACC, A, TB) \
template <int SD, uint64_t DB> __device__ __forceinline__ void NAME(float* d, uint32_t a0, uint32_t a1, uint32_t a2, uint32_t a3, uint32_t ob) { \
  asm volatile("{.reg .b64 b; mov.b64 b, {" A(4) ", " A(5) "};\nwgmma.mma_async.sync.aligned." SHAPE ".f32.bf16.bf16 " REGS \
               ", {" A(0) "," A(1) "," A(2) "," A(3) "}, b, " A(6) ", 1, 1, " TB ";}" \
    : ACC(d) : "r"(a0), "r"(a1), "r"(a2), "r"(a3), "r"(ob + (uint32_t)DB), "n"((uint32_t)(DB >> 32)), "n"(SD)); \
}
#define ACC4(d) "+f"(d[0]), "+f"(d[1]), "+f"(d[2]), "+f"(d[3])
#define ACC16(d) ACC8(d), ACC8((d + 8))
#define OP4(i) OP4_##i
#define OP4_0 "%4"
#define OP4_1 "%5"
#define OP4_2 "%6"
#define OP4_3 "%7"
#define OP4_4 "%8"
#define OP4_5 "%9"
#define OP4_6 "%10"
#define OP16(i) OP16_##i
#define OP16_0 "%16"
#define OP16_1 "%17"
#define OP16_2 "%18"
#define OP16_3 "%19"
#define OP16_4 "%20"
#define OP16_5 "%21"
#define OP16_6 "%22"
#define OP32(i) OP32_##i
#define OP32_0 "%32"
#define OP32_1 "%33"
#define OP32_2 "%34"
#define OP32_3 "%35"
#define OP32_4 "%36"
#define OP32_5 "%37"
#define OP32_6 "%38"
WG_RSO(wg_rs8o, "m64n8k16", "{%0,%1,%2,%3}", ACC4, OP4, "1")
#define R16 "{%0,%1,%2,%3,%4,%5,%6,%7,%8,%9,%10,%11,%12,%13,%14,%15}"
WG_RSO(wg_rs32o, "m64n32k16", R16, ACC16, OP16, "1")
WG_RSO(wg_rs64o, "m64n64k16", R32, ACC32, OP32, "0")
WG_RSO(wg_rs32k, "m64n32k16", R16, ACC16, OP16, "0")
template <uint64_t DA, uint64_t DB> __device__ __forceinline__ void wg_ss32k(float* d, uint32_t ob) {
  asm volatile("{.reg .b64 b; mov.b64 b, {%17, %18};\nwgmma.mma_async.sync.aligned.m64n32k16.f32.bf16.bf16 " R16 ", %16, b, 1, 1, 1, 1, 0;}"
    : ACC16(d) : "l"(DA), "r"(ob + (uint32_t)DB), "n"((uint32_t)(DB >> 32)));
}
template <int N> __device__ __forceinline__ void reg_inc() { asm volatile("setmaxnreg.inc.sync.aligned.u32 %0;" :: "n"(N)); }
template <int N> __device__ __forceinline__ void reg_dec() { asm volatile("setmaxnreg.dec.sync.aligned.u32 %0;" :: "n"(N)); }
__device__ __forceinline__ void cluster_sync() {
  asm volatile("barrier.cluster.arrive.relaxed.aligned;\nbarrier.cluster.wait.aligned;" ::: "memory");
}

template <int KS>
__device__ __forceinline__ void load_frags(uint32_t* a, uint32_t src) {
  const int lane = threadIdx.x & 31, w = (threadIdx.x >> 5) & 3;
  const int k = ((lane >> 4) << 3) + (lane & 7), u = w * 2 + ((lane >> 3) & 1);
  const uint32_t base = src + k * 128 + ((u ^ (k & 7)) << 4);
#pragma unroll
  for (int ks = 0; ks < KS; ks++) ldsm4t(a[ks * 4], a[ks * 4 + 1], a[ks * 4 + 2], a[ks * 4 + 3], base + ks * 2048);
}

__device__ __forceinline__ uint32_t badd2(uint32_t a, uint32_t b) { uint32_t r; asm("add.rn.bf16x2 %0, %1, %2;" : "=r"(r) : "r"(a), "r"(b)); return r; }
__device__ __forceinline__ uint32_t bsub2(uint32_t a, uint32_t b) { uint32_t r; asm("sub.rn.bf16x2 %0, %1, %2;" : "=r"(r) : "r"(a), "r"(b)); return r; }
__device__ __forceinline__ uint32_t bmul2(uint32_t a, uint32_t b) { uint32_t r; asm("mul.rn.bf16x2 %0, %1, %2;" : "=r"(r) : "r"(a), "r"(b)); return r; }
__device__ __forceinline__ uint32_t bfma2(uint32_t a, uint32_t b, uint32_t c) { uint32_t r; asm("fma.rn.bf16x2 %0, %1, %2, %3;" : "=r"(r) : "r"(a), "r"(b), "r"(c)); return r; }
template <int R> __device__ __forceinline__ void layernorm9(const uint32_t* x, uint32_t* o) {
  const uint32_t ones = 0x3F803F80u;
  float a[R][3][4], q[R], s[R];
#pragma unroll
  for (int i = 0; i < 9 * R; i++) {
    float* d = a[i % R][i / R % 3];
    if (i < 3 * R) d[0] = d[1] = d[2] = d[3] = 0.f;
    mma8(d, x[i % R * 9 + i / R], ones, x[i % R * 9 + i / R]);
  }
#pragma unroll
  for (int r = 0; r < R; r++) {
    q[r] = threadIdx.x & 4 ? a[r][0][1] + a[r][1][1] + a[r][2][1] : a[r][0][0] + a[r][1][0] + a[r][2][0];
    s[r] = (a[r][0][2] + a[r][0][3]) + (a[r][1][2] + a[r][1][3]) + (a[r][2][2] + a[r][2][3]);
  }
#pragma unroll
  for (int r = 0; r < R; r++) { q[r] += __shfl_xor_sync(~0u, q[r], 4); s[r] += __shfl_xor_sync(~0u, s[r], 1); }
#pragma unroll
  for (int r = 0; r < R; r++) { q[r] += __shfl_xor_sync(~0u, q[r], 9); s[r] += __shfl_xor_sync(~0u, s[r], 2); }
#pragma unroll
  for (int r = 0; r < R; r++) q[r] = __shfl_sync(~0u, q[r], 0) + __shfl_sync(~0u, q[r], 18);
#pragma unroll
  for (int r = 0; r < R; r++) {
    const float mean = s[r] * (1.f / DM), var = fmaxf(fmaf(q[r], 1.f / DM, -mean * mean), 0.f);
    float sd;
    asm("sqrt.approx.ftz.f32 %0, %1;" : "=f"(sd) : "f"(bf_lo(pack2(bf_lo(pack2(var, 0.f)) + 1e-5f, 0.f))));
    const float inv = rcp(bf_lo(pack2(sd, 0.f)));
    const uint32_t mb = pack2(mean, mean), hi = pack2(inv, inv), lo = pack2(inv - bf_lo(hi), inv - bf_lo(hi));
#pragma unroll
    for (int i = r * 9; i < r * 9 + 9; i++) {
      const uint32_t d = bsub2(x[i], mb);
      o[i] = bfma2(d, hi, bmul2(d, lo));
    }
  }
}
__device__ __forceinline__ void store_ln_row(int layer, int tok, const uint32_t* o) {
  const int lane = threadIdx.x & 31, r = tok & 31;
  unsigned char* p = g_lnimg + (size_t)(layer * NSEG + (tok >> 5)) * (9 * 4096) + r * 128 + (((lane >> 2) ^ (r & 7)) << 4) + (lane & 3) * 4;
#pragma unroll
  for (int i = 0; i < 9; i++) *(uint32_t*)(p + i * 4096) = o[i];
}
struct Params { CUtensorMap map[11]; const bf16 *X, *K, *V, *shift, *Hk, *Dk, *mem0, *Wq, *Wk, *Wv, *Wo; bf16* out; uint32_t dly[24]; };
#define PACE P.dly[20]
#define S1G P.dly[21]
#define S1DLY P.dly[22]
#define DLYS P.dly[0]
#define DLYW P.dly[1]
#define KLATE P.dly[2]
#define DLYQ P.dly[3]
#define DLYK P.dly[4]
#define DLYG P.dly[5]
#define KWIN P.dly[6]
#define KMIN P.dly[7]
uint32_t h_dly[24] = {900, 150, 100, 40, 3650, 4900, 1750, 300, 1740, 1840, 1900, 2230, 2340, 2430, 3080, 3170, 3380, 3460, 3580, 6000, 165, 12000, 18000};

constexpr uint32_t C_W = 0, C_M = 147456, C_KV = C_M + 18432, C_QM = C_KV + 32768, C_KM = C_QM + 2048,
                   C_VM = C_KM + 2048, C_OI = C_VM + 2048, C_SX = C_OI + 4096, C_KM2 = C_SX + 2560, C_VM2 = C_KM2 + 128,
                   C_KV2 = C_KM2 + 2048, C_Q = C_KV2 + 8192, C_BAR = C_Q + 8192;
constexpr uint32_t CB_FULL = C_BAR, CB_REF = C_BAR + 16, CB_SX = C_BAR + 32, CB_OX = C_BAR + 40, CB_XX = C_BAR + 48, CB_Q = C_BAR + 56, C_BAD = C_BAR + 64, W_BAR = C_BAR + 80, T_BAR = W_BAR + 24, S_GEN = C_BAR + 128, C_REF = C_BAR + 132, CB_VF = C_BAR + 144, CB_M = C_BAR + 160, CB_MV = C_BAR + 200;
constexpr uint32_t G_W = 0, G_RING = 147456, G_W2 = G_RING + 9 * 8192, G_BAR = G_W2 + 8192;
constexpr uint32_t O_W = 0, O_RING = 3 * 40960, O_ST = O_RING + 11 * 8192, O_BAR = O_ST + 16384, OB_ST = O_BAR + 64;
constexpr uint32_t F_A = 0, F_XY = 36864, F_L = F_XY + 36864, F_X = F_L + 18432, F_Y = F_L + 2 * 36864, F_BAR = C_BAR;
constexpr uint32_t SMEM_BYTES = C_BAR + 256;
static_assert(G_BAR + 256 <= SMEM_BYTES && O_BAR + 256 <= SMEM_BYTES && F_BAR + 16 <= SMEM_BYTES && SMEM_BYTES <= 232448, "smem map");
enum { B_INIT = 1, B_M, B_QK, B_S, B_V, B_O, B_X, B_WG0, B_WG1, B_WG2, B_G, B_OE, B_T, B_R };

__device__ __forceinline__ uint4 pack_partial(const float* d, uint32_t tag) {
  uint32_t x;
  asm("lop3.b32 %0, %1, 1, %2, 0xb8;" : "=r"(x) : "r"(pack2(d[0], d[1])), "r"(tag));
  return make_uint4(x, pack2(d[4], d[5]), pack2(d[2], d[3]), pack2(d[6], d[7]));
}
__device__ __forceinline__ void store_partial(uint4* p, const uint4& v) { st_b128(p, v.x, v.y, v.z, v.w); }
__device__ __forceinline__ void gather_reduce(const uint32_t* p, uint32_t* dst, uint32_t m0, bool shared, uint32_t tag, uint32_t lane, uint32_t sb, int n, int TS0) {
  int tries = 0;
  float u, v;
  bool bad;
  TR(TS0);
  do {
    uint32_t x[16];
#pragma unroll
    for (int i = 0; i < 16; i++) asm volatile("ld.relaxed.gpu.global.u32 %0, [%1];" : "=r"(x[i]) : "l"(p + i * 64) : "memory");
    tries++;
    float a[2] = {bf_lo(x[0]), bf_lo(x[1])}, b[2] = {bf_hi(x[0]), bf_hi(x[1])};
    uint32_t t = 0;
#pragma unroll
    for (int i = 2; i < 16; i++) { a[i & 1] += bf_lo(x[i]); b[i & 1] += bf_hi(x[i]); }
#pragma unroll
    for (int i = 0; i < 16; i += 4)
      asm("{.reg .b32 y, z; lop3.b32 y, %1, %2, %5, 0x7e; lop3.b32 z, %3, %4, %5, 0x7e; lop3.b32 %0, %0, y, z, 0xfe;}"
          : "+r"(t) : "r"(x[i]), "r"(x[i + 1]), "r"(x[i + 2]), "r"(x[i + 3]), "r"(tag));
    u = a[0] + a[1]; v = b[0] + b[1];
    bad = __any_sync(~0u, (t & 1) && !(lane & 3));
    if (shared) { u += __shfl_xor_sync(~0u, u, 8); v += __shfl_xor_sync(~0u, v, 8); }
    u += __shfl_xor_sync(~0u, u, 16);
    v += __shfl_xor_sync(~0u, v, 16);
    st_relaxed_if(dst, n < LAG && (lane & 1) ? m0 : pack2(u, v), !bad);
  } while (bad);
  TR(TS0 + 3); TRV(TS0 + 2, tries);
  CNT((TS0 - 16) >> 2, tries);
}
__device__ __forceinline__ uint32_t sent_bad(const uint4& v) { return max(max(v.x, v.y), max(v.z, v.w)) == SENT; }

__host__ __device__ constexpr int o_ks(int s) { return s & (s < 8 ? 3 : 7); }
__host__ __device__ constexpr bool o_reg(int s) { return s < 8 ? (s & 3) != 3 : !(s & 1); }
__host__ __device__ constexpr int o_slot(int s) { return s < 8 ? (o_reg(s) ? s - (s >> 2) : s >> 2) : s & 1 ? (s - 5) >> 1 : (s + 4) >> 1; }
__device__ __forceinline__ int g_unit(int wg) {
  const int i = bid() - N_CHAIN;
  return i < 32 ? wg * 64 + i : 2 * i - 32 + wg;
}
__device__ __forceinline__ uint32_t pinned(uint32_t v) { return __shfl_sync(~0u, v, threadIdx.x & 31); }
template <class T> __device__ __forceinline__ T* pinned(T* p) { return (T*)__shfl_sync(~0u, (unsigned long long)p, threadIdx.x & 31); }
enum { CHAIN, GROLE, OROLE };
template <int ROLE, bool SYNC> __device__ __forceinline__ void load_box(const Params& P, uint32_t sb, bool regs, int wg, int i, uint32_t mb, bool on) {
  const int b = bid();
  int map, col = 0, ks = 0, c2 = 0, c3 = 0;
  uint32_t dst = wg * 73728;
  if (ROLE == CHAIN) {
    const int k = i - 1, st = regs ? (k < 6 ? k + k / 3 : 2 * k - 4) : k < 2 ? 4 * k + 3 : 2 * k + 5;
    dst += i ? (17 + i) * 2048 : 0;
    if (wg || i == 0) { map = wg + i; col = b * 64; c3 = !regs; }
    else if (!regs && k >= 14) { map = 6; ks = b * 4 + k - 14; }
    else { map = 6; col = 64 + (st < 8 ? (st >> 2) * 64 : (st >> 3) * 128 + (b & 1) * 64); ks = (b * 4) ^ o_ks(st); }
  } else if (ROLE == GROLE) {
    const int q = g_unit(wg);
    map = ((q >> 5) + 1) % 3;
    if (i) { map += 3; col = (q & 31) * 128 + (i - 1) * 64; ks = 34; dst = G_W2 + wg * 4096 + (i - 1) * 2048; }
    else { map += 8; c2 = (q & 31) * 2; c3 = !regs; }
  } else {
    const int o = b - N_CHAIN - N_G, ksl = o / 3;
    map = 7; col = ((o % 3) * 3 + (wg + ksl) % 3) * 64; dst = (wg * (regs ? 24 : 20) + i) * 2048;
    ks = (ksl * 11 - max(ksl - 4, 0)) * 4 + (regs ? i / 3 * 5 + i % 3 * 2 : i < 16 ? i / 2 * 5 + 1 + i % 2 * 2 : i + 24);
    c3 = (ks & 1) * 2; ks >>= 1;
  }
  if (SYNC) { col = pinned(col); ks = pinned(ks); bar_sync(B_WG0 + wg, 256); }
  if (on) asm volatile("cp.async.bulk.tensor.5d.shared::cluster.global.tile.mbarrier::complete_tx::bytes [%0], [%1, {%2, %3, %4, %5, %6}], [%7];"
               :: "r"(sb + dst), "l"(&P.map[map]), "r"(col), "r"(0), "r"(c2), "r"(c3), "r"(ks), "r"(mb) : "memory");
}
template <int ROLE, bool SYNC = false> __device__ __forceinline__ void load_wg(const Params& P, uint32_t sb, bool regs, int wg, int quarter) {
  const int i = (threadIdx.x & 31) * 4 + quarter;
  const int n = ROLE == CHAIN ? 36 : ROLE == GROLE ? (regs ? 38 : 36) : regs ? 24 : bid() < N_CHAIN + N_G + 12 ? 20 : 16;
  load_box<ROLE, SYNC>(P, sb, regs, wg, i, sb + W_BAR + wg * 8, i < (ROLE == CHAIN ? (wg ? 2 : 19) : ROLE == GROLE ? n - 35 : n));
  if (i == 0) mbar_expect(sb + W_BAR + wg * 8, n * 2048);
  __syncwarp();
}
__device__ __forceinline__ uint32_t near_half(uint32_t blk, uint32_t reader) {
  return __ldcg(g_near + (blk >> 3)) ^ (~blk & 1) ^ __ldcg(g_side + (blk >> 3)) ^ __ldcg(g_side + reader);
}

__device__ __forceinline__ uint32_t opaque_tid() { uint32_t t; asm volatile("mov.u32 %0, %%tid.x;" : "=r"(t)); return t; }
__device__ __forceinline__ void m_fetch(uint32_t sb, uint32_t src, uint32_t b, uint32_t mb) {
  bulk_load(sb + C_M + (b ? b * 4096 - 2048 : 0), (const unsigned char*)g_mimg + ((src ^ ((b & 1) * 4096)) + b * 8192), b ? 4096 : 2048, mb);
}
__device__ __forceinline__ uint32_t m_probe(uint32_t lane) { return lane * 32 + (lane & 4) * 4 + (lane >> 3) * 4; }
__device__ __forceinline__ uint32_t m_max(uint32_t a, uint32_t b) {
  return max(max(lds32(a), lds32(a + 1024)), max(lds32(b), lds32(b + 1024)));
}
template <int S0, int N> __device__ __forceinline__ void o_steps(float* d, const uint32_t* a) {
  constexpr int SD = o_ks(S0) != 0;
  if constexpr (o_reg(S0)) wg_rs16<SD>(d, a + (18 + o_slot(S0)) * 4, desc_n16(C_OI + o_ks(S0) * 512));
  else wg_ss16<SD>(d, desc_sw128(C_W + (18 + o_slot(S0)) * 2048), desc_n16(C_OI + o_ks(S0) * 512));
  if constexpr (N > 1) o_steps<S0 + 1, N - 1>(d, a);
}
template <int BASE, int KS, int N> __device__ __forceinline__ void m_steps(float* d, const uint32_t* a, uint32_t oa) {
  wg_rs16<KS != 0>(d, a + (BASE + KS / 2) * 4, desc_m(C_M + KS * 512));
  wg_ss16o<1, desc_sw128(C_W + (BASE + KS / 2) * 2048), desc_m(C_M + KS * 512 + 512)>(d, oa, 0);
  if constexpr (N > 2) m_steps<BASE, KS + 2, N - 2>(d, a, oa);
}

__device__ __forceinline__ void chain_proj(const Params& P, uint32_t sb) {
  const uint32_t c = chain_id(), h = c >> 1, j = c & 1, wid = __shfl_sync(~0u, threadIdx.x >> 5, 0), wg = wid >> 2, w = wid & 3;
  const uint32_t t = threadIdx.x & 127, lane = pinned(t & 31), mine = pinned(sb + t * 16), rb = mapa(sb, j ^ 1);
  const uint32_t theirs = pinned(rb + C_KM2 + w * 512 + lane * 4), oa = wg * 4608;
  uint32_t a[144];
  mbar_wait(sb + W_BAR + wg * 8, 0);
  if (threadIdx.x == 0) TS(23);
  load_frags<36>(a, sb + C_W + wg * 73728);
  fence_async_smem();
  bar_arrive(B_WG0 + wg, 256);
  if (threadIdx.x == 0) TS(24);
  bar_sync(B_WG2, 384);
  const uint32_t round = min(w, 2u) + (wg ? 0 : 3), gdly = P.dly[8 + round], ps = t >> 2, pf = j * 16 + (ps >> 1);
  uint4* const dsts = pinned(g_xb + (ps * 4096 + near_half(ps * 8, ps * 2) * 256 + c * 4 + (t & 3)));
  uint4* const dstf = pinned(g_xb + (pf * 4096 + 512 + near_half(pf * 8 + 1, pf * 2) * 256 + h * 8 + (t & 7)));
  const uint32_t* const gsrc = (const uint32_t*)g_xb + (h * 16384 + min(w, 2u) * 4096 + near_half(h * 8 + !wg, h * 2) * 1024 +
                               (wg ? (lane & 24) * 2 + j * 8 + (lane & 7) : 2048 + (lane & 16) * 2 + j * 16 + (lane & 15)));
  uint32_t* gdst = g_mimg + (16384 + (lane >> 4) * 1024 + (lane & 2) * 4 +
                   (wg ? (round ? 1536 + round * 512 : 0) + h * 16 + ((lane ^ (c >> 2)) & 1) * 4 + j * 2 + ((lane >> 2) & 1)
                       : (round - 1) * 2048 + c * 16 + ((lane ^ (c >> 1)) & 1) * 4 + ((lane >> 2) & 3)));
  const uint32_t m0 = __ldcg(gdst - 16384);
  mbar_wait(sb + W_BAR + wg * 8, 1);
  bar_sync(B_INIT, 256);
  if ((threadIdx.x & 127) == 0) TS(4);

  uint32_t ring = 1;
#pragma unroll 1
  for (int n = 0; n < STEPS; n++) {
    float d[8], e[8];
    uint32_t redo = n + 1;
    do {
      mbar_wait(sb + CB_M, n & 1);
      wg_fence();
      m_steps<0, 0, 4>(d, a, oa);
      if (VE && wg) m_steps<18, 0, 4>(e, a, 4608);
      wg_commit();
      if (wid == 0) TR(8);
      mbar_wait(sb + CB_M + 8, n & 1);
      wg_fence();
      m_steps<0, 4, 8>(d, a, oa);
      if (VE > 4 && wg) m_steps<18, 4, (VE > 4 ? VE - 4 : 2)>(e, a, 4608);
      wg_commit();
      mbar_wait(sb + CB_MV, n & 1);
      redo = lds32(sb + C_BAD) == redo ? SENT : 0;
    } while (redo);
    mbar_wait(sb + CB_MV + 8, n & 1);
    wg_fence();
    m_steps<0, 12, 8>(d, a, oa);
    wg_commit();
    mbar_wait(sb + CB_MV + 16, n & 1);
    wg_fence();
    m_steps<0, 20, 8>(d, a, oa);
    wg_commit();
    mbar_wait(sb + CB_MV + 24, n & 1);
    wg_fence();
    m_steps<0, 28, 8>(d, a, oa);
    wg_commit();
    wg_wait<0>();
    if (w == 0) TR(6 + wg);
    const uint32_t f0 = pack2(d[0], d[1]), f1 = pack2(d[4], d[5]), f2 = pack2(d[2], d[3]), f3 = pack2(d[6], d[7]);
    stsm4(mine + C_QM + wg * 2048, f0, f1, f2, f3);
    bar_arrive(B_QK, 416);
    const uint32_t tag = (n & 1) ^ 1;
    if (wg) {
      if (n + 1 < STEPS) bar_sync(B_S, 256);
      wg_fence();
      m_steps<18, VE, 36 - VE>(e, a, 4608);
      wg_commit();
      st_async1(theirs, j ? f0 : f1, rb + CB_XX);
      st_async1(theirs + 256, j ? f2 : f3, rb + CB_XX);
      wg_wait<0>();
      if (w == 0) TR(11);
      const uint32_t v0 = pack2(e[0], e[1]), v1 = pack2(e[4], e[5]), v2 = pack2(e[2], e[3]), v3 = pack2(e[6], e[7]);
      stsm4(mine + C_VM, v0, v1, v2, v3);
      bar_arrive(B_V, 256);
      st_async1(theirs + 128, j ? v0 : v1, rb + CB_XX);
      st_async1(theirs + 384, j ? v2 : v3, rb + CB_XX);
      if (n + 1 == STEPS) break;
      bar_sync(B_O, 256);
      if (!WFENCE) fence_async_smem();
      wg_fence();
#pragma unroll
      for (int ks = 0; ks < 4; ks++) {
        if (ks == 0) wg_ss16<0>(d, desc_sw128(C_W + 32 * 2048), desc_n16(C_OI));
        else wg_ss16<1>(d, desc_sw128(C_W + (32 + ks) * 2048), desc_n16(C_OI + ks * 512));
      }
      wg_commit();
      bar_arrive(B_X, 256);
      if (w == 0) TR(0);
      wg_wait<0>();
      store_partial(dsts, pack_partial(d, tag));
      bar_arrive(B_M, 160);
      if (w == 0) TR(1);
    } else {
      if (n + 1 == STEPS) break;
      bar_sync(B_X, 256);
      wg_fence();
      o_steps<0, 4>(d, a);
      wg_commit();
      o_steps<4, 4>(e, a);
      wg_commit();
      wg_wait<1>();
      store_partial(dsts + 1024, pack_partial(d, tag));
      if (w == 0) TR(2);
      if (OGAP == 0) { wg_fence(); o_steps<8, 4>(d, a); wg_commit(); wg_wait<1>(); } else wg_wait<0>();
      store_partial(dsts + 2048, pack_partial(e, tag));
      if (w == 0) TR(3);
      wg_fence();
      if (OGAP) o_steps<8, 4>(d, a);
      if (OGAP < 2) o_steps<16, 4>(e, a);
      wg_commit();
      bar_sync(B_T, 256);
      if (w == 0) { TRV(61, 0); TR(12); }
      wg_fence();
      o_steps<12, 4>(d, a);
      wg_commit();
      if (OGAP == 2) o_steps<16, 4>(e, a);
      o_steps<20, 4>(e, a);
      wg_commit();
      wg_wait<1>();
      store_partial(dstf, pack_partial(d, tag));
      if (w == 0) TR(4);
      wg_fence();
      o_steps<24, 8>(d, a);
      wg_commit();
      wg_wait<1>();
      store_partial(dstf + 1024, pack_partial(e, tag));
      bar_arrive(B_OE, 256);
      if (w == 0) TR(5);
      wg_wait<0>();
      store_partial(dstf + 2048, pack_partial(d, tag));
      if (w == 0) TR(15);
    }
    if (w < 3) {
      mbar_wait(sb + CB_REF, n & 1);
      wait_until(lds32(sb + C_REF), gdly);
      gather_reduce(gsrc, gdst, m0, wg, tag, lane, sb, n, 16 + round * 4);
      if (++ring == MRING) { ring = 0; gdst -= MRING * 16384; }
      gdst += 16384;
    }
  }
}

template <int KS> __device__ __forceinline__ void x_scores(float* s, float* sm, const uint4* q, uint32_t ok, uint32_t om) {
  wg_rs32o<1, desc_sw64(C_KV + KS * 1024)>(s, q[KS].x, q[KS].y, q[KS].z, q[KS].w, ok);
  wg_rs8o<1, desc_n16(C_KM + KS * 512)>(sm, q[KS].x, q[KS].y, q[KS].z, q[KS].w, om);
  if constexpr (KS < 3) x_scores<KS + 1>(s, sm, q, ok, om);
}

__device__ __forceinline__ void chain_attn(const Params& P, uint32_t sb) {
  const int c = chain_id(), j = c & 1;
  const int tid = threadIdx.x, lane = tid & 31, w = __shfl_sync(~0u, (tid >> 5) & 3, 0);
  const int l = w >> 1, u = w & 1;
  const uint32_t rb = mapa(sb, j ^ 1);
  const float sc = 0.08838834764831845f * 1.4426950408889634f;
  const uint32_t ones = 0x3F803F80u;
  const uint32_t km_off = C_KM + (lane >> 3) * 256 + l * 128 + (lane & 7) * 16;
  const uint32_t qm_off = C_QM + (lane >> 4) * 256 + l * 128 + (lane & 7) * 16;
  const uint32_t kv_off = C_KV + l * 4096 + (lane & 15) * 64 + (((lane >> 4) ^ (u * 2) ^ ((lane >> 1) & 3)) << 4);

  load_wg<CHAIN, true>(P, sb, false, 1, w);
  if (lane == 0) mbar_arrive(sb + CB_M);
#pragma unroll 1
  for (int n = 0; n < STEPS; n++) {
    const uint32_t kvb = sb + kv_off + (n & 1) * 16384;
    if (w == 0 && elect()) { mbar_expect(sb + CB_SX, 2560); mbar_expect(sb + CB_OX, 2048); mbar_expect(sb + CB_XX, 2048); }
    mbar_wait(sb + CB_FULL + (n & 1) * 8, (n >> 1) & 1);
    if (n < 3 && tid == 256) TS(n ? 20 + n : 5);
    __syncwarp();
    {
      uint32_t km[8];
      uint4 kx[8];
#pragma unroll
      for (int i = 0; i < 8; i++) ldsm4t(kx[i].x, kx[i].y, kx[i].z, kx[i].w, (kvb ^ ((i & 1) * 32)) + (i >> 1) * 1024);
      mbar_wait(sb + CB_VF, n & 1);
      if (w == 1) TRD(60, kx[7].x);
      bar_sync(B_QK, 416);
      if (n + 1 == STEPS) {
        bar_sync(B_V, 256);
      } else {
      uint32_t qm[16];
#pragma unroll
      for (int ks = 0; ks < 4; ks++) ldsm4t(qm[4 * ks], qm[4 * ks + 1], qm[4 * ks + 2], qm[4 * ks + 3], sb + qm_off + ks * 512);
      ldsm4t(km[0], km[1], km[2], km[3], sb + km_off);
      ldsm4t(km[4], km[5], km[6], km[7], sb + km_off + 1024);
      float s[5][4];
#pragma unroll
      for (int i = 0; i < 5; i++) { s[i][0] = s[i][1] = s[i][2] = s[i][3] = 0.f; }
#pragma unroll
      for (int ks = 0; ks < 4; ks++) {
        const uint32_t* q = qm + 4 * ks;
        mma16(s[1], q[0], q[1], q[2], q[3], kx[2 * ks].x, kx[2 * ks].y);
        mma16(s[2], q[0], q[1], q[2], q[3], kx[2 * ks].z, kx[2 * ks].w);
        mma16(s[0], q[0], q[1], q[2], q[3], km[2 * ks], km[2 * ks + 1]);
        mma16(s[3], q[0], q[1], q[2], q[3], kx[2 * ks + 1].x, kx[2 * ks + 1].y);
        mma16(s[4], q[0], q[1], q[2], q[3], kx[2 * ks + 1].z, kx[2 * ks + 1].w);
      }
      const uint32_t sx = C_SX + l * 1280;
      st_async4(rb + sx + u * 512 + lane * 16, s[1][0], s[1][1], s[2][0], s[2][1], rb + CB_SX);
      st_async1(rb + sx + 1024 + u * 128 + lane * 4, __float_as_uint(u ? s[0][1] : s[0][0]), rb + CB_SX);
      bar_arrive_after<B_S, 256>(__float_as_uint(s[3][0]), __float_as_uint(s[4][0]));
      uint4 vx[4];
#pragma unroll
      for (int i = 0; i < 4; i++) ldsm4(vx[i].x, vx[i].y, vx[i].z, vx[i].w, (kvb ^ ((i & 1) * 32)) + 8192 + (2 * u + (i >> 1)) * 1024);
      mbar_wait(sb + CB_SX, n & 1);
      const uint4 p0 = lds128(sb + sx + u * 512 + lane * 16), p1 = lds128(sb + sx + (u ^ 1) * 512 + lane * 16);
      const uint2 p2 = make_uint2(lds32(sb + sx + 1024 + lane * 4), lds32(sb + sx + 1152 + lane * 4));
      float t[10] = {s[0][0] + __uint_as_float(p2.x), s[0][1] + __uint_as_float(p2.y),
                     s[1][0] + __uint_as_float(p0.x), s[1][1] + __uint_as_float(p0.y),
                     s[2][0] + __uint_as_float(p0.z), s[2][1] + __uint_as_float(p0.w),
                     s[3][0] + __uint_as_float(p1.x), s[3][1] + __uint_as_float(p1.y),
                     s[4][0] + __uint_as_float(p1.z), s[4][1] + __uint_as_float(p1.w)};
      float mx = fmaxf(fmaxf(fmaxf(fmaxf(t[2], t[3]), fmaxf(t[4], t[5])), fmaxf(fmaxf(t[6], t[7]), fmaxf(t[8], t[9]))), fmaxf(t[0], t[1]));
      mx = fmaxf(fmaxf(mx, __shfl_xor_sync(~0u, mx, 1)), fmaxf(__shfl_xor_sync(~0u, mx, 2), __shfl_xor_sync(~0u, mx, 3)));
      const float ms = -mx * sc;
#pragma unroll
      for (int i = 0; i < 10; i++) t[i] = ex2(fmaf(t[i], sc, ms));
      uint32_t p[5];
#pragma unroll
      for (int i = 0; i < 5; i++) p[i] = pack2(t[2 * i], t[2 * i + 1]);
      p[1] |= (p[0] & p[3] & p[4]) & 0x80008000u;
      float o[2][4], z[4] = {0.f, 0.f, 0.f, 0.f};
      mma16(z, ones, ones, ones, ones, p[1], p[2]);
#pragma unroll
      for (int i = 0; i < 2; i++) {
        o[i][0] = o[i][1] = o[i][2] = o[i][3] = 0.f;
        mma16(o[i], vx[2 * i].x, vx[2 * i].y, vx[2 * i].z, vx[2 * i].w, p[1], p[2]);
      }
      mma16(z, ones, ones, ones, ones, p[3], p[4]);
#pragma unroll
      for (int i = 0; i < 2; i++) mma16(o[i], vx[2 * i + 1].x, vx[2 * i + 1].y, vx[2 * i + 1].z, vx[2 * i + 1].w, p[3], p[4]);
      mma8(z, ones, ones, p[0]);
      bar_sync_after<B_V, 256>(p[1]);
      ldsm4(km[0], km[1], km[2], km[3], sb + km_off + (C_VM - C_KM) + u * 1024);
      mma8(o[0], km[0], km[1], p[0]);
      mma8(o[1], km[2], km[3], p[0]);
      const float i0 = rcp(z[0]), i1 = rcp(z[1]);
      const uint32_t oo = C_OI + u * 1024 + l * 128 + lane * 4;
      uint32_t ow[4];
#pragma unroll
      for (int i = 0; i < 2; i++) { ow[2 * i] = pack2(o[i][0] * i0, o[i][1] * i1); ow[2 * i + 1] = pack2(o[i][2] * i0, o[i][3] * i1); }
      stsm4(sb + C_OI + u * 1024 + l * 128 + (lane >> 3) * 256 + (lane & 7) * 16, ow[0], ow[1], ow[2], ow[3]);
      if (WFENCE) fence_async_smem();
      bar_arrive(B_O, 256);
#pragma unroll
      for (int i = 0; i < 4; i++) st_async1(rb + oo + 2048 + i * 256, ow[i], rb + CB_OX);
      }
    }
    {
      const uint32_t lane = opaque_tid() & 31, own = ((n & 1) * 16384 + j * 4096) >> 4;
      float s[16], sm[4];
#pragma unroll
      for (int i = 0; i < 16; i++) s[i] = sm[i & 3] = 0.f;
      {
        uint4 q[4];
        mbar_wait(sb + CB_Q, n & 1);
        auto load_q = [&]() {
#pragma unroll
          for (int ks = 0; ks < 4; ks++) q[ks] = lds128(sb + C_Q + (ks >> 1) * 4096 + w * 1024 + (ks & 1) * 512 + lane * 16);
        };
        if (QPOS == 0) load_q();
        mbar_wait(sb + CB_XX, n & 1);
        if (n + 1 < STEPS) mbar_wait(sb + CB_OX, n & 1);
        fence_async_smem();
        if (n + 1 < STEPS) bar_arrive(B_T, 256);
        if (QPOS == 1) load_q();
        if (n + 1 < STEPS) bar_sync(B_OE, 256);
        if (QPOS == 2) load_q();
        if (w == 1) { TRV(61, 0); TR(9); }
#pragma unroll 1
        for (uint32_t hf = 0; hf < 2; hf++) {
          wg_fence();
          x_scores<0>(s, sm, q, hf ? (C_KV2 - C_KV) >> 4 : own, hf ? (C_KM2 - C_KM) >> 4 : j * 8);
          wg_commit();
          wg_wait<0>();
#pragma unroll
          for (int ks = 0; ks < 4; ks++) asm volatile("mov.b32 %0, %1; mov.b32 %2, %3;" : "+r"(q[ks].x), "+r"(q[ks].y), "+r"(q[ks].z), "+r"(q[ks].w));
        }
      }
      const float neg = -1e9f * 11.313708498984761f;
      const int lim = 8 * (w - (int)(lane & 3)) + (int)(lane >> 2);
      float t[10] = {sm[0], sm[1]};
#pragma unroll
      for (int i = 0; i < 8; i++) t[2 + i] = i > lim ? neg : s[(i >> 1) * 4 + (i & 1)];
      float mx = fmaxf(fmaxf(fmaxf(fmaxf(t[2], t[3]), fmaxf(t[4], t[5])), fmaxf(fmaxf(t[6], t[7]), fmaxf(t[8], t[9]))), fmaxf(t[0], t[1]));
      mx = fmaxf(fmaxf(mx, __shfl_xor_sync(~0u, mx, 1)), fmaxf(__shfl_xor_sync(~0u, mx, 2), __shfl_xor_sync(~0u, mx, 3)));
      const float ms = -mx * sc;
#pragma unroll
      for (int i = 0; i < 10; i++) t[i] = ex2(fmaf(t[i], sc, ms));
      uint32_t p[5];
#pragma unroll
      for (int i = 0; i < 5; i++) p[i] = pack2(t[2 * i], t[2 * i + 1]);
      float z = ((t[0] + t[1]) + (t[2] + t[3])) + ((t[4] + t[5]) + (t[6] + t[7])) + (t[8] + t[9]);
      const uint32_t row = sb + C_Q + w * 1024 + (lane >> 2) * 128 + (((lane & 3) ^ (lane >> 2)) << 4);
#pragma unroll 1
      for (uint32_t hf = 0; hf < 2; hf++) {
        float o[32];
        const uint32_t vo = hf ? (C_KV2 + 4096 - C_KV - 8192) >> 4 : own;
        wg_fence();
        wg_rs64o<0, desc_sw64(C_KV + 8192)>(o, p[1], p[1], p[2], p[2], vo);
        wg_rs64o<1, desc_sw64(C_KV + 8192 + 32)>(o, p[3], p[3], p[4], p[4], vo);
        wg_rs64o<1, mkdesc(C_VM, 128, 256, 0)>(o, p[0], p[0], 0, 0, hf ? (C_VM2 - C_VM) >> 4 : j * 8);
        wg_commit();
        if (hf) {
          if (elect()) mbar_arrive(sb + CB_M);
        } else {
          z += __shfl_xor_sync(~0u, z, 1);
          z = rcp(z + __shfl_xor_sync(~0u, z, 2));
        }
        wg_wait<0>();
#pragma unroll
        for (int qq = 0; qq < 2; qq++) {
          const float* r = o + 16 * qq;
          sts128((row ^ (qq * 64)) + hf * 4096,
                 make_uint4(pack2(r[0] * z, r[1] * z), pack2(r[4] * z, r[5] * z), pack2(r[8] * z, r[9] * z), pack2(r[12] * z, r[13] * z)));
        }
      }
      bar_arrive(B_G, 160);
      if (w == 1) TR(10);
    }
  }
  if ((threadIdx.x & 127) == 0) TS(6);
}

__device__ __forceinline__ void chain_aux(const Params& P, uint32_t sb) {
  const uint32_t c = chain_id(), j = c & 1, lane = threadIdx.x & 31, w = __shfl_sync(~0u, (threadIdx.x >> 5) & 3, 0);
  load_wg<CHAIN, true>(P, sb, false, 0, w);
  if (threadIdx.x == 384) TS(25);
  if (threadIdx.x == 384) grid_wait(1, lds32(sb + S_GEN));
  bar_sync(B_WG2, 384);
  if (threadIdx.x == 384) TS(13);
  if (w == 0) {
    const uint32_t* fg = g_fl + FL_G + near_half(XB_F, c) * 1024 + (c >> 1) * 8;
#pragma unroll 1
    for (int n = 0; n < STEPS; n++) {
      const unsigned char* blk = g_qkv + (uint32_t)((n % QRING) * (N_CHAIN * 24576));
      const uint32_t t1 = clk(), kb = sb + CB_FULL + (n & 1) * 8, kv = sb + C_KV + (n & 1) * 16384;
      uint32_t t0 = t1 - 100000, x = 0;
      if (n > 0) {
        wait_until(t1, KMIN);
        do asm volatile("ld.relaxed.gpu.global.u32 %0, [%1];" : "=r"(x) : "l"(fg) : "memory"); while (x <= n && clk() - t1 < KWIN);
        if (NOBULK) x = n + 1;
        if (x > n) {
          asm volatile("fence.acquire.gpu;" ::: "memory");
          fence_async_global();
          if (elect()) { mbar_expect(kb, 8192); bulk_load(kv, blk + c * 24576, 8192, kb); }
        }
        T3(0); CNT(12, 1 + (x <= n));
        mbar_wait(sb + CB_REF, (n - 1) & 1);
        t0 = lds32(sb + C_REF);
        wait_until(t0, DLYK - 500);
      }
      if (!NOBULK) wait_flags(fg + (lane & 1) * 256, n + 1);
      fence_async_global();
      wait_until(t0, DLYK);
      if (elect()) {
        if (x <= n) { mbar_expect(kb, 8192); bulk_load(kv, blk + c * 24576, 8192, kb); }
        mbar_expect(sb + CB_VF, 8192);
        bulk_load(kv + 8192, blk + (c * 24576 + 8192), 8192, sb + CB_VF);
      }
      T3(1);
      if (!NOBULK) wait_flags(fg + 512, n + 1);
      T3(2);
      fence_async_global();
      if (n > 0) bar_sync(B_R, 64);
      if (elect()) {
        mbar_expect(sb + CB_Q, 16384);
        bulk_load(sb + C_Q, blk + (c * 24576 + 16384), 8192, sb + CB_Q);
        bulk_load(sb + C_KV2, blk + ((c ^ 1) * 24576 + j * 4096), 4096, sb + CB_Q);
        bulk_load(sb + C_KV2 + 4096, blk + ((c ^ 1) * 24576 + 8192 + j * 4096), 4096, sb + CB_Q);
      }
      T3(3);
    }
  } else {
    const uint32_t near = __ballot_sync(~0u, near_half(XB_M + min(lane, MRING - 1u) * 8, c));
    uint32_t ring = 0;
    if (w > 1) {
      const uint32_t odd = w & 1, chk = pinned(sb + C_M + odd * 2048 + m_probe(lane)), again = sb + CB_MV + 32 + odd * 8;
      const bool one = elect();
      uint32_t mph = 0;
#pragma unroll 1
      for (int n = 0; n <= STEPS; n++) {
#pragma unroll
        for (int k = 0; k < 3; k++) {
          if (n == STEPS || (k == 2 && odd)) break;
          const uint32_t b = 2 * k + odd, at = chk + (k ? k * 8192 - 2048 + odd * 2048 : 0);
          uint32_t mb = sb + CB_M + b * 8, ph = n & 1;
          int it = 1;
          while (true) {
            mbar_wait(mb, ph);
            const bool bad = __any_sync(~0u, (k ? m_max(at, at + 2048) : max(m_max(at, at ^ 8), odd ? m_max(at + 2048, (at ^ 8) + 2048) : 0)) == SENT);
            if (one && !bad) mbar_arrive(sb + CB_MV + (k ? b * 8 - 8 : 0));
            if (!bad) break;
            mb = again; ph = mph; mph ^= 1;
            if (one) {
              if (k == 0) sts32(sb + C_BAD, n + 1);
              mbar_expect(mb, b ? 4096 : 2048);
              m_fetch(sb, ring * 65536 + ((near >> ring) & 1) * 4096, b, mb);
            }
            __syncwarp();
            spin_guard(it);
          }
          TR(41 + b * 4); CNT(6 + b, it);
        }
        ring = ring + 1 == MRING ? 0 : ring + 1;
        if (!odd) {
          if (n < STEPS) { TRSYNC(); TRDUMP(n - 2); }
        } else if (n > 0) {
          unsigned char* o = g_oimg + (uint32_t)(((n - 1) & (RING - 1)) * (N_CHAIN * 8192) + j * 4096);
          bar_sync(B_G, 160);
          fence_async_smem();
          if (one) {
            bulk_store(o + c * 8192, sb + C_Q, 4096);
            bulk_store(o + (c ^ 1) * 8192, sb + C_Q + 4096, 4096);
            asm volatile("cp.async.bulk.commit_group;\ncp.async.bulk.wait_group.read 0;" ::: "memory");
            { const int n_ = n - 1; { const int n = n_; T3(4); (void)n; } }
          }
          __syncwarp();
          if (n < STEPS) bar_arrive(B_R, 64);
          if (one) {
            bulk_done_inc(g_fl + FL_O + c);
            { const int n_ = n - 1; { const int n = n_; T3(5); (void)n; } }
          }
          __syncwarp();
        }
      }
    } else {
      const uint32_t* ts = g_fl + FL_SYNC + near_half(XB_F + 1, c) * 1024 + lane * 2;
      uint32_t t0 = clk() - 100000;
#pragma unroll 1
      for (int n = 0; n < STEPS; n++) {
        const uint32_t src = ring * 65536 + ((near >> ring) & 1) * 4096;
        if (lane < 5) mbar_expect(sb + CB_M + lane * 8, lane ? 4096 : 2048);
        __syncwarp();
        if (elect()) {
#pragma unroll
          for (int b = 0; b < 5; b++) {
            wait_until(t0, P.dly[14 + b]);
            m_fetch(sb, src, b, sb + CB_M + b * 8);
            TR(40 + b * 4);
          }
        }
        __syncwarp();
        ring = ring + 1 == MRING ? 0 : ring + 1;
        uint32_t va, vb;
        const uint32_t off = timer_offset(), tag = (uint32_t)(n + 1) << 24;
        bar_sync(B_QK, 416);
        if (n + 1 == STEPS) break;
        sts32(sb + C_REF + 4, 0);
        const uint32_t c0 = clk(), stamp = c0 + off;
        st_relaxed_if(g_fl + FL_SYNC + lane * 1024 + c, tag | (stamp & 0xFFFFFF), lane < 2);
        TR(13);
        wait_until(c0, DLYS);
        int it = 0;
        do {
          asm volatile("ld.relaxed.gpu.global.v2.u32 {%0,%1}, [%2];" : "=r"(va), "=r"(vb) : "l"(ts) : "memory");
          spin_guard(it);
        } while (__any_sync(~0u, ((va ^ tag) | (vb ^ tag)) >> 24));
        const int late = __reduce_max_sync(~0u, max((int)((va - stamp) << 8), (int)((vb - stamp) << 8))) >> 8;
        t0 = c0 + min((uint32_t)late, clk() - c0);
        if (elect()) {
          sts32(sb + C_REF, t0);
          mbar_arrive(sb + CB_REF);
        }
        st_relaxed_if(g_fl + FL_TICK + lane * 1024, tag | ((t0 + off) & 0xFFFFFF), c == 0 && lane < 2);
        TR(14); CNT(11, it);
        bar_sync(B_M, 160);
      }
    }
  }
}

template <int WG>
__device__ __forceinline__ void g_math(const Params& P, uint32_t sb) {
  const int q = g_unit(WG);
  const int lane = threadIdx.x & 31, w = (threadIdx.x >> 5) & 3;
  const bool isq = q >= 64;
  uint32_t a[136];
  {
    const uint32_t stage = sb + G_W + WG * 73728;
    mbar_wait(sb + W_BAR + WG * 8, 0);
    if (threadIdx.x == 0) TS(23);
    load_frags<34>(a, stage);
    fence_async_smem();
    bar_sync(B_WG0 + WG, 128);
    if (threadIdx.x == 0) TS(24);
    load_wg<GROLE>(P, sb, false, WG, w);
    if (threadIdx.x == 0) TS(25);
    mbar_wait(sb + W_BAR + WG * 8, 1);
  }
  if ((threadIdx.x & 127) == 0) TS(4);
  const uint32_t off0 = (q & 31) * 49152 + (q >> 5) * 8192 +
                        (isq ? (w >> 1) * 4096 + (w & 1) * 512 + lane * 16 : w * 1024 + (lane >> 2) * 64 + (((lane ^ (lane >> 3)) & 3) << 4));
#pragma unroll 1
  for (int n = 0; n < STEPS; n++) {
    float d0[32], d1[32];
    if (WG == 0 && n >= LOCK0) bar_sync(B_OE, 160);
    if (n > 0) bar_sync(B_V + WG, 256);
#pragma unroll
    for (int ch = 0; ch < 9; ch++) {
      mbar_wait(sb + G_BAR + ch * 8, n & 1);
      if (ch == 0) { if ((threadIdx.x & 127) == 0) T3(5 + WG * 3); __syncwarp(); }
      if (ch == 4) { if ((threadIdx.x & 127) == 0) T3(6 + WG * 3); __syncwarp(); }
      if (ch == 8 && (WG == 0 ? n > 0 : n + 1 < STEPS)) bar_arrive(B_V + (WG ^ 1), 256);
      wg_fence();
#pragma unroll
      for (int kk = 0; kk < 4 - FASTG; kk++) {
        const int i = ch * 4 + kk;
        float* d = i & 1 ? d1 : d0;
        const uint64_t db = desc_sw128(G_RING + ch * 8192 + (kk & 2) * 32);
        if (i < 2) wg_rs64<0>(d, a + i * 4, db);
        else if (i < 34) wg_rs64<1>(d, a + i * 4, db);
        else wg_ss64<1>(d, desc_sw128(G_W2 + WG * 4096 + (i - 34) * 2048), db);
        wg_ss64<1>(d, desc_sw128(G_W + WG * 73728 + i * 2048), db + 2);
      }
      wg_commit();
      if (ch > 0) { wg_wait<1>(); if (lane == 0) mbar_arrive(sb + G_BAR + 128 + (ch - 1) * 8); }
    }
    wg_wait<0>();
    if (lane == 0) mbar_arrive(sb + G_BAR + 128 + 8 * 8);
    if ((threadIdx.x & 127) == 0) T3(7 + WG * 3);
    __syncwarp();
    uint32_t tw = clk() + (WG ? 0 : DLYW);
    unsigned char* base = g_qkv + (size_t)(n & (QRING - 1)) * (N_CHAIN * 24576);
    if ((ABL & 1) && d0[0] != 1234.5f) {
    } else if (isq) {
#pragma unroll
      for (int i = 0; i < 8; i++) {
        const float *d = (i < 4 ? d0 : d1) + 4 * i, *e = (i < 4 ? d1 : d0) + 4 * i;
        wait_until(tw, 0); tw += P.dly[2 + WG];
        *(uint4*)(base + off0 + (i >> 2) * 24576 + (i & 3) * 1024) =
          make_uint4(movmat(pack2(d[0], d[1])), movmat(pack2(e[0], e[1])), movmat(pack2(d[2], d[3])), movmat(pack2(e[2], e[3])));
      }
    } else {
#pragma unroll
      for (int i = 0; i < 8; i++) {
        const float* d = (i < 4 ? d0 : d1) + 8 * (i & 2) + 2 * (i & 1);
        wait_until(tw, 0); tw += P.dly[2 + WG];
        *(uint4*)(base + off0 + (i >> 2) * 24576 + (i & 2) * 2048 + (i & 1) * 512) =
          make_uint4(pack2(d[0], d[1]), pack2(d[4], d[5]), pack2(d[8], d[9]), pack2(d[12], d[13]));
      }
    }
    bar_arrive(B_M + WG, 160);
  }
}

__device__ __forceinline__ void fill16(void* p, uint32_t v) {
  asm volatile("st.global.v4.u32 [%0], {%1,%1,%1,%1};" :: "l"(p), "r"(v) : "memory");
}
__device__ __forceinline__ void g_load(const Params& P, uint32_t sb) {
  const int lane = threadIdx.x & 31, w = __shfl_sync(~0u, (threadIdx.x >> 5) & 3, 0);
  if (w == 2) return;
  if (w < 2) { bar_sync(15, 192); fence_async_smem(); }
  uint32_t fl = 0;
#pragma unroll 1
  for (int n = w == 3 ? LOCK0 : 0; n < STEPS; n++) {
    if (w && n == LOCK0) { grid_wait(1, lds32(sb + S_GEN)); fl = near_half(XB_F, bid()) * 1024; }
    if (w == 3) {
      const uint32_t tag = (uint32_t)(n - LOCK0 + 1) << 24;
      uint32_t v; int it = 0;
      do { asm volatile("ld.relaxed.gpu.global.u32 %0, [%1];" : "=r"(v) : "l"(g_fl + fl + FL_TICK) : "memory"); spin_guard(it); } while (!NOCHAIN && v < tag);
      const uint32_t off = timer_offset(), now = clk(), t0 = now - ((v ^ tag) >> 24 ? DLYG : (now + off - v) & 0xFFFFFF);
      asm volatile("fence.acquire.gpu;" ::: "memory");
      if (lane == 0) T3(11);
      __syncwarp();
      wait_until(t0, DLYG);
      if (lane == 0) T3(4);
      bar_sync(B_OE, 160);
      continue;
    }
    if (w == 0 || n == 0) {
      if (n < NSEG) wait_flags(g_lnflag + n * 16 + (lane & 1) * 8, 1);
    } else if (!NOCHAIN && n >= LAG) {
      wait_flags(g_fl + fl + FL_F + (lane & 1) * 8, n - LAG + 1);
    }
    if (w) { if (lane == 0) T3(12); bar_sync(B_X, 96); }
    fence_async_global();
    const unsigned char* src = g_lnimg + (uint32_t)((w ? (n >= LAG ? NSEG + n - LAG : 0) : min(n, NSEG - 1)) * 36864);
#pragma unroll 1
    for (int ch = 0; ch < 9; ch++) {
      const uint32_t full = sb + G_BAR + ch * 8;
      mbar_wait(full + 128, (n & 1) ^ 1);
      if (elect()) {
        mbar_expect(full, ABL & 2 ? 16 : 4096);
        bulk_load(sb + G_RING + ch * 8192 + w * 4096, src + ch * 4096, ABL & 2 ? 16 : 4096, full);
      }
    }
  }
}

__device__ __forceinline__ void g_aux(const Params& P, uint32_t sb) {
  const int lane = threadIdx.x & 31, w = (threadIdx.x >> 5) & 3;
  if (w == 1 || w == 2) {
    const int q = g_unit(w - 1);
    uint32_t* f = g_fl + FL_G + q * 8;
#pragma unroll 1
    for (int n = 0; n < STEPS; n++) {
      const uint32_t ln = opaque_tid() & 31;
      uint4* z = (uint4*)g_oacc + (uint32_t)(((n + 1) % ARING) * (16 * DM) + q * 96 + ln);
      if (!(ABL & 16)) { fill16(z, 0); fill16(z + 32, 0); fill16(z + 64, 0); }
      if (n + 3 >= MRING && q < 80) fill16((uint4*)g_mimg + (uint32_t)(((n + 3) % MRING) * 4096 + q * 32 + ln), SENT);
      bar_sync(B_M + (w - 1), 160);
      if (lane == 0) { T3(w * 2 - 2); fence_async_global(); flag_release(f, n + 1); T3(w * 2 - 1); }
      __syncwarp();
    }
  } else {
    const uint32_t u = (bid() - N_CHAIN) * 2 + (w & 1), r = u / 36 * 16 + (u & 3) * 4 + (lane >> 3);
    uint32_t o = r * (DM / 8) + (u % 36 >> 2) * 8 + ((lane & 7) ^ ((r >> 1) & 3)), fl = 0;
#pragma unroll 1
    for (int k = -LAG - 1; k < STEPS; k++) {
      if (k < NSEG - 1) bar_sync(B_X, 96);
      if (k < LAG || u >= 72) continue;
      if (k == NSEG - 1) { fl = near_half(XB_F, bid()) * 1024; wait_flags(g_fl + fl + FL_F + (lane & 1) * 8, NSEG + 1); }
      const uint4 x = __ldcg((const uint4*)P.out + o);
      if (k >= NSEG - 1) wait_flags(g_fl + fl + FL_OCNT + (max(k, NSEG) % OCRING) * 8, N_O * 3 * (max(k, NSEG) / OCRING + 1));
      const float4* a = (const float4*)g_oacc + ((k % ARING) * (16 * DM) + 8 * DM + u * 64 + lane * 2);
      const float4 p = __ldcg(a), v = __ldcg(a + 1);
      ((uint4*)P.out)[o] = make_uint4(badd2(x.x, pack2(p.x, p.y)), badd2(x.y, pack2(p.z, p.w)), badd2(x.z, pack2(v.x, v.y)), badd2(x.w, pack2(v.z, v.w)));
      o += 4 * DM;
    }
    if ((threadIdx.x & 127) == 0) TS(7);
  }
}

template <int WG, bool HALF, int KS, int N> __device__ __forceinline__ void o_mma(float* d, const uint32_t* a, uint32_t ob) {
  constexpr uint64_t db = desc_sw128(O_RING + (KS >> 2) * 8192 + (KS & 3) * 32);
  constexpr uint64_t da = desc_sw128(O_W + WG * 40960 + (KS < 40 ? KS / 5 * 2 + KS % 5 / 2 : KS - 24) * 2048);
  if constexpr (KS < 40 && !(KS % 5 & 1)) {
    const uint32_t* r = a + (KS / 5 * 3 + KS % 5 / 2) * 4;
    if constexpr (HALF) wg_rs32k<KS != 0, db>(d, r[0], r[1], r[2], r[3], ob); else wg_rs64<KS != 0>(d, r, db);
  } else {
    if constexpr (HALF) wg_ss32k<da, db>(d, ob); else wg_ss64<1>(d, da, db);
  }
  if constexpr (N > 1) o_mma<WG, HALF, KS + 1, N - 1>(d, a, ob);
}
template <int WG, bool HALF, int GR> __device__ __forceinline__ void o_groups(float* d, const uint32_t* a, uint32_t sb, int n, bool more) {
  const uint32_t ob = n < NSEG ? 0 : 256;
  mbar_wait(sb + O_BAR + GR * 8, n & 1);
  if (GR == 0) { if ((threadIdx.x & 127) == 0) T3(13 + WG); __syncwarp(); }
  if (GR == (WG == 0 ? OTURN : 4) && (WG < 2 || n + 1 < STEPS)) bar_arrive(B_V + (WG + 1) % 3, 256);
  wg_fence();
  o_mma<WG, HALF, GR * 8, 8 - 2 * FASTG>(d, a, ob);
  if (GR == 4 && more) o_mma<WG, HALF, 40, 4>(d, a, ob);
  wg_commit();
  if (GR > 0) { wg_wait<1>(); if ((threadIdx.x & 31) == 0) mbar_arrive(sb + O_BAR + 128 + (GR - 1) * 8); }
  if constexpr (GR < 4) o_groups<WG, HALF, GR + 1>(d, a, sb, n, more);
}
template <int WG, bool HALF> __device__ __forceinline__ void o_step(const uint32_t* a, uint32_t sb, uint32_t st0, int n, bool more) {
  float d[HALF ? 16 : 32];
  if (WG > 0 || n > 0) bar_sync(B_V + WG, 256);
  o_groups<WG, HALF, 0>(d, a, sb, n, more);
  wg_wait<0>();
  if ((threadIdx.x & 31) == 0) mbar_arrive(sb + O_BAR + 128 + 4 * 8);
  if ((threadIdx.x & 127) == 0) T3(WG == 0 ? 1 : WG == 1 ? 8 : 12);
  __syncwarp();
#pragma unroll(HALF ? 1 : 2)
  for (int sl = 0; sl < 2; sl++) {
    mbar_wait(sb + OB_ST + WG * 16 + sl * 8, (n & 1) ^ (WG == 0));
    if (!HALF || sl == (n >= NSEG)) {
#pragma unroll
      for (int nb = 0; nb < 4; nb++) {
        const float* r = d + (HALF ? 0 : sl * 16) + nb * 4;
        const uint32_t ad = st0 + sl * 8192 + nb * 2048;
        sts32(ad, __float_as_uint(r[0]));
        sts32(ad + 256, __float_as_uint(r[1]));
        sts32(ad ^ 32, __float_as_uint(r[2]));
        sts32((ad ^ 32) + 256, __float_as_uint(r[3]));
      }
      fence_async_smem();
    }
    bar_arrive((sl ? B_G : B_M) + WG, 160);
  }
}
template <int WG>
__device__ __forceinline__ void o_math(const Params& P, uint32_t sb) {
  const bool more = bid() < N_CHAIN + N_G + 12;
  const int lane = threadIdx.x & 31, w = (threadIdx.x >> 5) & 3, g = lane >> 2, tq = lane & 3;
  uint32_t a[96];
  mbar_wait(sb + W_BAR + WG * 8, 0);
  load_frags<24>(a, sb + WG * 49152);
  fence_async_smem();
  bar_sync(B_INIT, 416);
  load_wg<OROLE>(P, sb, false, WG, w);
  mbar_wait(sb + W_BAR + WG * 8, 1);
  if ((threadIdx.x & 127) == 0) TS(4);
  const uint32_t st0 = sb + O_ST + tq * 512 + ((w * 16 + g) ^ (tq * 8)) * 4;
#pragma unroll 1
  for (int n = 0; n < STEPS; n++) {
    if (n < LAG || n >= NSEG) o_step<WG, true>(a, sb, st0, n, more); else o_step<WG, false>(a, sb, st0, n, more);
  }
}

__device__ __forceinline__ void o_aux(const Params& P, uint32_t sb) {
  const int i = bid() - N_CHAIN - N_G, ksl = i / 3;
  const int c0 = ksl * 11 - max(ksl - 4, 0), nc = ksl < 4 ? 11 : 10;
  const int lane = threadIdx.x & 31, w = __shfl_sync(~0u, (threadIdx.x >> 5) & 3, 0);
  if (w == 0) {
    bar_sync(B_INIT, 416);
    const uint32_t* f = g_fl + FL_O + near_half(XB_F + 1, bid()) * 1024 + min((c0 & ~1) + lane, (c0 + nc - 1) | 1);
#pragma unroll 1
    for (int n = 0; n < STEPS; n++) {
      const unsigned char* src = g_oimg + (uint32_t)(((n % RING) * N_CHAIN + c0) * 8192);
      if (!NOCHAIN) wait_flags(f, n + 1);
      fence_async_global();
      if (lane == 0) T3(0);
#pragma unroll
      for (int gr = 0; gr < 5; gr++) {
        const uint32_t full = sb + O_BAR + gr * 8, bytes = ABL & 4 ? 16 : (gr < 4 ? 2 : nc - 8) * 8192;
        mbar_wait(full + 128, (n & 1) ^ 1);
        if (elect()) {
          if (n < LAG || n >= NSEG) {
            mbar_expect(full, bytes >> 1);
            for (uint32_t o = gr * 16384 + (n < LAG ? 0 : 4096); o < gr * 16384 + bytes; o += 8192) bulk_load(sb + O_RING + o, src + o, 4096, full);
          } else {
            mbar_expect(full, bytes);
            bulk_load(sb + O_RING + gr * 16384, src + gr * 16384, bytes, full);
          }
        }
      }
    }
  } else {
#pragma unroll 1
    for (int n = 0; n < STEPS; n++) {
      float* dst = g_oacc + (uint32_t)((n % ARING) * (64 * DM) + ((i % 3) * 3 + (w - 1 + ksl) % 3) * 1024);
      const bool early = w == 3 && n < NSEG;
      bar_sync(B_M + (w - 1), 160);
      if (lane == 0) {
        T3(w * 2);
        if (n < NSEG && !(ABL & 8)) { bulk_reduce(dst, sb + O_ST, 4096); bulk_reduce(dst + 16 * DM, sb + O_ST + 4096, 4096); }
        asm volatile("cp.async.bulk.commit_group;" ::: "memory");
        if (early) {
          asm volatile("cp.async.bulk.wait_group.read 0;" ::: "memory");
          mbar_arrive(sb + OB_ST);
          T3(8 + w);
          bulk_done_inc(g_fl + FL_OCNT + (n % OCRING) * 8);
          T3(w * 2 + 1);
        }
      }
      __syncwarp();
      bar_sync(B_G + (w - 1), 160);
      if (lane == 0) {
        if (n >= LAG && !(ABL & 8)) { bulk_reduce(dst + 32 * DM, sb + O_ST + 8192, 4096); bulk_reduce(dst + 48 * DM, sb + O_ST + 12288, 4096); }
        asm volatile("cp.async.bulk.commit_group;\ncp.async.bulk.wait_group.read 1;" ::: "memory");
        if (!early) mbar_arrive(sb + OB_ST + (w % 3) * 16);
        asm volatile("cp.async.bulk.wait_group.read 0;" ::: "memory");
        mbar_arrive(sb + OB_ST + (w % 3) * 16 + 8);
        if (!early) {
          T3(8 + w);
          bulk_done_inc(g_fl + FL_OCNT + (n % OCRING) * 8);
          T3(w * 2 + 1);
        }
      }
      __syncwarp();
    }
  }
}

constexpr uint32_t Y_PITCH = 1168, Y_ROWS = 16 * Y_PITCH;
template <int R> __device__ __forceinline__ void y_rows(uint32_t* y, uint32_t src, uint32_t dst, int w, int bar) {
  const int lane = threadIdx.x & 31;
#pragma unroll
  for (int k = 0; k < 2 * R + 1; k++) {
    const int op = w + k * (16 / R);
    if (k == 2 * R && w >= 4) break;
    uint32_t a, b, c, d;
    ldsm4t(a, b, c, d, src + op * 512 + (lane & 16) * 16 + (lane & 7) * 32 + (lane & 8) * 2);
    stsm4(dst + (lane & 15) * Y_PITCH + op * 32 + (lane & 16), a, b, c, d);
  }
  bar_sync(bar, 512 / R);
  const uint32_t row = dst + ((w & 6) * 2 + (w >> 3) * 2 + (w & 1)) * Y_PITCH + lane * 4;
#pragma unroll
  for (int i = 0; i < 9 * R; i++) y[i] = lds32(row + i / 9 * 2 * Y_PITCH + i % 9 * 128);
}

__device__ __forceinline__ void f_role(const Params& P, uint32_t sb) {
  const int lane = threadIdx.x & 31, w = __shfl_sync(~0u, threadIdx.x >> 5, 0), r0 = (bid() - N_CHAIN - N_G - N_O) * 16;
  if (w == 8) {
    const uint32_t* fo = g_fl + FL_OCNT + near_half(XB_F, bid()) * 1024;
    fence_async_global();
#pragma unroll 1
    for (int n = 0; n < NSEG; n++) {
      bar_sync(2, 288);
      if (elect()) {
        mbar_expect(sb + F_BAR, 36864);
        bulk_load(sb + F_XY, P.X + (size_t)(n * 32 + r0) * DM, 18432, sb + F_BAR);
        bulk_load(sb + F_XY + 18432, g_yT + (size_t)(n * 32 + r0) * DM, 18432, sb + F_BAR);
        mbar_expect(sb + F_BAR + 8, 36864);
        T3(1);
      }
      wait_flags(fo + (n % OCRING) * 8, NOCHAIN == 5 ? 0 : N_O * 3 * (n / OCRING + 1));
      fence_async_global();
      if (elect()) { bulk_load(sb + F_A, g_oacc + (uint32_t)((n % ARING) * (64 * DM) + r0 * DM), 36864, sb + F_BAR + 8); T3(0); }
    }
  } else if (w == 9) {
#pragma unroll 1
    for (int n = 0; n < NSEG; n++) {
      const uint32_t st = sb + (n & 1) * 36864;
      unsigned char* p = g_lnimg + (uint32_t)((NSEG + n) * 36864 + r0 * 128);
      bar_sync(1, 288);
      if (elect()) {
        T3(2);
#pragma unroll
        for (int i = 0; i < 9; i++) bulk_store(p + i * 4096, st + F_L + i * 2048, 2048);
        asm volatile("cp.async.bulk.commit_group;" ::: "memory");
        bulk_done_inc(g_fl + FL_F + (bid() & 1) * 8);
        T3(3);
        bulk_store(P.out + (size_t)(n * 32 + r0) * DM, st + F_X, 18432);
        asm volatile("cp.async.bulk.commit_group;\ncp.async.bulk.wait_group.read 0;" ::: "memory");
        if (n + 1 == NSEG) bulk_done_inc(g_fl + FL_F + (bid() & 1) * 8);
      }
      __syncwarp();
    }
  } else if (w < 8) {
    const uint32_t row = sb + w * 1152 + lane * 4, acc = sb + F_A + w * 256 + (lane ^ ((w & 6) * 2)) * 8;
    const uint32_t ln = sb + F_L + w * 128 + (((lane >> 2) ^ w) << 4) + (lane & 3) * 4;
#pragma unroll 1
    for (int n = -1; n < NSEG; n++) {
      const uint32_t st = (n & 1) * 36864;
      uint32_t x[18], y[18], l[18];
      if (n >= 0) mbar_wait(sb + F_BAR, n & 1);
#pragma unroll
      for (int i = 0; i < 18; i++) x[i] = lds32(row + F_XY + i / 9 * 9216 + i % 9 * 128);
      y_rows<2>(y, sb + F_XY + 18432, sb + F_Y, w, 3);
      layernorm9<2>(x, l);
#pragma unroll
      for (int i = 0; i < 18; i++) x[i] = badd2(x[i], bmul2(l[i], y[i]));
      if (n >= 0) mbar_wait(sb + F_BAR + 8, n & 1);
      if (threadIdx.x == 0 && n >= 0) T3(4);
      __syncwarp();
      uint2 a[18];
#pragma unroll
      for (int i = 0; i < 18; i++) a[i] = lds64(acc + i / 9 * 2048 + i % 9 * 4096);
#pragma unroll
      for (int i = 0; i < 18; i++) x[i] = badd2(x[i], pack2(__uint_as_float(a[i].x), __uint_as_float(a[i].y)));
      if (n + 1 < NSEG) bar_arrive(2, 288);
      layernorm9<2>(x, l);
#pragma unroll
      for (int i = 0; i < 18; i++) { x[i] = badd2(x[i], bmul2(l[i], y[i])); sts32(row + st + F_X + i / 9 * 9216 + i % 9 * 128, x[i]); }
      layernorm9<2>(x, l);
#pragma unroll
      for (int i = 0; i < 18; i++) sts32(ln + st + i / 9 * 1024 + i % 9 * 2048, l[i]);
      fence_async_smem();
      if (n >= 0) bar_sync(1, 288); else bar_sync(3, 256);
    }
  }
}

constexpr uint32_t P_CH = 147456, P_CHSZ = 12800, P_H = 4352;
static_assert(P_CH + 6 * P_CHSZ <= G_BAR, "prologue smem");

template <int N>
__device__ __forceinline__ void conv_fold(float (*acc)[4], bool hi, uint32_t mine, uint32_t theirs, int bar, int cnt) {
#pragma unroll
  for (int i = 0; i < N / 2; i++) {
    uint4 v;
    v.x = __float_as_uint(hi ? acc[i][0] : acc[i + N / 2][0]); v.y = __float_as_uint(hi ? acc[i][1] : acc[i + N / 2][1]);
    v.z = __float_as_uint(hi ? acc[i][2] : acc[i + N / 2][2]); v.w = __float_as_uint(hi ? acc[i][3] : acc[i + N / 2][3]);
    sts128(mine + i * 512, v);
  }
  bar_sync(bar, cnt);
#pragma unroll
  for (int i = 0; i < N / 2; i++) {
    const uint4 v = lds128(theirs + i * 512);
    acc[i][0] = (hi ? acc[i + N / 2][0] : acc[i][0]) + __uint_as_float(v.x); acc[i][1] = (hi ? acc[i + N / 2][1] : acc[i][1]) + __uint_as_float(v.y);
    acc[i][2] = (hi ? acc[i + N / 2][2] : acc[i][2]) + __uint_as_float(v.z); acc[i][3] = (hi ? acc[i + N / 2][3] : acc[i][3]) + __uint_as_float(v.w);
  }
}
template <int N>
__device__ __forceinline__ void conv_store(const float (*acc)[4], int tile0, uint32_t su, int d, uint32_t dd) {
  const int lane = threadIdx.x & 31, g = lane >> 2, tq = lane & 3;
#pragma unroll
  for (int i = 0; i < N; i++) {
    const uint32_t ad = su + (8 + (tile0 + i) * 8 + g) * 32 + tq * 4, sw = (g & 4) << 2;
    const uint32_t lo = badd2(movmat(pack2(acc[i][0], acc[i][1])), bmul2(lds32(ad + sw), dd));
    const uint32_t hi = badd2(movmat(pack2(acc[i][2], acc[i][3])), bmul2(lds32(ad + (sw ^ 16)), dd));
    ((uint2*)g_yT)[(((tile0 + i) * 8 + g) * DM + d) * 4 + tq] = make_uint2(lo, hi);
  }
}

__device__ __forceinline__ void prologue(const Params& P, uint32_t sb) {
  const int b = bid(), tid = threadIdx.x, lane = tid & 31, warp = tid >> 5, t0 = b * 16;
  const bool isg = b >= N_CHAIN && b < N_CHAIN + N_G;
  const int nch = isg ? 2 : b < 128 ? 6 : 0, chb = b < N_CHAIN ? b * 6 : isg ? b * 2 + 256 : b * 6 - 192;
  const uint32_t tstart = clk();
  if (tid < 288) {
    if (b < 128) {
      const int c = (tid >> 1) * 4, tt = t0 + (tid & 1) * 8;
      uint2 kr[11], vr[8];
#pragma unroll
      for (int i = 0; i < 11; i++) { const int t = tt + i - 3; kr[i] = t >= 0 ? __ldg((const uint2*)(P.K + (size_t)t * DM + c)) : make_uint2(0, 0); }
#pragma unroll
      for (int i = 0; i < 8; i++) vr[i] = __ldg((const uint2*)(P.V + (size_t)(tt + i) * DM + c));
#pragma unroll
      for (int e = 0; e < 2; e++) {
        const uint4 sh = __ldg((const uint4*)(P.shift + c * 4) + e);
        const uint32_t s0 = __byte_perm(sh.x, sh.z, 0x5410), s1 = __byte_perm(sh.x, sh.z, 0x7632);
        const uint32_t s2 = __byte_perm(sh.y, sh.w, 0x5410), s3 = __byte_perm(sh.y, sh.w, 0x7632);
        uint32_t v[8];
#pragma unroll
        for (int i = 0; i < 8; i++) {
          const uint32_t k3 = e ? kr[i].y : kr[i].x, k2 = e ? kr[i + 1].y : kr[i + 1].x, k1 = e ? kr[i + 2].y : kr[i + 2].x, k0 = e ? kr[i + 3].y : kr[i + 3].x;
          v[i] = bmul2(badd2(badd2(badd2(bmul2(k3, s3), bmul2(k2, s2)), bmul2(k1, s1)), bmul2(k0, s0)), e ? vr[i].y : vr[i].x);
        }
        *(uint4*)(g_kvT + (size_t)(c + 2 * e) * KVP + tt) =
          make_uint4(__byte_perm(v[0], v[1], 0x5410), __byte_perm(v[2], v[3], 0x5410), __byte_perm(v[4], v[5], 0x5410), __byte_perm(v[6], v[7], 0x5410));
        *(uint4*)(g_kvT + (size_t)(c + 2 * e + 1) * KVP + tt) =
          make_uint4(__byte_perm(v[0], v[1], 0x7632), __byte_perm(v[2], v[3], 0x7632), __byte_perm(v[4], v[5], 0x7632), __byte_perm(v[6], v[7], 0x7632));
      }
    }
  } else if (tid < 384) {
    const int t = tid - 288;
    for (int i = t; i < 32 * nch; i += 96) asm volatile("prefetch.global.L2 [%0];" :: "l"(P.Hk + (size_t)chb * SEQ + i * 64));
    for (int i = b * 96 + t; i < 32 * DM; i += N_CTA * 96) ((uint4*)g_oacc)[i] = make_uint4(0, 0, 0, 0);
    if (b * 96 + t < 128 * 8) g_lnflag[b * 96 + t] = 0;
    if (t == 95) sts32(sb + S_GEN, ld_acquire(g_gbar));
  }
  if (warp < 12) {
    bar_arrive(10, 416);
    if (tid == 128) TS(14);
    const int ch = 5 - (warp >> 1), sub = warp & 1, d = chb + ch;
    const uint32_t su = sb + P_CH + ch * P_CHSZ;
    if (ch < nch) {
      const uint32_t* hs = (const uint32_t*)(P.Hk + (size_t)d * SEQ);
#pragma unroll
      for (int q = sub * 32 + lane; q < 256; q += 64) {
        const uint4 c = __ldg((const uint4*)hs + q);
        const uint32_t prev = q ? __ldg(hs + 4 * q - 1) : 0u;
        sts128(su + P_H + 32 + q * 16, make_uint4(__byte_perm(c.x, prev, 0x7610), __byte_perm(c.y, c.x, 0x7610), __byte_perm(c.z, c.y, 0x7610), __byte_perm(c.w, c.z, 0x7610)));
        sts128(su + P_H + 4224 + q * 16, make_uint4(__byte_perm(c.x, 0, 0x1032), __byte_perm(c.y, 0, 0x1032), __byte_perm(c.z, 0, 0x1032), __byte_perm(c.w, 0, 0x1032)));
      }
      if (sub == 1 && lane == 0) sts32(su + P_CHSZ - 16, __bfloat16_as_ushort(P.Dk[d]) * 0x10001u);
      if (sub == 0 && lane < 20) sts128(su + (lane < 16 ? lane * 16 : P_H + (lane & 2) * 2096 + (lane & 1) * 16), make_uint4(0, 0, 0, 0));
    }
    bar_sync(11, 416);
    if (ch < nch) {
#pragma unroll
      for (int q = sub * 32 + lane; q < 256; q += 64) {
        const int row = (q >> 1) + 8;
        sts128(su + row * 32 + (((q & 1) ^ ((row >> 2) & 1)) << 4), __ldcg((const uint4*)(g_kvT + (size_t)d * KVP) + q));
      }
    }
    const int g = lane >> 2, tq = lane & 3;
    const uint32_t sh = su + P_H + (g & 1) * 4192 + (8 + (g >> 1) - tq) * 4;
    float acc[16][4];
#pragma unroll
    for (int i = 0; i < 16; i++) { acc[i][0] = acc[i][1] = acc[i][2] = acc[i][3] = 0.f; }
    auto u_addr = [&](int res) {
      const int row = 8 - res + ((lane >> 4) << 3) + (lane & 7);
      return su + row * 32 + ((((lane >> 3) & 1) ^ ((row >> 2) & 1)) << 4);
    };
    if (ch < nch) {
      bar_sync(1 + ch, 64);
      if (tid == 352) TS(11);
      if (sub) {
#pragma unroll 4
        for (int res = 0; res < 8; res++) {
          uint32_t b0, b1, b2, b3;
          ldsm4(b0, b1, b2, b3, u_addr(res));
          const uint32_t r0 = lds32(sh + res * 32);
          mma16(acc[0], r0, lds32(sh + res * 32 + 16), lds32(sh + res * 32 - 16), r0, b0, b1);
        }
        conv_store<1>(acc, 0, su, d, lds32(su + P_CHSZ - 16));
      }
    }
    bar_arrive(12, 416);
    if (isg && warp < 8) { while ((int)(clk() - tstart - S1G) < 0) __nanosleep(200); load_wg<GROLE>(P, sb, true, warp >> 2, warp & 3); }
    if (ch < nch) {
#pragma unroll 1
      for (int res = sub * 4; res < sub * 4 + 4; res++) {
        uint32_t bf[16][2];
        const uint32_t ad = u_addr(res);
#pragma unroll
        for (int f = 0; f < 16; f += 2) ldsm4(bf[f][0], bf[f][1], bf[f + 1][0], bf[f + 1][1], ad + f * 256);
#pragma unroll
        for (int k = 0; k < 16; k++) {
          const int jj = k & 1 ? k >> 1 : 15 - (k >> 1);
          const uint32_t ah = sh + (8 * jj + res) * 32;
          const uint32_t r0 = lds32(ah), r1 = lds32(ah + 16), rm = lds32(ah - 16);
#pragma unroll
          for (int i = max(jj, 1); i < 16; i++) mma16(acc[i], r0, r1, rm, r0, bf[i - jj][0], bf[i - jj][1]);
        }
      }
      bar_sync(1 + ch, 64);
      if (tid == 352) TS(12);
      const uint32_t xb = su + P_H + lane * 16, dd = lds32(su + P_CHSZ - 16);
      conv_fold<16>(acc, sub, xb + sub * 4096, xb + (sub ^ 1) * 4096, 1 + ch, 64);
      conv_store<8>(acc, sub * 8, su, d, dd);
    }
  } else {
    for (int i = b; i < 194 + MRING * 5; i += N_CTA) {
      const int n = (i - 194) / 5, r = (i - 194) % 5, blk = i < 192 ? i / 6 * 8 + i % 6 : i < 194 ? XB_F + i - 192 : XB_M + n * 8 + r;
      const uint32_t fill = i < 194 ? 0u : SENT;
#pragma unroll 1
      for (int q = tid - 384; q < 256 && warp < 15; q += 96) {
        uint4 v = make_uint4(fill, fill, fill, fill);
        if (i >= 194 && n == 0 && (r > 0 || q < 128)) {
          const bf16* m = P.mem0 + (max(r * 8 - 4, 0) + (q >> 5)) * 16 + ((q >> 1) & 1) * 8 + ((q >> 2) & 7);
          v.x = pack2(__bfloat162float(m[0]), __bfloat162float(m[DM])); v.y = pack2(__bfloat162float(m[2 * DM]), __bfloat162float(m[3 * DM]));
          v.z = pack2(__bfloat162float(m[4 * DM]), __bfloat162float(m[5 * DM])); v.w = pack2(__bfloat162float(m[6 * DM]), __bfloat162float(m[7 * DM]));
        }
        g_xb[blk * 512 + q] = v;
        g_xb[blk * 512 + 256 + q] = v;
      }
    }
    if (tid < 388) g_xb[XB_REF * 512 + (tid & 2) * 128 + (b & ~1) + (tid & 1)] = make_uint4(0, 0, 0, 0);
    else if (tid < 392 && b < N_GRP) g_xb[(b * 8 + 7) * 512 + (tid & 2) * 128 + (tid & 1)] = make_uint4(0, 0, 0, 0);
    if (warp < 15) { bar_arrive(9, 128); bar_sync(7, 96); }
    if (tid == 384) TS(8);
    if (warp == 12) {
      const bf16* w = lane < 6 ? (lane % 3 == 0 ? P.Wk : lane % 3 == 1 ? P.Wv : P.Wq) + (((b >> 5) * 2 + lane / 3) * 32 + (b & 31)) * 2048
                               : (lane < 8 ? P.Wo + (lane - 6) * (9 * 131072) : P.X) + b * 2048;
      uint32_t t = tstart + P.dly[19];
      if ((int)(clk() - t) > 0) t = clk();
#pragma unroll 1
      for (int st = 0; st < 9 && b < N_CHAIN; st++) {
#pragma unroll 1
        for (int i = 0; i < 9; i++, t += PACE) {
          wait_until(t, 0);
          if (lane == st) asm volatile("cp.async.bulk.prefetch.L2.global [%0], 4096;" :: "l"(w + i * (lane < 6 ? 262144 : 131072)) : "memory");
        }
      }
      if (lane == 0) TS(10);
    } else if (warp == 15) {
      bar_sync(10, 416);
      if (lane == 0) { grid_arrive(0); if (nch) grid_wait(0, lds32(sb + S_GEN)); }
      __syncwarp();
      bar_arrive(11, 416);
      if (lane == 0) TS(1);
      bar_sync(9, 128);
      bar_sync(12, 416);
      if (lane == 0) { TS(16); grid_arrive(2); TS(17); }
    } else if (lane == 0) {
      if (warp == 13 || (warp == 14 && b < N_GRP)) {
        uint32_t* p = (uint32_t*)(g_xb + (warp == 13 ? XB_REF * 512 + b : (b * 8 + 7) * 512));
        int votes = 0;
        for (int rep = 0; rep < 24 && abs(votes) < 7; rep++) {
          uint32_t v0, v1, c0, c1;
          asm volatile("atom.relaxed.gpu.global.add.u32 %0, [%4], 0;\n atom.relaxed.gpu.global.add.u32 %1, [%5], 0;\n"
                       "{.reg .pred p; setp.eq.u32 p, %0, 0x7ffffff3; @p trap; mov.u32 %2, %%clock; setp.eq.u32 p, %1, 0x7ffffff3; @p trap; mov.u32 %3, %%clock;}"
                       : "=&r"(v0), "=&r"(v1), "=&r"(c0), "=&r"(c1) : "l"(p + (rep & 1) * 1024), "l"(p + ((rep & 1) ^ 1) * 1024) : "memory");
          votes += ((c1 - c0 > 80u) == (rep & 1)) ? 1 : -1;
        }
        if (warp == 13) { g_side[b] = votes > 0; TS(9); } else g_near[b] = votes > 0;
      }
    }
    __syncwarp();
    if (warp > 12 && b < N_CHAIN) {
      while ((int)(clk() - tstart - S1DLY) < 0) __nanosleep(200);
      for (int k = warp - 13; k < 8; k += 3) load_wg<CHAIN>(P, sb, true, 1 - k / 4, k & 3);
    }
  }
  if (b < N_CHAIN + N_G && (warp < 8 || (isg && warp >= 12))) bar_arrive(0, 512); else bar_sync(0, 512);
  if (tid == 352) TS(2);
}

__device__ __forceinline__ void publish_y() {
  if (threadIdx.x == 383) { grid_arrive(1); TS(18); }
  __syncwarp();
}

template <int R> __device__ __forceinline__ void ln_tiles(const Params& P, uint32_t sb) {
  const int lane = threadIdx.x & 31, w = (threadIdx.x >> 5) & (16 / R - 1), half = R == 1 ? 0 : threadIdx.x >> 8, u = N_CTA - 1 - bid();
  const int first = R == 1 ? u : 46 - 2 * u + half, step = R == 1 ? 4 : 40, last = R == 1 ? 8 : 128;
  const uint32_t raw = sb + P_CH + half * (18432 + Y_ROWS), mb = sb + T_BAR + (R - 1 + half) * 8;
  const bool lead = w == 16 / R - 1 && lane == 0;
  auto load_y = [&](const bf16* src, int tile) {
    fence_async_global();
    mbar_expect(mb, 18432);
    bulk_load(raw, src + (size_t)tile * 16 * DM, 18432, mb);
  };
  uint32_t nx[9 * R];
  auto load_x = [&](int tile) {
#pragma unroll
    for (int i = 0; i < 9 * R; i++) nx[i] = __ldg((const uint32_t*)(P.X + (size_t)(tile * 16 + w + i / 9 * 8) * DM) + i % 9 * 32 + lane);
  };
  load_x(first);
  if (R == 2) {
    if (lead) { grid_wait(1, lds32(sb + S_GEN)); if (u > 3) TS(13); load_y(g_yT, first); }
    __syncwarp();
  }
#pragma unroll 1
  for (int tile = first, real = R - 1, ph = 0; tile < last; tile += real * step, real = 1, ph ^= 1) {
    uint32_t x[9 * R], l[9 * R], y[9 * R];
    const bool ts = threadIdx.x == 0 && (R == 1 ? tile == first : u > 3 && tile == first + step);
    if (ts) TS(26);
#pragma unroll
    for (int i = 0; i < 9 * R; i++) x[i] = nx[i];
    layernorm9<R>(x, l);
    if (real && tile + step < last) load_x(tile + step);
    if (R == 2 && tile == first + step && u >= N_F && w < 6) load_wg<OROLE>(P, sb, true, w >> 1, half * 2 + (w & 1));
    if (R == 1 && tile == first && lead) {
      if (real) grid_wait(2, lds32(sb + S_GEN));
      TS(13);
      load_y(real ? g_yT : P.Hk, tile);
    }
    bar_sync(13 + half, 512 / R);
    mbar_wait(mb, ph);
    if (ts) TS(28);
    y_rows<R>(y, raw, raw + 18432, w, 13 + half);
    if (ts) TS(29);
    if (lead && real && tile + step < last) { fence_async_smem(); load_y(g_yT, tile + step); }
    __syncwarp();
#pragma unroll
    for (int i = 0; i < 9 * R; i++) x[i] = badd2(x[i], bmul2(l[i], y[i]));
    layernorm9<R>(x, l);
    if (ts && l[0] != 0x12345) TS(30);
#pragma unroll
    for (int r = 0; r < R; r++) store_ln_row(0, tile * 16 + w + r * 8, l + r * 9);
    if (R == 1) {
      __syncthreads();
      if (threadIdx.x == 32 && real) { if (tile < 4) TS(19); st_release(g_lnflag + tile * 8, 1); if (tile < 4) TS(20); }
      __syncwarp();
    }
    if (ts) TS(31);
  }
  if (R == 2) {
    __syncthreads();
    if (threadIdx.x >= 506) {
      asm volatile("fence.acq_rel.gpu;" ::: "memory");
      st_relaxed_if(g_lnflag + ((first ^ (lane & 1)) + (lane - 26) / 2 * step) * 8, 1, true);
    }
    __syncwarp();
    fence_async_smem();
    if (threadIdx.x == 0) TS(15);
  }
}

__global__ void __cluster_dims__(2, 1, 1) __launch_bounds__(512, 1) k_main(const __grid_constant__ Params P) {
  extern __shared__ __align__(1024) unsigned char smem[];
  const uint32_t sb = (uint32_t)__cvta_generic_to_shared(smem);
  const int b = bid(), wg = threadIdx.x >> 7;
  if ((threadIdx.x & 127) == 0) TS(0);
  if (threadIdx.x == 480) {
    if ((sb & 0xFFFFFF) != SBASE) __trap();
    for (int i = 0; i < 6; i++) mbar_init(sb + W_BAR + i * 8, 1);
    if (b < N_CHAIN) {
      mbar_init(sb + CB_FULL, 1); mbar_init(sb + CB_FULL + 8, 1);
      mbar_init(sb + CB_REF, 1);
      mbar_init(sb + CB_SX, 1); mbar_init(sb + CB_OX, 1); mbar_init(sb + CB_XX, 1); mbar_init(sb + CB_Q, 1); mbar_init(sb + CB_VF, 1); mbar_init(sb + CB_VF + 8, 1);
      sts32(sb + C_BAD, 0);
      for (int i = 0; i < 11; i++) mbar_init(sb + CB_M + i * 8, i == 0 ? 5 : i == 5 ? 2 : 1);
    } else if (b < N_CHAIN + N_G) {
      for (int i = 0; i < 9; i++) { mbar_init(sb + G_BAR + i * 8, 2); mbar_init(sb + G_BAR + 128 + i * 8, 8); }
    } else if (b < N_CHAIN + N_G + N_O) {
      for (int i = 0; i < 5; i++) { mbar_init(sb + O_BAR + i * 8, 1); mbar_init(sb + O_BAR + 128 + i * 8, 12); }
      for (int i = 0; i < 6; i++) mbar_init(sb + OB_ST + i * 8, 1);
    } else {
      mbar_init(sb + F_BAR, 1); mbar_init(sb + F_BAR + 8, 1);
    }
    asm volatile("fence.mbarrier_init.release.cluster;" ::: "memory");
    fence_async_smem();
  }
  __syncwarp();
  asm volatile("barrier.cluster.arrive.relaxed.aligned;" ::: "memory");
  prologue(P, sb);
  asm volatile("barrier.cluster.wait.aligned;" ::: "memory");
  fence_async_smem();
  if (b >= N_CHAIN + N_G) publish_y();
  if (b >= 128) ln_tiles<1>(P, sb);
  if (b >= N_CHAIN + N_G) ln_tiles<2>(P, sb);
  if ((threadIdx.x & 127) == 0) TS(3);
  if (b < N_CHAIN) {
    if (wg < 2) { reg_inc<200>(); chain_proj(P, sb); }
    else if (wg == 2) { reg_dec<ATTR>(); publish_y(); chain_attn(P, sb); }
    else { reg_dec<112 - ATTR>(); chain_aux(P, sb); }
  } else if (NOBULK) {
    if (b < N_CHAIN + N_G) publish_y();
    {
      if (wg == 0) {
        float d[4] = {0.f, 0.f, 0.f, 0.f};
        for (int n = 0; n < STEPS - 1; n++) {
          const uint32_t* f = g_fl + FL_TICK;
          uint32_t x;
          do { for (int k = 0; k < 16; k++) mma16(d, 0, 0, 0, 0, 0, 0); asm volatile("ld.relaxed.gpu.global.u32 %0, [%1];" : "=r"(x) : "l"(f) : "memory"); } while ((x >> 24) <= n);
          const int q = (b - N_CHAIN) * 4 + (threadIdx.x >> 5);
          if (n + 5 >= MRING && q < 80) fill16((uint4*)g_mimg + (uint32_t)(((n + 5) % MRING) * 4096 + q * 32 + (threadIdx.x & 31)), SENT);
        }
        if (d[0] == 1.f) P.out[0] = __float2bfloat16(0.f);
      }
    }
  } else if (b < N_CHAIN + N_G) {
    if (wg == 0) { reg_inc<232>(); g_math<0>(P, sb); }
    else if (wg == 1) { reg_inc<232>(); g_math<1>(P, sb); }
    else if (wg == 2) { reg_dec<24>(); bar_arrive(15, 192); publish_y(); g_aux(P, sb); }
    else { reg_dec<24>(); g_load(P, sb); }
  } else if (b < N_CHAIN + N_G + N_O) {
    if (wg == 0) { reg_inc<160>(); o_math<0>(P, sb); }
    else if (wg == 1) { reg_inc<160>(); o_math<1>(P, sb); }
    else if (wg == 2) { reg_inc<160>(); o_math<2>(P, sb); }
    else { reg_dec<32>(); o_aux(P, sb); }
  } else {
    f_role(P, sb);
  }
}

}

extern "C" void kernel_launch(void* const* d_in, const int* in_sizes, int n_in, void* d_out, int out_size) {
  typedef CUresult (*Encode)(CUtensorMap*, CUtensorMapDataType, cuuint32_t, void*, const cuuint64_t*, const cuuint64_t*, const cuuint32_t*, const cuuint32_t*,
                             CUtensorMapInterleave, CUtensorMapSwizzle, CUtensorMapL2promotion, CUtensorMapFloatOOBfill);
  static Encode encode = nullptr;
  if (!encode) cudaGetDriverEntryPoint("cuTensorMapEncodeTiled", (void**)&encode, cudaEnableDefault);
  Params P;
  for (int i = 0; i < 11; i++) {
    const bool wo = i == 6 || i == 7;
    const cuuint64_t cols = wo ? DM : HD, rows = HD + DM - cols, pitch = cols * 2;
    const cuuint64_t dim[4][5] = {{cols, 2, 8, 2, 18}, {cols, 16, 1, 1, rows / 16}, {cols, 2, 4, 4, rows / 32}, {64, 16, 64, 2, 18}};
    const cuuint64_t stride[4][4] = {{8 * pitch, pitch, 16 * pitch, 32 * pitch}, {pitch, pitch, pitch, 16 * pitch},
                                     {pitch, 8 * pitch, 2 * pitch, 32 * pitch}, {pitch, 128, 16 * pitch, 32 * pitch}};
    const cuuint32_t box[4][5] = {{64, 2, 8, 1, 18}, {64, 16, 1, 1, 1}, {64, 2, 4, 2, 1}, {64, 16, 2, 1, 18}}, one[5] = {1, 1, 1, 1, 1};
    const int k = i < 3 ? 0 : i < 7 ? 1 : i < 8 ? 2 : 3;
    encode(&P.map[i], CU_TENSOR_MAP_DATA_TYPE_BFLOAT16, 5, d_in[wo ? 11 : 8 + (i & 7) % 3], dim[k], stride[k], box[k], one,
           CU_TENSOR_MAP_INTERLEAVE_NONE, CU_TENSOR_MAP_SWIZZLE_128B, CU_TENSOR_MAP_L2_PROMOTION_L2_128B, CU_TENSOR_MAP_FLOAT_OOB_FILL_NONE);
  }
  P.X = (const bf16*)d_in[0]; P.K = (const bf16*)d_in[1]; P.V = (const bf16*)d_in[2];
  P.shift = (const bf16*)d_in[3]; P.Hk = (const bf16*)d_in[4]; P.Dk = (const bf16*)d_in[5];
  P.mem0 = (const bf16*)d_in[7];
  P.Wq = (const bf16*)d_in[8]; P.Wk = (const bf16*)d_in[9]; P.Wv = (const bf16*)d_in[10]; P.Wo = (const bf16*)d_in[11];
  P.out = (bf16*)d_out;
  for (int i = 0; i < 24; i++) P.dly[i] = h_dly[i];
  cudaFuncSetAttribute(k_main, cudaFuncAttributeMaxDynamicSharedMemorySize, SMEM_BYTES);
  k_main<<<N_CTA, 512, SMEM_BYTES>>>(P);
}
```

```cpp
#include <cuda.h>
#include <cuda_runtime.h>
#include <cuda_bf16.h>
#include <stdint.h>

namespace {

typedef __nv_bfloat16 bf16;

constexpr int SEQ = 2048, DM = 576, HD = 4096, NSEG = 64;
#define PLACE 1
#define LAGV 7
constexpr int LAG = LAGV, STEPS = NSEG + LAG, RING = 8, QRING = 4;
static_assert(LAG < RING, "ring");
constexpr int N_CHAIN = 64, N_G = 48, N_O = 18, N_F = 2;
constexpr uint32_t SBASE = 1024;
constexpr uint32_t SENT = 0xFFFFFFFFu;
constexpr int SPIN_MAX = 1 << 22;

__device__ __forceinline__ uint32_t bid() {
  uint32_t b;
  asm volatile("mov.u32 %0, %%ctaid.x;" : "=r"(b));
  return b < 6 ? b + 106 : b < 8 ? b + 122 : b < 114 ? b - 8 : b < 130 ? b - 2 : b;
}
__device__ __forceinline__ uint32_t chain_id() { return blockIdx.x - (PLACE ? 8 : 0); }
constexpr int KVP = SEQ + 64;
__device__ __align__(1024) bf16 g_kvT[DM * KVP];
__device__ __align__(1024) bf16 g_yT[DM * SEQ];
__device__ __align__(1024) unsigned char g_lnimg[2 * NSEG * 9 * 4096];
__device__ __align__(1024) unsigned char g_qkv[QRING * N_CHAIN * 24576];
__device__ __align__(1024) unsigned char g_oimg[RING * N_CHAIN * 8192];
constexpr int ARING = 16;
static_assert(ARING >= LAG + 9, "accumulator ring");
__device__ __align__(1024) float g_oacc[ARING * 64 * DM];
constexpr int MRING = LAG + 4, N_GRP = 32 + MRING + 1;
constexpr int XB_M = 256, XB_F = XB_M + MRING * 8, XB_REF = XB_F + 2, N_CTA = N_CHAIN + N_G + N_O + N_F;
__device__ __align__(65536) uint4 g_xb[N_GRP * 4096];
#define g_mimg ((uint32_t*)(g_xb + XB_M * 512))
__device__ uint32_t g_near[N_GRP];
__device__ uint32_t g_side[N_CTA];
__device__ __align__(128) uint32_t g_gbar[3 * 32];
constexpr int FL_G = 0, FL_F = 96 * 8, FL_OCNT = FL_F + 2 * 8, OCRING = 16, FL_TICK = 992, FL_O = 2048, FL_SYNC = FL_O + 128;
static_assert(FL_OCNT + OCRING * 8 <= FL_TICK, "flag block");
#define g_fl ((uint32_t*)(g_xb + XB_F * 512))
__device__ __align__(1024) uint32_t g_lnflag[128 * 8];
#define TS(slot)

#define OTURN 2
#define LOCK0 3
#define FASTG 0
#define NOBULK 0
#define WFENCE 0
#define QPOS 0
#define VE 4
#define OGAP 2
#define NOCHAIN 0
#define BFENCE 2
#define ABL 0
#define ATTR 80
#define CNT(slot, tries)
#define T3(slot)
#define TR(slot)
#define TRV(slot, val)
#define TRD(slot, dep)
#define TRSYNC()
#define TRDUMP(n)
#define CLK(t) "{.reg .b64 x; .reg .b32 h; mov.u64 x, %%clock64; mov.b64 {" t ", h}, x;}"
__device__ __forceinline__ uint32_t clk() { uint32_t t; asm volatile(CLK("%0") : "=r"(t) :: "memory"); return t; }
__device__ __forceinline__ void wait_until(uint32_t t0, uint32_t d) {
  asm volatile("{.reg .pred p; .reg .u32 t;\n"
               "W: " CLK("t") " sub.u32 t, t, %0; setp.lt.s32 p, t, 0; @p bra.uni W;}"
               :: "r"(t0 + d) : "memory");
}
__device__ __forceinline__ uint32_t pack2(float lo, float hi) {
  uint32_t r; asm("cvt.rn.bf16x2.f32 %0, %1, %2;" : "=r"(r) : "f"(hi), "f"(lo)); return r;
}
__device__ __forceinline__ float bf_lo(uint32_t v) { return __uint_as_float(v << 16); }
__device__ __forceinline__ float bf_hi(uint32_t v) { return __uint_as_float(v & 0xFFFF0000u); }

__device__ __forceinline__ uint4 ld_relaxed4(const void* p) {
  uint4 v; asm volatile("ld.relaxed.gpu.global.v4.u32 {%0,%1,%2,%3}, [%4];" : "=r"(v.x), "=r"(v.y), "=r"(v.z), "=r"(v.w) : "l"(p) : "memory"); return v;
}
__device__ __forceinline__ void st_b128(void* p, uint32_t a, uint32_t b, uint32_t c, uint32_t d) {
  asm volatile("{.reg .b128 v; mov.b128 v, {%1,%2,%3,%4}; st.relaxed.gpu.global.b128 [%0], v;}" :: "l"(p), "r"(a), "r"(b), "r"(c), "r"(d) : "memory");
}
__device__ __forceinline__ void reload_b128(uint4& v, const void* p, uint32_t again) {
  asm volatile("{.reg .pred p; .reg .b128 v; setp.ne.u32 p, %5, 0; mov.b128 v, {%0,%1,%2,%3};\n"
               "@p ld.relaxed.gpu.global.b128 v, [%4]; mov.b128 {%0,%1,%2,%3}, v;}"
    : "+r"(v.x), "+r"(v.y), "+r"(v.z), "+r"(v.w) : "l"(p), "r"(again) : "memory");
}
__device__ __forceinline__ void reload4(uint4& v, const void* p, uint32_t again) {
  asm volatile("{.reg .pred p; setp.ne.u32 p, %5, 0; @p ld.relaxed.gpu.global.v4.u32 {%0,%1,%2,%3}, [%4];}"
    : "+r"(v.x), "+r"(v.y), "+r"(v.z), "+r"(v.w) : "l"(p), "r"(again) : "memory");
}
__device__ __forceinline__ void st_relaxed4(void* p, uint32_t a, uint32_t b, uint32_t c, uint32_t d) {
  asm volatile("st.relaxed.gpu.global.v4.u32 [%0], {%1,%2,%3,%4};" :: "l"(p), "r"(a), "r"(b), "r"(c), "r"(d) : "memory");
}
__device__ __forceinline__ void st_relaxed_if(void* p, uint32_t a, bool on) {
  asm volatile("{.reg .pred p; setp.ne.u32 p, %2, 0; @p st.relaxed.gpu.global.u32 [%0], %1;}" :: "l"(p), "r"(a), "r"((uint32_t)on) : "memory");
}
__device__ __forceinline__ uint32_t ld_acquire(const uint32_t* p) {
  uint32_t v; asm volatile("ld.acquire.gpu.global.u32 %0, [%1];" : "=r"(v) : "l"(p) : "memory"); return v;
}
__device__ __forceinline__ void st_release(uint32_t* p, uint32_t v) {
  asm volatile("st.release.gpu.global.u32 [%0], %1;" :: "l"(p), "r"(v) : "memory");
}
__device__ __forceinline__ void bulk_reduce(float* dst, uint32_t src, uint32_t bytes) {
  asm volatile("cp.reduce.async.bulk.global.shared::cta.bulk_group.add.f32 [%0], [%1], %2;" :: "l"(dst), "r"(src), "r"(bytes) : "memory");
}
__device__ __forceinline__ void bulk_done_inc(uint32_t* p) {
  asm volatile("cp.async.bulk.wait_group 0;\n"
               "fence.proxy.async.global;\nfence.release.gpu;\n"
               "red.relaxed.gpu.global.add.u32 [%0], 1;\nred.relaxed.gpu.global.add.u32 [%0+4096], 1;" :: "l"(p) : "memory");
}
__device__ __forceinline__ void flag_release(uint32_t* p, uint32_t v) {
  asm volatile("fence.release.gpu;\nst.relaxed.gpu.global.u32 [%0], %1;\nst.relaxed.gpu.global.u32 [%0+4096], %1;" :: "l"(p), "r"(v) : "memory");
}
__device__ __forceinline__ void spin_guard(int& it) {
  asm volatile("{.reg .pred p; add.s32 %0, %0, 1; setp.gt.s32 p, %0, %1; @p trap;}" : "+r"(it) : "n"(SPIN_MAX));
}
__device__ __forceinline__ void wait_flag(const uint32_t* p, uint32_t v) {
  int it = 0;
  while (ld_acquire(p) < v) spin_guard(it);
}
__device__ __forceinline__ void wait_flags(const uint32_t* p, uint32_t v) {
  int it = 0;
  while (true) {
    uint32_t x; asm volatile("ld.relaxed.gpu.global.u32 %0, [%1];" : "=r"(x) : "l"(p) : "memory");
    if (__all_sync(~0u, x >= v)) break;
    spin_guard(it);
  }
  asm volatile("fence.acquire.gpu;" ::: "memory");
}
__device__ __forceinline__ uint32_t timer_offset() {
  uint32_t g0, g;
  asm volatile("mov.u32 %0, %%globaltimer_lo;" : "=r"(g0) :: "memory");
  do { asm volatile("mov.u32 %0, %%globaltimer_lo;" : "=r"(g) :: "memory"); } while (g == g0);
  return (g >> 5) * 58 - clk();
}
__device__ __forceinline__ void grid_arrive(int i) {
  asm volatile("red.release.gpu.global.add.u32 [%0], %1;" :: "l"(g_gbar + i * 32), "r"(bid() ? 1u : 257u - N_CTA) : "memory");
}
__device__ __forceinline__ void grid_wait(int i, uint32_t gen) {
  int it = 0;
  while (((ld_acquire(g_gbar + i * 32) ^ gen) >> 8) == 0) spin_guard(it);
}
__device__ __forceinline__ bool elect() {
  uint32_t r; asm volatile("{.reg .pred p; elect.sync _|p, -1; selp.u32 %0, 1, 0, p;}" : "=r"(r)); return r;
}
__device__ __forceinline__ void bar_sync(int id, int cnt) { asm volatile("bar.sync %0, %1;" :: "r"(id), "r"(cnt) : "memory"); }
__device__ __forceinline__ void bar_arrive(int id, int cnt) { asm volatile("bar.arrive %0, %1;" :: "r"(id), "r"(cnt) : "memory"); }
template <int id, int cnt> __device__ __forceinline__ void bar_arrive_after(uint32_t a, uint32_t b) {
  asm volatile("{.reg .pred p; setp.ne.u32 p, %2, 0xfff12345; setp.ne.and.u32 p, %3, 0xfff12345, p; @p bar.arrive %0, %1;}" :: "n"(id), "n"(cnt), "r"(a), "r"(b) : "memory");
}
template <int id, int cnt> __device__ __forceinline__ void bar_sync_after(uint32_t a) {
  asm volatile("{.reg .pred p; setp.ne.u32 p, %2, 0xfff12345; @p bar.sync %0, %1;}" :: "n"(id), "n"(cnt), "r"(a) : "memory");
}
__device__ __forceinline__ void fence_async_smem() { asm volatile("fence.proxy.async.shared::cta;" ::: "memory"); }
__device__ __forceinline__ void fence_async_global() { asm volatile("fence.proxy.async.global;" ::: "memory"); }
__device__ __forceinline__ void mbar_init(uint32_t mb, int cnt) { asm volatile("mbarrier.init.shared::cta.b64 [%0], %1;" :: "r"(mb), "r"(cnt) : "memory"); }
__device__ __forceinline__ void mbar_arrive(uint32_t mb) { asm volatile("mbarrier.arrive.shared::cta.b64 _, [%0];" :: "r"(mb) : "memory"); }
__device__ __forceinline__ void mbar_arrive_after(uint32_t mb, uint32_t a, uint32_t lane) {
  asm volatile("{.reg .pred p; setp.ne.u32 p, %1, 0xfff12345; setp.eq.and.u32 p, %2, 0, p; @p mbarrier.arrive.shared::cta.b64 _, [%0];}" :: "r"(mb), "r"(a), "r"(lane) : "memory");
}
__device__ __forceinline__ void mbar_expect(uint32_t mb, uint32_t bytes) {
  asm volatile("mbarrier.arrive.expect_tx.shared::cta.b64 _, [%0], %1;" :: "r"(mb), "r"(bytes) : "memory");
}
__device__ __forceinline__ void mbar_wait_guard(uint32_t mb, uint32_t parity) {
  uint32_t ok; int it = 0;
  while (true) {
    asm volatile("{.reg .pred p; mbarrier.try_wait.parity.shared::cta.b64 p, [%1], %2; selp.u32 %0, 1, 0, p;}" : "=r"(ok) : "r"(mb), "r"(parity) : "memory");
    if (ok) break;
    spin_guard(it);
  }
}
__device__ __forceinline__ void mbar_wait(uint32_t mb, uint32_t parity) {
  asm volatile("{.reg .pred p;\nW: mbarrier.try_wait.parity.shared::cta.b64 p, [%0], %1;\n@!p bra W;}" :: "r"(mb), "r"(parity) : "memory");
}
__device__ __forceinline__ void bulk_load(uint32_t dst, const void* src, uint32_t bytes, uint32_t mb) {
  asm volatile("cp.async.bulk.shared::cluster.global.mbarrier::complete_tx::bytes [%0], [%1], %2, [%3];" :: "r"(dst), "l"(src), "r"(bytes), "r"(mb) : "memory");
}
__device__ __forceinline__ void bulk_store(void* dst, uint32_t src, uint32_t bytes) {
  asm volatile("cp.async.bulk.global.shared::cta.bulk_group [%0], [%1], %2;" :: "l"(dst), "r"(src), "r"(bytes) : "memory");
}
__device__ __forceinline__ void cp_async16(uint32_t dst, const void* src) {
  asm volatile("cp.async.cg.shared.global [%0], [%1], 16;" :: "r"(dst), "l"(src) : "memory");
}
__device__ __forceinline__ void cp_async_wait_all() { asm volatile("cp.async.wait_all;" ::: "memory"); }
__device__ __forceinline__ uint32_t mapa(uint32_t a, uint32_t rank) {
  uint32_t r; asm("mapa.shared::cluster.u32 %0, %1, %2;" : "=r"(r) : "r"(a), "r"(rank)); return r;
}
__device__ __forceinline__ void st_async4(uint32_t dst, float a, float b, float c, float d, uint32_t mb) {
  asm volatile("st.async.shared::cluster.mbarrier::complete_tx::bytes.v4.f32 [%0], {%1,%2,%3,%4}, [%5];" :: "r"(dst), "f"(a), "f"(b), "f"(c), "f"(d), "r"(mb) : "memory");
}
__device__ __forceinline__ void st_async2(uint32_t dst, float a, float b, uint32_t mb) {
  asm volatile("st.async.shared::cluster.mbarrier::complete_tx::bytes.v2.f32 [%0], {%1,%2}, [%3];" :: "r"(dst), "f"(a), "f"(b), "r"(mb) : "memory");
}
__device__ __forceinline__ void st_async1(uint32_t dst, uint32_t a, uint32_t mb) {
  asm volatile("st.async.shared::cluster.mbarrier::complete_tx::bytes.u32 [%0], %1, [%2];" :: "r"(dst), "r"(a), "r"(mb) : "memory");
}
__device__ __forceinline__ uint4 lds128(uint32_t a) {
  uint4 v; asm volatile("ld.shared.v4.u32 {%0,%1,%2,%3}, [%4];" : "=r"(v.x), "=r"(v.y), "=r"(v.z), "=r"(v.w) : "r"(a) : "memory"); return v;
}
__device__ __forceinline__ uint2 lds64(uint32_t a) {
  uint2 v; asm volatile("ld.shared.v2.u32 {%0,%1}, [%2];" : "=r"(v.x), "=r"(v.y) : "r"(a) : "memory"); return v;
}
__device__ __forceinline__ uint32_t lds32(uint32_t a) {
  uint32_t v; asm volatile("ld.shared.u32 %0, [%1];" : "=r"(v) : "r"(a) : "memory"); return v;
}
__device__ __forceinline__ void sts128(uint32_t a, uint4 v) {
  asm volatile("st.shared.v4.u32 [%0], {%1,%2,%3,%4};" :: "r"(a), "r"(v.x), "r"(v.y), "r"(v.z), "r"(v.w) : "memory");
}
__device__ __forceinline__ void sts64(uint32_t a, uint32_t x, uint32_t y) {
  asm volatile("st.shared.v2.u32 [%0], {%1,%2};" :: "r"(a), "r"(x), "r"(y) : "memory");
}
__device__ __forceinline__ void sts32(uint32_t a, uint32_t x) { asm volatile("st.shared.u32 [%0], %1;" :: "r"(a), "r"(x) : "memory"); }
__device__ __forceinline__ void ldsm4(uint32_t& r0, uint32_t& r1, uint32_t& r2, uint32_t& r3, uint32_t a) {
  asm volatile("ldmatrix.sync.aligned.m8n8.x4.shared.b16 {%0,%1,%2,%3}, [%4];" : "=r"(r0), "=r"(r1), "=r"(r2), "=r"(r3) : "r"(a) : "memory");
}
__device__ __forceinline__ void ldsm4t(uint32_t& r0, uint32_t& r1, uint32_t& r2, uint32_t& r3, uint32_t a) {
  asm volatile("ldmatrix.sync.aligned.m8n8.x4.trans.shared.b16 {%0,%1,%2,%3}, [%4];" : "=r"(r0), "=r"(r1), "=r"(r2), "=r"(r3) : "r"(a) : "memory");
}
__device__ __forceinline__ void stsm4(uint32_t a, uint32_t r0, uint32_t r1, uint32_t r2, uint32_t r3) {
  asm volatile("stmatrix.sync.aligned.m8n8.x4.shared.b16 [%0], {%1,%2,%3,%4};" :: "r"(a), "r"(r0), "r"(r1), "r"(r2), "r"(r3) : "memory");
}
__device__ __forceinline__ uint32_t movmat(uint32_t a) {
  uint32_t d; asm volatile("movmatrix.sync.aligned.m8n8.trans.b16 %0, %1;" : "=r"(d) : "r"(a)); return d;
}
__device__ __forceinline__ void mma16(float* d, uint32_t a0, uint32_t a1, uint32_t a2, uint32_t a3, uint32_t b0, uint32_t b1) {
  asm volatile("mma.sync.aligned.m16n8k16.row.col.f32.bf16.bf16.f32 {%0,%1,%2,%3}, {%4,%5,%6,%7}, {%8,%9}, {%0,%1,%2,%3};"
    : "+f"(d[0]), "+f"(d[1]), "+f"(d[2]), "+f"(d[3]) : "r"(a0), "r"(a1), "r"(a2), "r"(a3), "r"(b0), "r"(b1));
}
__device__ __forceinline__ void mma8(float* d, uint32_t a0, uint32_t a1, uint32_t b0) {
  asm volatile("mma.sync.aligned.m16n8k8.row.col.f32.bf16.bf16.f32 {%0,%1,%2,%3}, {%4,%5}, {%6}, {%0,%1,%2,%3};"
    : "+f"(d[0]), "+f"(d[1]), "+f"(d[2]), "+f"(d[3]) : "r"(a0), "r"(a1), "r"(b0));
}
__device__ __forceinline__ float rcp(float x) { float r; asm("rcp.approx.ftz.f32 %0, %1;" : "=f"(r) : "f"(x)); return r; }
__device__ __forceinline__ float ex2(float x) { float r; asm("ex2.approx.ftz.f32 %0, %1;" : "=f"(r) : "f"(x)); return r; }

__host__ __device__ constexpr uint64_t mkdesc(uint32_t off, uint32_t lbo, uint32_t sbo, uint32_t swz) {
  return (uint64_t)((SBASE + off) >> 4) | ((uint64_t)(lbo >> 4) << 16) | ((uint64_t)(sbo >> 4) << 32) | ((uint64_t)swz << 62);
}
__host__ __device__ constexpr uint64_t desc_sw128(uint32_t off) { return mkdesc(off, 16, 1024, 1); }
__host__ __device__ constexpr uint64_t desc_n16(uint32_t off) { return mkdesc(off, 256, 128, 0); }
__host__ __device__ constexpr uint64_t desc_m(uint32_t off) { return mkdesc(off, 16, 256, 3); }

__host__ __device__ constexpr uint64_t desc_sw64(uint32_t off) { return mkdesc(off, 16, 512, 2); }

__device__ __forceinline__ void wg_fence() { asm volatile("wgmma.fence.sync.aligned;" ::: "memory"); }
__device__ __forceinline__ void wg_commit() { asm volatile("wgmma.commit_group.sync.aligned;" ::: "memory"); }
template <int N> __device__ __forceinline__ void wg_wait() { asm volatile("wgmma.wait_group.sync.aligned %0;" :: "n"(N) : "memory"); }

#define ACC8(d) "+f"(d[0]), "+f"(d[1]), "+f"(d[2]), "+f"(d[3]), "+f"(d[4]), "+f"(d[5]), "+f"(d[6]), "+f"(d[7])
#define ACC32(d) ACC8(d), ACC8((d + 8)), ACC8((d + 16)), ACC8((d + 24))
#define R8 "{%0,%1,%2,%3,%4,%5,%6,%7}"
#define R32 "{%0,%1,%2,%3,%4,%5,%6,%7,%8,%9,%10,%11,%12,%13,%14,%15,%16,%17,%18,%19,%20,%21,%22,%23,%24,%25,%26,%27,%28,%29,%30,%31}"
template <int SD> __device__ __forceinline__ void wg_rs16(float* d, const uint32_t* a, uint64_t db) {
  asm volatile("wgmma.mma_async.sync.aligned.m64n16k16.f32.bf16.bf16 " R8 ", {%8,%9,%10,%11}, %12, %13, 1, 1, 1;"
    : ACC8(d) : "r"(a[0]), "r"(a[1]), "r"(a[2]), "r"(a[3]), "l"(db), "n"(SD));
}
template <int SD> __device__ __forceinline__ void wg_ss16(float* d, uint64_t da, uint64_t db) {
  asm volatile("wgmma.mma_async.sync.aligned.m64n16k16.f32.bf16.bf16 " R8 ", %8, %9, %10, 1, 1, 1, 1;"
    : ACC8(d) : "l"(da), "l"(db), "n"(SD));
}
template <int SD, uint64_t DA, uint64_t DB> __device__ __forceinline__ void wg_ss16o(float* d, uint32_t oa, uint32_t ob) {
  asm volatile("{.reg .b32 x, y; .reg .b64 a, b; add.u32 x, %8, %10; add.u32 y, %9, %12; mov.b64 a, {x, %11}; mov.b64 b, {y, %13};\n"
               "wgmma.mma_async.sync.aligned.m64n16k16.f32.bf16.bf16 " R8 ", a, b, %14, 1, 1, 1, 1;}"
    : ACC8(d) : "r"(oa), "r"(ob), "n"((uint32_t)DA), "n"((uint32_t)(DA >> 32)), "n"((uint32_t)DB), "n"((uint32_t)(DB >> 32)), "n"(SD));
}
template <int SD> __device__ __forceinline__ void wg_rs64(float* d, const uint32_t* a, uint64_t db) {
  asm volatile("wgmma.mma_async.sync.aligned.m64n64k16.f32.bf16.bf16 " R32 ", {%32,%33,%34,%35}, %36, %37, 1, 1, 0;"
    : ACC32(d) : "r"(a[0]), "r"(a[1]), "r"(a[2]), "r"(a[3]), "l"(db), "n"(SD));
}
template <int SD> __device__ __forceinline__ void wg_ss64(float* d, uint64_t da, uint64_t db) {
  asm volatile("wgmma.mma_async.sync.aligned.m64n64k16.f32.bf16.bf16 " R32 ", %32, %33, %34, 1, 1, 1, 0;"
    : ACC32(d) : "l"(da), "l"(db), "n"(SD));
}
#define WG_RSO(NAME, SHAPE, REGS, ACC, A, TB) \
template <int SD, uint64_t DB> __device__ __forceinline__ void NAME(float* d, uint32_t a0, uint32_t a1, uint32_t a2, uint32_t a3, uint32_t ob) { \
  asm volatile("{.reg .b64 b; mov.b64 b, {" A(4) ", " A(5) "};\nwgmma.mma_async.sync.aligned." SHAPE ".f32.bf16.bf16 " REGS \
               ", {" A(0) "," A(1) "," A(2) "," A(3) "}, b, " A(6) ", 1, 1, " TB ";}" \
    : ACC(d) : "r"(a0), "r"(a1), "r"(a2), "r"(a3), "r"(ob + (uint32_t)DB), "n"((uint32_t)(DB >> 32)), "n"(SD)); \
}
#define ACC4(d) "+f"(d[0]), "+f"(d[1]), "+f"(d[2]), "+f"(d[3])
#define ACC16(d) ACC8(d), ACC8((d + 8))
#define OP4(i) OP4_##i
#define OP4_0 "%4"
#define OP4_1 "%5"
#define OP4_2 "%6"
#define OP4_3 "%7"
#define OP4_4 "%8"
#define OP4_5 "%9"
#define OP4_6 "%10"
#define OP16(i) OP16_##i
#define OP16_0 "%16"
#define OP16_1 "%17"
#define OP16_2 "%18"
#define OP16_3 "%19"
#define OP16_4 "%20"
#define OP16_5 "%21"
#define OP16_6 "%22"
#define OP32(i) OP32_##i
#define OP32_0 "%32"
#define OP32_1 "%33"
#define OP32_2 "%34"
#define OP32_3 "%35"
#define OP32_4 "%36"
#define OP32_5 "%37"
#define OP32_6 "%38"
WG_RSO(wg_rs8o, "m64n8k16", "{%0,%1,%2,%3}", ACC4, OP4, "1")
#define R16 "{%0,%1,%2,%3,%4,%5,%6,%7,%8,%9,%10,%11,%12,%13,%14,%15}"
WG_RSO(wg_rs32o, "m64n32k16", R16, ACC16, OP16, "1")
WG_RSO(wg_rs64o, "m64n64k16", R32, ACC32, OP32, "0")
WG_RSO(wg_rs32k, "m64n32k16", R16, ACC16, OP16, "0")
template <uint64_t DA, uint64_t DB> __device__ __forceinline__ void wg_ss32k(float* d, uint32_t ob) {
  asm volatile("{.reg .b64 b; mov.b64 b, {%17, %18};\nwgmma.mma_async.sync.aligned.m64n32k16.f32.bf16.bf16 " R16 ", %16, b, 1, 1, 1, 1, 0;}"
    : ACC16(d) : "l"(DA), "r"(ob + (uint32_t)DB), "n"((uint32_t)(DB >> 32)));
}
template <int N> __device__ __forceinline__ void reg_inc() { asm volatile("setmaxnreg.inc.sync.aligned.u32 %0;" :: "n"(N)); }
template <int N> __device__ __forceinline__ void reg_dec() { asm volatile("setmaxnreg.dec.sync.aligned.u32 %0;" :: "n"(N)); }
__device__ __forceinline__ void cluster_sync() {
  asm volatile("barrier.cluster.arrive.relaxed.aligned;\nbarrier.cluster.wait.aligned;" ::: "memory");
}

template <int KS>
__device__ __forceinline__ void load_frags(uint32_t* a, uint32_t src) {
  const int lane = threadIdx.x & 31, w = (threadIdx.x >> 5) & 3;
  const int k = ((lane >> 4) << 3) + (lane & 7), u = w * 2 + ((lane >> 3) & 1);
  const uint32_t base = src + k * 128 + ((u ^ (k & 7)) << 4);
#pragma unroll
  for (int ks = 0; ks < KS; ks++) ldsm4t(a[ks * 4], a[ks * 4 + 1], a[ks * 4 + 2], a[ks * 4 + 3], base + ks * 2048);
}

__device__ __forceinline__ uint32_t badd2(uint32_t a, uint32_t b) { uint32_t r; asm("add.rn.bf16x2 %0, %1, %2;" : "=r"(r) : "r"(a), "r"(b)); return r; }
__device__ __forceinline__ uint32_t bsub2(uint32_t a, uint32_t b) { uint32_t r; asm("sub.rn.bf16x2 %0, %1, %2;" : "=r"(r) : "r"(a), "r"(b)); return r; }
__device__ __forceinline__ uint32_t bmul2(uint32_t a, uint32_t b) { uint32_t r; asm("mul.rn.bf16x2 %0, %1, %2;" : "=r"(r) : "r"(a), "r"(b)); return r; }
__device__ __forceinline__ uint32_t bfma2(uint32_t a, uint32_t b, uint32_t c) { uint32_t r; asm("fma.rn.bf16x2 %0, %1, %2, %3;" : "=r"(r) : "r"(a), "r"(b), "r"(c)); return r; }
template <int R> __device__ __forceinline__ void layernorm9(const uint32_t* x, uint32_t* o) {
  const uint32_t ones = 0x3F803F80u;
  float a[R][3][4], q[R], s[R];
#pragma unroll
  for (int i = 0; i < 9 * R; i++) {
    float* d = a[i % R][i / R % 3];
    if (i < 3 * R) d[0] = d[1] = d[2] = d[3] = 0.f;
    mma8(d, x[i % R * 9 + i / R], ones, x[i % R * 9 + i / R]);
  }
#pragma unroll
  for (int r = 0; r < R; r++) {
    q[r] = threadIdx.x & 4 ? a[r][0][1] + a[r][1][1] + a[r][2][1] : a[r][0][0] + a[r][1][0] + a[r][2][0];
    s[r] = (a[r][0][2] + a[r][0][3]) + (a[r][1][2] + a[r][1][3]) + (a[r][2][2] + a[r][2][3]);
  }
#pragma unroll
  for (int r = 0; r < R; r++) { q[r] += __shfl_xor_sync(~0u, q[r], 4); s[r] += __shfl_xor_sync(~0u, s[r], 1); }
#pragma unroll
  for (int r = 0; r < R; r++) { q[r] += __shfl_xor_sync(~0u, q[r], 9); s[r] += __shfl_xor_sync(~0u, s[r], 2); }
#pragma unroll
  for (int r = 0; r < R; r++) q[r] = __shfl_sync(~0u, q[r], 0) + __shfl_sync(~0u, q[r], 18);
#pragma unroll
  for (int r = 0; r < R; r++) {
    const float mean = s[r] * (1.f / DM), var = fmaxf(fmaf(q[r], 1.f / DM, -mean * mean), 0.f);
    float sd;
    asm("sqrt.approx.ftz.f32 %0, %1;" : "=f"(sd) : "f"(bf_lo(pack2(bf_lo(pack2(var, 0.f)) + 1e-5f, 0.f))));
    const float inv = rcp(bf_lo(pack2(sd, 0.f)));
    const uint32_t mb = pack2(mean, mean), hi = pack2(inv, inv), lo = pack2(inv - bf_lo(hi), inv - bf_lo(hi));
#pragma unroll
    for (int i = r * 9; i < r * 9 + 9; i++) {
      const uint32_t d = bsub2(x[i], mb);
      o[i] = bfma2(d, hi, bmul2(d, lo));
    }
  }
}
__device__ __forceinline__ void store_ln_row(int layer, int tok, const uint32_t* o) {
  const int lane = threadIdx.x & 31, r = tok & 31;
  unsigned char* p = g_lnimg + (size_t)(layer * NSEG + (tok >> 5)) * (9 * 4096) + r * 128 + (((lane >> 2) ^ (r & 7)) << 4) + (lane & 3) * 4;
#pragma unroll
  for (int i = 0; i < 9; i++) *(uint32_t*)(p + i * 4096) = o[i];
}
struct Params { CUtensorMap map[11]; const bf16 *X, *K, *V, *shift, *Hk, *Dk, *mem0, *Wq, *Wk, *Wv, *Wo; bf16* out; uint32_t dly[24]; };
#define PACE P.dly[20]
#define S1G P.dly[21]
#define S1DLY P.dly[22]
#define DLYS P.dly[0]
#define DLYW P.dly[1]
#define KLATE P.dly[2]
#define DLYQ P.dly[3]
#define DLYK P.dly[4]
#define DLYG P.dly[5]
#define KWIN P.dly[6]
#define KMIN P.dly[7]
uint32_t h_dly[24] = {900, 950, 100, 40, 3540, 4200, 2750, 1300, 1600, 1700, 1840, 2140, 2290, 2420, 2900, 3030, 3220, 3350, 3510, 6000, 165, 12000, 18000};

constexpr uint32_t C_W = 0, C_M = 147456, C_KV = C_M + 18432, C_OS = C_KV + 24576, C_QM = C_KV + 32768, C_KM = C_QM + 2048,
                   C_VM = C_KM + 2048, C_OI = C_VM + 2048, C_SX = C_OI + 4096, C_KM2 = C_SX + 2560, C_VM2 = C_KM2 + 128,
                   C_KV2 = C_KM2 + 2048, C_Q = C_KV2 + 8192, C_BAR = C_Q + 8192;
constexpr uint32_t CB_FULL = C_BAR, CB_REF = C_BAR + 16, CB_SX = C_BAR + 32, CB_OX = C_BAR + 40, CB_XX = C_BAR + 48, CB_Q = C_BAR + 56, C_BAD = C_BAR + 64, W_BAR = C_BAR + 80, T_BAR = W_BAR + 24, S_GEN = C_BAR + 128, C_REF = C_BAR + 132, CB_VF = C_BAR + 144, CB_M = C_BAR + 160, CB_MV = C_BAR + 200;
constexpr uint32_t G_W = 0, G_RING = 147456, G_W2 = G_RING + 9 * 8192, G_BAR = G_W2 + 8192;
constexpr uint32_t O_W = 0, O_RING = 3 * 40960, O_ST = O_RING + 11 * 8192, O_BAR = O_ST + 16384, OB_ST = O_BAR + 64;
constexpr uint32_t F_A = 0, F_XY = 36864, F_L = F_XY + 36864, F_X = F_L + 18432, F_Y = F_L + 2 * 36864, F_BAR = C_BAR;
constexpr uint32_t SMEM_BYTES = C_BAR + 256;
static_assert(G_BAR + 256 <= SMEM_BYTES && O_BAR + 256 <= SMEM_BYTES && F_BAR + 16 <= SMEM_BYTES && SMEM_BYTES <= 232448, "smem map");
enum { B_INIT = 1, B_M, B_QK, B_S, B_V, B_O, B_X, B_WG0, B_WG1, B_WG2, B_G, B_OE, B_T, B_R };

__device__ __forceinline__ uint4 pack_partial(const float* d, uint32_t tag) {
  uint32_t x;
  asm("lop3.b32 %0, %1, 1, %2, 0xb8;" : "=r"(x) : "r"(pack2(d[0], d[1])), "r"(tag));
  return make_uint4(x, pack2(d[4], d[5]), pack2(d[2], d[3]), pack2(d[6], d[7]));
}
__device__ __forceinline__ void store_partial(uint4* p, const uint4& v) { st_b128(p, v.x, v.y, v.z, v.w); }
__device__ __forceinline__ void gather_reduce(const uint32_t* p, uint32_t* dst, uint32_t m0, bool shared, uint32_t tag, uint32_t lane, uint32_t sb, int n, int TS0) {
  int tries = 0;
  float u, v;
  bool bad;
  TR(TS0);
  do {
    uint32_t x[16];
#pragma unroll
    for (int i = 0; i < 16; i++) asm volatile("ld.relaxed.gpu.global.u32 %0, [%1];" : "=r"(x[i]) : "l"(p + i * 64) : "memory");
    tries++;
    float a[2] = {bf_lo(x[0]), bf_lo(x[1])}, b[2] = {bf_hi(x[0]), bf_hi(x[1])};
    uint32_t t = 0;
#pragma unroll
    for (int i = 2; i < 16; i++) { a[i & 1] += bf_lo(x[i]); b[i & 1] += bf_hi(x[i]); }
#pragma unroll
    for (int i = 0; i < 16; i += 4)
      asm("{.reg .b32 y, z; lop3.b32 y, %1, %2, %5, 0x7e; lop3.b32 z, %3, %4, %5, 0x7e; lop3.b32 %0, %0, y, z, 0xfe;}"
          : "+r"(t) : "r"(x[i]), "r"(x[i + 1]), "r"(x[i + 2]), "r"(x[i + 3]), "r"(tag));
    u = a[0] + a[1]; v = b[0] + b[1];
    bad = __any_sync(~0u, (t & 1) && !(lane & 3));
    if (shared) { u += __shfl_xor_sync(~0u, u, 8); v += __shfl_xor_sync(~0u, v, 8); }
    u += __shfl_xor_sync(~0u, u, 16);
    v += __shfl_xor_sync(~0u, v, 16);
    st_relaxed_if(dst, n < LAG && (lane & 1) ? m0 : pack2(u, v), !bad);
  } while (bad);
  TR(TS0 + 3); TRV(TS0 + 2, tries);
  CNT((TS0 - 16) >> 2, tries);
}
__device__ __forceinline__ uint32_t sent_bad(const uint4& v) { return max(max(v.x, v.y), max(v.z, v.w)) == SENT; }

__host__ __device__ constexpr int o_ks(int s) { return s & (s < 8 ? 3 : 7); }
__host__ __device__ constexpr bool o_reg(int s) { return s < 8 ? (s & 3) != 3 : !(s & 1); }
__host__ __device__ constexpr int o_slot(int s) { return s < 8 ? (o_reg(s) ? s - (s >> 2) : s >> 2) : s & 1 ? (s - 5) >> 1 : (s + 4) >> 1; }
__device__ __forceinline__ int g_unit(int wg) {
  const int i = bid() - N_CHAIN;
  return i < 32 ? wg * 64 + i : 2 * i - 32 + wg;
}
__device__ __forceinline__ uint32_t pinned(uint32_t v) { return __shfl_sync(~0u, v, threadIdx.x & 31); }
template <class T> __device__ __forceinline__ T* pinned(T* p) { return (T*)__shfl_sync(~0u, (unsigned long long)p, threadIdx.x & 31); }
enum { CHAIN, GROLE, OROLE };
template <int ROLE, bool SYNC> __device__ __forceinline__ void load_box(const Params& P, uint32_t sb, bool regs, int wg, int i, uint32_t mb, bool on) {
  const int b = bid();
  int map, col = 0, ks = 0, c2 = 0, c3 = 0;
  uint32_t dst = wg * 73728;
  if (ROLE == CHAIN) {
    const int k = i - 1, st = regs ? (k < 6 ? k + k / 3 : 2 * k - 4) : k < 2 ? 4 * k + 3 : 2 * k + 5;
    dst += i ? (17 + i) * 2048 : 0;
    if (wg || i == 0) { map = wg + i; col = b * 64; c3 = !regs; }
    else if (!regs && k >= 14) { map = 6; ks = b * 4 + k - 14; }
    else { map = 6; col = 64 + (st < 8 ? (st >> 2) * 64 : (st >> 3) * 128 + (b & 1) * 64); ks = (b * 4) ^ o_ks(st); }
  } else if (ROLE == GROLE) {
    const int q = g_unit(wg);
    map = ((q >> 5) + 1) % 3;
    if (i) { map += 3; col = (q & 31) * 128 + (i - 1) * 64; ks = 34; dst = G_W2 + wg * 4096 + (i - 1) * 2048; }
    else { map += 8; c2 = (q & 31) * 2; c3 = !regs; }
  } else {
    const int o = b - N_CHAIN - N_G, ksl = o / 3;
    map = 7; col = ((o % 3) * 3 + (wg + ksl) % 3) * 64; dst = (wg * (regs ? 24 : 20) + i) * 2048;
    ks = (ksl * 11 - max(ksl - 4, 0)) * 4 + (regs ? i / 3 * 5 + i % 3 * 2 : i < 16 ? i / 2 * 5 + 1 + i % 2 * 2 : i + 24);
    c3 = (ks & 1) * 2; ks >>= 1;
  }
  if (SYNC) { col = pinned(col); ks = pinned(ks); bar_sync(B_WG0 + wg, 256); }
  if (on) asm volatile("cp.async.bulk.tensor.5d.shared::cluster.global.tile.mbarrier::complete_tx::bytes [%0], [%1, {%2, %3, %4, %5, %6}], [%7];"
               :: "r"(sb + dst), "l"(&P.map[map]), "r"(col), "r"(0), "r"(c2), "r"(c3), "r"(ks), "r"(mb) : "memory");
}
template <int ROLE, bool SYNC = false> __device__ __forceinline__ void load_wg(const Params& P, uint32_t sb, bool regs, int wg, int quarter) {
  const int i = (threadIdx.x & 31) * 4 + quarter;
  const int n = ROLE == CHAIN ? 36 : ROLE == GROLE ? (regs ? 38 : 36) : regs ? 24 : bid() < N_CHAIN + N_G + 12 ? 20 : 16;
  load_box<ROLE, SYNC>(P, sb, regs, wg, i, sb + W_BAR + wg * 8, i < (ROLE == CHAIN ? (wg ? 2 : 19) : ROLE == GROLE ? n - 35 : n));
  if (i == 0) mbar_expect(sb + W_BAR + wg * 8, n * 2048);
  __syncwarp();
}
__device__ __forceinline__ uint32_t near_half(uint32_t blk, uint32_t reader) {
  return __ldcg(g_near + (blk >> 3)) ^ (~blk & 1) ^ __ldcg(g_side + (blk >> 3)) ^ __ldcg(g_side + reader);
}

__device__ __forceinline__ uint32_t opaque_tid() { uint32_t t; asm volatile("mov.u32 %0, %%tid.x;" : "=r"(t)); return t; }
__device__ __forceinline__ void m_fetch(uint32_t sb, uint32_t src, uint32_t b, uint32_t mb) {
  bulk_load(sb + C_M + (b ? b * 4096 - 2048 : 0), (const unsigned char*)g_mimg + ((src ^ ((b & 1) * 4096)) + b * 8192), b ? 4096 : 2048, mb);
}
__device__ __forceinline__ uint32_t m_probe(uint32_t lane) { return lane * 32 + (lane & 4) * 4 + (lane >> 3) * 4; }
__device__ __forceinline__ uint32_t m_max(uint32_t a, uint32_t b) {
  return max(max(lds32(a), lds32(a + 1024)), max(lds32(b), lds32(b + 1024)));
}
template <int S0, int N> __device__ __forceinline__ void o_steps(float* d, const uint32_t* a) {
  constexpr int SD = o_ks(S0) != 0;
  if constexpr (o_reg(S0)) wg_rs16<SD>(d, a + (18 + o_slot(S0)) * 4, desc_n16(C_OI + o_ks(S0) * 512));
  else wg_ss16<SD>(d, desc_sw128(C_W + (18 + o_slot(S0)) * 2048), desc_n16(C_OI + o_ks(S0) * 512));
  if constexpr (N > 1) o_steps<S0 + 1, N - 1>(d, a);
}
template <int BASE, int KS, int N> __device__ __forceinline__ void m_steps(float* d, const uint32_t* a, uint32_t oa) {
  wg_rs16<KS != 0>(d, a + (BASE + KS / 2) * 4, desc_m(C_M + KS * 512));
  wg_ss16o<1, desc_sw128(C_W + (BASE + KS / 2) * 2048), desc_m(C_M + KS * 512 + 512)>(d, oa, 0);
  if constexpr (N > 2) m_steps<BASE, KS + 2, N - 2>(d, a, oa);
}

__device__ __forceinline__ void chain_proj(const Params& P, uint32_t sb) {
  const uint32_t c = chain_id(), h = c >> 1, j = c & 1, wid = __shfl_sync(~0u, threadIdx.x >> 5, 0), wg = wid >> 2, w = wid & 3;
  const uint32_t t = threadIdx.x & 127, lane = pinned(t & 31), mine = pinned(sb + t * 16), rb = mapa(sb, j ^ 1);
  const uint32_t theirs = pinned(rb + C_KM2 + w * 512 + lane * 4), oa = wg * 4608;
  uint32_t a[144];
  mbar_wait(sb + W_BAR + wg * 8, 0);
  if (threadIdx.x == 0) TS(23);
  load_frags<36>(a, sb + C_W + wg * 73728);
  fence_async_smem();
  bar_arrive(B_WG0 + wg, 256);
  if (threadIdx.x == 0) TS(24);
  bar_sync(B_WG2, 384);
  const uint32_t round = min(w, 2u) + (wg ? 0 : 3), gdly = P.dly[8 + round], ps = t >> 2, pf = j * 16 + (ps >> 1);
  uint4* const dsts = pinned(g_xb + (ps * 4096 + near_half(ps * 8, ps * 2) * 256 + c * 4 + (t & 3)));
  uint4* const dstf = pinned(g_xb + (pf * 4096 + 512 + near_half(pf * 8 + 1, pf * 2) * 256 + h * 8 + (t & 7)));
  const uint32_t* const gsrc = (const uint32_t*)g_xb + (h * 16384 + min(w, 2u) * 4096 + near_half(h * 8 + !wg, h * 2) * 1024 +
                               (wg ? (lane & 24) * 2 + j * 8 + (lane & 7) : 2048 + (lane & 16) * 2 + j * 16 + (lane & 15)));
  uint32_t* gdst = g_mimg + (16384 + (lane >> 4) * 1024 + (lane & 2) * 4 +
                   (wg ? (round ? 1536 + round * 512 : 0) + h * 16 + ((lane ^ (c >> 2)) & 1) * 4 + j * 2 + ((lane >> 2) & 1)
                       : (round - 1) * 2048 + c * 16 + ((lane ^ (c >> 1)) & 1) * 4 + ((lane >> 2) & 3)));
  const uint32_t m0 = __ldcg(gdst - 16384);
  mbar_wait(sb + W_BAR + wg * 8, 1);
  bar_sync(B_INIT, 256);
  if ((threadIdx.x & 127) == 0) TS(4);

  uint32_t ring = 1;
#pragma unroll 1
  for (int n = 0; n < STEPS; n++) {
    float d[8], e[8];
    uint32_t redo = n + 1;
    do {
      mbar_wait(sb + CB_M, n & 1);
      wg_fence();
      m_steps<0, 0, 4>(d, a, oa);
      if (VE && wg) m_steps<18, 0, 4>(e, a, 4608);
      wg_commit();
      if (wid == 0) TR(8);
      mbar_wait(sb + CB_M + 8, n & 1);
      wg_fence();
      m_steps<0, 4, 8>(d, a, oa);
      if (VE > 4 && wg) m_steps<18, 4, (VE > 4 ? VE - 4 : 2)>(e, a, 4608);
      wg_commit();
      mbar_wait(sb + CB_MV, n & 1);
      redo = lds32(sb + C_BAD) == redo ? SENT : 0;
    } while (redo);
    mbar_wait(sb + CB_MV + 8, n & 1);
    wg_fence();
    m_steps<0, 12, 8>(d, a, oa);
    wg_commit();
    mbar_wait(sb + CB_MV + 16, n & 1);
    wg_fence();
    m_steps<0, 20, 8>(d, a, oa);
    wg_commit();
    mbar_wait(sb + CB_MV + 24, n & 1);
    wg_fence();
    m_steps<0, 28, 8>(d, a, oa);
    wg_commit();
    wg_wait<0>();
    if (w == 0) TR(6 + wg);
    const uint32_t f0 = pack2(d[0], d[1]), f1 = pack2(d[4], d[5]), f2 = pack2(d[2], d[3]), f3 = pack2(d[6], d[7]);
    stsm4(mine + C_QM + wg * 2048, f0, f1, f2, f3);
    bar_arrive(B_QK, 416);
    const uint32_t tag = (n & 1) ^ 1;
    if (wg) {
      if (n + 1 < STEPS) bar_sync(B_S, 256);
      wg_fence();
      m_steps<18, VE, 36 - VE>(e, a, 4608);
      wg_commit();
      const uint32_t k0 = j ? f0 : f1, k1 = j ? f2 : f3;
      wg_wait<0>();
      if (w == 0) TR(11);
      const uint32_t v0 = pack2(e[0], e[1]), v1 = pack2(e[4], e[5]), v2 = pack2(e[2], e[3]), v3 = pack2(e[6], e[7]);
      stsm4(mine + C_VM, v0, v1, v2, v3);
      bar_arrive(B_V, 256);
      st_async1(theirs, k0, rb + CB_XX);
      st_async1(theirs + 256, k1, rb + CB_XX);
      st_async1(theirs + 128, j ? v0 : v1, rb + CB_XX);
      st_async1(theirs + 384, j ? v2 : v3, rb + CB_XX);
      if (n + 1 == STEPS) break;
      bar_sync(B_O, 256);
      if (!WFENCE) fence_async_smem();
      wg_fence();
#pragma unroll
      for (int ks = 0; ks < 4; ks++) {
        if (ks == 0) wg_ss16<0>(d, desc_sw128(C_W + 32 * 2048), desc_n16(C_OI));
        else wg_ss16<1>(d, desc_sw128(C_W + (32 + ks) * 2048), desc_n16(C_OI + ks * 512));
      }
      wg_commit();
      bar_arrive(B_X, 256);
      if (w == 0) TR(0);
      wg_wait<0>();
      store_partial(dsts, pack_partial(d, tag));
      bar_arrive(B_M, 160);
      if (w == 0) TR(1);
    } else {
      if (n + 1 == STEPS) break;
      bar_sync(B_X, 256);
      wg_fence();
      o_steps<0, 4>(d, a);
      wg_commit();
      o_steps<4, 4>(e, a);
      wg_commit();
      wg_wait<1>();
      store_partial(dsts + 1024, pack_partial(d, tag));
      if (w == 0) TR(2);
      if (OGAP == 0) { wg_fence(); o_steps<8, 4>(d, a); wg_commit(); wg_wait<1>(); } else wg_wait<0>();
      store_partial(dsts + 2048, pack_partial(e, tag));
      if (w == 0) TR(3);
      wg_fence();
      if (OGAP) o_steps<8, 4>(d, a);
      if (OGAP < 2) o_steps<16, 4>(e, a);
      wg_commit();
      bar_sync(B_T, 256);
      if (w == 0) { TRV(61, 0); TR(12); }
      wg_fence();
      o_steps<12, 4>(d, a);
      wg_commit();
      if (OGAP == 2) o_steps<16, 4>(e, a);
      o_steps<20, 4>(e, a);
      wg_commit();
      wg_wait<1>();
      store_partial(dstf, pack_partial(d, tag));
      if (w == 0) TR(4);
      wg_fence();
      o_steps<24, 8>(d, a);
      wg_commit();
      wg_wait<1>();
      store_partial(dstf + 1024, pack_partial(e, tag));
      bar_arrive(B_OE, 256);
      if (w == 0) TR(5);
      wg_wait<0>();
      store_partial(dstf + 2048, pack_partial(d, tag));
      if (w == 0) TR(15);
    }
    if (w < 3) {
      mbar_wait(sb + CB_REF, n & 1);
      wait_until(lds32(sb + C_REF), gdly);
      gather_reduce(gsrc, gdst, m0, wg, tag, lane, sb, n, 16 + round * 4);
      if (++ring == MRING) { ring = 0; gdst -= MRING * 16384; }
      gdst += 16384;
    }
  }
}

template <int KS> __device__ __forceinline__ void x_scores(float* s, float* sm, const uint4* q, uint32_t ok, uint32_t om) {
  wg_rs32o<1, desc_sw64(C_KV + KS * 1024)>(s, q[KS].x, q[KS].y, q[KS].z, q[KS].w, ok);
  wg_rs8o<1, desc_n16(C_KM + KS * 512)>(sm, q[KS].x, q[KS].y, q[KS].z, q[KS].w, om);
  if constexpr (KS < 3) x_scores<KS + 1>(s, sm, q, ok, om);
}

__device__ __forceinline__ void chain_attn(const Params& P, uint32_t sb) {
  const int c = chain_id(), j = c & 1;
  const int tid = threadIdx.x, lane = tid & 31, w = __shfl_sync(~0u, (tid >> 5) & 3, 0);
  const int l = w >> 1, u = w & 1;
  const uint32_t rb = mapa(sb, j ^ 1);
  const float sc = 0.08838834764831845f * 1.4426950408889634f;
  const uint32_t ones = 0x3F803F80u;
  const uint32_t km_off = C_KM + (lane >> 3) * 256 + l * 128 + (lane & 7) * 16;
  const uint32_t qm_off = C_QM + (lane >> 4) * 256 + l * 128 + (lane & 7) * 16;
  const uint32_t kv_off = C_KV + l * 4096 + (lane & 15) * 64 + (((lane >> 4) ^ (u * 2) ^ ((lane >> 1) & 3)) << 4);

  load_wg<CHAIN, true>(P, sb, false, 1, w);
  if (lane == 0) mbar_arrive(sb + CB_M);
#pragma unroll 1
  for (int n = 0; n < STEPS; n++) {
    const uint32_t kvb = sb + kv_off + (n & 1) * 16384;
    if (w == 0 && elect()) { mbar_expect(sb + CB_SX, 2560); mbar_expect(sb + CB_OX, 2048); mbar_expect(sb + CB_XX, 2048); }
    mbar_wait(sb + CB_FULL + (n & 1) * 8, (n >> 1) & 1);
    if (n < 3 && tid == 256) TS(n ? 20 + n : 5);
    __syncwarp();
    {
      uint32_t km[8];
      uint4 kx[8];
#pragma unroll
      for (int i = 0; i < 8; i++) ldsm4t(kx[i].x, kx[i].y, kx[i].z, kx[i].w, (kvb ^ ((i & 1) * 32)) + (i >> 1) * 1024);
      mbar_wait(sb + CB_VF, n & 1);
      if (w == 1) TRD(60, kx[7].x);
      bar_sync(B_QK, 416);
      if (n + 1 == STEPS) {
        bar_sync(B_V, 256);
      } else {
      uint32_t qm[16];
#pragma unroll
      for (int ks = 0; ks < 4; ks++) ldsm4t(qm[4 * ks], qm[4 * ks + 1], qm[4 * ks + 2], qm[4 * ks + 3], sb + qm_off + ks * 512);
      ldsm4t(km[0], km[1], km[2], km[3], sb + km_off);
      ldsm4t(km[4], km[5], km[6], km[7], sb + km_off + 1024);
      float s[5][4];
      uint4 vx[4];
#pragma unroll
      for (int i = 0; i < 5; i++) { s[i][0] = s[i][1] = s[i][2] = s[i][3] = 0.f; }
#pragma unroll
      for (int ks = 0; ks < 4; ks++) {
        const uint32_t* q = qm + 4 * ks;
        if (ks == 1 || ks == 2) {
#pragma unroll
          for (int i = 2 * ks - 2; i < 2 * ks; i++) ldsm4(vx[i].x, vx[i].y, vx[i].z, vx[i].w, ((sb + kv_off) ^ ((i & 1) * 32)) + 8192 + (2 * u + (i >> 1)) * 1024);
        }
        mma16(s[1], q[0], q[1], q[2], q[3], kx[2 * ks].x, kx[2 * ks].y);
        mma16(s[2], q[0], q[1], q[2], q[3], kx[2 * ks].z, kx[2 * ks].w);
        mma16(s[0], q[0], q[1], q[2], q[3], km[2 * ks], km[2 * ks + 1]);
        mma16(s[3], q[0], q[1], q[2], q[3], kx[2 * ks + 1].x, kx[2 * ks + 1].y);
        mma16(s[4], q[0], q[1], q[2], q[3], kx[2 * ks + 1].z, kx[2 * ks + 1].w);
      }
      const uint32_t sx = C_SX + l * 1280;
      st_async4(rb + sx + u * 512 + lane * 16, s[1][0], s[1][1], s[2][0], s[2][1], rb + CB_SX);
      st_async1(rb + sx + 1024 + u * 128 + lane * 4, __float_as_uint(u ? s[0][1] : s[0][0]), rb + CB_SX);
      bar_arrive_after<B_S, 256>(__float_as_uint(s[3][0]), __float_as_uint(s[4][0]));
      mbar_wait(sb + CB_SX, n & 1);
      const uint4 p0 = lds128(sb + sx + u * 512 + lane * 16), p1 = lds128(sb + sx + (u ^ 1) * 512 + lane * 16);
      const uint2 p2 = make_uint2(lds32(sb + sx + 1024 + lane * 4), lds32(sb + sx + 1152 + lane * 4));
      float t[10] = {s[0][0] + __uint_as_float(p2.x), s[0][1] + __uint_as_float(p2.y),
                     s[1][0] + __uint_as_float(p0.x), s[1][1] + __uint_as_float(p0.y),
                     s[2][0] + __uint_as_float(p0.z), s[2][1] + __uint_as_float(p0.w),
                     s[3][0] + __uint_as_float(p1.x), s[3][1] + __uint_as_float(p1.y),
                     s[4][0] + __uint_as_float(p1.z), s[4][1] + __uint_as_float(p1.w)};
      float mx = fmaxf(fmaxf(fmaxf(fmaxf(t[2], t[3]), fmaxf(t[4], t[5])), fmaxf(fmaxf(t[6], t[7]), fmaxf(t[8], t[9]))), fmaxf(t[0], t[1]));
      mx = fmaxf(fmaxf(mx, __shfl_xor_sync(~0u, mx, 1)), fmaxf(__shfl_xor_sync(~0u, mx, 2), __shfl_xor_sync(~0u, mx, 3)));
      const float ms = -mx * sc;
#pragma unroll
      for (int i = 0; i < 10; i++) t[i] = ex2(fmaf(t[i], sc, ms));
      uint32_t p[5];
#pragma unroll
      for (int i = 0; i < 5; i++) p[i] = pack2(t[2 * i], t[2 * i + 1]);
      p[1] |= (p[0] & p[3] & p[4]) & 0x80008000u;
      float o[2][4], z[4] = {0.f, 0.f, 0.f, 0.f};
      mma16(z, ones, ones, ones, ones, p[1], p[2]);
#pragma unroll
      for (int i = 0; i < 2; i++) {
        o[i][0] = o[i][1] = o[i][2] = o[i][3] = 0.f;
        mma16(o[i], vx[2 * i].x, vx[2 * i].y, vx[2 * i].z, vx[2 * i].w, p[1], p[2]);
      }
      mma16(z, ones, ones, ones, ones, p[3], p[4]);
#pragma unroll
      for (int i = 0; i < 2; i++) mma16(o[i], vx[2 * i + 1].x, vx[2 * i + 1].y, vx[2 * i + 1].z, vx[2 * i + 1].w, p[3], p[4]);
      mma8(z, ones, ones, p[0]);
      bar_sync_after<B_V, 256>(p[1]);
      ldsm4(km[0], km[1], km[2], km[3], sb + km_off + (C_VM - C_KM) + u * 1024);
      mma8(o[0], km[0], km[1], p[0]);
      mma8(o[1], km[2], km[3], p[0]);
      const float i0 = rcp(z[0]), i1 = rcp(z[1]);
      const uint32_t oo = C_OI + u * 1024 + l * 128 + lane * 4;
      uint32_t ow[4];
#pragma unroll
      for (int i = 0; i < 2; i++) { ow[2 * i] = pack2(o[i][0] * i0, o[i][1] * i1); ow[2 * i + 1] = pack2(o[i][2] * i0, o[i][3] * i1); }
      stsm4(sb + C_OI + u * 1024 + l * 128 + (lane >> 3) * 256 + (lane & 7) * 16, ow[0], ow[1], ow[2], ow[3]);
      if (WFENCE) fence_async_smem();
      bar_arrive(B_O, 256);
#pragma unroll
      for (int i = 0; i < 4; i++) st_async1(rb + oo + 2048 + i * 256, ow[i], rb + CB_OX);
      }
    }
    {
      const uint32_t lane = opaque_tid() & 31, own = ((n & 1) * 16384 + j * 4096) >> 4;
      float s[16], sm[4];
#pragma unroll
      for (int i = 0; i < 16; i++) s[i] = sm[i & 3] = 0.f;
      {
        uint4 q[4];
        mbar_wait(sb + CB_Q, n & 1);
        auto load_q = [&]() {
#pragma unroll
          for (int ks = 0; ks < 4; ks++) q[ks] = lds128(sb + C_Q + (ks >> 1) * 4096 + w * 1024 + (ks & 1) * 512 + lane * 16);
        };
        if (QPOS == 0) load_q();
        mbar_wait(sb + CB_XX, n & 1);
        if (n + 1 < STEPS) mbar_wait(sb + CB_OX, n & 1);
        fence_async_smem();
        if (n + 1 < STEPS) bar_arrive(B_T, 256);
        if (QPOS == 1) load_q();
        if (n + 1 < STEPS) bar_sync(B_OE, 256);
        if (QPOS == 2) load_q();
        if (w == 1) { TRV(61, 0); TR(9); }
#pragma unroll 1
        for (uint32_t hf = 0; hf < 2; hf++) {
          wg_fence();
          x_scores<0>(s, sm, q, hf ? (C_KV2 - C_KV) >> 4 : own, hf ? (C_KM2 - C_KM) >> 4 : j * 8);
          wg_commit();
          wg_wait<0>();
#pragma unroll
          for (int ks = 0; ks < 4; ks++) asm volatile("mov.b32 %0, %1; mov.b32 %2, %3;" : "+r"(q[ks].x), "+r"(q[ks].y), "+r"(q[ks].z), "+r"(q[ks].w));
        }
      }
      const float neg = -1e9f * 11.313708498984761f;
      const int lim = 8 * (w - (int)(lane & 3)) + (int)(lane >> 2);
      float t[10] = {sm[0], sm[1]};
#pragma unroll
      for (int i = 0; i < 8; i++) t[2 + i] = i > lim ? neg : s[(i >> 1) * 4 + (i & 1)];
      float mx = fmaxf(fmaxf(fmaxf(fmaxf(t[2], t[3]), fmaxf(t[4], t[5])), fmaxf(fmaxf(t[6], t[7]), fmaxf(t[8], t[9]))), fmaxf(t[0], t[1]));
      mx = fmaxf(fmaxf(mx, __shfl_xor_sync(~0u, mx, 1)), fmaxf(__shfl_xor_sync(~0u, mx, 2), __shfl_xor_sync(~0u, mx, 3)));
      const float ms = -mx * sc;
#pragma unroll
      for (int i = 0; i < 10; i++) t[i] = ex2(fmaf(t[i], sc, ms));
      uint32_t p[5];
#pragma unroll
      for (int i = 0; i < 5; i++) p[i] = pack2(t[2 * i], t[2 * i + 1]);
      float z = ((t[0] + t[1]) + (t[2] + t[3])) + ((t[4] + t[5]) + (t[6] + t[7])) + (t[8] + t[9]);
      const uint32_t row = sb + C_OS + w * 1024 + (lane >> 2) * 128 + (((lane & 3) ^ (lane >> 2)) << 4);
#pragma unroll 1
      for (uint32_t hf = 0; hf < 2; hf++) {
        float o[32];
        const uint32_t vo = hf ? (C_KV2 + 4096 - C_KV - 8192) >> 4 : j * 256;
        wg_fence();
        wg_rs64o<0, desc_sw64(C_KV + 8192)>(o, p[1], p[1], p[2], p[2], vo);
        wg_rs64o<1, desc_sw64(C_KV + 8192 + 32)>(o, p[3], p[3], p[4], p[4], vo);
        wg_rs64o<1, mkdesc(C_VM, 128, 256, 0)>(o, p[0], p[0], 0, 0, hf ? (C_VM2 - C_VM) >> 4 : j * 8);
        wg_commit();
        if (hf) {
          if (elect()) mbar_arrive(sb + CB_M);
        } else {
          z += __shfl_xor_sync(~0u, z, 1);
          z = rcp(z + __shfl_xor_sync(~0u, z, 2));
        }
        wg_wait<0>();
#pragma unroll
        for (int qq = 0; qq < 2; qq++) {
          const float* r = o + 16 * qq;
          sts128((row ^ (qq * 64)) + hf * 4096,
                 make_uint4(pack2(r[0] * z, r[1] * z), pack2(r[4] * z, r[5] * z), pack2(r[8] * z, r[9] * z), pack2(r[12] * z, r[13] * z)));
        }
      }
      bar_arrive(B_G, 160);
      if (n + 1 < STEPS) bar_arrive(B_R, 160);
      if (w == 1) TR(10);
    }
  }
  if ((threadIdx.x & 127) == 0) TS(6);
}

__device__ __forceinline__ void chain_aux(const Params& P, uint32_t sb) {
  const uint32_t c = chain_id(), j = c & 1, lane = threadIdx.x & 31, w = __shfl_sync(~0u, (threadIdx.x >> 5) & 3, 0);
  load_wg<CHAIN, true>(P, sb, false, 0, w);
  if (threadIdx.x == 384) TS(25);
  if (threadIdx.x == 384) grid_wait(1, lds32(sb + S_GEN));
  bar_sync(B_WG2, 384);
  if (threadIdx.x == 384) TS(13);
  if (w == 0) {
    const uint32_t* fg = g_fl + FL_G + near_half(XB_F, c) * 1024 + (c >> 1) * 8;
#pragma unroll 1
    for (int n = 0; n < STEPS; n++) {
      const unsigned char* blk = g_qkv + (uint32_t)((n % QRING) * (N_CHAIN * 24576));
      const uint32_t t1 = clk(), kb = sb + CB_FULL + (n & 1) * 8, kv = sb + C_KV + (n & 1) * 16384;
      uint32_t t0 = t1 - 100000, x = 0;
      if (n > 0) {
        wait_until(t1, KMIN);
        do asm volatile("ld.relaxed.gpu.global.u32 %0, [%1];" : "=r"(x) : "l"(fg) : "memory"); while (x <= n && clk() - t1 < KWIN);
        if (NOBULK) x = n + 1;
        if (x > n) {
          asm volatile("fence.acquire.gpu;" ::: "memory");
          fence_async_global();
          if (elect()) { mbar_expect(kb, 8192); bulk_load(kv, blk + c * 24576, 8192, kb); }
        }
        T3(0); CNT(12, 1 + (x <= n));
        mbar_wait(sb + CB_REF, (n - 1) & 1);
        t0 = lds32(sb + C_REF);
        wait_until(t0, DLYK - 500);
      }
      if (!NOBULK) wait_flags(fg + min(lane, 2u) * 256, n + 1);
      T3(2);
      fence_async_global();
      if (n > 0) bar_sync(B_R, 160);
      wait_until(t0, DLYK);
      if (elect()) {
        if (x <= n) { mbar_expect(kb, 8192); bulk_load(kv, blk + c * 24576, 8192, kb); }
        mbar_expect(sb + CB_VF, 8192);
        bulk_load(sb + C_KV + 8192, blk + (c * 24576 + 8192), 8192, sb + CB_VF);
        mbar_expect(sb + CB_Q, 16384);
        bulk_load(sb + C_Q, blk + (c * 24576 + 16384), 8192, sb + CB_Q);
        bulk_load(sb + C_KV2, blk + ((c ^ 1) * 24576 + j * 4096), 4096, sb + CB_Q);
        bulk_load(sb + C_KV2 + 4096, blk + ((c ^ 1) * 24576 + 8192 + j * 4096), 4096, sb + CB_Q);
      }
      T3(1);
      T3(3);
    }
  } else {
    const uint32_t near = __ballot_sync(~0u, near_half(XB_M + min(lane, MRING - 1u) * 8, c));
    uint32_t ring = 0;
    if (w > 1) {
      const uint32_t odd = w & 1, chk = pinned(sb + C_M + odd * 2048 + m_probe(lane)), again = sb + CB_MV + 32 + odd * 8;
      const bool one = elect();
      uint32_t mph = 0;
#pragma unroll 1
      for (int n = 0; n <= STEPS; n++) {
#pragma unroll
        for (int k = 0; k < 3; k++) {
          if (n == STEPS || (k == 2 && odd)) break;
          const uint32_t b = 2 * k + odd, at = chk + (k ? k * 8192 - 2048 + odd * 2048 : 0);
          uint32_t mb = sb + CB_M + b * 8, ph = n & 1;
          int it = 1;
          while (true) {
            mbar_wait(mb, ph);
            const bool bad = __any_sync(~0u, (k ? m_max(at, at + 2048) : max(m_max(at, at ^ 8), odd ? m_max(at + 2048, (at ^ 8) + 2048) : 0)) == SENT);
            if (one && !bad) mbar_arrive(sb + CB_MV + (k ? b * 8 - 8 : 0));
            if (!bad) break;
            mb = again; ph = mph; mph ^= 1;
            if (one) {
              if (k == 0) sts32(sb + C_BAD, n + 1);
              mbar_expect(mb, b ? 4096 : 2048);
              m_fetch(sb, ring * 65536 + ((near >> ring) & 1) * 4096, b, mb);
            }
            __syncwarp();
            spin_guard(it);
          }
          TR(41 + b * 4); CNT(6 + b, it);
        }
        ring = ring + 1 == MRING ? 0 : ring + 1;
        if (!odd) {
          if (n < STEPS) { TRSYNC(); TRDUMP(n - 2); }
        } else {
          unsigned char* o = g_oimg + (uint32_t)(((n - 1) & (RING - 1)) * (N_CHAIN * 8192) + j * 4096);
          if (n > 0) bar_sync(B_G, 160);
          fence_async_smem();
          if (one) {
            if (n > 0) {
              bulk_store(o + c * 8192, sb + C_OS, 4096);
              bulk_store(o + (c ^ 1) * 8192, sb + C_OS + 4096, 4096);
              asm volatile("cp.async.bulk.commit_group;\ncp.async.bulk.wait_group.read 0;" ::: "memory");
              { const int n_ = n - 1; { const int n = n_; T3(4); (void)n; } }
            }
            mbar_arrive(sb + CB_Q);
            if (n > 0) {
              bulk_done_inc(g_fl + FL_O + c);
              { const int n_ = n - 1; { const int n = n_; T3(5); (void)n; } }
            }
          }
          __syncwarp();
        }
      }
    } else {
      const uint32_t* ts = g_fl + FL_SYNC + near_half(XB_F + 1, c) * 1024 + lane * 2;
      uint32_t t0 = clk() - 100000;
#pragma unroll 1
      for (int n = 0; n < STEPS; n++) {
        const uint32_t src = ring * 65536 + ((near >> ring) & 1) * 4096;
        if (lane < 5) mbar_expect(sb + CB_M + lane * 8, lane ? 4096 : 2048);
        __syncwarp();
        if (elect()) {
#pragma unroll
          for (int b = 0; b < 5; b++) {
            wait_until(t0, P.dly[14 + b]);
            m_fetch(sb, src, b, sb + CB_M + b * 8);
            TR(40 + b * 4);
          }
        }
        __syncwarp();
        ring = ring + 1 == MRING ? 0 : ring + 1;
        uint32_t va, vb;
        const uint32_t off = timer_offset(), tag = (uint32_t)(n + 1) << 24;
        bar_sync(B_QK, 416);
        if (n + 1 == STEPS) break;
        sts32(sb + C_REF + 4, 0);
        const uint32_t c0 = clk(), stamp = c0 + off;
        st_relaxed_if(g_fl + FL_SYNC + lane * 1024 + c, tag | (stamp & 0xFFFFFF), lane < 2);
        TR(13);
        wait_until(c0, DLYS);
        int it = 0;
        do {
          asm volatile("ld.relaxed.gpu.global.v2.u32 {%0,%1}, [%2];" : "=r"(va), "=r"(vb) : "l"(ts) : "memory");
          spin_guard(it);
        } while (__any_sync(~0u, ((va ^ tag) | (vb ^ tag)) >> 24));
        const int late = __reduce_max_sync(~0u, max((int)((va - stamp) << 8), (int)((vb - stamp) << 8))) >> 8;
        t0 = c0 + min((uint32_t)late, clk() - c0);
        if (elect()) {
          sts32(sb + C_REF, t0);
          mbar_arrive(sb + CB_REF);
        }
        st_relaxed_if(g_fl + FL_TICK + lane * 1024, tag | ((t0 + off) & 0xFFFFFF), c == 0 && lane < 2);
        TR(14); CNT(11, it);
        bar_sync(B_M, 160);
      }
    }
  }
}

template <int WG>
__device__ __forceinline__ void g_math(const Params& P, uint32_t sb) {
  const int q = g_unit(WG);
  const int lane = threadIdx.x & 31, w = (threadIdx.x >> 5) & 3;
  const bool isq = q >= 64;
  uint32_t a[136];
  {
    const uint32_t stage = sb + G_W + WG * 73728;
    mbar_wait(sb + W_BAR + WG * 8, 0);
    if (threadIdx.x == 0) TS(23);
    load_frags<34>(a, stage);
    fence_async_smem();
    bar_sync(B_WG0 + WG, 128);
    if (threadIdx.x == 0) TS(24);
    load_wg<GROLE>(P, sb, false, WG, w);
    if (threadIdx.x == 0) TS(25);
    mbar_wait(sb + W_BAR + WG * 8, 1);
  }
  if ((threadIdx.x & 127) == 0) TS(4);
  const uint32_t off0 = (q & 31) * 49152 + (q >> 5) * 8192 +
                        (isq ? (w >> 1) * 4096 + (w & 1) * 512 + lane * 16 : w * 1024 + (lane >> 2) * 64 + (((lane ^ (lane >> 3)) & 3) << 4));
#pragma unroll 1
  for (int n = 0; n < STEPS; n++) {
    float d0[32], d1[32];
    if (WG == 0 && n >= LOCK0) bar_sync(B_OE, 160);
    if (n > 0) bar_sync(B_V + WG, 256);
#pragma unroll
    for (int ch = 0; ch < 9; ch++) {
      mbar_wait(sb + G_BAR + ch * 8, n & 1);
      if (ch == 0) { if ((threadIdx.x & 127) == 0) T3(5 + WG * 3); __syncwarp(); }
      if (ch == 4) { if ((threadIdx.x & 127) == 0) T3(6 + WG * 3); __syncwarp(); }
      if (ch == 8 && (WG == 0 ? n > 0 : n + 1 < STEPS)) bar_arrive(B_V + (WG ^ 1), 256);
      wg_fence();
#pragma unroll
      for (int kk = 0; kk < 4 - FASTG; kk++) {
        const int i = ch * 4 + kk;
        float* d = i & 1 ? d1 : d0;
        const uint64_t db = desc_sw128(G_RING + ch * 8192 + (kk & 2) * 32);
        if (i < 2) wg_rs64<0>(d, a + i * 4, db);
        else if (i < 34) wg_rs64<1>(d, a + i * 4, db);
        else wg_ss64<1>(d, desc_sw128(G_W2 + WG * 4096 + (i - 34) * 2048), db);
        wg_ss64<1>(d, desc_sw128(G_W + WG * 73728 + i * 2048), db + 2);
      }
      wg_commit();
      if (ch > 0) { wg_wait<1>(); if (lane == 0) mbar_arrive(sb + G_BAR + 128 + (ch - 1) * 8); }
    }
    wg_wait<0>();
    if (lane == 0) mbar_arrive(sb + G_BAR + 128 + 8 * 8);
    if ((threadIdx.x & 127) == 0) T3(7 + WG * 3);
    __syncwarp();
    uint32_t tw = clk() + (WG ? 0 : DLYW);
    unsigned char* base = g_qkv + (size_t)(n & (QRING - 1)) * (N_CHAIN * 24576);
    if ((ABL & 1) && d0[0] != 1234.5f) {
    } else if (isq) {
#pragma unroll
      for (int i = 0; i < 8; i++) {
        const float *d = (i < 4 ? d0 : d1) + 4 * i, *e = (i < 4 ? d1 : d0) + 4 * i;
        wait_until(tw, 0); tw += P.dly[2 + WG];
        *(uint4*)(base + off0 + (i >> 2) * 24576 + (i & 3) * 1024) =
          make_uint4(movmat(pack2(d[0], d[1])), movmat(pack2(e[0], e[1])), movmat(pack2(d[2], d[3])), movmat(pack2(e[2], e[3])));
      }
    } else {
#pragma unroll
      for (int i = 0; i < 8; i++) {
        const float* d = (i < 4 ? d0 : d1) + 8 * (i & 2) + 2 * (i & 1);
        wait_until(tw, 0); tw += P.dly[2 + WG];
        *(uint4*)(base + off0 + (i >> 2) * 24576 + (i & 2) * 2048 + (i & 1) * 512) =
          make_uint4(pack2(d[0], d[1]), pack2(d[4], d[5]), pack2(d[8], d[9]), pack2(d[12], d[13]));
      }
    }
    bar_arrive(B_M + WG, 160);
  }
}

__device__ __forceinline__ void fill16(void* p, uint32_t v) {
  asm volatile("st.global.v4.u32 [%0], {%1,%1,%1,%1};" :: "l"(p), "r"(v) : "memory");
}
__device__ __forceinline__ void g_load(const Params& P, uint32_t sb) {
  const int lane = threadIdx.x & 31, w = __shfl_sync(~0u, (threadIdx.x >> 5) & 3, 0);
  if (w == 2) return;
  if (w < 2) { bar_sync(15, 192); fence_async_smem(); }
  uint32_t fl = 0;
#pragma unroll 1
  for (int n = w == 3 ? LOCK0 : 0; n < STEPS; n++) {
    if (w && n == LOCK0) { grid_wait(1, lds32(sb + S_GEN)); fl = near_half(XB_F, bid()) * 1024; }
    if (w == 3) {
      const uint32_t tag = (uint32_t)(n - LOCK0 + 1) << 24;
      uint32_t v; int it = 0;
      do { asm volatile("ld.relaxed.gpu.global.u32 %0, [%1];" : "=r"(v) : "l"(g_fl + fl + FL_TICK) : "memory"); spin_guard(it); } while (!NOCHAIN && v < tag);
      const uint32_t off = timer_offset(), now = clk(), t0 = now - ((v ^ tag) >> 24 ? DLYG : (now + off - v) & 0xFFFFFF);
      asm volatile("fence.acquire.gpu;" ::: "memory");
      if (lane == 0) T3(11);
      __syncwarp();
      wait_until(t0, DLYG);
      if (lane == 0) T3(4);
      bar_sync(B_OE, 160);
      continue;
    }
    if (w == 0 || n == 0) {
      if (n < NSEG) wait_flags(g_lnflag + n * 16 + (lane & 1) * 8, 1);
    } else if (!NOCHAIN && n >= LAG) {
      wait_flags(g_fl + fl + FL_F + (lane & 1) * 8, n - LAG + 1);
    }
    if (w) { if (lane == 0) T3(12); bar_sync(B_X, 96); }
    fence_async_global();
    const unsigned char* src = g_lnimg + (uint32_t)((w ? (n >= LAG ? NSEG + n - LAG : 0) : min(n, NSEG - 1)) * 36864);
#pragma unroll 1
    for (int ch = 0; ch < 9; ch++) {
      const uint32_t full = sb + G_BAR + ch * 8;
      mbar_wait(full + 128, (n & 1) ^ 1);
      if (elect()) {
        mbar_expect(full, ABL & 2 ? 16 : 4096);
        bulk_load(sb + G_RING + ch * 8192 + w * 4096, src + ch * 4096, ABL & 2 ? 16 : 4096, full);
      }
    }
  }
}

__device__ __forceinline__ void g_aux(const Params& P, uint32_t sb) {
  const int lane = threadIdx.x & 31, w = (threadIdx.x >> 5) & 3;
  if (w == 1 || w == 2) {
    const int q = g_unit(w - 1);
    uint32_t* f = g_fl + FL_G + q * 8;
#pragma unroll 1
    for (int n = 0; n < STEPS; n++) {
      const uint32_t ln = opaque_tid() & 31;
      uint4* z = (uint4*)g_oacc + (uint32_t)(((n + 1) % ARING) * (16 * DM) + q * 96 + ln);
      if (!(ABL & 16)) { fill16(z, 0); fill16(z + 32, 0); fill16(z + 64, 0); }
      if (n + 3 >= MRING && q < 80) fill16((uint4*)g_mimg + (uint32_t)(((n + 3) % MRING) * 4096 + q * 32 + ln), SENT);
      bar_sync(B_M + (w - 1), 160);
      if (lane == 0) { T3(w * 2 - 2); fence_async_global(); flag_release(f, n + 1); T3(w * 2 - 1); }
      __syncwarp();
    }
  } else {
    const uint32_t u = (bid() - N_CHAIN) * 2 + (w & 1), r = u / 36 * 16 + (u & 3) * 4 + (lane >> 3);
    uint32_t o = r * (DM / 8) + (u % 36 >> 2) * 8 + ((lane & 7) ^ ((r >> 1) & 3)), fl = 0;
#pragma unroll 1
    for (int k = -LAG - 1; k < STEPS; k++) {
      if (k < NSEG - 1) bar_sync(B_X, 96);
      if (k < LAG || u >= 72) continue;
      if (k == NSEG - 1) { fl = near_half(XB_F, bid()) * 1024; wait_flags(g_fl + fl + FL_F + (lane & 1) * 8, NSEG + 1); }
      const uint4 x = __ldcg((const uint4*)P.out + o);
      if (k >= NSEG - 1) wait_flags(g_fl + fl + FL_OCNT + (max(k, NSEG) % OCRING) * 8, N_O * 3 * (max(k, NSEG) / OCRING + 1));
      const float4* a = (const float4*)g_oacc + ((k % ARING) * (16 * DM) + 8 * DM + u * 64 + lane * 2);
      const float4 p = __ldcg(a), v = __ldcg(a + 1);
      ((uint4*)P.out)[o] = make_uint4(badd2(x.x, pack2(p.x, p.y)), badd2(x.y, pack2(p.z, p.w)), badd2(x.z, pack2(v.x, v.y)), badd2(x.w, pack2(v.z, v.w)));
      o += 4 * DM;
    }
    if ((threadIdx.x & 127) == 0) TS(7);
  }
}

template <int WG, bool HALF, int KS, int N> __device__ __forceinline__ void o_mma(float* d, const uint32_t* a, uint32_t ob) {
  constexpr uint64_t db = desc_sw128(O_RING + (KS >> 2) * 8192 + (KS & 3) * 32);
  constexpr uint64_t da = desc_sw128(O_W + WG * 40960 + (KS < 40 ? KS / 5 * 2 + KS % 5 / 2 : KS - 24) * 2048);
  if constexpr (KS < 40 && !(KS % 5 & 1)) {
    const uint32_t* r = a + (KS / 5 * 3 + KS % 5 / 2) * 4;
    if constexpr (HALF) wg_rs32k<KS != 0, db>(d, r[0], r[1], r[2], r[3], ob); else wg_rs64<KS != 0>(d, r, db);
  } else {
    if constexpr (HALF) wg_ss32k<da, db>(d, ob); else wg_ss64<1>(d, da, db);
  }
  if constexpr (N > 1) o_mma<WG, HALF, KS + 1, N - 1>(d, a, ob);
}
template <int WG, bool HALF, int GR> __device__ __forceinline__ void o_groups(float* d, const uint32_t* a, uint32_t sb, int n, bool more) {
  const uint32_t ob = n < NSEG ? 0 : 256;
  mbar_wait(sb + O_BAR + GR * 8, n & 1);
  if (GR == 0) { if ((threadIdx.x & 127) == 0) T3(13 + WG); __syncwarp(); }
  if (GR == (WG == 0 ? OTURN : 4) && (WG < 2 || n + 1 < STEPS)) bar_arrive(B_V + (WG + 1) % 3, 256);
  wg_fence();
  o_mma<WG, HALF, GR * 8, 8 - 2 * FASTG>(d, a, ob);
  if (GR == 4 && more) o_mma<WG, HALF, 40, 4>(d, a, ob);
  wg_commit();
  if (GR > 0) { wg_wait<1>(); if ((threadIdx.x & 31) == 0) mbar_arrive(sb + O_BAR + 128 + (GR - 1) * 8); }
  if constexpr (GR < 4) o_groups<WG, HALF, GR + 1>(d, a, sb, n, more);
}
template <int WG, bool HALF> __device__ __forceinline__ void o_step(const uint32_t* a, uint32_t sb, uint32_t st0, int n, bool more) {
  float d[HALF ? 16 : 32];
  if (WG > 0 || n > 0) bar_sync(B_V + WG, 256);
  o_groups<WG, HALF, 0>(d, a, sb, n, more);
  wg_wait<0>();
  if ((threadIdx.x & 31) == 0) mbar_arrive(sb + O_BAR + 128 + 4 * 8);
  if ((threadIdx.x & 127) == 0) T3(WG == 0 ? 1 : WG == 1 ? 8 : 12);
  __syncwarp();
#pragma unroll(HALF ? 1 : 2)
  for (int sl = 0; sl < 2; sl++) {
    mbar_wait(sb + OB_ST + WG * 16 + sl * 8, (n & 1) ^ (WG == 0));
    if (!HALF || sl == (n >= NSEG)) {
#pragma unroll
      for (int nb = 0; nb < 4; nb++) {
        const float* r = d + (HALF ? 0 : sl * 16) + nb * 4;
        const uint32_t ad = st0 + sl * 8192 + nb * 2048;
        sts32(ad, __float_as_uint(r[0]));
        sts32(ad + 256, __float_as_uint(r[1]));
        sts32(ad ^ 32, __float_as_uint(r[2]));
        sts32((ad ^ 32) + 256, __float_as_uint(r[3]));
      }
      fence_async_smem();
    }
    bar_arrive((sl ? B_G : B_M) + WG, 160);
  }
}
template <int WG>
__device__ __forceinline__ void o_math(const Params& P, uint32_t sb) {
  const bool more = bid() < N_CHAIN + N_G + 12;
  const int lane = threadIdx.x & 31, w = (threadIdx.x >> 5) & 3, g = lane >> 2, tq = lane & 3;
  uint32_t a[96];
  mbar_wait(sb + W_BAR + WG * 8, 0);
  load_frags<24>(a, sb + WG * 49152);
  fence_async_smem();
  bar_sync(B_INIT, 416);
  load_wg<OROLE>(P, sb, false, WG, w);
  mbar_wait(sb + W_BAR + WG * 8, 1);
  if ((threadIdx.x & 127) == 0) TS(4);
  const uint32_t st0 = sb + O_ST + tq * 512 + ((w * 16 + g) ^ (tq * 8)) * 4;
#pragma unroll 1
  for (int n = 0; n < STEPS; n++) {
    if (n < LAG || n >= NSEG) o_step<WG, true>(a, sb, st0, n, more); else o_step<WG, false>(a, sb, st0, n, more);
  }
}

__device__ __forceinline__ void o_aux(const Params& P, uint32_t sb) {
  const int i = bid() - N_CHAIN - N_G, ksl = i / 3;
  const int c0 = ksl * 11 - max(ksl - 4, 0), nc = ksl < 4 ? 11 : 10;
  const int lane = threadIdx.x & 31, w = __shfl_sync(~0u, (threadIdx.x >> 5) & 3, 0);
  if (w == 0) {
    bar_sync(B_INIT, 416);
    const uint32_t* f = g_fl + FL_O + near_half(XB_F + 1, bid()) * 1024 + min((c0 & ~1) + lane, (c0 + nc - 1) | 1);
#pragma unroll 1
    for (int n = 0; n < STEPS; n++) {
      const unsigned char* src = g_oimg + (uint32_t)(((n % RING) * N_CHAIN + c0) * 8192);
      if (!NOCHAIN) wait_flags(f, n + 1);
      fence_async_global();
      if (lane == 0) T3(0);
#pragma unroll
      for (int gr = 0; gr < 5; gr++) {
        const uint32_t full = sb + O_BAR + gr * 8, bytes = ABL & 4 ? 16 : (gr < 4 ? 2 : nc - 8) * 8192;
        mbar_wait(full + 128, (n & 1) ^ 1);
        if (elect()) {
          if (n < LAG || n >= NSEG) {
            mbar_expect(full, bytes >> 1);
            for (uint32_t o = gr * 16384 + (n < LAG ? 0 : 4096); o < gr * 16384 + bytes; o += 8192) bulk_load(sb + O_RING + o, src + o, 4096, full);
          } else {
            mbar_expect(full, bytes);
            bulk_load(sb + O_RING + gr * 16384, src + gr * 16384, bytes, full);
          }
        }
      }
    }
  } else {
#pragma unroll 1
    for (int n = 0; n < STEPS; n++) {
      float* dst = g_oacc + (uint32_t)((n % ARING) * (64 * DM) + ((i % 3) * 3 + (w - 1 + ksl) % 3) * 1024);
      const bool early = w == 3 && n < NSEG;
      bar_sync(B_M + (w - 1), 160);
      if (lane == 0) {
        T3(w * 2);
        if (n < NSEG && !(ABL & 8)) { bulk_reduce(dst, sb + O_ST, 4096); bulk_reduce(dst + 16 * DM, sb + O_ST + 4096, 4096); }
        asm volatile("cp.async.bulk.commit_group;" ::: "memory");
        if (early) {
          asm volatile("cp.async.bulk.wait_group.read 0;" ::: "memory");
          mbar_arrive(sb + OB_ST);
          T3(8 + w);
          bulk_done_inc(g_fl + FL_OCNT + (n % OCRING) * 8);
          T3(w * 2 + 1);
        }
      }
      __syncwarp();
      bar_sync(B_G + (w - 1), 160);
      if (lane == 0) {
        if (n >= LAG && !(ABL & 8)) { bulk_reduce(dst + 32 * DM, sb + O_ST + 8192, 4096); bulk_reduce(dst + 48 * DM, sb + O_ST + 12288, 4096); }
        asm volatile("cp.async.bulk.commit_group;\ncp.async.bulk.wait_group.read 1;" ::: "memory");
        if (!early) mbar_arrive(sb + OB_ST + (w % 3) * 16);
        asm volatile("cp.async.bulk.wait_group.read 0;" ::: "memory");
        mbar_arrive(sb + OB_ST + (w % 3) * 16 + 8);
        if (!early) {
          T3(8 + w);
          bulk_done_inc(g_fl + FL_OCNT + (n % OCRING) * 8);
          T3(w * 2 + 1);
        }
      }
      __syncwarp();
    }
  }
}

constexpr uint32_t Y_PITCH = 1168, Y_ROWS = 16 * Y_PITCH;
template <int R> __device__ __forceinline__ void y_rows(uint32_t* y, uint32_t src, uint32_t dst, int w, int bar) {
  const int lane = threadIdx.x & 31;
#pragma unroll
  for (int k = 0; k < 2 * R + 1; k++) {
    const int op = w + k * (16 / R);
    if (k == 2 * R && w >= 4) break;
    uint32_t a, b, c, d;
    ldsm4t(a, b, c, d, src + op * 512 + (lane & 16) * 16 + (lane & 7) * 32 + (lane & 8) * 2);
    stsm4(dst + (lane & 15) * Y_PITCH + op * 32 + (lane & 16), a, b, c, d);
  }
  bar_sync(bar, 512 / R);
  const uint32_t row = dst + ((w & 6) * 2 + (w >> 3) * 2 + (w & 1)) * Y_PITCH + lane * 4;
#pragma unroll
  for (int i = 0; i < 9 * R; i++) y[i] = lds32(row + i / 9 * 2 * Y_PITCH + i % 9 * 128);
}

__device__ __forceinline__ void f_role(const Params& P, uint32_t sb) {
  const int lane = threadIdx.x & 31, w = __shfl_sync(~0u, threadIdx.x >> 5, 0), r0 = (bid() - N_CHAIN - N_G - N_O) * 16;
  if (w == 8) {
    const uint32_t* fo = g_fl + FL_OCNT + near_half(XB_F, bid()) * 1024;
    fence_async_global();
#pragma unroll 1
    for (int n = 0; n < NSEG; n++) {
      bar_sync(2, 288);
      if (elect()) {
        mbar_expect(sb + F_BAR, 36864);
        bulk_load(sb + F_XY, P.X + (size_t)(n * 32 + r0) * DM, 18432, sb + F_BAR);
        bulk_load(sb + F_XY + 18432, g_yT + (size_t)(n * 32 + r0) * DM, 18432, sb + F_BAR);
        mbar_expect(sb + F_BAR + 8, 36864);
        T3(1);
      }
      wait_flags(fo + (n % OCRING) * 8, NOCHAIN == 5 ? 0 : N_O * 3 * (n / OCRING + 1));
      fence_async_global();
      if (elect()) { bulk_load(sb + F_A, g_oacc + (uint32_t)((n % ARING) * (64 * DM) + r0 * DM), 36864, sb + F_BAR + 8); T3(0); }
    }
  } else if (w == 9) {
#pragma unroll 1
    for (int n = 0; n < NSEG; n++) {
      const uint32_t st = sb + (n & 1) * 36864;
      unsigned char* p = g_lnimg + (uint32_t)((NSEG + n) * 36864 + r0 * 128);
      bar_sync(1, 288);
      if (elect()) {
        T3(2);
#pragma unroll
        for (int i = 0; i < 9; i++) bulk_store(p + i * 4096, st + F_L + i * 2048, 2048);
        asm volatile("cp.async.bulk.commit_group;" ::: "memory");
        bulk_done_inc(g_fl + FL_F + (bid() & 1) * 8);
        T3(3);
        bulk_store(P.out + (size_t)(n * 32 + r0) * DM, st + F_X, 18432);
        asm volatile("cp.async.bulk.commit_group;\ncp.async.bulk.wait_group.read 0;" ::: "memory");
        if (n + 1 == NSEG) bulk_done_inc(g_fl + FL_F + (bid() & 1) * 8);
      }
      __syncwarp();
    }
  } else if (w < 8) {
    const uint32_t row = sb + w * 1152 + lane * 4, acc = sb + F_A + w * 256 + (lane ^ ((w & 6) * 2)) * 8;
    const uint32_t ln = sb + F_L + w * 128 + (((lane >> 2) ^ w) << 4) + (lane & 3) * 4;
#pragma unroll 1
    for (int n = -1; n < NSEG; n++) {
      const uint32_t st = (n & 1) * 36864;
      uint32_t x[18], y[18], l[18];
      if (n >= 0) mbar_wait(sb + F_BAR, n & 1);
#pragma unroll
      for (int i = 0; i < 18; i++) x[i] = lds32(row + F_XY + i / 9 * 9216 + i % 9 * 128);
      y_rows<2>(y, sb + F_XY + 18432, sb + F_Y, w, 3);
      layernorm9<2>(x, l);
#pragma unroll
      for (int i = 0; i < 18; i++) x[i] = badd2(x[i], bmul2(l[i], y[i]));
      if (n >= 0) mbar_wait(sb + F_BAR + 8, n & 1);
      if (threadIdx.x == 0 && n >= 0) T3(4);
      __syncwarp();
      uint2 a[18];
#pragma unroll
      for (int i = 0; i < 18; i++) a[i] = lds64(acc + i / 9 * 2048 + i % 9 * 4096);
#pragma unroll
      for (int i = 0; i < 18; i++) x[i] = badd2(x[i], pack2(__uint_as_float(a[i].x), __uint_as_float(a[i].y)));
      if (n + 1 < NSEG) bar_arrive(2, 288);
      layernorm9<2>(x, l);
#pragma unroll
      for (int i = 0; i < 18; i++) { x[i] = badd2(x[i], bmul2(l[i], y[i])); sts32(row + st + F_X + i / 9 * 9216 + i % 9 * 128, x[i]); }
      layernorm9<2>(x, l);
#pragma unroll
      for (int i = 0; i < 18; i++) sts32(ln + st + i / 9 * 1024 + i % 9 * 2048, l[i]);
      fence_async_smem();
      if (n >= 0) bar_sync(1, 288); else bar_sync(3, 256);
    }
  }
}

constexpr uint32_t P_CH = 147456, P_CHSZ = 12800, P_H = 4352;
static_assert(P_CH + 6 * P_CHSZ <= G_BAR, "prologue smem");

template <int N>
__device__ __forceinline__ void conv_fold(float (*acc)[4], bool hi, uint32_t mine, uint32_t theirs, int bar, int cnt) {
#pragma unroll
  for (int i = 0; i < N / 2; i++) {
    uint4 v;
    v.x = __float_as_uint(hi ? acc[i][0] : acc[i + N / 2][0]); v.y = __float_as_uint(hi ? acc[i][1] : acc[i + N / 2][1]);
    v.z = __float_as_uint(hi ? acc[i][2] : acc[i + N / 2][2]); v.w = __float_as_uint(hi ? acc[i][3] : acc[i + N / 2][3]);
    sts128(mine + i * 512, v);
  }
  bar_sync(bar, cnt);
#pragma unroll
  for (int i = 0; i < N / 2; i++) {
    const uint4 v = lds128(theirs + i * 512);
    acc[i][0] = (hi ? acc[i + N / 2][0] : acc[i][0]) + __uint_as_float(v.x); acc[i][1] = (hi ? acc[i + N / 2][1] : acc[i][1]) + __uint_as_float(v.y);
    acc[i][2] = (hi ? acc[i + N / 2][2] : acc[i][2]) + __uint_as_float(v.z); acc[i][3] = (hi ? acc[i + N / 2][3] : acc[i][3]) + __uint_as_float(v.w);
  }
}
template <int N>
__device__ __forceinline__ void conv_store(const float (*acc)[4], int tile0, uint32_t su, int d, uint32_t dd) {
  const int lane = threadIdx.x & 31, g = lane >> 2, tq = lane & 3;
#pragma unroll
  for (int i = 0; i < N; i++) {
    const uint32_t ad = su + (8 + (tile0 + i) * 8 + g) * 32 + tq * 4, sw = (g & 4) << 2;
    const uint32_t lo = badd2(movmat(pack2(acc[i][0], acc[i][1])), bmul2(lds32(ad + sw), dd));
    const uint32_t hi = badd2(movmat(pack2(acc[i][2], acc[i][3])), bmul2(lds32(ad + (sw ^ 16)), dd));
    ((uint2*)g_yT)[(((tile0 + i) * 8 + g) * DM + d) * 4 + tq] = make_uint2(lo, hi);
  }
}

__device__ __forceinline__ void prologue(const Params& P, uint32_t sb) {
  const int b = bid(), tid = threadIdx.x, lane = tid & 31, warp = tid >> 5, t0 = b * 16;
  const bool isg = b >= N_CHAIN && b < N_CHAIN + N_G;
  const int nch = isg ? 2 : b < 128 ? 6 : 0, chb = b < N_CHAIN ? b * 6 : isg ? b * 2 + 256 : b * 6 - 192;
  const uint32_t tstart = clk();
  if (tid < 288) {
    if (b < 128) {
      const int c = (tid >> 1) * 4, tt = t0 + (tid & 1) * 8;
      uint2 kr[11], vr[8];
#pragma unroll
      for (int i = 0; i < 11; i++) { const int t = tt + i - 3; kr[i] = t >= 0 ? __ldg((const uint2*)(P.K + (size_t)t * DM + c)) : make_uint2(0, 0); }
#pragma unroll
      for (int i = 0; i < 8; i++) vr[i] = __ldg((const uint2*)(P.V + (size_t)(tt + i) * DM + c));
#pragma unroll
      for (int e = 0; e < 2; e++) {
        const uint4 sh = __ldg((const uint4*)(P.shift + c * 4) + e);
        const uint32_t s0 = __byte_perm(sh.x, sh.z, 0x5410), s1 = __byte_perm(sh.x, sh.z, 0x7632);
        const uint32_t s2 = __byte_perm(sh.y, sh.w, 0x5410), s3 = __byte_perm(sh.y, sh.w, 0x7632);
        uint32_t v[8];
#pragma unroll
        for (int i = 0; i < 8; i++) {
          const uint32_t k3 = e ? kr[i].y : kr[i].x, k2 = e ? kr[i + 1].y : kr[i + 1].x, k1 = e ? kr[i + 2].y : kr[i + 2].x, k0 = e ? kr[i + 3].y : kr[i + 3].x;
          v[i] = bmul2(badd2(badd2(badd2(bmul2(k3, s3), bmul2(k2, s2)), bmul2(k1, s1)), bmul2(k0, s0)), e ? vr[i].y : vr[i].x);
        }
        *(uint4*)(g_kvT + (size_t)(c + 2 * e) * KVP + tt) =
          make_uint4(__byte_perm(v[0], v[1], 0x5410), __byte_perm(v[2], v[3], 0x5410), __byte_perm(v[4], v[5], 0x5410), __byte_perm(v[6], v[7], 0x5410));
        *(uint4*)(g_kvT + (size_t)(c + 2 * e + 1) * KVP + tt) =
          make_uint4(__byte_perm(v[0], v[1], 0x7632), __byte_perm(v[2], v[3], 0x7632), __byte_perm(v[4], v[5], 0x7632), __byte_perm(v[6], v[7], 0x7632));
      }
    }
  } else if (tid < 384) {
    const int t = tid - 288;
    for (int i = t; i < 32 * nch; i += 96) asm volatile("prefetch.global.L2 [%0];" :: "l"(P.Hk + (size_t)chb * SEQ + i * 64));
    for (int i = b * 96 + t; i < 32 * DM; i += N_CTA * 96) ((uint4*)g_oacc)[i] = make_uint4(0, 0, 0, 0);
    if (b * 96 + t < 128 * 8) g_lnflag[b * 96 + t] = 0;
    if (t == 95) sts32(sb + S_GEN, ld_acquire(g_gbar));
  }
  if (warp < 12) {
    bar_arrive(10, 416);
    if (tid == 128) TS(14);
    const int ch = 5 - (warp >> 1), sub = warp & 1, d = chb + ch;
    const uint32_t su = sb + P_CH + ch * P_CHSZ;
    if (ch < nch) {
      const uint32_t* hs = (const uint32_t*)(P.Hk + (size_t)d * SEQ);
#pragma unroll
      for (int q = sub * 32 + lane; q < 256; q += 64) {
        const uint4 c = __ldg((const uint4*)hs + q);
        const uint32_t prev = q ? __ldg(hs + 4 * q - 1) : 0u;
        sts128(su + P_H + 32 + q * 16, make_uint4(__byte_perm(c.x, prev, 0x7610), __byte_perm(c.y, c.x, 0x7610), __byte_perm(c.z, c.y, 0x7610), __byte_perm(c.w, c.z, 0x7610)));
        sts128(su + P_H + 4224 + q * 16, make_uint4(__byte_perm(c.x, 0, 0x1032), __byte_perm(c.y, 0, 0x1032), __byte_perm(c.z, 0, 0x1032), __byte_perm(c.w, 0, 0x1032)));
      }
      if (sub == 1 && lane == 0) sts32(su + P_CHSZ - 16, __bfloat16_as_ushort(P.Dk[d]) * 0x10001u);
      if (sub == 0 && lane < 20) sts128(su + (lane < 16 ? lane * 16 : P_H + (lane & 2) * 2096 + (lane & 1) * 16), make_uint4(0, 0, 0, 0));
    }
    bar_sync(11, 416);
    if (ch < nch) {
#pragma unroll
      for (int q = sub * 32 + lane; q < 256; q += 64) {
        const int row = (q >> 1) + 8;
        sts128(su + row * 32 + (((q & 1) ^ ((row >> 2) & 1)) << 4), __ldcg((const uint4*)(g_kvT + (size_t)d * KVP) + q));
      }
    }
    const int g = lane >> 2, tq = lane & 3;
    const uint32_t sh = su + P_H + (g & 1) * 4192 + (8 + (g >> 1) - tq) * 4;
    float acc[16][4];
#pragma unroll
    for (int i = 0; i < 16; i++) { acc[i][0] = acc[i][1] = acc[i][2] = acc[i][3] = 0.f; }
    auto u_addr = [&](int res) {
      const int row = 8 - res + ((lane >> 4) << 3) + (lane & 7);
      return su + row * 32 + ((((lane >> 3) & 1) ^ ((row >> 2) & 1)) << 4);
    };
    if (ch < nch) {
      bar_sync(1 + ch, 64);
      if (tid == 352) TS(11);
      if (sub) {
#pragma unroll 4
        for (int res = 0; res < 8; res++) {
          uint32_t b0, b1, b2, b3;
          ldsm4(b0, b1, b2, b3, u_addr(res));
          const uint32_t r0 = lds32(sh + res * 32);
          mma16(acc[0], r0, lds32(sh + res * 32 + 16), lds32(sh + res * 32 - 16), r0, b0, b1);
        }
        conv_store<1>(acc, 0, su, d, lds32(su + P_CHSZ - 16));
      }
    }
    bar_arrive(12, 416);
    if (isg && warp < 8) { while ((int)(clk() - tstart - S1G) < 0) __nanosleep(200); load_wg<GROLE>(P, sb, true, warp >> 2, warp & 3); }
    if (ch < nch) {
#pragma unroll 1
      for (int res = sub * 4; res < sub * 4 + 4; res++) {
        uint32_t bf[16][2];
        const uint32_t ad = u_addr(res);
#pragma unroll
        for (int f = 0; f < 16; f += 2) ldsm4(bf[f][0], bf[f][1], bf[f + 1][0], bf[f + 1][1], ad + f * 256);
#pragma unroll
        for (int k = 0; k < 16; k++) {
          const int jj = k & 1 ? k >> 1 : 15 - (k >> 1);
          const uint32_t ah = sh + (8 * jj + res) * 32;
          const uint32_t r0 = lds32(ah), r1 = lds32(ah + 16), rm = lds32(ah - 16);
#pragma unroll
          for (int i = max(jj, 1); i < 16; i++) mma16(acc[i], r0, r1, rm, r0, bf[i - jj][0], bf[i - jj][1]);
        }
      }
      bar_sync(1 + ch, 64);
      if (tid == 352) TS(12);
      const uint32_t xb = su + P_H + lane * 16, dd = lds32(su + P_CHSZ - 16);
      conv_fold<16>(acc, sub, xb + sub * 4096, xb + (sub ^ 1) * 4096, 1 + ch, 64);
      conv_store<8>(acc, sub * 8, su, d, dd);
    }
  } else {
    for (int i = b; i < 194 + MRING * 5; i += N_CTA) {
      const int n = (i - 194) / 5, r = (i - 194) % 5, blk = i < 192 ? i / 6 * 8 + i % 6 : i < 194 ? XB_F + i - 192 : XB_M + n * 8 + r;
      const uint32_t fill = i < 194 ? 0u : SENT;
#pragma unroll 1
      for (int q = tid - 384; q < 256 && warp < 15; q += 96) {
        uint4 v = make_uint4(fill, fill, fill, fill);
        if (i >= 194 && n == 0 && (r > 0 || q < 128)) {
          const bf16* m = P.mem0 + (max(r * 8 - 4, 0) + (q >> 5)) * 16 + ((q >> 1) & 1) * 8 + ((q >> 2) & 7);
          v.x = pack2(__bfloat162float(m[0]), __bfloat162float(m[DM])); v.y = pack2(__bfloat162float(m[2 * DM]), __bfloat162float(m[3 * DM]));
          v.z = pack2(__bfloat162float(m[4 * DM]), __bfloat162float(m[5 * DM])); v.w = pack2(__bfloat162float(m[6 * DM]), __bfloat162float(m[7 * DM]));
        }
        g_xb[blk * 512 + q] = v;
        g_xb[blk * 512 + 256 + q] = v;
      }
    }
    if (tid < 388) g_xb[XB_REF * 512 + (tid & 2) * 128 + (b & ~1) + (tid & 1)] = make_uint4(0, 0, 0, 0);
    else if (tid < 392 && b < N_GRP) g_xb[(b * 8 + 7) * 512 + (tid & 2) * 128 + (tid & 1)] = make_uint4(0, 0, 0, 0);
    if (warp < 15) { bar_arrive(9, 128); bar_sync(7, 96); }
    if (tid == 384) TS(8);
    if (warp == 12) {
      const bf16* w = lane < 6 ? (lane % 3 == 0 ? P.Wk : lane % 3 == 1 ? P.Wv : P.Wq) + (((b >> 5) * 2 + lane / 3) * 32 + (b & 31)) * 2048
                               : (lane < 8 ? P.Wo + (lane - 6) * (9 * 131072) : P.X) + b * 2048;
      uint32_t t = tstart + P.dly[19];
      if ((int)(clk() - t) > 0) t = clk();
#pragma unroll 1
      for (int st = 0; st < 9 && b < N_CHAIN; st++) {
#pragma unroll 1
        for (int i = 0; i < 9; i++, t += PACE) {
          wait_until(t, 0);
          if (lane == st) asm volatile("cp.async.bulk.prefetch.L2.global [%0], 4096;" :: "l"(w + i * (lane < 6 ? 262144 : 131072)) : "memory");
        }
      }
      if (lane == 0) TS(10);
    } else if (warp == 15) {
      bar_sync(10, 416);
      if (lane == 0) { grid_arrive(0); if (nch) grid_wait(0, lds32(sb + S_GEN)); }
      __syncwarp();
      bar_arrive(11, 416);
      if (lane == 0) TS(1);
      bar_sync(9, 128);
      bar_sync(12, 416);
      if (lane == 0) { TS(16); grid_arrive(2); TS(17); }
    } else if (lane == 0) {
      if (warp == 13 || (warp == 14 && b < N_GRP)) {
        uint32_t* p = (uint32_t*)(g_xb + (warp == 13 ? XB_REF * 512 + b : (b * 8 + 7) * 512));
        int votes = 0;
        for (int rep = 0; rep < 24 && abs(votes) < 7; rep++) {
          uint32_t v0, v1, c0, c1;
          asm volatile("atom.relaxed.gpu.global.add.u32 %0, [%4], 0;\n atom.relaxed.gpu.global.add.u32 %1, [%5], 0;\n"
                       "{.reg .pred p; setp.eq.u32 p, %0, 0x7ffffff3; @p trap; mov.u32 %2, %%clock; setp.eq.u32 p, %1, 0x7ffffff3; @p trap; mov.u32 %3, %%clock;}"
                       : "=&r"(v0), "=&r"(v1), "=&r"(c0), "=&r"(c1) : "l"(p + (rep & 1) * 1024), "l"(p + ((rep & 1) ^ 1) * 1024) : "memory");
          votes += ((c1 - c0 > 80u) == (rep & 1)) ? 1 : -1;
        }
        if (warp == 13) { g_side[b] = votes > 0; TS(9); } else g_near[b] = votes > 0;
      }
    }
    __syncwarp();
    if (warp > 12 && b < N_CHAIN) {
      while ((int)(clk() - tstart - S1DLY) < 0) __nanosleep(200);
      for (int k = warp - 13; k < 8; k += 3) load_wg<CHAIN>(P, sb, true, 1 - k / 4, k & 3);
    }
  }
  if (b < N_CHAIN + N_G && (warp < 8 || (isg && warp >= 12))) bar_arrive(0, 512); else bar_sync(0, 512);
  if (tid == 352) TS(2);
}

__device__ __forceinline__ void publish_y() {
  if (threadIdx.x == 383) { grid_arrive(1); TS(18); }
  __syncwarp();
}

template <int R> __device__ __forceinline__ void ln_tiles(const Params& P, uint32_t sb) {
  const int lane = threadIdx.x & 31, w = (threadIdx.x >> 5) & (16 / R - 1), half = R == 1 ? 0 : threadIdx.x >> 8, u = N_CTA - 1 - bid();
  const int first = R == 1 ? u : 46 - 2 * u + half, step = R == 1 ? 4 : 40, last = R == 1 ? 8 : 128;
  const uint32_t raw = sb + P_CH + half * (18432 + Y_ROWS), mb = sb + T_BAR + (R - 1 + half) * 8;
  const bool lead = w == 16 / R - 1 && lane == 0;
  auto load_y = [&](const bf16* src, int tile) {
    fence_async_global();
    mbar_expect(mb, 18432);
    bulk_load(raw, src + (size_t)tile * 16 * DM, 18432, mb);
  };
  uint32_t nx[9 * R];
  auto load_x = [&](int tile) {
#pragma unroll
    for (int i = 0; i < 9 * R; i++) nx[i] = __ldg((const uint32_t*)(P.X + (size_t)(tile * 16 + w + i / 9 * 8) * DM) + i % 9 * 32 + lane);
  };
  load_x(first);
  if (R == 2) {
    if (lead) { grid_wait(1, lds32(sb + S_GEN)); if (u > 3) TS(13); load_y(g_yT, first); }
    __syncwarp();
  }
#pragma unroll 1
  for (int tile = first, real = R - 1, ph = 0; tile < last; tile += real * step, real = 1, ph ^= 1) {
    uint32_t x[9 * R], l[9 * R], y[9 * R];
    const bool ts = threadIdx.x == 0 && (R == 1 ? tile == first : u > 3 && tile == first + step);
    if (ts) TS(26);
#pragma unroll
    for (int i = 0; i < 9 * R; i++) x[i] = nx[i];
    layernorm9<R>(x, l);
    if (real && tile + step < last) load_x(tile + step);
    if (R == 2 && tile == first + step && u >= N_F && w < 6) load_wg<OROLE>(P, sb, true, w >> 1, half * 2 + (w & 1));
    if (R == 1 && tile == first && lead) {
      if (real) grid_wait(2, lds32(sb + S_GEN));
      TS(13);
      load_y(real ? g_yT : P.Hk, tile);
    }
    bar_sync(13 + half, 512 / R);
    mbar_wait(mb, ph);
    if (ts) TS(28);
    y_rows<R>(y, raw, raw + 18432, w, 13 + half);
    if (ts) TS(29);
    if (lead && real && tile + step < last) { fence_async_smem(); load_y(g_yT, tile + step); }
    __syncwarp();
#pragma unroll
    for (int i = 0; i < 9 * R; i++) x[i] = badd2(x[i], bmul2(l[i], y[i]));
    layernorm9<R>(x, l);
    if (ts && l[0] != 0x12345) TS(30);
#pragma unroll
    for (int r = 0; r < R; r++) store_ln_row(0, tile * 16 + w + r * 8, l + r * 9);
    if (R == 1) {
      __syncthreads();
      if (threadIdx.x == 32 && real) { if (tile < 4) TS(19); st_release(g_lnflag + tile * 8, 1); if (tile < 4) TS(20); }
      __syncwarp();
    }
    if (ts) TS(31);
  }
  if (R == 2) {
    __syncthreads();
    if (threadIdx.x >= 506) {
      asm volatile("fence.acq_rel.gpu;" ::: "memory");
      st_relaxed_if(g_lnflag + ((first ^ (lane & 1)) + (lane - 26) / 2 * step) * 8, 1, true);
    }
    __syncwarp();
    fence_async_smem();
    if (threadIdx.x == 0) TS(15);
  }
}

__global__ void __cluster_dims__(2, 1, 1) __launch_bounds__(512, 1) k_main(const __grid_constant__ Params P) {
  extern __shared__ __align__(1024) unsigned char smem[];
  const uint32_t sb = (uint32_t)__cvta_generic_to_shared(smem);
  const int b = bid(), wg = threadIdx.x >> 7;
  if ((threadIdx.x & 127) == 0) TS(0);
  if (threadIdx.x == 480) {
    if ((sb & 0xFFFFFF) != SBASE) __trap();
    for (int i = 0; i < 6; i++) mbar_init(sb + W_BAR + i * 8, 1);
    if (b < N_CHAIN) {
      mbar_init(sb + CB_FULL, 1); mbar_init(sb + CB_FULL + 8, 1);
      mbar_init(sb + CB_REF, 1);
      mbar_init(sb + CB_SX, 1); mbar_init(sb + CB_OX, 1); mbar_init(sb + CB_XX, 1); mbar_init(sb + CB_Q, 2); mbar_init(sb + CB_VF, 1); mbar_init(sb + CB_VF + 8, 1);
      sts32(sb + C_BAD, 0);
      for (int i = 0; i < 11; i++) mbar_init(sb + CB_M + i * 8, i == 0 ? 5 : i == 5 ? 2 : 1);
    } else if (b < N_CHAIN + N_G) {
      for (int i = 0; i < 9; i++) { mbar_init(sb + G_BAR + i * 8, 2); mbar_init(sb + G_BAR + 128 + i * 8, 8); }
    } else if (b < N_CHAIN + N_G + N_O) {
      for (int i = 0; i < 5; i++) { mbar_init(sb + O_BAR + i * 8, 1); mbar_init(sb + O_BAR + 128 + i * 8, 12); }
      for (int i = 0; i < 6; i++) mbar_init(sb + OB_ST + i * 8, 1);
    } else {
      mbar_init(sb + F_BAR, 1); mbar_init(sb + F_BAR + 8, 1);
    }
    asm volatile("fence.mbarrier_init.release.cluster;" ::: "memory");
    fence_async_smem();
  }
  __syncwarp();
  asm volatile("barrier.cluster.arrive.relaxed.aligned;" ::: "memory");
  prologue(P, sb);
  asm volatile("barrier.cluster.wait.aligned;" ::: "memory");
  fence_async_smem();
  if (b >= N_CHAIN + N_G) publish_y();
  if (b >= 128) ln_tiles<1>(P, sb);
  if (b >= N_CHAIN + N_G) ln_tiles<2>(P, sb);
  if ((threadIdx.x & 127) == 0) TS(3);
  if (b < N_CHAIN) {
    if (wg < 2) { reg_inc<200>(); chain_proj(P, sb); }
    else if (wg == 2) { reg_dec<ATTR>(); publish_y(); chain_attn(P, sb); }
    else { reg_dec<112 - ATTR>(); chain_aux(P, sb); }
  } else if (NOBULK) {
    if (b < N_CHAIN + N_G) publish_y();
    {
      if (wg == 0) {
        float d[4] = {0.f, 0.f, 0.f, 0.f};
        for (int n = 0; n < STEPS - 1; n++) {
          const uint32_t* f = g_fl + FL_TICK;
          uint32_t x;
          do { for (int k = 0; k < 16; k++) mma16(d, 0, 0, 0, 0, 0, 0); asm volatile("ld.relaxed.gpu.global.u32 %0, [%1];" : "=r"(x) : "l"(f) : "memory"); } while ((x >> 24) <= n);
          const int q = (b - N_CHAIN) * 4 + (threadIdx.x >> 5);
          if (n + 5 >= MRING && q < 80) fill16((uint4*)g_mimg + (uint32_t)(((n + 5) % MRING) * 4096 + q * 32 + (threadIdx.x & 31)), SENT);
        }
        if (d[0] == 1.f) P.out[0] = __float2bfloat16(0.f);
      }
    }
  } else if (b < N_CHAIN + N_G) {
    if (wg == 0) { reg_inc<232>(); g_math<0>(P, sb); }
    else if (wg == 1) { reg_inc<232>(); g_math<1>(P, sb); }
    else if (wg == 2) { reg_dec<24>(); bar_arrive(15, 192); publish_y(); g_aux(P, sb); }
    else { reg_dec<24>(); g_load(P, sb); }
  } else if (b < N_CHAIN + N_G + N_O) {
    if (wg == 0) { reg_inc<160>(); o_math<0>(P, sb); }
    else if (wg == 1) { reg_inc<160>(); o_math<1>(P, sb); }
    else if (wg == 2) { reg_inc<160>(); o_math<2>(P, sb); }
    else { reg_dec<32>(); o_aux(P, sb); }
  } else {
    f_role(P, sb);
  }
}

}

extern "C" void kernel_launch(void* const* d_in, const int* in_sizes, int n_in, void* d_out, int out_size) {
  typedef CUresult (*Encode)(CUtensorMap*, CUtensorMapDataType, cuuint32_t, void*, const cuuint64_t*, const cuuint64_t*, const cuuint32_t*, const cuuint32_t*,
                             CUtensorMapInterleave, CUtensorMapSwizzle, CUtensorMapL2promotion, CUtensorMapFloatOOBfill);
  static Encode encode = nullptr;
  if (!encode) cudaGetDriverEntryPoint("cuTensorMapEncodeTiled", (void**)&encode, cudaEnableDefault);
  Params P;
  for (int i = 0; i < 11; i++) {
    const bool wo = i == 6 || i == 7;
    const cuuint64_t cols = wo ? DM : HD, rows = HD + DM - cols, pitch = cols * 2;
    const cuuint64_t dim[4][5] = {{cols, 2, 8, 2, 18}, {cols, 16, 1, 1, rows / 16}, {cols, 2, 4, 4, rows / 32}, {64, 16, 64, 2, 18}};
    const cuuint64_t stride[4][4] = {{8 * pitch, pitch, 16 * pitch, 32 * pitch}, {pitch, pitch, pitch, 16 * pitch},
                                     {pitch, 8 * pitch, 2 * pitch, 32 * pitch}, {pitch, 128, 16 * pitch, 32 * pitch}};
    const cuuint32_t box[4][5] = {{64, 2, 8, 1, 18}, {64, 16, 1, 1, 1}, {64, 2, 4, 2, 1}, {64, 16, 2, 1, 18}}, one[5] = {1, 1, 1, 1, 1};
    const int k = i < 3 ? 0 : i < 7 ? 1 : i < 8 ? 2 : 3;
    encode(&P.map[i], CU_TENSOR_MAP_DATA_TYPE_BFLOAT16, 5, d_in[wo ? 11 : 8 + (i & 7) % 3], dim[k], stride[k], box[k], one,
           CU_TENSOR_MAP_INTERLEAVE_NONE, CU_TENSOR_MAP_SWIZZLE_128B, CU_TENSOR_MAP_L2_PROMOTION_L2_128B, CU_TENSOR_MAP_FLOAT_OOB_FILL_NONE);
  }
  P.X = (const bf16*)d_in[0]; P.K = (const bf16*)d_in[1]; P.V = (const bf16*)d_in[2];
  P.shift = (const bf16*)d_in[3]; P.Hk = (const bf16*)d_in[4]; P.Dk = (const bf16*)d_in[5];
  P.mem0 = (const bf16*)d_in[7];
  P.Wq = (const bf16*)d_in[8]; P.Wk = (const bf16*)d_in[9]; P.Wv = (const bf16*)d_in[10]; P.Wo = (const bf16*)d_in[11];
  P.out = (bf16*)d_out;
  for (int i = 0; i < 24; i++) P.dly[i] = h_dly[i];
  cudaFuncSetAttribute(k_main, cudaFuncAttributeMaxDynamicSharedMemorySize, SMEM_BYTES);
  k_main<<<N_CTA, 512, SMEM_BYTES>>>(P);
}
```

```cpp
#include <cuda.h>
#include <cuda_runtime.h>
#include <cuda_bf16.h>
#include <stdint.h>

namespace {

typedef __nv_bfloat16 bf16;

constexpr int SEQ = 2048, DM = 576, HD = 4096, NSEG = 64;
#define PLACE 1
#define LAGV 7
constexpr int LAG = LAGV, STEPS = NSEG + LAG, RING = 8, QRING = 4;
static_assert(LAG < RING, "ring");
constexpr int N_CHAIN = 64, N_G = 48, N_O = 18, N_F = 2;
constexpr uint32_t SBASE = 1024;
constexpr uint32_t SENT = 0xFFFFFFFFu;
constexpr int SPIN_MAX = 1 << 22;

__device__ __forceinline__ uint32_t bid() {
  uint32_t b;
  asm volatile("mov.u32 %0, %%ctaid.x;" : "=r"(b));
  return b < 6 ? b + 106 : b < 8 ? b + 122 : b < 114 ? b - 8 : b < 130 ? b - 2 : b;
}
__device__ __forceinline__ uint32_t chain_id() { return blockIdx.x - (PLACE ? 8 : 0); }
constexpr int KVP = SEQ + 64;
__device__ __align__(1024) bf16 g_kvT[DM * KVP];
__device__ __align__(1024) bf16 g_yT[DM * SEQ];
__device__ __align__(1024) unsigned char g_lnimg[2 * NSEG * 9 * 4096];
__device__ __align__(1024) unsigned char g_qkv[QRING * N_CHAIN * 24576];
__device__ __align__(1024) unsigned char g_oimg[RING * N_CHAIN * 8192];
constexpr int ARING = 16;
static_assert(ARING >= LAG + 9, "accumulator ring");
__device__ __align__(1024) float g_oacc[ARING * 64 * DM];
constexpr int MRING = LAG + 4, N_GRP = 32 + MRING + 1;
constexpr int XB_M = 256, XB_F = XB_M + MRING * 8, XB_REF = XB_F + 2, N_CTA = N_CHAIN + N_G + N_O + N_F;
__device__ __align__(65536) uint4 g_xb[N_GRP * 4096];
#define g_mimg ((uint32_t*)(g_xb + XB_M * 512))
__device__ uint32_t g_near[N_GRP];
__device__ uint32_t g_side[N_CTA];
__device__ __align__(128) uint32_t g_gbar[3 * 32];
constexpr int FL_G = 0, FL_F = 96 * 8, FL_OCNT = FL_F + 2 * 8, OCRING = 16, FL_TICK = 992, FL_O = 2048, FL_SYNC = FL_O + 128;
static_assert(FL_OCNT + OCRING * 8 <= FL_TICK, "flag block");
#define g_fl ((uint32_t*)(g_xb + XB_F * 512))
__device__ __align__(1024) uint32_t g_lnflag[128 * 8];
#define TS(slot)

#define OTURN 2
#define LOCK0 3
#define FASTO 0
#define FASTG 0
#define NOBULK 0
#define VPAT 0x15bbd249u
#define XR 3
#define WFENCE 0
#define QPOS 0
#define VE 4
#define OGAP 2
#define NOCHAIN 0
#define BFENCE 2
#define ABL 0
#define ATTR 80
#define CNT(slot, tries)
#define T3(slot)
#define TR(slot)
#define TRV(slot, val)
#define TRD(slot, dep)
#define TRSYNC()
#define TRDUMP(n)
#define CLK(t) "{.reg .b64 x; .reg .b32 h; mov.u64 x, %%clock64; mov.b64 {" t ", h}, x;}"
__device__ __forceinline__ uint32_t clk() { uint32_t t; asm volatile(CLK("%0") : "=r"(t) :: "memory"); return t; }
__device__ __forceinline__ void wait_until(uint32_t t0, uint32_t d) {
  asm volatile("{.reg .pred p; .reg .u32 t;\n"
               "W: " CLK("t") " sub.u32 t, t, %0; setp.lt.s32 p, t, 0; @p bra.uni W;}"
               :: "r"(t0 + d) : "memory");
}
__device__ __forceinline__ uint32_t pack2(float lo, float hi) {
  uint32_t r; asm("cvt.rn.bf16x2.f32 %0, %1, %2;" : "=r"(r) : "f"(hi), "f"(lo)); return r;
}
__device__ __forceinline__ float bf_lo(uint32_t v) { return __uint_as_float(v << 16); }
__device__ __forceinline__ float bf_hi(uint32_t v) { return __uint_as_float(v & 0xFFFF0000u); }

__device__ __forceinline__ uint4 ld_relaxed4(const void* p) {
  uint4 v; asm volatile("ld.relaxed.gpu.global.v4.u32 {%0,%1,%2,%3}, [%4];" : "=r"(v.x), "=r"(v.y), "=r"(v.z), "=r"(v.w) : "l"(p) : "memory"); return v;
}
__device__ __forceinline__ void st_b128(void* p, uint32_t a, uint32_t b, uint32_t c, uint32_t d) {
  asm volatile("{.reg .b128 v; mov.b128 v, {%1,%2,%3,%4}; st.relaxed.gpu.global.b128 [%0], v;}" :: "l"(p), "r"(a), "r"(b), "r"(c), "r"(d) : "memory");
}
__device__ __forceinline__ void reload_b128(uint4& v, const void* p, uint32_t again) {
  asm volatile("{.reg .pred p; .reg .b128 v; setp.ne.u32 p, %5, 0; mov.b128 v, {%0,%1,%2,%3};\n"
               "@p ld.relaxed.gpu.global.b128 v, [%4]; mov.b128 {%0,%1,%2,%3}, v;}"
    : "+r"(v.x), "+r"(v.y), "+r"(v.z), "+r"(v.w) : "l"(p), "r"(again) : "memory");
}
__device__ __forceinline__ void reload4(uint4& v, const void* p, uint32_t again) {
  asm volatile("{.reg .pred p; setp.ne.u32 p, %5, 0; @p ld.relaxed.gpu.global.v4.u32 {%0,%1,%2,%3}, [%4];}"
    : "+r"(v.x), "+r"(v.y), "+r"(v.z), "+r"(v.w) : "l"(p), "r"(again) : "memory");
}
__device__ __forceinline__ void st_relaxed4(void* p, uint32_t a, uint32_t b, uint32_t c, uint32_t d) {
  asm volatile("st.relaxed.gpu.global.v4.u32 [%0], {%1,%2,%3,%4};" :: "l"(p), "r"(a), "r"(b), "r"(c), "r"(d) : "memory");
}
__device__ __forceinline__ void st_relaxed_if(void* p, uint32_t a, bool on) {
  asm volatile("{.reg .pred p; setp.ne.u32 p, %2, 0; @p st.relaxed.gpu.global.u32 [%0], %1;}" :: "l"(p), "r"(a), "r"((uint32_t)on) : "memory");
}
__device__ __forceinline__ uint32_t ld_acquire(const uint32_t* p) {
  uint32_t v; asm volatile("ld.acquire.gpu.global.u32 %0, [%1];" : "=r"(v) : "l"(p) : "memory"); return v;
}
__device__ __forceinline__ void st_release(uint32_t* p, uint32_t v) {
  asm volatile("st.release.gpu.global.u32 [%0], %1;" :: "l"(p), "r"(v) : "memory");
}
__device__ __forceinline__ void bulk_reduce(float* dst, uint32_t src, uint32_t bytes) {
  asm volatile("cp.reduce.async.bulk.global.shared::cta.bulk_group.add.f32 [%0], [%1], %2;" :: "l"(dst), "r"(src), "r"(bytes) : "memory");
}
__device__ __forceinline__ void bulk_done_inc(uint32_t* p) {
  asm volatile("cp.async.bulk.wait_group 0;\n"
               "fence.proxy.async.global;\nfence.release.gpu;\n"
               "red.relaxed.gpu.global.add.u32 [%0], 1;\nred.relaxed.gpu.global.add.u32 [%0+4096], 1;" :: "l"(p) : "memory");
}
__device__ __forceinline__ void flag_release(uint32_t* p, uint32_t v) {
  asm volatile("fence.release.gpu;\nst.relaxed.gpu.global.u32 [%0], %1;\nst.relaxed.gpu.global.u32 [%0+4096], %1;" :: "l"(p), "r"(v) : "memory");
}
__device__ __forceinline__ void spin_guard(int& it) {
  asm volatile("{.reg .pred p; add.s32 %0, %0, 1; setp.gt.s32 p, %0, %1; @p trap;}" : "+r"(it) : "n"(SPIN_MAX));
}
__device__ __forceinline__ void wait_flag(const uint32_t* p, uint32_t v) {
  int it = 0;
  while (ld_acquire(p) < v) spin_guard(it);
}
__device__ __forceinline__ void wait_flags(const uint32_t* p, uint32_t v) {
  int it = 0;
  while (true) {
    uint32_t x; asm volatile("ld.relaxed.gpu.global.u32 %0, [%1];" : "=r"(x) : "l"(p) : "memory");
    if (__all_sync(~0u, x >= v)) break;
    spin_guard(it);
  }
  asm volatile("fence.acquire.gpu;" ::: "memory");
}
__device__ __forceinline__ uint32_t timer_offset() {
  uint32_t g0, g;
  asm volatile("mov.u32 %0, %%globaltimer_lo;" : "=r"(g0) :: "memory");
  do { asm volatile("mov.u32 %0, %%globaltimer_lo;" : "=r"(g) :: "memory"); } while (g == g0);
  return (g >> 5) * 58 - clk();
}
__device__ __forceinline__ void grid_arrive(int i) {
  asm volatile("red.release.gpu.global.add.u32 [%0], %1;" :: "l"(g_gbar + i * 32), "r"(bid() ? 1u : 257u - N_CTA) : "memory");
}
__device__ __forceinline__ void grid_wait(int i, uint32_t gen) {
  int it = 0;
  while (((ld_acquire(g_gbar + i * 32) ^ gen) >> 8) == 0) spin_guard(it);
}
__device__ __forceinline__ bool elect() {
  uint32_t r; asm volatile("{.reg .pred p; elect.sync _|p, -1; selp.u32 %0, 1, 0, p;}" : "=r"(r)); return r;
}
__device__ __forceinline__ void bar_sync(int id, int cnt) { asm volatile("bar.sync %0, %1;" :: "r"(id), "r"(cnt) : "memory"); }
__device__ __forceinline__ void bar_arrive(int id, int cnt) { asm volatile("bar.arrive %0, %1;" :: "r"(id), "r"(cnt) : "memory"); }
template <int id, int cnt> __device__ __forceinline__ void bar_arrive_after(uint32_t a, uint32_t b) {
  asm volatile("{.reg .pred p; setp.ne.u32 p, %2, 0xfff12345; setp.ne.and.u32 p, %3, 0xfff12345, p; @p bar.arrive %0, %1;}" :: "n"(id), "n"(cnt), "r"(a), "r"(b) : "memory");
}
template <int id, int cnt> __device__ __forceinline__ void bar_sync_after(uint32_t a) {
  asm volatile("{.reg .pred p; setp.ne.u32 p, %2, 0xfff12345; @p bar.sync %0, %1;}" :: "n"(id), "n"(cnt), "r"(a) : "memory");
}
__device__ __forceinline__ void fence_async_smem() { asm volatile("fence.proxy.async.shared::cta;" ::: "memory"); }
__device__ __forceinline__ void fence_async_global() { asm volatile("fence.proxy.async.global;" ::: "memory"); }
__device__ __forceinline__ void mbar_init(uint32_t mb, int cnt) { asm volatile("mbarrier.init.shared::cta.b64 [%0], %1;" :: "r"(mb), "r"(cnt) : "memory"); }
__device__ __forceinline__ void mbar_arrive(uint32_t mb) { asm volatile("mbarrier.arrive.shared::cta.b64 _, [%0];" :: "r"(mb) : "memory"); }
__device__ __forceinline__ void mbar_arrive_after(uint32_t mb, uint32_t a, uint32_t lane) {
  asm volatile("{.reg .pred p; setp.ne.u32 p, %1, 0xfff12345; setp.eq.and.u32 p, %2, 0, p; @p mbarrier.arrive.shared::cta.b64 _, [%0];}" :: "r"(mb), "r"(a), "r"(lane) : "memory");
}
__device__ __forceinline__ void mbar_expect(uint32_t mb, uint32_t bytes) {
  asm volatile("mbarrier.arrive.expect_tx.shared::cta.b64 _, [%0], %1;" :: "r"(mb), "r"(bytes) : "memory");
}
__device__ __forceinline__ void mbar_wait_guard(uint32_t mb, uint32_t parity) {
  uint32_t ok; int it = 0;
  while (true) {
    asm volatile("{.reg .pred p; mbarrier.try_wait.parity.shared::cta.b64 p, [%1], %2; selp.u32 %0, 1, 0, p;}" : "=r"(ok) : "r"(mb), "r"(parity) : "memory");
    if (ok) break;
    spin_guard(it);
  }
}
__device__ __forceinline__ void mbar_wait(uint32_t mb, uint32_t parity) {
  asm volatile("{.reg .pred p;\nW: mbarrier.try_wait.parity.shared::cta.b64 p, [%0], %1;\n@!p bra W;}" :: "r"(mb), "r"(parity) : "memory");
}
__device__ __forceinline__ void bulk_load(uint32_t dst, const void* src, uint32_t bytes, uint32_t mb) {
  asm volatile("cp.async.bulk.shared::cluster.global.mbarrier::complete_tx::bytes [%0], [%1], %2, [%3];" :: "r"(dst), "l"(src), "r"(bytes), "r"(mb) : "memory");
}
__device__ __forceinline__ void bulk_store(void* dst, uint32_t src, uint32_t bytes) {
  asm volatile("cp.async.bulk.global.shared::cta.bulk_group [%0], [%1], %2;" :: "l"(dst), "r"(src), "r"(bytes) : "memory");
}
__device__ __forceinline__ void cp_async16(uint32_t dst, const void* src) {
  asm volatile("cp.async.cg.shared.global [%0], [%1], 16;" :: "r"(dst), "l"(src) : "memory");
}
__device__ __forceinline__ void cp_async_wait_all() { asm volatile("cp.async.wait_all;" ::: "memory"); }
__device__ __forceinline__ uint32_t mapa(uint32_t a, uint32_t rank) {
  uint32_t r; asm("mapa.shared::cluster.u32 %0, %1, %2;" : "=r"(r) : "r"(a), "r"(rank)); return r;
}
__device__ __forceinline__ void st_async4(uint32_t dst, float a, float b, float c, float d, uint32_t mb) {
  asm volatile("st.async.shared::cluster.mbarrier::complete_tx::bytes.v4.f32 [%0], {%1,%2,%3,%4}, [%5];" :: "r"(dst), "f"(a), "f"(b), "f"(c), "f"(d), "r"(mb) : "memory");
}
__device__ __forceinline__ void st_async2(uint32_t dst, float a, float b, uint32_t mb) {
  asm volatile("st.async.shared::cluster.mbarrier::complete_tx::bytes.v2.f32 [%0], {%1,%2}, [%3];" :: "r"(dst), "f"(a), "f"(b), "r"(mb) : "memory");
}
__device__ __forceinline__ void st_async1(uint32_t dst, uint32_t a, uint32_t mb) {
  asm volatile("st.async.shared::cluster.mbarrier::complete_tx::bytes.u32 [%0], %1, [%2];" :: "r"(dst), "r"(a), "r"(mb) : "memory");
}
__device__ __forceinline__ uint4 lds128(uint32_t a) {
  uint4 v; asm volatile("ld.shared.v4.u32 {%0,%1,%2,%3}, [%4];" : "=r"(v.x), "=r"(v.y), "=r"(v.z), "=r"(v.w) : "r"(a) : "memory"); return v;
}
__device__ __forceinline__ uint2 lds64(uint32_t a) {
  uint2 v; asm volatile("ld.shared.v2.u32 {%0,%1}, [%2];" : "=r"(v.x), "=r"(v.y) : "r"(a) : "memory"); return v;
}
__device__ __forceinline__ uint32_t lds32(uint32_t a) {
  uint32_t v; asm volatile("ld.shared.u32 %0, [%1];" : "=r"(v) : "r"(a) : "memory"); return v;
}
__device__ __forceinline__ void sts128(uint32_t a, uint4 v) {
  asm volatile("st.shared.v4.u32 [%0], {%1,%2,%3,%4};" :: "r"(a), "r"(v.x), "r"(v.y), "r"(v.z), "r"(v.w) : "memory");
}
__device__ __forceinline__ void sts64(uint32_t a, uint32_t x, uint32_t y) {
  asm volatile("st.shared.v2.u32 [%0], {%1,%2};" :: "r"(a), "r"(x), "r"(y) : "memory");
}
__device__ __forceinline__ void sts32(uint32_t a, uint32_t x) { asm volatile("st.shared.u32 [%0], %1;" :: "r"(a), "r"(x) : "memory"); }
__device__ __forceinline__ void ldsm4(uint32_t& r0, uint32_t& r1, uint32_t& r2, uint32_t& r3, uint32_t a) {
  asm volatile("ldmatrix.sync.aligned.m8n8.x4.shared.b16 {%0,%1,%2,%3}, [%4];" : "=r"(r0), "=r"(r1), "=r"(r2), "=r"(r3) : "r"(a) : "memory");
}
__device__ __forceinline__ void ldsm4t(uint32_t& r0, uint32_t& r1, uint32_t& r2, uint32_t& r3, uint32_t a) {
  asm volatile("ldmatrix.sync.aligned.m8n8.x4.trans.shared.b16 {%0,%1,%2,%3}, [%4];" : "=r"(r0), "=r"(r1), "=r"(r2), "=r"(r3) : "r"(a) : "memory");
}
__device__ __forceinline__ void stsm4(uint32_t a, uint32_t r0, uint32_t r1, uint32_t r2, uint32_t r3) {
  asm volatile("stmatrix.sync.aligned.m8n8.x4.shared.b16 [%0], {%1,%2,%3,%4};" :: "r"(a), "r"(r0), "r"(r1), "r"(r2), "r"(r3) : "memory");
}
__device__ __forceinline__ uint32_t movmat(uint32_t a) {
  uint32_t d; asm volatile("movmatrix.sync.aligned.m8n8.trans.b16 %0, %1;" : "=r"(d) : "r"(a)); return d;
}
__device__ __forceinline__ void mma16(float* d, uint32_t a0, uint32_t a1, uint32_t a2, uint32_t a3, uint32_t b0, uint32_t b1) {
  asm volatile("mma.sync.aligned.m16n8k16.row.col.f32.bf16.bf16.f32 {%0,%1,%2,%3}, {%4,%5,%6,%7}, {%8,%9}, {%0,%1,%2,%3};"
    : "+f"(d[0]), "+f"(d[1]), "+f"(d[2]), "+f"(d[3]) : "r"(a0), "r"(a1), "r"(a2), "r"(a3), "r"(b0), "r"(b1));
}
__device__ __forceinline__ void mma8(float* d, uint32_t a0, uint32_t a1, uint32_t b0) {
  asm volatile("mma.sync.aligned.m16n8k8.row.col.f32.bf16.bf16.f32 {%0,%1,%2,%3}, {%4,%5}, {%6}, {%0,%1,%2,%3};"
    : "+f"(d[0]), "+f"(d[1]), "+f"(d[2]), "+f"(d[3]) : "r"(a0), "r"(a1), "r"(b0));
}
__device__ __forceinline__ float rcp(float x) { float r; asm("rcp.approx.ftz.f32 %0, %1;" : "=f"(r) : "f"(x)); return r; }
__device__ __forceinline__ float ex2(float x) { float r; asm("ex2.approx.ftz.f32 %0, %1;" : "=f"(r) : "f"(x)); return r; }

__host__ __device__ constexpr uint64_t mkdesc(uint32_t off, uint32_t lbo, uint32_t sbo, uint32_t swz) {
  return (uint64_t)((SBASE + off) >> 4) | ((uint64_t)(lbo >> 4) << 16) | ((uint64_t)(sbo >> 4) << 32) | ((uint64_t)swz << 62);
}
__host__ __device__ constexpr uint64_t desc_sw128(uint32_t off) { return mkdesc(off, 16, 1024, 1); }
__host__ __device__ constexpr uint64_t desc_n16(uint32_t off) { return mkdesc(off, 256, 128, 0); }
__host__ __device__ constexpr uint64_t desc_m(uint32_t off) { return mkdesc(off, 16, 256, 3); }

__host__ __device__ constexpr uint64_t desc_sw64(uint32_t off) { return mkdesc(off, 16, 512, 2); }

__device__ __forceinline__ void wg_fence() { asm volatile("wgmma.fence.sync.aligned;" ::: "memory"); }
__device__ __forceinline__ void wg_commit() { asm volatile("wgmma.commit_group.sync.aligned;" ::: "memory"); }
template <int N> __device__ __forceinline__ void wg_wait() { asm volatile("wgmma.wait_group.sync.aligned %0;" :: "n"(N) : "memory"); }

#define ACC8(d) "+f"(d[0]), "+f"(d[1]), "+f"(d[2]), "+f"(d[3]), "+f"(d[4]), "+f"(d[5]), "+f"(d[6]), "+f"(d[7])
#define ACC32(d) ACC8(d), ACC8((d + 8)), ACC8((d + 16)), ACC8((d + 24))
#define R8 "{%0,%1,%2,%3,%4,%5,%6,%7}"
#define R32 "{%0,%1,%2,%3,%4,%5,%6,%7,%8,%9,%10,%11,%12,%13,%14,%15,%16,%17,%18,%19,%20,%21,%22,%23,%24,%25,%26,%27,%28,%29,%30,%31}"
template <int SD> __device__ __forceinline__ void wg_rs16(float* d, const uint32_t* a, uint64_t db) {
  asm volatile("wgmma.mma_async.sync.aligned.m64n16k16.f32.bf16.bf16 " R8 ", {%8,%9,%10,%11}, %12, %13, 1, 1, 1;"
    : ACC8(d) : "r"(a[0]), "r"(a[1]), "r"(a[2]), "r"(a[3]), "l"(db), "n"(SD));
}
template <int SD> __device__ __forceinline__ void wg_ss16(float* d, uint64_t da, uint64_t db) {
  asm volatile("wgmma.mma_async.sync.aligned.m64n16k16.f32.bf16.bf16 " R8 ", %8, %9, %10, 1, 1, 1, 1;"
    : ACC8(d) : "l"(da), "l"(db), "n"(SD));
}
template <int SD, uint64_t DA, uint64_t DB> __device__ __forceinline__ void wg_ss16o(float* d, uint32_t oa, uint32_t ob) {
  asm volatile("{.reg .b32 x, y; .reg .b64 a, b; add.u32 x, %8, %10; add.u32 y, %9, %12; mov.b64 a, {x, %11}; mov.b64 b, {y, %13};\n"
               "wgmma.mma_async.sync.aligned.m64n16k16.f32.bf16.bf16 " R8 ", a, b, %14, 1, 1, 1, 1;}"
    : ACC8(d) : "r"(oa), "r"(ob), "n"((uint32_t)DA), "n"((uint32_t)(DA >> 32)), "n"((uint32_t)DB), "n"((uint32_t)(DB >> 32)), "n"(SD));
}
template <int SD> __device__ __forceinline__ void wg_rs64(float* d, const uint32_t* a, uint64_t db) {
  asm volatile("wgmma.mma_async.sync.aligned.m64n64k16.f32.bf16.bf16 " R32 ", {%32,%33,%34,%35}, %36, %37, 1, 1, 0;"
    : ACC32(d) : "r"(a[0]), "r"(a[1]), "r"(a[2]), "r"(a[3]), "l"(db), "n"(SD));
}
template <int SD> __device__ __forceinline__ void wg_ss64(float* d, uint64_t da, uint64_t db) {
  asm volatile("wgmma.mma_async.sync.aligned.m64n64k16.f32.bf16.bf16 " R32 ", %32, %33, %34, 1, 1, 1, 0;"
    : ACC32(d) : "l"(da), "l"(db), "n"(SD));
}
#define WG_RSO(NAME, SHAPE, REGS, ACC, A, TB) \
template <int SD, uint64_t DB> __device__ __forceinline__ void NAME(float* d, uint32_t a0, uint32_t a1, uint32_t a2, uint32_t a3, uint32_t ob) { \
  asm volatile("{.reg .b64 b; mov.b64 b, {" A(4) ", " A(5) "};\nwgmma.mma_async.sync.aligned." SHAPE ".f32.bf16.bf16 " REGS \
               ", {" A(0) "," A(1) "," A(2) "," A(3) "}, b, " A(6) ", 1, 1, " TB ";}" \
    : ACC(d) : "r"(a0), "r"(a1), "r"(a2), "r"(a3), "r"(ob + (uint32_t)DB), "n"((uint32_t)(DB >> 32)), "n"(SD)); \
}
#define ACC4(d) "+f"(d[0]), "+f"(d[1]), "+f"(d[2]), "+f"(d[3])
#define ACC16(d) ACC8(d), ACC8((d + 8))
#define OP4(i) OP4_##i
#define OP4_0 "%4"
#define OP4_1 "%5"
#define OP4_2 "%6"
#define OP4_3 "%7"
#define OP4_4 "%8"
#define OP4_5 "%9"
#define OP4_6 "%10"
#define OP16(i) OP16_##i
#define OP16_0 "%16"
#define OP16_1 "%17"
#define OP16_2 "%18"
#define OP16_3 "%19"
#define OP16_4 "%20"
#define OP16_5 "%21"
#define OP16_6 "%22"
#define OP32(i) OP32_##i
#define OP32_0 "%32"
#define OP32_1 "%33"
#define OP32_2 "%34"
#define OP32_3 "%35"
#define OP32_4 "%36"
#define OP32_5 "%37"
#define OP32_6 "%38"
WG_RSO(wg_rs8o, "m64n8k16", "{%0,%1,%2,%3}", ACC4, OP4, "1")
#define R16 "{%0,%1,%2,%3,%4,%5,%6,%7,%8,%9,%10,%11,%12,%13,%14,%15}"
WG_RSO(wg_rs32o, "m64n32k16", R16, ACC16, OP16, "1")
WG_RSO(wg_rs64o, "m64n64k16", R32, ACC32, OP32, "0")
WG_RSO(wg_rs32k, "m64n32k16", R16, ACC16, OP16, "0")
template <uint64_t DA, uint64_t DB> __device__ __forceinline__ void wg_ss32k(float* d, uint32_t ob) {
  asm volatile("{.reg .b64 b; mov.b64 b, {%17, %18};\nwgmma.mma_async.sync.aligned.m64n32k16.f32.bf16.bf16 " R16 ", %16, b, 1, 1, 1, 1, 0;}"
    : ACC16(d) : "l"(DA), "r"(ob + (uint32_t)DB), "n"((uint32_t)(DB >> 32)));
}
template <int N> __device__ __forceinline__ void reg_inc() { asm volatile("setmaxnreg.inc.sync.aligned.u32 %0;" :: "n"(N)); }
template <int N> __device__ __forceinline__ void reg_dec() { asm volatile("setmaxnreg.dec.sync.aligned.u32 %0;" :: "n"(N)); }
__device__ __forceinline__ void cluster_sync() {
  asm volatile("barrier.cluster.arrive.relaxed.aligned;\nbarrier.cluster.wait.aligned;" ::: "memory");
}

template <int KS>
__device__ __forceinline__ void load_frags(uint32_t* a, uint32_t src) {
  const int lane = threadIdx.x & 31, w = (threadIdx.x >> 5) & 3;
  const int k = ((lane >> 4) << 3) + (lane & 7), u = w * 2 + ((lane >> 3) & 1);
  const uint32_t base = src + k * 128 + ((u ^ (k & 7)) << 4);
#pragma unroll
  for (int ks = 0; ks < KS; ks++) ldsm4t(a[ks * 4], a[ks * 4 + 1], a[ks * 4 + 2], a[ks * 4 + 3], base + ks * 2048);
}

__device__ __forceinline__ uint32_t badd2(uint32_t a, uint32_t b) { uint32_t r; asm("add.rn.bf16x2 %0, %1, %2;" : "=r"(r) : "r"(a), "r"(b)); return r; }
__device__ __forceinline__ uint32_t bsub2(uint32_t a, uint32_t b) { uint32_t r; asm("sub.rn.bf16x2 %0, %1, %2;" : "=r"(r) : "r"(a), "r"(b)); return r; }
__device__ __forceinline__ uint32_t bmul2(uint32_t a, uint32_t b) { uint32_t r; asm("mul.rn.bf16x2 %0, %1, %2;" : "=r"(r) : "r"(a), "r"(b)); return r; }
__device__ __forceinline__ uint32_t bfma2(uint32_t a, uint32_t b, uint32_t c) { uint32_t r; asm("fma.rn.bf16x2 %0, %1, %2, %3;" : "=r"(r) : "r"(a), "r"(b), "r"(c)); return r; }
template <int R> __device__ __forceinline__ void layernorm9(const uint32_t* x, uint32_t* o) {
  const uint32_t ones = 0x3F803F80u;
  float a[R][3][4], q[R], s[R];
#pragma unroll
  for (int i = 0; i < 9 * R; i++) {
    float* d = a[i % R][i / R % 3];
    if (i < 3 * R) d[0] = d[1] = d[2] = d[3] = 0.f;
    mma8(d, x[i % R * 9 + i / R], ones, x[i % R * 9 + i / R]);
  }
#pragma unroll
  for (int r = 0; r < R; r++) {
    q[r] = threadIdx.x & 4 ? a[r][0][1] + a[r][1][1] + a[r][2][1] : a[r][0][0] + a[r][1][0] + a[r][2][0];
    s[r] = (a[r][0][2] + a[r][0][3]) + (a[r][1][2] + a[r][1][3]) + (a[r][2][2] + a[r][2][3]);
  }
#pragma unroll
  for (int r = 0; r < R; r++) { q[r] += __shfl_xor_sync(~0u, q[r], 4); s[r] += __shfl_xor_sync(~0u, s[r], 1); }
#pragma unroll
  for (int r = 0; r < R; r++) { q[r] += __shfl_xor_sync(~0u, q[r], 9); s[r] += __shfl_xor_sync(~0u, s[r], 2); }
#pragma unroll
  for (int r = 0; r < R; r++) q[r] = __shfl_sync(~0u, q[r], 0) + __shfl_sync(~0u, q[r], 18);
#pragma unroll
  for (int r = 0; r < R; r++) {
    const float mean = s[r] * (1.f / DM), var = fmaxf(fmaf(q[r], 1.f / DM, -mean * mean), 0.f);
    float sd;
    asm("sqrt.approx.ftz.f32 %0, %1;" : "=f"(sd) : "f"(bf_lo(pack2(bf_lo(pack2(var, 0.f)) + 1e-5f, 0.f))));
    const float inv = rcp(bf_lo(pack2(sd, 0.f)));
    const uint32_t mb = pack2(mean, mean), hi = pack2(inv, inv), lo = pack2(inv - bf_lo(hi), inv - bf_lo(hi));
#pragma unroll
    for (int i = r * 9; i < r * 9 + 9; i++) {
      const uint32_t d = bsub2(x[i], mb);
      o[i] = bfma2(d, hi, bmul2(d, lo));
    }
  }
}
__device__ __forceinline__ void store_ln_row(int layer, int tok, const uint32_t* o) {
  const int lane = threadIdx.x & 31, r = tok & 31;
  unsigned char* p = g_lnimg + (size_t)(layer * NSEG + (tok >> 5)) * (9 * 4096) + r * 128 + (((lane >> 2) ^ (r & 7)) << 4) + (lane & 3) * 4;
#pragma unroll
  for (int i = 0; i < 9; i++) *(uint32_t*)(p + i * 4096) = o[i];
}
struct Params { CUtensorMap map[11]; const bf16 *X, *K, *V, *shift, *Hk, *Dk, *mem0, *Wq, *Wk, *Wv, *Wo; bf16* out; uint32_t dly[24]; };
#define PACE P.dly[20]
#define S1G P.dly[21]
#define S1DLY P.dly[22]
#define DLYS P.dly[0]
#define DLYW P.dly[1]
#define KLATE P.dly[2]
#define DLYQ P.dly[3]
#define DLYK P.dly[4]
#define DLYG P.dly[5]
#define KWIN P.dly[6]
#define KMIN P.dly[7]
uint32_t h_dly[24] = {900, 350, 100, 60, 3570, 4330, 2750, 1300, 1600, 1700, 1840, 2140, 2290, 2420, 2950, 3070, 3230, 3380, 3530, 7500, 165, 12000, 18000, 4000};

constexpr uint32_t C_W = 0, C_M = 147456, C_KV = C_M + 18432, C_OS = C_KV + 24576, C_QM = C_KV + 32768, C_KM = C_QM + 2048,
                   C_VM = C_KM + 2048, C_OI = C_VM + 2048, C_SX = C_OI + 4096, C_KM2 = C_SX + 2560, C_VM2 = C_KM2 + 128,
                   C_KV2 = C_KM2 + 2048, C_Q = C_KV2 + 8192, C_BAR = C_Q + 8192;
constexpr uint32_t CB_FULL = C_BAR, CB_REF = C_BAR + 16, CB_SX = C_BAR + 32, CB_OX = C_BAR + 40, CB_XX = C_BAR + 48, CB_Q = C_BAR + 56, C_BAD = C_BAR + 64, W_BAR = C_BAR + 80, T_BAR = W_BAR + 24, S_GEN = C_BAR + 128, C_REF = C_BAR + 132, CB_VF = C_BAR + 144, CB_M = C_BAR + 160, CB_MV = C_BAR + 200;
constexpr uint32_t G_W = 0, G_RING = 147456, G_W2 = G_RING + 9 * 8192, G_BAR = G_W2 + 8192;
constexpr uint32_t O_W = 0, O_RING = 3 * 40960, O_ST = O_RING + 11 * 8192, O_BAR = O_ST + 16384, OB_ST = O_BAR + 64;
constexpr uint32_t F_A = 0, F_XY = 36864, F_L = F_XY + 36864, F_X = F_L + 18432, F_Y = F_L + 2 * 36864, F_BAR = C_BAR;
constexpr uint32_t SMEM_BYTES = C_BAR + 256;
static_assert(G_BAR + 256 <= SMEM_BYTES && O_BAR + 256 <= SMEM_BYTES && F_BAR + 16 <= SMEM_BYTES && SMEM_BYTES <= 232448, "smem map");
enum { B_INIT = 1, B_M, B_QK, B_S, B_V, B_O, B_X, B_WG0, B_WG1, B_WG2, B_G, B_OE, B_T, B_R };

__device__ __forceinline__ uint4 pack_partial(const float* d, uint32_t tag) {
  uint32_t x;
  asm("lop3.b32 %0, %1, 1, %2, 0xb8;" : "=r"(x) : "r"(pack2(d[0], d[1])), "r"(tag));
  return make_uint4(x, pack2(d[4], d[5]), pack2(d[2], d[3]), pack2(d[6], d[7]));
}
__device__ __forceinline__ void store_partial(uint4* p, const uint4& v) { st_b128(p, v.x, v.y, v.z, v.w); }
__device__ __forceinline__ void gather_reduce(const uint32_t* p, uint32_t* dst, uint32_t m0, bool shared, uint32_t tag, uint32_t lane, uint32_t sb, int n, int TS0) {
  int tries = 0;
  float u, v;
  bool bad;
  TR(TS0);
  do {
    uint32_t x[16];
#pragma unroll
    for (int i = 0; i < 16; i++) asm volatile("ld.relaxed.gpu.global.u32 %0, [%1];" : "=r"(x[i]) : "l"(p + i * 64) : "memory");
    tries++;
    float a[2] = {bf_lo(x[0]), bf_lo(x[1])}, b[2] = {bf_hi(x[0]), bf_hi(x[1])};
    uint32_t t = 0;
#pragma unroll
    for (int i = 2; i < 16; i++) { a[i & 1] += bf_lo(x[i]); b[i & 1] += bf_hi(x[i]); }
#pragma unroll
    for (int i = 0; i < 16; i += 4)
      asm("{.reg .b32 y, z; lop3.b32 y, %1, %2, %5, 0x7e; lop3.b32 z, %3, %4, %5, 0x7e; lop3.b32 %0, %0, y, z, 0xfe;}"
          : "+r"(t) : "r"(x[i]), "r"(x[i + 1]), "r"(x[i + 2]), "r"(x[i + 3]), "r"(tag));
    u = a[0] + a[1]; v = b[0] + b[1];
    bad = __any_sync(~0u, (t & 1) && !(lane & 3));
    if (shared) { u += __shfl_xor_sync(~0u, u, 8); v += __shfl_xor_sync(~0u, v, 8); }
    u += __shfl_xor_sync(~0u, u, 16);
    v += __shfl_xor_sync(~0u, v, 16);
    st_relaxed_if(dst, n < LAG && (lane & 1) ? m0 : pack2(u, v), !bad);
  } while (bad);
  TR(TS0 + 3); TRV(TS0 + 2, tries);
  CNT((TS0 - 16) >> 2, tries);
}
__device__ __forceinline__ uint32_t sent_bad(const uint4& v) { return max(max(v.x, v.y), max(v.z, v.w)) == SENT; }

__host__ __device__ constexpr int o_ks(int s) { return s & (s < 8 ? 3 : 7); }
__host__ __device__ constexpr bool o_reg(int s) { return s < 8 ? (s & 3) != 3 : !(s & 1); }
__host__ __device__ constexpr int o_slot(int s) { return s < 8 ? (o_reg(s) ? s - (s >> 2) : s >> 2) : s & 1 ? (s - 5) >> 1 : (s + 4) >> 1; }
__device__ __forceinline__ int g_unit(int wg) {
  const int i = bid() - N_CHAIN;
  return i < 32 ? wg * 64 + i : 2 * i - 32 + wg;
}
__device__ __forceinline__ uint32_t pinned(uint32_t v) { return __shfl_sync(~0u, v, threadIdx.x & 31); }
template <class T> __device__ __forceinline__ T* pinned(T* p) { return (T*)__shfl_sync(~0u, (unsigned long long)p, threadIdx.x & 31); }
enum { CHAIN, GROLE, OROLE };
template <int ROLE, bool SYNC> __device__ __forceinline__ void load_box(const Params& P, uint32_t sb, bool regs, int wg, int i, uint32_t mb, bool on) {
  const int b = bid();
  int map, col = 0, ks = 0, c2 = 0, c3 = 0;
  uint32_t dst = wg * 73728;
  if (ROLE == CHAIN) {
    const int k = i - 1, st = regs ? (k < 6 ? k + k / 3 : 2 * k - 4) : k < 2 ? 4 * k + 3 : 2 * k + 5;
    dst += i ? (17 + i) * 2048 : 0;
    if (wg || i == 0) { map = wg + i; col = b * 64; c3 = !regs; }
    else if (!regs && k >= 14) { map = 6; ks = b * 4 + k - 14; }
    else { map = 6; col = 64 + (st < 8 ? (st >> 2) * 64 : (st >> 3) * 128 + (b & 1) * 64); ks = (b * 4) ^ o_ks(st); }
  } else if (ROLE == GROLE) {
    const int q = g_unit(wg);
    map = ((q >> 5) + 1) % 3;
    if (i) { map += 3; col = (q & 31) * 128 + (i - 1) * 64; ks = 34; dst = G_W2 + wg * 4096 + (i - 1) * 2048; }
    else { map += 8; c2 = (q & 31) * 2; c3 = !regs; }
  } else {
    const int o = b - N_CHAIN - N_G, ksl = o / 3;
    map = 7; col = ((o % 3) * 3 + (wg + ksl) % 3) * 64; dst = (wg * (regs ? 24 : 20) + i) * 2048;
    ks = (ksl * 11 - max(ksl - 4, 0)) * 4 + (regs ? i / 3 * 5 + i % 3 * 2 : i < 16 ? i / 2 * 5 + 1 + i % 2 * 2 : i + 24);
    c3 = (ks & 1) * 2; ks >>= 1;
  }
  if (SYNC) { col = pinned(col); ks = pinned(ks); bar_sync(B_WG0 + wg, 256); }
  if (on) asm volatile("cp.async.bulk.tensor.5d.shared::cluster.global.tile.mbarrier::complete_tx::bytes [%0], [%1, {%2, %3, %4, %5, %6}], [%7];"
               :: "r"(sb + dst), "l"(&P.map[map]), "r"(col), "r"(0), "r"(c2), "r"(c3), "r"(ks), "r"(mb) : "memory");
}
template <int ROLE, bool SYNC = false> __device__ __forceinline__ void load_wg(const Params& P, uint32_t sb, bool regs, int wg, int quarter) {
  const int i = (threadIdx.x & 31) * 4 + quarter;
  const int n = ROLE == CHAIN ? 36 : ROLE == GROLE ? (regs ? 38 : 36) : regs ? 24 : bid() < N_CHAIN + N_G + 12 ? 20 : 16;
  load_box<ROLE, SYNC>(P, sb, regs, wg, i, sb + W_BAR + wg * 8, i < (ROLE == CHAIN ? (wg ? 2 : 19) : ROLE == GROLE ? n - 35 : n));
  if (i == 0) mbar_expect(sb + W_BAR + wg * 8, n * 2048);
  __syncwarp();
}
__device__ __forceinline__ uint32_t near_half(uint32_t blk, uint32_t reader) {
  return __ldcg(g_near + (blk >> 3)) ^ (~blk & 1) ^ __ldcg(g_side + (blk >> 3)) ^ __ldcg(g_side + reader);
}

__device__ __forceinline__ uint32_t opaque_tid() { uint32_t t; asm volatile("mov.u32 %0, %%tid.x;" : "=r"(t)); return t; }
__device__ __forceinline__ void m_fetch(uint32_t sb, uint32_t src, uint32_t b, uint32_t mb) {
  bulk_load(sb + C_M + (b ? b * 4096 - 2048 : 0), (const unsigned char*)g_mimg + ((src ^ ((b & 1) * 4096)) + b * 8192), b ? 4096 : 2048, mb);
}
__device__ __forceinline__ uint32_t m_probe(uint32_t lane) { return lane * 32 + (lane & 4) * 4 + (lane >> 3) * 4; }
__device__ __forceinline__ uint32_t m_max(uint32_t a, uint32_t b) {
  return max(max(lds32(a), lds32(a + 1024)), max(lds32(b), lds32(b + 1024)));
}
template <int S0, int N> __device__ __forceinline__ void o_steps(float* d, const uint32_t* a) {
  constexpr int SD = o_ks(S0) != 0;
  if constexpr (o_reg(S0)) wg_rs16<SD>(d, a + (18 + o_slot(S0)) * 4, desc_n16(C_OI + o_ks(S0) * 512));
  else wg_ss16<SD>(d, desc_sw128(C_W + (18 + o_slot(S0)) * 2048), desc_n16(C_OI + o_ks(S0) * 512));
  if constexpr (N > 1) o_steps<S0 + 1, N - 1>(d, a);
}
template <int BASE, int KS, int N> __device__ __forceinline__ void m_steps(float* d, const uint32_t* a, uint32_t oa) {
  wg_rs16<KS != 0>(d, a + (BASE + KS / 2) * 4, desc_m(C_M + KS * 512));
  if constexpr (KS >= 36 - 2 * XR) wg_rs16<1>(d, a + (18 + XR + KS / 2) * 4, desc_m(C_M + KS * 512 + 512));
  else wg_ss16o<1, desc_sw128(C_W + (BASE + KS / 2) * 2048), desc_m(C_M + KS * 512 + 512)>(d, oa, 0);
  if constexpr (N > 2) m_steps<BASE, KS + 2, N - 2>(d, a, oa);
}

template <int I, int R, int S> __device__ __forceinline__ void v_steps(float* d, const uint32_t* a) {
  constexpr bool reg = (VPAT >> I) & 1;
  if constexpr (reg) wg_rs16<1>(d, a + (18 + R) * 4, desc_m(C_M + R * 1024));
  else wg_ss16<1>(d, desc_sw128(C_W + (54 + S) * 2048), desc_m(C_M + S * 1024 + 512));
  if constexpr (I < 31) v_steps<I + 1, R + reg, S + !reg>(d, a);
  else static_assert(R + reg == 18, "pattern");
}

__device__ __forceinline__ void chain_proj(const Params& P, uint32_t sb) {
  const uint32_t c = chain_id(), h = c >> 1, j = c & 1, wid = __shfl_sync(~0u, threadIdx.x >> 5, 0), wg = wid >> 2, w = wid & 3;
  const uint32_t t = threadIdx.x & 127, lane = pinned(t & 31), mine = pinned(sb + t * 16), rb = mapa(sb, j ^ 1);
  const uint32_t theirs = pinned(rb + C_KM2 + w * 512 + lane * 4), oa = wg * 4608;
  uint32_t a[144 + 4 * XR];
  mbar_wait(sb + W_BAR + wg * 8, 0);
  if (threadIdx.x == 0) TS(23);
  load_frags<36>(a, sb + C_W + wg * 73728);
  fence_async_smem();
  bar_arrive(B_WG0 + wg, 256);
  if (threadIdx.x == 0) TS(24);
  bar_sync(B_WG2, 384);
  const uint32_t round = min(w, 2u) + (wg ? 0 : 3), gdly = P.dly[8 + round], ps = t >> 2, pf = j * 16 + (ps >> 1);
  uint4* const dsts = pinned(g_xb + (ps * 4096 + near_half(ps * 8, ps * 2) * 256 + c * 4 + (t & 3)));
  uint4* const dstf = pinned(g_xb + (pf * 4096 + 512 + near_half(pf * 8 + 1, pf * 2) * 256 + h * 8 + (t & 7)));
  const uint32_t* const gsrc = (const uint32_t*)g_xb + (h * 16384 + min(w, 2u) * 4096 + near_half(h * 8 + !wg, h * 2) * 1024 +
                               (wg ? (lane & 24) * 2 + j * 8 + (lane & 7) : 2048 + (lane & 16) * 2 + j * 16 + (lane & 15)));
  uint32_t* gdst = g_mimg + (16384 + (lane >> 4) * 1024 + (lane & 2) * 4 +
                   (wg ? (round ? 1536 + round * 512 : 0) + h * 16 + ((lane ^ (c >> 2)) & 1) * 4 + j * 2 + ((lane >> 2) & 1)
                       : (round - 1) * 2048 + c * 16 + ((lane ^ (c >> 1)) & 1) * 4 + ((lane >> 2) & 3)));
  const uint32_t m0 = __ldcg(gdst - 16384);
  mbar_wait(sb + W_BAR + wg * 8, 1);
  load_frags<XR>(a + 144, sb + C_W + wg * 73728 + (18 - XR) * 2048);
  bar_sync(B_INIT, 256);
  if ((threadIdx.x & 127) == 0) TS(4);

  uint32_t ring = 1;
#pragma unroll 1
  for (int n = 0; n < STEPS; n++) {
    float d[8], e[8];
#pragma unroll
    for (int i = 0; i < 8; i++) e[i] = 0.f;
    uint32_t redo = n + 1;
#pragma unroll 1
    do {
      mbar_wait(sb + CB_M, n & 1);
      wg_fence();
      m_steps<0, 0, 4>(d, a, oa);
      wg_commit();
      if (wg) { wg_fence(); m_steps<18, 0, 4>(e, a, 4608); wg_commit(); }
      if (wid == 0) TR(8);
      mbar_wait(sb + CB_M + 8, n & 1);
      wg_fence();
      m_steps<0, 4, 8>(d, a, oa);
      wg_commit();
      mbar_wait(sb + CB_MV, n & 1);
      asm volatile("{.reg .pred p; .reg .u32 t; ld.shared.u32 t, [%1]; setp.eq.u32 p, t, %0; selp.u32 %0, -1, 0, p;}" : "+r"(redo) : "r"(sb + C_BAD) : "memory");
    } while (redo);
    wg_fence();
    m_steps<0, 12, 8>(d, a, oa);
    wg_commit();
    mbar_wait(sb + CB_MV + 16, n & 1);
    wg_fence();
    m_steps<0, 20, 8>(d, a, oa);
    wg_commit();
    mbar_wait(sb + CB_MV + 24, n & 1);
    wg_fence();
    m_steps<0, 28, 8>(d, a, oa);
    wg_commit();
    wg_wait<0>();
    if (w == 0) TR(6 + wg);
    const uint32_t f0 = pack2(d[0], d[1]), f1 = pack2(d[4], d[5]), f2 = pack2(d[2], d[3]), f3 = pack2(d[6], d[7]);
    stsm4(mine + C_QM + wg * 2048, f0, f1, f2, f3);
    bar_arrive(B_QK, 416);
    const uint32_t tag = (n & 1) ^ 1;
    if (wg) {
      if (n + 1 < STEPS) bar_sync(B_S, 256);
      wg_fence();
      v_steps<0, 2, 2>(e, a);
      wg_commit();
      const uint32_t k0 = j ? f0 : f1, k1 = j ? f2 : f3;
      wg_wait<0>();
      if (w == 0) TR(11);
      const uint32_t v0 = pack2(e[0], e[1]), v1 = pack2(e[4], e[5]), v2 = pack2(e[2], e[3]), v3 = pack2(e[6], e[7]);
      stsm4(mine + C_VM, v0, v1, v2, v3);
      bar_arrive(B_V, 256);
      st_async1(theirs, k0, rb + CB_XX);
      st_async1(theirs + 256, k1, rb + CB_XX);
      st_async1(theirs + 128, j ? v0 : v1, rb + CB_XX);
      st_async1(theirs + 384, j ? v2 : v3, rb + CB_XX);
      if (n + 1 == STEPS) break;
      bar_sync(B_O, 256);
      if (!WFENCE) fence_async_smem();
      wg_fence();
#pragma unroll
      for (int ks = 0; ks < 4; ks++) {
        if (ks == 0) wg_ss16<0>(d, desc_sw128(C_W + 32 * 2048), desc_n16(C_OI));
        else wg_ss16<1>(d, desc_sw128(C_W + (32 + ks) * 2048), desc_n16(C_OI + ks * 512));
      }
      wg_commit();
      bar_arrive(B_X, 256);
      if (w == 0) TR(0);
      wg_wait<0>();
      store_partial(dsts, pack_partial(d, tag));
      bar_arrive(B_M, 160);
      if (w == 0) TR(1);
    } else {
      if (n + 1 == STEPS) break;
      bar_sync(B_X, 256);
      wg_fence();
      o_steps<0, 4>(d, a);
      wg_commit();
      o_steps<4, 4>(e, a);
      wg_commit();
      wg_wait<1>();
      store_partial(dsts + 1024, pack_partial(d, tag));
      if (w == 0) TR(2);
      if (OGAP == 0) { wg_fence(); o_steps<8, 4>(d, a); wg_commit(); wg_wait<1>(); } else wg_wait<0>();
      store_partial(dsts + 2048, pack_partial(e, tag));
      if (w == 0) TR(3);
      wg_fence();
      if (OGAP) o_steps<8, 4>(d, a);
      if (OGAP < 2) o_steps<16, 4>(e, a);
      wg_commit();
      bar_sync(B_T, 256);
      if (w == 0) { TRV(61, 0); TR(12); }
      wg_fence();
      o_steps<12, 4>(d, a);
      wg_commit();
      if (OGAP == 2) o_steps<16, 4>(e, a);
      o_steps<20, 4>(e, a);
      wg_commit();
      wg_wait<1>();
      store_partial(dstf, pack_partial(d, tag));
      if (w == 0) TR(4);
      wg_fence();
      o_steps<24, 8>(d, a);
      wg_commit();
      wg_wait<1>();
      store_partial(dstf + 1024, pack_partial(e, tag));
      bar_arrive(B_OE, 256);
      if (w == 0) TR(5);
      wg_wait<0>();
      store_partial(dstf + 2048, pack_partial(d, tag));
      if (w == 0) TR(15);
    }
    if (w < 3) {
      mbar_wait(sb + CB_REF, n & 1);
      wait_until(lds32(sb + C_REF), gdly);
      gather_reduce(gsrc, gdst, m0, wg, tag, lane, sb, n, 16 + round * 4);
      if (++ring == MRING) { ring = 0; gdst -= MRING * 16384; }
      gdst += 16384;
    }
  }
}

template <int KS> __device__ __forceinline__ void x_scores(float* s, float* sm, const uint4* q, uint32_t ok, uint32_t om) {
  wg_rs32o<1, desc_sw64(C_KV + KS * 1024)>(s, q[KS].x, q[KS].y, q[KS].z, q[KS].w, ok);
  wg_rs8o<1, desc_n16(C_KM + KS * 512)>(sm, q[KS].x, q[KS].y, q[KS].z, q[KS].w, om);
  if constexpr (KS < 3) x_scores<KS + 1>(s, sm, q, ok, om);
}

__device__ __forceinline__ void chain_attn(const Params& P, uint32_t sb) {
  const int c = chain_id(), j = c & 1;
  const int tid = threadIdx.x, lane = tid & 31, w = __shfl_sync(~0u, (tid >> 5) & 3, 0);
  const int l = w >> 1, u = w & 1;
  const uint32_t rb = mapa(sb, j ^ 1);
  const float sc = 0.08838834764831845f * 1.4426950408889634f;
  const uint32_t ones = 0x3F803F80u;
  const uint32_t km_off = C_KM + (lane >> 3) * 256 + l * 128 + (lane & 7) * 16;
  const uint32_t qm_off = C_QM + (lane >> 4) * 256 + l * 128 + (lane & 7) * 16;
  const uint32_t kv_off = C_KV + l * 4096 + (lane & 15) * 64 + (((lane >> 4) ^ (u * 2) ^ ((lane >> 1) & 3)) << 4);

  load_wg<CHAIN, true>(P, sb, false, 1, w);
  if (lane == 0) mbar_arrive(sb + CB_M);
#pragma unroll 1
  for (int n = 0; n < STEPS; n++) {
    const uint32_t kvb = sb + kv_off + (n & 1) * 16384;
    if (w == 0 && elect()) { mbar_expect(sb + CB_SX, 2560); mbar_expect(sb + CB_OX, 2048); mbar_expect(sb + CB_XX, 2048); }
    mbar_wait(sb + CB_FULL + (n & 1) * 8, (n >> 1) & 1);
    if (n < 3 && tid == 256) TS(n ? 20 + n : 5);
    __syncwarp();
    {
      uint32_t km[8];
      uint4 kx[8];
#pragma unroll
      for (int i = 0; i < 8; i++) ldsm4t(kx[i].x, kx[i].y, kx[i].z, kx[i].w, (kvb ^ ((i & 1) * 32)) + (i >> 1) * 1024);
      mbar_wait(sb + CB_VF, n & 1);
      if (w == 1) TRD(60, kx[7].x);
      bar_sync(B_QK, 416);
      if (n + 1 == STEPS) {
        bar_sync(B_V, 256);
      } else {
      uint32_t qm[16];
#pragma unroll
      for (int ks = 0; ks < 4; ks++) ldsm4t(qm[4 * ks], qm[4 * ks + 1], qm[4 * ks + 2], qm[4 * ks + 3], sb + qm_off + ks * 512);
      ldsm4t(km[0], km[1], km[2], km[3], sb + km_off);
      ldsm4t(km[4], km[5], km[6], km[7], sb + km_off + 1024);
      float s[5][4];
      uint4 vx[4];
#pragma unroll
      for (int i = 0; i < 5; i++) { s[i][0] = s[i][1] = s[i][2] = s[i][3] = 0.f; }
#pragma unroll
      for (int ks = 0; ks < 4; ks++) {
        const uint32_t* q = qm + 4 * ks;
        if (ks == 1 || ks == 2) {
#pragma unroll
          for (int i = 2 * ks - 2; i < 2 * ks; i++) ldsm4(vx[i].x, vx[i].y, vx[i].z, vx[i].w, ((sb + kv_off) ^ ((i & 1) * 32)) + 8192 + (2 * u + (i >> 1)) * 1024);
        }
        mma16(s[1], q[0], q[1], q[2], q[3], kx[2 * ks].x, kx[2 * ks].y);
        mma16(s[2], q[0], q[1], q[2], q[3], kx[2 * ks].z, kx[2 * ks].w);
        mma16(s[0], q[0], q[1], q[2], q[3], km[2 * ks], km[2 * ks + 1]);
        mma16(s[3], q[0], q[1], q[2], q[3], kx[2 * ks + 1].x, kx[2 * ks + 1].y);
        mma16(s[4], q[0], q[1], q[2], q[3], kx[2 * ks + 1].z, kx[2 * ks + 1].w);
      }
      const uint32_t sx = C_SX + l * 1280;
      st_async4(rb + sx + u * 512 + lane * 16, s[1][0], s[1][1], s[2][0], s[2][1], rb + CB_SX);
      st_async1(rb + sx + 1024 + u * 128 + lane * 4, __float_as_uint(u ? s[0][1] : s[0][0]), rb + CB_SX);
      bar_arrive_after<B_S, 256>(__float_as_uint(s[3][0]), __float_as_uint(s[4][0]));
      mbar_wait(sb + CB_SX, n & 1);
      const uint4 p0 = lds128(sb + sx + u * 512 + lane * 16), p1 = lds128(sb + sx + (u ^ 1) * 512 + lane * 16);
      const uint2 p2 = make_uint2(lds32(sb + sx + 1024 + lane * 4), lds32(sb + sx + 1152 + lane * 4));
      float t[10] = {s[0][0] + __uint_as_float(p2.x), s[0][1] + __uint_as_float(p2.y),
                     s[1][0] + __uint_as_float(p0.x), s[1][1] + __uint_as_float(p0.y),
                     s[2][0] + __uint_as_float(p0.z), s[2][1] + __uint_as_float(p0.w),
                     s[3][0] + __uint_as_float(p1.x), s[3][1] + __uint_as_float(p1.y),
                     s[4][0] + __uint_as_float(p1.z), s[4][1] + __uint_as_float(p1.w)};
      float mx = fmaxf(fmaxf(fmaxf(fmaxf(t[2], t[3]), fmaxf(t[4], t[5])), fmaxf(fmaxf(t[6], t[7]), fmaxf(t[8], t[9]))), fmaxf(t[0], t[1]));
      mx = fmaxf(fmaxf(mx, __shfl_xor_sync(~0u, mx, 1)), fmaxf(__shfl_xor_sync(~0u, mx, 2), __shfl_xor_sync(~0u, mx, 3)));
      const float ms = -mx * sc;
#pragma unroll
      for (int i = 0; i < 10; i++) t[i] = ex2(fmaf(t[i], sc, ms));
      uint32_t p[5];
#pragma unroll
      for (int i = 0; i < 5; i++) p[i] = pack2(t[2 * i], t[2 * i + 1]);
      p[1] |= (p[0] & p[3] & p[4]) & 0x80008000u;
      float o[2][4], z[4] = {0.f, 0.f, 0.f, 0.f};
      mma16(z, ones, ones, ones, ones, p[1], p[2]);
#pragma unroll
      for (int i = 0; i < 2; i++) {
        o[i][0] = o[i][1] = o[i][2] = o[i][3] = 0.f;
        mma16(o[i], vx[2 * i].x, vx[2 * i].y, vx[2 * i].z, vx[2 * i].w, p[1], p[2]);
      }
      mma16(z, ones, ones, ones, ones, p[3], p[4]);
#pragma unroll
      for (int i = 0; i < 2; i++) mma16(o[i], vx[2 * i + 1].x, vx[2 * i + 1].y, vx[2 * i + 1].z, vx[2 * i + 1].w, p[3], p[4]);
      mma8(z, ones, ones, p[0]);
      bar_sync_after<B_V, 256>(p[1]);
      ldsm4(km[0], km[1], km[2], km[3], sb + km_off + (C_VM - C_KM) + u * 1024);
      mma8(o[0], km[0], km[1], p[0]);
      mma8(o[1], km[2], km[3], p[0]);
      const float i0 = rcp(z[0]), i1 = rcp(z[1]);
      const uint32_t oo = C_OI + u * 1024 + l * 128 + lane * 4;
      uint32_t ow[4];
#pragma unroll
      for (int i = 0; i < 2; i++) { ow[2 * i] = pack2(o[i][0] * i0, o[i][1] * i1); ow[2 * i + 1] = pack2(o[i][2] * i0, o[i][3] * i1); }
      stsm4(sb + C_OI + u * 1024 + l * 128 + (lane >> 3) * 256 + (lane & 7) * 16, ow[0], ow[1], ow[2], ow[3]);
      if (WFENCE) fence_async_smem();
      bar_arrive(B_O, 256);
#pragma unroll
      for (int i = 0; i < 4; i++) st_async1(rb + oo + 2048 + i * 256, ow[i], rb + CB_OX);
      }
    }
    {
      const uint32_t lane = opaque_tid() & 31, own = ((n & 1) * 16384 + j * 4096) >> 4;
      float s[16], sm[4];
#pragma unroll
      for (int i = 0; i < 16; i++) s[i] = sm[i & 3] = 0.f;
      {
        uint4 q[4];
        mbar_wait(sb + CB_Q, n & 1);
        auto load_q = [&]() {
#pragma unroll
          for (int ks = 0; ks < 4; ks++) q[ks] = lds128(sb + C_Q + (ks >> 1) * 4096 + w * 1024 + (ks & 1) * 512 + lane * 16);
        };
        if (QPOS == 0) load_q();
        mbar_wait(sb + CB_XX, n & 1);
        if (n + 1 < STEPS) mbar_wait(sb + CB_OX, n & 1);
        fence_async_smem();
        if (n + 1 < STEPS) bar_arrive(B_T, 256);
        if (QPOS == 1) load_q();
        if (n + 1 < STEPS) bar_sync(B_OE, 256);
        if (QPOS == 2) load_q();
        if (w == 1) { TRV(61, 0); TR(9); }
#pragma unroll 1
        for (uint32_t hf = 0; hf < 2; hf++) {
          wg_fence();
          x_scores<0>(s, sm, q, hf ? (C_KV2 - C_KV) >> 4 : own, hf ? (C_KM2 - C_KM) >> 4 : j * 8);
          wg_commit();
          wg_wait<0>();
#pragma unroll
          for (int ks = 0; ks < 4; ks++) asm volatile("mov.b32 %0, %1; mov.b32 %2, %3;" : "+r"(q[ks].x), "+r"(q[ks].y), "+r"(q[ks].z), "+r"(q[ks].w));
        }
      }
      const float neg = -1e9f * 11.313708498984761f;
      const int lim = 8 * (w - (int)(lane & 3)) + (int)(lane >> 2);
      float t[10] = {sm[0], sm[1]};
#pragma unroll
      for (int i = 0; i < 8; i++) t[2 + i] = i > lim ? neg : s[(i >> 1) * 4 + (i & 1)];
      float mx = fmaxf(fmaxf(fmaxf(fmaxf(t[2], t[3]), fmaxf(t[4], t[5])), fmaxf(fmaxf(t[6], t[7]), fmaxf(t[8], t[9]))), fmaxf(t[0], t[1]));
      mx = fmaxf(fmaxf(mx, __shfl_xor_sync(~0u, mx, 1)), fmaxf(__shfl_xor_sync(~0u, mx, 2), __shfl_xor_sync(~0u, mx, 3)));
      const float ms = -mx * sc;
#pragma unroll
      for (int i = 0; i < 10; i++) t[i] = ex2(fmaf(t[i], sc, ms));
      uint32_t p[5];
#pragma unroll
      for (int i = 0; i < 5; i++) p[i] = pack2(t[2 * i], t[2 * i + 1]);
      float z = ((t[0] + t[1]) + (t[2] + t[3])) + ((t[4] + t[5]) + (t[6] + t[7])) + (t[8] + t[9]);
      const uint32_t row = sb + C_OS + w * 1024 + (lane >> 2) * 128 + (((lane & 3) ^ (lane >> 2)) << 4);
#pragma unroll 1
      for (uint32_t hf = 0; hf < 2; hf++) {
        float o[32];
        const uint32_t vo = hf ? (C_KV2 + 4096 - C_KV - 8192) >> 4 : j * 256;
        wg_fence();
        wg_rs64o<0, desc_sw64(C_KV + 8192)>(o, p[1], p[1], p[2], p[2], vo);
        wg_rs64o<1, desc_sw64(C_KV + 8192 + 32)>(o, p[3], p[3], p[4], p[4], vo);
        wg_rs64o<1, mkdesc(C_VM, 128, 256, 0)>(o, p[0], p[0], 0, 0, hf ? (C_VM2 - C_VM) >> 4 : j * 8);
        wg_commit();
        if (hf) {
          if (elect()) mbar_arrive(sb + CB_M);
        } else {
          z += __shfl_xor_sync(~0u, z, 1);
          z = rcp(z + __shfl_xor_sync(~0u, z, 2));
        }
        wg_wait<0>();
#pragma unroll
        for (int qq = 0; qq < 2; qq++) {
          const float* r = o + 16 * qq;
          sts128((row ^ (qq * 64)) + hf * 4096,
                 make_uint4(pack2(r[0] * z, r[1] * z), pack2(r[4] * z, r[5] * z), pack2(r[8] * z, r[9] * z), pack2(r[12] * z, r[13] * z)));
        }
      }
      bar_arrive(B_G, 160);
      if (n + 1 < STEPS) bar_arrive(B_R, 160);
      if (w == 1) TR(10);
    }
  }
  if ((threadIdx.x & 127) == 0) TS(6);
}

__device__ __forceinline__ void chain_aux(const Params& P, uint32_t sb) {
  const uint32_t c = chain_id(), j = c & 1, lane = threadIdx.x & 31, w = __shfl_sync(~0u, (threadIdx.x >> 5) & 3, 0);
  load_wg<CHAIN, true>(P, sb, false, 0, w);
  if (threadIdx.x == 384) TS(25);
  if (threadIdx.x == 384) grid_wait(1, lds32(sb + S_GEN));
  bar_sync(B_WG2, 384);
  if (threadIdx.x == 384) TS(13);
  if (w == 0) {
    const uint32_t* fg = g_fl + FL_G + near_half(XB_F, c) * 1024 + (c >> 1) * 8;
#pragma unroll 1
    for (int n = 0; n < STEPS; n++) {
      const unsigned char* blk = g_qkv + (uint32_t)((n % QRING) * (N_CHAIN * 24576));
      const uint32_t t1 = clk(), kb = sb + CB_FULL + (n & 1) * 8, kv = sb + C_KV + (n & 1) * 16384;
      uint32_t t0 = t1 - 100000, x = 0;
      if (n > 0) {
        wait_until(t1, KMIN);
        do asm volatile("ld.relaxed.gpu.global.u32 %0, [%1];" : "=r"(x) : "l"(fg) : "memory"); while (x <= n && clk() - t1 < KWIN);
        if (NOBULK) x = n + 1;
        if (x > n) {
          asm volatile("fence.acquire.gpu;" ::: "memory");
          fence_async_global();
          if (elect()) { mbar_expect(kb, 8192); bulk_load(kv, blk + c * 24576, 8192, kb); }
        }
        T3(0); CNT(12, 1 + (x <= n));
        mbar_wait(sb + CB_REF, (n - 1) & 1);
        t0 = lds32(sb + C_REF);
        wait_until(t0, DLYK - 500);
      }
      if (!NOBULK) wait_flags(fg + min(lane, 2u) * 256, n + 1);
      T3(2);
      fence_async_global();
      if (n > 0) bar_sync(B_R, 160);
      wait_until(t0, DLYK);
      if (elect()) {
        if (x <= n) { mbar_expect(kb, 8192); bulk_load(kv, blk + c * 24576, 8192, kb); }
        mbar_expect(sb + CB_VF, 8192);
        bulk_load(sb + C_KV + 8192, blk + (c * 24576 + 8192), 8192, sb + CB_VF);
        mbar_expect(sb + CB_Q, 16384);
        bulk_load(sb + C_Q, blk + (c * 24576 + 16384), 8192, sb + CB_Q);
        bulk_load(sb + C_KV2, blk + ((c ^ 1) * 24576 + j * 4096), 4096, sb + CB_Q);
        bulk_load(sb + C_KV2 + 4096, blk + ((c ^ 1) * 24576 + 8192 + j * 4096), 4096, sb + CB_Q);
      }
      T3(1);
      T3(3);
    }
  } else {
    const uint32_t near = __ballot_sync(~0u, near_half(XB_M + min(lane, MRING - 1u) * 8, c));
    uint32_t ring = 0;
    if (w > 1) {
      const uint32_t odd = w & 1, chk = pinned(sb + C_M + odd * 2048 + m_probe(lane)), again = sb + CB_MV + 32 + odd * 8;
      const bool one = elect();
      uint32_t mph = 0;
#pragma unroll 1
      for (int n = 0; n <= STEPS; n++) {
#pragma unroll
        for (int k = 0; k < 3; k++) {
          if (n == STEPS || (k == 2 && odd)) break;
          const uint32_t b = 2 * k + odd, at = chk + (k ? k * 8192 - 2048 + odd * 2048 : 0);
          uint32_t mb = sb + CB_M + b * 8, ph = n & 1;
          int it = 1;
          while (true) {
            mbar_wait(mb, ph);
            const bool bad = __any_sync(~0u, (k ? m_max(at, at + 2048) : max(m_max(at, at ^ 8), odd ? m_max(at + 2048, (at ^ 8) + 2048) : 0)) == SENT);
            if (one && !bad) mbar_arrive(sb + CB_MV + (b > 2 ? b * 8 - 8 : 0));
            if (!bad) break;
            mb = again; ph = mph; mph ^= 1;
            if (one) {
              if (k == 0) sts32(sb + C_BAD, n + 1);
              mbar_expect(mb, b ? 4096 : 2048);
              m_fetch(sb, ring * 65536 + ((near >> ring) & 1) * 4096, b, mb);
            }
            __syncwarp();
            spin_guard(it);
          }
          TR(41 + b * 4); CNT(6 + b, it);
        }
        ring = ring + 1 == MRING ? 0 : ring + 1;
        if (!odd) {
          if (n < STEPS) { TRSYNC(); TRDUMP(n - 2); }
        } else {
          unsigned char* o = g_oimg + (uint32_t)(((n - 1) & (RING - 1)) * (N_CHAIN * 8192) + j * 4096);
          if (n > 0) bar_sync(B_G, 160);
          fence_async_smem();
          if (one) {
            if (n > 0) {
              bulk_store(o + c * 8192, sb + C_OS, 4096);
              bulk_store(o + (c ^ 1) * 8192, sb + C_OS + 4096, 4096);
              asm volatile("cp.async.bulk.commit_group;\ncp.async.bulk.wait_group.read 0;" ::: "memory");
              { const int n_ = n - 1; { const int n = n_; T3(4); (void)n; } }
            }
            mbar_arrive(sb + CB_Q);
            if (n > 0) {
              bulk_done_inc(g_fl + FL_O + c);
              { const int n_ = n - 1; { const int n = n_; T3(5); (void)n; } }
            }
          }
          __syncwarp();
        }
      }
    } else {
      const uint32_t* ts = g_fl + FL_SYNC + near_half(XB_F + 1, c) * 1024 + lane * 2;
      uint32_t t0 = clk() - 100000;
#pragma unroll 1
      for (int n = 0; n < STEPS; n++) {
        const uint32_t src = ring * 65536 + ((near >> ring) & 1) * 4096;
        if (lane < 5) mbar_expect(sb + CB_M + lane * 8, lane ? 4096 : 2048);
        __syncwarp();
        if (elect()) {
#pragma unroll
          for (int b = 0; b < 5; b++) {
            wait_until(t0, P.dly[14 + b]);
            m_fetch(sb, src, b, sb + CB_M + b * 8);
            TR(40 + b * 4);
          }
        }
        __syncwarp();
        ring = ring + 1 == MRING ? 0 : ring + 1;
        uint32_t va, vb;
        const uint32_t off = timer_offset(), tag = (uint32_t)(n + 1) << 24;
        bar_sync(B_QK, 416);
        if (n + 1 == STEPS) break;
        sts32(sb + C_REF + 4, 0);
        const uint32_t c0 = clk(), stamp = c0 + off;
        st_relaxed_if(g_fl + FL_SYNC + lane * 1024 + c, tag | (stamp & 0xFFFFFF), lane < 2);
        TR(13);
        wait_until(c0, DLYS);
        int it = 0;
        do {
          asm volatile("ld.relaxed.gpu.global.v2.u32 {%0,%1}, [%2];" : "=r"(va), "=r"(vb) : "l"(ts) : "memory");
          spin_guard(it);
        } while (__any_sync(~0u, ((va ^ tag) | (vb ^ tag)) >> 24));
        const int late = __reduce_max_sync(~0u, max((int)((va - stamp) << 8), (int)((vb - stamp) << 8))) >> 8;
        t0 = c0 + min((uint32_t)late, clk() - c0);
        if (elect()) {
          sts32(sb + C_REF, t0);
          mbar_arrive(sb + CB_REF);
        }
        st_relaxed_if(g_fl + FL_TICK + lane * 1024, tag | ((t0 + off) & 0xFFFFFF), c == 0 && lane < 2);
        TR(14); CNT(11, it);
        bar_sync(B_M, 160);
      }
    }
  }
}

template <int WG>
__device__ __forceinline__ void g_math(const Params& P, uint32_t sb) {
  const int q = g_unit(WG);
  const int lane = threadIdx.x & 31, w = (threadIdx.x >> 5) & 3;
  const bool isq = q >= 64;
  uint32_t a[136];
  {
    const uint32_t stage = sb + G_W + WG * 73728;
    mbar_wait(sb + W_BAR + WG * 8, 0);
    if (threadIdx.x == 0) TS(23);
    load_frags<34>(a, stage);
    fence_async_smem();
    bar_sync(B_WG0 + WG, 128);
    if (threadIdx.x == 0) TS(24);
    load_wg<GROLE>(P, sb, false, WG, w);
    if (threadIdx.x == 0) TS(25);
    mbar_wait(sb + W_BAR + WG * 8, 1);
  }
  if ((threadIdx.x & 127) == 0) TS(4);
  const uint32_t off0 = (q & 31) * 49152 + (q >> 5) * 8192 +
                        (isq ? (w >> 1) * 4096 + (w & 1) * 512 + lane * 16 : w * 1024 + (lane >> 2) * 64 + (((lane ^ (lane >> 3)) & 3) << 4));
#pragma unroll 1
  for (int n = 0; n < STEPS; n++) {
    float d0[32], d1[32];
    if (WG == 0 && n >= LOCK0) bar_sync(B_OE, 160);
    if (n > 0) bar_sync(B_V + WG, 256);
#pragma unroll
    for (int ch = 0; ch < 9; ch++) {
      mbar_wait(sb + G_BAR + ch * 8, n & 1);
      if (ch == 0) { if ((threadIdx.x & 127) == 0) T3(5 + WG * 3); __syncwarp(); }
      if (ch == 4) { if ((threadIdx.x & 127) == 0) T3(6 + WG * 3); __syncwarp(); }
      if (ch == 8 && (WG == 0 ? n > 0 : n + 1 < STEPS)) bar_arrive(B_V + (WG ^ 1), 256);
      wg_fence();
#pragma unroll
      for (int kk = 0; kk < (ch < FASTG ? 3 : 4); kk++) {
        const int i = ch * 4 + kk;
        float* d = i & 1 ? d1 : d0;
        const uint64_t db = desc_sw128(G_RING + ch * 8192 + (kk & 2) * 32);
        if (i < 2) wg_rs64<0>(d, a + i * 4, db);
        else if (i < 34) wg_rs64<1>(d, a + i * 4, db);
        else wg_ss64<1>(d, desc_sw128(G_W2 + WG * 4096 + (i - 34) * 2048), db);
        wg_ss64<1>(d, desc_sw128(G_W + WG * 73728 + i * 2048), db + 2);
      }
      wg_commit();
      if (ch > 0) { wg_wait<1>(); if (lane == 0) mbar_arrive(sb + G_BAR + 128 + (ch - 1) * 8); }
    }
    wg_wait<0>();
    if (lane == 0) mbar_arrive(sb + G_BAR + 128 + 8 * 8);
    if ((threadIdx.x & 127) == 0) T3(7 + WG * 3);
    __syncwarp();
    uint32_t tw = clk() + (n == 0 ? -100000 : WG ? 0 : DLYW);
    unsigned char* base = g_qkv + (size_t)(n & (QRING - 1)) * (N_CHAIN * 24576);
    if ((ABL & 1) && d0[0] != 1234.5f) {
    } else if (isq) {
#pragma unroll
      for (int i = 0; i < 8; i++) {
        const float *d = (i < 4 ? d0 : d1) + 4 * i, *e = (i < 4 ? d1 : d0) + 4 * i;
        wait_until(tw, 0); tw += P.dly[2 + WG];
        *(uint4*)(base + off0 + (i >> 2) * 24576 + (i & 3) * 1024) =
          make_uint4(movmat(pack2(d[0], d[1])), movmat(pack2(e[0], e[1])), movmat(pack2(d[2], d[3])), movmat(pack2(e[2], e[3])));
      }
    } else {
#pragma unroll
      for (int i = 0; i < 8; i++) {
        const float* d = (i < 4 ? d0 : d1) + 8 * (i & 2) + 2 * (i & 1);
        wait_until(tw, 0); tw += P.dly[2 + WG];
        *(uint4*)(base + off0 + (i >> 2) * 24576 + (i & 2) * 2048 + (i & 1) * 512) =
          make_uint4(pack2(d[0], d[1]), pack2(d[4], d[5]), pack2(d[8], d[9]), pack2(d[12], d[13]));
      }
    }
    bar_arrive(B_M + WG, 160);
  }
}

__device__ __forceinline__ void fill16(void* p, uint32_t v) {
  asm volatile("st.global.v4.u32 [%0], {%1,%1,%1,%1};" :: "l"(p), "r"(v) : "memory");
}
__device__ __forceinline__ void g_load(const Params& P, uint32_t sb) {
  const int lane = threadIdx.x & 31, w = __shfl_sync(~0u, (threadIdx.x >> 5) & 3, 0);
  if (w == 2) return;
  if (w < 2) { bar_sync(15, 192); fence_async_smem(); }
  uint32_t fl = 0;
#pragma unroll 1
  for (int n = w == 3 ? LOCK0 : 0; n < STEPS; n++) {
    if (w && n == LOCK0) { grid_wait(1, lds32(sb + S_GEN)); fl = near_half(XB_F, bid()) * 1024; }
    if (w == 3) {
      const uint32_t tag = (uint32_t)(n - LOCK0 + 1) << 24;
      uint32_t v; int it = 0;
      do { asm volatile("ld.relaxed.gpu.global.u32 %0, [%1];" : "=r"(v) : "l"(g_fl + fl + FL_TICK) : "memory"); spin_guard(it); } while (!NOCHAIN && v < tag);
      const uint32_t off = timer_offset(), now = clk(), t0 = now - ((v ^ tag) >> 24 ? DLYG : (now + off - v) & 0xFFFFFF);
      asm volatile("fence.acquire.gpu;" ::: "memory");
      if (lane == 0) T3(11);
      __syncwarp();
      wait_until(t0, DLYG);
      if (lane == 0) T3(4);
      bar_sync(B_OE, 160);
      continue;
    }
    if (w == 0 || n == 0) {
      if (n < NSEG) wait_flags(g_lnflag + n * 16 + (lane & 1) * 8, 1);
    } else if (!NOCHAIN && n >= LAG) {
      wait_flags(g_fl + fl + FL_F + (lane & 1) * 8, n - LAG + 1);
    }
    if (w) { if (lane == 0) T3(12); bar_sync(B_X, 96); }
    fence_async_global();
    const unsigned char* src = g_lnimg + (uint32_t)((w ? (n >= LAG ? NSEG + n - LAG : 0) : min(n, NSEG - 1)) * 36864);
#pragma unroll 1
    for (int ch = 0; ch < 9; ch++) {
      const uint32_t full = sb + G_BAR + ch * 8;
      mbar_wait(full + 128, (n & 1) ^ 1);
      if (elect()) {
        mbar_expect(full, ABL & 2 ? 16 : 4096);
        bulk_load(sb + G_RING + ch * 8192 + w * 4096, src + ch * 4096, ABL & 2 ? 16 : 4096, full);
      }
    }
  }
}

__device__ __forceinline__ void g_aux(const Params& P, uint32_t sb) {
  const int lane = threadIdx.x & 31, w = (threadIdx.x >> 5) & 3;
  if (w == 1 || w == 2) {
    const int q = g_unit(w - 1);
    uint32_t* f = g_fl + FL_G + q * 8;
#pragma unroll 1
    for (int n = 0; n < STEPS; n++) {
      const uint32_t ln = opaque_tid() & 31;
      uint4* z = (uint4*)g_oacc + (uint32_t)(((n + 1) % ARING) * (16 * DM) + q * 96 + ln);
      if (!(ABL & 16)) { fill16(z, 0); fill16(z + 32, 0); fill16(z + 64, 0); }
      if (n + 3 >= MRING && q < 80) fill16((uint4*)g_mimg + (uint32_t)(((n + 3) % MRING) * 4096 + q * 32 + ln), SENT);
      bar_sync(B_M + (w - 1), 160);
      if (lane == 0) { T3(w * 2 - 2); fence_async_global(); flag_release(f, n + 1); T3(w * 2 - 1); }
      __syncwarp();
    }
  } else {
    const uint32_t u = (bid() - N_CHAIN) * 2 + (w & 1), r = u / 36 * 16 + (u & 3) * 4 + (lane >> 3);
    uint32_t o = r * (DM / 8) + (u % 36 >> 2) * 8 + ((lane & 7) ^ ((r >> 1) & 3)), fl = 0;
#pragma unroll 1
    for (int k = -LAG - 1; k < STEPS; k++) {
      if (k < NSEG - 1) bar_sync(B_X, 96);
      if (k < LAG || u >= 72) continue;
      if (k == NSEG - 1) { fl = near_half(XB_F, bid()) * 1024; wait_flags(g_fl + fl + FL_F + (lane & 1) * 8, NSEG + 1); }
      const uint4 x = __ldcg((const uint4*)P.out + o);
      if (k >= NSEG - 1) wait_flags(g_fl + fl + FL_OCNT + (max(k, NSEG) % OCRING) * 8, N_O * 3 * (max(k, NSEG) / OCRING + 1));
      const float4* a = (const float4*)g_oacc + ((k % ARING) * (16 * DM) + 8 * DM + u * 64 + lane * 2);
      const float4 p = __ldcg(a), v = __ldcg(a + 1);
      ((uint4*)P.out)[o] = make_uint4(badd2(x.x, pack2(p.x, p.y)), badd2(x.y, pack2(p.z, p.w)), badd2(x.z, pack2(v.x, v.y)), badd2(x.w, pack2(v.z, v.w)));
      o += 4 * DM;
    }
    if ((threadIdx.x & 127) == 0) TS(7);
  }
}

template <int WG, bool HALF, int KS, int N> __device__ __forceinline__ void o_mma(float* d, const uint32_t* a, uint32_t ob) {
  constexpr uint64_t db = desc_sw128(O_RING + (KS >> 2) * 8192 + (KS & 3) * 32);
  constexpr uint64_t da = desc_sw128(O_W + WG * 40960 + (KS < 40 ? KS / 5 * 2 + KS % 5 / 2 : KS - 24) * 2048);
  if constexpr (KS < 40 && !(KS % 5 & 1)) {
    const uint32_t* r = a + (KS / 5 * 3 + KS % 5 / 2) * 4;
    if constexpr (HALF) wg_rs32k<KS != 0, db>(d, r[0], r[1], r[2], r[3], ob); else wg_rs64<KS != 0>(d, r, db);
  } else {
    if constexpr (HALF) wg_ss32k<da, db>(d, ob); else wg_ss64<1>(d, da, db);
  }
  if constexpr (N > 1) o_mma<WG, HALF, KS + 1, N - 1>(d, a, ob);
}
template <int WG, bool HALF, int GR> __device__ __forceinline__ void o_groups(float* d, const uint32_t* a, uint32_t sb, int n, bool more) {
  const uint32_t ob = n < NSEG ? 0 : 256;
  mbar_wait(sb + O_BAR + GR * 8, n & 1);
  if (GR == 0) { if ((threadIdx.x & 127) == 0) T3(13 + WG); __syncwarp(); }
  if (GR == (WG == 0 ? OTURN : 4) && (WG < 2 || n + 1 < STEPS)) bar_arrive(B_V + (WG + 1) % 3, 256);
  wg_fence();
  o_mma<WG, HALF, GR * 8, 8 - 2 * FASTO>(d, a, ob);
  if (GR == 4 && more) o_mma<WG, HALF, 40, 4>(d, a, ob);
  wg_commit();
  if (GR > 0) { wg_wait<1>(); if ((threadIdx.x & 31) == 0) mbar_arrive(sb + O_BAR + 128 + (GR - 1) * 8); }
  if constexpr (GR < 4) o_groups<WG, HALF, GR + 1>(d, a, sb, n, more);
}
template <int WG, bool HALF> __device__ __forceinline__ void o_step(const uint32_t* a, uint32_t sb, uint32_t st0, int n, bool more) {
  float d[HALF ? 16 : 32];
  if (WG > 0 || n > 0) bar_sync(B_V + WG, 256);
  o_groups<WG, HALF, 0>(d, a, sb, n, more);
  wg_wait<0>();
  if ((threadIdx.x & 31) == 0) mbar_arrive(sb + O_BAR + 128 + 4 * 8);
  if ((threadIdx.x & 127) == 0) T3(WG == 0 ? 1 : WG == 1 ? 8 : 12);
  __syncwarp();
#pragma unroll(HALF ? 1 : 2)
  for (int sl = 0; sl < 2; sl++) {
    mbar_wait(sb + OB_ST + WG * 16 + sl * 8, (n & 1) ^ (WG == 0));
    if (!HALF || sl == (n >= NSEG)) {
#pragma unroll
      for (int nb = 0; nb < 4; nb++) {
        const float* r = d + (HALF ? 0 : sl * 16) + nb * 4;
        const uint32_t ad = st0 + sl * 8192 + nb * 2048;
        sts32(ad, __float_as_uint(r[0]));
        sts32(ad + 256, __float_as_uint(r[1]));
        sts32(ad ^ 32, __float_as_uint(r[2]));
        sts32((ad ^ 32) + 256, __float_as_uint(r[3]));
      }
      fence_async_smem();
    }
    bar_arrive((sl ? B_G : B_M) + WG, 160);
  }
}
template <int WG>
__device__ __forceinline__ void o_math(const Params& P, uint32_t sb) {
  const bool more = bid() < N_CHAIN + N_G + 12;
  const int lane = threadIdx.x & 31, w = (threadIdx.x >> 5) & 3, g = lane >> 2, tq = lane & 3;
  uint32_t a[96];
  mbar_wait(sb + W_BAR + WG * 8, 0);
  load_frags<24>(a, sb + WG * 49152);
  fence_async_smem();
  bar_sync(B_INIT, 416);
  load_wg<OROLE>(P, sb, false, WG, w);
  mbar_wait(sb + W_BAR + WG * 8, 1);
  if ((threadIdx.x & 127) == 0) TS(4);
  const uint32_t st0 = sb + O_ST + tq * 512 + ((w * 16 + g) ^ (tq * 8)) * 4;
#pragma unroll 1
  for (int n = 0; n < STEPS; n++) {
    if (n < LAG || n >= NSEG) o_step<WG, true>(a, sb, st0, n, more); else o_step<WG, false>(a, sb, st0, n, more);
  }
}

__device__ __forceinline__ void o_aux(const Params& P, uint32_t sb) {
  const int i = bid() - N_CHAIN - N_G, ksl = i / 3;
  const int c0 = ksl * 11 - max(ksl - 4, 0), nc = ksl < 4 ? 11 : 10;
  const int lane = threadIdx.x & 31, w = __shfl_sync(~0u, (threadIdx.x >> 5) & 3, 0);
  if (w == 0) {
    bar_sync(B_INIT, 416);
    const uint32_t* f = g_fl + FL_O + near_half(XB_F + 1, bid()) * 1024 + min((c0 & ~1) + lane, (c0 + nc - 1) | 1);
#pragma unroll 1
    for (int n = 0; n < STEPS; n++) {
      const unsigned char* src = g_oimg + (uint32_t)(((n % RING) * N_CHAIN + c0) * 8192);
      if (!NOCHAIN) wait_flags(f, n + 1);
      fence_async_global();
      if (lane == 0) T3(0);
#pragma unroll
      for (int gr = 0; gr < 5; gr++) {
        const uint32_t full = sb + O_BAR + gr * 8, bytes = ABL & 4 ? 16 : (gr < 4 ? 2 : nc - 8) * 8192;
        mbar_wait(full + 128, (n & 1) ^ 1);
        if (elect()) {
          if (n < LAG || n >= NSEG) {
            mbar_expect(full, bytes >> 1);
            for (uint32_t o = gr * 16384 + (n < LAG ? 0 : 4096); o < gr * 16384 + bytes; o += 8192) bulk_load(sb + O_RING + o, src + o, 4096, full);
          } else {
            mbar_expect(full, bytes);
            bulk_load(sb + O_RING + gr * 16384, src + gr * 16384, bytes, full);
          }
        }
      }
    }
  } else {
#pragma unroll 1
    for (int n = 0; n < STEPS; n++) {
      float* dst = g_oacc + (uint32_t)((n % ARING) * (64 * DM) + ((i % 3) * 3 + (w - 1 + ksl) % 3) * 1024);
      const bool early = w == 3 && n < NSEG;
      bar_sync(B_M + (w - 1), 160);
      if (lane == 0) {
        T3(w * 2);
        if (n < NSEG && !(ABL & 8)) { bulk_reduce(dst, sb + O_ST, 4096); bulk_reduce(dst + 16 * DM, sb + O_ST + 4096, 4096); }
        asm volatile("cp.async.bulk.commit_group;" ::: "memory");
        if (early) {
          asm volatile("cp.async.bulk.wait_group.read 0;" ::: "memory");
          mbar_arrive(sb + OB_ST);
          T3(8 + w);
          bulk_done_inc(g_fl + FL_OCNT + (n % OCRING) * 8);
          T3(w * 2 + 1);
        }
      }
      __syncwarp();
      bar_sync(B_G + (w - 1), 160);
      if (lane == 0) {
        if (n >= LAG && !(ABL & 8)) { bulk_reduce(dst + 32 * DM, sb + O_ST + 8192, 4096); bulk_reduce(dst + 48 * DM, sb + O_ST + 12288, 4096); }
        asm volatile("cp.async.bulk.commit_group;\ncp.async.bulk.wait_group.read 1;" ::: "memory");
        if (!early) mbar_arrive(sb + OB_ST + (w % 3) * 16);
        asm volatile("cp.async.bulk.wait_group.read 0;" ::: "memory");
        mbar_arrive(sb + OB_ST + (w % 3) * 16 + 8);
        if (!early) {
          T3(8 + w);
          bulk_done_inc(g_fl + FL_OCNT + (n % OCRING) * 8);
          T3(w * 2 + 1);
        }
      }
      __syncwarp();
    }
  }
}

constexpr uint32_t Y_PITCH = 1168, Y_ROWS = 16 * Y_PITCH;
template <int R> __device__ __forceinline__ void y_rows(uint32_t* y, uint32_t src, uint32_t dst, int w, int bar) {
  const int lane = threadIdx.x & 31;
#pragma unroll
  for (int k = 0; k < 2 * R + 1; k++) {
    const int op = w + k * (16 / R);
    if (k == 2 * R && w >= 4) break;
    uint32_t a, b, c, d;
    ldsm4t(a, b, c, d, src + op * 512 + (lane & 16) * 16 + (lane & 7) * 32 + (lane & 8) * 2);
    stsm4(dst + (lane & 15) * Y_PITCH + op * 32 + (lane & 16), a, b, c, d);
  }
  bar_sync(bar, 512 / R);
  const uint32_t row = dst + ((w & 6) * 2 + (w >> 3) * 2 + (w & 1)) * Y_PITCH + lane * 4;
#pragma unroll
  for (int i = 0; i < 9 * R; i++) y[i] = lds32(row + i / 9 * 2 * Y_PITCH + i % 9 * 128);
}

__device__ __forceinline__ void f_role(const Params& P, uint32_t sb) {
  const int lane = threadIdx.x & 31, w = __shfl_sync(~0u, threadIdx.x >> 5, 0), r0 = (bid() - N_CHAIN - N_G - N_O) * 16;
  if (w == 8) {
    const uint32_t* fo = g_fl + FL_OCNT + near_half(XB_F, bid()) * 1024;
    fence_async_global();
#pragma unroll 1
    for (int n = 0; n < NSEG; n++) {
      bar_sync(2, 288);
      if (elect()) {
        mbar_expect(sb + F_BAR, 36864);
        bulk_load(sb + F_XY, P.X + (size_t)(n * 32 + r0) * DM, 18432, sb + F_BAR);
        bulk_load(sb + F_XY + 18432, g_yT + (size_t)(n * 32 + r0) * DM, 18432, sb + F_BAR);
        mbar_expect(sb + F_BAR + 8, 36864);
        T3(1);
      }
      wait_flags(fo + (n % OCRING) * 8, NOCHAIN == 5 ? 0 : N_O * 3 * (n / OCRING + 1));
      fence_async_global();
      if (elect()) { bulk_load(sb + F_A, g_oacc + (uint32_t)((n % ARING) * (64 * DM) + r0 * DM), 36864, sb + F_BAR + 8); T3(0); }
    }
  } else if (w == 9) {
#pragma unroll 1
    for (int n = 0; n < NSEG; n++) {
      const uint32_t st = sb + (n & 1) * 36864;
      unsigned char* p = g_lnimg + (uint32_t)((NSEG + n) * 36864 + r0 * 128);
      bar_sync(1, 288);
      if (elect()) {
        T3(2);
#pragma unroll
        for (int i = 0; i < 9; i++) bulk_store(p + i * 4096, st + F_L + i * 2048, 2048);
        asm volatile("cp.async.bulk.commit_group;" ::: "memory");
        bulk_done_inc(g_fl + FL_F + (bid() & 1) * 8);
        T3(3);
        bulk_store(P.out + (size_t)(n * 32 + r0) * DM, st + F_X, 18432);
        asm volatile("cp.async.bulk.commit_group;\ncp.async.bulk.wait_group.read 0;" ::: "memory");
        if (n + 1 == NSEG) bulk_done_inc(g_fl + FL_F + (bid() & 1) * 8);
      }
      __syncwarp();
    }
  } else if (w < 8) {
    const uint32_t row = sb + w * 1152 + lane * 4, acc = sb + F_A + w * 256 + (lane ^ ((w & 6) * 2)) * 8;
    const uint32_t ln = sb + F_L + w * 128 + (((lane >> 2) ^ w) << 4) + (lane & 3) * 4;
#pragma unroll 1
    for (int n = -1; n < NSEG; n++) {
      const uint32_t st = (n & 1) * 36864;
      uint32_t x[18], y[18], l[18];
      if (n >= 0) mbar_wait(sb + F_BAR, n & 1);
#pragma unroll
      for (int i = 0; i < 18; i++) x[i] = lds32(row + F_XY + i / 9 * 9216 + i % 9 * 128);
      y_rows<2>(y, sb + F_XY + 18432, sb + F_Y, w, 3);
      layernorm9<2>(x, l);
#pragma unroll
      for (int i = 0; i < 18; i++) x[i] = badd2(x[i], bmul2(l[i], y[i]));
      if (n >= 0) mbar_wait(sb + F_BAR + 8, n & 1);
      if (threadIdx.x == 0 && n >= 0) T3(4);
      __syncwarp();
      uint2 a[18];
#pragma unroll
      for (int i = 0; i < 18; i++) a[i] = lds64(acc + i / 9 * 2048 + i % 9 * 4096);
#pragma unroll
      for (int i = 0; i < 18; i++) x[i] = badd2(x[i], pack2(__uint_as_float(a[i].x), __uint_as_float(a[i].y)));
      if (n + 1 < NSEG) bar_arrive(2, 288);
      layernorm9<2>(x, l);
#pragma unroll
      for (int i = 0; i < 18; i++) { x[i] = badd2(x[i], bmul2(l[i], y[i])); sts32(row + st + F_X + i / 9 * 9216 + i % 9 * 128, x[i]); }
      layernorm9<2>(x, l);
#pragma unroll
      for (int i = 0; i < 18; i++) sts32(ln + st + i / 9 * 1024 + i % 9 * 2048, l[i]);
      fence_async_smem();
      if (n >= 0) bar_sync(1, 288); else bar_sync(3, 256);
    }
  }
}

constexpr uint32_t P_CH = 147456, P_CHSZ = 12800, P_H = 4352;
static_assert(P_CH + 6 * P_CHSZ <= G_BAR, "prologue smem");

template <int N>
__device__ __forceinline__ void conv_fold(float (*acc)[4], bool hi, uint32_t mine, uint32_t theirs, int bar, int cnt) {
#pragma unroll
  for (int i = 0; i < N / 2; i++) {
    uint4 v;
    v.x = __float_as_uint(hi ? acc[i][0] : acc[i + N / 2][0]); v.y = __float_as_uint(hi ? acc[i][1] : acc[i + N / 2][1]);
    v.z = __float_as_uint(hi ? acc[i][2] : acc[i + N / 2][2]); v.w = __float_as_uint(hi ? acc[i][3] : acc[i + N / 2][3]);
    sts128(mine + i * 512, v);
  }
  bar_sync(bar, cnt);
#pragma unroll
  for (int i = 0; i < N / 2; i++) {
    const uint4 v = lds128(theirs + i * 512);
    acc[i][0] = (hi ? acc[i + N / 2][0] : acc[i][0]) + __uint_as_float(v.x); acc[i][1] = (hi ? acc[i + N / 2][1] : acc[i][1]) + __uint_as_float(v.y);
    acc[i][2] = (hi ? acc[i + N / 2][2] : acc[i][2]) + __uint_as_float(v.z); acc[i][3] = (hi ? acc[i + N / 2][3] : acc[i][3]) + __uint_as_float(v.w);
  }
}
template <int N>
__device__ __forceinline__ void conv_store(const float (*acc)[4], int tile0, uint32_t su, int d, uint32_t dd) {
  const int lane = threadIdx.x & 31, g = lane >> 2, tq = lane & 3;
#pragma unroll
  for (int i = 0; i < N; i++) {
    const uint32_t ad = su + (8 + (tile0 + i) * 8 + g) * 32 + tq * 4, sw = (g & 4) << 2;
    const uint32_t lo = badd2(movmat(pack2(acc[i][0], acc[i][1])), bmul2(lds32(ad + sw), dd));
    const uint32_t hi = badd2(movmat(pack2(acc[i][2], acc[i][3])), bmul2(lds32(ad + (sw ^ 16)), dd));
    ((uint2*)g_yT)[(((tile0 + i) * 8 + g) * DM + d) * 4 + tq] = make_uint2(lo, hi);
  }
}

__device__ __forceinline__ void prologue(const Params& P, uint32_t sb) {
  const int b = bid(), tid = threadIdx.x, lane = tid & 31, warp = tid >> 5, t0 = b * 16;
  const bool isg = b >= N_CHAIN && b < N_CHAIN + N_G;
  const int nch = isg ? 2 : b < 128 ? 6 : 0, chb = b < N_CHAIN ? b * 6 : isg ? b * 2 + 256 : b * 6 - 192;
  const uint32_t tstart = clk();
  if (tid < 288) {
    if (b < 128) {
      const int c = (tid >> 1) * 4, tt = t0 + (tid & 1) * 8;
      uint2 kr[11], vr[8];
#pragma unroll
      for (int i = 0; i < 11; i++) { const int t = tt + i - 3; kr[i] = t >= 0 ? __ldg((const uint2*)(P.K + (size_t)t * DM + c)) : make_uint2(0, 0); }
#pragma unroll
      for (int i = 0; i < 8; i++) vr[i] = __ldg((const uint2*)(P.V + (size_t)(tt + i) * DM + c));
#pragma unroll
      for (int e = 0; e < 2; e++) {
        const uint4 sh = __ldg((const uint4*)(P.shift + c * 4) + e);
        const uint32_t s0 = __byte_perm(sh.x, sh.z, 0x5410), s1 = __byte_perm(sh.x, sh.z, 0x7632);
        const uint32_t s2 = __byte_perm(sh.y, sh.w, 0x5410), s3 = __byte_perm(sh.y, sh.w, 0x7632);
        uint32_t v[8];
#pragma unroll
        for (int i = 0; i < 8; i++) {
          const uint32_t k3 = e ? kr[i].y : kr[i].x, k2 = e ? kr[i + 1].y : kr[i + 1].x, k1 = e ? kr[i + 2].y : kr[i + 2].x, k0 = e ? kr[i + 3].y : kr[i + 3].x;
          v[i] = bmul2(badd2(badd2(badd2(bmul2(k3, s3), bmul2(k2, s2)), bmul2(k1, s1)), bmul2(k0, s0)), e ? vr[i].y : vr[i].x);
        }
        *(uint4*)(g_kvT + (size_t)(c + 2 * e) * KVP + tt) =
          make_uint4(__byte_perm(v[0], v[1], 0x5410), __byte_perm(v[2], v[3], 0x5410), __byte_perm(v[4], v[5], 0x5410), __byte_perm(v[6], v[7], 0x5410));
        *(uint4*)(g_kvT + (size_t)(c + 2 * e + 1) * KVP + tt) =
          make_uint4(__byte_perm(v[0], v[1], 0x7632), __byte_perm(v[2], v[3], 0x7632), __byte_perm(v[4], v[5], 0x7632), __byte_perm(v[6], v[7], 0x7632));
      }
    }
  } else if (tid < 384) {
    const int t = tid - 288;
    for (int i = b * 96 + t; i < 16 * DM; i += N_CTA * 96) ((uint4*)g_oacc)[i] = make_uint4(0, 0, 0, 0);
    if (b * 96 + t < 128 * 8) g_lnflag[b * 96 + t] = 0;
    if (t == 95) sts32(sb + S_GEN, ld_acquire(g_gbar));
    __syncwarp();
    wait_until(tstart, P.dly[23]);
    for (int i = t; i < 32 * nch; i += 96) asm volatile("prefetch.global.L2 [%0];" :: "l"(P.Hk + (size_t)chb * SEQ + i * 64));
  }
  if (warp < 12) {
    bar_arrive(10, 416);
    if (tid == 128) TS(14);
    const int ch = 5 - (warp >> 1), sub = warp & 1, d = chb + ch;
    const uint32_t su = sb + P_CH + ch * P_CHSZ;
    if (ch < nch) {
      const uint32_t* hs = (const uint32_t*)(P.Hk + (size_t)d * SEQ);
#pragma unroll
      for (int q = sub * 32 + lane; q < 256; q += 64) {
        const uint4 c = __ldg((const uint4*)hs + q);
        const uint32_t prev = q ? __ldg(hs + 4 * q - 1) : 0u;
        sts128(su + P_H + 32 + q * 16, make_uint4(__byte_perm(c.x, prev, 0x7610), __byte_perm(c.y, c.x, 0x7610), __byte_perm(c.z, c.y, 0x7610), __byte_perm(c.w, c.z, 0x7610)));
        sts128(su + P_H + 4224 + q * 16, make_uint4(__byte_perm(c.x, 0, 0x1032), __byte_perm(c.y, 0, 0x1032), __byte_perm(c.z, 0, 0x1032), __byte_perm(c.w, 0, 0x1032)));
      }
      if (sub == 1 && lane == 0) sts32(su + P_CHSZ - 16, __bfloat16_as_ushort(P.Dk[d]) * 0x10001u);
      if (sub == 0 && lane < 20) sts128(su + (lane < 16 ? lane * 16 : P_H + (lane & 2) * 2096 + (lane & 1) * 16), make_uint4(0, 0, 0, 0));
    }
    bar_sync(11, 416);
    if (ch < nch) {
#pragma unroll
      for (int q = sub * 32 + lane; q < 256; q += 64) {
        const int row = (q >> 1) + 8;
        sts128(su + row * 32 + (((q & 1) ^ ((row >> 2) & 1)) << 4), __ldcg((const uint4*)(g_kvT + (size_t)d * KVP) + q));
      }
    }
    const int g = lane >> 2, tq = lane & 3;
    const uint32_t sh = su + P_H + (g & 1) * 4192 + (8 + (g >> 1) - tq) * 4;
    float acc[16][4];
#pragma unroll
    for (int i = 0; i < 16; i++) { acc[i][0] = acc[i][1] = acc[i][2] = acc[i][3] = 0.f; }
    auto u_addr = [&](int res) {
      const int row = 8 - res + ((lane >> 4) << 3) + (lane & 7);
      return su + row * 32 + ((((lane >> 3) & 1) ^ ((row >> 2) & 1)) << 4);
    };
    if (ch < nch) {
      bar_sync(1 + ch, 64);
      if (tid == 352) TS(11);
      if (sub) {
#pragma unroll 4
        for (int res = 0; res < 8; res++) {
          uint32_t b0, b1, b2, b3;
          ldsm4(b0, b1, b2, b3, u_addr(res));
          const uint32_t r0 = lds32(sh + res * 32);
          mma16(acc[0], r0, lds32(sh + res * 32 + 16), lds32(sh + res * 32 - 16), r0, b0, b1);
        }
        conv_store<1>(acc, 0, su, d, lds32(su + P_CHSZ - 16));
      }
    }
    bar_arrive(12, 416);
    if (isg && warp < 8) { while ((int)(clk() - tstart - S1G) < 0) __nanosleep(200); load_wg<GROLE>(P, sb, true, warp >> 2, warp & 3); }
    if (ch < nch) {
#pragma unroll 1
      for (int res = sub * 4; res < sub * 4 + 4; res++) {
        uint32_t bf[16][2];
        const uint32_t ad = u_addr(res);
#pragma unroll
        for (int f = 0; f < 16; f += 2) ldsm4(bf[f][0], bf[f][1], bf[f + 1][0], bf[f + 1][1], ad + f * 256);
#pragma unroll
        for (int k = 0; k < 16; k++) {
          const int jj = k & 1 ? k >> 1 : 15 - (k >> 1);
          const uint32_t ah = sh + (8 * jj + res) * 32;
          const uint32_t r0 = lds32(ah), r1 = lds32(ah + 16), rm = lds32(ah - 16);
#pragma unroll
          for (int i = max(jj, 1); i < 16; i++) mma16(acc[i], r0, r1, rm, r0, bf[i - jj][0], bf[i - jj][1]);
        }
      }
      bar_sync(1 + ch, 64);
      if (tid == 352) TS(12);
      const uint32_t xb = su + P_H + lane * 16, dd = lds32(su + P_CHSZ - 16);
      conv_fold<16>(acc, sub, xb + sub * 4096, xb + (sub ^ 1) * 4096, 1 + ch, 64);
      conv_store<8>(acc, sub * 8, su, d, dd);
    }
  } else {
    for (int i = b; i < 194 + MRING * 5; i += N_CTA) {
      const int n = (i - 194) / 5, r = (i - 194) % 5, blk = i < 192 ? i / 6 * 8 + i % 6 : i < 194 ? XB_F + i - 192 : XB_M + n * 8 + r;
      const uint32_t fill = i < 194 ? 0u : SENT;
#pragma unroll 1
      for (int q = tid - 384; q < 256 && warp < 15; q += 96) {
        uint4 v = make_uint4(fill, fill, fill, fill);
        if (i >= 194 && n == 0 && (r > 0 || q < 128)) {
          const bf16* m = P.mem0 + (max(r * 8 - 4, 0) + (q >> 5)) * 16 + ((q >> 1) & 1) * 8 + ((q >> 2) & 7);
          v.x = pack2(__bfloat162float(m[0]), __bfloat162float(m[DM])); v.y = pack2(__bfloat162float(m[2 * DM]), __bfloat162float(m[3 * DM]));
          v.z = pack2(__bfloat162float(m[4 * DM]), __bfloat162float(m[5 * DM])); v.w = pack2(__bfloat162float(m[6 * DM]), __bfloat162float(m[7 * DM]));
        }
        g_xb[blk * 512 + q] = v;
        g_xb[blk * 512 + 256 + q] = v;
      }
    }
    if (tid < 388) g_xb[XB_REF * 512 + (tid & 2) * 128 + (b & ~1) + (tid & 1)] = make_uint4(0, 0, 0, 0);
    else if (tid < 392 && b < N_GRP) g_xb[(b * 8 + 7) * 512 + (tid & 2) * 128 + (tid & 1)] = make_uint4(0, 0, 0, 0);
    if (warp < 15) { bar_arrive(9, 128); bar_sync(7, 96); }
    if (tid == 384) TS(8);
    if (warp == 12) {
      const bf16* w = lane < 6 ? (lane % 3 == 0 ? P.Wk : lane % 3 == 1 ? P.Wv : P.Wq) + (((b >> 5) * 2 + lane / 3) * 32 + (b & 31)) * 2048
                               : (lane < 8 ? P.Wo + (lane - 6) * (9 * 131072) : P.X) + b * 2048;
      uint32_t t = tstart + P.dly[19];
      if ((int)(clk() - t) > 0) t = clk();
#pragma unroll 1
      for (int st = 0; st < 9 && b < N_CHAIN; st++) {
#pragma unroll 1
        for (int i = 0; i < 9; i++, t += PACE) {
          wait_until(t, 0);
          if (lane == st) asm volatile("cp.async.bulk.prefetch.L2.global [%0], 4096;" :: "l"(w + i * (lane < 6 ? 262144 : 131072)) : "memory");
        }
      }
      if (lane == 0) TS(10);
    } else if (warp == 15) {
      bar_sync(10, 416);
      if (lane == 0) { grid_arrive(0); if (nch) grid_wait(0, lds32(sb + S_GEN)); }
      __syncwarp();
      bar_arrive(11, 416);
      if (lane == 0) TS(1);
      bar_sync(9, 128);
      bar_sync(12, 416);
      if (lane == 0) { TS(16); grid_arrive(2); TS(17); }
    } else if (lane == 0) {
      if (warp == 13 || (warp == 14 && b < N_GRP)) {
        uint32_t* p = (uint32_t*)(g_xb + (warp == 13 ? XB_REF * 512 + b : (b * 8 + 7) * 512));
        int votes = 0;
        for (int rep = 0; rep < 24 && abs(votes) < 7; rep++) {
          uint32_t v0, v1, c0, c1;
          asm volatile("atom.relaxed.gpu.global.add.u32 %0, [%4], 0;\n atom.relaxed.gpu.global.add.u32 %1, [%5], 0;\n"
                       "{.reg .pred p; setp.eq.u32 p, %0, 0x7ffffff3; @p trap; mov.u32 %2, %%clock; setp.eq.u32 p, %1, 0x7ffffff3; @p trap; mov.u32 %3, %%clock;}"
                       : "=&r"(v0), "=&r"(v1), "=&r"(c0), "=&r"(c1) : "l"(p + (rep & 1) * 1024), "l"(p + ((rep & 1) ^ 1) * 1024) : "memory");
          votes += ((c1 - c0 > 80u) == (rep & 1)) ? 1 : -1;
        }
        if (warp == 13) { g_side[b] = votes > 0; TS(9); } else g_near[b] = votes > 0;
      }
    }
    __syncwarp();
    if (warp > 12 && b < N_CHAIN) {
      while ((int)(clk() - tstart - S1DLY) < 0) __nanosleep(200);
      for (int k = warp - 13; k < 8; k += 3) load_wg<CHAIN>(P, sb, true, 1 - k / 4, k & 3);
    }
  }
  if (b < N_CHAIN + N_G && (warp < 8 || (isg && warp >= 12))) bar_arrive(0, 512); else bar_sync(0, 512);
  if (tid == 352) TS(2);
}

__device__ __forceinline__ void publish_y() {
  if (threadIdx.x == 383) { grid_arrive(1); TS(18); }
  __syncwarp();
}

template <int R> __device__ __forceinline__ void ln_tiles(const Params& P, uint32_t sb) {
  const int lane = threadIdx.x & 31, w = (threadIdx.x >> 5) & (16 / R - 1), half = R == 1 ? 0 : threadIdx.x >> 8, u = N_CTA - 1 - bid();
  const int first = R == 1 ? u : 46 - 2 * u + half, step = R == 1 ? 4 : 40, last = R == 1 ? 8 : 128;
  const uint32_t raw = sb + P_CH + half * (18432 + Y_ROWS), mb = sb + T_BAR + (R - 1 + half) * 8;
  const bool lead = w == 16 / R - 1 && lane == 0;
  auto load_y = [&](const bf16* src, int tile) {
    fence_async_global();
    mbar_expect(mb, 18432);
    bulk_load(raw, src + (size_t)tile * 16 * DM, 18432, mb);
  };
  uint32_t nx[9 * R];
  auto load_x = [&](int tile) {
#pragma unroll
    for (int i = 0; i < 9 * R; i++) nx[i] = __ldg((const uint32_t*)(P.X + (size_t)(tile * 16 + w + i / 9 * 8) * DM) + i % 9 * 32 + lane);
  };
  load_x(first);
  if (R == 2) {
    if (lead) { grid_wait(1, lds32(sb + S_GEN)); if (u > 3) TS(13); load_y(g_yT, first); }
    __syncwarp();
  }
#pragma unroll 1
  for (int tile = first, real = R - 1, ph = 0; tile < last; tile += real * step, real = 1, ph ^= 1) {
    uint32_t x[9 * R], l[9 * R], y[9 * R];
    const bool ts = threadIdx.x == 0 && (R == 1 ? tile == first : u > 3 && tile == first + step);
    if (ts) TS(26);
#pragma unroll
    for (int i = 0; i < 9 * R; i++) x[i] = nx[i];
    layernorm9<R>(x, l);
    if (real && tile + step < last) load_x(tile + step);
    if (R == 2 && tile == first + step && u >= N_F && w < 6) load_wg<OROLE>(P, sb, true, w >> 1, half * 2 + (w & 1));
    if (R == 1 && tile == first && lead) {
      if (real) grid_wait(2, lds32(sb + S_GEN));
      TS(13);
      load_y(real ? g_yT : P.Hk, tile);
    }
    bar_sync(13 + half, 512 / R);
    mbar_wait(mb, ph);
    if (ts) TS(28);
    y_rows<R>(y, raw, raw + 18432, w, 13 + half);
    if (ts) TS(29);
    if (lead && real && tile + step < last) { fence_async_smem(); load_y(g_yT, tile + step); }
    __syncwarp();
#pragma unroll
    for (int i = 0; i < 9 * R; i++) x[i] = badd2(x[i], bmul2(l[i], y[i]));
    layernorm9<R>(x, l);
    if (ts && l[0] != 0x12345) TS(30);
#pragma unroll
    for (int r = 0; r < R; r++) store_ln_row(0, tile * 16 + w + r * 8, l + r * 9);
    if (R == 1) {
      __syncthreads();
      if (threadIdx.x == 32 && real) { if (tile < 4) TS(19); st_release(g_lnflag + tile * 8, 1); if (tile < 4) TS(20); }
      __syncwarp();
    }
    if (ts) TS(31);
  }
  if (R == 2) {
    __syncthreads();
    if (threadIdx.x >= 506) {
      asm volatile("fence.acq_rel.gpu;" ::: "memory");
      st_relaxed_if(g_lnflag + ((first ^ (lane & 1)) + (lane - 26) / 2 * step) * 8, 1, true);
    }
    __syncwarp();
    fence_async_smem();
    if (threadIdx.x == 0) TS(15);
  }
}

__global__ void __cluster_dims__(2, 1, 1) __launch_bounds__(512, 1) k_main(const __grid_constant__ Params P) {
  extern __shared__ __align__(1024) unsigned char smem[];
  const uint32_t sb = (uint32_t)__cvta_generic_to_shared(smem);
  const int b = bid(), wg = threadIdx.x >> 7;
  if ((threadIdx.x & 127) == 0) TS(0);
  if (threadIdx.x == 480) {
    if ((sb & 0xFFFFFF) != SBASE) __trap();
    for (int i = 0; i < 6; i++) mbar_init(sb + W_BAR + i * 8, 1);
    if (b < N_CHAIN) {
      mbar_init(sb + CB_FULL, 1); mbar_init(sb + CB_FULL + 8, 1);
      mbar_init(sb + CB_REF, 1);
      mbar_init(sb + CB_SX, 1); mbar_init(sb + CB_OX, 1); mbar_init(sb + CB_XX, 1); mbar_init(sb + CB_Q, 2); mbar_init(sb + CB_VF, 1); mbar_init(sb + CB_VF + 8, 1);
      sts32(sb + C_BAD, 0);
      for (int i = 0; i < 11; i++) mbar_init(sb + CB_M + i * 8, i == 0 ? 5 : i == 5 ? 3 : 1);
    } else if (b < N_CHAIN + N_G) {
      for (int i = 0; i < 9; i++) { mbar_init(sb + G_BAR + i * 8, 2); mbar_init(sb + G_BAR + 128 + i * 8, 8); }
    } else if (b < N_CHAIN + N_G + N_O) {
      for (int i = 0; i < 5; i++) { mbar_init(sb + O_BAR + i * 8, 1); mbar_init(sb + O_BAR + 128 + i * 8, 12); }
      for (int i = 0; i < 6; i++) mbar_init(sb + OB_ST + i * 8, 1);
    } else {
      mbar_init(sb + F_BAR, 1); mbar_init(sb + F_BAR + 8, 1);
    }
    asm volatile("fence.mbarrier_init.release.cluster;" ::: "memory");
    fence_async_smem();
  }
  __syncwarp();
  asm volatile("barrier.cluster.arrive.relaxed.aligned;" ::: "memory");
  prologue(P, sb);
  asm volatile("barrier.cluster.wait.aligned;" ::: "memory");
  fence_async_smem();
  if (b >= N_CHAIN + N_G) publish_y();
  if (b >= 128) ln_tiles<1>(P, sb);
  if (b >= N_CHAIN + N_G) ln_tiles<2>(P, sb);
  if ((threadIdx.x & 127) == 0) TS(3);
  if (b < N_CHAIN) {
    if (wg < 2) { reg_inc<200>(); chain_proj(P, sb); }
    else if (wg == 2) { reg_dec<ATTR>(); publish_y(); chain_attn(P, sb); }
    else { reg_dec<112 - ATTR>(); chain_aux(P, sb); }
  } else if (NOBULK) {
    if (b < N_CHAIN + N_G) publish_y();
    {
      if (wg == 0) {
        float d[4] = {0.f, 0.f, 0.f, 0.f};
        for (int n = 0; n < STEPS - 1; n++) {
          const uint32_t* f = g_fl + FL_TICK;
          uint32_t x;
          do { for (int k = 0; k < 16; k++) mma16(d, 0, 0, 0, 0, 0, 0); asm volatile("ld.relaxed.gpu.global.u32 %0, [%1];" : "=r"(x) : "l"(f) : "memory"); } while ((x >> 24) <= n);
          const int q = (b - N_CHAIN) * 4 + (threadIdx.x >> 5);
          if (n + 5 >= MRING && q < 80) fill16((uint4*)g_mimg + (uint32_t)(((n + 5) % MRING) * 4096 + q * 32 + (threadIdx.x & 31)), SENT);
        }
        if (d[0] == 1.f) P.out[0] = __float2bfloat16(0.f);
      }
    }
  } else if (b < N_CHAIN + N_G) {
    if (wg == 0) { reg_inc<232>(); g_math<0>(P, sb); }
    else if (wg == 1) { reg_inc<232>(); g_math<1>(P, sb); }
    else if (wg == 2) { reg_dec<24>(); bar_arrive(15, 192); publish_y(); g_aux(P, sb); }
    else { reg_dec<24>(); g_load(P, sb); }
  } else if (b < N_CHAIN + N_G + N_O) {
    if (wg == 0) { reg_inc<160>(); o_math<0>(P, sb); }
    else if (wg == 1) { reg_inc<160>(); o_math<1>(P, sb); }
    else if (wg == 2) { reg_inc<160>(); o_math<2>(P, sb); }
    else { reg_dec<32>(); o_aux(P, sb); }
  } else {
    f_role(P, sb);
  }
}

}

extern "C" void kernel_launch(void* const* d_in, const int* in_sizes, int n_in, void* d_out, int out_size) {
  typedef CUresult (*Encode)(CUtensorMap*, CUtensorMapDataType, cuuint32_t, void*, const cuuint64_t*, const cuuint64_t*, const cuuint32_t*, const cuuint32_t*,
                             CUtensorMapInterleave, CUtensorMapSwizzle, CUtensorMapL2promotion, CUtensorMapFloatOOBfill);
  static Encode encode = nullptr;
  if (!encode) cudaGetDriverEntryPoint("cuTensorMapEncodeTiled", (void**)&encode, cudaEnableDefault);
  Params P;
  for (int i = 0; i < 11; i++) {
    const bool wo = i == 6 || i == 7;
    const cuuint64_t cols = wo ? DM : HD, rows = HD + DM - cols, pitch = cols * 2;
    const cuuint64_t dim[4][5] = {{cols, 2, 8, 2, 18}, {cols, 16, 1, 1, rows / 16}, {cols, 2, 4, 4, rows / 32}, {64, 16, 64, 2, 18}};
    const cuuint64_t stride[4][4] = {{8 * pitch, pitch, 16 * pitch, 32 * pitch}, {pitch, pitch, pitch, 16 * pitch},
                                     {pitch, 8 * pitch, 2 * pitch, 32 * pitch}, {pitch, 128, 16 * pitch, 32 * pitch}};
    const cuuint32_t box[4][5] = {{64, 2, 8, 1, 18}, {64, 16, 1, 1, 1}, {64, 2, 4, 2, 1}, {64, 16, 2, 1, 18}}, one[5] = {1, 1, 1, 1, 1};
    const int k = i < 3 ? 0 : i < 7 ? 1 : i < 8 ? 2 : 3;
    encode(&P.map[i], CU_TENSOR_MAP_DATA_TYPE_BFLOAT16, 5, d_in[wo ? 11 : 8 + (i & 7) % 3], dim[k], stride[k], box[k], one,
           CU_TENSOR_MAP_INTERLEAVE_NONE, CU_TENSOR_MAP_SWIZZLE_128B, CU_TENSOR_MAP_L2_PROMOTION_L2_128B, CU_TENSOR_MAP_FLOAT_OOB_FILL_NONE);
  }
  P.X = (const bf16*)d_in[0]; P.K = (const bf16*)d_in[1]; P.V = (const bf16*)d_in[2];
  P.shift = (const bf16*)d_in[3]; P.Hk = (const bf16*)d_in[4]; P.Dk = (const bf16*)d_in[5];
  P.mem0 = (const bf16*)d_in[7];
  P.Wq = (const bf16*)d_in[8]; P.Wk = (const bf16*)d_in[9]; P.Wv = (const bf16*)d_in[10]; P.Wo = (const bf16*)d_in[11];
  P.out = (bf16*)d_out;
  for (int i = 0; i < 24; i++) P.dly[i] = h_dly[i];
  cudaFuncSetAttribute(k_main, cudaFuncAttributeMaxDynamicSharedMemorySize, SMEM_BYTES);
  k_main<<<N_CTA, 512, SMEM_BYTES>>>(P);
}
```

```cpp
#include <cuda.h>
#include <cuda_runtime.h>
#include <cuda_bf16.h>
#include <stdint.h>

namespace {

typedef __nv_bfloat16 bf16;

constexpr int SEQ = 2048, DM = 576, HD = 4096, NSEG = 64;
#define PLACE 1
#define LAGV 7
constexpr int LAG = LAGV, STEPS = NSEG + LAG, RING = 8, QRING = 4;
static_assert(LAG < RING, "ring");
constexpr int N_CHAIN = 64, N_G = 48, N_O = 18, N_F = 2;
constexpr uint32_t SBASE = 1024;
constexpr uint32_t SENT = 0xFFFFFFFFu;
constexpr int SPIN_MAX = 1 << 22;

__device__ __forceinline__ uint32_t bid() {
  uint32_t b;
  asm volatile("mov.u32 %0, %%ctaid.x;" : "=r"(b));
  return b < 6 ? b + 106 : b < 8 ? b + 122 : b < 114 ? b - 8 : b < 130 ? b - 2 : b;
}
__device__ __forceinline__ uint32_t chain_id() { return blockIdx.x - (PLACE ? 8 : 0); }
constexpr int KVP = SEQ + 64;
__device__ __align__(1024) bf16 g_kvT[DM * KVP];
__device__ __align__(1024) bf16 g_yT[DM * SEQ];
__device__ __align__(1024) unsigned char g_lnimg[2 * NSEG * 9 * 4096];
__device__ __align__(1024) unsigned char g_qkv[QRING * N_CHAIN * 24576];
__device__ __align__(1024) unsigned char g_oimg[RING * N_CHAIN * 8192];
constexpr int ARING = 16;
static_assert(ARING >= LAG + 9, "accumulator ring");
__device__ __align__(1024) float g_oacc[ARING * 64 * DM];
constexpr int MRING = LAG + 4, N_GRP = 32 + MRING + 1;
constexpr int XB_M = 256, XB_F = XB_M + MRING * 8, XB_REF = XB_F + 2, N_CTA = N_CHAIN + N_G + N_O + N_F;
__device__ __align__(65536) uint4 g_xb[N_GRP * 4096];
#define g_mimg ((uint32_t*)(g_xb + XB_M * 512))
__device__ uint32_t g_near[N_GRP];
__device__ uint32_t g_side[N_CTA];
__device__ __align__(128) uint32_t g_gbar[3 * 32];
constexpr int FL_G = 0, FL_F = 96 * 8, FL_OCNT = FL_F + 2 * 8, OCRING = 16, FL_TICK = 992, FL_O = 2048, FL_SYNC = FL_O + 128;
static_assert(FL_OCNT + OCRING * 8 <= FL_TICK, "flag block");
#define g_fl ((uint32_t*)(g_xb + XB_F * 512))
__device__ __align__(1024) uint32_t g_lnflag[128 * 8];
#define TS(slot)

#define OTURN 2
#define LOCK0 3
#define FASTO 0
#define FASTG 0
#define NOBULK 0
#define VPAT 0x15bbd249u
#define XR 3
#define WFENCE 0
#define QPOS 0
#define VE 4
#define OGAP 2
#define NOCHAIN 0
#define BFENCE 2
#define ABL 0
#define ATTR 80
#define CNT(slot, tries)
#define T3(slot)
#define TR(slot)
#define TRV(slot, val)
#define TRD(slot, dep)
#define TRSYNC()
#define TRDUMP(n)
#define CLK(t) "{.reg .b64 x; .reg .b32 h; mov.u64 x, %%clock64; mov.b64 {" t ", h}, x;}"
__device__ __forceinline__ uint32_t clk() { uint32_t t; asm volatile(CLK("%0") : "=r"(t) :: "memory"); return t; }
__device__ __forceinline__ void wait_until(uint32_t t0, uint32_t d) {
  asm volatile("{.reg .pred p; .reg .u32 t;\n"
               "W: " CLK("t") " sub.u32 t, t, %0; setp.lt.s32 p, t, 0; @p bra.uni W;}"
               :: "r"(t0 + d) : "memory");
}
__device__ __forceinline__ uint32_t pack2(float lo, float hi) {
  uint32_t r; asm("cvt.rn.bf16x2.f32 %0, %1, %2;" : "=r"(r) : "f"(hi), "f"(lo)); return r;
}
__device__ __forceinline__ float bf_lo(uint32_t v) { return __uint_as_float(v << 16); }
__device__ __forceinline__ float bf_hi(uint32_t v) { return __uint_as_float(v & 0xFFFF0000u); }

__device__ __forceinline__ uint4 ld_relaxed4(const void* p) {
  uint4 v; asm volatile("ld.relaxed.gpu.global.v4.u32 {%0,%1,%2,%3}, [%4];" : "=r"(v.x), "=r"(v.y), "=r"(v.z), "=r"(v.w) : "l"(p) : "memory"); return v;
}
__device__ __forceinline__ void st_b128(void* p, uint32_t a, uint32_t b, uint32_t c, uint32_t d) {
  asm volatile("{.reg .b128 v; mov.b128 v, {%1,%2,%3,%4}; st.relaxed.gpu.global.b128 [%0], v;}" :: "l"(p), "r"(a), "r"(b), "r"(c), "r"(d) : "memory");
}
__device__ __forceinline__ void reload_b128(uint4& v, const void* p, uint32_t again) {
  asm volatile("{.reg .pred p; .reg .b128 v; setp.ne.u32 p, %5, 0; mov.b128 v, {%0,%1,%2,%3};\n"
               "@p ld.relaxed.gpu.global.b128 v, [%4]; mov.b128 {%0,%1,%2,%3}, v;}"
    : "+r"(v.x), "+r"(v.y), "+r"(v.z), "+r"(v.w) : "l"(p), "r"(again) : "memory");
}
__device__ __forceinline__ void reload4(uint4& v, const void* p, uint32_t again) {
  asm volatile("{.reg .pred p; setp.ne.u32 p, %5, 0; @p ld.relaxed.gpu.global.v4.u32 {%0,%1,%2,%3}, [%4];}"
    : "+r"(v.x), "+r"(v.y), "+r"(v.z), "+r"(v.w) : "l"(p), "r"(again) : "memory");
}
__device__ __forceinline__ void st_relaxed4(void* p, uint32_t a, uint32_t b, uint32_t c, uint32_t d) {
  asm volatile("st.relaxed.gpu.global.v4.u32 [%0], {%1,%2,%3,%4};" :: "l"(p), "r"(a), "r"(b), "r"(c), "r"(d) : "memory");
}
__device__ __forceinline__ void st_relaxed_if(void* p, uint32_t a, bool on) {
  asm volatile("{.reg .pred p; setp.ne.u32 p, %2, 0; @p st.relaxed.gpu.global.u32 [%0], %1;}" :: "l"(p), "r"(a), "r"((uint32_t)on) : "memory");
}
__device__ __forceinline__ uint32_t ld_acquire(const uint32_t* p) {
  uint32_t v; asm volatile("ld.acquire.gpu.global.u32 %0, [%1];" : "=r"(v) : "l"(p) : "memory"); return v;
}
__device__ __forceinline__ void st_release(uint32_t* p, uint32_t v) {
  asm volatile("st.release.gpu.global.u32 [%0], %1;" :: "l"(p), "r"(v) : "memory");
}
__device__ __forceinline__ void bulk_reduce(float* dst, uint32_t src, uint32_t bytes) {
  asm volatile("cp.reduce.async.bulk.global.shared::cta.bulk_group.add.f32 [%0], [%1], %2;" :: "l"(dst), "r"(src), "r"(bytes) : "memory");
}
__device__ __forceinline__ void bulk_done_inc(uint32_t* p) {
  asm volatile("cp.async.bulk.wait_group 0;\n"
               "fence.proxy.async.global;\nfence.release.gpu;\n"
               "red.relaxed.gpu.global.add.u32 [%0], 1;\nred.relaxed.gpu.global.add.u32 [%0+4096], 1;" :: "l"(p) : "memory");
}
__device__ __forceinline__ void flag_release(uint32_t* p, uint32_t v) {
  asm volatile("fence.release.gpu;\nst.relaxed.gpu.global.u32 [%0], %1;\nst.relaxed.gpu.global.u32 [%0+4096], %1;" :: "l"(p), "r"(v) : "memory");
}
__device__ __forceinline__ void spin_guard(int& it) {
  asm volatile("{.reg .pred p; add.s32 %0, %0, 1; setp.gt.s32 p, %0, %1; @p trap;}" : "+r"(it) : "n"(SPIN_MAX));
}
__device__ __forceinline__ void wait_flag(const uint32_t* p, uint32_t v) {
  int it = 0;
  while (ld_acquire(p) < v) spin_guard(it);
}
__device__ __forceinline__ void wait_flags(const uint32_t* p, uint32_t v) {
  int it = 0;
  while (true) {
    uint32_t x; asm volatile("ld.relaxed.gpu.global.u32 %0, [%1];" : "=r"(x) : "l"(p) : "memory");
    if (__all_sync(~0u, x >= v)) break;
    spin_guard(it);
  }
  asm volatile("fence.acquire.gpu;" ::: "memory");
}
__device__ __forceinline__ uint32_t timer_offset() {
  uint32_t g0, g;
  asm volatile("mov.u32 %0, %%globaltimer_lo;" : "=r"(g0) :: "memory");
  do { asm volatile("mov.u32 %0, %%globaltimer_lo;" : "=r"(g) :: "memory"); } while (g == g0);
  return (g >> 5) * 58 - clk();
}
__device__ __forceinline__ void grid_arrive(int i) {
  asm volatile("red.release.gpu.global.add.u32 [%0], %1;" :: "l"(g_gbar + i * 32), "r"(bid() ? 1u : 257u - N_CTA) : "memory");
}
__device__ __forceinline__ void grid_wait(int i, uint32_t gen) {
  int it = 0;
  while (((ld_acquire(g_gbar + i * 32) ^ gen) >> 8) == 0) spin_guard(it);
}
__device__ __forceinline__ bool elect() {
  uint32_t r; asm volatile("{.reg .pred p; elect.sync _|p, -1; selp.u32 %0, 1, 0, p;}" : "=r"(r)); return r;
}
__device__ __forceinline__ void bar_sync(int id, int cnt) { asm volatile("bar.sync %0, %1;" :: "r"(id), "r"(cnt) : "memory"); }
__device__ __forceinline__ void bar_arrive(int id, int cnt) { asm volatile("bar.arrive %0, %1;" :: "r"(id), "r"(cnt) : "memory"); }
template <int id, int cnt> __device__ __forceinline__ void bar_arrive_after(uint32_t a, uint32_t b) {
  asm volatile("{.reg .pred p; setp.ne.u32 p, %2, 0xfff12345; setp.ne.and.u32 p, %3, 0xfff12345, p; @p bar.arrive %0, %1;}" :: "n"(id), "n"(cnt), "r"(a), "r"(b) : "memory");
}
template <int id, int cnt> __device__ __forceinline__ void bar_sync_after(uint32_t a) {
  asm volatile("{.reg .pred p; setp.ne.u32 p, %2, 0xfff12345; @p bar.sync %0, %1;}" :: "n"(id), "n"(cnt), "r"(a) : "memory");
}
__device__ __forceinline__ void fence_async_smem() { asm volatile("fence.proxy.async.shared::cta;" ::: "memory"); }
__device__ __forceinline__ void fence_async_global() { asm volatile("fence.proxy.async.global;" ::: "memory"); }
__device__ __forceinline__ void mbar_init(uint32_t mb, int cnt) { asm volatile("mbarrier.init.shared::cta.b64 [%0], %1;" :: "r"(mb), "r"(cnt) : "memory"); }
__device__ __forceinline__ void mbar_arrive(uint32_t mb) { asm volatile("mbarrier.arrive.shared::cta.b64 _, [%0];" :: "r"(mb) : "memory"); }
__device__ __forceinline__ void mbar_arrive_after(uint32_t mb, uint32_t a, uint32_t lane) {
  asm volatile("{.reg .pred p; setp.ne.u32 p, %1, 0xfff12345; setp.eq.and.u32 p, %2, 0, p; @p mbarrier.arrive.shared::cta.b64 _, [%0];}" :: "r"(mb), "r"(a), "r"(lane) : "memory");
}
__device__ __forceinline__ void mbar_expect(uint32_t mb, uint32_t bytes) {
  asm volatile("mbarrier.arrive.expect_tx.shared::cta.b64 _, [%0], %1;" :: "r"(mb), "r"(bytes) : "memory");
}
__device__ __forceinline__ void mbar_wait_guard(uint32_t mb, uint32_t parity) {
  uint32_t ok; int it = 0;
  while (true) {
    asm volatile("{.reg .pred p; mbarrier.try_wait.parity.shared::cta.b64 p, [%1], %2; selp.u32 %0, 1, 0, p;}" : "=r"(ok) : "r"(mb), "r"(parity) : "memory");
    if (ok) break;
    spin_guard(it);
  }
}
__device__ __forceinline__ void mbar_wait(uint32_t mb, uint32_t parity) {
  asm volatile("{.reg .pred p;\nW: mbarrier.try_wait.parity.shared::cta.b64 p, [%0], %1;\n@!p bra W;}" :: "r"(mb), "r"(parity) : "memory");
}
__device__ __forceinline__ void bulk_load(uint32_t dst, const void* src, uint32_t bytes, uint32_t mb) {
  asm volatile("cp.async.bulk.shared::cluster.global.mbarrier::complete_tx::bytes [%0], [%1], %2, [%3];" :: "r"(dst), "l"(src), "r"(bytes), "r"(mb) : "memory");
}
__device__ __forceinline__ void bulk_store(void* dst, uint32_t src, uint32_t bytes) {
  asm volatile("cp.async.bulk.global.shared::cta.bulk_group [%0], [%1], %2;" :: "l"(dst), "r"(src), "r"(bytes) : "memory");
}
__device__ __forceinline__ void cp_async16(uint32_t dst, const void* src) {
  asm volatile("cp.async.cg.shared.global [%0], [%1], 16;" :: "r"(dst), "l"(src) : "memory");
}
__device__ __forceinline__ void cp_async_wait_all() { asm volatile("cp.async.wait_all;" ::: "memory"); }
__device__ __forceinline__ uint32_t mapa(uint32_t a, uint32_t rank) {
  uint32_t r; asm("mapa.shared::cluster.u32 %0, %1, %2;" : "=r"(r) : "r"(a), "r"(rank)); return r;
}
__device__ __forceinline__ void st_async4(uint32_t dst, float a, float b, float c, float d, uint32_t mb) {
  asm volatile("st.async.shared::cluster.mbarrier::complete_tx::bytes.v4.f32 [%0], {%1,%2,%3,%4}, [%5];" :: "r"(dst), "f"(a), "f"(b), "f"(c), "f"(d), "r"(mb) : "memory");
}
__device__ __forceinline__ void st_async2(uint32_t dst, float a, float b, uint32_t mb) {
  asm volatile("st.async.shared::cluster.mbarrier::complete_tx::bytes.v2.f32 [%0], {%1,%2}, [%3];" :: "r"(dst), "f"(a), "f"(b), "r"(mb) : "memory");
}
__device__ __forceinline__ void st_async1(uint32_t dst, uint32_t a, uint32_t mb) {
  asm volatile("st.async.shared::cluster.mbarrier::complete_tx::bytes.u32 [%0], %1, [%2];" :: "r"(dst), "r"(a), "r"(mb) : "memory");
}
__device__ __forceinline__ uint4 lds128(uint32_t a) {
  uint4 v; asm volatile("ld.shared.v4.u32 {%0,%1,%2,%3}, [%4];" : "=r"(v.x), "=r"(v.y), "=r"(v.z), "=r"(v.w) : "r"(a) : "memory"); return v;
}
__device__ __forceinline__ uint2 lds64(uint32_t a) {
  uint2 v; asm volatile("ld.shared.v2.u32 {%0,%1}, [%2];" : "=r"(v.x), "=r"(v.y) : "r"(a) : "memory"); return v;
}
__device__ __forceinline__ uint32_t lds32(uint32_t a) {
  uint32_t v; asm volatile("ld.shared.u32 %0, [%1];" : "=r"(v) : "r"(a) : "memory"); return v;
}
__device__ __forceinline__ void sts128(uint32_t a, uint4 v) {
  asm volatile("st.shared.v4.u32 [%0], {%1,%2,%3,%4};" :: "r"(a), "r"(v.x), "r"(v.y), "r"(v.z), "r"(v.w) : "memory");
}
__device__ __forceinline__ void sts64(uint32_t a, uint32_t x, uint32_t y) {
  asm volatile("st.shared.v2.u32 [%0], {%1,%2};" :: "r"(a), "r"(x), "r"(y) : "memory");
}
__device__ __forceinline__ void sts32(uint32_t a, uint32_t x) { asm volatile("st.shared.u32 [%0], %1;" :: "r"(a), "r"(x) : "memory"); }
__device__ __forceinline__ void ldsm4(uint32_t& r0, uint32_t& r1, uint32_t& r2, uint32_t& r3, uint32_t a) {
  asm volatile("ldmatrix.sync.aligned.m8n8.x4.shared.b16 {%0,%1,%2,%3}, [%4];" : "=r"(r0), "=r"(r1), "=r"(r2), "=r"(r3) : "r"(a) : "memory");
}
__device__ __forceinline__ void ldsm4t(uint32_t& r0, uint32_t& r1, uint32_t& r2, uint32_t& r3, uint32_t a) {
  asm volatile("ldmatrix.sync.aligned.m8n8.x4.trans.shared.b16 {%0,%1,%2,%3}, [%4];" : "=r"(r0), "=r"(r1), "=r"(r2), "=r"(r3) : "r"(a) : "memory");
}
__device__ __forceinline__ void stsm4(uint32_t a, uint32_t r0, uint32_t r1, uint32_t r2, uint32_t r3) {
  asm volatile("stmatrix.sync.aligned.m8n8.x4.shared.b16 [%0], {%1,%2,%3,%4};" :: "r"(a), "r"(r0), "r"(r1), "r"(r2), "r"(r3) : "memory");
}
__device__ __forceinline__ uint32_t movmat(uint32_t a) {
  uint32_t d; asm volatile("movmatrix.sync.aligned.m8n8.trans.b16 %0, %1;" : "=r"(d) : "r"(a)); return d;
}
__device__ __forceinline__ void mma16(float* d, uint32_t a0, uint32_t a1, uint32_t a2, uint32_t a3, uint32_t b0, uint32_t b1) {
  asm volatile("mma.sync.aligned.m16n8k16.row.col.f32.bf16.bf16.f32 {%0,%1,%2,%3}, {%4,%5,%6,%7}, {%8,%9}, {%0,%1,%2,%3};"
    : "+f"(d[0]), "+f"(d[1]), "+f"(d[2]), "+f"(d[3]) : "r"(a0), "r"(a1), "r"(a2), "r"(a3), "r"(b0), "r"(b1));
}
__device__ __forceinline__ void mma8(float* d, uint32_t a0, uint32_t a1, uint32_t b0) {
  asm volatile("mma.sync.aligned.m16n8k8.row.col.f32.bf16.bf16.f32 {%0,%1,%2,%3}, {%4,%5}, {%6}, {%0,%1,%2,%3};"
    : "+f"(d[0]), "+f"(d[1]), "+f"(d[2]), "+f"(d[3]) : "r"(a0), "r"(a1), "r"(b0));
}
__device__ __forceinline__ float rcp(float x) { float r; asm("rcp.approx.ftz.f32 %0, %1;" : "=f"(r) : "f"(x)); return r; }
__device__ __forceinline__ float ex2(float x) { float r; asm("ex2.approx.ftz.f32 %0, %1;" : "=f"(r) : "f"(x)); return r; }

__host__ __device__ constexpr uint64_t mkdesc(uint32_t off, uint32_t lbo, uint32_t sbo, uint32_t swz) {
  return (uint64_t)((SBASE + off) >> 4) | ((uint64_t)(lbo >> 4) << 16) | ((uint64_t)(sbo >> 4) << 32) | ((uint64_t)swz << 62);
}
__host__ __device__ constexpr uint64_t desc_sw128(uint32_t off) { return mkdesc(off, 16, 1024, 1); }
__host__ __device__ constexpr uint64_t desc_n16(uint32_t off) { return mkdesc(off, 256, 128, 0); }
__host__ __device__ constexpr uint64_t desc_m(uint32_t off) { return mkdesc(off, 16, 256, 3); }

__host__ __device__ constexpr uint64_t desc_sw64(uint32_t off) { return mkdesc(off, 16, 512, 2); }

__device__ __forceinline__ void wg_fence() { asm volatile("wgmma.fence.sync.aligned;" ::: "memory"); }
__device__ __forceinline__ void wg_commit() { asm volatile("wgmma.commit_group.sync.aligned;" ::: "memory"); }
template <int N> __device__ __forceinline__ void wg_wait() { asm volatile("wgmma.wait_group.sync.aligned %0;" :: "n"(N) : "memory"); }

#define ACC8(d) "+f"(d[0]), "+f"(d[1]), "+f"(d[2]), "+f"(d[3]), "+f"(d[4]), "+f"(d[5]), "+f"(d[6]), "+f"(d[7])
#define ACC32(d) ACC8(d), ACC8((d + 8)), ACC8((d + 16)), ACC8((d + 24))
#define R8 "{%0,%1,%2,%3,%4,%5,%6,%7}"
#define R32 "{%0,%1,%2,%3,%4,%5,%6,%7,%8,%9,%10,%11,%12,%13,%14,%15,%16,%17,%18,%19,%20,%21,%22,%23,%24,%25,%26,%27,%28,%29,%30,%31}"
template <int SD> __device__ __forceinline__ void wg_rs16(float* d, const uint32_t* a, uint64_t db) {
  asm volatile("wgmma.mma_async.sync.aligned.m64n16k16.f32.bf16.bf16 " R8 ", {%8,%9,%10,%11}, %12, %13, 1, 1, 1;"
    : ACC8(d) : "r"(a[0]), "r"(a[1]), "r"(a[2]), "r"(a[3]), "l"(db), "n"(SD));
}
template <int SD> __device__ __forceinline__ void wg_ss16(float* d, uint64_t da, uint64_t db) {
  asm volatile("wgmma.mma_async.sync.aligned.m64n16k16.f32.bf16.bf16 " R8 ", %8, %9, %10, 1, 1, 1, 1;"
    : ACC8(d) : "l"(da), "l"(db), "n"(SD));
}
template <int SD, uint64_t DA, uint64_t DB> __device__ __forceinline__ void wg_ss16o(float* d, uint32_t oa, uint32_t ob) {
  asm volatile("{.reg .b32 x, y; .reg .b64 a, b; add.u32 x, %8, %10; add.u32 y, %9, %12; mov.b64 a, {x, %11}; mov.b64 b, {y, %13};\n"
               "wgmma.mma_async.sync.aligned.m64n16k16.f32.bf16.bf16 " R8 ", a, b, %14, 1, 1, 1, 1;}"
    : ACC8(d) : "r"(oa), "r"(ob), "n"((uint32_t)DA), "n"((uint32_t)(DA >> 32)), "n"((uint32_t)DB), "n"((uint32_t)(DB >> 32)), "n"(SD));
}
template <int SD> __device__ __forceinline__ void wg_rs64(float* d, const uint32_t* a, uint64_t db) {
  asm volatile("wgmma.mma_async.sync.aligned.m64n64k16.f32.bf16.bf16 " R32 ", {%32,%33,%34,%35}, %36, %37, 1, 1, 0;"
    : ACC32(d) : "r"(a[0]), "r"(a[1]), "r"(a[2]), "r"(a[3]), "l"(db), "n"(SD));
}
template <int SD> __device__ __forceinline__ void wg_ss64(float* d, uint64_t da, uint64_t db) {
  asm volatile("wgmma.mma_async.sync.aligned.m64n64k16.f32.bf16.bf16 " R32 ", %32, %33, %34, 1, 1, 1, 0;"
    : ACC32(d) : "l"(da), "l"(db), "n"(SD));
}
#define WG_RSO(NAME, SHAPE, REGS, ACC, A, TB) \
template <int SD, uint64_t DB> __device__ __forceinline__ void NAME(float* d, uint32_t a0, uint32_t a1, uint32_t a2, uint32_t a3, uint32_t ob) { \
  asm volatile("{.reg .b64 b; mov.b64 b, {" A(4) ", " A(5) "};\nwgmma.mma_async.sync.aligned." SHAPE ".f32.bf16.bf16 " REGS \
               ", {" A(0) "," A(1) "," A(2) "," A(3) "}, b, " A(6) ", 1, 1, " TB ";}" \
    : ACC(d) : "r"(a0), "r"(a1), "r"(a2), "r"(a3), "r"(ob + (uint32_t)DB), "n"((uint32_t)(DB >> 32)), "n"(SD)); \
}
#define ACC4(d) "+f"(d[0]), "+f"(d[1]), "+f"(d[2]), "+f"(d[3])
#define ACC16(d) ACC8(d), ACC8((d + 8))
#define OP4(i) OP4_##i
#define OP4_0 "%4"
#define OP4_1 "%5"
#define OP4_2 "%6"
#define OP4_3 "%7"
#define OP4_4 "%8"
#define OP4_5 "%9"
#define OP4_6 "%10"
#define OP16(i) OP16_##i
#define OP16_0 "%16"
#define OP16_1 "%17"
#define OP16_2 "%18"
#define OP16_3 "%19"
#define OP16_4 "%20"
#define OP16_5 "%21"
#define OP16_6 "%22"
#define OP32(i) OP32_##i
#define OP32_0 "%32"
#define OP32_1 "%33"
#define OP32_2 "%34"
#define OP32_3 "%35"
#define OP32_4 "%36"
#define OP32_5 "%37"
#define OP32_6 "%38"
WG_RSO(wg_rs8o, "m64n8k16", "{%0,%1,%2,%3}", ACC4, OP4, "1")
#define R16 "{%0,%1,%2,%3,%4,%5,%6,%7,%8,%9,%10,%11,%12,%13,%14,%15}"
WG_RSO(wg_rs32o, "m64n32k16", R16, ACC16, OP16, "1")
WG_RSO(wg_rs64o, "m64n64k16", R32, ACC32, OP32, "0")
WG_RSO(wg_rs32k, "m64n32k16", R16, ACC16, OP16, "0")
template <uint64_t DA, uint64_t DB> __device__ __forceinline__ void wg_ss32k(float* d, uint32_t ob) {
  asm volatile("{.reg .b64 b; mov.b64 b, {%17, %18};\nwgmma.mma_async.sync.aligned.m64n32k16.f32.bf16.bf16 " R16 ", %16, b, 1, 1, 1, 1, 0;}"
    : ACC16(d) : "l"(DA), "r"(ob + (uint32_t)DB), "n"((uint32_t)(DB >> 32)));
}
template <int N> __device__ __forceinline__ void reg_inc() { asm volatile("setmaxnreg.inc.sync.aligned.u32 %0;" :: "n"(N)); }
template <int N> __device__ __forceinline__ void reg_dec() { asm volatile("setmaxnreg.dec.sync.aligned.u32 %0;" :: "n"(N)); }
__device__ __forceinline__ void cluster_sync() {
  asm volatile("barrier.cluster.arrive.relaxed.aligned;\nbarrier.cluster.wait.aligned;" ::: "memory");
}

template <int KS>
__device__ __forceinline__ void load_frags(uint32_t* a, uint32_t src) {
  const int lane = threadIdx.x & 31, w = (threadIdx.x >> 5) & 3;
  const int k = ((lane >> 4) << 3) + (lane & 7), u = w * 2 + ((lane >> 3) & 1);
  const uint32_t base = src + k * 128 + ((u ^ (k & 7)) << 4);
#pragma unroll
  for (int ks = 0; ks < KS; ks++) ldsm4t(a[ks * 4], a[ks * 4 + 1], a[ks * 4 + 2], a[ks * 4 + 3], base + ks * 2048);
}

__device__ __forceinline__ uint32_t badd2(uint32_t a, uint32_t b) { uint32_t r; asm("add.rn.bf16x2 %0, %1, %2;" : "=r"(r) : "r"(a), "r"(b)); return r; }
__device__ __forceinline__ uint32_t bsub2(uint32_t a, uint32_t b) { uint32_t r; asm("sub.rn.bf16x2 %0, %1, %2;" : "=r"(r) : "r"(a), "r"(b)); return r; }
__device__ __forceinline__ uint32_t bmul2(uint32_t a, uint32_t b) { uint32_t r; asm("mul.rn.bf16x2 %0, %1, %2;" : "=r"(r) : "r"(a), "r"(b)); return r; }
__device__ __forceinline__ uint32_t bfma2(uint32_t a, uint32_t b, uint32_t c) { uint32_t r; asm("fma.rn.bf16x2 %0, %1, %2, %3;" : "=r"(r) : "r"(a), "r"(b), "r"(c)); return r; }
template <int R> __device__ __forceinline__ void layernorm9(const uint32_t* x, uint32_t* o) {
  const uint32_t ones = 0x3F803F80u;
  float a[R][3][4], q[R], s[R];
#pragma unroll
  for (int i = 0; i < 9 * R; i++) {
    float* d = a[i % R][i / R % 3];
    if (i < 3 * R) d[0] = d[1] = d[2] = d[3] = 0.f;
    mma8(d, x[i % R * 9 + i / R], ones, x[i % R * 9 + i / R]);
  }
#pragma unroll
  for (int r = 0; r < R; r++) {
    q[r] = threadIdx.x & 4 ? a[r][0][1] + a[r][1][1] + a[r][2][1] : a[r][0][0] + a[r][1][0] + a[r][2][0];
    s[r] = (a[r][0][2] + a[r][0][3]) + (a[r][1][2] + a[r][1][3]) + (a[r][2][2] + a[r][2][3]);
  }
#pragma unroll
  for (int r = 0; r < R; r++) { q[r] += __shfl_xor_sync(~0u, q[r], 4); s[r] += __shfl_xor_sync(~0u, s[r], 1); }
#pragma unroll
  for (int r = 0; r < R; r++) { q[r] += __shfl_xor_sync(~0u, q[r], 9); s[r] += __shfl_xor_sync(~0u, s[r], 2); }
#pragma unroll
  for (int r = 0; r < R; r++) q[r] = __shfl_sync(~0u, q[r], 0) + __shfl_sync(~0u, q[r], 18);
#pragma unroll
  for (int r = 0; r < R; r++) {
    const float mean = s[r] * (1.f / DM), var = fmaxf(fmaf(q[r], 1.f / DM, -mean * mean), 0.f);
    float sd;
    asm("sqrt.approx.ftz.f32 %0, %1;" : "=f"(sd) : "f"(bf_lo(pack2(bf_lo(pack2(var, 0.f)) + 1e-5f, 0.f))));
    const float inv = rcp(bf_lo(pack2(sd, 0.f)));
    const uint32_t mb = pack2(mean, mean), hi = pack2(inv, inv), lo = pack2(inv - bf_lo(hi), inv - bf_lo(hi));
#pragma unroll
    for (int i = r * 9; i < r * 9 + 9; i++) {
      const uint32_t d = bsub2(x[i], mb);
      o[i] = bfma2(d, hi, bmul2(d, lo));
    }
  }
}
__device__ __forceinline__ void store_ln_row(int layer, int tok, const uint32_t* o) {
  const int lane = threadIdx.x & 31, r = tok & 31;
  unsigned char* p = g_lnimg + (size_t)(layer * NSEG + (tok >> 5)) * (9 * 4096) + r * 128 + (((lane >> 2) ^ (r & 7)) << 4) + (lane & 3) * 4;
#pragma unroll
  for (int i = 0; i < 9; i++) *(uint32_t*)(p + i * 4096) = o[i];
}
struct Params { CUtensorMap map[11]; const bf16 *X, *K, *V, *shift, *Hk, *Dk, *mem0, *Wq, *Wk, *Wv, *Wo; bf16* out; uint32_t dly[24]; };
#define PACE P.dly[20]
#define S1G P.dly[21]
#define S1DLY P.dly[22]
#define DLYS P.dly[0]
#define DLYW P.dly[1]
#define KLATE P.dly[2]
#define DLYQ P.dly[3]
#define DLYK P.dly[4]
#define DLYG P.dly[5]
#define KWIN P.dly[6]
#define KMIN P.dly[7]
uint32_t h_dly[24] = {900, 350, 100, 60, 3570, 4120, 2750, 1300, 1600, 1690, 1800, 2120, 2250, 2380, 2950, 3060, 3230, 3380, 3530, 7500, 165, 12000, 18000, 4000};

constexpr uint32_t C_W = 0, C_M = 147456, C_KV = C_M + 18432, C_OS = C_KV + 24576, C_QM = C_KV + 32768, C_KM = C_QM + 2048,
                   C_VM = C_KM + 2048, C_OI = C_VM + 2048, C_SX = C_OI + 4096, C_KM2 = C_SX + 2560, C_VM2 = C_KM2 + 128,
                   C_KV2 = C_KM2 + 2048, C_Q = C_KV2 + 8192, C_BAR = C_Q + 8192;
constexpr uint32_t CB_FULL = C_BAR, CB_REF = C_BAR + 16, CB_SX = C_BAR + 32, CB_OX = C_BAR + 40, CB_XX = C_BAR + 48, CB_Q = C_BAR + 56, C_BAD = C_BAR + 64, W_BAR = C_BAR + 80, T_BAR = W_BAR + 24, S_GEN = C_BAR + 128, C_REF = C_BAR + 132, CB_VF = C_BAR + 144, CB_M = C_BAR + 160, CB_MV = C_BAR + 200;
constexpr uint32_t G_W = 0, G_RING = 147456, G_W2 = G_RING + 9 * 8192, G_BAR = G_W2 + 8192;
constexpr uint32_t O_W = 0, O_RING = 3 * 40960, O_ST = O_RING + 11 * 8192, O_BAR = O_ST + 16384, OB_ST = O_BAR + 64;
constexpr uint32_t F_A = 0, F_XY = 36864, F_L = F_XY + 36864, F_X = F_L + 18432, F_Y = F_L + 2 * 36864, F_BAR = C_BAR;
constexpr uint32_t SMEM_BYTES = C_BAR + 256;
static_assert(G_BAR + 256 <= SMEM_BYTES && O_BAR + 256 <= SMEM_BYTES && F_BAR + 16 <= SMEM_BYTES && SMEM_BYTES <= 232448, "smem map");
enum { B_INIT = 1, B_M, B_QK, B_S, B_V, B_O, B_X, B_WG0, B_WG1, B_WG2, B_G, B_OE, B_T, B_R };

__device__ __forceinline__ uint4 pack_partial(const float* d, uint32_t tag) {
  uint32_t x;
  asm("lop3.b32 %0, %1, 1, %2, 0xb8;" : "=r"(x) : "r"(pack2(d[0], d[1])), "r"(tag));
  return make_uint4(x, pack2(d[4], d[5]), pack2(d[2], d[3]), pack2(d[6], d[7]));
}
__device__ __forceinline__ void store_partial(uint4* p, const uint4& v) { st_b128(p, v.x, v.y, v.z, v.w); }
__device__ __forceinline__ void gather_reduce(const uint32_t* p, uint32_t* dst, uint32_t m0, bool shared, uint32_t tag, uint32_t lane, uint32_t sb, int n, int TS0) {
  int tries = 0;
  bool bad;
  TR(TS0);
  do {
    uint2 x[8];
#pragma unroll
    for (int i = 0; i < 8; i++)
      asm volatile("{.reg .b64 v; ld.relaxed.gpu.global.b64 v, [%2]; mov.b64 {%0, %1}, v;}" : "=r"(x[i].x), "=r"(x[i].y) : "l"(p + i * 128) : "memory");
    spin_guard(tries);
    float a = bf_lo(x[0].x), b = bf_hi(x[0].x), c = bf_lo(x[0].y), d = bf_hi(x[0].y);
    uint32_t t = x[0].x ^ tag;
#pragma unroll
    for (int i = 1; i < 8; i++) {
      a += bf_lo(x[i].x); b += bf_hi(x[i].x); c += bf_lo(x[i].y); d += bf_hi(x[i].y);
      asm("lop3.b32 %0, %0, %1, %2, 0xf6;" : "+r"(t) : "r"(x[i].x), "r"(tag));
    }
    bad = __any_sync(~0u, t & ~lane & 1);
    const bool up = lane & 8;
    float u = (up ? c : a) + __shfl_xor_sync(~0u, up ? a : c, 8), v = (up ? d : b) + __shfl_xor_sync(~0u, up ? b : d, 8);
    if (shared) { u += __shfl_xor_sync(~0u, u, 4); v += __shfl_xor_sync(~0u, v, 4); }
    u += __shfl_xor_sync(~0u, u, 16);
    v += __shfl_xor_sync(~0u, v, 16);
    st_relaxed_if(dst, n < LAG && up ? m0 : pack2(u, v), !bad);
  } while (bad);
  TR(TS0 + 3); TRV(TS0 + 2, tries);
  CNT((TS0 - 16) >> 2, tries);
}
__device__ __forceinline__ uint32_t sent_bad(const uint4& v) { return max(max(v.x, v.y), max(v.z, v.w)) == SENT; }

__host__ __device__ constexpr int o_ks(int s) { return s & (s < 8 ? 3 : 7); }
__host__ __device__ constexpr bool o_reg(int s) { return s < 8 ? (s & 3) != 3 : !(s & 1); }
__host__ __device__ constexpr int o_slot(int s) { return s < 8 ? (o_reg(s) ? s - (s >> 2) : s >> 2) : s & 1 ? (s - 5) >> 1 : (s + 4) >> 1; }
__device__ __forceinline__ int g_unit(int wg) {
  const int i = bid() - N_CHAIN;
  return i < 32 ? wg * 64 + i : 2 * i - 32 + wg;
}
__device__ __forceinline__ uint32_t pinned(uint32_t v) { return __shfl_sync(~0u, v, threadIdx.x & 31); }
template <class T> __device__ __forceinline__ T* pinned(T* p) { return (T*)__shfl_sync(~0u, (unsigned long long)p, threadIdx.x & 31); }
enum { CHAIN, GROLE, OROLE };
template <int ROLE, bool SYNC> __device__ __forceinline__ void load_box(const Params& P, uint32_t sb, bool regs, int wg, int i, uint32_t mb, bool on) {
  const int b = bid();
  int map, col = 0, ks = 0, c2 = 0, c3 = 0;
  uint32_t dst = wg * 73728;
  if (ROLE == CHAIN) {
    const int k = i - 1, st = regs ? (k < 6 ? k + k / 3 : 2 * k - 4) : k < 2 ? 4 * k + 3 : 2 * k + 5;
    dst += i ? (17 + i) * 2048 : 0;
    if (wg || i == 0) { map = wg + i; col = b * 64; c3 = !regs; }
    else if (!regs && k >= 14) { map = 6; ks = b * 4 + k - 14; }
    else { map = 6; col = 64 + (st < 8 ? (st >> 2) * 64 : (st >> 3) * 128 + (b & 1) * 64); ks = (b * 4) ^ o_ks(st); }
  } else if (ROLE == GROLE) {
    const int q = g_unit(wg);
    map = ((q >> 5) + 1) % 3;
    if (i) { map += 3; col = (q & 31) * 128 + (i - 1) * 64; ks = 34; dst = G_W2 + wg * 4096 + (i - 1) * 2048; }
    else { map += 8; c2 = (q & 31) * 2; c3 = !regs; }
  } else {
    const int o = b - N_CHAIN - N_G, ksl = o / 3;
    map = 7; col = ((o % 3) * 3 + (wg + ksl) % 3) * 64; dst = (wg * (regs ? 24 : 20) + i) * 2048;
    ks = (ksl * 11 - max(ksl - 4, 0)) * 4 + (regs ? i / 3 * 5 + i % 3 * 2 : i < 16 ? i / 2 * 5 + 1 + i % 2 * 2 : i + 24);
    c3 = (ks & 1) * 2; ks >>= 1;
  }
  if (SYNC) { col = pinned(col); ks = pinned(ks); bar_sync(B_WG0 + wg, 256); }
  if (on) asm volatile("cp.async.bulk.tensor.5d.shared::cluster.global.tile.mbarrier::complete_tx::bytes [%0], [%1, {%2, %3, %4, %5, %6}], [%7];"
               :: "r"(sb + dst), "l"(&P.map[map]), "r"(col), "r"(0), "r"(c2), "r"(c3), "r"(ks), "r"(mb) : "memory");
}
template <int ROLE, bool SYNC = false> __device__ __forceinline__ void load_wg(const Params& P, uint32_t sb, bool regs, int wg, int quarter) {
  const int i = (threadIdx.x & 31) * 4 + quarter;
  const int n = ROLE == CHAIN ? 36 : ROLE == GROLE ? (regs ? 38 : 36) : regs ? 24 : bid() < N_CHAIN + N_G + 12 ? 20 : 16;
  load_box<ROLE, SYNC>(P, sb, regs, wg, i, sb + W_BAR + wg * 8, i < (ROLE == CHAIN ? (wg ? 2 : 19) : ROLE == GROLE ? n - 35 : n));
  if (i == 0) mbar_expect(sb + W_BAR + wg * 8, n * 2048);
  __syncwarp();
}
__device__ __forceinline__ uint32_t near_half(uint32_t blk, uint32_t reader) {
  return __ldcg(g_near + (blk >> 3)) ^ (~blk & 1) ^ __ldcg(g_side + (blk >> 3)) ^ __ldcg(g_side + reader);
}

__device__ __forceinline__ uint32_t opaque_tid() { uint32_t t; asm volatile("mov.u32 %0, %%tid.x;" : "=r"(t)); return t; }
__device__ __forceinline__ void m_fetch(uint32_t sb, uint32_t src, uint32_t b, uint32_t mb) {
  bulk_load(sb + C_M + (b ? b * 4096 - 2048 : 0), (const unsigned char*)g_mimg + ((src ^ ((b & 1) * 4096)) + b * 8192), b ? 4096 : 2048, mb);
}
__device__ __forceinline__ uint32_t m_probe(uint32_t lane) { return lane * 32 + (lane & 4) * 4 + (lane >> 3) * 4; }
__device__ __forceinline__ uint32_t m_max(uint32_t a, uint32_t b) {
  return max(max(lds32(a), lds32(a + 1024)), max(lds32(b), lds32(b + 1024)));
}
template <int S0, int N> __device__ __forceinline__ void o_steps(float* d, const uint32_t* a) {
  constexpr int SD = o_ks(S0) != 0;
  if constexpr (o_reg(S0)) wg_rs16<SD>(d, a + (18 + o_slot(S0)) * 4, desc_n16(C_OI + o_ks(S0) * 512));
  else wg_ss16<SD>(d, desc_sw128(C_W + (18 + o_slot(S0)) * 2048), desc_n16(C_OI + o_ks(S0) * 512));
  if constexpr (N > 1) o_steps<S0 + 1, N - 1>(d, a);
}
template <int BASE, int KS, int N> __device__ __forceinline__ void m_steps(float* d, const uint32_t* a, uint32_t oa) {
  wg_rs16<KS != 0>(d, a + (BASE + KS / 2) * 4, desc_m(C_M + KS * 512));
  if constexpr (KS >= 36 - 2 * XR) wg_rs16<1>(d, a + (18 + XR + KS / 2) * 4, desc_m(C_M + KS * 512 + 512));
  else wg_ss16o<1, desc_sw128(C_W + (BASE + KS / 2) * 2048), desc_m(C_M + KS * 512 + 512)>(d, oa, 0);
  if constexpr (N > 2) m_steps<BASE, KS + 2, N - 2>(d, a, oa);
}

template <int I, int R, int S> __device__ __forceinline__ void v_steps(float* d, const uint32_t* a) {
  constexpr bool reg = (VPAT >> I) & 1;
  if constexpr (reg) wg_rs16<1>(d, a + (18 + R) * 4, desc_m(C_M + R * 1024));
  else wg_ss16<1>(d, desc_sw128(C_W + (54 + S) * 2048), desc_m(C_M + S * 1024 + 512));
  if constexpr (I < 31) v_steps<I + 1, R + reg, S + !reg>(d, a);
  else static_assert(R + reg == 18, "pattern");
}

__device__ __forceinline__ void chain_proj(const Params& P, uint32_t sb) {
  const uint32_t c = chain_id(), h = c >> 1, j = c & 1, wid = __shfl_sync(~0u, threadIdx.x >> 5, 0), wg = wid >> 2, w = wid & 3;
  const uint32_t t = threadIdx.x & 127, lane = pinned(t & 31), mine = pinned(sb + t * 16), rb = mapa(sb, j ^ 1);
  const uint32_t theirs = pinned(rb + C_KM2 + w * 512 + lane * 4), oa = wg * 4608;
  uint32_t a[144 + 4 * XR];
  mbar_wait(sb + W_BAR + wg * 8, 0);
  if (threadIdx.x == 0) TS(23);
  load_frags<36>(a, sb + C_W + wg * 73728);
  fence_async_smem();
  bar_arrive(B_WG0 + wg, 256);
  if (threadIdx.x == 0) TS(24);
  bar_sync(B_WG2, 384);
  const uint32_t round = min(w, 2u) + (wg ? 0 : 3), gdly = P.dly[8 + round], ps = t >> 2, pf = j * 16 + (ps >> 1);
  uint4* const dsts = pinned(g_xb + (ps * 4096 + near_half(ps * 8, ps * 2) * 256 + c * 4 + (t & 3)));
  uint4* const dstf = pinned(g_xb + (pf * 4096 + 512 + near_half(pf * 8 + 1, pf * 2) * 256 + h * 8 + (t & 7)));
  const uint32_t* const gsrc = (const uint32_t*)g_xb + (h * 16384 + min(w, 2u) * 4096 + near_half(h * 8 + !wg, h * 2) * 1024 +
                               (wg ? (lane & 28) * 4 + j * 8 + (lane & 3) * 2 : 2048 + (lane & 24) * 4 + j * 16 + (lane & 7) * 2));
  uint32_t* gdst = g_mimg + (16384 + (lane >> 4) * 1024 + (lane & 1) * 8 +
                   (wg ? (round ? 1536 + round * 512 : 0) + h * 16 + (((lane >> 1) ^ c) & 4) + j * 2 + ((lane >> 1) & 1)
                       : (round - 1) * 2048 + c * 16 + (((lane >> 1) ^ (c * 2)) & 4) + ((lane >> 1) & 3)));
  const uint32_t m0 = __ldcg(gdst - 16384);
  mbar_wait(sb + W_BAR + wg * 8, 1);
  load_frags<XR>(a + 144, sb + C_W + wg * 73728 + (18 - XR) * 2048);
  bar_sync(B_INIT, 256);
  if ((threadIdx.x & 127) == 0) TS(4);

  uint32_t ring = 1;
#pragma unroll 1
  for (int n = 0; n < STEPS; n++) {
    float d[8], e[8];
#pragma unroll
    for (int i = 0; i < 8; i++) e[i] = 0.f;
    uint32_t redo = n + 1;
#pragma unroll 1
    do {
      mbar_wait(sb + CB_M, n & 1);
      wg_fence();
      m_steps<0, 0, 4>(d, a, oa);
      wg_commit();
      if (wg) { wg_fence(); m_steps<18, 0, 4>(e, a, 4608); wg_commit(); }
      if (wid == 0) TR(8);
      mbar_wait(sb + CB_M + 8, n & 1);
      wg_fence();
      m_steps<0, 4, 8>(d, a, oa);
      wg_commit();
      mbar_wait(sb + CB_MV, n & 1);
      asm volatile("{.reg .pred p; .reg .u32 t; ld.shared.u32 t, [%1]; setp.eq.u32 p, t, %0; selp.u32 %0, -1, 0, p;}" : "+r"(redo) : "r"(sb + C_BAD) : "memory");
    } while (redo);
    wg_fence();
    m_steps<0, 12, 8>(d, a, oa);
    wg_commit();
    mbar_wait(sb + CB_MV + 16, n & 1);
    wg_fence();
    m_steps<0, 20, 8>(d, a, oa);
    wg_commit();
    mbar_wait(sb + CB_MV + 24, n & 1);
    wg_fence();
    m_steps<0, 28, 8>(d, a, oa);
    wg_commit();
    wg_wait<0>();
    if (w == 0) TR(6 + wg);
    const uint32_t f0 = pack2(d[0], d[1]), f1 = pack2(d[4], d[5]), f2 = pack2(d[2], d[3]), f3 = pack2(d[6], d[7]);
    stsm4(mine + C_QM + wg * 2048, f0, f1, f2, f3);
    bar_arrive(B_QK, 416);
    const uint32_t tag = (n & 1) ^ 1;
    if (wg) {
      if (n + 1 < STEPS) bar_sync(B_S, 256);
      wg_fence();
      v_steps<0, 2, 2>(e, a);
      wg_commit();
      const uint32_t k0 = j ? f0 : f1, k1 = j ? f2 : f3;
      wg_wait<0>();
      if (w == 0) TR(11);
      const uint32_t v0 = pack2(e[0], e[1]), v1 = pack2(e[4], e[5]), v2 = pack2(e[2], e[3]), v3 = pack2(e[6], e[7]);
      stsm4(mine + C_VM, v0, v1, v2, v3);
      bar_arrive(B_V, 256);
      st_async1(theirs, k0, rb + CB_XX);
      st_async1(theirs + 256, k1, rb + CB_XX);
      st_async1(theirs + 128, j ? v0 : v1, rb + CB_XX);
      st_async1(theirs + 384, j ? v2 : v3, rb + CB_XX);
      if (n + 1 == STEPS) break;
      bar_sync(B_O, 256);
      if (!WFENCE) fence_async_smem();
      wg_fence();
#pragma unroll
      for (int ks = 0; ks < 4; ks++) {
        if (ks == 0) wg_ss16<0>(d, desc_sw128(C_W + 32 * 2048), desc_n16(C_OI));
        else wg_ss16<1>(d, desc_sw128(C_W + (32 + ks) * 2048), desc_n16(C_OI + ks * 512));
      }
      wg_commit();
      bar_arrive(B_X, 256);
      if (w == 0) TR(0);
      wg_wait<0>();
      store_partial(dsts, pack_partial(d, tag));
      bar_arrive(B_M, 160);
      if (w == 0) TR(1);
    } else {
      if (n + 1 == STEPS) break;
      bar_sync(B_X, 256);
      wg_fence();
      o_steps<0, 4>(d, a);
      wg_commit();
      o_steps<4, 4>(e, a);
      wg_commit();
      wg_wait<1>();
      store_partial(dsts + 1024, pack_partial(d, tag));
      if (w == 0) TR(2);
      if (OGAP == 0) { wg_fence(); o_steps<8, 4>(d, a); wg_commit(); wg_wait<1>(); } else wg_wait<0>();
      store_partial(dsts + 2048, pack_partial(e, tag));
      if (w == 0) TR(3);
      wg_fence();
      if (OGAP) o_steps<8, 4>(d, a);
      if (OGAP < 2) o_steps<16, 4>(e, a);
      wg_commit();
      bar_sync(B_T, 256);
      if (w == 0) { TRV(61, 0); TR(12); }
      wg_fence();
      o_steps<12, 4>(d, a);
      wg_commit();
      if (OGAP == 2) o_steps<16, 4>(e, a);
      o_steps<20, 4>(e, a);
      wg_commit();
      wg_wait<1>();
      store_partial(dstf, pack_partial(d, tag));
      if (w == 0) TR(4);
      wg_fence();
      o_steps<24, 8>(d, a);
      wg_commit();
      wg_wait<1>();
      store_partial(dstf + 1024, pack_partial(e, tag));
      bar_arrive(B_OE, 256);
      if (w == 0) TR(5);
      wg_wait<0>();
      store_partial(dstf + 2048, pack_partial(d, tag));
      if (w == 0) TR(15);
    }
    if (w < 3) {
      mbar_wait(sb + CB_REF, n & 1);
      wait_until(lds32(sb + C_REF), gdly);
      gather_reduce(gsrc, gdst, m0, wg, tag, lane, sb, n, 16 + round * 4);
      if (++ring == MRING) { ring = 0; gdst -= MRING * 16384; }
      gdst += 16384;
    }
  }
}

template <int KS> __device__ __forceinline__ void x_scores(float* s, float* sm, const uint4* q, uint32_t ok, uint32_t om) {
  wg_rs32o<1, desc_sw64(C_KV + KS * 1024)>(s, q[KS].x, q[KS].y, q[KS].z, q[KS].w, ok);
  wg_rs8o<1, desc_n16(C_KM + KS * 512)>(sm, q[KS].x, q[KS].y, q[KS].z, q[KS].w, om);
  if constexpr (KS < 3) x_scores<KS + 1>(s, sm, q, ok, om);
}

__device__ __forceinline__ void chain_attn(const Params& P, uint32_t sb) {
  const int c = chain_id(), j = c & 1;
  const int tid = threadIdx.x, lane = tid & 31, w = __shfl_sync(~0u, (tid >> 5) & 3, 0);
  const int l = w >> 1, u = w & 1;
  const uint32_t rb = mapa(sb, j ^ 1);
  const float sc = 0.08838834764831845f * 1.4426950408889634f;
  const uint32_t ones = 0x3F803F80u;
  const uint32_t km_off = C_KM + (lane >> 3) * 256 + l * 128 + (lane & 7) * 16;
  const uint32_t qm_off = C_QM + (lane >> 4) * 256 + l * 128 + (lane & 7) * 16;
  const uint32_t kv_off = C_KV + l * 4096 + (lane & 15) * 64 + (((lane >> 4) ^ (u * 2) ^ ((lane >> 1) & 3)) << 4);

  load_wg<CHAIN, true>(P, sb, false, 1, w);
  if (lane == 0) mbar_arrive(sb + CB_M);
#pragma unroll 1
  for (int n = 0; n < STEPS; n++) {
    const uint32_t kvb = sb + kv_off + (n & 1) * 16384;
    if (w == 0 && elect()) { mbar_expect(sb + CB_SX, 2560); mbar_expect(sb + CB_OX, 2048); mbar_expect(sb + CB_XX, 2048); }
    mbar_wait(sb + CB_FULL + (n & 1) * 8, (n >> 1) & 1);
    if (n < 3 && tid == 256) TS(n ? 20 + n : 5);
    __syncwarp();
    {
      uint32_t km[8];
      uint4 kx[8];
#pragma unroll
      for (int i = 0; i < 8; i++) ldsm4t(kx[i].x, kx[i].y, kx[i].z, kx[i].w, (kvb ^ ((i & 1) * 32)) + (i >> 1) * 1024);
      mbar_wait(sb + CB_VF, n & 1);
      if (w == 1) TRD(60, kx[7].x);
      bar_sync(B_QK, 416);
      if (n + 1 == STEPS) {
        bar_sync(B_V, 256);
      } else {
      uint32_t qm[16];
#pragma unroll
      for (int ks = 0; ks < 4; ks++) ldsm4t(qm[4 * ks], qm[4 * ks + 1], qm[4 * ks + 2], qm[4 * ks + 3], sb + qm_off + ks * 512);
      ldsm4t(km[0], km[1], km[2], km[3], sb + km_off);
      ldsm4t(km[4], km[5], km[6], km[7], sb + km_off + 1024);
      float s[5][4];
      uint4 vx[4];
#pragma unroll
      for (int i = 0; i < 5; i++) { s[i][0] = s[i][1] = s[i][2] = s[i][3] = 0.f; }
#pragma unroll
      for (int ks = 0; ks < 4; ks++) {
        const uint32_t* q = qm + 4 * ks;
        if (ks == 1 || ks == 2) {
#pragma unroll
          for (int i = 2 * ks - 2; i < 2 * ks; i++) ldsm4(vx[i].x, vx[i].y, vx[i].z, vx[i].w, ((sb + kv_off) ^ ((i & 1) * 32)) + 8192 + (2 * u + (i >> 1)) * 1024);
        }
        mma16(s[1], q[0], q[1], q[2], q[3], kx[2 * ks].x, kx[2 * ks].y);
        mma16(s[2], q[0], q[1], q[2], q[3], kx[2 * ks].z, kx[2 * ks].w);
        mma16(s[0], q[0], q[1], q[2], q[3], km[2 * ks], km[2 * ks + 1]);
        mma16(s[3], q[0], q[1], q[2], q[3], kx[2 * ks + 1].x, kx[2 * ks + 1].y);
        mma16(s[4], q[0], q[1], q[2], q[3], kx[2 * ks + 1].z, kx[2 * ks + 1].w);
      }
      const uint32_t sx = C_SX + l * 1280;
      st_async4(rb + sx + u * 512 + lane * 16, s[1][0], s[1][1], s[2][0], s[2][1], rb + CB_SX);
      st_async1(rb + sx + 1024 + u * 128 + lane * 4, __float_as_uint(u ? s[0][1] : s[0][0]), rb + CB_SX);
      bar_arrive_after<B_S, 256>(__float_as_uint(s[3][0]), __float_as_uint(s[4][0]));
      mbar_wait(sb + CB_SX, n & 1);
      const uint4 p0 = lds128(sb + sx + u * 512 + lane * 16), p1 = lds128(sb + sx + (u ^ 1) * 512 + lane * 16);
      const uint2 p2 = make_uint2(lds32(sb + sx + 1024 + lane * 4), lds32(sb + sx + 1152 + lane * 4));
      float t[10] = {s[0][0] + __uint_as_float(p2.x), s[0][1] + __uint_as_float(p2.y),
                     s[1][0] + __uint_as_float(p0.x), s[1][1] + __uint_as_float(p0.y),
                     s[2][0] + __uint_as_float(p0.z), s[2][1] + __uint_as_float(p0.w),
                     s[3][0] + __uint_as_float(p1.x), s[3][1] + __uint_as_float(p1.y),
                     s[4][0] + __uint_as_float(p1.z), s[4][1] + __uint_as_float(p1.w)};
      float mx = fmaxf(fmaxf(fmaxf(fmaxf(t[2], t[3]), fmaxf(t[4], t[5])), fmaxf(fmaxf(t[6], t[7]), fmaxf(t[8], t[9]))), fmaxf(t[0], t[1]));
      mx = fmaxf(fmaxf(mx, __shfl_xor_sync(~0u, mx, 1)), fmaxf(__shfl_xor_sync(~0u, mx, 2), __shfl_xor_sync(~0u, mx, 3)));
      const float ms = -mx * sc;
#pragma unroll
      for (int i = 0; i < 10; i++) t[i] = ex2(fmaf(t[i], sc, ms));
      uint32_t p[5];
#pragma unroll
      for (int i = 0; i < 5; i++) p[i] = pack2(t[2 * i], t[2 * i + 1]);
      p[1] |= (p[0] & p[3] & p[4]) & 0x80008000u;
      float o[2][4], z[4] = {0.f, 0.f, 0.f, 0.f};
      mma16(z, ones, ones, ones, ones, p[1], p[2]);
#pragma unroll
      for (int i = 0; i < 2; i++) {
        o[i][0] = o[i][1] = o[i][2] = o[i][3] = 0.f;
        mma16(o[i], vx[2 * i].x, vx[2 * i].y, vx[2 * i].z, vx[2 * i].w, p[1], p[2]);
      }
      mma16(z, ones, ones, ones, ones, p[3], p[4]);
#pragma unroll
      for (int i = 0; i < 2; i++) mma16(o[i], vx[2 * i + 1].x, vx[2 * i + 1].y, vx[2 * i + 1].z, vx[2 * i + 1].w, p[3], p[4]);
      mma8(z, ones, ones, p[0]);
      bar_sync_after<B_V, 256>(p[1]);
      ldsm4(km[0], km[1], km[2], km[3], sb + km_off + (C_VM - C_KM) + u * 1024);
      mma8(o[0], km[0], km[1], p[0]);
      mma8(o[1], km[2], km[3], p[0]);
      const float i0 = rcp(z[0]), i1 = rcp(z[1]);
      const uint32_t oo = C_OI + u * 1024 + l * 128 + lane * 4;
      uint32_t ow[4];
#pragma unroll
      for (int i = 0; i < 2; i++) { ow[2 * i] = pack2(o[i][0] * i0, o[i][1] * i1); ow[2 * i + 1] = pack2(o[i][2] * i0, o[i][3] * i1); }
      stsm4(sb + C_OI + u * 1024 + l * 128 + (lane >> 3) * 256 + (lane & 7) * 16, ow[0], ow[1], ow[2], ow[3]);
      if (WFENCE) fence_async_smem();
      bar_arrive(B_O, 256);
#pragma unroll
      for (int i = 0; i < 4; i++) st_async1(rb + oo + 2048 + i * 256, ow[i], rb + CB_OX);
      }
    }
    {
      const uint32_t lane = opaque_tid() & 31, own = ((n & 1) * 16384 + j * 4096) >> 4;
      float s[16], sm[4];
#pragma unroll
      for (int i = 0; i < 16; i++) s[i] = sm[i & 3] = 0.f;
      {
        uint4 q[4];
        mbar_wait(sb + CB_Q, n & 1);
        auto load_q = [&]() {
#pragma unroll
          for (int ks = 0; ks < 4; ks++) q[ks] = lds128(sb + C_Q + (ks >> 1) * 4096 + w * 1024 + (ks & 1) * 512 + lane * 16);
        };
        if (QPOS == 0) load_q();
        mbar_wait(sb + CB_XX, n & 1);
        if (n + 1 < STEPS) mbar_wait(sb + CB_OX, n & 1);
        fence_async_smem();
        if (n + 1 < STEPS) bar_arrive(B_T, 256);
        if (QPOS == 1) load_q();
        if (n + 1 < STEPS) bar_sync(B_OE, 256);
        if (QPOS == 2) load_q();
        if (w == 1) { TRV(61, 0); TR(9); }
#pragma unroll 1
        for (uint32_t hf = 0; hf < 2; hf++) {
          wg_fence();
          x_scores<0>(s, sm, q, hf ? (C_KV2 - C_KV) >> 4 : own, hf ? (C_KM2 - C_KM) >> 4 : j * 8);
          wg_commit();
          wg_wait<0>();
#pragma unroll
          for (int ks = 0; ks < 4; ks++) asm volatile("mov.b32 %0, %1; mov.b32 %2, %3;" : "+r"(q[ks].x), "+r"(q[ks].y), "+r"(q[ks].z), "+r"(q[ks].w));
        }
      }
      const float neg = -1e9f * 11.313708498984761f;
      const int lim = 8 * (w - (int)(lane & 3)) + (int)(lane >> 2);
      float t[10] = {sm[0], sm[1]};
#pragma unroll
      for (int i = 0; i < 8; i++) t[2 + i] = i > lim ? neg : s[(i >> 1) * 4 + (i & 1)];
      float mx = fmaxf(fmaxf(fmaxf(fmaxf(t[2], t[3]), fmaxf(t[4], t[5])), fmaxf(fmaxf(t[6], t[7]), fmaxf(t[8], t[9]))), fmaxf(t[0], t[1]));
      mx = fmaxf(fmaxf(mx, __shfl_xor_sync(~0u, mx, 1)), fmaxf(__shfl_xor_sync(~0u, mx, 2), __shfl_xor_sync(~0u, mx, 3)));
      const float ms = -mx * sc;
#pragma unroll
      for (int i = 0; i < 10; i++) t[i] = ex2(fmaf(t[i], sc, ms));
      uint32_t p[5];
#pragma unroll
      for (int i = 0; i < 5; i++) p[i] = pack2(t[2 * i], t[2 * i + 1]);
      float z = ((t[0] + t[1]) + (t[2] + t[3])) + ((t[4] + t[5]) + (t[6] + t[7])) + (t[8] + t[9]);
      const uint32_t row = sb + C_OS + w * 1024 + (lane >> 2) * 128 + (((lane & 3) ^ (lane >> 2)) << 4);
#pragma unroll 1
      for (uint32_t hf = 0; hf < 2; hf++) {
        float o[32];
        const uint32_t vo = hf ? (C_KV2 + 4096 - C_KV - 8192) >> 4 : j * 256;
        wg_fence();
        wg_rs64o<0, desc_sw64(C_KV + 8192)>(o, p[1], p[1], p[2], p[2], vo);
        wg_rs64o<1, desc_sw64(C_KV + 8192 + 32)>(o, p[3], p[3], p[4], p[4], vo);
        wg_rs64o<1, mkdesc(C_VM, 128, 256, 0)>(o, p[0], p[0], 0, 0, hf ? (C_VM2 - C_VM) >> 4 : j * 8);
        wg_commit();
        if (hf) {
          if (elect()) mbar_arrive(sb + CB_M);
        } else {
          z += __shfl_xor_sync(~0u, z, 1);
          z = rcp(z + __shfl_xor_sync(~0u, z, 2));
        }
        wg_wait<0>();
#pragma unroll
        for (int qq = 0; qq < 2; qq++) {
          const float* r = o + 16 * qq;
          sts128((row ^ (qq * 64)) + hf * 4096,
                 make_uint4(pack2(r[0] * z, r[1] * z), pack2(r[4] * z, r[5] * z), pack2(r[8] * z, r[9] * z), pack2(r[12] * z, r[13] * z)));
        }
      }
      bar_arrive(B_G, 160);
      if (n + 1 < STEPS) bar_arrive(B_R, 160);
      if (w == 1) TR(10);
    }
  }
  if ((threadIdx.x & 127) == 0) TS(6);
}

__device__ __forceinline__ void chain_aux(const Params& P, uint32_t sb) {
  const uint32_t c = chain_id(), j = c & 1, lane = threadIdx.x & 31, w = __shfl_sync(~0u, (threadIdx.x >> 5) & 3, 0);
  load_wg<CHAIN, true>(P, sb, false, 0, w);
  if (threadIdx.x == 384) TS(25);
  if (threadIdx.x == 384) grid_wait(1, lds32(sb + S_GEN));
  bar_sync(B_WG2, 384);
  if (threadIdx.x == 384) TS(13);
  if (w == 0) {
    const uint32_t* fg = g_fl + FL_G + near_half(XB_F, c) * 1024 + (c >> 1) * 8;
#pragma unroll 1
    for (int n = 0; n < STEPS; n++) {
      const unsigned char* blk = g_qkv + (uint32_t)((n % QRING) * (N_CHAIN * 24576));
      const uint32_t t1 = clk(), kb = sb + CB_FULL + (n & 1) * 8, kv = sb + C_KV + (n & 1) * 16384;
      uint32_t t0 = t1 - 100000, x = 0;
      if (n > 0) {
        wait_until(t1, KMIN);
        do asm volatile("ld.relaxed.gpu.global.u32 %0, [%1];" : "=r"(x) : "l"(fg) : "memory"); while (x <= n && clk() - t1 < KWIN);
        if (NOBULK) x = n + 1;
        if (x > n) {
          asm volatile("fence.acquire.gpu;" ::: "memory");
          fence_async_global();
          if (elect()) { mbar_expect(kb, 8192); bulk_load(kv, blk + c * 24576, 8192, kb); }
        }
        T3(0); CNT(12, 1 + (x <= n));
        mbar_wait(sb + CB_REF, (n - 1) & 1);
        t0 = lds32(sb + C_REF);
        wait_until(t0, DLYK - 500);
      }
      if (!NOBULK) wait_flags(fg + min(lane, 2u) * 256, n + 1);
      T3(2);
      fence_async_global();
      if (n > 0) bar_sync(B_R, 160);
      wait_until(t0, DLYK);
      if (elect()) {
        if (x <= n) { mbar_expect(kb, 8192); bulk_load(kv, blk + c * 24576, 8192, kb); }
        mbar_expect(sb + CB_VF, 8192);
        bulk_load(sb + C_KV + 8192, blk + (c * 24576 + 8192), 8192, sb + CB_VF);
        mbar_expect(sb + CB_Q, 16384);
        bulk_load(sb + C_Q, blk + (c * 24576 + 16384), 8192, sb + CB_Q);
        bulk_load(sb + C_KV2, blk + ((c ^ 1) * 24576 + j * 4096), 4096, sb + CB_Q);
        bulk_load(sb + C_KV2 + 4096, blk + ((c ^ 1) * 24576 + 8192 + j * 4096), 4096, sb + CB_Q);
      }
      T3(1);
      T3(3);
    }
  } else {
    const uint32_t near = __ballot_sync(~0u, near_half(XB_M + min(lane, MRING - 1u) * 8, c));
    uint32_t ring = 0;
    if (w > 1) {
      const uint32_t odd = w & 1, chk = pinned(sb + C_M + odd * 2048 + m_probe(lane)), again = sb + CB_MV + 32 + odd * 8;
      const bool one = elect();
      uint32_t mph = 0;
#pragma unroll 1
      for (int n = 0; n <= STEPS; n++) {
#pragma unroll
        for (int k = 0; k < 3; k++) {
          if (n == STEPS || (k == 2 && odd)) break;
          const uint32_t b = 2 * k + odd, at = chk + (k ? k * 8192 - 2048 + odd * 2048 : 0);
          uint32_t mb = sb + CB_M + b * 8, ph = n & 1;
          int it = 1;
          while (true) {
            mbar_wait(mb, ph);
            const bool bad = __any_sync(~0u, (k ? m_max(at, at + 2048) : max(m_max(at, at ^ 8), odd ? m_max(at + 2048, (at ^ 8) + 2048) : 0)) == SENT);
            if (one && !bad) mbar_arrive(sb + CB_MV + (b > 2 ? b * 8 - 8 : 0));
            if (!bad) break;
            mb = again; ph = mph; mph ^= 1;
            if (one) {
              if (k == 0) sts32(sb + C_BAD, n + 1);
              mbar_expect(mb, b ? 4096 : 2048);
              m_fetch(sb, ring * 65536 + ((near >> ring) & 1) * 4096, b, mb);
            }
            __syncwarp();
            spin_guard(it);
          }
          TR(41 + b * 4); CNT(6 + b, it);
        }
        ring = ring + 1 == MRING ? 0 : ring + 1;
        if (!odd) {
          if (n < STEPS) { TRSYNC(); TRDUMP(n - 2); }
        } else {
          unsigned char* o = g_oimg + (uint32_t)(((n - 1) & (RING - 1)) * (N_CHAIN * 8192) + j * 4096);
          if (n > 0) bar_sync(B_G, 160);
          fence_async_smem();
          if (one) {
            if (n > 0) {
              bulk_store(o + c * 8192, sb + C_OS, 4096);
              bulk_store(o + (c ^ 1) * 8192, sb + C_OS + 4096, 4096);
              asm volatile("cp.async.bulk.commit_group;\ncp.async.bulk.wait_group.read 0;" ::: "memory");
              { const int n_ = n - 1; { const int n = n_; T3(4); (void)n; } }
            }
            mbar_arrive(sb + CB_Q);
            if (n > 0) {
              bulk_done_inc(g_fl + FL_O + c);
              { const int n_ = n - 1; { const int n = n_; T3(5); (void)n; } }
            }
          }
          __syncwarp();
        }
      }
    } else {
      const uint32_t* ts = g_fl + FL_SYNC + near_half(XB_F + 1, c) * 1024 + lane * 2;
      uint32_t t0 = clk() - 100000;
#pragma unroll 1
      for (int n = 0; n < STEPS; n++) {
        const uint32_t src = ring * 65536 + ((near >> ring) & 1) * 4096;
        if (lane < 5) mbar_expect(sb + CB_M + lane * 8, lane ? 4096 : 2048);
        __syncwarp();
        if (elect()) {
#pragma unroll
          for (int b = 0; b < 5; b++) {
            wait_until(t0, P.dly[14 + b]);
            m_fetch(sb, src, b, sb + CB_M + b * 8);
            TR(40 + b * 4);
          }
        }
        __syncwarp();
        ring = ring + 1 == MRING ? 0 : ring + 1;
        uint32_t va, vb;
        const uint32_t off = timer_offset(), tag = (uint32_t)(n + 1) << 24;
        bar_sync(B_QK, 416);
        if (n + 1 == STEPS) break;
        sts32(sb + C_REF + 4, 0);
        const uint32_t c0 = clk(), stamp = c0 + off;
        st_relaxed_if(g_fl + FL_SYNC + lane * 1024 + c, tag | (stamp & 0xFFFFFF), lane < 2);
        TR(13);
        wait_until(c0, DLYS);
        int it = 0;
        do {
          asm volatile("ld.relaxed.gpu.global.v2.u32 {%0,%1}, [%2];" : "=r"(va), "=r"(vb) : "l"(ts) : "memory");
          spin_guard(it);
        } while (__any_sync(~0u, ((va ^ tag) | (vb ^ tag)) >> 24));
        const int late = __reduce_max_sync(~0u, max((int)((va - stamp) << 8), (int)((vb - stamp) << 8))) >> 8;
        t0 = c0 + min((uint32_t)late, clk() - c0);
        if (elect()) {
          sts32(sb + C_REF, t0);
          mbar_arrive(sb + CB_REF);
        }
        st_relaxed_if(g_fl + FL_TICK + lane * 1024, tag | ((t0 + off) & 0xFFFFFF), c == 0 && lane < 2);
        TR(14); CNT(11, it);
        bar_sync(B_M, 160);
      }
    }
  }
}

template <int WG>
__device__ __forceinline__ void g_math(const Params& P, uint32_t sb) {
  const int q = g_unit(WG);
  const int lane = threadIdx.x & 31, w = (threadIdx.x >> 5) & 3;
  const bool isq = q >= 64;
  uint32_t a[136];
  {
    const uint32_t stage = sb + G_W + WG * 73728;
    mbar_wait(sb + W_BAR + WG * 8, 0);
    if (threadIdx.x == 0) TS(23);
    load_frags<34>(a, stage);
    fence_async_smem();
    bar_sync(B_WG0 + WG, 128);
    if (threadIdx.x == 0) TS(24);
    load_wg<GROLE>(P, sb, false, WG, w);
    if (threadIdx.x == 0) TS(25);
    mbar_wait(sb + W_BAR + WG * 8, 1);
  }
  if ((threadIdx.x & 127) == 0) TS(4);
  const uint32_t off0 = (q & 31) * 49152 + (q >> 5) * 8192 +
                        (isq ? (w >> 1) * 4096 + (w & 1) * 512 + lane * 16 : w * 1024 + (lane >> 2) * 64 + (((lane ^ (lane >> 3)) & 3) << 4));
#pragma unroll 1
  for (int n = 0; n < STEPS; n++) {
    float d0[32], d1[32];
    if (WG == 0 && n >= LOCK0) bar_sync(B_OE, 160);
    if (n > 0) bar_sync(B_V + WG, 256);
#pragma unroll
    for (int ch = 0; ch < 9; ch++) {
      mbar_wait(sb + G_BAR + ch * 8, n & 1);
      if (ch == 0) { if ((threadIdx.x & 127) == 0) T3(5 + WG * 3); __syncwarp(); }
      if (ch == 4) { if ((threadIdx.x & 127) == 0) T3(6 + WG * 3); __syncwarp(); }
      if (ch == 8 && (WG == 0 ? n > 0 : n + 1 < STEPS)) bar_arrive(B_V + (WG ^ 1), 256);
      wg_fence();
#pragma unroll
      for (int kk = 0; kk < (ch < FASTG ? 3 : 4); kk++) {
        const int i = ch * 4 + kk;
        float* d = i & 1 ? d1 : d0;
        const uint64_t db = desc_sw128(G_RING + ch * 8192 + (kk & 2) * 32);
        if (i < 2) wg_rs64<0>(d, a + i * 4, db);
        else if (i < 34) wg_rs64<1>(d, a + i * 4, db);
        else wg_ss64<1>(d, desc_sw128(G_W2 + WG * 4096 + (i - 34) * 2048), db);
        wg_ss64<1>(d, desc_sw128(G_W + WG * 73728 + i * 2048), db + 2);
      }
      wg_commit();
      if (ch > 0) { wg_wait<1>(); if (lane == 0) mbar_arrive(sb + G_BAR + 128 + (ch - 1) * 8); }
    }
    wg_wait<0>();
    if (lane == 0) mbar_arrive(sb + G_BAR + 128 + 8 * 8);
    if ((threadIdx.x & 127) == 0) T3(7 + WG * 3);
    __syncwarp();
    uint32_t tw = clk() + (n == 0 ? -100000 : WG ? 0 : DLYW);
    unsigned char* base = g_qkv + (size_t)(n & (QRING - 1)) * (N_CHAIN * 24576);
    if ((ABL & 1) && d0[0] != 1234.5f) {
    } else if (isq) {
#pragma unroll
      for (int i = 0; i < 8; i++) {
        const float *d = (i < 4 ? d0 : d1) + 4 * i, *e = (i < 4 ? d1 : d0) + 4 * i;
        wait_until(tw, 0); tw += P.dly[2 + WG];
        *(uint4*)(base + off0 + (i >> 2) * 24576 + (i & 3) * 1024) =
          make_uint4(movmat(pack2(d[0], d[1])), movmat(pack2(e[0], e[1])), movmat(pack2(d[2], d[3])), movmat(pack2(e[2], e[3])));
      }
    } else {
#pragma unroll
      for (int i = 0; i < 8; i++) {
        const float* d = (i < 4 ? d0 : d1) + 8 * (i & 2) + 2 * (i & 1);
        wait_until(tw, 0); tw += P.dly[2 + WG];
        *(uint4*)(base + off0 + (i >> 2) * 24576 + (i & 2) * 2048 + (i & 1) * 512) =
          make_uint4(pack2(d[0], d[1]), pack2(d[4], d[5]), pack2(d[8], d[9]), pack2(d[12], d[13]));
      }
    }
    bar_arrive(B_M + WG, 160);
  }
}

__device__ __forceinline__ void fill16(void* p, uint32_t v) {
  asm volatile("st.global.v4.u32 [%0], {%1,%1,%1,%1};" :: "l"(p), "r"(v) : "memory");
}
__device__ __forceinline__ void g_load(const Params& P, uint32_t sb) {
  const int lane = threadIdx.x & 31, w = __shfl_sync(~0u, (threadIdx.x >> 5) & 3, 0);
  if (w == 2) return;
  if (w < 2) { bar_sync(15, 192); fence_async_smem(); }
  uint32_t fl = 0;
#pragma unroll 1
  for (int n = w == 3 ? LOCK0 : 0; n < STEPS; n++) {
    if (w && n == LOCK0) { grid_wait(1, lds32(sb + S_GEN)); fl = near_half(XB_F, bid()) * 1024; }
    if (w == 3) {
      const uint32_t tag = (uint32_t)(n - LOCK0 + 1) << 24;
      uint32_t v; int it = 0;
      do { asm volatile("ld.relaxed.gpu.global.u32 %0, [%1];" : "=r"(v) : "l"(g_fl + fl + FL_TICK) : "memory"); spin_guard(it); } while (!NOCHAIN && v < tag);
      const uint32_t off = timer_offset(), now = clk(), t0 = now - ((v ^ tag) >> 24 ? DLYG : (now + off - v) & 0xFFFFFF);
      asm volatile("fence.acquire.gpu;" ::: "memory");
      if (lane == 0) T3(11);
      __syncwarp();
      wait_until(t0, DLYG);
      if (lane == 0) T3(4);
      bar_sync(B_OE, 160);
      continue;
    }
    if (w == 0 || n == 0) {
      if (n < NSEG) wait_flags(g_lnflag + n * 16 + (lane & 1) * 8, 1);
    } else if (!NOCHAIN && n >= LAG) {
      wait_flags(g_fl + fl + FL_F + (lane & 1) * 8, n - LAG + 1);
    }
    if (w) { if (lane == 0) T3(12); bar_sync(B_X, 96); }
    fence_async_global();
    const unsigned char* src = g_lnimg + (uint32_t)((w ? (n >= LAG ? NSEG + n - LAG : 0) : min(n, NSEG - 1)) * 36864);
#pragma unroll 1
    for (int ch = 0; ch < 9; ch++) {
      const uint32_t full = sb + G_BAR + ch * 8;
      mbar_wait(full + 128, (n & 1) ^ 1);
      if (elect()) {
        mbar_expect(full, ABL & 2 ? 16 : 4096);
        bulk_load(sb + G_RING + ch * 8192 + w * 4096, src + ch * 4096, ABL & 2 ? 16 : 4096, full);
      }
    }
  }
}

__device__ __forceinline__ void g_aux(const Params& P, uint32_t sb) {
  const int lane = threadIdx.x & 31, w = (threadIdx.x >> 5) & 3;
  if (w == 1 || w == 2) {
    const int q = g_unit(w - 1);
    uint32_t* f = g_fl + FL_G + q * 8;
#pragma unroll 1
    for (int n = 0; n < STEPS; n++) {
      const uint32_t ln = opaque_tid() & 31;
      uint4* z = (uint4*)g_oacc + (uint32_t)(((n + 1) % ARING) * (16 * DM) + q * 96 + ln);
      if (!(ABL & 16)) { fill16(z, 0); fill16(z + 32, 0); fill16(z + 64, 0); }
      if (n + 3 >= MRING && q < 80) fill16((uint4*)g_mimg + (uint32_t)(((n + 3) % MRING) * 4096 + q * 32 + ln), SENT);
      bar_sync(B_M + (w - 1), 160);
      if (lane == 0) { T3(w * 2 - 2); fence_async_global(); flag_release(f, n + 1); T3(w * 2 - 1); }
      __syncwarp();
    }
  } else {
    const uint32_t u = (bid() - N_CHAIN) * 2 + (w & 1), r = u / 36 * 16 + (u & 3) * 4 + (lane >> 3);
    uint32_t o = r * (DM / 8) + (u % 36 >> 2) * 8 + ((lane & 7) ^ ((r >> 1) & 3)), fl = 0;
#pragma unroll 1
    for (int k = -LAG - 1; k < STEPS; k++) {
      if (k < NSEG - 1) bar_sync(B_X, 96);
      if (k < LAG || u >= 72) continue;
      if (k == NSEG - 1) { fl = near_half(XB_F, bid()) * 1024; wait_flags(g_fl + fl + FL_F + (lane & 1) * 8, NSEG + 1); }
      const uint4 x = __ldcg((const uint4*)P.out + o);
      if (k >= NSEG - 1) wait_flags(g_fl + fl + FL_OCNT + (max(k, NSEG) % OCRING) * 8, N_O * 3 * (max(k, NSEG) / OCRING + 1));
      const float4* a = (const float4*)g_oacc + ((k % ARING) * (16 * DM) + 8 * DM + u * 64 + lane * 2);
      const float4 p = __ldcg(a), v = __ldcg(a + 1);
      ((uint4*)P.out)[o] = make_uint4(badd2(x.x, pack2(p.x, p.y)), badd2(x.y, pack2(p.z, p.w)), badd2(x.z, pack2(v.x, v.y)), badd2(x.w, pack2(v.z, v.w)));
      o += 4 * DM;
    }
    if ((threadIdx.x & 127) == 0) TS(7);
  }
}

template <int WG, bool HALF, int KS, int N> __device__ __forceinline__ void o_mma(float* d, const uint32_t* a, uint32_t ob) {
  constexpr uint64_t db = desc_sw128(O_RING + (KS >> 2) * 8192 + (KS & 3) * 32);
  constexpr uint64_t da = desc_sw128(O_W + WG * 40960 + (KS < 40 ? KS / 5 * 2 + KS % 5 / 2 : KS - 24) * 2048);
  if constexpr (KS < 40 && !(KS % 5 & 1)) {
    const uint32_t* r = a + (KS / 5 * 3 + KS % 5 / 2) * 4;
    if constexpr (HALF) wg_rs32k<KS != 0, db>(d, r[0], r[1], r[2], r[3], ob); else wg_rs64<KS != 0>(d, r, db);
  } else {
    if constexpr (HALF) wg_ss32k<da, db>(d, ob); else wg_ss64<1>(d, da, db);
  }
  if constexpr (N > 1) o_mma<WG, HALF, KS + 1, N - 1>(d, a, ob);
}
template <int WG, bool HALF, int GR> __device__ __forceinline__ void o_groups(float* d, const uint32_t* a, uint32_t sb, int n, bool more) {
  const uint32_t ob = n < NSEG ? 0 : 256;
  mbar_wait(sb + O_BAR + GR * 8, n & 1);
  if (GR == 0) { if ((threadIdx.x & 127) == 0) T3(13 + WG); __syncwarp(); }
  if (GR == (WG == 0 ? OTURN : 4) && (WG < 2 || n + 1 < STEPS)) bar_arrive(B_V + (WG + 1) % 3, 256);
  wg_fence();
  o_mma<WG, HALF, GR * 8, 8 - 2 * FASTO>(d, a, ob);
  if (GR == 4 && more) o_mma<WG, HALF, 40, 4>(d, a, ob);
  wg_commit();
  if (GR > 0) { wg_wait<1>(); if ((threadIdx.x & 31) == 0) mbar_arrive(sb + O_BAR + 128 + (GR - 1) * 8); }
  if constexpr (GR < 4) o_groups<WG, HALF, GR + 1>(d, a, sb, n, more);
}
template <int WG, bool HALF> __device__ __forceinline__ void o_step(const uint32_t* a, uint32_t sb, uint32_t st0, int n, bool more) {
  float d[HALF ? 16 : 32];
  if (WG > 0 || n > 0) bar_sync(B_V + WG, 256);
  o_groups<WG, HALF, 0>(d, a, sb, n, more);
  wg_wait<0>();
  if ((threadIdx.x & 31) == 0) mbar_arrive(sb + O_BAR + 128 + 4 * 8);
  if ((threadIdx.x & 127) == 0) T3(WG == 0 ? 1 : WG == 1 ? 8 : 12);
  __syncwarp();
#pragma unroll(HALF ? 1 : 2)
  for (int sl = 0; sl < 2; sl++) {
    mbar_wait(sb + OB_ST + WG * 16 + sl * 8, (n & 1) ^ (WG == 0));
    if (!HALF || sl == (n >= NSEG)) {
#pragma unroll
      for (int nb = 0; nb < 4; nb++) {
        const float* r = d + (HALF ? 0 : sl * 16) + nb * 4;
        const uint32_t ad = st0 + sl * 8192 + nb * 2048;
        sts32(ad, __float_as_uint(r[0]));
        sts32(ad + 256, __float_as_uint(r[1]));
        sts32(ad ^ 32, __float_as_uint(r[2]));
        sts32((ad ^ 32) + 256, __float_as_uint(r[3]));
      }
      fence_async_smem();
    }
    bar_arrive((sl ? B_G : B_M) + WG, 160);
  }
}
template <int WG>
__device__ __forceinline__ void o_math(const Params& P, uint32_t sb) {
  const bool more = bid() < N_CHAIN + N_G + 12;
  const int lane = threadIdx.x & 31, w = (threadIdx.x >> 5) & 3, g = lane >> 2, tq = lane & 3;
  uint32_t a[96];
  mbar_wait(sb + W_BAR + WG * 8, 0);
  load_frags<24>(a, sb + WG * 49152);
  fence_async_smem();
  bar_sync(B_INIT, 416);
  load_wg<OROLE>(P, sb, false, WG, w);
  mbar_wait(sb + W_BAR + WG * 8, 1);
  if ((threadIdx.x & 127) == 0) TS(4);
  const uint32_t st0 = sb + O_ST + tq * 512 + ((w * 16 + g) ^ (tq * 8)) * 4;
#pragma unroll 1
  for (int n = 0; n < STEPS; n++) {
    if (n < LAG || n >= NSEG) o_step<WG, true>(a, sb, st0, n, more); else o_step<WG, false>(a, sb, st0, n, more);
  }
}

__device__ __forceinline__ void o_aux(const Params& P, uint32_t sb) {
  const int i = bid() - N_CHAIN - N_G, ksl = i / 3;
  const int c0 = ksl * 11 - max(ksl - 4, 0), nc = ksl < 4 ? 11 : 10;
  const int lane = threadIdx.x & 31, w = __shfl_sync(~0u, (threadIdx.x >> 5) & 3, 0);
  if (w == 0) {
    bar_sync(B_INIT, 416);
    const uint32_t* f = g_fl + FL_O + near_half(XB_F + 1, bid()) * 1024 + min((c0 & ~1) + lane, (c0 + nc - 1) | 1);
#pragma unroll 1
    for (int n = 0; n < STEPS; n++) {
      const unsigned char* src = g_oimg + (uint32_t)(((n % RING) * N_CHAIN + c0) * 8192);
      if (!NOCHAIN) wait_flags(f, n + 1);
      fence_async_global();
      if (lane == 0) T3(0);
#pragma unroll
      for (int gr = 0; gr < 5; gr++) {
        const uint32_t full = sb + O_BAR + gr * 8, bytes = ABL & 4 ? 16 : (gr < 4 ? 2 : nc - 8) * 8192;
        mbar_wait(full + 128, (n & 1) ^ 1);
        if (elect()) {
          if (n < LAG || n >= NSEG) {
            mbar_expect(full, bytes >> 1);
            for (uint32_t o = gr * 16384 + (n < LAG ? 0 : 4096); o < gr * 16384 + bytes; o += 8192) bulk_load(sb + O_RING + o, src + o, 4096, full);
          } else {
            mbar_expect(full, bytes);
            bulk_load(sb + O_RING + gr * 16384, src + gr * 16384, bytes, full);
          }
        }
      }
    }
  } else {
#pragma unroll 1
    for (int n = 0; n < STEPS; n++) {
      float* dst = g_oacc + (uint32_t)((n % ARING) * (64 * DM) + ((i % 3) * 3 + (w - 1 + ksl) % 3) * 1024);
      const bool early = w == 3 && n < NSEG;
      bar_sync(B_M + (w - 1), 160);
      if (lane == 0) {
        T3(w * 2);
        if (n < NSEG && !(ABL & 8)) { bulk_reduce(dst, sb + O_ST, 4096); bulk_reduce(dst + 16 * DM, sb + O_ST + 4096, 4096); }
        asm volatile("cp.async.bulk.commit_group;" ::: "memory");
        if (early) {
          asm volatile("cp.async.bulk.wait_group.read 0;" ::: "memory");
          mbar_arrive(sb + OB_ST);
          T3(8 + w);
          bulk_done_inc(g_fl + FL_OCNT + (n % OCRING) * 8);
          T3(w * 2 + 1);
        }
      }
      __syncwarp();
      bar_sync(B_G + (w - 1), 160);
      if (lane == 0) {
        if (n >= LAG && !(ABL & 8)) { bulk_reduce(dst + 32 * DM, sb + O_ST + 8192, 4096); bulk_reduce(dst + 48 * DM, sb + O_ST + 12288, 4096); }
        asm volatile("cp.async.bulk.commit_group;\ncp.async.bulk.wait_group.read 1;" ::: "memory");
        if (!early) mbar_arrive(sb + OB_ST + (w % 3) * 16);
        asm volatile("cp.async.bulk.wait_group.read 0;" ::: "memory");
        mbar_arrive(sb + OB_ST + (w % 3) * 16 + 8);
        if (!early) {
          T3(8 + w);
          bulk_done_inc(g_fl + FL_OCNT + (n % OCRING) * 8);
          T3(w * 2 + 1);
        }
      }
      __syncwarp();
    }
  }
}

constexpr uint32_t Y_PITCH = 1168, Y_ROWS = 16 * Y_PITCH;
template <int R> __device__ __forceinline__ void y_rows(uint32_t* y, uint32_t src, uint32_t dst, int w, int bar) {
  const int lane = threadIdx.x & 31;
#pragma unroll
  for (int k = 0; k < 2 * R + 1; k++) {
    const int op = w + k * (16 / R);
    if (k == 2 * R && w >= 4) break;
    uint32_t a, b, c, d;
    ldsm4t(a, b, c, d, src + op * 512 + (lane & 16) * 16 + (lane & 7) * 32 + (lane & 8) * 2);
    stsm4(dst + (lane & 15) * Y_PITCH + op * 32 + (lane & 16), a, b, c, d);
  }
  bar_sync(bar, 512 / R);
  const uint32_t row = dst + ((w & 6) * 2 + (w >> 3) * 2 + (w & 1)) * Y_PITCH + lane * 4;
#pragma unroll
  for (int i = 0; i < 9 * R; i++) y[i] = lds32(row + i / 9 * 2 * Y_PITCH + i % 9 * 128);
}

__device__ __forceinline__ void f_role(const Params& P, uint32_t sb) {
  const int lane = threadIdx.x & 31, w = __shfl_sync(~0u, threadIdx.x >> 5, 0), r0 = (bid() - N_CHAIN - N_G - N_O) * 16;
  if (w == 8) {
    const uint32_t* fo = g_fl + FL_OCNT + near_half(XB_F, bid()) * 1024;
    fence_async_global();
#pragma unroll 1
    for (int n = 0; n < NSEG; n++) {
      bar_sync(2, 288);
      if (elect()) {
        mbar_expect(sb + F_BAR, 36864);
        bulk_load(sb + F_XY, P.X + (size_t)(n * 32 + r0) * DM, 18432, sb + F_BAR);
        bulk_load(sb + F_XY + 18432, g_yT + (size_t)(n * 32 + r0) * DM, 18432, sb + F_BAR);
        mbar_expect(sb + F_BAR + 8, 36864);
        T3(1);
      }
      wait_flags(fo + (n % OCRING) * 8, NOCHAIN == 5 ? 0 : N_O * 3 * (n / OCRING + 1));
      fence_async_global();
      if (elect()) { bulk_load(sb + F_A, g_oacc + (uint32_t)((n % ARING) * (64 * DM) + r0 * DM), 36864, sb + F_BAR + 8); T3(0); }
    }
  } else if (w == 9) {
#pragma unroll 1
    for (int n = 0; n < NSEG; n++) {
      const uint32_t st = sb + (n & 1) * 36864;
      unsigned char* p = g_lnimg + (uint32_t)((NSEG + n) * 36864 + r0 * 128);
      bar_sync(1, 288);
      if (elect()) {
        T3(2);
#pragma unroll
        for (int i = 0; i < 9; i++) bulk_store(p + i * 4096, st + F_L + i * 2048, 2048);
        asm volatile("cp.async.bulk.commit_group;" ::: "memory");
        bulk_done_inc(g_fl + FL_F + (bid() & 1) * 8);
        T3(3);
        bulk_store(P.out + (size_t)(n * 32 + r0) * DM, st + F_X, 18432);
        asm volatile("cp.async.bulk.commit_group;\ncp.async.bulk.wait_group.read 0;" ::: "memory");
        if (n + 1 == NSEG) bulk_done_inc(g_fl + FL_F + (bid() & 1) * 8);
      }
      __syncwarp();
    }
  } else if (w < 8) {
    const uint32_t row = sb + w * 1152 + lane * 4, acc = sb + F_A + w * 256 + (lane ^ ((w & 6) * 2)) * 8;
    const uint32_t ln = sb + F_L + w * 128 + (((lane >> 2) ^ w) << 4) + (lane & 3) * 4;
#pragma unroll 1
    for (int n = -1; n < NSEG; n++) {
      const uint32_t st = (n & 1) * 36864;
      uint32_t x[18], y[18], l[18];
      if (n >= 0) mbar_wait(sb + F_BAR, n & 1);
#pragma unroll
      for (int i = 0; i < 18; i++) x[i] = lds32(row + F_XY + i / 9 * 9216 + i % 9 * 128);
      y_rows<2>(y, sb + F_XY + 18432, sb + F_Y, w, 3);
      layernorm9<2>(x, l);
#pragma unroll
      for (int i = 0; i < 18; i++) x[i] = badd2(x[i], bmul2(l[i], y[i]));
      if (n >= 0) mbar_wait(sb + F_BAR + 8, n & 1);
      if (threadIdx.x == 0 && n >= 0) T3(4);
      __syncwarp();
      uint2 a[18];
#pragma unroll
      for (int i = 0; i < 18; i++) a[i] = lds64(acc + i / 9 * 2048 + i % 9 * 4096);
#pragma unroll
      for (int i = 0; i < 18; i++) x[i] = badd2(x[i], pack2(__uint_as_float(a[i].x), __uint_as_float(a[i].y)));
      if (n + 1 < NSEG) bar_arrive(2, 288);
      layernorm9<2>(x, l);
#pragma unroll
      for (int i = 0; i < 18; i++) { x[i] = badd2(x[i], bmul2(l[i], y[i])); sts32(row + st + F_X + i / 9 * 9216 + i % 9 * 128, x[i]); }
      layernorm9<2>(x, l);
#pragma unroll
      for (int i = 0; i < 18; i++) sts32(ln + st + i / 9 * 1024 + i % 9 * 2048, l[i]);
      fence_async_smem();
      if (n >= 0) bar_sync(1, 288); else bar_sync(3, 256);
    }
  }
}

constexpr uint32_t P_CH = 147456, P_CHSZ = 12800, P_H = 4352;
static_assert(P_CH + 6 * P_CHSZ <= G_BAR, "prologue smem");

template <int N>
__device__ __forceinline__ void conv_fold(float (*acc)[4], bool hi, uint32_t mine, uint32_t theirs, int bar, int cnt) {
#pragma unroll
  for (int i = 0; i < N / 2; i++) {
    uint4 v;
    v.x = __float_as_uint(hi ? acc[i][0] : acc[i + N / 2][0]); v.y = __float_as_uint(hi ? acc[i][1] : acc[i + N / 2][1]);
    v.z = __float_as_uint(hi ? acc[i][2] : acc[i + N / 2][2]); v.w = __float_as_uint(hi ? acc[i][3] : acc[i + N / 2][3]);
    sts128(mine + i * 512, v);
  }
  bar_sync(bar, cnt);
#pragma unroll
  for (int i = 0; i < N / 2; i++) {
    const uint4 v = lds128(theirs + i * 512);
    acc[i][0] = (hi ? acc[i + N / 2][0] : acc[i][0]) + __uint_as_float(v.x); acc[i][1] = (hi ? acc[i + N / 2][1] : acc[i][1]) + __uint_as_float(v.y);
    acc[i][2] = (hi ? acc[i + N / 2][2] : acc[i][2]) + __uint_as_float(v.z); acc[i][3] = (hi ? acc[i + N / 2][3] : acc[i][3]) + __uint_as_float(v.w);
  }
}
template <int N>
__device__ __forceinline__ void conv_store(const float (*acc)[4], int tile0, uint32_t su, int d, uint32_t dd) {
  const int lane = threadIdx.x & 31, g = lane >> 2, tq = lane & 3;
#pragma unroll
  for (int i = 0; i < N; i++) {
    const uint32_t ad = su + (8 + (tile0 + i) * 8 + g) * 32 + tq * 4, sw = (g & 4) << 2;
    const uint32_t lo = badd2(movmat(pack2(acc[i][0], acc[i][1])), bmul2(lds32(ad + sw), dd));
    const uint32_t hi = badd2(movmat(pack2(acc[i][2], acc[i][3])), bmul2(lds32(ad + (sw ^ 16)), dd));
    ((uint2*)g_yT)[(((tile0 + i) * 8 + g) * DM + d) * 4 + tq] = make_uint2(lo, hi);
  }
}

__device__ __forceinline__ void prologue(const Params& P, uint32_t sb) {
  const int b = bid(), tid = threadIdx.x, lane = tid & 31, warp = tid >> 5, t0 = b * 16;
  const bool isg = b >= N_CHAIN && b < N_CHAIN + N_G;
  const int nch = isg ? 2 : b < 128 ? 6 : 0, chb = b < N_CHAIN ? b * 6 : isg ? b * 2 + 256 : b * 6 - 192;
  const uint32_t tstart = clk();
  if (tid < 288) {
    if (b < 128) {
      const int c = (tid >> 1) * 4, tt = t0 + (tid & 1) * 8;
      uint2 kr[11], vr[8];
#pragma unroll
      for (int i = 0; i < 11; i++) { const int t = tt + i - 3; kr[i] = t >= 0 ? __ldg((const uint2*)(P.K + (size_t)t * DM + c)) : make_uint2(0, 0); }
#pragma unroll
      for (int i = 0; i < 8; i++) vr[i] = __ldg((const uint2*)(P.V + (size_t)(tt + i) * DM + c));
#pragma unroll
      for (int e = 0; e < 2; e++) {
        const uint4 sh = __ldg((const uint4*)(P.shift + c * 4) + e);
        const uint32_t s0 = __byte_perm(sh.x, sh.z, 0x5410), s1 = __byte_perm(sh.x, sh.z, 0x7632);
        const uint32_t s2 = __byte_perm(sh.y, sh.w, 0x5410), s3 = __byte_perm(sh.y, sh.w, 0x7632);
        uint32_t v[8];
#pragma unroll
        for (int i = 0; i < 8; i++) {
          const uint32_t k3 = e ? kr[i].y : kr[i].x, k2 = e ? kr[i + 1].y : kr[i + 1].x, k1 = e ? kr[i + 2].y : kr[i + 2].x, k0 = e ? kr[i + 3].y : kr[i + 3].x;
          v[i] = bmul2(badd2(badd2(badd2(bmul2(k3, s3), bmul2(k2, s2)), bmul2(k1, s1)), bmul2(k0, s0)), e ? vr[i].y : vr[i].x);
        }
        *(uint4*)(g_kvT + (size_t)(c + 2 * e) * KVP + tt) =
          make_uint4(__byte_perm(v[0], v[1], 0x5410), __byte_perm(v[2], v[3], 0x5410), __byte_perm(v[4], v[5], 0x5410), __byte_perm(v[6], v[7], 0x5410));
        *(uint4*)(g_kvT + (size_t)(c + 2 * e + 1) * KVP + tt) =
          make_uint4(__byte_perm(v[0], v[1], 0x7632), __byte_perm(v[2], v[3], 0x7632), __byte_perm(v[4], v[5], 0x7632), __byte_perm(v[6], v[7], 0x7632));
      }
    }
  } else if (tid < 384) {
    const int t = tid - 288;
    for (int i = b * 96 + t; i < 16 * DM; i += N_CTA * 96) ((uint4*)g_oacc)[i] = make_uint4(0, 0, 0, 0);
    if (b * 96 + t < 128 * 8) g_lnflag[b * 96 + t] = 0;
    if (t == 95) sts32(sb + S_GEN, ld_acquire(g_gbar));
    __syncwarp();
    wait_until(tstart, P.dly[23]);
    for (int i = t; i < 32 * nch; i += 96) asm volatile("prefetch.global.L2 [%0];" :: "l"(P.Hk + (size_t)chb * SEQ + i * 64));
  }
  if (warp < 12) {
    bar_arrive(10, 416);
    if (tid == 128) TS(14);
    const int ch = 5 - (warp >> 1), sub = warp & 1, d = chb + ch;
    const uint32_t su = sb + P_CH + ch * P_CHSZ;
    if (ch < nch) {
      const uint32_t* hs = (const uint32_t*)(P.Hk + (size_t)d * SEQ);
#pragma unroll
      for (int q = sub * 32 + lane; q < 256; q += 64) {
        const uint4 c = __ldg((const uint4*)hs + q);
        const uint32_t prev = q ? __ldg(hs + 4 * q - 1) : 0u;
        sts128(su + P_H + 32 + q * 16, make_uint4(__byte_perm(c.x, prev, 0x7610), __byte_perm(c.y, c.x, 0x7610), __byte_perm(c.z, c.y, 0x7610), __byte_perm(c.w, c.z, 0x7610)));
        sts128(su + P_H + 4224 + q * 16, make_uint4(__byte_perm(c.x, 0, 0x1032), __byte_perm(c.y, 0, 0x1032), __byte_perm(c.z, 0, 0x1032), __byte_perm(c.w, 0, 0x1032)));
      }
      if (sub == 1 && lane == 0) sts32(su + P_CHSZ - 16, __bfloat16_as_ushort(P.Dk[d]) * 0x10001u);
      if (sub == 0 && lane < 20) sts128(su + (lane < 16 ? lane * 16 : P_H + (lane & 2) * 2096 + (lane & 1) * 16), make_uint4(0, 0, 0, 0));
    }
    bar_sync(11, 416);
    if (ch < nch) {
#pragma unroll
      for (int q = sub * 32 + lane; q < 256; q += 64) {
        const int row = (q >> 1) + 8;
        sts128(su + row * 32 + (((q & 1) ^ ((row >> 2) & 1)) << 4), __ldcg((const uint4*)(g_kvT + (size_t)d * KVP) + q));
      }
    }
    const int g = lane >> 2, tq = lane & 3;
    const uint32_t sh = su + P_H + (g & 1) * 4192 + (8 + (g >> 1) - tq) * 4;
    float acc[16][4];
#pragma unroll
    for (int i = 0; i < 16; i++) { acc[i][0] = acc[i][1] = acc[i][2] = acc[i][3] = 0.f; }
    auto u_addr = [&](int res) {
      const int row = 8 - res + ((lane >> 4) << 3) + (lane & 7);
      return su + row * 32 + ((((lane >> 3) & 1) ^ ((row >> 2) & 1)) << 4);
    };
    if (ch < nch) {
      bar_sync(1 + ch, 64);
      if (tid == 352) TS(11);
      if (sub) {
#pragma unroll 4
        for (int res = 0; res < 8; res++) {
          uint32_t b0, b1, b2, b3;
          ldsm4(b0, b1, b2, b3, u_addr(res));
          const uint32_t r0 = lds32(sh + res * 32);
          mma16(acc[0], r0, lds32(sh + res * 32 + 16), lds32(sh + res * 32 - 16), r0, b0, b1);
        }
        conv_store<1>(acc, 0, su, d, lds32(su + P_CHSZ - 16));
      }
    }
    bar_arrive(12, 416);
    if (isg && warp < 8) { while ((int)(clk() - tstart - S1G) < 0) __nanosleep(200); load_wg<GROLE>(P, sb, true, warp >> 2, warp & 3); }
    if (ch < nch) {
#pragma unroll 1
      for (int res = sub * 4; res < sub * 4 + 4; res++) {
        uint32_t bf[16][2];
        const uint32_t ad = u_addr(res);
#pragma unroll
        for (int f = 0; f < 16; f += 2) ldsm4(bf[f][0], bf[f][1], bf[f + 1][0], bf[f + 1][1], ad + f * 256);
#pragma unroll
        for (int k = 0; k < 16; k++) {
          const int jj = k & 1 ? k >> 1 : 15 - (k >> 1);
          const uint32_t ah = sh + (8 * jj + res) * 32;
          const uint32_t r0 = lds32(ah), r1 = lds32(ah + 16), rm = lds32(ah - 16);
#pragma unroll
          for (int i = max(jj, 1); i < 16; i++) mma16(acc[i], r0, r1, rm, r0, bf[i - jj][0], bf[i - jj][1]);
        }
      }
      bar_sync(1 + ch, 64);
      if (tid == 352) TS(12);
      const uint32_t xb = su + P_H + lane * 16, dd = lds32(su + P_CHSZ - 16);
      conv_fold<16>(acc, sub, xb + sub * 4096, xb + (sub ^ 1) * 4096, 1 + ch, 64);
      conv_store<8>(acc, sub * 8, su, d, dd);
    }
  } else {
    for (int i = b; i < 194 + MRING * 5; i += N_CTA) {
      const int n = (i - 194) / 5, r = (i - 194) % 5, blk = i < 192 ? i / 6 * 8 + i % 6 : i < 194 ? XB_F + i - 192 : XB_M + n * 8 + r;
      const uint32_t fill = i < 194 ? 0u : SENT;
#pragma unroll 1
      for (int q = tid - 384; q < 256 && warp < 15; q += 96) {
        uint4 v = make_uint4(fill, fill, fill, fill);
        if (i >= 194 && n == 0 && (r > 0 || q < 128)) {
          const bf16* m = P.mem0 + (max(r * 8 - 4, 0) + (q >> 5)) * 16 + ((q >> 1) & 1) * 8 + ((q >> 2) & 7);
          v.x = pack2(__bfloat162float(m[0]), __bfloat162float(m[DM])); v.y = pack2(__bfloat162float(m[2 * DM]), __bfloat162float(m[3 * DM]));
          v.z = pack2(__bfloat162float(m[4 * DM]), __bfloat162float(m[5 * DM])); v.w = pack2(__bfloat162float(m[6 * DM]), __bfloat162float(m[7 * DM]));
        }
        g_xb[blk * 512 + q] = v;
        g_xb[blk * 512 + 256 + q] = v;
      }
    }
    if (tid < 388) g_xb[XB_REF * 512 + (tid & 2) * 128 + (b & ~1) + (tid & 1)] = make_uint4(0, 0, 0, 0);
    else if (tid < 392 && b < N_GRP) g_xb[(b * 8 + 7) * 512 + (tid & 2) * 128 + (tid & 1)] = make_uint4(0, 0, 0, 0);
    if (warp < 15) { bar_arrive(9, 128); bar_sync(7, 96); }
    if (tid == 384) TS(8);
    if (warp == 12) {
      const bf16* w = lane < 6 ? (lane % 3 == 0 ? P.Wk : lane % 3 == 1 ? P.Wv : P.Wq) + (((b >> 5) * 2 + lane / 3) * 32 + (b & 31)) * 2048
                               : (lane < 8 ? P.Wo + (lane - 6) * (9 * 131072) : P.X) + b * 2048;
      uint32_t t = tstart + P.dly[19];
      if ((int)(clk() - t) > 0) t = clk();
#pragma unroll 1
      for (int st = 0; st < 9 && b < N_CHAIN; st++) {
#pragma unroll 1
        for (int i = 0; i < 9; i++, t += PACE) {
          wait_until(t, 0);
          if (lane == st) asm volatile("cp.async.bulk.prefetch.L2.global [%0], 4096;" :: "l"(w + i * (lane < 6 ? 262144 : 131072)) : "memory");
        }
      }
      if (lane == 0) TS(10);
    } else if (warp == 15) {
      bar_sync(10, 416);
      if (lane == 0) { grid_arrive(0); if (nch) grid_wait(0, lds32(sb + S_GEN)); }
      __syncwarp();
      bar_arrive(11, 416);
      if (lane == 0) TS(1);
      bar_sync(9, 128);
      bar_sync(12, 416);
      if (lane == 0) { TS(16); grid_arrive(2); TS(17); }
    } else if (lane == 0) {
      if (warp == 13 || (warp == 14 && b < N_GRP)) {
        uint32_t* p = (uint32_t*)(g_xb + (warp == 13 ? XB_REF * 512 + b : (b * 8 + 7) * 512));
        int votes = 0;
        for (int rep = 0; rep < 24 && abs(votes) < 7; rep++) {
          uint32_t v0, v1, c0, c1;
          asm volatile("atom.relaxed.gpu.global.add.u32 %0, [%4], 0;\n atom.relaxed.gpu.global.add.u32 %1, [%5], 0;\n"
                       "{.reg .pred p; setp.eq.u32 p, %0, 0x7ffffff3; @p trap; mov.u32 %2, %%clock; setp.eq.u32 p, %1, 0x7ffffff3; @p trap; mov.u32 %3, %%clock;}"
                       : "=&r"(v0), "=&r"(v1), "=&r"(c0), "=&r"(c1) : "l"(p + (rep & 1) * 1024), "l"(p + ((rep & 1) ^ 1) * 1024) : "memory");
          votes += ((c1 - c0 > 80u) == (rep & 1)) ? 1 : -1;
        }
        if (warp == 13) { g_side[b] = votes > 0; TS(9); } else g_near[b] = votes > 0;
      }
    }
    __syncwarp();
    if (warp > 12 && b < N_CHAIN) {
      while ((int)(clk() - tstart - S1DLY) < 0) __nanosleep(200);
      for (int k = warp - 13; k < 8; k += 3) load_wg<CHAIN>(P, sb, true, 1 - k / 4, k & 3);
    }
  }
  if (b < N_CHAIN + N_G && (warp < 8 || (isg && warp >= 12))) bar_arrive(0, 512); else bar_sync(0, 512);
  if (tid == 352) TS(2);
}

__device__ __forceinline__ void publish_y() {
  if (threadIdx.x == 383) { grid_arrive(1); TS(18); }
  __syncwarp();
}

template <int R> __device__ __forceinline__ void ln_tiles(const Params& P, uint32_t sb) {
  const int lane = threadIdx.x & 31, w = (threadIdx.x >> 5) & (16 / R - 1), half = R == 1 ? 0 : threadIdx.x >> 8, u = N_CTA - 1 - bid();
  const int first = R == 1 ? u : 46 - 2 * u + half, step = R == 1 ? 4 : 40, last = R == 1 ? 8 : 128;
  const uint32_t raw = sb + P_CH + half * (18432 + Y_ROWS), mb = sb + T_BAR + (R - 1 + half) * 8;
  const bool lead = w == 16 / R - 1 && lane == 0;
  auto load_y = [&](const bf16* src, int tile) {
    fence_async_global();
    mbar_expect(mb, 18432);
    bulk_load(raw, src + (size_t)tile * 16 * DM, 18432, mb);
  };
  uint32_t nx[9 * R];
  auto load_x = [&](int tile) {
#pragma unroll
    for (int i = 0; i < 9 * R; i++) nx[i] = __ldg((const uint32_t*)(P.X + (size_t)(tile * 16 + w + i / 9 * 8) * DM) + i % 9 * 32 + lane);
  };
  load_x(first);
  if (R == 2) {
    if (lead) { grid_wait(1, lds32(sb + S_GEN)); if (u > 3) TS(13); load_y(g_yT, first); }
    __syncwarp();
  }
#pragma unroll 1
  for (int tile = first, real = R - 1, ph = 0; tile < last; tile += real * step, real = 1, ph ^= 1) {
    uint32_t x[9 * R], l[9 * R], y[9 * R];
    const bool ts = threadIdx.x == 0 && (R == 1 ? tile == first : u > 3 && tile == first + step);
    if (ts) TS(26);
#pragma unroll
    for (int i = 0; i < 9 * R; i++) x[i] = nx[i];
    layernorm9<R>(x, l);
    if (real && tile + step < last) load_x(tile + step);
    if (R == 2 && tile == first + step && u >= N_F && w < 6) load_wg<OROLE>(P, sb, true, w >> 1, half * 2 + (w & 1));
    if (R == 1 && tile == first && lead) {
      if (real) grid_wait(2, lds32(sb + S_GEN));
      TS(13);
      load_y(real ? g_yT : P.Hk, tile);
    }
    bar_sync(13 + half, 512 / R);
    mbar_wait(mb, ph);
    if (ts) TS(28);
    y_rows<R>(y, raw, raw + 18432, w, 13 + half);
    if (ts) TS(29);
    if (lead && real && tile + step < last) { fence_async_smem(); load_y(g_yT, tile + step); }
    __syncwarp();
#pragma unroll
    for (int i = 0; i < 9 * R; i++) x[i] = badd2(x[i], bmul2(l[i], y[i]));
    layernorm9<R>(x, l);
    if (ts && l[0] != 0x12345) TS(30);
#pragma unroll
    for (int r = 0; r < R; r++) store_ln_row(0, tile * 16 + w + r * 8, l + r * 9);
    if (R == 1) {
      __syncthreads();
      if (threadIdx.x == 32 && real) { if (tile < 4) TS(19); st_release(g_lnflag + tile * 8, 1); if (tile < 4) TS(20); }
      __syncwarp();
    }
    if (ts) TS(31);
  }
  if (R == 2) {
    __syncthreads();
    if (threadIdx.x >= 506) {
      asm volatile("fence.acq_rel.gpu;" ::: "memory");
      st_relaxed_if(g_lnflag + ((first ^ (lane & 1)) + (lane - 26) / 2 * step) * 8, 1, true);
    }
    __syncwarp();
    fence_async_smem();
    if (threadIdx.x == 0) TS(15);
  }
}

__global__ void __cluster_dims__(2, 1, 1) __launch_bounds__(512, 1) k_main(const __grid_constant__ Params P) {
  extern __shared__ __align__(1024) unsigned char smem[];
  const uint32_t sb = (uint32_t)__cvta_generic_to_shared(smem);
  const int b = bid(), wg = threadIdx.x >> 7;
  if ((threadIdx.x & 127) == 0) TS(0);
  if (threadIdx.x == 480) {
    if ((sb & 0xFFFFFF) != SBASE) __trap();
    for (int i = 0; i < 6; i++) mbar_init(sb + W_BAR + i * 8, 1);
    if (b < N_CHAIN) {
      mbar_init(sb + CB_FULL, 1); mbar_init(sb + CB_FULL + 8, 1);
      mbar_init(sb + CB_REF, 1);
      mbar_init(sb + CB_SX, 1); mbar_init(sb + CB_OX, 1); mbar_init(sb + CB_XX, 1); mbar_init(sb + CB_Q, 2); mbar_init(sb + CB_VF, 1); mbar_init(sb + CB_VF + 8, 1);
      sts32(sb + C_BAD, 0);
      for (int i = 0; i < 11; i++) mbar_init(sb + CB_M + i * 8, i == 0 ? 5 : i == 5 ? 3 : 1);
    } else if (b < N_CHAIN + N_G) {
      for (int i = 0; i < 9; i++) { mbar_init(sb + G_BAR + i * 8, 2); mbar_init(sb + G_BAR + 128 + i * 8, 8); }
    } else if (b < N_CHAIN + N_G + N_O) {
      for (int i = 0; i < 5; i++) { mbar_init(sb + O_BAR + i * 8, 1); mbar_init(sb + O_BAR + 128 + i * 8, 12); }
      for (int i = 0; i < 6; i++) mbar_init(sb + OB_ST + i * 8, 1);
    } else {
      mbar_init(sb + F_BAR, 1); mbar_init(sb + F_BAR + 8, 1);
    }
    asm volatile("fence.mbarrier_init.release.cluster;" ::: "memory");
    fence_async_smem();
  }
  __syncwarp();
  asm volatile("barrier.cluster.arrive.relaxed.aligned;" ::: "memory");
  prologue(P, sb);
  asm volatile("barrier.cluster.wait.aligned;" ::: "memory");
  fence_async_smem();
  if (b >= N_CHAIN + N_G) publish_y();
  if (b >= 128) ln_tiles<1>(P, sb);
  if (b >= N_CHAIN + N_G) ln_tiles<2>(P, sb);
  if ((threadIdx.x & 127) == 0) TS(3);
  if (b < N_CHAIN) {
    if (wg < 2) { reg_inc<200>(); chain_proj(P, sb); }
    else if (wg == 2) { reg_dec<ATTR>(); publish_y(); chain_attn(P, sb); }
    else { reg_dec<112 - ATTR>(); chain_aux(P, sb); }
  } else if (NOBULK) {
    if (b < N_CHAIN + N_G) publish_y();
    {
      if (wg == 0) {
        float d[4] = {0.f, 0.f, 0.f, 0.f};
        for (int n = 0; n < STEPS - 1; n++) {
          const uint32_t* f = g_fl + FL_TICK;
          uint32_t x;
          do { for (int k = 0; k < 16; k++) mma16(d, 0, 0, 0, 0, 0, 0); asm volatile("ld.relaxed.gpu.global.u32 %0, [%1];" : "=r"(x) : "l"(f) : "memory"); } while ((x >> 24) <= n);
          const int q = (b - N_CHAIN) * 4 + (threadIdx.x >> 5);
          if (n + 5 >= MRING && q < 80) fill16((uint4*)g_mimg + (uint32_t)(((n + 5) % MRING) * 4096 + q * 32 + (threadIdx.x & 31)), SENT);
        }
        if (d[0] == 1.f) P.out[0] = __float2bfloat16(0.f);
      }
    }
  } else if (b < N_CHAIN + N_G) {
    if (wg == 0) { reg_inc<232>(); g_math<0>(P, sb); }
    else if (wg == 1) { reg_inc<232>(); g_math<1>(P, sb); }
    else if (wg == 2) { reg_dec<24>(); bar_arrive(15, 192); publish_y(); g_aux(P, sb); }
    else { reg_dec<24>(); g_load(P, sb); }
  } else if (b < N_CHAIN + N_G + N_O) {
    if (wg == 0) { reg_inc<160>(); o_math<0>(P, sb); }
    else if (wg == 1) { reg_inc<160>(); o_math<1>(P, sb); }
    else if (wg == 2) { reg_inc<160>(); o_math<2>(P, sb); }
    else { reg_dec<32>(); o_aux(P, sb); }
  } else {
    f_role(P, sb);
  }
}

}

extern "C" void kernel_launch(void* const* d_in, const int* in_sizes, int n_in, void* d_out, int out_size) {
  typedef CUresult (*Encode)(CUtensorMap*, CUtensorMapDataType, cuuint32_t, void*, const cuuint64_t*, const cuuint64_t*, const cuuint32_t*, const cuuint32_t*,
                             CUtensorMapInterleave, CUtensorMapSwizzle, CUtensorMapL2promotion, CUtensorMapFloatOOBfill);
  static Encode encode = nullptr;
  if (!encode) cudaGetDriverEntryPoint("cuTensorMapEncodeTiled", (void**)&encode, cudaEnableDefault);
  Params P;
  for (int i = 0; i < 11; i++) {
    const bool wo = i == 6 || i == 7;
    const cuuint64_t cols = wo ? DM : HD, rows = HD + DM - cols, pitch = cols * 2;
    const cuuint64_t dim[4][5] = {{cols, 2, 8, 2, 18}, {cols, 16, 1, 1, rows / 16}, {cols, 2, 4, 4, rows / 32}, {64, 16, 64, 2, 18}};
    const cuuint64_t stride[4][4] = {{8 * pitch, pitch, 16 * pitch, 32 * pitch}, {pitch, pitch, pitch, 16 * pitch},
                                     {pitch, 8 * pitch, 2 * pitch, 32 * pitch}, {pitch, 128, 16 * pitch, 32 * pitch}};
    const cuuint32_t box[4][5] = {{64, 2, 8, 1, 18}, {64, 16, 1, 1, 1}, {64, 2, 4, 2, 1}, {64, 16, 2, 1, 18}}, one[5] = {1, 1, 1, 1, 1};
    const int k = i < 3 ? 0 : i < 7 ? 1 : i < 8 ? 2 : 3;
    encode(&P.map[i], CU_TENSOR_MAP_DATA_TYPE_BFLOAT16, 5, d_in[wo ? 11 : 8 + (i & 7) % 3], dim[k], stride[k], box[k], one,
           CU_TENSOR_MAP_INTERLEAVE_NONE, CU_TENSOR_MAP_SWIZZLE_128B, CU_TENSOR_MAP_L2_PROMOTION_L2_128B, CU_TENSOR_MAP_FLOAT_OOB_FILL_NONE);
  }
  P.X = (const bf16*)d_in[0]; P.K = (const bf16*)d_in[1]; P.V = (const bf16*)d_in[2];
  P.shift = (const bf16*)d_in[3]; P.Hk = (const bf16*)d_in[4]; P.Dk = (const bf16*)d_in[5];
  P.mem0 = (const bf16*)d_in[7];
  P.Wq = (const bf16*)d_in[8]; P.Wk = (const bf16*)d_in[9]; P.Wv = (const bf16*)d_in[10]; P.Wo = (const bf16*)d_in[11];
  P.out = (bf16*)d_out;
  for (int i = 0; i < 24; i++) P.dly[i] = h_dly[i];
  cudaFuncSetAttribute(k_main, cudaFuncAttributeMaxDynamicSharedMemorySize, SMEM_BYTES);
  k_main<<<N_CTA, 512, SMEM_BYTES>>>(P);
}
```

```cpp
#include <cuda.h>
#include <cuda_runtime.h>
#include <cuda_bf16.h>
#include <stdint.h>

namespace {

typedef __nv_bfloat16 bf16;

constexpr int SEQ = 2048, DM = 576, HD = 4096, NSEG = 64;
#define PLACE 1
#define LAGV 7
constexpr int LAG = LAGV, STEPS = NSEG + LAG, RING = 8, QRING = 4;
static_assert(LAG < RING, "ring");
constexpr int N_CHAIN = 64, N_G = 48, N_O = 18, N_F = 2;
constexpr uint32_t SBASE = 1024;
constexpr uint32_t SENT = 0xFFFFFFFFu;
constexpr int SPIN_MAX = 1 << 22;

__device__ __forceinline__ uint32_t bid() {
  uint32_t b;
  asm volatile("mov.u32 %0, %%ctaid.x;" : "=r"(b));
  return b < 6 ? b + 106 : b < 8 ? b + 122 : b < 114 ? b - 8 : b < 130 ? b - 2 : b;
}
__device__ __forceinline__ uint32_t chain_id() { return blockIdx.x - (PLACE ? 8 : 0); }
constexpr int KVP = SEQ + 64;
__device__ __align__(1024) bf16 g_kvT[DM * KVP];
__device__ __align__(1024) bf16 g_yT[DM * SEQ];
__device__ __align__(1024) unsigned char g_lnimg[2 * NSEG * 9 * 4096];
__device__ __align__(1024) unsigned char g_qkv[QRING * N_CHAIN * 24576];
__device__ __align__(1024) unsigned char g_oimg[RING * N_CHAIN * 8192];
constexpr int ARING = 16;
static_assert(ARING >= LAG + 9, "accumulator ring");
__device__ __align__(1024) float g_oacc[ARING * 64 * DM];
constexpr int MRING = LAG + 4, N_GRP = 32 + MRING + 1;
constexpr int XB_M = 256, XB_F = XB_M + MRING * 8, XB_REF = XB_F + 2, N_CTA = N_CHAIN + N_G + N_O + N_F;
__device__ __align__(65536) uint4 g_xb[N_GRP * 4096];
#define g_mimg ((uint32_t*)(g_xb + XB_M * 512))
__device__ uint32_t g_near[N_GRP];
__device__ uint32_t g_side[N_CTA];
__device__ __align__(128) uint32_t g_gbar[3 * 32];
constexpr int FL_G = 0, FL_F = 96 * 8, FL_OCNT = FL_F + 2 * 8, OCRING = 16, FL_TICK = 992, FL_O = 2048, FL_SYNC = FL_O + 128;
static_assert(FL_OCNT + OCRING * 8 <= FL_TICK, "flag block");
#define g_fl ((uint32_t*)(g_xb + XB_F * 512))
__device__ __align__(1024) uint32_t g_lnflag[128 * 8];
#define TS(slot)

#define OTURN 2
#define LOCK0 3
#define FASTO 0
#define FASTG 0
#define NOBULK 0
#define VPAT 0x15bbd249u
#define XR 3
#define RATE 1
#define WFENCE 0
#define QPOS 0
#define VE 4
#define OGAP 2
#define NOCHAIN 0
#define BFENCE 2
#define ABL 0
#define ATTR 80
#define CNT(slot, tries)
#define T3(slot)
#define TR(slot)
#define TRV(slot, val)
#define TRD(slot, dep)
#define TRSYNC()
#define TRDUMP(n)
#define CLK(t) "{.reg .b64 x; .reg .b32 h; mov.u64 x, %%clock64; mov.b64 {" t ", h}, x;}"
__device__ __forceinline__ uint32_t clk() { uint32_t t; asm volatile(CLK("%0") : "=r"(t) :: "memory"); return t; }
__device__ __forceinline__ void wait_until(uint32_t t0, uint32_t d) {
  asm volatile("{.reg .pred p; .reg .u32 t;\n"
               "W: " CLK("t") " sub.u32 t, t, %0; setp.lt.s32 p, t, 0; @p bra.uni W;}"
               :: "r"(t0 + d) : "memory");
}
__device__ __forceinline__ uint32_t pack2(float lo, float hi) {
  uint32_t r; asm("cvt.rn.bf16x2.f32 %0, %1, %2;" : "=r"(r) : "f"(hi), "f"(lo)); return r;
}
__device__ __forceinline__ float bf_lo(uint32_t v) { return __uint_as_float(v << 16); }
__device__ __forceinline__ float bf_hi(uint32_t v) { return __uint_as_float(v & 0xFFFF0000u); }

__device__ __forceinline__ uint4 ld_relaxed4(const void* p) {
  uint4 v; asm volatile("ld.relaxed.gpu.global.v4.u32 {%0,%1,%2,%3}, [%4];" : "=r"(v.x), "=r"(v.y), "=r"(v.z), "=r"(v.w) : "l"(p) : "memory"); return v;
}
__device__ __forceinline__ void st_b128(void* p, uint32_t a, uint32_t b, uint32_t c, uint32_t d) {
  asm volatile("{.reg .b128 v; mov.b128 v, {%1,%2,%3,%4}; st.relaxed.gpu.global.b128 [%0], v;}" :: "l"(p), "r"(a), "r"(b), "r"(c), "r"(d) : "memory");
}
__device__ __forceinline__ void reload_b128(uint4& v, const void* p, uint32_t again) {
  asm volatile("{.reg .pred p; .reg .b128 v; setp.ne.u32 p, %5, 0; mov.b128 v, {%0,%1,%2,%3};\n"
               "@p ld.relaxed.gpu.global.b128 v, [%4]; mov.b128 {%0,%1,%2,%3}, v;}"
    : "+r"(v.x), "+r"(v.y), "+r"(v.z), "+r"(v.w) : "l"(p), "r"(again) : "memory");
}
__device__ __forceinline__ void reload4(uint4& v, const void* p, uint32_t again) {
  asm volatile("{.reg .pred p; setp.ne.u32 p, %5, 0; @p ld.relaxed.gpu.global.v4.u32 {%0,%1,%2,%3}, [%4];}"
    : "+r"(v.x), "+r"(v.y), "+r"(v.z), "+r"(v.w) : "l"(p), "r"(again) : "memory");
}
__device__ __forceinline__ void st_relaxed4(void* p, uint32_t a, uint32_t b, uint32_t c, uint32_t d) {
  asm volatile("st.relaxed.gpu.global.v4.u32 [%0], {%1,%2,%3,%4};" :: "l"(p), "r"(a), "r"(b), "r"(c), "r"(d) : "memory");
}
__device__ __forceinline__ void st_relaxed_if(void* p, uint32_t a, bool on) {
  asm volatile("{.reg .pred p; setp.ne.u32 p, %2, 0; @p st.relaxed.gpu.global.u32 [%0], %1;}" :: "l"(p), "r"(a), "r"((uint32_t)on) : "memory");
}
__device__ __forceinline__ uint32_t ld_acquire(const uint32_t* p) {
  uint32_t v; asm volatile("ld.acquire.gpu.global.u32 %0, [%1];" : "=r"(v) : "l"(p) : "memory"); return v;
}
__device__ __forceinline__ void st_release(uint32_t* p, uint32_t v) {
  asm volatile("st.release.gpu.global.u32 [%0], %1;" :: "l"(p), "r"(v) : "memory");
}
__device__ __forceinline__ void bulk_reduce(float* dst, uint32_t src, uint32_t bytes) {
  asm volatile("cp.reduce.async.bulk.global.shared::cta.bulk_group.add.f32 [%0], [%1], %2;" :: "l"(dst), "r"(src), "r"(bytes) : "memory");
}
__device__ __forceinline__ void bulk_done_inc(uint32_t* p) {
  asm volatile("cp.async.bulk.wait_group 0;\n"
               "fence.proxy.async.global;\nfence.release.gpu;\n"
               "red.relaxed.gpu.global.add.u32 [%0], 1;\nred.relaxed.gpu.global.add.u32 [%0+4096], 1;" :: "l"(p) : "memory");
}
__device__ __forceinline__ void flag_release(uint32_t* p, uint32_t v) {
  asm volatile("fence.release.gpu;\nst.relaxed.gpu.global.u32 [%0], %1;\nst.relaxed.gpu.global.u32 [%0+4096], %1;" :: "l"(p), "r"(v) : "memory");
}
__device__ __forceinline__ void spin_guard(int& it) {
  asm volatile("{.reg .pred p; add.s32 %0, %0, 1; setp.gt.s32 p, %0, %1; @p trap;}" : "+r"(it) : "n"(SPIN_MAX));
}
__device__ __forceinline__ void wait_flag(const uint32_t* p, uint32_t v) {
  int it = 0;
  while (ld_acquire(p) < v) spin_guard(it);
}
__device__ __forceinline__ void wait_flags(const uint32_t* p, uint32_t v) {
  int it = 0;
  while (true) {
    uint32_t x; asm volatile("ld.relaxed.gpu.global.u32 %0, [%1];" : "=r"(x) : "l"(p) : "memory");
    if (__all_sync(~0u, x >= v)) break;
    spin_guard(it);
  }
  asm volatile("fence.acquire.gpu;" ::: "memory");
}
__device__ __forceinline__ uint32_t timer_offset() {
  uint32_t g0, g;
  asm volatile("mov.u32 %0, %%globaltimer_lo;" : "=r"(g0) :: "memory");
  do { asm volatile("mov.u32 %0, %%globaltimer_lo;" : "=r"(g) :: "memory"); } while (g == g0);
  return (g >> 5) * 58 - clk();
}
__device__ __forceinline__ void grid_arrive(int i) {
  asm volatile("red.release.gpu.global.add.u32 [%0], %1;" :: "l"(g_gbar + i * 32), "r"(bid() ? 1u : 257u - N_CTA) : "memory");
}
__device__ __forceinline__ void grid_wait(int i, uint32_t gen) {
  int it = 0;
  while (((ld_acquire(g_gbar + i * 32) ^ gen) >> 8) == 0) spin_guard(it);
}
__device__ __forceinline__ bool elect() {
  uint32_t r; asm volatile("{.reg .pred p; elect.sync _|p, -1; selp.u32 %0, 1, 0, p;}" : "=r"(r)); return r;
}
__device__ __forceinline__ void bar_sync(int id, int cnt) { asm volatile("bar.sync %0, %1;" :: "r"(id), "r"(cnt) : "memory"); }
__device__ __forceinline__ void bar_arrive(int id, int cnt) { asm volatile("bar.arrive %0, %1;" :: "r"(id), "r"(cnt) : "memory"); }
template <int id, int cnt> __device__ __forceinline__ void bar_arrive_after(uint32_t a, uint32_t b) {
  asm volatile("{.reg .pred p; setp.ne.u32 p, %2, 0xfff12345; setp.ne.and.u32 p, %3, 0xfff12345, p; @p bar.arrive %0, %1;}" :: "n"(id), "n"(cnt), "r"(a), "r"(b) : "memory");
}
template <int id, int cnt> __device__ __forceinline__ void bar_sync_after(uint32_t a) {
  asm volatile("{.reg .pred p; setp.ne.u32 p, %2, 0xfff12345; @p bar.sync %0, %1;}" :: "n"(id), "n"(cnt), "r"(a) : "memory");
}
__device__ __forceinline__ void fence_async_smem() { asm volatile("fence.proxy.async.shared::cta;" ::: "memory"); }
__device__ __forceinline__ void fence_async_global() { asm volatile("fence.proxy.async.global;" ::: "memory"); }
__device__ __forceinline__ void mbar_init(uint32_t mb, int cnt) { asm volatile("mbarrier.init.shared::cta.b64 [%0], %1;" :: "r"(mb), "r"(cnt) : "memory"); }
__device__ __forceinline__ void mbar_arrive(uint32_t mb) { asm volatile("mbarrier.arrive.shared::cta.b64 _, [%0];" :: "r"(mb) : "memory"); }
__device__ __forceinline__ void mbar_arrive_after(uint32_t mb, uint32_t a, uint32_t lane) {
  asm volatile("{.reg .pred p; setp.ne.u32 p, %1, 0xfff12345; setp.eq.and.u32 p, %2, 0, p; @p mbarrier.arrive.shared::cta.b64 _, [%0];}" :: "r"(mb), "r"(a), "r"(lane) : "memory");
}
__device__ __forceinline__ void mbar_expect(uint32_t mb, uint32_t bytes) {
  asm volatile("mbarrier.arrive.expect_tx.shared::cta.b64 _, [%0], %1;" :: "r"(mb), "r"(bytes) : "memory");
}
__device__ __forceinline__ void mbar_wait_guard(uint32_t mb, uint32_t parity) {
  uint32_t ok; int it = 0;
  while (true) {
    asm volatile("{.reg .pred p; mbarrier.try_wait.parity.shared::cta.b64 p, [%1], %2; selp.u32 %0, 1, 0, p;}" : "=r"(ok) : "r"(mb), "r"(parity) : "memory");
    if (ok) break;
    spin_guard(it);
  }
}
__device__ __forceinline__ void mbar_wait(uint32_t mb, uint32_t parity) {
  asm volatile("{.reg .pred p;\nW: mbarrier.try_wait.parity.shared::cta.b64 p, [%0], %1;\n@!p bra W;}" :: "r"(mb), "r"(parity) : "memory");
}
__device__ __forceinline__ void bulk_load(uint32_t dst, const void* src, uint32_t bytes, uint32_t mb) {
  asm volatile("cp.async.bulk.shared::cluster.global.mbarrier::complete_tx::bytes [%0], [%1], %2, [%3];" :: "r"(dst), "l"(src), "r"(bytes), "r"(mb) : "memory");
}
__device__ __forceinline__ void bulk_store(void* dst, uint32_t src, uint32_t bytes) {
  asm volatile("cp.async.bulk.global.shared::cta.bulk_group [%0], [%1], %2;" :: "l"(dst), "r"(src), "r"(bytes) : "memory");
}
__device__ __forceinline__ void cp_async16(uint32_t dst, const void* src) {
  asm volatile("cp.async.cg.shared.global [%0], [%1], 16;" :: "r"(dst), "l"(src) : "memory");
}
__device__ __forceinline__ void cp_async_wait_all() { asm volatile("cp.async.wait_all;" ::: "memory"); }
__device__ __forceinline__ uint32_t mapa(uint32_t a, uint32_t rank) {
  uint32_t r; asm("mapa.shared::cluster.u32 %0, %1, %2;" : "=r"(r) : "r"(a), "r"(rank)); return r;
}
__device__ __forceinline__ void st_async4(uint32_t dst, float a, float b, float c, float d, uint32_t mb) {
  asm volatile("st.async.shared::cluster.mbarrier::complete_tx::bytes.v4.f32 [%0], {%1,%2,%3,%4}, [%5];" :: "r"(dst), "f"(a), "f"(b), "f"(c), "f"(d), "r"(mb) : "memory");
}
__device__ __forceinline__ void st_async2(uint32_t dst, float a, float b, uint32_t mb) {
  asm volatile("st.async.shared::cluster.mbarrier::complete_tx::bytes.v2.f32 [%0], {%1,%2}, [%3];" :: "r"(dst), "f"(a), "f"(b), "r"(mb) : "memory");
}
__device__ __forceinline__ void st_async1(uint32_t dst, uint32_t a, uint32_t mb) {
  asm volatile("st.async.shared::cluster.mbarrier::complete_tx::bytes.u32 [%0], %1, [%2];" :: "r"(dst), "r"(a), "r"(mb) : "memory");
}
__device__ __forceinline__ uint4 lds128(uint32_t a) {
  uint4 v; asm volatile("ld.shared.v4.u32 {%0,%1,%2,%3}, [%4];" : "=r"(v.x), "=r"(v.y), "=r"(v.z), "=r"(v.w) : "r"(a) : "memory"); return v;
}
__device__ __forceinline__ uint2 lds64(uint32_t a) {
  uint2 v; asm volatile("ld.shared.v2.u32 {%0,%1}, [%2];" : "=r"(v.x), "=r"(v.y) : "r"(a) : "memory"); return v;
}
__device__ __forceinline__ uint32_t lds32(uint32_t a) {
  uint32_t v; asm volatile("ld.shared.u32 %0, [%1];" : "=r"(v) : "r"(a) : "memory"); return v;
}
__device__ __forceinline__ void sts128(uint32_t a, uint4 v) {
  asm volatile("st.shared.v4.u32 [%0], {%1,%2,%3,%4};" :: "r"(a), "r"(v.x), "r"(v.y), "r"(v.z), "r"(v.w) : "memory");
}
__device__ __forceinline__ void sts64(uint32_t a, uint32_t x, uint32_t y) {
  asm volatile("st.shared.v2.u32 [%0], {%1,%2};" :: "r"(a), "r"(x), "r"(y) : "memory");
}
__device__ __forceinline__ void sts32(uint32_t a, uint32_t x) { asm volatile("st.shared.u32 [%0], %1;" :: "r"(a), "r"(x) : "memory"); }
__device__ __forceinline__ void ldsm4(uint32_t& r0, uint32_t& r1, uint32_t& r2, uint32_t& r3, uint32_t a) {
  asm volatile("ldmatrix.sync.aligned.m8n8.x4.shared.b16 {%0,%1,%2,%3}, [%4];" : "=r"(r0), "=r"(r1), "=r"(r2), "=r"(r3) : "r"(a) : "memory");
}
__device__ __forceinline__ void ldsm4t(uint32_t& r0, uint32_t& r1, uint32_t& r2, uint32_t& r3, uint32_t a) {
  asm volatile("ldmatrix.sync.aligned.m8n8.x4.trans.shared.b16 {%0,%1,%2,%3}, [%4];" : "=r"(r0), "=r"(r1), "=r"(r2), "=r"(r3) : "r"(a) : "memory");
}
__device__ __forceinline__ void stsm4(uint32_t a, uint32_t r0, uint32_t r1, uint32_t r2, uint32_t r3) {
  asm volatile("stmatrix.sync.aligned.m8n8.x4.shared.b16 [%0], {%1,%2,%3,%4};" :: "r"(a), "r"(r0), "r"(r1), "r"(r2), "r"(r3) : "memory");
}
__device__ __forceinline__ uint32_t movmat(uint32_t a) {
  uint32_t d; asm volatile("movmatrix.sync.aligned.m8n8.trans.b16 %0, %1;" : "=r"(d) : "r"(a)); return d;
}
__device__ __forceinline__ void mma16(float* d, uint32_t a0, uint32_t a1, uint32_t a2, uint32_t a3, uint32_t b0, uint32_t b1) {
  asm volatile("mma.sync.aligned.m16n8k16.row.col.f32.bf16.bf16.f32 {%0,%1,%2,%3}, {%4,%5,%6,%7}, {%8,%9}, {%0,%1,%2,%3};"
    : "+f"(d[0]), "+f"(d[1]), "+f"(d[2]), "+f"(d[3]) : "r"(a0), "r"(a1), "r"(a2), "r"(a3), "r"(b0), "r"(b1));
}
__device__ __forceinline__ void mma8(float* d, uint32_t a0, uint32_t a1, uint32_t b0) {
  asm volatile("mma.sync.aligned.m16n8k8.row.col.f32.bf16.bf16.f32 {%0,%1,%2,%3}, {%4,%5}, {%6}, {%0,%1,%2,%3};"
    : "+f"(d[0]), "+f"(d[1]), "+f"(d[2]), "+f"(d[3]) : "r"(a0), "r"(a1), "r"(b0));
}
__device__ __forceinline__ float rcp(float x) { float r; asm("rcp.approx.ftz.f32 %0, %1;" : "=f"(r) : "f"(x)); return r; }
__device__ __forceinline__ float ex2(float x) { float r; asm("ex2.approx.ftz.f32 %0, %1;" : "=f"(r) : "f"(x)); return r; }

__host__ __device__ constexpr uint64_t mkdesc(uint32_t off, uint32_t lbo, uint32_t sbo, uint32_t swz) {
  return (uint64_t)((SBASE + off) >> 4) | ((uint64_t)(lbo >> 4) << 16) | ((uint64_t)(sbo >> 4) << 32) | ((uint64_t)swz << 62);
}
__host__ __device__ constexpr uint64_t desc_sw128(uint32_t off) { return mkdesc(off, 16, 1024, 1); }
__host__ __device__ constexpr uint64_t desc_n16(uint32_t off) { return mkdesc(off, 256, 128, 0); }
__host__ __device__ constexpr uint64_t desc_m(uint32_t off) { return mkdesc(off, 16, 256, 3); }

__host__ __device__ constexpr uint64_t desc_sw64(uint32_t off) { return mkdesc(off, 16, 512, 2); }

__device__ __forceinline__ void wg_fence() { asm volatile("wgmma.fence.sync.aligned;" ::: "memory"); }
__device__ __forceinline__ void wg_commit() { asm volatile("wgmma.commit_group.sync.aligned;" ::: "memory"); }
template <int N> __device__ __forceinline__ void wg_wait() { asm volatile("wgmma.wait_group.sync.aligned %0;" :: "n"(N) : "memory"); }

#define ACC8(d) "+f"(d[0]), "+f"(d[1]), "+f"(d[2]), "+f"(d[3]), "+f"(d[4]), "+f"(d[5]), "+f"(d[6]), "+f"(d[7])
#define ACC32(d) ACC8(d), ACC8((d + 8)), ACC8((d + 16)), ACC8((d + 24))
#define R8 "{%0,%1,%2,%3,%4,%5,%6,%7}"
#define R32 "{%0,%1,%2,%3,%4,%5,%6,%7,%8,%9,%10,%11,%12,%13,%14,%15,%16,%17,%18,%19,%20,%21,%22,%23,%24,%25,%26,%27,%28,%29,%30,%31}"
template <int SD> __device__ __forceinline__ void wg_rs16(float* d, const uint32_t* a, uint64_t db) {
  asm volatile("wgmma.mma_async.sync.aligned.m64n16k16.f32.bf16.bf16 " R8 ", {%8,%9,%10,%11}, %12, %13, 1, 1, 1;"
    : ACC8(d) : "r"(a[0]), "r"(a[1]), "r"(a[2]), "r"(a[3]), "l"(db), "n"(SD));
}
template <int SD> __device__ __forceinline__ void wg_ss16(float* d, uint64_t da, uint64_t db) {
  asm volatile("wgmma.mma_async.sync.aligned.m64n16k16.f32.bf16.bf16 " R8 ", %8, %9, %10, 1, 1, 1, 1;"
    : ACC8(d) : "l"(da), "l"(db), "n"(SD));
}
template <int SD, uint64_t DA, uint64_t DB> __device__ __forceinline__ void wg_ss16o(float* d, uint32_t oa, uint32_t ob) {
  asm volatile("{.reg .b32 x, y; .reg .b64 a, b; add.u32 x, %8, %10; add.u32 y, %9, %12; mov.b64 a, {x, %11}; mov.b64 b, {y, %13};\n"
               "wgmma.mma_async.sync.aligned.m64n16k16.f32.bf16.bf16 " R8 ", a, b, %14, 1, 1, 1, 1;}"
    : ACC8(d) : "r"(oa), "r"(ob), "n"((uint32_t)DA), "n"((uint32_t)(DA >> 32)), "n"((uint32_t)DB), "n"((uint32_t)(DB >> 32)), "n"(SD));
}
template <int SD> __device__ __forceinline__ void wg_rs64(float* d, const uint32_t* a, uint64_t db) {
  asm volatile("wgmma.mma_async.sync.aligned.m64n64k16.f32.bf16.bf16 " R32 ", {%32,%33,%34,%35}, %36, %37, 1, 1, 0;"
    : ACC32(d) : "r"(a[0]), "r"(a[1]), "r"(a[2]), "r"(a[3]), "l"(db), "n"(SD));
}
template <int SD> __device__ __forceinline__ void wg_ss64(float* d, uint64_t da, uint64_t db) {
  asm volatile("wgmma.mma_async.sync.aligned.m64n64k16.f32.bf16.bf16 " R32 ", %32, %33, %34, 1, 1, 1, 0;"
    : ACC32(d) : "l"(da), "l"(db), "n"(SD));
}
#define WG_RSO(NAME, SHAPE, REGS, ACC, A, TB) \
template <int SD, uint64_t DB> __device__ __forceinline__ void NAME(float* d, uint32_t a0, uint32_t a1, uint32_t a2, uint32_t a3, uint32_t ob) { \
  asm volatile("{.reg .b64 b; mov.b64 b, {" A(4) ", " A(5) "};\nwgmma.mma_async.sync.aligned." SHAPE ".f32.bf16.bf16 " REGS \
               ", {" A(0) "," A(1) "," A(2) "," A(3) "}, b, " A(6) ", 1, 1, " TB ";}" \
    : ACC(d) : "r"(a0), "r"(a1), "r"(a2), "r"(a3), "r"(ob + (uint32_t)DB), "n"((uint32_t)(DB >> 32)), "n"(SD)); \
}
#define ACC4(d) "+f"(d[0]), "+f"(d[1]), "+f"(d[2]), "+f"(d[3])
#define ACC16(d) ACC8(d), ACC8((d + 8))
#define OP4(i) OP4_##i
#define OP4_0 "%4"
#define OP4_1 "%5"
#define OP4_2 "%6"
#define OP4_3 "%7"
#define OP4_4 "%8"
#define OP4_5 "%9"
#define OP4_6 "%10"
#define OP16(i) OP16_##i
#define OP16_0 "%16"
#define OP16_1 "%17"
#define OP16_2 "%18"
#define OP16_3 "%19"
#define OP16_4 "%20"
#define OP16_5 "%21"
#define OP16_6 "%22"
#define OP32(i) OP32_##i
#define OP32_0 "%32"
#define OP32_1 "%33"
#define OP32_2 "%34"
#define OP32_3 "%35"
#define OP32_4 "%36"
#define OP32_5 "%37"
#define OP32_6 "%38"
WG_RSO(wg_rs8o, "m64n8k16", "{%0,%1,%2,%3}", ACC4, OP4, "1")
#define R16 "{%0,%1,%2,%3,%4,%5,%6,%7,%8,%9,%10,%11,%12,%13,%14,%15}"
WG_RSO(wg_rs32o, "m64n32k16", R16, ACC16, OP16, "1")
WG_RSO(wg_rs64o, "m64n64k16", R32, ACC32, OP32, "0")
WG_RSO(wg_rs32k, "m64n32k16", R16, ACC16, OP16, "0")
template <uint64_t DA, uint64_t DB> __device__ __forceinline__ void wg_ss32k(float* d, uint32_t ob) {
  asm volatile("{.reg .b64 b; mov.b64 b, {%17, %18};\nwgmma.mma_async.sync.aligned.m64n32k16.f32.bf16.bf16 " R16 ", %16, b, 1, 1, 1, 1, 0;}"
    : ACC16(d) : "l"(DA), "r"(ob + (uint32_t)DB), "n"((uint32_t)(DB >> 32)));
}
template <int N> __device__ __forceinline__ void reg_inc() { asm volatile("setmaxnreg.inc.sync.aligned.u32 %0;" :: "n"(N)); }
template <int N> __device__ __forceinline__ void reg_dec() { asm volatile("setmaxnreg.dec.sync.aligned.u32 %0;" :: "n"(N)); }
__device__ __forceinline__ void cluster_sync() {
  asm volatile("barrier.cluster.arrive.relaxed.aligned;\nbarrier.cluster.wait.aligned;" ::: "memory");
}

template <int KS>
__device__ __forceinline__ void load_frags(uint32_t* a, uint32_t src) {
  const int lane = threadIdx.x & 31, w = (threadIdx.x >> 5) & 3;
  const int k = ((lane >> 4) << 3) + (lane & 7), u = w * 2 + ((lane >> 3) & 1);
  const uint32_t base = src + k * 128 + ((u ^ (k & 7)) << 4);
#pragma unroll
  for (int ks = 0; ks < KS; ks++) ldsm4t(a[ks * 4], a[ks * 4 + 1], a[ks * 4 + 2], a[ks * 4 + 3], base + ks * 2048);
}

__device__ __forceinline__ uint32_t badd2(uint32_t a, uint32_t b) { uint32_t r; asm("add.rn.bf16x2 %0, %1, %2;" : "=r"(r) : "r"(a), "r"(b)); return r; }
__device__ __forceinline__ uint32_t bsub2(uint32_t a, uint32_t b) { uint32_t r; asm("sub.rn.bf16x2 %0, %1, %2;" : "=r"(r) : "r"(a), "r"(b)); return r; }
__device__ __forceinline__ uint32_t bmul2(uint32_t a, uint32_t b) { uint32_t r; asm("mul.rn.bf16x2 %0, %1, %2;" : "=r"(r) : "r"(a), "r"(b)); return r; }
__device__ __forceinline__ uint32_t bfma2(uint32_t a, uint32_t b, uint32_t c) { uint32_t r; asm("fma.rn.bf16x2 %0, %1, %2, %3;" : "=r"(r) : "r"(a), "r"(b), "r"(c)); return r; }
template <int R> __device__ __forceinline__ void layernorm9(const uint32_t* x, uint32_t* o) {
  const uint32_t ones = 0x3F803F80u;
  float a[R][3][4], q[R], s[R];
#pragma unroll
  for (int i = 0; i < 9 * R; i++) {
    float* d = a[i % R][i / R % 3];
    if (i < 3 * R) d[0] = d[1] = d[2] = d[3] = 0.f;
    mma8(d, x[i % R * 9 + i / R], ones, x[i % R * 9 + i / R]);
  }
#pragma unroll
  for (int r = 0; r < R; r++) {
    q[r] = threadIdx.x & 4 ? a[r][0][1] + a[r][1][1] + a[r][2][1] : a[r][0][0] + a[r][1][0] + a[r][2][0];
    s[r] = (a[r][0][2] + a[r][0][3]) + (a[r][1][2] + a[r][1][3]) + (a[r][2][2] + a[r][2][3]);
  }
#pragma unroll
  for (int r = 0; r < R; r++) { q[r] += __shfl_xor_sync(~0u, q[r], 4); s[r] += __shfl_xor_sync(~0u, s[r], 1); }
#pragma unroll
  for (int r = 0; r < R; r++) { q[r] += __shfl_xor_sync(~0u, q[r], 9); s[r] += __shfl_xor_sync(~0u, s[r], 2); }
#pragma unroll
  for (int r = 0; r < R; r++) q[r] = __shfl_sync(~0u, q[r], 0) + __shfl_sync(~0u, q[r], 18);
#pragma unroll
  for (int r = 0; r < R; r++) {
    const float mean = s[r] * (1.f / DM), var = fmaxf(fmaf(q[r], 1.f / DM, -mean * mean), 0.f);
    float sd;
    asm("sqrt.approx.ftz.f32 %0, %1;" : "=f"(sd) : "f"(bf_lo(pack2(bf_lo(pack2(var, 0.f)) + 1e-5f, 0.f))));
    const float inv = rcp(bf_lo(pack2(sd, 0.f)));
    const uint32_t mb = pack2(mean, mean), hi = pack2(inv, inv), lo = pack2(inv - bf_lo(hi), inv - bf_lo(hi));
#pragma unroll
    for (int i = r * 9; i < r * 9 + 9; i++) {
      const uint32_t d = bsub2(x[i], mb);
      o[i] = bfma2(d, hi, bmul2(d, lo));
    }
  }
}
__device__ __forceinline__ void store_ln_row(int layer, int tok, const uint32_t* o) {
  const int lane = threadIdx.x & 31, r = tok & 31;
  unsigned char* p = g_lnimg + (size_t)(layer * NSEG + (tok >> 5)) * (9 * 4096) + r * 128 + (((lane >> 2) ^ (r & 7)) << 4) + (lane & 3) * 4;
#pragma unroll
  for (int i = 0; i < 9; i++) *(uint32_t*)(p + i * 4096) = o[i];
}
struct Params { CUtensorMap map[11]; const bf16 *X, *K, *V, *shift, *Hk, *Dk, *mem0, *Wq, *Wk, *Wv, *Wo; bf16* out; uint32_t dly[24]; };
#define PACE P.dly[20]
#define S1G P.dly[21]
#define S1DLY P.dly[22]
#define DLYS P.dly[0]
#define DLYW P.dly[1]
#define KLATE P.dly[2]
#define DLYQ P.dly[3]
#define DLYK P.dly[4]
#define DLYG P.dly[5]
#define KWIN P.dly[6]
#define KMIN P.dly[7]
uint32_t h_dly[24] = {900, 350, 100, 60, 3570, 4120, 2750, 1300, 1600, 1690, 1800, 2120, 2250, 2380, 2950, 3060, 3230, 3380, 3530, 7500, 165, 12000, 18000, 4000};

constexpr uint32_t C_W = 0, C_M = 147456, C_KV = C_M + 18432, C_OS = C_KV + 24576, C_QM = C_KV + 32768, C_KM = C_QM + 2048,
                   C_VM = C_KM + 2048, C_OI = C_VM + 2048, C_SX = C_OI + 4096, C_KM2 = C_SX + 2560, C_VM2 = C_KM2 + 128,
                   C_KV2 = C_KM2 + 2048, C_Q = C_KV2 + 8192, C_BAR = C_Q + 8192;
constexpr uint32_t CB_FULL = C_BAR, CB_REF = C_BAR + 16, CB_SX = C_BAR + 32, CB_OX = C_BAR + 40, CB_XX = C_BAR + 48, CB_Q = C_BAR + 56, C_BAD = C_BAR + 64, W_BAR = C_BAR + 80, T_BAR = W_BAR + 24, S_GEN = C_BAR + 128, C_REF = C_BAR + 132, CB_VF = C_BAR + 144, CB_M = C_BAR + 160, CB_MV = C_BAR + 200;
constexpr uint32_t G_W = 0, G_RING = 147456, G_W2 = G_RING + 9 * 8192, G_BAR = G_W2 + 8192;
constexpr uint32_t O_W = 0, O_RING = 3 * 40960, O_ST = O_RING + 11 * 8192, O_BAR = O_ST + 16384, OB_ST = O_BAR + 64;
constexpr uint32_t F_A = 0, F_XY = 36864, F_L = F_XY + 36864, F_X = F_L + 18432, F_Y = F_L + 2 * 36864, F_BAR = C_BAR;
constexpr uint32_t SMEM_BYTES = C_BAR + 256;
static_assert(G_BAR + 256 <= SMEM_BYTES && O_BAR + 256 <= SMEM_BYTES && F_BAR + 16 <= SMEM_BYTES && SMEM_BYTES <= 232448, "smem map");
enum { B_INIT = 1, B_M, B_QK, B_S, B_V, B_O, B_X, B_WG0, B_WG1, B_WG2, B_G, B_OE, B_T, B_R };

__device__ __forceinline__ uint4 pack_partial(const float* d, uint32_t tag) {
  uint32_t x;
  asm("lop3.b32 %0, %1, 1, %2, 0xb8;" : "=r"(x) : "r"(pack2(d[0], d[1])), "r"(tag));
  return make_uint4(x, pack2(d[4], d[5]), pack2(d[2], d[3]), pack2(d[6], d[7]));
}
__device__ __forceinline__ void store_partial(uint4* p, const uint4& v) { st_b128(p, v.x, v.y, v.z, v.w); }
__device__ __forceinline__ void gather_reduce(const uint32_t* p, uint32_t* dst, uint32_t m0, bool shared, uint32_t tag, uint32_t lane, uint32_t sb, int n, int TS0) {
  int tries = 0;
  bool bad;
  TR(TS0);
  do {
    uint2 x[8];
#pragma unroll
    for (int i = 0; i < 8; i++)
      asm volatile("{.reg .b64 v; ld.relaxed.gpu.global.b64 v, [%2]; mov.b64 {%0, %1}, v;}" : "=r"(x[i].x), "=r"(x[i].y) : "l"(p + i * 128) : "memory");
    spin_guard(tries);
    float a = bf_lo(x[0].x), b = bf_hi(x[0].x), c = bf_lo(x[0].y), d = bf_hi(x[0].y);
    uint32_t t = x[0].x ^ tag;
#pragma unroll
    for (int i = 1; i < 8; i++) {
      a += bf_lo(x[i].x); b += bf_hi(x[i].x); c += bf_lo(x[i].y); d += bf_hi(x[i].y);
      asm("lop3.b32 %0, %0, %1, %2, 0xf6;" : "+r"(t) : "r"(x[i].x), "r"(tag));
    }
    bad = __any_sync(~0u, t & ~lane & 1);
    const bool up = lane & 8;
    float u = (up ? c : a) + __shfl_xor_sync(~0u, up ? a : c, 8), v = (up ? d : b) + __shfl_xor_sync(~0u, up ? b : d, 8);
    if (shared) { u += __shfl_xor_sync(~0u, u, 4); v += __shfl_xor_sync(~0u, v, 4); }
    u += __shfl_xor_sync(~0u, u, 16);
    v += __shfl_xor_sync(~0u, v, 16);
    st_relaxed_if(dst, n < LAG && up ? m0 : pack2(u, v), !bad);
  } while (bad);
  TR(TS0 + 3); TRV(TS0 + 2, tries);
  CNT((TS0 - 16) >> 2, tries);
}
__device__ __forceinline__ uint32_t sent_bad(const uint4& v) { return max(max(v.x, v.y), max(v.z, v.w)) == SENT; }

__host__ __device__ constexpr int o_ks(int s) { return s & (s < 8 ? 3 : 7); }
__host__ __device__ constexpr bool o_reg(int s) { return s < 8 ? (s & 3) != 3 : !(s & 1); }
__host__ __device__ constexpr int o_slot(int s) { return s < 8 ? (o_reg(s) ? s - (s >> 2) : s >> 2) : s & 1 ? (s - 5) >> 1 : (s + 4) >> 1; }
__device__ __forceinline__ int g_unit(int wg) {
  const int i = bid() - N_CHAIN;
  return i < 32 ? wg * 64 + i : 2 * i - 32 + wg;
}
__device__ __forceinline__ uint32_t pinned(uint32_t v) { return __shfl_sync(~0u, v, threadIdx.x & 31); }
template <class T> __device__ __forceinline__ T* pinned(T* p) { return (T*)__shfl_sync(~0u, (unsigned long long)p, threadIdx.x & 31); }
enum { CHAIN, GROLE, OROLE };
template <int ROLE, bool SYNC> __device__ __forceinline__ void load_box(const Params& P, uint32_t sb, bool regs, int wg, int i, uint32_t mb, bool on) {
  const int b = bid();
  int map, col = 0, ks = 0, c2 = 0, c3 = 0;
  uint32_t dst = wg * 73728;
  if (ROLE == CHAIN) {
    const int k = i - 1, st = regs ? (k < 6 ? k + k / 3 : 2 * k - 4) : k < 2 ? 4 * k + 3 : 2 * k + 5;
    dst += i ? (17 + i) * 2048 : 0;
    if (wg || i == 0) { map = wg + i; col = b * 64; c3 = !regs; }
    else if (!regs && k >= 14) { map = 6; ks = b * 4 + k - 14; }
    else { map = 6; col = 64 + (st < 8 ? (st >> 2) * 64 : (st >> 3) * 128 + (b & 1) * 64); ks = (b * 4) ^ o_ks(st); }
  } else if (ROLE == GROLE) {
    const int q = g_unit(wg);
    map = ((q >> 5) + 1) % 3;
    if (i) { map += 3; col = (q & 31) * 128 + (i - 1) * 64; ks = 34; dst = G_W2 + wg * 4096 + (i - 1) * 2048; }
    else { map += 8; c2 = (q & 31) * 2; c3 = !regs; }
  } else {
    const int o = b - N_CHAIN - N_G, ksl = o / 3;
    map = 7; col = ((o % 3) * 3 + (wg + ksl) % 3) * 64; dst = (wg * (regs ? 24 : 20) + i) * 2048;
    ks = (ksl * 11 - max(ksl - 4, 0)) * 4 + (regs ? i / 3 * 5 + i % 3 * 2 : i < 16 ? i / 2 * 5 + 1 + i % 2 * 2 : i + 24);
    c3 = (ks & 1) * 2; ks >>= 1;
  }
  if (SYNC) { col = pinned(col); ks = pinned(ks); bar_sync(B_WG0 + wg, 256); }
  if (on) asm volatile("cp.async.bulk.tensor.5d.shared::cluster.global.tile.mbarrier::complete_tx::bytes [%0], [%1, {%2, %3, %4, %5, %6}], [%7];"
               :: "r"(sb + dst), "l"(&P.map[map]), "r"(col), "r"(0), "r"(c2), "r"(c3), "r"(ks), "r"(mb) : "memory");
}
template <int ROLE, bool SYNC = false> __device__ __forceinline__ void load_wg(const Params& P, uint32_t sb, bool regs, int wg, int quarter) {
  const int i = (threadIdx.x & 31) * 4 + quarter;
  const int n = ROLE == CHAIN ? 36 : ROLE == GROLE ? (regs ? 38 : 36) : regs ? 24 : bid() < N_CHAIN + N_G + 12 ? 20 : 16;
  load_box<ROLE, SYNC>(P, sb, regs, wg, i, sb + W_BAR + wg * 8, i < (ROLE == CHAIN ? (wg ? 2 : 19) : ROLE == GROLE ? n - 35 : n));
  if (i == 0) mbar_expect(sb + W_BAR + wg * 8, n * 2048);
  __syncwarp();
}
__device__ __forceinline__ uint32_t near_half(uint32_t blk, uint32_t reader) {
  return __ldcg(g_near + (blk >> 3)) ^ (~blk & 1) ^ __ldcg(g_side + (blk >> 3)) ^ __ldcg(g_side + reader);
}

__device__ __forceinline__ uint32_t opaque_tid() { uint32_t t; asm volatile("mov.u32 %0, %%tid.x;" : "=r"(t)); return t; }
__device__ __forceinline__ void m_fetch(uint32_t sb, uint32_t src, uint32_t b, uint32_t mb) {
  bulk_load(sb + C_M + (b ? b * 4096 - 2048 : 0), (const unsigned char*)g_mimg + ((src ^ ((b & 1) * 4096)) + b * 8192), b ? 4096 : 2048, mb);
}
__device__ __forceinline__ uint32_t m_probe(uint32_t lane) { return lane * 32 + (lane & 4) * 4 + (lane >> 3) * 4; }
__device__ __forceinline__ uint32_t m_max(uint32_t a, uint32_t b) {
  return max(max(lds32(a), lds32(a + 1024)), max(lds32(b), lds32(b + 1024)));
}
template <int S0, int N> __device__ __forceinline__ void o_steps(float* d, const uint32_t* a) {
  constexpr int SD = o_ks(S0) != 0;
  if constexpr (o_reg(S0)) wg_rs16<SD>(d, a + (18 + o_slot(S0)) * 4, desc_n16(C_OI + o_ks(S0) * 512));
  else wg_ss16<SD>(d, desc_sw128(C_W + (18 + o_slot(S0)) * 2048), desc_n16(C_OI + o_ks(S0) * 512));
  if constexpr (N > 1) o_steps<S0 + 1, N - 1>(d, a);
}
template <int BASE, int KS, int N> __device__ __forceinline__ void m_steps(float* d, const uint32_t* a, uint32_t oa) {
  wg_rs16<KS != 0>(d, a + (BASE + KS / 2) * 4, desc_m(C_M + KS * 512));
  if constexpr (KS >= 36 - 2 * XR) wg_rs16<1>(d, a + (18 + XR + KS / 2) * 4, desc_m(C_M + KS * 512 + 512));
  else wg_ss16o<1, desc_sw128(C_W + (BASE + KS / 2) * 2048), desc_m(C_M + KS * 512 + 512)>(d, oa, 0);
  if constexpr (N > 2) m_steps<BASE, KS + 2, N - 2>(d, a, oa);
}

template <int I, int R, int S> __device__ __forceinline__ void v_steps(float* d, const uint32_t* a) {
  constexpr bool reg = (VPAT >> I) & 1;
  if constexpr (reg) wg_rs16<1>(d, a + (18 + R) * 4, desc_m(C_M + R * 1024));
  else wg_ss16<1>(d, desc_sw128(C_W + (54 + S) * 2048), desc_m(C_M + S * 1024 + 512));
  if constexpr (I < 31) v_steps<I + 1, R + reg, S + !reg>(d, a);
  else static_assert(R + reg == 18, "pattern");
}

__device__ __forceinline__ void chain_proj(const Params& P, uint32_t sb) {
  const uint32_t c = chain_id(), h = c >> 1, j = c & 1, wid = __shfl_sync(~0u, threadIdx.x >> 5, 0), wg = wid >> 2, w = wid & 3;
  const uint32_t t = threadIdx.x & 127, lane = pinned(t & 31), mine = pinned(sb + t * 16), rb = mapa(sb, j ^ 1);
  const uint32_t theirs = pinned(rb + C_KM2 + w * 512 + lane * 4), oa = wg * 4608;
  uint32_t a[144 + 4 * XR];
  mbar_wait(sb + W_BAR + wg * 8, 0);
  if (threadIdx.x == 0) TS(23);
  load_frags<36>(a, sb + C_W + wg * 73728);
  fence_async_smem();
  bar_arrive(B_WG0 + wg, 256);
  if (threadIdx.x == 0) TS(24);
  bar_sync(B_WG2, 384);
  const uint32_t round = min(w, 2u) + (wg ? 0 : 3), gdly = P.dly[8 + round], ps = t >> 2, pf = j * 16 + (ps >> 1);
  uint4* const dsts = pinned(g_xb + (ps * 4096 + near_half(ps * 8, ps * 2) * 256 + c * 4 + (t & 3)));
  uint4* const dstf = pinned(g_xb + (pf * 4096 + 512 + near_half(pf * 8 + 1, pf * 2) * 256 + h * 8 + (t & 7)));
  const uint32_t* const gsrc = (const uint32_t*)g_xb + (h * 16384 + min(w, 2u) * 4096 + near_half(h * 8 + !wg, h * 2) * 1024 +
                               (wg ? (lane & 28) * 4 + j * 8 + (lane & 3) * 2 : 2048 + (lane & 24) * 4 + j * 16 + (lane & 7) * 2));
  uint32_t* gdst = g_mimg + (16384 + (lane >> 4) * 1024 + (lane & 1) * 8 +
                   (wg ? (round ? 1536 + round * 512 : 0) + h * 16 + (((lane >> 1) ^ c) & 4) + j * 2 + ((lane >> 1) & 1)
                       : (round - 1) * 2048 + c * 16 + (((lane >> 1) ^ (c * 2)) & 4) + ((lane >> 1) & 3)));
  const uint32_t m0 = __ldcg(gdst - 16384);
  mbar_wait(sb + W_BAR + wg * 8, 1);
  load_frags<XR>(a + 144, sb + C_W + wg * 73728 + (18 - XR) * 2048);
  bar_sync(B_INIT, 256);
  if ((threadIdx.x & 127) == 0) TS(4);

  uint32_t ring = 1;
#pragma unroll 1
  for (int n = 0; n < STEPS; n++) {
    float d[8], e[8];
#pragma unroll
    for (int i = 0; i < 8; i++) e[i] = 0.f;
    uint32_t redo = n + 1;
#pragma unroll 1
    do {
      mbar_wait(sb + CB_M, n & 1);
      wg_fence();
      m_steps<0, 0, 4>(d, a, oa);
      wg_commit();
      if (wg) { wg_fence(); m_steps<18, 0, 4>(e, a, 4608); wg_commit(); }
      if (wid == 0) TR(8);
      mbar_wait(sb + CB_M + 8, n & 1);
      wg_fence();
      m_steps<0, 4, 8>(d, a, oa);
      wg_commit();
      mbar_wait(sb + CB_MV, n & 1);
      asm volatile("{.reg .pred p; .reg .u32 t; ld.shared.u32 t, [%1]; setp.eq.u32 p, t, %0; selp.u32 %0, -1, 0, p;}" : "+r"(redo) : "r"(sb + C_BAD) : "memory");
    } while (redo);
    wg_fence();
    m_steps<0, 12, 8>(d, a, oa);
    wg_commit();
    mbar_wait(sb + CB_MV + 16, n & 1);
    wg_fence();
    m_steps<0, 20, 8>(d, a, oa);
    wg_commit();
    mbar_wait(sb + CB_MV + 24, n & 1);
    wg_fence();
    m_steps<0, 28, 8>(d, a, oa);
    wg_commit();
    wg_wait<0>();
    if (w == 0) TR(6 + wg);
    const uint32_t f0 = pack2(d[0], d[1]), f1 = pack2(d[4], d[5]), f2 = pack2(d[2], d[3]), f3 = pack2(d[6], d[7]);
    stsm4(mine + C_QM + wg * 2048, f0, f1, f2, f3);
    bar_arrive(B_QK, 416);
    const uint32_t tag = (n & 1) ^ 1;
    if (wg) {
      if (n + 1 < STEPS) bar_sync(B_S, 256);
      wg_fence();
      v_steps<0, 2, 2>(e, a);
      wg_commit();
      const uint32_t k0 = j ? f0 : f1, k1 = j ? f2 : f3;
      wg_wait<0>();
      if (w == 0) TR(11);
      const uint32_t v0 = pack2(e[0], e[1]), v1 = pack2(e[4], e[5]), v2 = pack2(e[2], e[3]), v3 = pack2(e[6], e[7]);
      stsm4(mine + C_VM, v0, v1, v2, v3);
      bar_arrive(B_V, 256);
      st_async1(theirs, k0, rb + CB_XX);
      st_async1(theirs + 256, k1, rb + CB_XX);
      st_async1(theirs + 128, j ? v0 : v1, rb + CB_XX);
      st_async1(theirs + 384, j ? v2 : v3, rb + CB_XX);
      if (n + 1 == STEPS) break;
      bar_sync(B_O, 256);
      if (!WFENCE) fence_async_smem();
      wg_fence();
#pragma unroll
      for (int ks = 0; ks < 4; ks++) {
        if (ks == 0) wg_ss16<0>(d, desc_sw128(C_W + 32 * 2048), desc_n16(C_OI));
        else wg_ss16<1>(d, desc_sw128(C_W + (32 + ks) * 2048), desc_n16(C_OI + ks * 512));
      }
      wg_commit();
      bar_arrive(B_X, 256);
      if (w == 0) TR(0);
      wg_wait<0>();
      store_partial(dsts, pack_partial(d, tag));
      bar_arrive(B_M, 160);
      if (w == 0) TR(1);
    } else {
      if (n + 1 == STEPS) break;
      bar_sync(B_X, 256);
      wg_fence();
      o_steps<0, 4>(d, a);
      wg_commit();
      o_steps<4, 4>(e, a);
      wg_commit();
      wg_wait<1>();
      store_partial(dsts + 1024, pack_partial(d, tag));
      if (w == 0) TR(2);
      if (OGAP == 0) { wg_fence(); o_steps<8, 4>(d, a); wg_commit(); wg_wait<1>(); } else wg_wait<0>();
      store_partial(dsts + 2048, pack_partial(e, tag));
      if (w == 0) TR(3);
      wg_fence();
      if (OGAP) o_steps<8, 4>(d, a);
      if (OGAP < 2) o_steps<16, 4>(e, a);
      wg_commit();
      bar_sync(B_T, 256);
      if (w == 0) { TRV(61, 0); TR(12); }
      wg_fence();
      o_steps<12, 4>(d, a);
      wg_commit();
      if (OGAP == 2) o_steps<16, 4>(e, a);
      o_steps<20, 4>(e, a);
      wg_commit();
      wg_wait<1>();
      store_partial(dstf, pack_partial(d, tag));
      if (w == 0) TR(4);
      wg_fence();
      o_steps<24, 8>(d, a);
      wg_commit();
      wg_wait<1>();
      store_partial(dstf + 1024, pack_partial(e, tag));
      bar_arrive(B_OE, 256);
      if (w == 0) TR(5);
      wg_wait<0>();
      store_partial(dstf + 2048, pack_partial(d, tag));
      if (w == 0) TR(15);
    }
    if (w < 3) {
      mbar_wait(sb + CB_REF, n & 1);
      wait_until(lds32(sb + C_REF), gdly);
      gather_reduce(gsrc, gdst, m0, wg, tag, lane, sb, n, 16 + round * 4);
      if (++ring == MRING) { ring = 0; gdst -= MRING * 16384; }
      gdst += 16384;
    }
  }
}

template <int KS> __device__ __forceinline__ void x_scores(float* s, float* sm, const uint4* q, uint32_t ok, uint32_t om) {
  wg_rs32o<1, desc_sw64(C_KV + KS * 1024)>(s, q[KS].x, q[KS].y, q[KS].z, q[KS].w, ok);
  wg_rs8o<1, desc_n16(C_KM + KS * 512)>(sm, q[KS].x, q[KS].y, q[KS].z, q[KS].w, om);
  if constexpr (KS < 3) x_scores<KS + 1>(s, sm, q, ok, om);
}

__device__ __forceinline__ void chain_attn(const Params& P, uint32_t sb) {
  const int c = chain_id(), j = c & 1;
  const int tid = threadIdx.x, lane = tid & 31, w = __shfl_sync(~0u, (tid >> 5) & 3, 0);
  const int l = w >> 1, u = w & 1;
  const uint32_t rb = mapa(sb, j ^ 1);
  const float sc = 0.08838834764831845f * 1.4426950408889634f;
  const uint32_t ones = 0x3F803F80u;
  const uint32_t km_off = C_KM + (lane >> 3) * 256 + l * 128 + (lane & 7) * 16;
  const uint32_t qm_off = C_QM + (lane >> 4) * 256 + l * 128 + (lane & 7) * 16;
  const uint32_t kv_off = C_KV + l * 4096 + (lane & 15) * 64 + (((lane >> 4) ^ (u * 2) ^ ((lane >> 1) & 3)) << 4);

  load_wg<CHAIN, true>(P, sb, false, 1, w);
  if (lane == 0) mbar_arrive(sb + CB_M);
#pragma unroll 1
  for (int n = 0; n < STEPS; n++) {
    const uint32_t kvb = sb + kv_off + (n & 1) * 16384;
    if (w == 0 && elect()) { mbar_expect(sb + CB_SX, 2560); mbar_expect(sb + CB_OX, 2048); mbar_expect(sb + CB_XX, 2048); }
    mbar_wait(sb + CB_FULL + (n & 1) * 8, (n >> 1) & 1);
    if (n < 3 && tid == 256) TS(n ? 20 + n : 5);
    __syncwarp();
    {
      uint32_t km[8];
      uint4 kx[8];
#pragma unroll
      for (int i = 0; i < 8; i++) ldsm4t(kx[i].x, kx[i].y, kx[i].z, kx[i].w, (kvb ^ ((i & 1) * 32)) + (i >> 1) * 1024);
      mbar_wait(sb + CB_VF, n & 1);
      if (w == 1) TRD(60, kx[7].x);
      bar_sync(B_QK, 416);
      if (n + 1 == STEPS) {
        bar_sync(B_V, 256);
      } else {
      uint32_t qm[16];
#pragma unroll
      for (int ks = 0; ks < 4; ks++) ldsm4t(qm[4 * ks], qm[4 * ks + 1], qm[4 * ks + 2], qm[4 * ks + 3], sb + qm_off + ks * 512);
      ldsm4t(km[0], km[1], km[2], km[3], sb + km_off);
      ldsm4t(km[4], km[5], km[6], km[7], sb + km_off + 1024);
      float s[5][4];
      uint4 vx[4];
#pragma unroll
      for (int i = 0; i < 5; i++) { s[i][0] = s[i][1] = s[i][2] = s[i][3] = 0.f; }
#pragma unroll
      for (int ks = 0; ks < 4; ks++) {
        const uint32_t* q = qm + 4 * ks;
        if (ks == 1 || ks == 2) {
#pragma unroll
          for (int i = 2 * ks - 2; i < 2 * ks; i++) ldsm4(vx[i].x, vx[i].y, vx[i].z, vx[i].w, ((sb + kv_off) ^ ((i & 1) * 32)) + 8192 + (2 * u + (i >> 1)) * 1024);
        }
        mma16(s[1], q[0], q[1], q[2], q[3], kx[2 * ks].x, kx[2 * ks].y);
        mma16(s[2], q[0], q[1], q[2], q[3], kx[2 * ks].z, kx[2 * ks].w);
        mma16(s[0], q[0], q[1], q[2], q[3], km[2 * ks], km[2 * ks + 1]);
        mma16(s[3], q[0], q[1], q[2], q[3], kx[2 * ks + 1].x, kx[2 * ks + 1].y);
        mma16(s[4], q[0], q[1], q[2], q[3], kx[2 * ks + 1].z, kx[2 * ks + 1].w);
      }
      const uint32_t sx = C_SX + l * 1280;
      st_async4(rb + sx + u * 512 + lane * 16, s[1][0], s[1][1], s[2][0], s[2][1], rb + CB_SX);
      st_async1(rb + sx + 1024 + u * 128 + lane * 4, __float_as_uint(u ? s[0][1] : s[0][0]), rb + CB_SX);
      bar_arrive_after<B_S, 256>(__float_as_uint(s[3][0]), __float_as_uint(s[4][0]));
      mbar_wait(sb + CB_SX, n & 1);
      const uint4 p0 = lds128(sb + sx + u * 512 + lane * 16), p1 = lds128(sb + sx + (u ^ 1) * 512 + lane * 16);
      const uint2 p2 = make_uint2(lds32(sb + sx + 1024 + lane * 4), lds32(sb + sx + 1152 + lane * 4));
      float t[10] = {s[0][0] + __uint_as_float(p2.x), s[0][1] + __uint_as_float(p2.y),
                     s[1][0] + __uint_as_float(p0.x), s[1][1] + __uint_as_float(p0.y),
                     s[2][0] + __uint_as_float(p0.z), s[2][1] + __uint_as_float(p0.w),
                     s[3][0] + __uint_as_float(p1.x), s[3][1] + __uint_as_float(p1.y),
                     s[4][0] + __uint_as_float(p1.z), s[4][1] + __uint_as_float(p1.w)};
      float mx = fmaxf(fmaxf(fmaxf(fmaxf(t[2], t[3]), fmaxf(t[4], t[5])), fmaxf(fmaxf(t[6], t[7]), fmaxf(t[8], t[9]))), fmaxf(t[0], t[1]));
      mx = fmaxf(fmaxf(mx, __shfl_xor_sync(~0u, mx, 1)), fmaxf(__shfl_xor_sync(~0u, mx, 2), __shfl_xor_sync(~0u, mx, 3)));
      const float ms = -mx * sc;
#pragma unroll
      for (int i = 0; i < 10; i++) t[i] = ex2(fmaf(t[i], sc, ms));
      uint32_t p[5];
#pragma unroll
      for (int i = 0; i < 5; i++) p[i] = pack2(t[2 * i], t[2 * i + 1]);
      p[1] |= (p[0] & p[3] & p[4]) & 0x80008000u;
      float o[2][4], z[4] = {0.f, 0.f, 0.f, 0.f};
      mma16(z, ones, ones, ones, ones, p[1], p[2]);
#pragma unroll
      for (int i = 0; i < 2; i++) {
        o[i][0] = o[i][1] = o[i][2] = o[i][3] = 0.f;
        mma16(o[i], vx[2 * i].x, vx[2 * i].y, vx[2 * i].z, vx[2 * i].w, p[1], p[2]);
      }
      mma16(z, ones, ones, ones, ones, p[3], p[4]);
#pragma unroll
      for (int i = 0; i < 2; i++) mma16(o[i], vx[2 * i + 1].x, vx[2 * i + 1].y, vx[2 * i + 1].z, vx[2 * i + 1].w, p[3], p[4]);
      mma8(z, ones, ones, p[0]);
      bar_sync_after<B_V, 256>(p[1]);
      ldsm4(km[0], km[1], km[2], km[3], sb + km_off + (C_VM - C_KM) + u * 1024);
      mma8(o[0], km[0], km[1], p[0]);
      mma8(o[1], km[2], km[3], p[0]);
      const float i0 = rcp(z[0]), i1 = rcp(z[1]);
      const uint32_t oo = C_OI + u * 1024 + l * 128 + lane * 4;
      uint32_t ow[4];
#pragma unroll
      for (int i = 0; i < 2; i++) { ow[2 * i] = pack2(o[i][0] * i0, o[i][1] * i1); ow[2 * i + 1] = pack2(o[i][2] * i0, o[i][3] * i1); }
      stsm4(sb + C_OI + u * 1024 + l * 128 + (lane >> 3) * 256 + (lane & 7) * 16, ow[0], ow[1], ow[2], ow[3]);
      if (WFENCE) fence_async_smem();
      bar_arrive(B_O, 256);
#pragma unroll
      for (int i = 0; i < 4; i++) st_async1(rb + oo + 2048 + i * 256, ow[i], rb + CB_OX);
      }
    }
    {
      const uint32_t lane = opaque_tid() & 31, own = ((n & 1) * 16384 + j * 4096) >> 4;
      float s[16], sm[4];
#pragma unroll
      for (int i = 0; i < 16; i++) s[i] = sm[i & 3] = 0.f;
      {
        uint4 q[4];
        mbar_wait(sb + CB_Q, n & 1);
        auto load_q = [&]() {
#pragma unroll
          for (int ks = 0; ks < 4; ks++) q[ks] = lds128(sb + C_Q + (ks >> 1) * 4096 + w * 1024 + (ks & 1) * 512 + lane * 16);
        };
        if (QPOS == 0) load_q();
        mbar_wait(sb + CB_XX, n & 1);
        if (n + 1 < STEPS) mbar_wait(sb + CB_OX, n & 1);
        fence_async_smem();
        if (n + 1 < STEPS) bar_arrive(B_T, 256);
        if (QPOS == 1) load_q();
        if (n + 1 < STEPS) bar_sync(B_OE, 256);
        if (QPOS == 2) load_q();
        if (w == 1) { TRV(61, 0); TR(9); }
#pragma unroll 1
        for (uint32_t hf = 0; hf < 2; hf++) {
          wg_fence();
          x_scores<0>(s, sm, q, hf ? (C_KV2 - C_KV) >> 4 : own, hf ? (C_KM2 - C_KM) >> 4 : j * 8);
          wg_commit();
          wg_wait<0>();
#pragma unroll
          for (int ks = 0; ks < 4; ks++) asm volatile("mov.b32 %0, %1; mov.b32 %2, %3;" : "+r"(q[ks].x), "+r"(q[ks].y), "+r"(q[ks].z), "+r"(q[ks].w));
        }
      }
      const float neg = -1e9f * 11.313708498984761f;
      const int lim = 8 * (w - (int)(lane & 3)) + (int)(lane >> 2);
      float t[10] = {sm[0], sm[1]};
#pragma unroll
      for (int i = 0; i < 8; i++) t[2 + i] = i > lim ? neg : s[(i >> 1) * 4 + (i & 1)];
      float mx = fmaxf(fmaxf(fmaxf(fmaxf(t[2], t[3]), fmaxf(t[4], t[5])), fmaxf(fmaxf(t[6], t[7]), fmaxf(t[8], t[9]))), fmaxf(t[0], t[1]));
      mx = fmaxf(fmaxf(mx, __shfl_xor_sync(~0u, mx, 1)), fmaxf(__shfl_xor_sync(~0u, mx, 2), __shfl_xor_sync(~0u, mx, 3)));
      const float ms = -mx * sc;
#pragma unroll
      for (int i = 0; i < 10; i++) t[i] = ex2(fmaf(t[i], sc, ms));
      uint32_t p[5];
#pragma unroll
      for (int i = 0; i < 5; i++) p[i] = pack2(t[2 * i], t[2 * i + 1]);
      float z = ((t[0] + t[1]) + (t[2] + t[3])) + ((t[4] + t[5]) + (t[6] + t[7])) + (t[8] + t[9]);
      const uint32_t row = sb + C_OS + w * 1024 + (lane >> 2) * 128 + (((lane & 3) ^ (lane >> 2)) << 4);
#pragma unroll 1
      for (uint32_t hf = 0; hf < 2; hf++) {
        float o[32];
        const uint32_t vo = hf ? (C_KV2 + 4096 - C_KV - 8192) >> 4 : j * 256;
        wg_fence();
        wg_rs64o<0, desc_sw64(C_KV + 8192)>(o, p[1], p[1], p[2], p[2], vo);
        wg_rs64o<1, desc_sw64(C_KV + 8192 + 32)>(o, p[3], p[3], p[4], p[4], vo);
        wg_rs64o<1, mkdesc(C_VM, 128, 256, 0)>(o, p[0], p[0], 0, 0, hf ? (C_VM2 - C_VM) >> 4 : j * 8);
        wg_commit();
        if (hf) {
          if (elect()) mbar_arrive(sb + CB_M);
        } else {
          z += __shfl_xor_sync(~0u, z, 1);
          z = rcp(z + __shfl_xor_sync(~0u, z, 2));
        }
        wg_wait<0>();
#pragma unroll
        for (int qq = 0; qq < 2; qq++) {
          const float* r = o + 16 * qq;
          sts128((row ^ (qq * 64)) + hf * 4096,
                 make_uint4(pack2(r[0] * z, r[1] * z), pack2(r[4] * z, r[5] * z), pack2(r[8] * z, r[9] * z), pack2(r[12] * z, r[13] * z)));
        }
      }
      bar_arrive(B_G, 160);
      if (n + 1 < STEPS) bar_arrive(B_R, 160);
      if (w == 1) TR(10);
    }
  }
  if ((threadIdx.x & 127) == 0) TS(6);
}

__device__ __forceinline__ void chain_aux(const Params& P, uint32_t sb) {
  const uint32_t c = chain_id(), j = c & 1, lane = threadIdx.x & 31, w = __shfl_sync(~0u, (threadIdx.x >> 5) & 3, 0);
  load_wg<CHAIN, true>(P, sb, false, 0, w);
  if (threadIdx.x == 384) TS(25);
  if (threadIdx.x == 384) grid_wait(1, lds32(sb + S_GEN));
  bar_sync(B_WG2, 384);
  if (threadIdx.x == 384) TS(13);
  if (w == 0) {
    const uint32_t* fg = g_fl + FL_G + near_half(XB_F, c) * 1024 + (c >> 1) * 8;
#pragma unroll 1
    for (int n = 0; n < STEPS; n++) {
      const unsigned char* blk = g_qkv + (uint32_t)((n % QRING) * (N_CHAIN * 24576));
      const uint32_t t1 = clk(), kb = sb + CB_FULL + (n & 1) * 8, kv = sb + C_KV + (n & 1) * 16384;
      uint32_t t0 = t1 - 100000, x = 0;
      if (n > 0) {
        wait_until(t1, KMIN);
        do asm volatile("ld.relaxed.gpu.global.u32 %0, [%1];" : "=r"(x) : "l"(fg) : "memory"); while (x <= n && clk() - t1 < KWIN);
        if (NOBULK) x = n + 1;
        if (x > n) {
          asm volatile("fence.acquire.gpu;" ::: "memory");
          fence_async_global();
          if (elect()) { mbar_expect(kb, 8192); bulk_load(kv, blk + c * 24576, 8192, kb); }
        }
        T3(0); CNT(12, 1 + (x <= n));
        mbar_wait(sb + CB_REF, (n - 1) & 1);
        t0 = lds32(sb + C_REF);
        wait_until(t0, DLYK - 500);
      }
      if (!NOBULK) wait_flags(fg + min(lane, 2u) * 256, n + 1);
      T3(2);
      fence_async_global();
      if (n > 0) bar_sync(B_R, 160);
      wait_until(t0, DLYK);
      if (elect()) {
        if (x <= n) { mbar_expect(kb, 8192); bulk_load(kv, blk + c * 24576, 8192, kb); }
        mbar_expect(sb + CB_VF, 8192);
        bulk_load(sb + C_KV + 8192, blk + (c * 24576 + 8192), 8192, sb + CB_VF);
        mbar_expect(sb + CB_Q, 16384);
        bulk_load(sb + C_Q, blk + (c * 24576 + 16384), 8192, sb + CB_Q);
        bulk_load(sb + C_KV2, blk + ((c ^ 1) * 24576 + j * 4096), 4096, sb + CB_Q);
        bulk_load(sb + C_KV2 + 4096, blk + ((c ^ 1) * 24576 + 8192 + j * 4096), 4096, sb + CB_Q);
      }
      T3(1);
      T3(3);
    }
  } else {
    const uint32_t near = __ballot_sync(~0u, near_half(XB_M + min(lane, MRING - 1u) * 8, c));
    uint32_t ring = 0;
    if (w > 1) {
      const uint32_t odd = w & 1, chk = pinned(sb + C_M + odd * 2048 + m_probe(lane)), again = sb + CB_MV + 32 + odd * 8;
      const bool one = elect();
      uint32_t mph = 0;
#pragma unroll 1
      for (int n = 0; n <= STEPS; n++) {
#pragma unroll
        for (int k = 0; k < 3; k++) {
          if (n == STEPS || (k == 2 && odd)) break;
          const uint32_t b = 2 * k + odd, at = chk + (k ? k * 8192 - 2048 + odd * 2048 : 0);
          uint32_t mb = sb + CB_M + b * 8, ph = n & 1;
          int it = 1;
          while (true) {
            mbar_wait(mb, ph);
            const bool bad = __any_sync(~0u, (k ? m_max(at, at + 2048) : max(m_max(at, at ^ 8), odd ? m_max(at + 2048, (at ^ 8) + 2048) : 0)) == SENT);
            if (one && !bad) mbar_arrive(sb + CB_MV + (b > 2 ? b * 8 - 8 : 0));
            if (!bad) break;
            mb = again; ph = mph; mph ^= 1;
            if (one) {
              if (k == 0) sts32(sb + C_BAD, n + 1);
              mbar_expect(mb, b ? 4096 : 2048);
              m_fetch(sb, ring * 65536 + ((near >> ring) & 1) * 4096, b, mb);
            }
            __syncwarp();
            spin_guard(it);
          }
          TR(41 + b * 4); CNT(6 + b, it);
        }
        ring = ring + 1 == MRING ? 0 : ring + 1;
        if (!odd) {
          if (n < STEPS) { TRSYNC(); TRDUMP(n - 2); }
        } else {
          unsigned char* o = g_oimg + (uint32_t)(((n - 1) & (RING - 1)) * (N_CHAIN * 8192) + j * 4096);
          if (n > 0) bar_sync(B_G, 160);
          fence_async_smem();
          if (one) {
            if (n > 0) {
              bulk_store(o + c * 8192, sb + C_OS, 4096);
              bulk_store(o + (c ^ 1) * 8192, sb + C_OS + 4096, 4096);
              asm volatile("cp.async.bulk.commit_group;\ncp.async.bulk.wait_group.read 0;" ::: "memory");
              { const int n_ = n - 1; { const int n = n_; T3(4); (void)n; } }
            }
            mbar_arrive(sb + CB_Q);
            if (n > 0) {
              bulk_done_inc(g_fl + FL_O + c);
              { const int n_ = n - 1; { const int n = n_; T3(5); (void)n; } }
            }
          }
          __syncwarp();
        }
      }
    } else {
      const uint32_t* ts = g_fl + FL_SYNC + near_half(XB_F + 1, c) * 1024 + lane * 2;
      uint32_t t0 = clk() - 100000, last = 0;
      int lag = 0;
#pragma unroll 1
      for (int n = 0; n < STEPS; n++) {
        const uint32_t src = ring * 65536 + ((near >> ring) & 1) * 4096;
        if (lane < 5) mbar_expect(sb + CB_M + lane * 8, lane ? 4096 : 2048);
        __syncwarp();
        if (elect()) {
#pragma unroll
          for (int b = 0; b < 5; b++) {
            wait_until(t0, P.dly[14 + b]);
            m_fetch(sb, src, b, sb + CB_M + b * 8);
            TR(40 + b * 4);
          }
        }
        __syncwarp();
        ring = ring + 1 == MRING ? 0 : ring + 1;
        uint32_t va, vb;
        const uint32_t off = timer_offset(), tag = (uint32_t)(n + 1) << 28;
        if (n > 1) lag += (int)(off - last) - (lag >> 2);
        last = off;
        const uint32_t mine = min(max((lag >> 3) + 256, 0), 511);
        bar_sync(B_QK, 416);
        if (n + 1 == STEPS) break;
        sts32(sb + C_REF + 4, 0);
        const uint32_t c0 = clk(), stamp = c0 + off;
        st_relaxed_if(g_fl + FL_SYNC + lane * 1024 + c, tag | (mine << 19) | (stamp & 0x7FFFF), lane < 2);
        TR(13);
        wait_until(c0, DLYS);
        int it = 0;
        do {
          asm volatile("ld.relaxed.gpu.global.v2.u32 {%0,%1}, [%2];" : "=r"(va), "=r"(vb) : "l"(ts) : "memory");
          spin_guard(it);
        } while (__any_sync(~0u, ((va ^ tag) | (vb ^ tag)) >> 28));
        const int late = __reduce_max_sync(~0u, max((int)((va - stamp) << 13), (int)((vb - stamp) << 13))) >> 13;
        const uint32_t fast = min(((__reduce_max_sync(~0u, max(va, vb)) >> 19) & 511) - mine, 100u) * RATE;
        t0 = c0 + min((uint32_t)late, clk() - c0);
        if (elect()) {
          sts32(sb + C_REF, t0 + (fast * 3 >> 2));
          mbar_arrive(sb + CB_REF);
        }
        st_relaxed_if(g_fl + FL_TICK + lane * 1024, (uint32_t)(n + 1) << 24 | ((t0 + off) & 0xFFFFFF), c == 0 && lane < 2);
        t0 += fast * 5 >> 2;
        TRV(59, fast);
        TR(14); CNT(11, it);
        bar_sync(B_M, 160);
      }
    }
  }
}

template <int WG>
__device__ __forceinline__ void g_math(const Params& P, uint32_t sb) {
  const int q = g_unit(WG);
  const int lane = threadIdx.x & 31, w = (threadIdx.x >> 5) & 3;
  const bool isq = q >= 64;
  uint32_t a[136];
  {
    const uint32_t stage = sb + G_W + WG * 73728;
    mbar_wait(sb + W_BAR + WG * 8, 0);
    if (threadIdx.x == 0) TS(23);
    load_frags<34>(a, stage);
    fence_async_smem();
    bar_sync(B_WG0 + WG, 128);
    if (threadIdx.x == 0) TS(24);
    load_wg<GROLE>(P, sb, false, WG, w);
    if (threadIdx.x == 0) TS(25);
    mbar_wait(sb + W_BAR + WG * 8, 1);
  }
  if ((threadIdx.x & 127) == 0) TS(4);
  const uint32_t off0 = (q & 31) * 49152 + (q >> 5) * 8192 +
                        (isq ? (w >> 1) * 4096 + (w & 1) * 512 + lane * 16 : w * 1024 + (lane >> 2) * 64 + (((lane ^ (lane >> 3)) & 3) << 4));
#pragma unroll 1
  for (int n = 0; n < STEPS; n++) {
    float d0[32], d1[32];
    if (WG == 0 && n >= LOCK0) bar_sync(B_OE, 160);
    if (n > 0) bar_sync(B_V + WG, 256);
#pragma unroll
    for (int ch = 0; ch < 9; ch++) {
      mbar_wait(sb + G_BAR + ch * 8, n & 1);
      if (ch == 0) { if ((threadIdx.x & 127) == 0) T3(5 + WG * 3); __syncwarp(); }
      if (ch == 4) { if ((threadIdx.x & 127) == 0) T3(6 + WG * 3); __syncwarp(); }
      if (ch == 8 && (WG == 0 ? n > 0 : n + 1 < STEPS)) bar_arrive(B_V + (WG ^ 1), 256);
      wg_fence();
#pragma unroll
      for (int kk = 0; kk < (ch < FASTG ? 3 : 4); kk++) {
        const int i = ch * 4 + kk;
        float* d = i & 1 ? d1 : d0;
        const uint64_t db = desc_sw128(G_RING + ch * 8192 + (kk & 2) * 32);
        if (i < 2) wg_rs64<0>(d, a + i * 4, db);
        else if (i < 34) wg_rs64<1>(d, a + i * 4, db);
        else wg_ss64<1>(d, desc_sw128(G_W2 + WG * 4096 + (i - 34) * 2048), db);
        wg_ss64<1>(d, desc_sw128(G_W + WG * 73728 + i * 2048), db + 2);
      }
      wg_commit();
      if (ch > 0) { wg_wait<1>(); if (lane == 0) mbar_arrive(sb + G_BAR + 128 + (ch - 1) * 8); }
    }
    wg_wait<0>();
    if (lane == 0) mbar_arrive(sb + G_BAR + 128 + 8 * 8);
    if ((threadIdx.x & 127) == 0) T3(7 + WG * 3);
    __syncwarp();
    uint32_t tw = clk() + (n == 0 ? -100000 : WG ? 0 : DLYW);
    unsigned char* base = g_qkv + (size_t)(n & (QRING - 1)) * (N_CHAIN * 24576);
    if ((ABL & 1) && d0[0] != 1234.5f) {
    } else if (isq) {
#pragma unroll
      for (int i = 0; i < 8; i++) {
        const float *d = (i < 4 ? d0 : d1) + 4 * i, *e = (i < 4 ? d1 : d0) + 4 * i;
        wait_until(tw, 0); tw += P.dly[2 + WG];
        *(uint4*)(base + off0 + (i >> 2) * 24576 + (i & 3) * 1024) =
          make_uint4(movmat(pack2(d[0], d[1])), movmat(pack2(e[0], e[1])), movmat(pack2(d[2], d[3])), movmat(pack2(e[2], e[3])));
      }
    } else {
#pragma unroll
      for (int i = 0; i < 8; i++) {
        const float* d = (i < 4 ? d0 : d1) + 8 * (i & 2) + 2 * (i & 1);
        wait_until(tw, 0); tw += P.dly[2 + WG];
        *(uint4*)(base + off0 + (i >> 2) * 24576 + (i & 2) * 2048 + (i & 1) * 512) =
          make_uint4(pack2(d[0], d[1]), pack2(d[4], d[5]), pack2(d[8], d[9]), pack2(d[12], d[13]));
      }
    }
    bar_arrive(B_M + WG, 160);
  }
}

__device__ __forceinline__ void fill16(void* p, uint32_t v) {
  asm volatile("st.global.v4.u32 [%0], {%1,%1,%1,%1};" :: "l"(p), "r"(v) : "memory");
}
__device__ __forceinline__ void g_load(const Params& P, uint32_t sb) {
  const int lane = threadIdx.x & 31, w = __shfl_sync(~0u, (threadIdx.x >> 5) & 3, 0);
  if (w == 2) return;
  if (w < 2) { bar_sync(15, 192); fence_async_smem(); }
  uint32_t fl = 0;
#pragma unroll 1
  for (int n = w == 3 ? LOCK0 : 0; n < STEPS; n++) {
    if (w && n == LOCK0) { grid_wait(1, lds32(sb + S_GEN)); fl = near_half(XB_F, bid()) * 1024; }
    if (w == 3) {
      const uint32_t tag = (uint32_t)(n - LOCK0 + 1) << 24;
      uint32_t v; int it = 0;
      do { asm volatile("ld.relaxed.gpu.global.u32 %0, [%1];" : "=r"(v) : "l"(g_fl + fl + FL_TICK) : "memory"); spin_guard(it); } while (!NOCHAIN && v < tag);
      const uint32_t off = timer_offset(), now = clk(), t0 = now - ((v ^ tag) >> 24 ? DLYG : (now + off - v) & 0xFFFFFF);
      asm volatile("fence.acquire.gpu;" ::: "memory");
      if (lane == 0) T3(11);
      __syncwarp();
      wait_until(t0, DLYG);
      if (lane == 0) T3(4);
      bar_sync(B_OE, 160);
      continue;
    }
    if (w == 0 || n == 0) {
      if (n < NSEG) wait_flags(g_lnflag + n * 16 + (lane & 1) * 8, 1);
    } else if (!NOCHAIN && n >= LAG) {
      wait_flags(g_fl + fl + FL_F + (lane & 1) * 8, n - LAG + 1);
    }
    if (w) { if (lane == 0) T3(12); bar_sync(B_X, 96); }
    fence_async_global();
    const unsigned char* src = g_lnimg + (uint32_t)((w ? (n >= LAG ? NSEG + n - LAG : 0) : min(n, NSEG - 1)) * 36864);
#pragma unroll 1
    for (int ch = 0; ch < 9; ch++) {
      const uint32_t full = sb + G_BAR + ch * 8;
      mbar_wait(full + 128, (n & 1) ^ 1);
      if (elect()) {
        mbar_expect(full, ABL & 2 ? 16 : 4096);
        bulk_load(sb + G_RING + ch * 8192 + w * 4096, src + ch * 4096, ABL & 2 ? 16 : 4096, full);
      }
    }
  }
}

__device__ __forceinline__ void g_aux(const Params& P, uint32_t sb) {
  const int lane = threadIdx.x & 31, w = (threadIdx.x >> 5) & 3;
  if (w == 1 || w == 2) {
    const int q = g_unit(w - 1);
    uint32_t* f = g_fl + FL_G + q * 8;
#pragma unroll 1
    for (int n = 0; n < STEPS; n++) {
      const uint32_t ln = opaque_tid() & 31;
      uint4* z = (uint4*)g_oacc + (uint32_t)(((n + 1) % ARING) * (16 * DM) + q * 96 + ln);
      if (!(ABL & 16)) { fill16(z, 0); fill16(z + 32, 0); fill16(z + 64, 0); }
      if (n + 3 >= MRING && q < 80) fill16((uint4*)g_mimg + (uint32_t)(((n + 3) % MRING) * 4096 + q * 32 + ln), SENT);
      bar_sync(B_M + (w - 1), 160);
      if (lane == 0) { T3(w * 2 - 2); fence_async_global(); flag_release(f, n + 1); T3(w * 2 - 1); }
      __syncwarp();
    }
  } else {
    const uint32_t u = (bid() - N_CHAIN) * 2 + (w & 1), r = u / 36 * 16 + (u & 3) * 4 + (lane >> 3);
    uint32_t o = r * (DM / 8) + (u % 36 >> 2) * 8 + ((lane & 7) ^ ((r >> 1) & 3)), fl = 0;
#pragma unroll 1
    for (int k = -LAG - 1; k < STEPS; k++) {
      if (k < NSEG - 1) bar_sync(B_X, 96);
      if (k < LAG || u >= 72) continue;
      if (k == NSEG - 1) { fl = near_half(XB_F, bid()) * 1024; wait_flags(g_fl + fl + FL_F + (lane & 1) * 8, NSEG + 1); }
      const uint4 x = __ldcg((const uint4*)P.out + o);
      if (k >= NSEG - 1) wait_flags(g_fl + fl + FL_OCNT + (max(k, NSEG) % OCRING) * 8, N_O * 3 * (max(k, NSEG) / OCRING + 1));
      const float4* a = (const float4*)g_oacc + ((k % ARING) * (16 * DM) + 8 * DM + u * 64 + lane * 2);
      const float4 p = __ldcg(a), v = __ldcg(a + 1);
      ((uint4*)P.out)[o] = make_uint4(badd2(x.x, pack2(p.x, p.y)), badd2(x.y, pack2(p.z, p.w)), badd2(x.z, pack2(v.x, v.y)), badd2(x.w, pack2(v.z, v.w)));
      o += 4 * DM;
    }
    if ((threadIdx.x & 127) == 0) TS(7);
  }
}

template <int WG, bool HALF, int KS, int N> __device__ __forceinline__ void o_mma(float* d, const uint32_t* a, uint32_t ob) {
  constexpr uint64_t db = desc_sw128(O_RING + (KS >> 2) * 8192 + (KS & 3) * 32);
  constexpr uint64_t da = desc_sw128(O_W + WG * 40960 + (KS < 40 ? KS / 5 * 2 + KS % 5 / 2 : KS - 24) * 2048);
  if constexpr (KS < 40 && !(KS % 5 & 1)) {
    const uint32_t* r = a + (KS / 5 * 3 + KS % 5 / 2) * 4;
    if constexpr (HALF) wg_rs32k<KS != 0, db>(d, r[0], r[1], r[2], r[3], ob); else wg_rs64<KS != 0>(d, r, db);
  } else {
    if constexpr (HALF) wg_ss32k<da, db>(d, ob); else wg_ss64<1>(d, da, db);
  }
  if constexpr (N > 1) o_mma<WG, HALF, KS + 1, N - 1>(d, a, ob);
}
template <int WG, bool HALF, int GR> __device__ __forceinline__ void o_groups(float* d, const uint32_t* a, uint32_t sb, int n, bool more) {
  const uint32_t ob = n < NSEG ? 0 : 256;
  mbar_wait(sb + O_BAR + GR * 8, n & 1);
  if (GR == 0) { if ((threadIdx.x & 127) == 0) T3(13 + WG); __syncwarp(); }
  if (GR == (WG == 0 ? OTURN : 4) && (WG < 2 || n + 1 < STEPS)) bar_arrive(B_V + (WG + 1) % 3, 256);
  wg_fence();
  o_mma<WG, HALF, GR * 8, 8 - 2 * FASTO>(d, a, ob);
  if (GR == 4 && more) o_mma<WG, HALF, 40, 4>(d, a, ob);
  wg_commit();
  if (GR > 0) { wg_wait<1>(); if ((threadIdx.x & 31) == 0) mbar_arrive(sb + O_BAR + 128 + (GR - 1) * 8); }
  if constexpr (GR < 4) o_groups<WG, HALF, GR + 1>(d, a, sb, n, more);
}
template <int WG, bool HALF> __device__ __forceinline__ void o_step(const uint32_t* a, uint32_t sb, uint32_t st0, int n, bool more) {
  float d[HALF ? 16 : 32];
  if (WG > 0 || n > 0) bar_sync(B_V + WG, 256);
  o_groups<WG, HALF, 0>(d, a, sb, n, more);
  wg_wait<0>();
  if ((threadIdx.x & 31) == 0) mbar_arrive(sb + O_BAR + 128 + 4 * 8);
  if ((threadIdx.x & 127) == 0) T3(WG == 0 ? 1 : WG == 1 ? 8 : 12);
  __syncwarp();
#pragma unroll(HALF ? 1 : 2)
  for (int sl = 0; sl < 2; sl++) {
    mbar_wait(sb + OB_ST + WG * 16 + sl * 8, (n & 1) ^ (WG == 0));
    if (!HALF || sl == (n >= NSEG)) {
#pragma unroll
      for (int nb = 0; nb < 4; nb++) {
        const float* r = d + (HALF ? 0 : sl * 16) + nb * 4;
        const uint32_t ad = st0 + sl * 8192 + nb * 2048;
        sts32(ad, __float_as_uint(r[0]));
        sts32(ad + 256, __float_as_uint(r[1]));
        sts32(ad ^ 32, __float_as_uint(r[2]));
        sts32((ad ^ 32) + 256, __float_as_uint(r[3]));
      }
      fence_async_smem();
    }
    bar_arrive((sl ? B_G : B_M) + WG, 160);
  }
}
template <int WG>
__device__ __forceinline__ void o_math(const Params& P, uint32_t sb) {
  const bool more = bid() < N_CHAIN + N_G + 12;
  const int lane = threadIdx.x & 31, w = (threadIdx.x >> 5) & 3, g = lane >> 2, tq = lane & 3;
  uint32_t a[96];
  mbar_wait(sb + W_BAR + WG * 8, 0);
  load_frags<24>(a, sb + WG * 49152);
  fence_async_smem();
  bar_sync(B_INIT, 416);
  load_wg<OROLE>(P, sb, false, WG, w);
  mbar_wait(sb + W_BAR + WG * 8, 1);
  if ((threadIdx.x & 127) == 0) TS(4);
  const uint32_t st0 = sb + O_ST + tq * 512 + ((w * 16 + g) ^ (tq * 8)) * 4;
#pragma unroll 1
  for (int n = 0; n < STEPS; n++) {
    if (n < LAG || n >= NSEG) o_step<WG, true>(a, sb, st0, n, more); else o_step<WG, false>(a, sb, st0, n, more);
  }
}

__device__ __forceinline__ void o_aux(const Params& P, uint32_t sb) {
  const int i = bid() - N_CHAIN - N_G, ksl = i / 3;
  const int c0 = ksl * 11 - max(ksl - 4, 0), nc = ksl < 4 ? 11 : 10;
  const int lane = threadIdx.x & 31, w = __shfl_sync(~0u, (threadIdx.x >> 5) & 3, 0);
  if (w == 0) {
    bar_sync(B_INIT, 416);
    const uint32_t* f = g_fl + FL_O + near_half(XB_F + 1, bid()) * 1024 + min((c0 & ~1) + lane, (c0 + nc - 1) | 1);
#pragma unroll 1
    for (int n = 0; n < STEPS; n++) {
      const unsigned char* src = g_oimg + (uint32_t)(((n % RING) * N_CHAIN + c0) * 8192);
      if (!NOCHAIN) wait_flags(f, n + 1);
      fence_async_global();
      if (lane == 0) T3(0);
#pragma unroll
      for (int gr = 0; gr < 5; gr++) {
        const uint32_t full = sb + O_BAR + gr * 8, bytes = ABL & 4 ? 16 : (gr < 4 ? 2 : nc - 8) * 8192;
        mbar_wait(full + 128, (n & 1) ^ 1);
        if (elect()) {
          if (n < LAG || n >= NSEG) {
            mbar_expect(full, bytes >> 1);
            for (uint32_t o = gr * 16384 + (n < LAG ? 0 : 4096); o < gr * 16384 + bytes; o += 8192) bulk_load(sb + O_RING + o, src + o, 4096, full);
          } else {
            mbar_expect(full, bytes);
            bulk_load(sb + O_RING + gr * 16384, src + gr * 16384, bytes, full);
          }
        }
      }
    }
  } else {
#pragma unroll 1
    for (int n = 0; n < STEPS; n++) {
      float* dst = g_oacc + (uint32_t)((n % ARING) * (64 * DM) + ((i % 3) * 3 + (w - 1 + ksl) % 3) * 1024);
      const bool early = w == 3 && n < NSEG;
      bar_sync(B_M + (w - 1), 160);
      if (lane == 0) {
        T3(w * 2);
        if (n < NSEG && !(ABL & 8)) { bulk_reduce(dst, sb + O_ST, 4096); bulk_reduce(dst + 16 * DM, sb + O_ST + 4096, 4096); }
        asm volatile("cp.async.bulk.commit_group;" ::: "memory");
        if (early) {
          asm volatile("cp.async.bulk.wait_group.read 0;" ::: "memory");
          mbar_arrive(sb + OB_ST);
          T3(8 + w);
          bulk_done_inc(g_fl + FL_OCNT + (n % OCRING) * 8);
          T3(w * 2 + 1);
        }
      }
      __syncwarp();
      bar_sync(B_G + (w - 1), 160);
      if (lane == 0) {
        if (n >= LAG && !(ABL & 8)) { bulk_reduce(dst + 32 * DM, sb + O_ST + 8192, 4096); bulk_reduce(dst + 48 * DM, sb + O_ST + 12288, 4096); }
        asm volatile("cp.async.bulk.commit_group;\ncp.async.bulk.wait_group.read 1;" ::: "memory");
        if (!early) mbar_arrive(sb + OB_ST + (w % 3) * 16);
        asm volatile("cp.async.bulk.wait_group.read 0;" ::: "memory");
        mbar_arrive(sb + OB_ST + (w % 3) * 16 + 8);
        if (!early) {
          T3(8 + w);
          bulk_done_inc(g_fl + FL_OCNT + (n % OCRING) * 8);
          T3(w * 2 + 1);
        }
      }
      __syncwarp();
    }
  }
}

constexpr uint32_t Y_PITCH = 1168, Y_ROWS = 16 * Y_PITCH;
template <int R> __device__ __forceinline__ void y_rows(uint32_t* y, uint32_t src, uint32_t dst, int w, int bar) {
  const int lane = threadIdx.x & 31;
#pragma unroll
  for (int k = 0; k < 2 * R + 1; k++) {
    const int op = w + k * (16 / R);
    if (k == 2 * R && w >= 4) break;
    uint32_t a, b, c, d;
    ldsm4t(a, b, c, d, src + op * 512 + (lane & 16) * 16 + (lane & 7) * 32 + (lane & 8) * 2);
    stsm4(dst + (lane & 15) * Y_PITCH + op * 32 + (lane & 16), a, b, c, d);
  }
  bar_sync(bar, 512 / R);
  const uint32_t row = dst + ((w & 6) * 2 + (w >> 3) * 2 + (w & 1)) * Y_PITCH + lane * 4;
#pragma unroll
  for (int i = 0; i < 9 * R; i++) y[i] = lds32(row + i / 9 * 2 * Y_PITCH + i % 9 * 128);
}

__device__ __forceinline__ void f_role(const Params& P, uint32_t sb) {
  const int lane = threadIdx.x & 31, w = __shfl_sync(~0u, threadIdx.x >> 5, 0), r0 = (bid() - N_CHAIN - N_G - N_O) * 16;
  if (w == 8) {
    const uint32_t* fo = g_fl + FL_OCNT + near_half(XB_F, bid()) * 1024;
    fence_async_global();
#pragma unroll 1
    for (int n = 0; n < NSEG; n++) {
      bar_sync(2, 288);
      if (elect()) {
        mbar_expect(sb + F_BAR, 36864);
        bulk_load(sb + F_XY, P.X + (size_t)(n * 32 + r0) * DM, 18432, sb + F_BAR);
        bulk_load(sb + F_XY + 18432, g_yT + (size_t)(n * 32 + r0) * DM, 18432, sb + F_BAR);
        mbar_expect(sb + F_BAR + 8, 36864);
        T3(1);
      }
      wait_flags(fo + (n % OCRING) * 8, NOCHAIN == 5 ? 0 : N_O * 3 * (n / OCRING + 1));
      fence_async_global();
      if (elect()) { bulk_load(sb + F_A, g_oacc + (uint32_t)((n % ARING) * (64 * DM) + r0 * DM), 36864, sb + F_BAR + 8); T3(0); }
    }
  } else if (w == 9) {
#pragma unroll 1
    for (int n = 0; n < NSEG; n++) {
      const uint32_t st = sb + (n & 1) * 36864;
      unsigned char* p = g_lnimg + (uint32_t)((NSEG + n) * 36864 + r0 * 128);
      bar_sync(1, 288);
      if (elect()) {
        T3(2);
#pragma unroll
        for (int i = 0; i < 9; i++) bulk_store(p + i * 4096, st + F_L + i * 2048, 2048);
        asm volatile("cp.async.bulk.commit_group;" ::: "memory");
        bulk_done_inc(g_fl + FL_F + (bid() & 1) * 8);
        T3(3);
        bulk_store(P.out + (size_t)(n * 32 + r0) * DM, st + F_X, 18432);
        asm volatile("cp.async.bulk.commit_group;\ncp.async.bulk.wait_group.read 0;" ::: "memory");
        if (n + 1 == NSEG) bulk_done_inc(g_fl + FL_F + (bid() & 1) * 8);
      }
      __syncwarp();
    }
  } else if (w < 8) {
    const uint32_t row = sb + w * 1152 + lane * 4, acc = sb + F_A + w * 256 + (lane ^ ((w & 6) * 2)) * 8;
    const uint32_t ln = sb + F_L + w * 128 + (((lane >> 2) ^ w) << 4) + (lane & 3) * 4;
#pragma unroll 1
    for (int n = -1; n < NSEG; n++) {
      const uint32_t st = (n & 1) * 36864;
      uint32_t x[18], y[18], l[18];
      if (n >= 0) mbar_wait(sb + F_BAR, n & 1);
#pragma unroll
      for (int i = 0; i < 18; i++) x[i] = lds32(row + F_XY + i / 9 * 9216 + i % 9 * 128);
      y_rows<2>(y, sb + F_XY + 18432, sb + F_Y, w, 3);
      layernorm9<2>(x, l);
#pragma unroll
      for (int i = 0; i < 18; i++) x[i] = badd2(x[i], bmul2(l[i], y[i]));
      if (n >= 0) mbar_wait(sb + F_BAR + 8, n & 1);
      if (threadIdx.x == 0 && n >= 0) T3(4);
      __syncwarp();
      uint2 a[18];
#pragma unroll
      for (int i = 0; i < 18; i++) a[i] = lds64(acc + i / 9 * 2048 + i % 9 * 4096);
#pragma unroll
      for (int i = 0; i < 18; i++) x[i] = badd2(x[i], pack2(__uint_as_float(a[i].x), __uint_as_float(a[i].y)));
      if (n + 1 < NSEG) bar_arrive(2, 288);
      layernorm9<2>(x, l);
#pragma unroll
      for (int i = 0; i < 18; i++) { x[i] = badd2(x[i], bmul2(l[i], y[i])); sts32(row + st + F_X + i / 9 * 9216 + i % 9 * 128, x[i]); }
      layernorm9<2>(x, l);
#pragma unroll
      for (int i = 0; i < 18; i++) sts32(ln + st + i / 9 * 1024 + i % 9 * 2048, l[i]);
      fence_async_smem();
      if (n >= 0) bar_sync(1, 288); else bar_sync(3, 256);
    }
  }
}

constexpr uint32_t P_CH = 147456, P_CHSZ = 12800, P_H = 4352;
static_assert(P_CH + 6 * P_CHSZ <= G_BAR, "prologue smem");

template <int N>
__device__ __forceinline__ void conv_fold(float (*acc)[4], bool hi, uint32_t mine, uint32_t theirs, int bar, int cnt) {
#pragma unroll
  for (int i = 0; i < N / 2; i++) {
    uint4 v;
    v.x = __float_as_uint(hi ? acc[i][0] : acc[i + N / 2][0]); v.y = __float_as_uint(hi ? acc[i][1] : acc[i + N / 2][1]);
    v.z = __float_as_uint(hi ? acc[i][2] : acc[i + N / 2][2]); v.w = __float_as_uint(hi ? acc[i][3] : acc[i + N / 2][3]);
    sts128(mine + i * 512, v);
  }
  bar_sync(bar, cnt);
#pragma unroll
  for (int i = 0; i < N / 2; i++) {
    const uint4 v = lds128(theirs + i * 512);
    acc[i][0] = (hi ? acc[i + N / 2][0] : acc[i][0]) + __uint_as_float(v.x); acc[i][1] = (hi ? acc[i + N / 2][1] : acc[i][1]) + __uint_as_float(v.y);
    acc[i][2] = (hi ? acc[i + N / 2][2] : acc[i][2]) + __uint_as_float(v.z); acc[i][3] = (hi ? acc[i + N / 2][3] : acc[i][3]) + __uint_as_float(v.w);
  }
}
template <int N>
__device__ __forceinline__ void conv_store(const float (*acc)[4], int tile0, uint32_t su, int d, uint32_t dd) {
  const int lane = threadIdx.x & 31, g = lane >> 2, tq = lane & 3;
#pragma unroll
  for (int i = 0; i < N; i++) {
    const uint32_t ad = su + (8 + (tile0 + i) * 8 + g) * 32 + tq * 4, sw = (g & 4) << 2;
    const uint32_t lo = badd2(movmat(pack2(acc[i][0], acc[i][1])), bmul2(lds32(ad + sw), dd));
    const uint32_t hi = badd2(movmat(pack2(acc[i][2], acc[i][3])), bmul2(lds32(ad + (sw ^ 16)), dd));
    ((uint2*)g_yT)[(((tile0 + i) * 8 + g) * DM + d) * 4 + tq] = make_uint2(lo, hi);
  }
}

__device__ __forceinline__ void prologue(const Params& P, uint32_t sb) {
  const int b = bid(), tid = threadIdx.x, lane = tid & 31, warp = tid >> 5, t0 = b * 16;
  const bool isg = b >= N_CHAIN && b < N_CHAIN + N_G;
  const int nch = isg ? 2 : b < 128 ? 6 : 0, chb = b < N_CHAIN ? b * 6 : isg ? b * 2 + 256 : b * 6 - 192;
  const uint32_t tstart = clk();
  if (tid < 288) {
    if (b < 128) {
      const int c = (tid >> 1) * 4, tt = t0 + (tid & 1) * 8;
      uint2 kr[11], vr[8];
#pragma unroll
      for (int i = 0; i < 11; i++) { const int t = tt + i - 3; kr[i] = t >= 0 ? __ldg((const uint2*)(P.K + (size_t)t * DM + c)) : make_uint2(0, 0); }
#pragma unroll
      for (int i = 0; i < 8; i++) vr[i] = __ldg((const uint2*)(P.V + (size_t)(tt + i) * DM + c));
#pragma unroll
      for (int e = 0; e < 2; e++) {
        const uint4 sh = __ldg((const uint4*)(P.shift + c * 4) + e);
        const uint32_t s0 = __byte_perm(sh.x, sh.z, 0x5410), s1 = __byte_perm(sh.x, sh.z, 0x7632);
        const uint32_t s2 = __byte_perm(sh.y, sh.w, 0x5410), s3 = __byte_perm(sh.y, sh.w, 0x7632);
        uint32_t v[8];
#pragma unroll
        for (int i = 0; i < 8; i++) {
          const uint32_t k3 = e ? kr[i].y : kr[i].x, k2 = e ? kr[i + 1].y : kr[i + 1].x, k1 = e ? kr[i + 2].y : kr[i + 2].x, k0 = e ? kr[i + 3].y : kr[i + 3].x;
          v[i] = bmul2(badd2(badd2(badd2(bmul2(k3, s3), bmul2(k2, s2)), bmul2(k1, s1)), bmul2(k0, s0)), e ? vr[i].y : vr[i].x);
        }
        *(uint4*)(g_kvT + (size_t)(c + 2 * e) * KVP + tt) =
          make_uint4(__byte_perm(v[0], v[1], 0x5410), __byte_perm(v[2], v[3], 0x5410), __byte_perm(v[4], v[5], 0x5410), __byte_perm(v[6], v[7], 0x5410));
        *(uint4*)(g_kvT + (size_t)(c + 2 * e + 1) * KVP + tt) =
          make_uint4(__byte_perm(v[0], v[1], 0x7632), __byte_perm(v[2], v[3], 0x7632), __byte_perm(v[4], v[5], 0x7632), __byte_perm(v[6], v[7], 0x7632));
      }
    }
  } else if (tid < 384) {
    const int t = tid - 288;
    for (int i = b * 96 + t; i < 16 * DM; i += N_CTA * 96) ((uint4*)g_oacc)[i] = make_uint4(0, 0, 0, 0);
    if (b * 96 + t < 128 * 8) g_lnflag[b * 96 + t] = 0;
    if (t == 95) sts32(sb + S_GEN, ld_acquire(g_gbar));
    __syncwarp();
    wait_until(tstart, P.dly[23]);
    for (int i = t; i < 32 * nch; i += 96) asm volatile("prefetch.global.L2 [%0];" :: "l"(P.Hk + (size_t)chb * SEQ + i * 64));
  }
  if (warp < 12) {
    bar_arrive(10, 416);
    if (tid == 128) TS(14);
    const int ch = 5 - (warp >> 1), sub = warp & 1, d = chb + ch;
    const uint32_t su = sb + P_CH + ch * P_CHSZ;
    if (ch < nch) {
      const uint32_t* hs = (const uint32_t*)(P.Hk + (size_t)d * SEQ);
#pragma unroll
      for (int q = sub * 32 + lane; q < 256; q += 64) {
        const uint4 c = __ldg((const uint4*)hs + q);
        const uint32_t prev = q ? __ldg(hs + 4 * q - 1) : 0u;
        sts128(su + P_H + 32 + q * 16, make_uint4(__byte_perm(c.x, prev, 0x7610), __byte_perm(c.y, c.x, 0x7610), __byte_perm(c.z, c.y, 0x7610), __byte_perm(c.w, c.z, 0x7610)));
        sts128(su + P_H + 4224 + q * 16, make_uint4(__byte_perm(c.x, 0, 0x1032), __byte_perm(c.y, 0, 0x1032), __byte_perm(c.z, 0, 0x1032), __byte_perm(c.w, 0, 0x1032)));
      }
      if (sub == 1 && lane == 0) sts32(su + P_CHSZ - 16, __bfloat16_as_ushort(P.Dk[d]) * 0x10001u);
      if (sub == 0 && lane < 20) sts128(su + (lane < 16 ? lane * 16 : P_H + (lane & 2) * 2096 + (lane & 1) * 16), make_uint4(0, 0, 0, 0));
    }
    bar_sync(11, 416);
    if (ch < nch) {
#pragma unroll
      for (int q = sub * 32 + lane; q < 256; q += 64) {
        const int row = (q >> 1) + 8;
        sts128(su + row * 32 + (((q & 1) ^ ((row >> 2) & 1)) << 4), __ldcg((const uint4*)(g_kvT + (size_t)d * KVP) + q));
      }
    }
    const int g = lane >> 2, tq = lane & 3;
    const uint32_t sh = su + P_H + (g & 1) * 4192 + (8 + (g >> 1) - tq) * 4;
    float acc[16][4];
#pragma unroll
    for (int i = 0; i < 16; i++) { acc[i][0] = acc[i][1] = acc[i][2] = acc[i][3] = 0.f; }
    auto u_addr = [&](int res) {
      const int row = 8 - res + ((lane >> 4) << 3) + (lane & 7);
      return su + row * 32 + ((((lane >> 3) & 1) ^ ((row >> 2) & 1)) << 4);
    };
    if (ch < nch) {
      bar_sync(1 + ch, 64);
      if (tid == 352) TS(11);
      if (sub) {
#pragma unroll 4
        for (int res = 0; res < 8; res++) {
          uint32_t b0, b1, b2, b3;
          ldsm4(b0, b1, b2, b3, u_addr(res));
          const uint32_t r0 = lds32(sh + res * 32);
          mma16(acc[0], r0, lds32(sh + res * 32 + 16), lds32(sh + res * 32 - 16), r0, b0, b1);
        }
        conv_store<1>(acc, 0, su, d, lds32(su + P_CHSZ - 16));
      }
    }
    bar_arrive(12, 416);
    if (isg && warp < 8) { while ((int)(clk() - tstart - S1G) < 0) __nanosleep(200); load_wg<GROLE>(P, sb, true, warp >> 2, warp & 3); }
    if (ch < nch) {
#pragma unroll 1
      for (int res = sub * 4; res < sub * 4 + 4; res++) {
        uint32_t bf[16][2];
        const uint32_t ad = u_addr(res);
#pragma unroll
        for (int f = 0; f < 16; f += 2) ldsm4(bf[f][0], bf[f][1], bf[f + 1][0], bf[f + 1][1], ad + f * 256);
#pragma unroll
        for (int k = 0; k < 16; k++) {
          const int jj = k & 1 ? k >> 1 : 15 - (k >> 1);
          const uint32_t ah = sh + (8 * jj + res) * 32;
          const uint32_t r0 = lds32(ah), r1 = lds32(ah + 16), rm = lds32(ah - 16);
#pragma unroll
          for (int i = max(jj, 1); i < 16; i++) mma16(acc[i], r0, r1, rm, r0, bf[i - jj][0], bf[i - jj][1]);
        }
      }
      bar_sync(1 + ch, 64);
      if (tid == 352) TS(12);
      const uint32_t xb = su + P_H + lane * 16, dd = lds32(su + P_CHSZ - 16);
      conv_fold<16>(acc, sub, xb + sub * 4096, xb + (sub ^ 1) * 4096, 1 + ch, 64);
      conv_store<8>(acc, sub * 8, su, d, dd);
    }
  } else {
    for (int i = b; i < 194 + MRING * 5; i += N_CTA) {
      const int n = (i - 194) / 5, r = (i - 194) % 5, blk = i < 192 ? i / 6 * 8 + i % 6 : i < 194 ? XB_F + i - 192 : XB_M + n * 8 + r;
      const uint32_t fill = i < 194 ? 0u : SENT;
#pragma unroll 1
      for (int q = tid - 384; q < 256 && warp < 15; q += 96) {
        uint4 v = make_uint4(fill, fill, fill, fill);
        if (i >= 194 && n == 0 && (r > 0 || q < 128)) {
          const bf16* m = P.mem0 + (max(r * 8 - 4, 0) + (q >> 5)) * 16 + ((q >> 1) & 1) * 8 + ((q >> 2) & 7);
          v.x = pack2(__bfloat162float(m[0]), __bfloat162float(m[DM])); v.y = pack2(__bfloat162float(m[2 * DM]), __bfloat162float(m[3 * DM]));
          v.z = pack2(__bfloat162float(m[4 * DM]), __bfloat162float(m[5 * DM])); v.w = pack2(__bfloat162float(m[6 * DM]), __bfloat162float(m[7 * DM]));
        }
        g_xb[blk * 512 + q] = v;
        g_xb[blk * 512 + 256 + q] = v;
      }
    }
    if (tid < 388) g_xb[XB_REF * 512 + (tid & 2) * 128 + (b & ~1) + (tid & 1)] = make_uint4(0, 0, 0, 0);
    else if (tid < 392 && b < N_GRP) g_xb[(b * 8 + 7) * 512 + (tid & 2) * 128 + (tid & 1)] = make_uint4(0, 0, 0, 0);
    if (warp < 15) { bar_arrive(9, 128); bar_sync(7, 96); }
    if (tid == 384) TS(8);
    if (warp == 12) {
      const bf16* w = lane < 6 ? (lane % 3 == 0 ? P.Wk : lane % 3 == 1 ? P.Wv : P.Wq) + (((b >> 5) * 2 + lane / 3) * 32 + (b & 31)) * 2048
                               : (lane < 8 ? P.Wo + (lane - 6) * (9 * 131072) : P.X) + b * 2048;
      uint32_t t = tstart + P.dly[19];
      if ((int)(clk() - t) > 0) t = clk();
#pragma unroll 1
      for (int st = 0; st < 9 && b < N_CHAIN; st++) {
#pragma unroll 1
        for (int i = 0; i < 9; i++, t += PACE) {
          wait_until(t, 0);
          if (lane == st) asm volatile("cp.async.bulk.prefetch.L2.global [%0], 4096;" :: "l"(w + i * (lane < 6 ? 262144 : 131072)) : "memory");
        }
      }
      if (lane == 0) TS(10);
    } else if (warp == 15) {
      bar_sync(10, 416);
      if (lane == 0) { grid_arrive(0); if (nch) grid_wait(0, lds32(sb + S_GEN)); }
      __syncwarp();
      bar_arrive(11, 416);
      if (lane == 0) TS(1);
      bar_sync(9, 128);
      bar_sync(12, 416);
      if (lane == 0) { TS(16); grid_arrive(2); TS(17); }
    } else if (lane == 0) {
      if (warp == 13 || (warp == 14 && b < N_GRP)) {
        uint32_t* p = (uint32_t*)(g_xb + (warp == 13 ? XB_REF * 512 + b : (b * 8 + 7) * 512));
        int votes = 0;
        for (int rep = 0; rep < 24 && abs(votes) < 7; rep++) {
          uint32_t v0, v1, c0, c1;
          asm volatile("atom.relaxed.gpu.global.add.u32 %0, [%4], 0;\n atom.relaxed.gpu.global.add.u32 %1, [%5], 0;\n"
                       "{.reg .pred p; setp.eq.u32 p, %0, 0x7ffffff3; @p trap; mov.u32 %2, %%clock; setp.eq.u32 p, %1, 0x7ffffff3; @p trap; mov.u32 %3, %%clock;}"
                       : "=&r"(v0), "=&r"(v1), "=&r"(c0), "=&r"(c1) : "l"(p + (rep & 1) * 1024), "l"(p + ((rep & 1) ^ 1) * 1024) : "memory");
          votes += ((c1 - c0 > 80u) == (rep & 1)) ? 1 : -1;
        }
        if (warp == 13) { g_side[b] = votes > 0; TS(9); } else g_near[b] = votes > 0;
      }
    }
    __syncwarp();
    if (warp > 12 && b < N_CHAIN) {
      while ((int)(clk() - tstart - S1DLY) < 0) __nanosleep(200);
      for (int k = warp - 13; k < 8; k += 3) load_wg<CHAIN>(P, sb, true, 1 - k / 4, k & 3);
    }
  }
  if (b < N_CHAIN + N_G && (warp < 8 || (isg && warp >= 12))) bar_arrive(0, 512); else bar_sync(0, 512);
  if (tid == 352) TS(2);
}

__device__ __forceinline__ void publish_y() {
  if (threadIdx.x == 383) { grid_arrive(1); TS(18); }
  __syncwarp();
}

template <int R> __device__ __forceinline__ void ln_tiles(const Params& P, uint32_t sb) {
  const int lane = threadIdx.x & 31, w = (threadIdx.x >> 5) & (16 / R - 1), half = R == 1 ? 0 : threadIdx.x >> 8, u = N_CTA - 1 - bid();
  const int first = R == 1 ? u : 46 - 2 * u + half, step = R == 1 ? 4 : 40, last = R == 1 ? 8 : 128;
  const uint32_t raw = sb + P_CH + half * (18432 + Y_ROWS), mb = sb + T_BAR + (R - 1 + half) * 8;
  const bool lead = w == 16 / R - 1 && lane == 0;
  auto load_y = [&](const bf16* src, int tile) {
    fence_async_global();
    mbar_expect(mb, 18432);
    bulk_load(raw, src + (size_t)tile * 16 * DM, 18432, mb);
  };
  uint32_t nx[9 * R];
  auto load_x = [&](int tile) {
#pragma unroll
    for (int i = 0; i < 9 * R; i++) nx[i] = __ldg((const uint32_t*)(P.X + (size_t)(tile * 16 + w + i / 9 * 8) * DM) + i % 9 * 32 + lane);
  };
  load_x(first);
  if (R == 2) {
    if (lead) { grid_wait(1, lds32(sb + S_GEN)); if (u > 3) TS(13); load_y(g_yT, first); }
    __syncwarp();
  }
#pragma unroll 1
  for (int tile = first, real = R - 1, ph = 0; tile < last; tile += real * step, real = 1, ph ^= 1) {
    uint32_t x[9 * R], l[9 * R], y[9 * R];
    const bool ts = threadIdx.x == 0 && (R == 1 ? tile == first : u > 3 && tile == first + step);
    if (ts) TS(26);
#pragma unroll
    for (int i = 0; i < 9 * R; i++) x[i] = nx[i];
    layernorm9<R>(x, l);
    if (real && tile + step < last) load_x(tile + step);
    if (R == 2 && tile == first + step && u >= N_F && w < 6) load_wg<OROLE>(P, sb, true, w >> 1, half * 2 + (w & 1));
    if (R == 1 && tile == first && lead) {
      if (real) grid_wait(2, lds32(sb + S_GEN));
      TS(13);
      load_y(real ? g_yT : P.Hk, tile);
    }
    bar_sync(13 + half, 512 / R);
    mbar_wait(mb, ph);
    if (ts) TS(28);
    y_rows<R>(y, raw, raw + 18432, w, 13 + half);
    if (ts) TS(29);
    if (lead && real && tile + step < last) { fence_async_smem(); load_y(g_yT, tile + step); }
    __syncwarp();
#pragma unroll
    for (int i = 0; i < 9 * R; i++) x[i] = badd2(x[i], bmul2(l[i], y[i]));
    layernorm9<R>(x, l);
    if (ts && l[0] != 0x12345) TS(30);
#pragma unroll
    for (int r = 0; r < R; r++) store_ln_row(0, tile * 16 + w + r * 8, l + r * 9);
    if (R == 1) {
      __syncthreads();
      if (threadIdx.x == 32 && real) { if (tile < 4) TS(19); st_release(g_lnflag + tile * 8, 1); if (tile < 4) TS(20); }
      __syncwarp();
    }
    if (ts) TS(31);
  }
  if (R == 2) {
    __syncthreads();
    if (threadIdx.x >= 506) {
      asm volatile("fence.acq_rel.gpu;" ::: "memory");
      st_relaxed_if(g_lnflag + ((first ^ (lane & 1)) + (lane - 26) / 2 * step) * 8, 1, true);
    }
    __syncwarp();
    fence_async_smem();
    if (threadIdx.x == 0) TS(15);
  }
}

__global__ void __cluster_dims__(2, 1, 1) __launch_bounds__(512, 1) k_main(const __grid_constant__ Params P) {
  extern __shared__ __align__(1024) unsigned char smem[];
  const uint32_t sb = (uint32_t)__cvta_generic_to_shared(smem);
  const int b = bid(), wg = threadIdx.x >> 7;
  if ((threadIdx.x & 127) == 0) TS(0);
  if (threadIdx.x == 480) {
    if ((sb & 0xFFFFFF) != SBASE) __trap();
    for (int i = 0; i < 6; i++) mbar_init(sb + W_BAR + i * 8, 1);
    if (b < N_CHAIN) {
      mbar_init(sb + CB_FULL, 1); mbar_init(sb + CB_FULL + 8, 1);
      mbar_init(sb + CB_REF, 1);
      mbar_init(sb + CB_SX, 1); mbar_init(sb + CB_OX, 1); mbar_init(sb + CB_XX, 1); mbar_init(sb + CB_Q, 2); mbar_init(sb + CB_VF, 1); mbar_init(sb + CB_VF + 8, 1);
      sts32(sb + C_BAD, 0);
      for (int i = 0; i < 11; i++) mbar_init(sb + CB_M + i * 8, i == 0 ? 5 : i == 5 ? 3 : 1);
    } else if (b < N_CHAIN + N_G) {
      for (int i = 0; i < 9; i++) { mbar_init(sb + G_BAR + i * 8, 2); mbar_init(sb + G_BAR + 128 + i * 8, 8); }
    } else if (b < N_CHAIN + N_G + N_O) {
      for (int i = 0; i < 5; i++) { mbar_init(sb + O_BAR + i * 8, 1); mbar_init(sb + O_BAR + 128 + i * 8, 12); }
      for (int i = 0; i < 6; i++) mbar_init(sb + OB_ST + i * 8, 1);
    } else {
      mbar_init(sb + F_BAR, 1); mbar_init(sb + F_BAR + 8, 1);
    }
    asm volatile("fence.mbarrier_init.release.cluster;" ::: "memory");
    fence_async_smem();
  }
  __syncwarp();
  asm volatile("barrier.cluster.arrive.relaxed.aligned;" ::: "memory");
  prologue(P, sb);
  asm volatile("barrier.cluster.wait.aligned;" ::: "memory");
  fence_async_smem();
  if (b >= N_CHAIN + N_G) publish_y();
  if (b >= 128) ln_tiles<1>(P, sb);
  if (b >= N_CHAIN + N_G) ln_tiles<2>(P, sb);
  if ((threadIdx.x & 127) == 0) TS(3);
  if (b < N_CHAIN) {
    if (wg < 2) { reg_inc<200>(); chain_proj(P, sb); }
    else if (wg == 2) { reg_dec<ATTR>(); publish_y(); chain_attn(P, sb); }
    else { reg_dec<112 - ATTR>(); chain_aux(P, sb); }
  } else if (NOBULK) {
    if (b < N_CHAIN + N_G) publish_y();
    {
      if (wg == 0) {
        float d[4] = {0.f, 0.f, 0.f, 0.f};
        for (int n = 0; n < STEPS - 1; n++) {
          const uint32_t* f = g_fl + FL_TICK;
          uint32_t x;
          do { for (int k = 0; k < 16; k++) mma16(d, 0, 0, 0, 0, 0, 0); asm volatile("ld.relaxed.gpu.global.u32 %0, [%1];" : "=r"(x) : "l"(f) : "memory"); } while ((x >> 24) <= n);
          const int q = (b - N_CHAIN) * 4 + (threadIdx.x >> 5);
          if (n + 5 >= MRING && q < 80) fill16((uint4*)g_mimg + (uint32_t)(((n + 5) % MRING) * 4096 + q * 32 + (threadIdx.x & 31)), SENT);
        }
        if (d[0] == 1.f) P.out[0] = __float2bfloat16(0.f);
      }
    }
  } else if (b < N_CHAIN + N_G) {
    if (wg == 0) { reg_inc<232>(); g_math<0>(P, sb); }
    else if (wg == 1) { reg_inc<232>(); g_math<1>(P, sb); }
    else if (wg == 2) { reg_dec<24>(); bar_arrive(15, 192); publish_y(); g_aux(P, sb); }
    else { reg_dec<24>(); g_load(P, sb); }
  } else if (b < N_CHAIN + N_G + N_O) {
    if (wg == 0) { reg_inc<160>(); o_math<0>(P, sb); }
    else if (wg == 1) { reg_inc<160>(); o_math<1>(P, sb); }
    else if (wg == 2) { reg_inc<160>(); o_math<2>(P, sb); }
    else { reg_dec<32>(); o_aux(P, sb); }
  } else {
    f_role(P, sb);
  }
}

}

extern "C" void kernel_launch(void* const* d_in, const int* in_sizes, int n_in, void* d_out, int out_size) {
  typedef CUresult (*Encode)(CUtensorMap*, CUtensorMapDataType, cuuint32_t, void*, const cuuint64_t*, const cuuint64_t*, const cuuint32_t*, const cuuint32_t*,
                             CUtensorMapInterleave, CUtensorMapSwizzle, CUtensorMapL2promotion, CUtensorMapFloatOOBfill);
  static Encode encode = nullptr;
  if (!encode) cudaGetDriverEntryPoint("cuTensorMapEncodeTiled", (void**)&encode, cudaEnableDefault);
  Params P;
  for (int i = 0; i < 11; i++) {
    const bool wo = i == 6 || i == 7;
    const cuuint64_t cols = wo ? DM : HD, rows = HD + DM - cols, pitch = cols * 2;
    const cuuint64_t dim[4][5] = {{cols, 2, 8, 2, 18}, {cols, 16, 1, 1, rows / 16}, {cols, 2, 4, 4, rows / 32}, {64, 16, 64, 2, 18}};
    const cuuint64_t stride[4][4] = {{8 * pitch, pitch, 16 * pitch, 32 * pitch}, {pitch, pitch, pitch, 16 * pitch},
                                     {pitch, 8 * pitch, 2 * pitch, 32 * pitch}, {pitch, 128, 16 * pitch, 32 * pitch}};
    const cuuint32_t box[4][5] = {{64, 2, 8, 1, 18}, {64, 16, 1, 1, 1}, {64, 2, 4, 2, 1}, {64, 16, 2, 1, 18}}, one[5] = {1, 1, 1, 1, 1};
    const int k = i < 3 ? 0 : i < 7 ? 1 : i < 8 ? 2 : 3;
    encode(&P.map[i], CU_TENSOR_MAP_DATA_TYPE_BFLOAT16, 5, d_in[wo ? 11 : 8 + (i & 7) % 3], dim[k], stride[k], box[k], one,
           CU_TENSOR_MAP_INTERLEAVE_NONE, CU_TENSOR_MAP_SWIZZLE_128B, CU_TENSOR_MAP_L2_PROMOTION_L2_128B, CU_TENSOR_MAP_FLOAT_OOB_FILL_NONE);
  }
  P.X = (const bf16*)d_in[0]; P.K = (const bf16*)d_in[1]; P.V = (const bf16*)d_in[2];
  P.shift = (const bf16*)d_in[3]; P.Hk = (const bf16*)d_in[4]; P.Dk = (const bf16*)d_in[5];
  P.mem0 = (const bf16*)d_in[7];
  P.Wq = (const bf16*)d_in[8]; P.Wk = (const bf16*)d_in[9]; P.Wv = (const bf16*)d_in[10]; P.Wo = (const bf16*)d_in[11];
  P.out = (bf16*)d_out;
  for (int i = 0; i < 24; i++) P.dly[i] = h_dly[i];
  cudaFuncSetAttribute(k_main, cudaFuncAttributeMaxDynamicSharedMemorySize, SMEM_BYTES);
  k_main<<<N_CTA, 512, SMEM_BYTES>>>(P);
}
```

```cpp
#include <cuda.h>
#include <cuda_runtime.h>
#include <cuda_bf16.h>
#include <stdint.h>

namespace {

typedef __nv_bfloat16 bf16;

constexpr int SEQ = 2048, DM = 576, HD = 4096, NSEG = 64;
#define PLACE 1
#define LAGV 7
constexpr int LAG = LAGV, STEPS = NSEG + LAG, RING = 8, QRING = 4;
static_assert(LAG < RING, "ring");
constexpr int N_CHAIN = 64, N_G = 48, N_O = 18, N_F = 2;
constexpr uint32_t SBASE = 1024;
constexpr uint32_t SENT = 0xFFFFFFFFu;
constexpr int SPIN_MAX = 1 << 22;

__device__ __forceinline__ uint32_t bid() {
  uint32_t b;
  asm volatile("mov.u32 %0, %%ctaid.x;" : "=r"(b));
  return b < 6 ? b + 106 : b < 8 ? b + 122 : b < 114 ? b - 8 : b < 130 ? b - 2 : b;
}
__device__ __forceinline__ uint32_t chain_id() { return blockIdx.x - (PLACE ? 8 : 0); }
constexpr int KVP = SEQ + 64;
__device__ __align__(1024) bf16 g_kvT[DM * KVP];
__device__ __align__(1024) bf16 g_yT[DM * SEQ];
__device__ __align__(1024) unsigned char g_lnimg[2 * NSEG * 9 * 4096];
__device__ __align__(1024) unsigned char g_qkv[QRING * N_CHAIN * 24576];
__device__ __align__(1024) unsigned char g_oimg[RING * N_CHAIN * 8192];
constexpr int ARING = 16;
static_assert(ARING >= LAG + 9, "accumulator ring");
__device__ __align__(1024) float g_oacc[ARING * 64 * DM];
constexpr int MRING = LAG + 4, N_GRP = 32 + MRING + 1;
constexpr int XB_M = 256, XB_F = XB_M + MRING * 8, XB_REF = XB_F + 2, N_CTA = N_CHAIN + N_G + N_O + N_F;
__device__ __align__(65536) uint4 g_xb[N_GRP * 4096];
#define g_mimg ((uint32_t*)(g_xb + XB_M * 512))
__device__ uint32_t g_near[N_GRP];
__device__ uint32_t g_side[N_CTA];
__device__ __align__(128) uint32_t g_gbar[3 * 32];
constexpr int FL_G = 0, FL_F = 96 * 8, FL_OCNT = FL_F + 2 * 8, OCRING = 16, FL_TICK = 992, FL_O = 2048, FL_SYNC = FL_O + 128;
static_assert(FL_OCNT + OCRING * 8 <= FL_TICK, "flag block");
#define g_fl ((uint32_t*)(g_xb + XB_F * 512))
__device__ __align__(1024) uint32_t g_lnflag[128 * 8];
#define TS(slot)

#define OTURN 2
#define LOCK0 3
#define FASTO 0
#define FASTG 0
#define NOBULK 0
#define VPAT 0x15bbd249u
#define XR 3
#define RATE 1
#define SAFE 3
#define WFENCE 0
#define QPOS 0
#define VE 4
#define OGAP 2
#define NOCHAIN 0
#define BFENCE 2
#define ABL 0
#define ATTR 80
#define CNT(slot, tries)
#define T3(slot)
#define TR(slot)
#define TRV(slot, val)
#define TRD(slot, dep)
#define TRSYNC()
#define TRDUMP(n)
#define CLK(t) "{.reg .b64 x; .reg .b32 h; mov.u64 x, %%clock64; mov.b64 {" t ", h}, x;}"
__device__ __forceinline__ uint32_t clk() { uint32_t t; asm volatile(CLK("%0") : "=r"(t) :: "memory"); return t; }
__device__ __forceinline__ void wait_until(uint32_t t0, uint32_t d) {
  asm volatile("{.reg .pred p; .reg .u32 t;\n"
               "W: " CLK("t") " sub.u32 t, t, %0; setp.lt.s32 p, t, 0; @p bra.uni W;}"
               :: "r"(t0 + d) : "memory");
}
__device__ __forceinline__ uint32_t pack2(float lo, float hi) {
  uint32_t r; asm("cvt.rn.bf16x2.f32 %0, %1, %2;" : "=r"(r) : "f"(hi), "f"(lo)); return r;
}
__device__ __forceinline__ float bf_lo(uint32_t v) { return __uint_as_float(v << 16); }
__device__ __forceinline__ float bf_hi(uint32_t v) { return __uint_as_float(v & 0xFFFF0000u); }

__device__ __forceinline__ uint4 ld_relaxed4(const void* p) {
  uint4 v; asm volatile("ld.relaxed.gpu.global.v4.u32 {%0,%1,%2,%3}, [%4];" : "=r"(v.x), "=r"(v.y), "=r"(v.z), "=r"(v.w) : "l"(p) : "memory"); return v;
}
__device__ __forceinline__ void st_b128(void* p, uint32_t a, uint32_t b, uint32_t c, uint32_t d) {
  asm volatile("{.reg .b128 v; mov.b128 v, {%1,%2,%3,%4}; st.relaxed.gpu.global.b128 [%0], v;}" :: "l"(p), "r"(a), "r"(b), "r"(c), "r"(d) : "memory");
}
__device__ __forceinline__ void reload_b128(uint4& v, const void* p, uint32_t again) {
  asm volatile("{.reg .pred p; .reg .b128 v; setp.ne.u32 p, %5, 0; mov.b128 v, {%0,%1,%2,%3};\n"
               "@p ld.relaxed.gpu.global.b128 v, [%4]; mov.b128 {%0,%1,%2,%3}, v;}"
    : "+r"(v.x), "+r"(v.y), "+r"(v.z), "+r"(v.w) : "l"(p), "r"(again) : "memory");
}
__device__ __forceinline__ void reload4(uint4& v, const void* p, uint32_t again) {
  asm volatile("{.reg .pred p; setp.ne.u32 p, %5, 0; @p ld.relaxed.gpu.global.v4.u32 {%0,%1,%2,%3}, [%4];}"
    : "+r"(v.x), "+r"(v.y), "+r"(v.z), "+r"(v.w) : "l"(p), "r"(again) : "memory");
}
__device__ __forceinline__ void st_relaxed4(void* p, uint32_t a, uint32_t b, uint32_t c, uint32_t d) {
  asm volatile("st.relaxed.gpu.global.v4.u32 [%0], {%1,%2,%3,%4};" :: "l"(p), "r"(a), "r"(b), "r"(c), "r"(d) : "memory");
}
__device__ __forceinline__ void st_relaxed_if(void* p, uint32_t a, bool on) {
  asm volatile("{.reg .pred p; setp.ne.u32 p, %2, 0; @p st.relaxed.gpu.global.u32 [%0], %1;}" :: "l"(p), "r"(a), "r"((uint32_t)on) : "memory");
}
__device__ __forceinline__ uint32_t ld_acquire(const uint32_t* p) {
  uint32_t v; asm volatile("ld.acquire.gpu.global.u32 %0, [%1];" : "=r"(v) : "l"(p) : "memory"); return v;
}
__device__ __forceinline__ void st_release(uint32_t* p, uint32_t v) {
  asm volatile("st.release.gpu.global.u32 [%0], %1;" :: "l"(p), "r"(v) : "memory");
}
__device__ __forceinline__ void bulk_reduce(float* dst, uint32_t src, uint32_t bytes) {
  asm volatile("cp.reduce.async.bulk.global.shared::cta.bulk_group.add.f32 [%0], [%1], %2;" :: "l"(dst), "r"(src), "r"(bytes) : "memory");
}
__device__ __forceinline__ void bulk_done_inc(uint32_t* p) {
  asm volatile("cp.async.bulk.wait_group 0;\n"
               "fence.proxy.async.global;\nfence.release.gpu;\n"
               "red.relaxed.gpu.global.add.u32 [%0], 1;\nred.relaxed.gpu.global.add.u32 [%0+4096], 1;" :: "l"(p) : "memory");
}
__device__ __forceinline__ void flag_release(uint32_t* p, uint32_t v) {
  asm volatile("fence.release.gpu;\nst.relaxed.gpu.global.u32 [%0], %1;\nst.relaxed.gpu.global.u32 [%0+4096], %1;" :: "l"(p), "r"(v) : "memory");
}
__device__ __forceinline__ void spin_guard(int& it) {
  asm volatile("{.reg .pred p; add.s32 %0, %0, 1; setp.gt.s32 p, %0, %1; @p trap;}" : "+r"(it) : "n"(SPIN_MAX));
}
__device__ __forceinline__ void wait_flag(const uint32_t* p, uint32_t v) {
  int it = 0;
  while (ld_acquire(p) < v) spin_guard(it);
}
__device__ __forceinline__ void wait_flags(const uint32_t* p, uint32_t v) {
  int it = 0;
  while (true) {
    uint32_t x; asm volatile("ld.relaxed.gpu.global.u32 %0, [%1];" : "=r"(x) : "l"(p) : "memory");
    if (__all_sync(~0u, x >= v)) break;
    spin_guard(it);
  }
  asm volatile("fence.acquire.gpu;" ::: "memory");
}
__device__ __forceinline__ uint32_t timer_offset() {
  uint32_t g0, g;
  asm volatile("mov.u32 %0, %%globaltimer_lo;" : "=r"(g0) :: "memory");
  do { asm volatile("mov.u32 %0, %%globaltimer_lo;" : "=r"(g) :: "memory"); } while (g == g0);
  return (g >> 5) * 58 - clk();
}
__device__ __forceinline__ void grid_arrive(int i) {
  asm volatile("red.release.gpu.global.add.u32 [%0], %1;" :: "l"(g_gbar + i * 32), "r"(bid() ? 1u : 257u - N_CTA) : "memory");
}
__device__ __forceinline__ void grid_wait(int i, uint32_t gen) {
  int it = 0;
  while (((ld_acquire(g_gbar + i * 32) ^ gen) >> 8) == 0) spin_guard(it);
}
__device__ __forceinline__ bool elect() {
  uint32_t r; asm volatile("{.reg .pred p; elect.sync _|p, -1; selp.u32 %0, 1, 0, p;}" : "=r"(r)); return r;
}
__device__ __forceinline__ void bar_sync(int id, int cnt) { asm volatile("bar.sync %0, %1;" :: "r"(id), "r"(cnt) : "memory"); }
__device__ __forceinline__ void bar_arrive(int id, int cnt) { asm volatile("bar.arrive %0, %1;" :: "r"(id), "r"(cnt) : "memory"); }
template <int id, int cnt> __device__ __forceinline__ void bar_arrive_after(uint32_t a, uint32_t b) {
  asm volatile("{.reg .pred p; setp.ne.u32 p, %2, 0xfff12345; setp.ne.and.u32 p, %3, 0xfff12345, p; @p bar.arrive %0, %1;}" :: "n"(id), "n"(cnt), "r"(a), "r"(b) : "memory");
}
template <int id, int cnt> __device__ __forceinline__ void bar_sync_after(uint32_t a) {
  asm volatile("{.reg .pred p; setp.ne.u32 p, %2, 0xfff12345; @p bar.sync %0, %1;}" :: "n"(id), "n"(cnt), "r"(a) : "memory");
}
__device__ __forceinline__ void fence_async_smem() { asm volatile("fence.proxy.async.shared::cta;" ::: "memory"); }
__device__ __forceinline__ void fence_async_global() { asm volatile("fence.proxy.async.global;" ::: "memory"); }
__device__ __forceinline__ void mbar_init(uint32_t mb, int cnt) { asm volatile("mbarrier.init.shared::cta.b64 [%0], %1;" :: "r"(mb), "r"(cnt) : "memory"); }
__device__ __forceinline__ void mbar_arrive(uint32_t mb) { asm volatile("mbarrier.arrive.shared::cta.b64 _, [%0];" :: "r"(mb) : "memory"); }
__device__ __forceinline__ void mbar_arrive_after(uint32_t mb, uint32_t a, uint32_t lane) {
  asm volatile("{.reg .pred p; setp.ne.u32 p, %1, 0xfff12345; setp.eq.and.u32 p, %2, 0, p; @p mbarrier.arrive.shared::cta.b64 _, [%0];}" :: "r"(mb), "r"(a), "r"(lane) : "memory");
}
__device__ __forceinline__ void mbar_expect(uint32_t mb, uint32_t bytes) {
  asm volatile("mbarrier.arrive.expect_tx.shared::cta.b64 _, [%0], %1;" :: "r"(mb), "r"(bytes) : "memory");
}
__device__ __forceinline__ void mbar_wait_guard(uint32_t mb, uint32_t parity) {
  uint32_t ok; int it = 0;
  while (true) {
    asm volatile("{.reg .pred p; mbarrier.try_wait.parity.shared::cta.b64 p, [%1], %2; selp.u32 %0, 1, 0, p;}" : "=r"(ok) : "r"(mb), "r"(parity) : "memory");
    if (ok) break;
    spin_guard(it);
  }
}
__device__ __forceinline__ void mbar_wait(uint32_t mb, uint32_t parity) {
  asm volatile("{.reg .pred p;\nW: mbarrier.try_wait.parity.shared::cta.b64 p, [%0], %1;\n@!p bra W;}" :: "r"(mb), "r"(parity) : "memory");
}
__device__ __forceinline__ void bulk_load(uint32_t dst, const void* src, uint32_t bytes, uint32_t mb) {
  asm volatile("cp.async.bulk.shared::cluster.global.mbarrier::complete_tx::bytes [%0], [%1], %2, [%3];" :: "r"(dst), "l"(src), "r"(bytes), "r"(mb) : "memory");
}
__device__ __forceinline__ void bulk_store(void* dst, uint32_t src, uint32_t bytes) {
  asm volatile("cp.async.bulk.global.shared::cta.bulk_group [%0], [%1], %2;" :: "l"(dst), "r"(src), "r"(bytes) : "memory");
}
__device__ __forceinline__ void cp_async16(uint32_t dst, const void* src) {
  asm volatile("cp.async.cg.shared.global [%0], [%1], 16;" :: "r"(dst), "l"(src) : "memory");
}
__device__ __forceinline__ void cp_async_wait_all() { asm volatile("cp.async.wait_all;" ::: "memory"); }
__device__ __forceinline__ uint32_t mapa(uint32_t a, uint32_t rank) {
  uint32_t r; asm("mapa.shared::cluster.u32 %0, %1, %2;" : "=r"(r) : "r"(a), "r"(rank)); return r;
}
__device__ __forceinline__ void st_async4(uint32_t dst, float a, float b, float c, float d, uint32_t mb) {
  asm volatile("st.async.shared::cluster.mbarrier::complete_tx::bytes.v4.f32 [%0], {%1,%2,%3,%4}, [%5];" :: "r"(dst), "f"(a), "f"(b), "f"(c), "f"(d), "r"(mb) : "memory");
}
__device__ __forceinline__ void st_async2(uint32_t dst, float a, float b, uint32_t mb) {
  asm volatile("st.async.shared::cluster.mbarrier::complete_tx::bytes.v2.f32 [%0], {%1,%2}, [%3];" :: "r"(dst), "f"(a), "f"(b), "r"(mb) : "memory");
}
__device__ __forceinline__ void st_async1(uint32_t dst, uint32_t a, uint32_t mb) {
  asm volatile("st.async.shared::cluster.mbarrier::complete_tx::bytes.u32 [%0], %1, [%2];" :: "r"(dst), "r"(a), "r"(mb) : "memory");
}
__device__ __forceinline__ uint4 lds128(uint32_t a) {
  uint4 v; asm volatile("ld.shared.v4.u32 {%0,%1,%2,%3}, [%4];" : "=r"(v.x), "=r"(v.y), "=r"(v.z), "=r"(v.w) : "r"(a) : "memory"); return v;
}
__device__ __forceinline__ uint2 lds64(uint32_t a) {
  uint2 v; asm volatile("ld.shared.v2.u32 {%0,%1}, [%2];" : "=r"(v.x), "=r"(v.y) : "r"(a) : "memory"); return v;
}
__device__ __forceinline__ uint32_t lds32(uint32_t a) {
  uint32_t v; asm volatile("ld.shared.u32 %0, [%1];" : "=r"(v) : "r"(a) : "memory"); return v;
}
__device__ __forceinline__ void sts128(uint32_t a, uint4 v) {
  asm volatile("st.shared.v4.u32 [%0], {%1,%2,%3,%4};" :: "r"(a), "r"(v.x), "r"(v.y), "r"(v.z), "r"(v.w) : "memory");
}
__device__ __forceinline__ void sts64(uint32_t a, uint32_t x, uint32_t y) {
  asm volatile("st.shared.v2.u32 [%0], {%1,%2};" :: "r"(a), "r"(x), "r"(y) : "memory");
}
__device__ __forceinline__ void sts32(uint32_t a, uint32_t x) { asm volatile("st.shared.u32 [%0], %1;" :: "r"(a), "r"(x) : "memory"); }
__device__ __forceinline__ void ldsm4(uint32_t& r0, uint32_t& r1, uint32_t& r2, uint32_t& r3, uint32_t a) {
  asm volatile("ldmatrix.sync.aligned.m8n8.x4.shared.b16 {%0,%1,%2,%3}, [%4];" : "=r"(r0), "=r"(r1), "=r"(r2), "=r"(r3) : "r"(a) : "memory");
}
__device__ __forceinline__ void ldsm4t(uint32_t& r0, uint32_t& r1, uint32_t& r2, uint32_t& r3, uint32_t a) {
  asm volatile("ldmatrix.sync.aligned.m8n8.x4.trans.shared.b16 {%0,%1,%2,%3}, [%4];" : "=r"(r0), "=r"(r1), "=r"(r2), "=r"(r3) : "r"(a) : "memory");
}
__device__ __forceinline__ void stsm4(uint32_t a, uint32_t r0, uint32_t r1, uint32_t r2, uint32_t r3) {
  asm volatile("stmatrix.sync.aligned.m8n8.x4.shared.b16 [%0], {%1,%2,%3,%4};" :: "r"(a), "r"(r0), "r"(r1), "r"(r2), "r"(r3) : "memory");
}
__device__ __forceinline__ uint32_t movmat(uint32_t a) {
  uint32_t d; asm volatile("movmatrix.sync.aligned.m8n8.trans.b16 %0, %1;" : "=r"(d) : "r"(a)); return d;
}
__device__ __forceinline__ void mma16(float* d, uint32_t a0, uint32_t a1, uint32_t a2, uint32_t a3, uint32_t b0, uint32_t b1) {
  asm volatile("mma.sync.aligned.m16n8k16.row.col.f32.bf16.bf16.f32 {%0,%1,%2,%3}, {%4,%5,%6,%7}, {%8,%9}, {%0,%1,%2,%3};"
    : "+f"(d[0]), "+f"(d[1]), "+f"(d[2]), "+f"(d[3]) : "r"(a0), "r"(a1), "r"(a2), "r"(a3), "r"(b0), "r"(b1));
}
__device__ __forceinline__ void mma8(float* d, uint32_t a0, uint32_t a1, uint32_t b0) {
  asm volatile("mma.sync.aligned.m16n8k8.row.col.f32.bf16.bf16.f32 {%0,%1,%2,%3}, {%4,%5}, {%6}, {%0,%1,%2,%3};"
    : "+f"(d[0]), "+f"(d[1]), "+f"(d[2]), "+f"(d[3]) : "r"(a0), "r"(a1), "r"(b0));
}
__device__ __forceinline__ float rcp(float x) { float r; asm("rcp.approx.ftz.f32 %0, %1;" : "=f"(r) : "f"(x)); return r; }
__device__ __forceinline__ float ex2(float x) { float r; asm("ex2.approx.ftz.f32 %0, %1;" : "=f"(r) : "f"(x)); return r; }

__host__ __device__ constexpr uint64_t mkdesc(uint32_t off, uint32_t lbo, uint32_t sbo, uint32_t swz) {
  return (uint64_t)((SBASE + off) >> 4) | ((uint64_t)(lbo >> 4) << 16) | ((uint64_t)(sbo >> 4) << 32) | ((uint64_t)swz << 62);
}
__host__ __device__ constexpr uint64_t desc_sw128(uint32_t off) { return mkdesc(off, 16, 1024, 1); }
__host__ __device__ constexpr uint64_t desc_n16(uint32_t off) { return mkdesc(off, 256, 128, 0); }
__host__ __device__ constexpr uint64_t desc_m(uint32_t off) { return mkdesc(off, 16, 256, 3); }

__host__ __device__ constexpr uint64_t desc_sw64(uint32_t off) { return mkdesc(off, 16, 512, 2); }

__device__ __forceinline__ void wg_fence() { asm volatile("wgmma.fence.sync.aligned;" ::: "memory"); }
__device__ __forceinline__ void wg_commit() { asm volatile("wgmma.commit_group.sync.aligned;" ::: "memory"); }
template <int N> __device__ __forceinline__ void wg_wait() { asm volatile("wgmma.wait_group.sync.aligned %0;" :: "n"(N) : "memory"); }

#define ACC8(d) "+f"(d[0]), "+f"(d[1]), "+f"(d[2]), "+f"(d[3]), "+f"(d[4]), "+f"(d[5]), "+f"(d[6]), "+f"(d[7])
#define ACC32(d) ACC8(d), ACC8((d + 8)), ACC8((d + 16)), ACC8((d + 24))
#define R8 "{%0,%1,%2,%3,%4,%5,%6,%7}"
#define R32 "{%0,%1,%2,%3,%4,%5,%6,%7,%8,%9,%10,%11,%12,%13,%14,%15,%16,%17,%18,%19,%20,%21,%22,%23,%24,%25,%26,%27,%28,%29,%30,%31}"
template <int SD> __device__ __forceinline__ void wg_rs16(float* d, const uint32_t* a, uint64_t db) {
  asm volatile("wgmma.mma_async.sync.aligned.m64n16k16.f32.bf16.bf16 " R8 ", {%8,%9,%10,%11}, %12, %13, 1, 1, 1;"
    : ACC8(d) : "r"(a[0]), "r"(a[1]), "r"(a[2]), "r"(a[3]), "l"(db), "n"(SD));
}
template <int SD> __device__ __forceinline__ void wg_ss16(float* d, uint64_t da, uint64_t db) {
  asm volatile("wgmma.mma_async.sync.aligned.m64n16k16.f32.bf16.bf16 " R8 ", %8, %9, %10, 1, 1, 1, 1;"
    : ACC8(d) : "l"(da), "l"(db), "n"(SD));
}
template <int SD, uint64_t DA, uint64_t DB> __device__ __forceinline__ void wg_ss16o(float* d, uint32_t oa, uint32_t ob) {
  asm volatile("{.reg .b32 x, y; .reg .b64 a, b; add.u32 x, %8, %10; add.u32 y, %9, %12; mov.b64 a, {x, %11}; mov.b64 b, {y, %13};\n"
               "wgmma.mma_async.sync.aligned.m64n16k16.f32.bf16.bf16 " R8 ", a, b, %14, 1, 1, 1, 1;}"
    : ACC8(d) : "r"(oa), "r"(ob), "n"((uint32_t)DA), "n"((uint32_t)(DA >> 32)), "n"((uint32_t)DB), "n"((uint32_t)(DB >> 32)), "n"(SD));
}
template <int SD> __device__ __forceinline__ void wg_rs64(float* d, const uint32_t* a, uint64_t db) {
  asm volatile("wgmma.mma_async.sync.aligned.m64n64k16.f32.bf16.bf16 " R32 ", {%32,%33,%34,%35}, %36, %37, 1, 1, 0;"
    : ACC32(d) : "r"(a[0]), "r"(a[1]), "r"(a[2]), "r"(a[3]), "l"(db), "n"(SD));
}
template <int SD> __device__ __forceinline__ void wg_ss64(float* d, uint64_t da, uint64_t db) {
  asm volatile("wgmma.mma_async.sync.aligned.m64n64k16.f32.bf16.bf16 " R32 ", %32, %33, %34, 1, 1, 1, 0;"
    : ACC32(d) : "l"(da), "l"(db), "n"(SD));
}
#define WG_RSO(NAME, SHAPE, REGS, ACC, A, TB) \
template <int SD, uint64_t DB> __device__ __forceinline__ void NAME(float* d, uint32_t a0, uint32_t a1, uint32_t a2, uint32_t a3, uint32_t ob) { \
  asm volatile("{.reg .b64 b; mov.b64 b, {" A(4) ", " A(5) "};\nwgmma.mma_async.sync.aligned." SHAPE ".f32.bf16.bf16 " REGS \
               ", {" A(0) "," A(1) "," A(2) "," A(3) "}, b, " A(6) ", 1, 1, " TB ";}" \
    : ACC(d) : "r"(a0), "r"(a1), "r"(a2), "r"(a3), "r"(ob + (uint32_t)DB), "n"((uint32_t)(DB >> 32)), "n"(SD)); \
}
#define ACC4(d) "+f"(d[0]), "+f"(d[1]), "+f"(d[2]), "+f"(d[3])
#define ACC16(d) ACC8(d), ACC8((d + 8))
#define OP4(i) OP4_##i
#define OP4_0 "%4"
#define OP4_1 "%5"
#define OP4_2 "%6"
#define OP4_3 "%7"
#define OP4_4 "%8"
#define OP4_5 "%9"
#define OP4_6 "%10"
#define OP16(i) OP16_##i
#define OP16_0 "%16"
#define OP16_1 "%17"
#define OP16_2 "%18"
#define OP16_3 "%19"
#define OP16_4 "%20"
#define OP16_5 "%21"
#define OP16_6 "%22"
#define OP32(i) OP32_##i
#define OP32_0 "%32"
#define OP32_1 "%33"
#define OP32_2 "%34"
#define OP32_3 "%35"
#define OP32_4 "%36"
#define OP32_5 "%37"
#define OP32_6 "%38"
WG_RSO(wg_rs8o, "m64n8k16", "{%0,%1,%2,%3}", ACC4, OP4, "1")
#define R16 "{%0,%1,%2,%3,%4,%5,%6,%7,%8,%9,%10,%11,%12,%13,%14,%15}"
WG_RSO(wg_rs32o, "m64n32k16", R16, ACC16, OP16, "1")
WG_RSO(wg_rs64o, "m64n64k16", R32, ACC32, OP32, "0")
WG_RSO(wg_rs32k, "m64n32k16", R16, ACC16, OP16, "0")
template <uint64_t DA, uint64_t DB> __device__ __forceinline__ void wg_ss32k(float* d, uint32_t ob) {
  asm volatile("{.reg .b64 b; mov.b64 b, {%17, %18};\nwgmma.mma_async.sync.aligned.m64n32k16.f32.bf16.bf16 " R16 ", %16, b, 1, 1, 1, 1, 0;}"
    : ACC16(d) : "l"(DA), "r"(ob + (uint32_t)DB), "n"((uint32_t)(DB >> 32)));
}
template <int N> __device__ __forceinline__ void reg_inc() { asm volatile("setmaxnreg.inc.sync.aligned.u32 %0;" :: "n"(N)); }
template <int N> __device__ __forceinline__ void reg_dec() { asm volatile("setmaxnreg.dec.sync.aligned.u32 %0;" :: "n"(N)); }
__device__ __forceinline__ void cluster_sync() {
  asm volatile("barrier.cluster.arrive.relaxed.aligned;\nbarrier.cluster.wait.aligned;" ::: "memory");
}

template <int KS>
__device__ __forceinline__ void load_frags(uint32_t* a, uint32_t src) {
  const int lane = threadIdx.x & 31, w = (threadIdx.x >> 5) & 3;
  const int k = ((lane >> 4) << 3) + (lane & 7), u = w * 2 + ((lane >> 3) & 1);
  const uint32_t base = src + k * 128 + ((u ^ (k & 7)) << 4);
#pragma unroll
  for (int ks = 0; ks < KS; ks++) ldsm4t(a[ks * 4], a[ks * 4 + 1], a[ks * 4 + 2], a[ks * 4 + 3], base + ks * 2048);
}

__device__ __forceinline__ uint32_t badd2(uint32_t a, uint32_t b) { uint32_t r; asm("add.rn.bf16x2 %0, %1, %2;" : "=r"(r) : "r"(a), "r"(b)); return r; }
__device__ __forceinline__ uint32_t bsub2(uint32_t a, uint32_t b) { uint32_t r; asm("sub.rn.bf16x2 %0, %1, %2;" : "=r"(r) : "r"(a), "r"(b)); return r; }
__device__ __forceinline__ uint32_t bmul2(uint32_t a, uint32_t b) { uint32_t r; asm("mul.rn.bf16x2 %0, %1, %2;" : "=r"(r) : "r"(a), "r"(b)); return r; }
__device__ __forceinline__ uint32_t bfma2(uint32_t a, uint32_t b, uint32_t c) { uint32_t r; asm("fma.rn.bf16x2 %0, %1, %2, %3;" : "=r"(r) : "r"(a), "r"(b), "r"(c)); return r; }
template <int R> __device__ __forceinline__ void layernorm9(const uint32_t* x, uint32_t* o) {
  const uint32_t ones = 0x3F803F80u;
  float a[R][3][4], q[R], s[R];
#pragma unroll
  for (int i = 0; i < 9 * R; i++) {
    float* d = a[i % R][i / R % 3];
    if (i < 3 * R) d[0] = d[1] = d[2] = d[3] = 0.f;
    mma8(d, x[i % R * 9 + i / R], ones, x[i % R * 9 + i / R]);
  }
#pragma unroll
  for (int r = 0; r < R; r++) {
    q[r] = threadIdx.x & 4 ? a[r][0][1] + a[r][1][1] + a[r][2][1] : a[r][0][0] + a[r][1][0] + a[r][2][0];
    s[r] = (a[r][0][2] + a[r][0][3]) + (a[r][1][2] + a[r][1][3]) + (a[r][2][2] + a[r][2][3]);
  }
#pragma unroll
  for (int r = 0; r < R; r++) { q[r] += __shfl_xor_sync(~0u, q[r], 4); s[r] += __shfl_xor_sync(~0u, s[r], 1); }
#pragma unroll
  for (int r = 0; r < R; r++) { q[r] += __shfl_xor_sync(~0u, q[r], 9); s[r] += __shfl_xor_sync(~0u, s[r], 2); }
#pragma unroll
  for (int r = 0; r < R; r++) q[r] = __shfl_sync(~0u, q[r], 0) + __shfl_sync(~0u, q[r], 18);
#pragma unroll
  for (int r = 0; r < R; r++) {
    const float mean = s[r] * (1.f / DM), var = fmaxf(fmaf(q[r], 1.f / DM, -mean * mean), 0.f);
    float sd;
    asm("sqrt.approx.ftz.f32 %0, %1;" : "=f"(sd) : "f"(bf_lo(pack2(bf_lo(pack2(var, 0.f)) + 1e-5f, 0.f))));
    const float inv = rcp(bf_lo(pack2(sd, 0.f)));
    const uint32_t mb = pack2(mean, mean), hi = pack2(inv, inv), lo = pack2(inv - bf_lo(hi), inv - bf_lo(hi));
#pragma unroll
    for (int i = r * 9; i < r * 9 + 9; i++) {
      const uint32_t d = bsub2(x[i], mb);
      o[i] = bfma2(d, hi, bmul2(d, lo));
    }
  }
}
__device__ __forceinline__ void store_ln_row(int layer, int tok, const uint32_t* o) {
  const int lane = threadIdx.x & 31, r = tok & 31;
  unsigned char* p = g_lnimg + (size_t)(layer * NSEG + (tok >> 5)) * (9 * 4096) + r * 128 + (((lane >> 2) ^ (r & 7)) << 4) + (lane & 3) * 4;
#pragma unroll
  for (int i = 0; i < 9; i++) *(uint32_t*)(p + i * 4096) = o[i];
}
struct Params { CUtensorMap map[11]; const bf16 *X, *K, *V, *shift, *Hk, *Dk, *mem0, *Wq, *Wk, *Wv, *Wo; bf16* out; uint32_t dly[24]; };
#define PACE P.dly[20]
#define S1G P.dly[21]
#define S1DLY P.dly[22]
#define DLYS P.dly[0]
#define DLYW P.dly[1]
#define KLATE P.dly[2]
#define DLYQ P.dly[3]
#define DLYK P.dly[4]
#define DLYG P.dly[5]
#define KWIN P.dly[6]
#define KMIN P.dly[7]
uint32_t h_dly[24] = {900, 350, 100, 60, 3570, 4120, 2750, 1300, 1600, 1690, 1800, 2120, 2250, 2380, 2950, 3060, 3230, 3380, 3530, 7500, 165, 12000, 18000, 4000};

constexpr uint32_t C_W = 0, C_M = 147456, C_KV = C_M + 18432, C_OS = C_KV + 24576, C_QM = C_KV + 32768, C_KM = C_QM + 2048,
                   C_VM = C_KM + 2048, C_OI = C_VM + 2048, C_SX = C_OI + 4096, C_KM2 = C_SX + 2560, C_VM2 = C_KM2 + 128,
                   C_KV2 = C_KM2 + 2048, C_Q = C_KV2 + 8192, C_BAR = C_Q + 8192;
constexpr uint32_t CB_FULL = C_BAR, CB_REF = C_BAR + 16, CB_SX = C_BAR + 32, CB_OX = C_BAR + 40, CB_XX = C_BAR + 48, CB_Q = C_BAR + 56, C_BAD = C_BAR + 64, W_BAR = C_BAR + 80, T_BAR = W_BAR + 24, S_GEN = C_BAR + 128, C_REF = C_BAR + 132, CB_VF = C_BAR + 144, CB_M = C_BAR + 160, CB_MV = C_BAR + 200;
constexpr uint32_t G_W = 0, G_RING = 147456, G_W2 = G_RING + 9 * 8192, G_BAR = G_W2 + 8192;
constexpr uint32_t O_W = 0, O_RING = 3 * 40960, O_ST = O_RING + 11 * 8192, O_BAR = O_ST + 16384, OB_ST = O_BAR + 64;
constexpr uint32_t F_A = 0, F_XY = 36864, F_L = F_XY + 36864, F_X = F_L + 18432, F_Y = F_L + 2 * 36864, F_BAR = C_BAR;
constexpr uint32_t SMEM_BYTES = C_BAR + 256;
static_assert(G_BAR + 256 <= SMEM_BYTES && O_BAR + 256 <= SMEM_BYTES && F_BAR + 16 <= SMEM_BYTES && SMEM_BYTES <= 232448, "smem map");
enum { B_INIT = 1, B_M, B_QK, B_S, B_V, B_O, B_X, B_WG0, B_WG1, B_WG2, B_G, B_OE, B_T, B_R };

__device__ __forceinline__ uint4 pack_partial(const float* d, uint32_t tag) {
  uint32_t x;
  asm("lop3.b32 %0, %1, 1, %2, 0xb8;" : "=r"(x) : "r"(pack2(d[0], d[1])), "r"(tag));
  return make_uint4(x, pack2(d[4], d[5]), pack2(d[2], d[3]), pack2(d[6], d[7]));
}
__device__ __forceinline__ void store_partial(uint4* p, const uint4& v) { st_b128(p, v.x, v.y, v.z, v.w); }
__device__ __forceinline__ void gather_reduce(const uint32_t* p, uint32_t* dst, uint32_t m0, bool shared, uint32_t tag, uint32_t lane, uint32_t sb, int n, int TS0) {
  int tries = 0;
  bool bad;
  TR(TS0);
  do {
    uint2 x[8];
#pragma unroll
    for (int i = 0; i < 8; i++)
      asm volatile("{.reg .b64 v; ld.relaxed.gpu.global.b64 v, [%2]; mov.b64 {%0, %1}, v;}" : "=r"(x[i].x), "=r"(x[i].y) : "l"(p + i * 128) : "memory");
    spin_guard(tries);
    float a = bf_lo(x[0].x), b = bf_hi(x[0].x), c = bf_lo(x[0].y), d = bf_hi(x[0].y);
    uint32_t t = x[0].x ^ tag;
#pragma unroll
    for (int i = 1; i < 8; i++) {
      a += bf_lo(x[i].x); b += bf_hi(x[i].x); c += bf_lo(x[i].y); d += bf_hi(x[i].y);
      asm("lop3.b32 %0, %0, %1, %2, 0xf6;" : "+r"(t) : "r"(x[i].x), "r"(tag));
    }
    bad = __any_sync(~0u, t & ~lane & 1);
    const bool up = lane & 8;
    float u = (up ? c : a) + __shfl_xor_sync(~0u, up ? a : c, 8), v = (up ? d : b) + __shfl_xor_sync(~0u, up ? b : d, 8);
    if (shared) { u += __shfl_xor_sync(~0u, u, 4); v += __shfl_xor_sync(~0u, v, 4); }
    u += __shfl_xor_sync(~0u, u, 16);
    v += __shfl_xor_sync(~0u, v, 16);
    st_relaxed_if(dst, n < LAG && up ? m0 : pack2(u, v), !bad);
  } while (bad);
  TR(TS0 + 3); TRV(TS0 + 2, tries);
  CNT((TS0 - 16) >> 2, tries);
}
__device__ __forceinline__ uint32_t sent_bad(const uint4& v) { return max(max(v.x, v.y), max(v.z, v.w)) == SENT; }

__host__ __device__ constexpr int o_ks(int s) { return s & (s < 8 ? 3 : 7); }
__host__ __device__ constexpr bool o_reg(int s) { return s < 8 ? (s & 3) != 3 : !(s & 1); }
__host__ __device__ constexpr int o_slot(int s) { return s < 8 ? (o_reg(s) ? s - (s >> 2) : s >> 2) : s & 1 ? (s - 5) >> 1 : (s + 4) >> 1; }
__device__ __forceinline__ int g_unit(int wg) {
  const int i = bid() - N_CHAIN;
  return i < 32 ? wg * 64 + i : 2 * i - 32 + wg;
}
__device__ __forceinline__ uint32_t pinned(uint32_t v) { return __shfl_sync(~0u, v, threadIdx.x & 31); }
template <class T> __device__ __forceinline__ T* pinned(T* p) { return (T*)__shfl_sync(~0u, (unsigned long long)p, threadIdx.x & 31); }
enum { CHAIN, GROLE, OROLE };
template <int ROLE, bool SYNC> __device__ __forceinline__ void load_box(const Params& P, uint32_t sb, bool regs, int wg, int i, uint32_t mb, bool on) {
  const int b = bid();
  int map, col = 0, ks = 0, c2 = 0, c3 = 0;
  uint32_t dst = wg * 73728;
  if (ROLE == CHAIN) {
    const int k = i - 1, st = regs ? (k < 6 ? k + k / 3 : 2 * k - 4) : k < 2 ? 4 * k + 3 : 2 * k + 5;
    dst += i ? (17 + i) * 2048 : 0;
    if (wg || i == 0) { map = wg + i; col = b * 64; c3 = !regs; }
    else if (!regs && k >= 14) { map = 6; ks = b * 4 + k - 14; }
    else { map = 6; col = 64 + (st < 8 ? (st >> 2) * 64 : (st >> 3) * 128 + (b & 1) * 64); ks = (b * 4) ^ o_ks(st); }
  } else if (ROLE == GROLE) {
    const int q = g_unit(wg);
    map = ((q >> 5) + 1) % 3;
    if (i) { map += 3; col = (q & 31) * 128 + (i - 1) * 64; ks = 34; dst = G_W2 + wg * 4096 + (i - 1) * 2048; }
    else { map += 8; c2 = (q & 31) * 2; c3 = !regs; }
  } else {
    const int o = b - N_CHAIN - N_G, ksl = o / 3;
    map = 7; col = ((o % 3) * 3 + (wg + ksl) % 3) * 64; dst = (wg * (regs ? 24 : 20) + i) * 2048;
    ks = (ksl * 11 - max(ksl - 4, 0)) * 4 + (regs ? i / 3 * 5 + i % 3 * 2 : i < 16 ? i / 2 * 5 + 1 + i % 2 * 2 : i + 24);
    c3 = (ks & 1) * 2; ks >>= 1;
  }
  if (SYNC) { col = pinned(col); ks = pinned(ks); bar_sync(B_WG0 + wg, 256); }
  if (on) asm volatile("cp.async.bulk.tensor.5d.shared::cluster.global.tile.mbarrier::complete_tx::bytes [%0], [%1, {%2, %3, %4, %5, %6}], [%7];"
               :: "r"(sb + dst), "l"(&P.map[map]), "r"(col), "r"(0), "r"(c2), "r"(c3), "r"(ks), "r"(mb) : "memory");
}
template <int ROLE, bool SYNC = false> __device__ __forceinline__ void load_wg(const Params& P, uint32_t sb, bool regs, int wg, int quarter) {
  const int i = (threadIdx.x & 31) * 4 + quarter;
  const int n = ROLE == CHAIN ? 36 : ROLE == GROLE ? (regs ? 38 : 36) : regs ? 24 : bid() < N_CHAIN + N_G + 12 ? 20 : 16;
  load_box<ROLE, SYNC>(P, sb, regs, wg, i, sb + W_BAR + wg * 8, i < (ROLE == CHAIN ? (wg ? 2 : 19) : ROLE == GROLE ? n - 35 : n));
  if (i == 0) mbar_expect(sb + W_BAR + wg * 8, n * 2048);
  __syncwarp();
}
__device__ __forceinline__ uint32_t near_half(uint32_t blk, uint32_t reader) {
  return __ldcg(g_near + (blk >> 3)) ^ (~blk & 1) ^ __ldcg(g_side + (blk >> 3)) ^ __ldcg(g_side + reader);
}

__device__ __forceinline__ uint32_t opaque_tid() { uint32_t t; asm volatile("mov.u32 %0, %%tid.x;" : "=r"(t)); return t; }
__device__ __forceinline__ void m_fetch(uint32_t sb, uint32_t src, uint32_t b, uint32_t mb) {
  bulk_load(sb + C_M + (b ? b * 4096 - 2048 : 0), (const unsigned char*)g_mimg + ((src ^ ((b & 1) * 4096)) + b * 8192), b ? 4096 : 2048, mb);
}
__device__ __forceinline__ uint32_t m_probe(uint32_t lane) { return lane * 32 + (lane & 4) * 4 + (lane >> 3) * 4; }
__device__ __forceinline__ uint32_t m_max(uint32_t a, uint32_t b) {
  return max(max(lds32(a), lds32(a + 1024)), max(lds32(b), lds32(b + 1024)));
}
template <int S0, int N> __device__ __forceinline__ void o_steps(float* d, const uint32_t* a) {
  constexpr int SD = o_ks(S0) != 0;
  if constexpr (o_reg(S0)) wg_rs16<SD>(d, a + (18 + o_slot(S0)) * 4, desc_n16(C_OI + o_ks(S0) * 512));
  else wg_ss16<SD>(d, desc_sw128(C_W + (18 + o_slot(S0)) * 2048), desc_n16(C_OI + o_ks(S0) * 512));
  if constexpr (N > 1) o_steps<S0 + 1, N - 1>(d, a);
}
template <int BASE, int KS, int N> __device__ __forceinline__ void m_steps(float* d, const uint32_t* a, uint32_t oa) {
  wg_rs16<KS != 0>(d, a + (BASE + KS / 2) * 4, desc_m(C_M + KS * 512));
  if constexpr (KS >= 36 - 2 * XR) wg_rs16<1>(d, a + (18 + XR + KS / 2) * 4, desc_m(C_M + KS * 512 + 512));
  else wg_ss16o<1, desc_sw128(C_W + (BASE + KS / 2) * 2048), desc_m(C_M + KS * 512 + 512)>(d, oa, 0);
  if constexpr (N > 2) m_steps<BASE, KS + 2, N - 2>(d, a, oa);
}

template <int I, int R, int S> __device__ __forceinline__ void v_steps(float* d, const uint32_t* a) {
  constexpr bool reg = (VPAT >> I) & 1;
  if constexpr (reg) wg_rs16<1>(d, a + (18 + R) * 4, desc_m(C_M + R * 1024));
  else wg_ss16<1>(d, desc_sw128(C_W + (54 + S) * 2048), desc_m(C_M + S * 1024 + 512));
  if constexpr (I < 31) v_steps<I + 1, R + reg, S + !reg>(d, a);
  else static_assert(R + reg == 18, "pattern");
}

__device__ __forceinline__ void chain_proj(const Params& P, uint32_t sb) {
  const uint32_t c = chain_id(), h = c >> 1, j = c & 1, wid = __shfl_sync(~0u, threadIdx.x >> 5, 0), wg = wid >> 2, w = wid & 3;
  const uint32_t t = threadIdx.x & 127, lane = pinned(t & 31), mine = pinned(sb + t * 16), rb = mapa(sb, j ^ 1);
  const uint32_t theirs = pinned(rb + C_KM2 + w * 512 + lane * 4), oa = wg * 4608;
  uint32_t a[144 + 4 * XR];
  mbar_wait(sb + W_BAR + wg * 8, 0);
  if (threadIdx.x == 0) TS(23);
  load_frags<36>(a, sb + C_W + wg * 73728);
  fence_async_smem();
  bar_arrive(B_WG0 + wg, 256);
  if (threadIdx.x == 0) TS(24);
  bar_sync(B_WG2, 384);
  const uint32_t round = min(w, 2u) + (wg ? 0 : 3), gdly = P.dly[8 + round], ps = t >> 2, pf = j * 16 + (ps >> 1);
  uint4* const dsts = pinned(g_xb + (ps * 4096 + near_half(ps * 8, ps * 2) * 256 + c * 4 + (t & 3)));
  uint4* const dstf = pinned(g_xb + (pf * 4096 + 512 + near_half(pf * 8 + 1, pf * 2) * 256 + h * 8 + (t & 7)));
  const uint32_t* const gsrc = (const uint32_t*)g_xb + (h * 16384 + min(w, 2u) * 4096 + near_half(h * 8 + !wg, h * 2) * 1024 +
                               (wg ? (lane & 28) * 4 + j * 8 + (lane & 3) * 2 : 2048 + (lane & 24) * 4 + j * 16 + (lane & 7) * 2));
  uint32_t* gdst = g_mimg + (16384 + (lane >> 4) * 1024 + (lane & 1) * 8 +
                   (wg ? (round ? 1536 + round * 512 : 0) + h * 16 + (((lane >> 1) ^ c) & 4) + j * 2 + ((lane >> 1) & 1)
                       : (round - 1) * 2048 + c * 16 + (((lane >> 1) ^ (c * 2)) & 4) + ((lane >> 1) & 3)));
  const uint32_t m0 = __ldcg(gdst - 16384);
  mbar_wait(sb + W_BAR + wg * 8, 1);
  load_frags<XR>(a + 144, sb + C_W + wg * 73728 + (18 - XR) * 2048);
  bar_sync(B_INIT, 256);
  if ((threadIdx.x & 127) == 0) TS(4);

  uint32_t ring = 1;
#pragma unroll 1
  for (int n = 0; n < STEPS; n++) {
    float d[8], e[8];
#pragma unroll
    for (int i = 0; i < 8; i++) e[i] = 0.f;
    uint32_t redo = n + 1;
#pragma unroll 1
    do {
      mbar_wait(sb + CB_M, n & 1);
      wg_fence();
      m_steps<0, 0, 4>(d, a, oa);
      wg_commit();
      if (wg) { wg_fence(); m_steps<18, 0, 4>(e, a, 4608); wg_commit(); }
      if (wid == 0) TR(8);
      mbar_wait(sb + CB_M + 8, n & 1);
      wg_fence();
      m_steps<0, 4, 8>(d, a, oa);
      wg_commit();
      mbar_wait(sb + CB_MV, n & 1);
      asm volatile("{.reg .pred p; .reg .u32 t; ld.shared.u32 t, [%1]; setp.eq.u32 p, t, %0; selp.u32 %0, -1, 0, p;}" : "+r"(redo) : "r"(sb + C_BAD) : "memory");
    } while (redo);
    wg_fence();
    m_steps<0, 12, 8>(d, a, oa);
    wg_commit();
    mbar_wait(sb + CB_MV + 16, n & 1);
    wg_fence();
    m_steps<0, 20, 8>(d, a, oa);
    wg_commit();
    mbar_wait(sb + CB_MV + 24, n & 1);
    wg_fence();
    m_steps<0, 28, 8>(d, a, oa);
    wg_commit();
    wg_wait<0>();
    if (w == 0) TR(6 + wg);
    const uint32_t f0 = pack2(d[0], d[1]), f1 = pack2(d[4], d[5]), f2 = pack2(d[2], d[3]), f3 = pack2(d[6], d[7]);
    stsm4(mine + C_QM + wg * 2048, f0, f1, f2, f3);
    bar_arrive(B_QK, 416);
    const uint32_t tag = (n & 1) ^ 1;
    if (wg) {
      if (n + 1 < STEPS) bar_sync(B_S, 256);
      wg_fence();
      v_steps<0, 2, 2>(e, a);
      wg_commit();
      const uint32_t k0 = j ? f0 : f1, k1 = j ? f2 : f3;
      if (SAFE & 1) mbar_wait(sb + CB_SX, n & 1);
      wg_wait<0>();
      if (w == 0) TR(11);
      const uint32_t v0 = pack2(e[0], e[1]), v1 = pack2(e[4], e[5]), v2 = pack2(e[2], e[3]), v3 = pack2(e[6], e[7]);
      stsm4(mine + C_VM, v0, v1, v2, v3);
      bar_arrive(B_V, 256);
      st_async1(theirs, k0, rb + CB_XX);
      st_async1(theirs + 256, k1, rb + CB_XX);
      st_async1(theirs + 128, j ? v0 : v1, rb + CB_XX);
      st_async1(theirs + 384, j ? v2 : v3, rb + CB_XX);
      if (n + 1 == STEPS) break;
      bar_sync(B_O, 256);
      if (!WFENCE) fence_async_smem();
      wg_fence();
#pragma unroll
      for (int ks = 0; ks < 4; ks++) {
        if (ks == 0) wg_ss16<0>(d, desc_sw128(C_W + 32 * 2048), desc_n16(C_OI));
        else wg_ss16<1>(d, desc_sw128(C_W + (32 + ks) * 2048), desc_n16(C_OI + ks * 512));
      }
      wg_commit();
      bar_arrive(B_X, 256);
      if (w == 0) TR(0);
      wg_wait<0>();
      store_partial(dsts, pack_partial(d, tag));
      bar_arrive(B_M, 160);
      if (w == 0) TR(1);
    } else {
      if (n + 1 == STEPS) break;
      bar_sync(B_X, 256);
      wg_fence();
      o_steps<0, 4>(d, a);
      wg_commit();
      o_steps<4, 4>(e, a);
      wg_commit();
      wg_wait<1>();
      store_partial(dsts + 1024, pack_partial(d, tag));
      if (w == 0) TR(2);
      if (OGAP == 0) { wg_fence(); o_steps<8, 4>(d, a); wg_commit(); wg_wait<1>(); } else wg_wait<0>();
      store_partial(dsts + 2048, pack_partial(e, tag));
      if (w == 0) TR(3);
      wg_fence();
      if (OGAP) o_steps<8, 4>(d, a);
      if (OGAP < 2) o_steps<16, 4>(e, a);
      wg_commit();
      bar_sync(B_T, 256);
      if (w == 0) { TRV(61, 0); TR(12); }
      wg_fence();
      o_steps<12, 4>(d, a);
      wg_commit();
      if (OGAP == 2) o_steps<16, 4>(e, a);
      o_steps<20, 4>(e, a);
      wg_commit();
      wg_wait<1>();
      store_partial(dstf, pack_partial(d, tag));
      if (w == 0) TR(4);
      wg_fence();
      o_steps<24, 8>(d, a);
      wg_commit();
      wg_wait<1>();
      store_partial(dstf + 1024, pack_partial(e, tag));
      bar_arrive(B_OE, 256);
      if (w == 0) TR(5);
      wg_wait<0>();
      store_partial(dstf + 2048, pack_partial(d, tag));
      if (w == 0) TR(15);
    }
    if (w < 3) {
      mbar_wait(sb + CB_REF, n & 1);
      wait_until(lds32(sb + C_REF), gdly);
      gather_reduce(gsrc, gdst, m0, wg, tag, lane, sb, n, 16 + round * 4);
      if (++ring == MRING) { ring = 0; gdst -= MRING * 16384; }
      gdst += 16384;
    }
  }
}

template <int KS> __device__ __forceinline__ void x_scores(float* s, float* sm, const uint4* q, uint32_t ok, uint32_t om) {
  wg_rs32o<1, desc_sw64(C_KV + KS * 1024)>(s, q[KS].x, q[KS].y, q[KS].z, q[KS].w, ok);
  wg_rs8o<1, desc_n16(C_KM + KS * 512)>(sm, q[KS].x, q[KS].y, q[KS].z, q[KS].w, om);
  if constexpr (KS < 3) x_scores<KS + 1>(s, sm, q, ok, om);
}

__device__ __forceinline__ void chain_attn(const Params& P, uint32_t sb) {
  const int c = chain_id(), j = c & 1;
  const int tid = threadIdx.x, lane = tid & 31, w = __shfl_sync(~0u, (tid >> 5) & 3, 0);
  const int l = w >> 1, u = w & 1;
  const uint32_t rb = mapa(sb, j ^ 1);
  const float sc = 0.08838834764831845f * 1.4426950408889634f;
  const uint32_t ones = 0x3F803F80u;
  const uint32_t km_off = C_KM + (lane >> 3) * 256 + l * 128 + (lane & 7) * 16;
  const uint32_t qm_off = C_QM + (lane >> 4) * 256 + l * 128 + (lane & 7) * 16;
  const uint32_t kv_off = C_KV + l * 4096 + (lane & 15) * 64 + (((lane >> 4) ^ (u * 2) ^ ((lane >> 1) & 3)) << 4);

  load_wg<CHAIN, true>(P, sb, false, 1, w);
  if (lane == 0) mbar_arrive(sb + CB_M);
#pragma unroll 1
  for (int n = 0; n < STEPS; n++) {
    const uint32_t kvb = sb + kv_off + (n & 1) * 16384;
    if (w == 0 && elect()) { mbar_expect(sb + CB_SX, 2560); mbar_expect(sb + CB_OX, 2048); mbar_expect(sb + CB_XX, 2048); }
    mbar_wait(sb + CB_FULL + (n & 1) * 8, (n >> 1) & 1);
    if (n < 3 && tid == 256) TS(n ? 20 + n : 5);
    __syncwarp();
    {
      uint32_t km[8];
      uint4 kx[8];
#pragma unroll
      for (int i = 0; i < 8; i++) ldsm4t(kx[i].x, kx[i].y, kx[i].z, kx[i].w, (kvb ^ ((i & 1) * 32)) + (i >> 1) * 1024);
      mbar_wait(sb + CB_VF, n & 1);
      if (w == 1) TRD(60, kx[7].x);
      bar_sync(B_QK, 416);
      if (n + 1 == STEPS) {
        st_async4(rb + C_SX + (tid & 127) * 16, 0.f, 0.f, 0.f, 0.f, rb + CB_SX);
        st_async1(rb + C_SX + 2048 + (tid & 127) * 4, 0, rb + CB_SX);
        bar_sync(B_V, 256);
      } else {
      uint32_t qm[16];
#pragma unroll
      for (int ks = 0; ks < 4; ks++) ldsm4t(qm[4 * ks], qm[4 * ks + 1], qm[4 * ks + 2], qm[4 * ks + 3], sb + qm_off + ks * 512);
      ldsm4t(km[0], km[1], km[2], km[3], sb + km_off);
      ldsm4t(km[4], km[5], km[6], km[7], sb + km_off + 1024);
      float s[5][4];
      uint4 vx[4];
#pragma unroll
      for (int i = 0; i < 5; i++) { s[i][0] = s[i][1] = s[i][2] = s[i][3] = 0.f; }
#pragma unroll
      for (int ks = 0; ks < 4; ks++) {
        const uint32_t* q = qm + 4 * ks;
        if (ks == 1 || ks == 2) {
#pragma unroll
          for (int i = 2 * ks - 2; i < 2 * ks; i++) ldsm4(vx[i].x, vx[i].y, vx[i].z, vx[i].w, ((sb + kv_off) ^ ((i & 1) * 32)) + 8192 + (2 * u + (i >> 1)) * 1024);
        }
        mma16(s[1], q[0], q[1], q[2], q[3], kx[2 * ks].x, kx[2 * ks].y);
        mma16(s[2], q[0], q[1], q[2], q[3], kx[2 * ks].z, kx[2 * ks].w);
        mma16(s[0], q[0], q[1], q[2], q[3], km[2 * ks], km[2 * ks + 1]);
        mma16(s[3], q[0], q[1], q[2], q[3], kx[2 * ks + 1].x, kx[2 * ks + 1].y);
        mma16(s[4], q[0], q[1], q[2], q[3], kx[2 * ks + 1].z, kx[2 * ks + 1].w);
      }
      const uint32_t sx = C_SX + l * 1280;
      st_async4(rb + sx + u * 512 + lane * 16, s[1][0], s[1][1], s[2][0], s[2][1], rb + CB_SX);
      st_async1(rb + sx + 1024 + u * 128 + lane * 4, __float_as_uint(u ? s[0][1] : s[0][0]), rb + CB_SX);
      bar_arrive_after<B_S, 256>(__float_as_uint(s[3][0]), __float_as_uint(s[4][0]));
      mbar_wait(sb + CB_SX, n & 1);
      const uint4 p0 = lds128(sb + sx + u * 512 + lane * 16), p1 = lds128(sb + sx + (u ^ 1) * 512 + lane * 16);
      const uint2 p2 = make_uint2(lds32(sb + sx + 1024 + lane * 4), lds32(sb + sx + 1152 + lane * 4));
      float t[10] = {s[0][0] + __uint_as_float(p2.x), s[0][1] + __uint_as_float(p2.y),
                     s[1][0] + __uint_as_float(p0.x), s[1][1] + __uint_as_float(p0.y),
                     s[2][0] + __uint_as_float(p0.z), s[2][1] + __uint_as_float(p0.w),
                     s[3][0] + __uint_as_float(p1.x), s[3][1] + __uint_as_float(p1.y),
                     s[4][0] + __uint_as_float(p1.z), s[4][1] + __uint_as_float(p1.w)};
      float mx = fmaxf(fmaxf(fmaxf(fmaxf(t[2], t[3]), fmaxf(t[4], t[5])), fmaxf(fmaxf(t[6], t[7]), fmaxf(t[8], t[9]))), fmaxf(t[0], t[1]));
      mx = fmaxf(fmaxf(mx, __shfl_xor_sync(~0u, mx, 1)), fmaxf(__shfl_xor_sync(~0u, mx, 2), __shfl_xor_sync(~0u, mx, 3)));
      const float ms = -mx * sc;
#pragma unroll
      for (int i = 0; i < 10; i++) t[i] = ex2(fmaf(t[i], sc, ms));
      uint32_t p[5];
#pragma unroll
      for (int i = 0; i < 5; i++) p[i] = pack2(t[2 * i], t[2 * i + 1]);
      p[1] |= (p[0] & p[3] & p[4]) & 0x80008000u;
      float o[2][4], z[4] = {0.f, 0.f, 0.f, 0.f};
      mma16(z, ones, ones, ones, ones, p[1], p[2]);
#pragma unroll
      for (int i = 0; i < 2; i++) {
        o[i][0] = o[i][1] = o[i][2] = o[i][3] = 0.f;
        mma16(o[i], vx[2 * i].x, vx[2 * i].y, vx[2 * i].z, vx[2 * i].w, p[1], p[2]);
      }
      mma16(z, ones, ones, ones, ones, p[3], p[4]);
#pragma unroll
      for (int i = 0; i < 2; i++) mma16(o[i], vx[2 * i + 1].x, vx[2 * i + 1].y, vx[2 * i + 1].z, vx[2 * i + 1].w, p[3], p[4]);
      mma8(z, ones, ones, p[0]);
      bar_sync_after<B_V, 256>(p[1]);
      ldsm4(km[0], km[1], km[2], km[3], sb + km_off + (C_VM - C_KM) + u * 1024);
      mma8(o[0], km[0], km[1], p[0]);
      mma8(o[1], km[2], km[3], p[0]);
      const float i0 = rcp(z[0]), i1 = rcp(z[1]);
      const uint32_t oo = C_OI + u * 1024 + l * 128 + lane * 4;
      uint32_t ow[4];
#pragma unroll
      for (int i = 0; i < 2; i++) { ow[2 * i] = pack2(o[i][0] * i0, o[i][1] * i1); ow[2 * i + 1] = pack2(o[i][2] * i0, o[i][3] * i1); }
      stsm4(sb + C_OI + u * 1024 + l * 128 + (lane >> 3) * 256 + (lane & 7) * 16, ow[0], ow[1], ow[2], ow[3]);
      if (WFENCE) fence_async_smem();
      bar_arrive(B_O, 256);
#pragma unroll
      for (int i = 0; i < 4; i++) st_async1(rb + oo + 2048 + i * 256, ow[i], rb + CB_OX);
      }
    }
    {
      const uint32_t lane = opaque_tid() & 31, own = ((n & 1) * 16384 + j * 4096) >> 4;
      float s[16], sm[4];
#pragma unroll
      for (int i = 0; i < 16; i++) s[i] = sm[i & 3] = 0.f;
      {
        uint4 q[4];
        mbar_wait(sb + CB_Q, n & 1);
        auto load_q = [&]() {
#pragma unroll
          for (int ks = 0; ks < 4; ks++) q[ks] = lds128(sb + C_Q + (ks >> 1) * 4096 + w * 1024 + (ks & 1) * 512 + lane * 16);
        };
        if (QPOS == 0) load_q();
        mbar_wait(sb + CB_XX, n & 1);
        if (n + 1 < STEPS) mbar_wait(sb + CB_OX, n & 1);
        fence_async_smem();
        if (n + 1 < STEPS) bar_arrive(B_T, 256);
        if (QPOS == 1) load_q();
        if (n + 1 < STEPS) bar_sync(B_OE, 256);
        if (QPOS == 2) load_q();
        if (w == 1) { TRV(61, 0); TR(9); }
#pragma unroll 1
        for (uint32_t hf = 0; hf < 2; hf++) {
          wg_fence();
          x_scores<0>(s, sm, q, hf ? (C_KV2 - C_KV) >> 4 : own, hf ? (C_KM2 - C_KM) >> 4 : j * 8);
          wg_commit();
          wg_wait<0>();
#pragma unroll
          for (int ks = 0; ks < 4; ks++) asm volatile("mov.b32 %0, %1; mov.b32 %2, %3;" : "+r"(q[ks].x), "+r"(q[ks].y), "+r"(q[ks].z), "+r"(q[ks].w));
        }
      }
      const float neg = -1e9f * 11.313708498984761f;
      const int lim = 8 * (w - (int)(lane & 3)) + (int)(lane >> 2);
      float t[10] = {sm[0], sm[1]};
#pragma unroll
      for (int i = 0; i < 8; i++) t[2 + i] = i > lim ? neg : s[(i >> 1) * 4 + (i & 1)];
      float mx = fmaxf(fmaxf(fmaxf(fmaxf(t[2], t[3]), fmaxf(t[4], t[5])), fmaxf(fmaxf(t[6], t[7]), fmaxf(t[8], t[9]))), fmaxf(t[0], t[1]));
      mx = fmaxf(fmaxf(mx, __shfl_xor_sync(~0u, mx, 1)), fmaxf(__shfl_xor_sync(~0u, mx, 2), __shfl_xor_sync(~0u, mx, 3)));
      const float ms = -mx * sc;
#pragma unroll
      for (int i = 0; i < 10; i++) t[i] = ex2(fmaf(t[i], sc, ms));
      uint32_t p[5];
#pragma unroll
      for (int i = 0; i < 5; i++) p[i] = pack2(t[2 * i], t[2 * i + 1]);
      float z = ((t[0] + t[1]) + (t[2] + t[3])) + ((t[4] + t[5]) + (t[6] + t[7])) + (t[8] + t[9]);
      const uint32_t row = sb + C_OS + w * 1024 + (lane >> 2) * 128 + (((lane & 3) ^ (lane >> 2)) << 4);
#pragma unroll 1
      for (uint32_t hf = 0; hf < 2; hf++) {
        float o[32];
        const uint32_t vo = hf ? (C_KV2 + 4096 - C_KV - 8192) >> 4 : j * 256;
        wg_fence();
        wg_rs64o<0, desc_sw64(C_KV + 8192)>(o, p[1], p[1], p[2], p[2], vo);
        wg_rs64o<1, desc_sw64(C_KV + 8192 + 32)>(o, p[3], p[3], p[4], p[4], vo);
        wg_rs64o<1, mkdesc(C_VM, 128, 256, 0)>(o, p[0], p[0], 0, 0, hf ? (C_VM2 - C_VM) >> 4 : j * 8);
        wg_commit();
        if (hf) {
          if (elect()) mbar_arrive(sb + CB_M);
        } else {
          z += __shfl_xor_sync(~0u, z, 1);
          z = rcp(z + __shfl_xor_sync(~0u, z, 2));
        }
        wg_wait<0>();
#pragma unroll
        for (int qq = 0; qq < 2; qq++) {
          const float* r = o + 16 * qq;
          sts128((row ^ (qq * 64)) + hf * 4096,
                 make_uint4(pack2(r[0] * z, r[1] * z), pack2(r[4] * z, r[5] * z), pack2(r[8] * z, r[9] * z), pack2(r[12] * z, r[13] * z)));
        }
      }
      bar_arrive(B_G, 160);
      if (n + 1 < STEPS) bar_arrive(B_R, 160);
      if (w == 1) TR(10);
    }
  }
  if ((threadIdx.x & 127) == 0) TS(6);
}

__device__ __forceinline__ void chain_aux(const Params& P, uint32_t sb) {
  const uint32_t c = chain_id(), j = c & 1, lane = threadIdx.x & 31, w = __shfl_sync(~0u, (threadIdx.x >> 5) & 3, 0);
  load_wg<CHAIN, true>(P, sb, false, 0, w);
  if (threadIdx.x == 384) TS(25);
  if (threadIdx.x == 384) grid_wait(1, lds32(sb + S_GEN));
  bar_sync(B_WG2, 384);
  if (threadIdx.x == 384) TS(13);
  if (w == 0) {
    const uint32_t* fg = g_fl + FL_G + near_half(XB_F, c) * 1024 + (c >> 1) * 8;
#pragma unroll 1
    for (int n = 0; n < STEPS; n++) {
      const unsigned char* blk = g_qkv + (uint32_t)((n % QRING) * (N_CHAIN * 24576));
      const uint32_t t1 = clk(), kb = sb + CB_FULL + (n & 1) * 8, kv = sb + C_KV + (n & 1) * 16384;
      uint32_t t0 = t1 - 100000, x = 0;
      if (n > 0) {
        wait_until(t1, KMIN);
        do asm volatile("ld.relaxed.gpu.global.u32 %0, [%1];" : "=r"(x) : "l"(fg) : "memory"); while (x <= n && clk() - t1 < KWIN);
        if (NOBULK) x = n + 1;
        if (x > n) {
          asm volatile("fence.acquire.gpu;" ::: "memory");
          fence_async_global();
          if (elect()) { mbar_expect(kb, 8192); bulk_load(kv, blk + c * 24576, 8192, kb); }
        }
        T3(0); CNT(12, 1 + (x <= n));
        mbar_wait(sb + CB_REF, (n - 1) & 1);
        t0 = lds32(sb + C_REF);
        wait_until(t0, DLYK - 500);
      }
      if (!NOBULK) wait_flags(fg + min(lane, 2u) * 256, n + 1);
      T3(2);
      fence_async_global();
      if (n > 0) bar_sync(B_R, 160);
      wait_until(t0, DLYK);
      if (elect()) {
        if (x <= n) { mbar_expect(kb, 8192); bulk_load(kv, blk + c * 24576, 8192, kb); }
        mbar_expect(sb + CB_VF, 8192);
        bulk_load(sb + C_KV + 8192, blk + (c * 24576 + 8192), 8192, sb + CB_VF);
        mbar_expect(sb + CB_Q, 16384);
        bulk_load(sb + C_Q, blk + (c * 24576 + 16384), 8192, sb + CB_Q);
        bulk_load(sb + C_KV2, blk + ((c ^ 1) * 24576 + j * 4096), 4096, sb + CB_Q);
        bulk_load(sb + C_KV2 + 4096, blk + ((c ^ 1) * 24576 + 8192 + j * 4096), 4096, sb + CB_Q);
      }
      T3(1);
      T3(3);
    }
  } else {
    const uint32_t near = __ballot_sync(~0u, near_half(XB_M + min(lane, MRING - 1u) * 8, c));
    uint32_t ring = 0;
    if (w > 1) {
      const uint32_t odd = w & 1, chk = pinned(sb + C_M + odd * 2048 + m_probe(lane)), again = sb + CB_MV + 32 + odd * 8;
      const bool one = elect();
      uint32_t mph = 0;
#pragma unroll 1
      for (int n = 0; n <= STEPS; n++) {
#pragma unroll
        for (int k = 0; k < 3; k++) {
          if (n == STEPS || (k == 2 && odd)) break;
          const uint32_t b = 2 * k + odd, at = chk + (k ? k * 8192 - 2048 + odd * 2048 : 0);
          uint32_t mb = sb + CB_M + b * 8, ph = n & 1;
          int it = 1;
          while (true) {
            mbar_wait(mb, ph);
            const bool bad = __any_sync(~0u, (k ? m_max(at, at + 2048) : max(m_max(at, at ^ 8), odd ? m_max(at + 2048, (at ^ 8) + 2048) : 0)) == SENT);
            if (one && !bad) mbar_arrive(sb + CB_MV + (b > 2 ? b * 8 - 8 : 0));
            if (!bad) break;
            mb = again; ph = mph; mph ^= 1;
            if (one) {
              if (k == 0) sts32(sb + C_BAD, n + 1);
              mbar_expect(mb, b ? 4096 : 2048);
              m_fetch(sb, ring * 65536 + ((near >> ring) & 1) * 4096, b, mb);
            }
            __syncwarp();
            spin_guard(it);
          }
          TR(41 + b * 4); CNT(6 + b, it);
        }
        ring = ring + 1 == MRING ? 0 : ring + 1;
        if (!odd) {
          if (n < STEPS) { TRSYNC(); TRDUMP(n - 2); }
        } else {
          unsigned char* o = g_oimg + (uint32_t)(((n - 1) & (RING - 1)) * (N_CHAIN * 8192) + j * 4096);
          if (n > 0) bar_sync(B_G, 160);
          fence_async_smem();
          if (one) {
            if (n > 0) {
              bulk_store(o + c * 8192, sb + C_OS, 4096);
              bulk_store(o + (c ^ 1) * 8192, sb + C_OS + 4096, 4096);
              asm volatile("cp.async.bulk.commit_group;\ncp.async.bulk.wait_group.read 0;" ::: "memory");
              { const int n_ = n - 1; { const int n = n_; T3(4); (void)n; } }
            }
            mbar_arrive(sb + CB_Q);
            if (n > 0) {
              bulk_done_inc(g_fl + FL_O + c);
              { const int n_ = n - 1; { const int n = n_; T3(5); (void)n; } }
            }
          }
          __syncwarp();
        }
      }
    } else {
      const uint32_t* ts = g_fl + FL_SYNC + near_half(XB_F + 1, c) * 1024 + lane * 2;
      uint32_t t0 = clk() - 100000, last = 0;
      int lag = 0;
#pragma unroll 1
      for (int n = 0; n < STEPS; n++) {
        const uint32_t src = ring * 65536 + ((near >> ring) & 1) * 4096;
        if (lane < 5) mbar_expect(sb + CB_M + lane * 8, lane ? 4096 : 2048);
        __syncwarp();
        if (elect()) {
#pragma unroll
          for (int b = 0; b < 5; b++) {
            wait_until(t0, P.dly[14 + b]);
            m_fetch(sb, src, b, sb + CB_M + b * 8);
            TR(40 + b * 4);
          }
        }
        __syncwarp();
        ring = ring + 1 == MRING ? 0 : ring + 1;
        uint32_t va, vb;
        const uint32_t off = timer_offset(), tag = (uint32_t)(n + 1) << 28;
        if (n > 1) lag += (int)(off - last) - (lag >> 2);
        last = off;
        const uint32_t mine = min(max((lag >> 3) + 256, 0), 511);
        bar_sync(B_QK, 416);
        if (n + 1 == STEPS) break;
        sts32(sb + C_REF + 4, 0);
        const uint32_t c0 = clk(), stamp = c0 + off;
        st_relaxed_if(g_fl + FL_SYNC + lane * 1024 + c, tag | (mine << 19) | (stamp & 0x7FFFF), lane < 2);
        TR(13);
        wait_until(c0, DLYS);
        int it = 0;
        do {
          asm volatile("ld.relaxed.gpu.global.v2.u32 {%0,%1}, [%2];" : "=r"(va), "=r"(vb) : "l"(ts) : "memory");
          spin_guard(it);
        } while (__any_sync(~0u, ((va ^ tag) | (vb ^ tag)) >> 28));
        const int late = __reduce_max_sync(~0u, max((int)((va - stamp) << 13), (int)((vb - stamp) << 13))) >> 13;
        const uint32_t fast = min(((__reduce_max_sync(~0u, max(va, vb)) >> 19) & 511) - mine, 100u) * RATE;
        t0 = c0 + min((uint32_t)late, clk() - c0);
        if (elect()) {
          sts32(sb + C_REF, t0 + (fast * 3 >> 2));
          mbar_arrive(sb + CB_REF);
        }
        st_relaxed_if(g_fl + FL_TICK + lane * 1024, (uint32_t)(n + 1) << 24 | ((t0 + off) & 0xFFFFFF), c == 0 && lane < 2);
        t0 += fast * 5 >> 2;
        TRV(59, fast);
        TR(14); CNT(11, it);
        bar_sync(B_M, 160);
      }
    }
  }
}

template <int WG>
__device__ __forceinline__ void g_math(const Params& P, uint32_t sb) {
  const int q = g_unit(WG);
  const int lane = threadIdx.x & 31, w = (threadIdx.x >> 5) & 3;
  const bool isq = q >= 64;
  uint32_t a[136];
  {
    const uint32_t stage = sb + G_W + WG * 73728;
    mbar_wait(sb + W_BAR + WG * 8, 0);
    if (threadIdx.x == 0) TS(23);
    load_frags<34>(a, stage);
    fence_async_smem();
    bar_sync(B_WG0 + WG, 128);
    if (threadIdx.x == 0) TS(24);
    load_wg<GROLE>(P, sb, false, WG, w);
    if (threadIdx.x == 0) TS(25);
    mbar_wait(sb + W_BAR + WG * 8, 1);
  }
  if ((threadIdx.x & 127) == 0) TS(4);
  const uint32_t off0 = (q & 31) * 49152 + (q >> 5) * 8192 +
                        (isq ? (w >> 1) * 4096 + (w & 1) * 512 + lane * 16 : w * 1024 + (lane >> 2) * 64 + (((lane ^ (lane >> 3)) & 3) << 4));
#pragma unroll 1
  for (int n = 0; n < STEPS; n++) {
    float d0[32], d1[32];
    if (WG == 0 && n >= LOCK0) bar_sync(B_OE, 160);
    if (n > 0) bar_sync(B_V + WG, 256);
#pragma unroll
    for (int ch = 0; ch < 9; ch++) {
      mbar_wait(sb + G_BAR + ch * 8, n & 1);
      if (ch == 0) { if ((threadIdx.x & 127) == 0) T3(5 + WG * 3); __syncwarp(); }
      if (ch == 4) { if ((threadIdx.x & 127) == 0) T3(6 + WG * 3); __syncwarp(); }
      if (ch == 8 && (WG == 0 ? n > 0 : n + 1 < STEPS)) bar_arrive(B_V + (WG ^ 1), 256);
      wg_fence();
#pragma unroll
      for (int kk = 0; kk < (ch < FASTG ? 3 : 4); kk++) {
        const int i = ch * 4 + kk;
        float* d = i & 1 ? d1 : d0;
        const uint64_t db = desc_sw128(G_RING + ch * 8192 + (kk & 2) * 32);
        if (i < 2) wg_rs64<0>(d, a + i * 4, db);
        else if (i < 34) wg_rs64<1>(d, a + i * 4, db);
        else wg_ss64<1>(d, desc_sw128(G_W2 + WG * 4096 + (i - 34) * 2048), db);
        wg_ss64<1>(d, desc_sw128(G_W + WG * 73728 + i * 2048), db + 2);
      }
      wg_commit();
      if (ch > 0) { wg_wait<1>(); if (lane == 0) mbar_arrive(sb + G_BAR + 128 + (ch - 1) * 8); }
    }
    wg_wait<0>();
    if (lane == 0) mbar_arrive(sb + G_BAR + 128 + 8 * 8);
    if ((threadIdx.x & 127) == 0) T3(7 + WG * 3);
    __syncwarp();
    uint32_t tw = clk() + (n == 0 ? -100000 : WG ? 0 : DLYW);
    unsigned char* base = g_qkv + (size_t)(n & (QRING - 1)) * (N_CHAIN * 24576);
    if ((ABL & 1) && d0[0] != 1234.5f) {
    } else if (isq) {
#pragma unroll
      for (int i = 0; i < 8; i++) {
        const float *d = (i < 4 ? d0 : d1) + 4 * i, *e = (i < 4 ? d1 : d0) + 4 * i;
        wait_until(tw, 0); tw += P.dly[2 + WG];
        *(uint4*)(base + off0 + (i >> 2) * 24576 + (i & 3) * 1024) =
          make_uint4(movmat(pack2(d[0], d[1])), movmat(pack2(e[0], e[1])), movmat(pack2(d[2], d[3])), movmat(pack2(e[2], e[3])));
      }
    } else {
#pragma unroll
      for (int i = 0; i < 8; i++) {
        const float* d = (i < 4 ? d0 : d1) + 8 * (i & 2) + 2 * (i & 1);
        wait_until(tw, 0); tw += P.dly[2 + WG];
        *(uint4*)(base + off0 + (i >> 2) * 24576 + (i & 2) * 2048 + (i & 1) * 512) =
          make_uint4(pack2(d[0], d[1]), pack2(d[4], d[5]), pack2(d[8], d[9]), pack2(d[12], d[13]));
      }
    }
    if (SAFE & 2) bar_sync(B_M + WG, 160); else bar_arrive(B_M + WG, 160);
  }
}

__device__ __forceinline__ void fill16(void* p, uint32_t v) {
  asm volatile("st.global.v4.u32 [%0], {%1,%1,%1,%1};" :: "l"(p), "r"(v) : "memory");
}
__device__ __forceinline__ void g_load(const Params& P, uint32_t sb) {
  const int lane = threadIdx.x & 31, w = __shfl_sync(~0u, (threadIdx.x >> 5) & 3, 0);
  if (w == 2) return;
  if (w < 2) { bar_sync(15, 192); fence_async_smem(); }
  uint32_t fl = 0;
#pragma unroll 1
  for (int n = w == 3 ? LOCK0 : 0; n < STEPS; n++) {
    if (w && n == LOCK0) { grid_wait(1, lds32(sb + S_GEN)); fl = near_half(XB_F, bid()) * 1024; }
    if (w == 3) {
      const uint32_t tag = (uint32_t)(n - LOCK0 + 1) << 24;
      uint32_t v; int it = 0;
      do { asm volatile("ld.relaxed.gpu.global.u32 %0, [%1];" : "=r"(v) : "l"(g_fl + fl + FL_TICK) : "memory"); spin_guard(it); } while (!NOCHAIN && v < tag);
      const uint32_t off = timer_offset(), now = clk(), t0 = now - ((v ^ tag) >> 24 ? DLYG : (now + off - v) & 0xFFFFFF);
      asm volatile("fence.acquire.gpu;" ::: "memory");
      if (lane == 0) T3(11);
      __syncwarp();
      wait_until(t0, DLYG);
      if (lane == 0) T3(4);
      bar_sync(B_OE, 160);
      continue;
    }
    if (w == 0 || n == 0) {
      if (n < NSEG) wait_flags(g_lnflag + n * 16 + (lane & 1) * 8, 1);
    } else if (!NOCHAIN && n >= LAG) {
      wait_flags(g_fl + fl + FL_F + (lane & 1) * 8, n - LAG + 1);
    }
    if (w) { if (lane == 0) T3(12); bar_sync(B_X, 96); }
    fence_async_global();
    const unsigned char* src = g_lnimg + (uint32_t)((w ? (n >= LAG ? NSEG + n - LAG : 0) : min(n, NSEG - 1)) * 36864);
#pragma unroll 1
    for (int ch = 0; ch < 9; ch++) {
      const uint32_t full = sb + G_BAR + ch * 8;
      mbar_wait(full + 128, (n & 1) ^ 1);
      if (elect()) {
        mbar_expect(full, ABL & 2 ? 16 : 4096);
        bulk_load(sb + G_RING + ch * 8192 + w * 4096, src + ch * 4096, ABL & 2 ? 16 : 4096, full);
      }
    }
  }
}

__device__ __forceinline__ void g_aux(const Params& P, uint32_t sb) {
  const int lane = threadIdx.x & 31, w = (threadIdx.x >> 5) & 3;
  if (w == 1 || w == 2) {
    const int q = g_unit(w - 1);
    uint32_t* f = g_fl + FL_G + q * 8;
#pragma unroll 1
    for (int n = 0; n < STEPS; n++) {
      const uint32_t ln = opaque_tid() & 31;
      uint4* z = (uint4*)g_oacc + (uint32_t)(((n + 1) % ARING) * (16 * DM) + q * 96 + ln);
      if (!(ABL & 16)) { fill16(z, 0); fill16(z + 32, 0); fill16(z + 64, 0); }
      if (n + 3 >= MRING && q < 80) fill16((uint4*)g_mimg + (uint32_t)(((n + 3) % MRING) * 4096 + q * 32 + ln), SENT);
      bar_sync(B_M + (w - 1), 160);
      if (lane == 0) { T3(w * 2 - 2); fence_async_global(); flag_release(f, n + 1); T3(w * 2 - 1); }
      __syncwarp();
    }
  } else {
    const uint32_t u = (bid() - N_CHAIN) * 2 + (w & 1), r = u / 36 * 16 + (u & 3) * 4 + (lane >> 3);
    uint32_t o = r * (DM / 8) + (u % 36 >> 2) * 8 + ((lane & 7) ^ ((r >> 1) & 3)), fl = 0;
#pragma unroll 1
    for (int k = -LAG - 1; k < STEPS; k++) {
      if (k < NSEG - 1) bar_sync(B_X, 96);
      if (k < LAG || u >= 72) continue;
      if (k == NSEG - 1) { fl = near_half(XB_F, bid()) * 1024; wait_flags(g_fl + fl + FL_F + (lane & 1) * 8, NSEG + 1); }
      const uint4 x = __ldcg((const uint4*)P.out + o);
      if (k >= NSEG - 1) wait_flags(g_fl + fl + FL_OCNT + (max(k, NSEG) % OCRING) * 8, N_O * 3 * (max(k, NSEG) / OCRING + 1));
      const float4* a = (const float4*)g_oacc + ((k % ARING) * (16 * DM) + 8 * DM + u * 64 + lane * 2);
      const float4 p = __ldcg(a), v = __ldcg(a + 1);
      ((uint4*)P.out)[o] = make_uint4(badd2(x.x, pack2(p.x, p.y)), badd2(x.y, pack2(p.z, p.w)), badd2(x.z, pack2(v.x, v.y)), badd2(x.w, pack2(v.z, v.w)));
      o += 4 * DM;
    }
    if ((threadIdx.x & 127) == 0) TS(7);
  }
}

template <int WG, bool HALF, int KS, int N> __device__ __forceinline__ void o_mma(float* d, const uint32_t* a, uint32_t ob) {
  constexpr uint64_t db = desc_sw128(O_RING + (KS >> 2) * 8192 + (KS & 3) * 32);
  constexpr uint64_t da = desc_sw128(O_W + WG * 40960 + (KS < 40 ? KS / 5 * 2 + KS % 5 / 2 : KS - 24) * 2048);
  if constexpr (KS < 40 && !(KS % 5 & 1)) {
    const uint32_t* r = a + (KS / 5 * 3 + KS % 5 / 2) * 4;
    if constexpr (HALF) wg_rs32k<KS != 0, db>(d, r[0], r[1], r[2], r[3], ob); else wg_rs64<KS != 0>(d, r, db);
  } else {
    if constexpr (HALF) wg_ss32k<da, db>(d, ob); else wg_ss64<1>(d, da, db);
  }
  if constexpr (N > 1) o_mma<WG, HALF, KS + 1, N - 1>(d, a, ob);
}
template <int WG, bool HALF, int GR> __device__ __forceinline__ void o_groups(float* d, const uint32_t* a, uint32_t sb, int n, bool more) {
  const uint32_t ob = n < NSEG ? 0 : 256;
  mbar_wait(sb + O_BAR + GR * 8, n & 1);
  if (GR == 0) { if ((threadIdx.x & 127) == 0) T3(13 + WG); __syncwarp(); }
  if (GR == (WG == 0 ? OTURN : 4) && (WG < 2 || n + 1 < STEPS)) bar_arrive(B_V + (WG + 1) % 3, 256);
  wg_fence();
  o_mma<WG, HALF, GR * 8, 8 - 2 * FASTO>(d, a, ob);
  if (GR == 4 && more) o_mma<WG, HALF, 40, 4>(d, a, ob);
  wg_commit();
  if (GR > 0) { wg_wait<1>(); if ((threadIdx.x & 31) == 0) mbar_arrive(sb + O_BAR + 128 + (GR - 1) * 8); }
  if constexpr (GR < 4) o_groups<WG, HALF, GR + 1>(d, a, sb, n, more);
}
template <int WG, bool HALF> __device__ __forceinline__ void o_step(const uint32_t* a, uint32_t sb, uint32_t st0, int n, bool more) {
  float d[HALF ? 16 : 32];
  if (WG > 0 || n > 0) bar_sync(B_V + WG, 256);
  o_groups<WG, HALF, 0>(d, a, sb, n, more);
  wg_wait<0>();
  if ((threadIdx.x & 31) == 0) mbar_arrive(sb + O_BAR + 128 + 4 * 8);
  if ((threadIdx.x & 127) == 0) T3(WG == 0 ? 1 : WG == 1 ? 8 : 12);
  __syncwarp();
#pragma unroll(HALF ? 1 : 2)
  for (int sl = 0; sl < 2; sl++) {
    mbar_wait(sb + OB_ST + WG * 16 + sl * 8, (n & 1) ^ (WG == 0));
    if (!HALF || sl == (n >= NSEG)) {
#pragma unroll
      for (int nb = 0; nb < 4; nb++) {
        const float* r = d + (HALF ? 0 : sl * 16) + nb * 4;
        const uint32_t ad = st0 + sl * 8192 + nb * 2048;
        sts32(ad, __float_as_uint(r[0]));
        sts32(ad + 256, __float_as_uint(r[1]));
        sts32(ad ^ 32, __float_as_uint(r[2]));
        sts32((ad ^ 32) + 256, __float_as_uint(r[3]));
      }
      fence_async_smem();
    }
    bar_arrive((sl ? B_G : B_M) + WG, 160);
  }
}
template <int WG>
__device__ __forceinline__ void o_math(const Params& P, uint32_t sb) {
  const bool more = bid() < N_CHAIN + N_G + 12;
  const int lane = threadIdx.x & 31, w = (threadIdx.x >> 5) & 3, g = lane >> 2, tq = lane & 3;
  uint32_t a[96];
  mbar_wait(sb + W_BAR + WG * 8, 0);
  load_frags<24>(a, sb + WG * 49152);
  fence_async_smem();
  bar_sync(B_INIT, 416);
  load_wg<OROLE>(P, sb, false, WG, w);
  mbar_wait(sb + W_BAR + WG * 8, 1);
  if ((threadIdx.x & 127) == 0) TS(4);
  const uint32_t st0 = sb + O_ST + tq * 512 + ((w * 16 + g) ^ (tq * 8)) * 4;
#pragma unroll 1
  for (int n = 0; n < STEPS; n++) {
    if (n < LAG || n >= NSEG) o_step<WG, true>(a, sb, st0, n, more); else o_step<WG, false>(a, sb, st0, n, more);
  }
}

__device__ __forceinline__ void o_aux(const Params& P, uint32_t sb) {
  const int i = bid() - N_CHAIN - N_G, ksl = i / 3;
  const int c0 = ksl * 11 - max(ksl - 4, 0), nc = ksl < 4 ? 11 : 10;
  const int lane = threadIdx.x & 31, w = __shfl_sync(~0u, (threadIdx.x >> 5) & 3, 0);
  if (w == 0) {
    bar_sync(B_INIT, 416);
    const uint32_t* f = g_fl + FL_O + near_half(XB_F + 1, bid()) * 1024 + min((c0 & ~1) + lane, (c0 + nc - 1) | 1);
#pragma unroll 1
    for (int n = 0; n < STEPS; n++) {
      const unsigned char* src = g_oimg + (uint32_t)(((n % RING) * N_CHAIN + c0) * 8192);
      if (!NOCHAIN) wait_flags(f, n + 1);
      fence_async_global();
      if (lane == 0) T3(0);
#pragma unroll
      for (int gr = 0; gr < 5; gr++) {
        const uint32_t full = sb + O_BAR + gr * 8, bytes = ABL & 4 ? 16 : (gr < 4 ? 2 : nc - 8) * 8192;
        mbar_wait(full + 128, (n & 1) ^ 1);
        if (elect()) {
          if (n < LAG || n >= NSEG) {
            mbar_expect(full, bytes >> 1);
            for (uint32_t o = gr * 16384 + (n < LAG ? 0 : 4096); o < gr * 16384 + bytes; o += 8192) bulk_load(sb + O_RING + o, src + o, 4096, full);
          } else {
            mbar_expect(full, bytes);
            bulk_load(sb + O_RING + gr * 16384, src + gr * 16384, bytes, full);
          }
        }
      }
    }
  } else {
#pragma unroll 1
    for (int n = 0; n < STEPS; n++) {
      float* dst = g_oacc + (uint32_t)((n % ARING) * (64 * DM) + ((i % 3) * 3 + (w - 1 + ksl) % 3) * 1024);
      const bool early = w == 3 && n < NSEG;
      bar_sync(B_M + (w - 1), 160);
      if (lane == 0) {
        T3(w * 2);
        if (n < NSEG && !(ABL & 8)) { bulk_reduce(dst, sb + O_ST, 4096); bulk_reduce(dst + 16 * DM, sb + O_ST + 4096, 4096); }
        asm volatile("cp.async.bulk.commit_group;" ::: "memory");
        if (early) {
          asm volatile("cp.async.bulk.wait_group.read 0;" ::: "memory");
          mbar_arrive(sb + OB_ST);
          T3(8 + w);
          bulk_done_inc(g_fl + FL_OCNT + (n % OCRING) * 8);
          T3(w * 2 + 1);
        }
      }
      __syncwarp();
      bar_sync(B_G + (w - 1), 160);
      if (lane == 0) {
        if (n >= LAG && !(ABL & 8)) { bulk_reduce(dst + 32 * DM, sb + O_ST + 8192, 4096); bulk_reduce(dst + 48 * DM, sb + O_ST + 12288, 4096); }
        asm volatile("cp.async.bulk.commit_group;\ncp.async.bulk.wait_group.read 1;" ::: "memory");
        if (!early) mbar_arrive(sb + OB_ST + (w % 3) * 16);
        asm volatile("cp.async.bulk.wait_group.read 0;" ::: "memory");
        mbar_arrive(sb + OB_ST + (w % 3) * 16 + 8);
        if (!early) {
          T3(8 + w);
          bulk_done_inc(g_fl + FL_OCNT + (n % OCRING) * 8);
          T3(w * 2 + 1);
        }
      }
      __syncwarp();
    }
  }
}

constexpr uint32_t Y_PITCH = 1168, Y_ROWS = 16 * Y_PITCH;
template <int R> __device__ __forceinline__ void y_rows(uint32_t* y, uint32_t src, uint32_t dst, int w, int bar) {
  const int lane = threadIdx.x & 31;
#pragma unroll
  for (int k = 0; k < 2 * R + 1; k++) {
    const int op = w + k * (16 / R);
    if (k == 2 * R && w >= 4) break;
    uint32_t a, b, c, d;
    ldsm4t(a, b, c, d, src + op * 512 + (lane & 16) * 16 + (lane & 7) * 32 + (lane & 8) * 2);
    stsm4(dst + (lane & 15) * Y_PITCH + op * 32 + (lane & 16), a, b, c, d);
  }
  bar_sync(bar, 512 / R);
  const uint32_t row = dst + ((w & 6) * 2 + (w >> 3) * 2 + (w & 1)) * Y_PITCH + lane * 4;
#pragma unroll
  for (int i = 0; i < 9 * R; i++) y[i] = lds32(row + i / 9 * 2 * Y_PITCH + i % 9 * 128);
}

__device__ __forceinline__ void f_role(const Params& P, uint32_t sb) {
  const int lane = threadIdx.x & 31, w = __shfl_sync(~0u, threadIdx.x >> 5, 0), r0 = (bid() - N_CHAIN - N_G - N_O) * 16;
  if (w == 8) {
    const uint32_t* fo = g_fl + FL_OCNT + near_half(XB_F, bid()) * 1024;
    fence_async_global();
#pragma unroll 1
    for (int n = 0; n < NSEG; n++) {
      bar_sync(2, 288);
      if (elect()) {
        mbar_expect(sb + F_BAR, 36864);
        bulk_load(sb + F_XY, P.X + (size_t)(n * 32 + r0) * DM, 18432, sb + F_BAR);
        bulk_load(sb + F_XY + 18432, g_yT + (size_t)(n * 32 + r0) * DM, 18432, sb + F_BAR);
        mbar_expect(sb + F_BAR + 8, 36864);
        T3(1);
      }
      wait_flags(fo + (n % OCRING) * 8, NOCHAIN == 5 ? 0 : N_O * 3 * (n / OCRING + 1));
      fence_async_global();
      if (elect()) { bulk_load(sb + F_A, g_oacc + (uint32_t)((n % ARING) * (64 * DM) + r0 * DM), 36864, sb + F_BAR + 8); T3(0); }
    }
  } else if (w == 9) {
#pragma unroll 1
    for (int n = 0; n < NSEG; n++) {
      const uint32_t st = sb + (n & 1) * 36864;
      unsigned char* p = g_lnimg + (uint32_t)((NSEG + n) * 36864 + r0 * 128);
      bar_sync(1, 288);
      if (elect()) {
        T3(2);
#pragma unroll
        for (int i = 0; i < 9; i++) bulk_store(p + i * 4096, st + F_L + i * 2048, 2048);
        asm volatile("cp.async.bulk.commit_group;" ::: "memory");
        bulk_done_inc(g_fl + FL_F + (bid() & 1) * 8);
        T3(3);
        bulk_store(P.out + (size_t)(n * 32 + r0) * DM, st + F_X, 18432);
        asm volatile("cp.async.bulk.commit_group;\ncp.async.bulk.wait_group.read 0;" ::: "memory");
        if (n + 1 == NSEG) bulk_done_inc(g_fl + FL_F + (bid() & 1) * 8);
      }
      __syncwarp();
    }
  } else if (w < 8) {
    const uint32_t row = sb + w * 1152 + lane * 4, acc = sb + F_A + w * 256 + (lane ^ ((w & 6) * 2)) * 8;
    const uint32_t ln = sb + F_L + w * 128 + (((lane >> 2) ^ w) << 4) + (lane & 3) * 4;
#pragma unroll 1
    for (int n = -1; n < NSEG; n++) {
      const uint32_t st = (n & 1) * 36864;
      uint32_t x[18], y[18], l[18];
      if (n >= 0) mbar_wait(sb + F_BAR, n & 1);
#pragma unroll
      for (int i = 0; i < 18; i++) x[i] = lds32(row + F_XY + i / 9 * 9216 + i % 9 * 128);
      y_rows<2>(y, sb + F_XY + 18432, sb + F_Y, w, 3);
      layernorm9<2>(x, l);
#pragma unroll
      for (int i = 0; i < 18; i++) x[i] = badd2(x[i], bmul2(l[i], y[i]));
      if (n >= 0) mbar_wait(sb + F_BAR + 8, n & 1);
      if (threadIdx.x == 0 && n >= 0) T3(4);
      __syncwarp();
      uint2 a[18];
#pragma unroll
      for (int i = 0; i < 18; i++) a[i] = lds64(acc + i / 9 * 2048 + i % 9 * 4096);
#pragma unroll
      for (int i = 0; i < 18; i++) x[i] = badd2(x[i], pack2(__uint_as_float(a[i].x), __uint_as_float(a[i].y)));
      if (n + 1 < NSEG) bar_arrive(2, 288);
      layernorm9<2>(x, l);
#pragma unroll
      for (int i = 0; i < 18; i++) { x[i] = badd2(x[i], bmul2(l[i], y[i])); sts32(row + st + F_X + i / 9 * 9216 + i % 9 * 128, x[i]); }
      layernorm9<2>(x, l);
#pragma unroll
      for (int i = 0; i < 18; i++) sts32(ln + st + i / 9 * 1024 + i % 9 * 2048, l[i]);
      fence_async_smem();
      if (n >= 0) bar_sync(1, 288); else bar_sync(3, 256);
    }
  }
}

constexpr uint32_t P_CH = 147456, P_CHSZ = 12800, P_H = 4352;
static_assert(P_CH + 6 * P_CHSZ <= G_BAR, "prologue smem");

template <int N>
__device__ __forceinline__ void conv_fold(float (*acc)[4], bool hi, uint32_t mine, uint32_t theirs, int bar, int cnt) {
#pragma unroll
  for (int i = 0; i < N / 2; i++) {
    uint4 v;
    v.x = __float_as_uint(hi ? acc[i][0] : acc[i + N / 2][0]); v.y = __float_as_uint(hi ? acc[i][1] : acc[i + N / 2][1]);
    v.z = __float_as_uint(hi ? acc[i][2] : acc[i + N / 2][2]); v.w = __float_as_uint(hi ? acc[i][3] : acc[i + N / 2][3]);
    sts128(mine + i * 512, v);
  }
  bar_sync(bar, cnt);
#pragma unroll
  for (int i = 0; i < N / 2; i++) {
    const uint4 v = lds128(theirs + i * 512);
    acc[i][0] = (hi ? acc[i + N / 2][0] : acc[i][0]) + __uint_as_float(v.x); acc[i][1] = (hi ? acc[i + N / 2][1] : acc[i][1]) + __uint_as_float(v.y);
    acc[i][2] = (hi ? acc[i + N / 2][2] : acc[i][2]) + __uint_as_float(v.z); acc[i][3] = (hi ? acc[i + N / 2][3] : acc[i][3]) + __uint_as_float(v.w);
  }
}
template <int N>
__device__ __forceinline__ void conv_store(const float (*acc)[4], int tile0, uint32_t su, int d, uint32_t dd) {
  const int lane = threadIdx.x & 31, g = lane >> 2, tq = lane & 3;
#pragma unroll
  for (int i = 0; i < N; i++) {
    const uint32_t ad = su + (8 + (tile0 + i) * 8 + g) * 32 + tq * 4, sw = (g & 4) << 2;
    const uint32_t lo = badd2(movmat(pack2(acc[i][0], acc[i][1])), bmul2(lds32(ad + sw), dd));
    const uint32_t hi = badd2(movmat(pack2(acc[i][2], acc[i][3])), bmul2(lds32(ad + (sw ^ 16)), dd));
    ((uint2*)g_yT)[(((tile0 + i) * 8 + g) * DM + d) * 4 + tq] = make_uint2(lo, hi);
  }
}

__device__ __forceinline__ void prologue(const Params& P, uint32_t sb) {
  const int b = bid(), tid = threadIdx.x, lane = tid & 31, warp = tid >> 5, t0 = b * 16;
  const bool isg = b >= N_CHAIN && b < N_CHAIN + N_G;
  const int nch = isg ? 2 : b < 128 ? 6 : 0, chb = b < N_CHAIN ? b * 6 : isg ? b * 2 + 256 : b * 6 - 192;
  const uint32_t tstart = clk();
  if (tid < 288) {
    if (b < 128) {
      const int c = (tid >> 1) * 4, tt = t0 + (tid & 1) * 8;
      uint2 kr[11], vr[8];
#pragma unroll
      for (int i = 0; i < 11; i++) { const int t = tt + i - 3; kr[i] = t >= 0 ? __ldg((const uint2*)(P.K + (size_t)t * DM + c)) : make_uint2(0, 0); }
#pragma unroll
      for (int i = 0; i < 8; i++) vr[i] = __ldg((const uint2*)(P.V + (size_t)(tt + i) * DM + c));
#pragma unroll
      for (int e = 0; e < 2; e++) {
        const uint4 sh = __ldg((const uint4*)(P.shift + c * 4) + e);
        const uint32_t s0 = __byte_perm(sh.x, sh.z, 0x5410), s1 = __byte_perm(sh.x, sh.z, 0x7632);
        const uint32_t s2 = __byte_perm(sh.y, sh.w, 0x5410), s3 = __byte_perm(sh.y, sh.w, 0x7632);
        uint32_t v[8];
#pragma unroll
        for (int i = 0; i < 8; i++) {
          const uint32_t k3 = e ? kr[i].y : kr[i].x, k2 = e ? kr[i + 1].y : kr[i + 1].x, k1 = e ? kr[i + 2].y : kr[i + 2].x, k0 = e ? kr[i + 3].y : kr[i + 3].x;
          v[i] = bmul2(badd2(badd2(badd2(bmul2(k3, s3), bmul2(k2, s2)), bmul2(k1, s1)), bmul2(k0, s0)), e ? vr[i].y : vr[i].x);
        }
        *(uint4*)(g_kvT + (size_t)(c + 2 * e) * KVP + tt) =
          make_uint4(__byte_perm(v[0], v[1], 0x5410), __byte_perm(v[2], v[3], 0x5410), __byte_perm(v[4], v[5], 0x5410), __byte_perm(v[6], v[7], 0x5410));
        *(uint4*)(g_kvT + (size_t)(c + 2 * e + 1) * KVP + tt) =
          make_uint4(__byte_perm(v[0], v[1], 0x7632), __byte_perm(v[2], v[3], 0x7632), __byte_perm(v[4], v[5], 0x7632), __byte_perm(v[6], v[7], 0x7632));
      }
    }
  } else if (tid < 384) {
    const int t = tid - 288;
    for (int i = b * 96 + t; i < 16 * DM; i += N_CTA * 96) ((uint4*)g_oacc)[i] = make_uint4(0, 0, 0, 0);
    if (b * 96 + t < 128 * 8) g_lnflag[b * 96 + t] = 0;
    if (t == 95) sts32(sb + S_GEN, ld_acquire(g_gbar));
    __syncwarp();
    wait_until(tstart, P.dly[23]);
    for (int i = t; i < 32 * nch; i += 96) asm volatile("prefetch.global.L2 [%0];" :: "l"(P.Hk + (size_t)chb * SEQ + i * 64));
  }
  if (warp < 12) {
    bar_arrive(10, 416);
    if (tid == 128) TS(14);
    const int ch = 5 - (warp >> 1), sub = warp & 1, d = chb + ch;
    const uint32_t su = sb + P_CH + ch * P_CHSZ;
    if (ch < nch) {
      const uint32_t* hs = (const uint32_t*)(P.Hk + (size_t)d * SEQ);
#pragma unroll
      for (int q = sub * 32 + lane; q < 256; q += 64) {
        const uint4 c = __ldg((const uint4*)hs + q);
        const uint32_t prev = q ? __ldg(hs + 4 * q - 1) : 0u;
        sts128(su + P_H + 32 + q * 16, make_uint4(__byte_perm(c.x, prev, 0x7610), __byte_perm(c.y, c.x, 0x7610), __byte_perm(c.z, c.y, 0x7610), __byte_perm(c.w, c.z, 0x7610)));
        sts128(su + P_H + 4224 + q * 16, make_uint4(__byte_perm(c.x, 0, 0x1032), __byte_perm(c.y, 0, 0x1032), __byte_perm(c.z, 0, 0x1032), __byte_perm(c.w, 0, 0x1032)));
      }
      if (sub == 1 && lane == 0) sts32(su + P_CHSZ - 16, __bfloat16_as_ushort(P.Dk[d]) * 0x10001u);
      if (sub == 0 && lane < 20) sts128(su + (lane < 16 ? lane * 16 : P_H + (lane & 2) * 2096 + (lane & 1) * 16), make_uint4(0, 0, 0, 0));
    }
    bar_sync(11, 416);
    if (ch < nch) {
#pragma unroll
      for (int q = sub * 32 + lane; q < 256; q += 64) {
        const int row = (q >> 1) + 8;
        sts128(su + row * 32 + (((q & 1) ^ ((row >> 2) & 1)) << 4), __ldcg((const uint4*)(g_kvT + (size_t)d * KVP) + q));
      }
    }
    const int g = lane >> 2, tq = lane & 3;
    const uint32_t sh = su + P_H + (g & 1) * 4192 + (8 + (g >> 1) - tq) * 4;
    float acc[16][4];
#pragma unroll
    for (int i = 0; i < 16; i++) { acc[i][0] = acc[i][1] = acc[i][2] = acc[i][3] = 0.f; }
    auto u_addr = [&](int res) {
      const int row = 8 - res + ((lane >> 4) << 3) + (lane & 7);
      return su + row * 32 + ((((lane >> 3) & 1) ^ ((row >> 2) & 1)) << 4);
    };
    if (ch < nch) {
      bar_sync(1 + ch, 64);
      if (tid == 352) TS(11);
      if (sub) {
#pragma unroll 4
        for (int res = 0; res < 8; res++) {
          uint32_t b0, b1, b2, b3;
          ldsm4(b0, b1, b2, b3, u_addr(res));
          const uint32_t r0 = lds32(sh + res * 32);
          mma16(acc[0], r0, lds32(sh + res * 32 + 16), lds32(sh + res * 32 - 16), r0, b0, b1);
        }
        conv_store<1>(acc, 0, su, d, lds32(su + P_CHSZ - 16));
      }
    }
    bar_arrive(12, 416);
    if (isg && warp < 8) { while ((int)(clk() - tstart - S1G) < 0) __nanosleep(200); load_wg<GROLE>(P, sb, true, warp >> 2, warp & 3); }
    if (ch < nch) {
#pragma unroll 1
      for (int res = sub * 4; res < sub * 4 + 4; res++) {
        uint32_t bf[16][2];
        const uint32_t ad = u_addr(res);
#pragma unroll
        for (int f = 0; f < 16; f += 2) ldsm4(bf[f][0], bf[f][1], bf[f + 1][0], bf[f + 1][1], ad + f * 256);
#pragma unroll
        for (int k = 0; k < 16; k++) {
          const int jj = k & 1 ? k >> 1 : 15 - (k >> 1);
          const uint32_t ah = sh + (8 * jj + res) * 32;
          const uint32_t r0 = lds32(ah), r1 = lds32(ah + 16), rm = lds32(ah - 16);
#pragma unroll
          for (int i = max(jj, 1); i < 16; i++) mma16(acc[i], r0, r1, rm, r0, bf[i - jj][0], bf[i - jj][1]);
        }
      }
      bar_sync(1 + ch, 64);
      if (tid == 352) TS(12);
      const uint32_t xb = su + P_H + lane * 16, dd = lds32(su + P_CHSZ - 16);
      conv_fold<16>(acc, sub, xb + sub * 4096, xb + (sub ^ 1) * 4096, 1 + ch, 64);
      conv_store<8>(acc, sub * 8, su, d, dd);
    }
  } else {
    for (int i = b; i < 194 + MRING * 5; i += N_CTA) {
      const int n = (i - 194) / 5, r = (i - 194) % 5, blk = i < 192 ? i / 6 * 8 + i % 6 : i < 194 ? XB_F + i - 192 : XB_M + n * 8 + r;
      const uint32_t fill = i < 194 ? 0u : SENT;
#pragma unroll 1
      for (int q = tid - 384; q < 256 && warp < 15; q += 96) {
        uint4 v = make_uint4(fill, fill, fill, fill);
        if (i >= 194 && n == 0 && (r > 0 || q < 128)) {
          const bf16* m = P.mem0 + (max(r * 8 - 4, 0) + (q >> 5)) * 16 + ((q >> 1) & 1) * 8 + ((q >> 2) & 7);
          v.x = pack2(__bfloat162float(m[0]), __bfloat162float(m[DM])); v.y = pack2(__bfloat162float(m[2 * DM]), __bfloat162float(m[3 * DM]));
          v.z = pack2(__bfloat162float(m[4 * DM]), __bfloat162float(m[5 * DM])); v.w = pack2(__bfloat162float(m[6 * DM]), __bfloat162float(m[7 * DM]));
        }
        g_xb[blk * 512 + q] = v;
        g_xb[blk * 512 + 256 + q] = v;
      }
    }
    if (tid < 388) g_xb[XB_REF * 512 + (tid & 2) * 128 + (b & ~1) + (tid & 1)] = make_uint4(0, 0, 0, 0);
    else if (tid < 392 && b < N_GRP) g_xb[(b * 8 + 7) * 512 + (tid & 2) * 128 + (tid & 1)] = make_uint4(0, 0, 0, 0);
    if (warp < 15) { bar_arrive(9, 128); bar_sync(7, 96); }
    if (tid == 384) TS(8);
    if (warp == 12) {
      const bf16* w = lane < 6 ? (lane % 3 == 0 ? P.Wk : lane % 3 == 1 ? P.Wv : P.Wq) + (((b >> 5) * 2 + lane / 3) * 32 + (b & 31)) * 2048
                               : (lane < 8 ? P.Wo + (lane - 6) * (9 * 131072) : P.X) + b * 2048;
      uint32_t t = tstart + P.dly[19];
      if ((int)(clk() - t) > 0) t = clk();
#pragma unroll 1
      for (int st = 0; st < 9 && b < N_CHAIN; st++) {
#pragma unroll 1
        for (int i = 0; i < 9; i++, t += PACE) {
          wait_until(t, 0);
          if (lane == st) asm volatile("cp.async.bulk.prefetch.L2.global [%0], 4096;" :: "l"(w + i * (lane < 6 ? 262144 : 131072)) : "memory");
        }
      }
      if (lane == 0) TS(10);
    } else if (warp == 15) {
      bar_sync(10, 416);
      if (lane == 0) { grid_arrive(0); if (nch) grid_wait(0, lds32(sb + S_GEN)); }
      __syncwarp();
      bar_arrive(11, 416);
      if (lane == 0) TS(1);
      bar_sync(9, 128);
      bar_sync(12, 416);
      if (lane == 0) { TS(16); grid_arrive(2); TS(17); }
    } else if (lane == 0) {
      if (warp == 13 || (warp == 14 && b < N_GRP)) {
        uint32_t* p = (uint32_t*)(g_xb + (warp == 13 ? XB_REF * 512 + b : (b * 8 + 7) * 512));
        int votes = 0;
        for (int rep = 0; rep < 24 && abs(votes) < 7; rep++) {
          uint32_t v0, v1, c0, c1;
          asm volatile("atom.relaxed.gpu.global.add.u32 %0, [%4], 1;\n atom.relaxed.gpu.global.add.u32 %1, [%5], 1;\n"
                       "{.reg .pred p; setp.eq.u32 p, %0, 0x7ffffff3; @p trap; mov.u32 %2, %%clock; setp.eq.u32 p, %1, 0x7ffffff3; @p trap; mov.u32 %3, %%clock;}"
                       : "=&r"(v0), "=&r"(v1), "=&r"(c0), "=&r"(c1) : "l"(p + (rep & 1) * 1024), "l"(p + ((rep & 1) ^ 1) * 1024) : "memory");
          votes += ((c1 - c0 > 80u) == (rep & 1)) ? 1 : -1;
        }
        if (warp == 13) { g_side[b] = votes > 0; TS(9); } else g_near[b] = votes > 0;
      }
    }
    __syncwarp();
    if (warp > 12 && b < N_CHAIN) {
      while ((int)(clk() - tstart - S1DLY) < 0) __nanosleep(200);
      for (int k = warp - 13; k < 8; k += 3) load_wg<CHAIN>(P, sb, true, 1 - k / 4, k & 3);
    }
  }
  if (b < N_CHAIN + N_G && (warp < 8 || (isg && warp >= 12))) bar_arrive(0, 512); else bar_sync(0, 512);
  if (tid == 352) TS(2);
}

__device__ __forceinline__ void publish_y() {
  if (threadIdx.x == 383) { grid_arrive(1); TS(18); }
  __syncwarp();
}

template <int R> __device__ __forceinline__ void ln_tiles(const Params& P, uint32_t sb) {
  const int lane = threadIdx.x & 31, w = (threadIdx.x >> 5) & (16 / R - 1), half = R == 1 ? 0 : threadIdx.x >> 8, u = N_CTA - 1 - bid();
  const int first = R == 1 ? u : 46 - 2 * u + half, step = R == 1 ? 4 : 40, last = R == 1 ? 8 : 128;
  const uint32_t raw = sb + P_CH + half * (18432 + Y_ROWS), mb = sb + T_BAR + (R - 1 + half) * 8;
  const bool lead = w == 16 / R - 1 && lane == 0;
  auto load_y = [&](const bf16* src, int tile) {
    fence_async_global();
    mbar_expect(mb, 18432);
    bulk_load(raw, src + (size_t)tile * 16 * DM, 18432, mb);
  };
  uint32_t nx[9 * R];
  auto load_x = [&](int tile) {
#pragma unroll
    for (int i = 0; i < 9 * R; i++) nx[i] = __ldg((const uint32_t*)(P.X + (size_t)(tile * 16 + w + i / 9 * 8) * DM) + i % 9 * 32 + lane);
  };
  load_x(first);
  if (R == 2) {
    if (lead) { grid_wait(1, lds32(sb + S_GEN)); if (u > 3) TS(13); load_y(g_yT, first); }
    __syncwarp();
  }
#pragma unroll 1
  for (int tile = first, real = R - 1, ph = 0; tile < last; tile += real * step, real = 1, ph ^= 1) {
    uint32_t x[9 * R], l[9 * R], y[9 * R];
    const bool ts = threadIdx.x == 0 && (R == 1 ? tile == first : u > 3 && tile == first + step);
    if (ts) TS(26);
#pragma unroll
    for (int i = 0; i < 9 * R; i++) x[i] = nx[i];
    layernorm9<R>(x, l);
    if (real && tile + step < last) load_x(tile + step);
    if (R == 2 && tile == first + step && u >= N_F && w < 6) load_wg<OROLE>(P, sb, true, w >> 1, half * 2 + (w & 1));
    if (R == 1 && tile == first && lead) {
      if (real) grid_wait(2, lds32(sb + S_GEN));
      TS(13);
      load_y(real ? g_yT : P.Hk, tile);
    }
    bar_sync(13 + half, 512 / R);
    mbar_wait(mb, ph);
    if (ts) TS(28);
    y_rows<R>(y, raw, raw + 18432, w, 13 + half);
    if (ts) TS(29);
    if (lead && real && tile + step < last) { fence_async_smem(); load_y(g_yT, tile + step); }
    __syncwarp();
#pragma unroll
    for (int i = 0; i < 9 * R; i++) x[i] = badd2(x[i], bmul2(l[i], y[i]));
    layernorm9<R>(x, l);
    if (ts && l[0] != 0x12345) TS(30);
#pragma unroll
    for (int r = 0; r < R; r++) store_ln_row(0, tile * 16 + w + r * 8, l + r * 9);
    if (R == 1) {
      __syncthreads();
      if (threadIdx.x == 32 && real) { if (tile < 4) TS(19); st_release(g_lnflag + tile * 8, 1); if (tile < 4) TS(20); }
      __syncwarp();
    }
    if (ts) TS(31);
  }
  if (R == 2) {
    __syncthreads();
    if (threadIdx.x >= 506) {
      asm volatile("fence.acq_rel.gpu;" ::: "memory");
      st_relaxed_if(g_lnflag + ((first ^ (lane & 1)) + (lane - 26) / 2 * step) * 8, 1, true);
    }
    __syncwarp();
    fence_async_smem();
    if (threadIdx.x == 0) TS(15);
  }
}

__global__ void __cluster_dims__(2, 1, 1) __launch_bounds__(512, 1) k_main(const __grid_constant__ Params P) {
  extern __shared__ __align__(1024) unsigned char smem[];
  const uint32_t sb = (uint32_t)__cvta_generic_to_shared(smem);
  const int b = bid(), wg = threadIdx.x >> 7;
  if ((threadIdx.x & 127) == 0) TS(0);
  if (threadIdx.x == 480) {
    if ((sb & 0xFFFFFF) != SBASE) __trap();
    for (int i = 0; i < 6; i++) mbar_init(sb + W_BAR + i * 8, 1);
    if (b < N_CHAIN) {
      mbar_init(sb + CB_FULL, 1); mbar_init(sb + CB_FULL + 8, 1);
      mbar_init(sb + CB_REF, 1);
      mbar_init(sb + CB_SX, 1); mbar_init(sb + CB_OX, 1); mbar_init(sb + CB_XX, 1); mbar_init(sb + CB_Q, 2); mbar_init(sb + CB_VF, 1); mbar_init(sb + CB_VF + 8, 1);
      sts32(sb + C_BAD, 0);
      for (int i = 0; i < 11; i++) mbar_init(sb + CB_M + i * 8, i == 0 ? 5 : i == 5 ? 3 : 1);
    } else if (b < N_CHAIN + N_G) {
      for (int i = 0; i < 9; i++) { mbar_init(sb + G_BAR + i * 8, 2); mbar_init(sb + G_BAR + 128 + i * 8, 8); }
    } else if (b < N_CHAIN + N_G + N_O) {
      for (int i = 0; i < 5; i++) { mbar_init(sb + O_BAR + i * 8, 1); mbar_init(sb + O_BAR + 128 + i * 8, 12); }
      for (int i = 0; i < 6; i++) mbar_init(sb + OB_ST + i * 8, 1);
    } else {
      mbar_init(sb + F_BAR, 1); mbar_init(sb + F_BAR + 8, 1);
    }
    asm volatile("fence.mbarrier_init.release.cluster;" ::: "memory");
    fence_async_smem();
  }
  __syncwarp();
  asm volatile("barrier.cluster.arrive.relaxed.aligned;" ::: "memory");
  prologue(P, sb);
  asm volatile("barrier.cluster.wait.aligned;" ::: "memory");
  fence_async_smem();
  if (b >= N_CHAIN + N_G) publish_y();
  if (b >= 128) ln_tiles<1>(P, sb);
  if (b >= N_CHAIN + N_G) ln_tiles<2>(P, sb);
  if ((threadIdx.x & 127) == 0) TS(3);
  if (b < N_CHAIN) {
    if (wg < 2) { reg_inc<200>(); chain_proj(P, sb); }
    else if (wg == 2) { reg_dec<ATTR>(); publish_y(); chain_attn(P, sb); }
    else { reg_dec<112 - ATTR>(); chain_aux(P, sb); }
  } else if (NOBULK) {
    if (b < N_CHAIN + N_G) publish_y();
    {
      if (wg == 0) {
        float d[4] = {0.f, 0.f, 0.f, 0.f};
        for (int n = 0; n < STEPS - 1; n++) {
          const uint32_t* f = g_fl + FL_TICK;
          uint32_t x;
          do { for (int k = 0; k < 16; k++) mma16(d, 0, 0, 0, 0, 0, 0); asm volatile("ld.relaxed.gpu.global.u32 %0, [%1];" : "=r"(x) : "l"(f) : "memory"); } while ((x >> 24) <= n);
          const int q = (b - N_CHAIN) * 4 + (threadIdx.x >> 5);
          if (n + 5 >= MRING && q < 80) fill16((uint4*)g_mimg + (uint32_t)(((n + 5) % MRING) * 4096 + q * 32 + (threadIdx.x & 31)), SENT);
        }
        if (d[0] == 1.f) P.out[0] = __float2bfloat16(0.f);
      }
    }
  } else if (b < N_CHAIN + N_G) {
    if (wg == 0) { reg_inc<232>(); g_math<0>(P, sb); }
    else if (wg == 1) { reg_inc<232>(); g_math<1>(P, sb); }
    else if (wg == 2) { reg_dec<24>(); bar_arrive(15, 192); publish_y(); g_aux(P, sb); }
    else { reg_dec<24>(); g_load(P, sb); }
  } else if (b < N_CHAIN + N_G + N_O) {
    if (wg == 0) { reg_inc<160>(); o_math<0>(P, sb); }
    else if (wg == 1) { reg_inc<160>(); o_math<1>(P, sb); }
    else if (wg == 2) { reg_inc<160>(); o_math<2>(P, sb); }
    else { reg_dec<32>(); o_aux(P, sb); }
  } else {
    f_role(P, sb);
  }
}

}

extern "C" void kernel_launch(void* const* d_in, const int* in_sizes, int n_in, void* d_out, int out_size) {
  typedef CUresult (*Encode)(CUtensorMap*, CUtensorMapDataType, cuuint32_t, void*, const cuuint64_t*, const cuuint64_t*, const cuuint32_t*, const cuuint32_t*,
                             CUtensorMapInterleave, CUtensorMapSwizzle, CUtensorMapL2promotion, CUtensorMapFloatOOBfill);
  static Encode encode = nullptr;
  if (!encode) cudaGetDriverEntryPoint("cuTensorMapEncodeTiled", (void**)&encode, cudaEnableDefault);
  Params P;
  for (int i = 0; i < 11; i++) {
    const bool wo = i == 6 || i == 7;
    const cuuint64_t cols = wo ? DM : HD, rows = HD + DM - cols, pitch = cols * 2;
    const cuuint64_t dim[4][5] = {{cols, 2, 8, 2, 18}, {cols, 16, 1, 1, rows / 16}, {cols, 2, 4, 4, rows / 32}, {64, 16, 64, 2, 18}};
    const cuuint64_t stride[4][4] = {{8 * pitch, pitch, 16 * pitch, 32 * pitch}, {pitch, pitch, pitch, 16 * pitch},
                                     {pitch, 8 * pitch, 2 * pitch, 32 * pitch}, {pitch, 128, 16 * pitch, 32 * pitch}};
    const cuuint32_t box[4][5] = {{64, 2, 8, 1, 18}, {64, 16, 1, 1, 1}, {64, 2, 4, 2, 1}, {64, 16, 2, 1, 18}}, one[5] = {1, 1, 1, 1, 1};
    const int k = i < 3 ? 0 : i < 7 ? 1 : i < 8 ? 2 : 3;
    encode(&P.map[i], CU_TENSOR_MAP_DATA_TYPE_BFLOAT16, 5, d_in[wo ? 11 : 8 + (i & 7) % 3], dim[k], stride[k], box[k], one,
           CU_TENSOR_MAP_INTERLEAVE_NONE, CU_TENSOR_MAP_SWIZZLE_128B, CU_TENSOR_MAP_L2_PROMOTION_L2_128B, CU_TENSOR_MAP_FLOAT_OOB_FILL_NONE);
  }
  P.X = (const bf16*)d_in[0]; P.K = (const bf16*)d_in[1]; P.V = (const bf16*)d_in[2];
  P.shift = (const bf16*)d_in[3]; P.Hk = (const bf16*)d_in[4]; P.Dk = (const bf16*)d_in[5];
  P.mem0 = (const bf16*)d_in[7];
  P.Wq = (const bf16*)d_in[8]; P.Wk = (const bf16*)d_in[9]; P.Wv = (const bf16*)d_in[10]; P.Wo = (const bf16*)d_in[11];
  P.out = (bf16*)d_out;
  for (int i = 0; i < 24; i++) P.dly[i] = h_dly[i];
  cudaFuncSetAttribute(k_main, cudaFuncAttributeMaxDynamicSharedMemorySize, SMEM_BYTES);
  k_main<<<N_CTA, 512, SMEM_BYTES>>>(P);
}
```

```cpp
#include <cuda.h>
#include <cuda_runtime.h>
#include <cuda_bf16.h>
#include <stdint.h>

namespace {

typedef __nv_bfloat16 bf16;

constexpr int SEQ = 2048, DM = 576, HD = 4096, NSEG = 64;
#define PLACE 1
#define LAGV 7
constexpr int LAG = LAGV, STEPS = NSEG + LAG, RING = 8, QRING = 4;
static_assert(LAG < RING, "ring");
constexpr int N_CHAIN = 64, N_G = 48, N_O = 18, N_F = 2;
constexpr uint32_t SBASE = 1024;
constexpr uint32_t SENT = 0xFFFFFFFFu;
constexpr int SPIN_MAX = 1 << 22;

__device__ __forceinline__ uint32_t bid() {
  uint32_t b;
  asm volatile("mov.u32 %0, %%ctaid.x;" : "=r"(b));
  return b < 6 ? b + 106 : b < 8 ? b + 122 : b < 114 ? b - 8 : b < 130 ? b - 2 : b;
}
__device__ __forceinline__ uint32_t chain_id() { return blockIdx.x - (PLACE ? 8 : 0); }
constexpr int KVP = SEQ + 64;
__device__ __align__(1024) bf16 g_kvT[DM * KVP];
__device__ __align__(1024) bf16 g_yT[DM * SEQ];
__device__ __align__(1024) unsigned char g_lnimg[2 * NSEG * 9 * 4096];
__device__ __align__(1024) unsigned char g_qkv[QRING * N_CHAIN * 24576];
__device__ __align__(1024) unsigned char g_oimg[RING * N_CHAIN * 8192];
constexpr int ARING = 16;
static_assert(ARING >= LAG + 9, "accumulator ring");
__device__ __align__(1024) float g_oacc[ARING * 64 * DM];
constexpr int MRING = LAG + 4, N_GRP = 32 + MRING + 1;
constexpr int XB_M = 256, XB_F = XB_M + MRING * 8, XB_REF = XB_F + 2, N_CTA = N_CHAIN + N_G + N_O + N_F;
__device__ __align__(65536) uint4 g_xb[N_GRP * 4096];
#define g_mimg ((uint32_t*)(g_xb + XB_M * 512))
__device__ uint32_t g_near[N_GRP];
__device__ uint32_t g_side[N_CTA];
__device__ __align__(128) uint32_t g_gbar[3 * 32];
constexpr int FL_G = 0, FL_F = 96 * 8, FL_OCNT = FL_F + 2 * 8, OCRING = 16, FL_TICK = 992, FL_O = 2048, FL_SYNC = FL_O + 128;
static_assert(FL_OCNT + OCRING * 8 <= FL_TICK, "flag block");
#define g_fl ((uint32_t*)(g_xb + XB_F * 512))
__device__ __align__(1024) uint32_t g_lnflag[128 * 8];
#define TS(slot)

#define OTURN 2
#define LOCK0 3
#define FASTO 0
#define FASTG 0
#define NOBULK 0
#define VPAT 0x15bbd249u
#define XR 3
#define RATE 1
#define SAFE 3
#define WFENCE 0
#define QPOS 0
#define VE 4
#define OGAP 2
#define NOCHAIN 0
#define BFENCE 2
#define ABL 0
#define ATTR 80
#define CNT(slot, tries)
#define T3(slot)
#define TR(slot)
#define TRV(slot, val)
#define TRD(slot, dep)
#define TRSYNC()
#define TRDUMP(n)
#define CLK(t) "{.reg .b64 x; .reg .b32 h; mov.u64 x, %%clock64; mov.b64 {" t ", h}, x;}"
__device__ __forceinline__ uint32_t clk() { uint32_t t; asm volatile(CLK("%0") : "=r"(t) :: "memory"); return t; }
__device__ __forceinline__ void wait_until(uint32_t t0, uint32_t d) {
  asm volatile("{.reg .pred p; .reg .u32 t;\n"
               "W: " CLK("t") " sub.u32 t, t, %0; setp.lt.s32 p, t, 0; @p bra.uni W;}"
               :: "r"(t0 + d) : "memory");
}
__device__ __forceinline__ uint32_t pack2(float lo, float hi) {
  uint32_t r; asm("cvt.rn.bf16x2.f32 %0, %1, %2;" : "=r"(r) : "f"(hi), "f"(lo)); return r;
}
__device__ __forceinline__ float bf_lo(uint32_t v) { return __uint_as_float(v << 16); }
__device__ __forceinline__ float bf_hi(uint32_t v) { return __uint_as_float(v & 0xFFFF0000u); }

__device__ __forceinline__ uint4 ld_relaxed4(const void* p) {
  uint4 v; asm volatile("ld.relaxed.gpu.global.v4.u32 {%0,%1,%2,%3}, [%4];" : "=r"(v.x), "=r"(v.y), "=r"(v.z), "=r"(v.w) : "l"(p) : "memory"); return v;
}
__device__ __forceinline__ void st_b128(void* p, uint32_t a, uint32_t b, uint32_t c, uint32_t d) {
  asm volatile("{.reg .b128 v; mov.b128 v, {%1,%2,%3,%4}; st.relaxed.gpu.global.b128 [%0], v;}" :: "l"(p), "r"(a), "r"(b), "r"(c), "r"(d) : "memory");
}
__device__ __forceinline__ void reload_b128(uint4& v, const void* p, uint32_t again) {
  asm volatile("{.reg .pred p; .reg .b128 v; setp.ne.u32 p, %5, 0; mov.b128 v, {%0,%1,%2,%3};\n"
               "@p ld.relaxed.gpu.global.b128 v, [%4]; mov.b128 {%0,%1,%2,%3}, v;}"
    : "+r"(v.x), "+r"(v.y), "+r"(v.z), "+r"(v.w) : "l"(p), "r"(again) : "memory");
}
__device__ __forceinline__ void reload4(uint4& v, const void* p, uint32_t again) {
  asm volatile("{.reg .pred p; setp.ne.u32 p, %5, 0; @p ld.relaxed.gpu.global.v4.u32 {%0,%1,%2,%3}, [%4];}"
    : "+r"(v.x), "+r"(v.y), "+r"(v.z), "+r"(v.w) : "l"(p), "r"(again) : "memory");
}
__device__ __forceinline__ void st_relaxed4(void* p, uint32_t a, uint32_t b, uint32_t c, uint32_t d) {
  asm volatile("st.relaxed.gpu.global.v4.u32 [%0], {%1,%2,%3,%4};" :: "l"(p), "r"(a), "r"(b), "r"(c), "r"(d) : "memory");
}
__device__ __forceinline__ void st_relaxed_if(void* p, uint32_t a, bool on) {
  asm volatile("{.reg .pred p; setp.ne.u32 p, %2, 0; @p st.relaxed.gpu.global.u32 [%0], %1;}" :: "l"(p), "r"(a), "r"((uint32_t)on) : "memory");
}
__device__ __forceinline__ uint32_t ld_acquire(const uint32_t* p) {
  uint32_t v; asm volatile("ld.acquire.gpu.global.u32 %0, [%1];" : "=r"(v) : "l"(p) : "memory"); return v;
}
__device__ __forceinline__ void st_release(uint32_t* p, uint32_t v) {
  asm volatile("st.release.gpu.global.u32 [%0], %1;" :: "l"(p), "r"(v) : "memory");
}
__device__ __forceinline__ void bulk_reduce(float* dst, uint32_t src, uint32_t bytes) {
  asm volatile("cp.reduce.async.bulk.global.shared::cta.bulk_group.add.f32 [%0], [%1], %2;" :: "l"(dst), "r"(src), "r"(bytes) : "memory");
}
__device__ __forceinline__ void bulk_done_inc(uint32_t* p) {
  asm volatile("cp.async.bulk.wait_group 0;\n"
               "fence.proxy.async.global;\nfence.release.gpu;\n"
               "red.relaxed.gpu.global.add.u32 [%0], 1;\nred.relaxed.gpu.global.add.u32 [%0+4096], 1;" :: "l"(p) : "memory");
}
__device__ __forceinline__ void flag_release(uint32_t* p, uint32_t v) {
  asm volatile("fence.release.gpu;\nst.relaxed.gpu.global.u32 [%0], %1;\nst.relaxed.gpu.global.u32 [%0+4096], %1;" :: "l"(p), "r"(v) : "memory");
}
__device__ __forceinline__ void spin_guard(int& it) {
  asm volatile("{.reg .pred p; add.s32 %0, %0, 1; setp.gt.s32 p, %0, %1; @p trap;}" : "+r"(it) : "n"(SPIN_MAX));
}
__device__ __forceinline__ void wait_flag(const uint32_t* p, uint32_t v) {
  int it = 0;
  while (ld_acquire(p) < v) spin_guard(it);
}
__device__ __forceinline__ void wait_flags(const uint32_t* p, uint32_t v) {
  int it = 0;
  while (true) {
    uint32_t x; asm volatile("ld.relaxed.gpu.global.u32 %0, [%1];" : "=r"(x) : "l"(p) : "memory");
    if (__all_sync(~0u, x >= v)) break;
    spin_guard(it);
  }
  asm volatile("fence.acquire.gpu;" ::: "memory");
}
__device__ __forceinline__ uint32_t timer_offset() {
  uint32_t g0, g;
  asm volatile("mov.u32 %0, %%globaltimer_lo;" : "=r"(g0) :: "memory");
  do { asm volatile("mov.u32 %0, %%globaltimer_lo;" : "=r"(g) :: "memory"); } while (g == g0);
  return (g >> 5) * 58 - clk();
}
__device__ __forceinline__ void grid_arrive(int i) {
  asm volatile("red.release.gpu.global.add.u32 [%0], %1;" :: "l"(g_gbar + i * 32), "r"(bid() ? 1u : 257u - N_CTA) : "memory");
}
__device__ __forceinline__ void grid_wait(int i, uint32_t gen) {
  int it = 0;
  while (((ld_acquire(g_gbar + i * 32) ^ gen) >> 8) == 0) spin_guard(it);
}
__device__ __forceinline__ bool elect() {
  uint32_t r; asm volatile("{.reg .pred p; elect.sync _|p, -1; selp.u32 %0, 1, 0, p;}" : "=r"(r)); return r;
}
__device__ __forceinline__ void bar_sync(int id, int cnt) { asm volatile("bar.sync %0, %1;" :: "r"(id), "r"(cnt) : "memory"); }
__device__ __forceinline__ void bar_arrive(int id, int cnt) { asm volatile("bar.arrive %0, %1;" :: "r"(id), "r"(cnt) : "memory"); }
template <int id, int cnt> __device__ __forceinline__ void bar_arrive_after(uint32_t a, uint32_t b) {
  asm volatile("{.reg .pred p; setp.ne.u32 p, %2, 0xfff12345; setp.ne.and.u32 p, %3, 0xfff12345, p; @p bar.arrive %0, %1;}" :: "n"(id), "n"(cnt), "r"(a), "r"(b) : "memory");
}
template <int id, int cnt> __device__ __forceinline__ void bar_sync_after(uint32_t a) {
  asm volatile("{.reg .pred p; setp.ne.u32 p, %2, 0xfff12345; @p bar.sync %0, %1;}" :: "n"(id), "n"(cnt), "r"(a) : "memory");
}
__device__ __forceinline__ void fence_async_smem() { asm volatile("fence.proxy.async.shared::cta;" ::: "memory"); }
__device__ __forceinline__ void fence_async_global() { asm volatile("fence.proxy.async.global;" ::: "memory"); }
__device__ __forceinline__ void mbar_init(uint32_t mb, int cnt) { asm volatile("mbarrier.init.shared::cta.b64 [%0], %1;" :: "r"(mb), "r"(cnt) : "memory"); }
__device__ __forceinline__ void mbar_arrive(uint32_t mb) { asm volatile("mbarrier.arrive.shared::cta.b64 _, [%0];" :: "r"(mb) : "memory"); }
__device__ __forceinline__ void mbar_arrive_after(uint32_t mb, uint32_t a, uint32_t lane) {
  asm volatile("{.reg .pred p; setp.ne.u32 p, %1, 0xfff12345; setp.eq.and.u32 p, %2, 0, p; @p mbarrier.arrive.shared::cta.b64 _, [%0];}" :: "r"(mb), "r"(a), "r"(lane) : "memory");
}
__device__ __forceinline__ void mbar_expect(uint32_t mb, uint32_t bytes) {
  asm volatile("mbarrier.arrive.expect_tx.shared::cta.b64 _, [%0], %1;" :: "r"(mb), "r"(bytes) : "memory");
}
__device__ __forceinline__ void mbar_wait_guard(uint32_t mb, uint32_t parity) {
  uint32_t ok; int it = 0;
  while (true) {
    asm volatile("{.reg .pred p; mbarrier.try_wait.parity.shared::cta.b64 p, [%1], %2; selp.u32 %0, 1, 0, p;}" : "=r"(ok) : "r"(mb), "r"(parity) : "memory");
    if (ok) break;
    spin_guard(it);
  }
}
__device__ __forceinline__ void mbar_wait(uint32_t mb, uint32_t parity) {
  asm volatile("{.reg .pred p;\nW: mbarrier.try_wait.parity.shared::cta.b64 p, [%0], %1;\n@!p bra W;}" :: "r"(mb), "r"(parity) : "memory");
}
__device__ __forceinline__ void bulk_load(uint32_t dst, const void* src, uint32_t bytes, uint32_t mb) {
  asm volatile("cp.async.bulk.shared::cluster.global.mbarrier::complete_tx::bytes [%0], [%1], %2, [%3];" :: "r"(dst), "l"(src), "r"(bytes), "r"(mb) : "memory");
}
__device__ __forceinline__ void bulk_store(void* dst, uint32_t src, uint32_t bytes) {
  asm volatile("cp.async.bulk.global.shared::cta.bulk_group [%0], [%1], %2;" :: "l"(dst), "r"(src), "r"(bytes) : "memory");
}
__device__ __forceinline__ void cp_async16(uint32_t dst, const void* src) {
  asm volatile("cp.async.cg.shared.global [%0], [%1], 16;" :: "r"(dst), "l"(src) : "memory");
}
__device__ __forceinline__ void cp_async_wait_all() { asm volatile("cp.async.wait_all;" ::: "memory"); }
__device__ __forceinline__ uint32_t mapa(uint32_t a, uint32_t rank) {
  uint32_t r; asm("mapa.shared::cluster.u32 %0, %1, %2;" : "=r"(r) : "r"(a), "r"(rank)); return r;
}
__device__ __forceinline__ void st_async4(uint32_t dst, float a, float b, float c, float d, uint32_t mb) {
  asm volatile("st.async.shared::cluster.mbarrier::complete_tx::bytes.v4.f32 [%0], {%1,%2,%3,%4}, [%5];" :: "r"(dst), "f"(a), "f"(b), "f"(c), "f"(d), "r"(mb) : "memory");
}
__device__ __forceinline__ void st_async2(uint32_t dst, float a, float b, uint32_t mb) {
  asm volatile("st.async.shared::cluster.mbarrier::complete_tx::bytes.v2.f32 [%0], {%1,%2}, [%3];" :: "r"(dst), "f"(a), "f"(b), "r"(mb) : "memory");
}
__device__ __forceinline__ void st_async1(uint32_t dst, uint32_t a, uint32_t mb) {
  asm volatile("st.async.shared::cluster.mbarrier::complete_tx::bytes.u32 [%0], %1, [%2];" :: "r"(dst), "r"(a), "r"(mb) : "memory");
}
__device__ __forceinline__ uint4 lds128(uint32_t a) {
  uint4 v; asm volatile("ld.shared.v4.u32 {%0,%1,%2,%3}, [%4];" : "=r"(v.x), "=r"(v.y), "=r"(v.z), "=r"(v.w) : "r"(a) : "memory"); return v;
}
__device__ __forceinline__ uint2 lds64(uint32_t a) {
  uint2 v; asm volatile("ld.shared.v2.u32 {%0,%1}, [%2];" : "=r"(v.x), "=r"(v.y) : "r"(a) : "memory"); return v;
}
__device__ __forceinline__ uint32_t lds32(uint32_t a) {
  uint32_t v; asm volatile("ld.shared.u32 %0, [%1];" : "=r"(v) : "r"(a) : "memory"); return v;
}
__device__ __forceinline__ void sts128(uint32_t a, uint4 v) {
  asm volatile("st.shared.v4.u32 [%0], {%1,%2,%3,%4};" :: "r"(a), "r"(v.x), "r"(v.y), "r"(v.z), "r"(v.w) : "memory");
}
__device__ __forceinline__ void sts64(uint32_t a, uint32_t x, uint32_t y) {
  asm volatile("st.shared.v2.u32 [%0], {%1,%2};" :: "r"(a), "r"(x), "r"(y) : "memory");
}
__device__ __forceinline__ void sts32(uint32_t a, uint32_t x) { asm volatile("st.shared.u32 [%0], %1;" :: "r"(a), "r"(x) : "memory"); }
__device__ __forceinline__ void ldsm4(uint32_t& r0, uint32_t& r1, uint32_t& r2, uint32_t& r3, uint32_t a) {
  asm volatile("ldmatrix.sync.aligned.m8n8.x4.shared.b16 {%0,%1,%2,%3}, [%4];" : "=r"(r0), "=r"(r1), "=r"(r2), "=r"(r3) : "r"(a) : "memory");
}
__device__ __forceinline__ void ldsm4t(uint32_t& r0, uint32_t& r1, uint32_t& r2, uint32_t& r3, uint32_t a) {
  asm volatile("ldmatrix.sync.aligned.m8n8.x4.trans.shared.b16 {%0,%1,%2,%3}, [%4];" : "=r"(r0), "=r"(r1), "=r"(r2), "=r"(r3) : "r"(a) : "memory");
}
__device__ __forceinline__ void stsm4(uint32_t a, uint32_t r0, uint32_t r1, uint32_t r2, uint32_t r3) {
  asm volatile("stmatrix.sync.aligned.m8n8.x4.shared.b16 [%0], {%1,%2,%3,%4};" :: "r"(a), "r"(r0), "r"(r1), "r"(r2), "r"(r3) : "memory");
}
__device__ __forceinline__ uint32_t movmat(uint32_t a) {
  uint32_t d; asm volatile("movmatrix.sync.aligned.m8n8.trans.b16 %0, %1;" : "=r"(d) : "r"(a)); return d;
}
__device__ __forceinline__ void mma16(float* d, uint32_t a0, uint32_t a1, uint32_t a2, uint32_t a3, uint32_t b0, uint32_t b1) {
  asm volatile("mma.sync.aligned.m16n8k16.row.col.f32.bf16.bf16.f32 {%0,%1,%2,%3}, {%4,%5,%6,%7}, {%8,%9}, {%0,%1,%2,%3};"
    : "+f"(d[0]), "+f"(d[1]), "+f"(d[2]), "+f"(d[3]) : "r"(a0), "r"(a1), "r"(a2), "r"(a3), "r"(b0), "r"(b1));
}
__device__ __forceinline__ void mma8(float* d, uint32_t a0, uint32_t a1, uint32_t b0) {
  asm volatile("mma.sync.aligned.m16n8k8.row.col.f32.bf16.bf16.f32 {%0,%1,%2,%3}, {%4,%5}, {%6}, {%0,%1,%2,%3};"
    : "+f"(d[0]), "+f"(d[1]), "+f"(d[2]), "+f"(d[3]) : "r"(a0), "r"(a1), "r"(b0));
}
__device__ __forceinline__ float rcp(float x) { float r; asm("rcp.approx.ftz.f32 %0, %1;" : "=f"(r) : "f"(x)); return r; }
__device__ __forceinline__ float ex2(float x) { float r; asm("ex2.approx.ftz.f32 %0, %1;" : "=f"(r) : "f"(x)); return r; }

__host__ __device__ constexpr uint64_t mkdesc(uint32_t off, uint32_t lbo, uint32_t sbo, uint32_t swz) {
  return (uint64_t)((SBASE + off) >> 4) | ((uint64_t)(lbo >> 4) << 16) | ((uint64_t)(sbo >> 4) << 32) | ((uint64_t)swz << 62);
}
__host__ __device__ constexpr uint64_t desc_sw128(uint32_t off) { return mkdesc(off, 16, 1024, 1); }
__host__ __device__ constexpr uint64_t desc_n16(uint32_t off) { return mkdesc(off, 256, 128, 0); }
__host__ __device__ constexpr uint64_t desc_m(uint32_t off) { return mkdesc(off, 16, 256, 3); }

__host__ __device__ constexpr uint64_t desc_sw64(uint32_t off) { return mkdesc(off, 16, 512, 2); }

__device__ __forceinline__ void wg_fence() { asm volatile("wgmma.fence.sync.aligned;" ::: "memory"); }
__device__ __forceinline__ void wg_commit() { asm volatile("wgmma.commit_group.sync.aligned;" ::: "memory"); }
template <int N> __device__ __forceinline__ void wg_wait() { asm volatile("wgmma.wait_group.sync.aligned %0;" :: "n"(N) : "memory"); }

#define ACC8(d) "+f"(d[0]), "+f"(d[1]), "+f"(d[2]), "+f"(d[3]), "+f"(d[4]), "+f"(d[5]), "+f"(d[6]), "+f"(d[7])
#define ACC32(d) ACC8(d), ACC8((d + 8)), ACC8((d + 16)), ACC8((d + 24))
#define R8 "{%0,%1,%2,%3,%4,%5,%6,%7}"
#define R32 "{%0,%1,%2,%3,%4,%5,%6,%7,%8,%9,%10,%11,%12,%13,%14,%15,%16,%17,%18,%19,%20,%21,%22,%23,%24,%25,%26,%27,%28,%29,%30,%31}"
template <int SD> __device__ __forceinline__ void wg_rs16(float* d, const uint32_t* a, uint64_t db) {
  asm volatile("wgmma.mma_async.sync.aligned.m64n16k16.f32.bf16.bf16 " R8 ", {%8,%9,%10,%11}, %12, %13, 1, 1, 1;"
    : ACC8(d) : "r"(a[0]), "r"(a[1]), "r"(a[2]), "r"(a[3]), "l"(db), "n"(SD));
}
template <int SD> __device__ __forceinline__ void wg_ss16(float* d, uint64_t da, uint64_t db) {
  asm volatile("wgmma.mma_async.sync.aligned.m64n16k16.f32.bf16.bf16 " R8 ", %8, %9, %10, 1, 1, 1, 1;"
    : ACC8(d) : "l"(da), "l"(db), "n"(SD));
}
template <int SD, uint64_t DA, uint64_t DB> __device__ __forceinline__ void wg_ss16o(float* d, uint32_t oa, uint32_t ob) {
  asm volatile("{.reg .b32 x, y; .reg .b64 a, b; add.u32 x, %8, %10; add.u32 y, %9, %12; mov.b64 a, {x, %11}; mov.b64 b, {y, %13};\n"
               "wgmma.mma_async.sync.aligned.m64n16k16.f32.bf16.bf16 " R8 ", a, b, %14, 1, 1, 1, 1;}"
    : ACC8(d) : "r"(oa), "r"(ob), "n"((uint32_t)DA), "n"((uint32_t)(DA >> 32)), "n"((uint32_t)DB), "n"((uint32_t)(DB >> 32)), "n"(SD));
}
template <int SD> __device__ __forceinline__ void wg_rs64(float* d, const uint32_t* a, uint64_t db) {
  asm volatile("wgmma.mma_async.sync.aligned.m64n64k16.f32.bf16.bf16 " R32 ", {%32,%33,%34,%35}, %36, %37, 1, 1, 0;"
    : ACC32(d) : "r"(a[0]), "r"(a[1]), "r"(a[2]), "r"(a[3]), "l"(db), "n"(SD));
}
template <int SD> __device__ __forceinline__ void wg_ss64(float* d, uint64_t da, uint64_t db) {
  asm volatile("wgmma.mma_async.sync.aligned.m64n64k16.f32.bf16.bf16 " R32 ", %32, %33, %34, 1, 1, 1, 0;"
    : ACC32(d) : "l"(da), "l"(db), "n"(SD));
}
#define WG_RSO(NAME, SHAPE, REGS, ACC, A, TB) \
template <int SD, uint64_t DB> __device__ __forceinline__ void NAME(float* d, uint32_t a0, uint32_t a1, uint32_t a2, uint32_t a3, uint32_t ob) { \
  asm volatile("{.reg .b64 b; mov.b64 b, {" A(4) ", " A(5) "};\nwgmma.mma_async.sync.aligned." SHAPE ".f32.bf16.bf16 " REGS \
               ", {" A(0) "," A(1) "," A(2) "," A(3) "}, b, " A(6) ", 1, 1, " TB ";}" \
    : ACC(d) : "r"(a0), "r"(a1), "r"(a2), "r"(a3), "r"(ob + (uint32_t)DB), "n"((uint32_t)(DB >> 32)), "n"(SD)); \
}
#define ACC4(d) "+f"(d[0]), "+f"(d[1]), "+f"(d[2]), "+f"(d[3])
#define ACC16(d) ACC8(d), ACC8((d + 8))
#define OP4(i) OP4_##i
#define OP4_0 "%4"
#define OP4_1 "%5"
#define OP4_2 "%6"
#define OP4_3 "%7"
#define OP4_4 "%8"
#define OP4_5 "%9"
#define OP4_6 "%10"
#define OP16(i) OP16_##i
#define OP16_0 "%16"
#define OP16_1 "%17"
#define OP16_2 "%18"
#define OP16_3 "%19"
#define OP16_4 "%20"
#define OP16_5 "%21"
#define OP16_6 "%22"
#define OP32(i) OP32_##i
#define OP32_0 "%32"
#define OP32_1 "%33"
#define OP32_2 "%34"
#define OP32_3 "%35"
#define OP32_4 "%36"
#define OP32_5 "%37"
#define OP32_6 "%38"
WG_RSO(wg_rs8o, "m64n8k16", "{%0,%1,%2,%3}", ACC4, OP4, "1")
#define R16 "{%0,%1,%2,%3,%4,%5,%6,%7,%8,%9,%10,%11,%12,%13,%14,%15}"
WG_RSO(wg_rs32o, "m64n32k16", R16, ACC16, OP16, "1")
WG_RSO(wg_rs64o, "m64n64k16", R32, ACC32, OP32, "0")
WG_RSO(wg_rs32k, "m64n32k16", R16, ACC16, OP16, "0")
template <uint64_t DA, uint64_t DB> __device__ __forceinline__ void wg_ss32k(float* d, uint32_t ob) {
  asm volatile("{.reg .b64 b; mov.b64 b, {%17, %18};\nwgmma.mma_async.sync.aligned.m64n32k16.f32.bf16.bf16 " R16 ", %16, b, 1, 1, 1, 1, 0;}"
    : ACC16(d) : "l"(DA), "r"(ob + (uint32_t)DB), "n"((uint32_t)(DB >> 32)));
}
template <int N> __device__ __forceinline__ void reg_inc() { asm volatile("setmaxnreg.inc.sync.aligned.u32 %0;" :: "n"(N)); }
template <int N> __device__ __forceinline__ void reg_dec() { asm volatile("setmaxnreg.dec.sync.aligned.u32 %0;" :: "n"(N)); }
__device__ __forceinline__ void cluster_sync() {
  asm volatile("barrier.cluster.arrive.relaxed.aligned;\nbarrier.cluster.wait.aligned;" ::: "memory");
}

template <int KS>
__device__ __forceinline__ void load_frags(uint32_t* a, uint32_t src) {
  const int lane = threadIdx.x & 31, w = (threadIdx.x >> 5) & 3;
  const int k = ((lane >> 4) << 3) + (lane & 7), u = w * 2 + ((lane >> 3) & 1);
  const uint32_t base = src + k * 128 + ((u ^ (k & 7)) << 4);
#pragma unroll
  for (int ks = 0; ks < KS; ks++) ldsm4t(a[ks * 4], a[ks * 4 + 1], a[ks * 4 + 2], a[ks * 4 + 3], base + ks * 2048);
}

__device__ __forceinline__ uint32_t badd2(uint32_t a, uint32_t b) { uint32_t r; asm("add.rn.bf16x2 %0, %1, %2;" : "=r"(r) : "r"(a), "r"(b)); return r; }
__device__ __forceinline__ uint32_t bsub2(uint32_t a, uint32_t b) { uint32_t r; asm("sub.rn.bf16x2 %0, %1, %2;" : "=r"(r) : "r"(a), "r"(b)); return r; }
__device__ __forceinline__ uint32_t bmul2(uint32_t a, uint32_t b) { uint32_t r; asm("mul.rn.bf16x2 %0, %1, %2;" : "=r"(r) : "r"(a), "r"(b)); return r; }
__device__ __forceinline__ uint32_t bfma2(uint32_t a, uint32_t b, uint32_t c) { uint32_t r; asm("fma.rn.bf16x2 %0, %1, %2, %3;" : "=r"(r) : "r"(a), "r"(b), "r"(c)); return r; }
template <int R> __device__ __forceinline__ void layernorm9(const uint32_t* x, uint32_t* o) {
  const uint32_t ones = 0x3F803F80u;
  float a[R][3][4], q[R], s[R];
#pragma unroll
  for (int i = 0; i < 9 * R; i++) {
    float* d = a[i % R][i / R % 3];
    if (i < 3 * R) d[0] = d[1] = d[2] = d[3] = 0.f;
    mma8(d, x[i % R * 9 + i / R], ones, x[i % R * 9 + i / R]);
  }
#pragma unroll
  for (int r = 0; r < R; r++) {
    q[r] = threadIdx.x & 4 ? a[r][0][1] + a[r][1][1] + a[r][2][1] : a[r][0][0] + a[r][1][0] + a[r][2][0];
    s[r] = (a[r][0][2] + a[r][0][3]) + (a[r][1][2] + a[r][1][3]) + (a[r][2][2] + a[r][2][3]);
  }
#pragma unroll
  for (int r = 0; r < R; r++) { q[r] += __shfl_xor_sync(~0u, q[r], 4); s[r] += __shfl_xor_sync(~0u, s[r], 1); }
#pragma unroll
  for (int r = 0; r < R; r++) { q[r] += __shfl_xor_sync(~0u, q[r], 9); s[r] += __shfl_xor_sync(~0u, s[r], 2); }
#pragma unroll
  for (int r = 0; r < R; r++) q[r] = __shfl_sync(~0u, q[r], 0) + __shfl_sync(~0u, q[r], 18);
#pragma unroll
  for (int r = 0; r < R; r++) {
    const float mean = s[r] * (1.f / DM), var = fmaxf(fmaf(q[r], 1.f / DM, -mean * mean), 0.f);
    float sd;
    asm("sqrt.approx.ftz.f32 %0, %1;" : "=f"(sd) : "f"(bf_lo(pack2(bf_lo(pack2(var, 0.f)) + 1e-5f, 0.f))));
    const float inv = rcp(bf_lo(pack2(sd, 0.f)));
    const uint32_t mb = pack2(mean, mean), hi = pack2(inv, inv), lo = pack2(inv - bf_lo(hi), inv - bf_lo(hi));
#pragma unroll
    for (int i = r * 9; i < r * 9 + 9; i++) {
      const uint32_t d = bsub2(x[i], mb);
      o[i] = bfma2(d, hi, bmul2(d, lo));
    }
  }
}
__device__ __forceinline__ void store_ln_row(int layer, int tok, const uint32_t* o) {
  const int lane = threadIdx.x & 31, r = tok & 31;
  unsigned char* p = g_lnimg + (size_t)(layer * NSEG + (tok >> 5)) * (9 * 4096) + r * 128 + (((lane >> 2) ^ (r & 7)) << 4) + (lane & 3) * 4;
#pragma unroll
  for (int i = 0; i < 9; i++) *(uint32_t*)(p + i * 4096) = o[i];
}
struct Params { CUtensorMap map[11]; const bf16 *X, *K, *V, *shift, *Hk, *Dk, *mem0, *Wq, *Wk, *Wv, *Wo; bf16* out; uint32_t dly[24]; };
#define PACE P.dly[20]
#define S1G P.dly[21]
#define S1DLY P.dly[22]
#define DLYS P.dly[0]
#define DLYW P.dly[1]
#define KLATE P.dly[2]
#define DLYQ P.dly[3]
#define DLYK P.dly[4]
#define DLYG P.dly[5]
#define KWIN P.dly[6]
#define KMIN P.dly[7]
uint32_t h_dly[24] = {900, 350, 100, 60, 3570, 4120, 2750, 1300, 1600, 1690, 1800, 2120, 2250, 2380, 2950, 3060, 3230, 3380, 3530, 7000, 160, 12500, 20500, 4000};

constexpr uint32_t C_W = 0, C_M = 147456, C_KV = C_M + 18432, C_OS = C_KV + 24576, C_QM = C_KV + 32768, C_KM = C_QM + 2048,
                   C_VM = C_KM + 2048, C_OI = C_VM + 2048, C_SX = C_OI + 4096, C_KM2 = C_SX + 2560, C_VM2 = C_KM2 + 128,
                   C_KV2 = C_KM2 + 2048, C_Q = C_KV2 + 8192, C_BAR = C_Q + 8192;
constexpr uint32_t CB_FULL = C_BAR, CB_REF = C_BAR + 16, CB_SX = C_BAR + 32, CB_OX = C_BAR + 40, CB_XX = C_BAR + 48, CB_Q = C_BAR + 56, C_BAD = C_BAR + 64, W_BAR = C_BAR + 80, T_BAR = W_BAR + 24, S_GEN = C_BAR + 128, C_REF = C_BAR + 132, CB_VF = C_BAR + 144, CB_M = C_BAR + 160, CB_MV = C_BAR + 200;
constexpr uint32_t G_W = 0, G_RING = 147456, G_W2 = G_RING + 9 * 8192, G_BAR = G_W2 + 8192;
constexpr uint32_t O_W = 0, O_RING = 3 * 40960, O_ST = O_RING + 11 * 8192, O_BAR = O_ST + 16384, OB_ST = O_BAR + 64;
constexpr uint32_t F_A = 0, F_XY = 36864, F_L = F_XY + 36864, F_X = F_L + 18432, F_Y = F_L + 2 * 36864, F_BAR = C_BAR;
constexpr uint32_t SMEM_BYTES = C_BAR + 256;
static_assert(G_BAR + 256 <= SMEM_BYTES && O_BAR + 256 <= SMEM_BYTES && F_BAR + 16 <= SMEM_BYTES && SMEM_BYTES <= 232448, "smem map");
enum { B_INIT = 1, B_M, B_QK, B_S, B_V, B_O, B_X, B_WG0, B_WG1, B_WG2, B_G, B_OE, B_T, B_R };

__device__ __forceinline__ uint4 pack_partial(const float* d, uint32_t tag) {
  uint32_t x;
  asm("lop3.b32 %0, %1, 1, %2, 0xb8;" : "=r"(x) : "r"(pack2(d[0], d[1])), "r"(tag));
  return make_uint4(x, pack2(d[4], d[5]), pack2(d[2], d[3]), pack2(d[6], d[7]));
}
__device__ __forceinline__ void store_partial(uint4* p, const uint4& v) { st_b128(p, v.x, v.y, v.z, v.w); }
__device__ __forceinline__ void gather_reduce(const uint32_t* p, uint32_t* dst, uint32_t m0, bool shared, uint32_t tag, uint32_t lane, uint32_t sb, int n, int TS0) {
  int tries = 0;
  bool bad;
  TR(TS0);
  do {
    uint2 x[8];
#pragma unroll
    for (int i = 0; i < 8; i++)
      asm volatile("{.reg .b64 v; ld.relaxed.gpu.global.b64 v, [%2]; mov.b64 {%0, %1}, v;}" : "=r"(x[i].x), "=r"(x[i].y) : "l"(p + i * 128) : "memory");
    spin_guard(tries);
    float a = bf_lo(x[0].x), b = bf_hi(x[0].x), c = bf_lo(x[0].y), d = bf_hi(x[0].y);
    uint32_t t = x[0].x ^ tag;
#pragma unroll
    for (int i = 1; i < 8; i++) {
      a += bf_lo(x[i].x); b += bf_hi(x[i].x); c += bf_lo(x[i].y); d += bf_hi(x[i].y);
      asm("lop3.b32 %0, %0, %1, %2, 0xf6;" : "+r"(t) : "r"(x[i].x), "r"(tag));
    }
    bad = __any_sync(~0u, t & ~lane & 1);
    const bool up = lane & 8;
    float u = (up ? c : a) + __shfl_xor_sync(~0u, up ? a : c, 8), v = (up ? d : b) + __shfl_xor_sync(~0u, up ? b : d, 8);
    if (shared) { u += __shfl_xor_sync(~0u, u, 4); v += __shfl_xor_sync(~0u, v, 4); }
    u += __shfl_xor_sync(~0u, u, 16);
    v += __shfl_xor_sync(~0u, v, 16);
    st_relaxed_if(dst, n < LAG && up ? m0 : pack2(u, v), !bad);
  } while (bad);
  TR(TS0 + 3); TRV(TS0 + 2, tries);
  CNT((TS0 - 16) >> 2, tries);
}
__device__ __forceinline__ uint32_t sent_bad(const uint4& v) { return max(max(v.x, v.y), max(v.z, v.w)) == SENT; }

__host__ __device__ constexpr int o_ks(int s) { return s & (s < 8 ? 3 : 7); }
__host__ __device__ constexpr bool o_reg(int s) { return s < 8 ? (s & 3) != 3 : !(s & 1); }
__host__ __device__ constexpr int o_slot(int s) { return s < 8 ? (o_reg(s) ? s - (s >> 2) : s >> 2) : s & 1 ? (s - 5) >> 1 : (s + 4) >> 1; }
__device__ __forceinline__ int g_unit(int wg) {
  const int i = bid() - N_CHAIN;
  return i < 32 ? wg * 64 + i : 2 * i - 32 + wg;
}
__device__ __forceinline__ uint32_t pinned(uint32_t v) { return __shfl_sync(~0u, v, threadIdx.x & 31); }
template <class T> __device__ __forceinline__ T* pinned(T* p) { return (T*)__shfl_sync(~0u, (unsigned long long)p, threadIdx.x & 31); }
enum { CHAIN, GROLE, OROLE };
template <int ROLE, bool SYNC> __device__ __forceinline__ void load_box(const Params& P, uint32_t sb, bool regs, int wg, int i, uint32_t mb, bool on) {
  const int b = bid();
  int map, col = 0, ks = 0, c2 = 0, c3 = 0;
  uint32_t dst = wg * 73728;
  if (ROLE == CHAIN) {
    const int k = i - 1, st = regs ? (k < 6 ? k + k / 3 : 2 * k - 4) : k < 2 ? 4 * k + 3 : 2 * k + 5;
    dst += i ? (17 + i) * 2048 : 0;
    if (wg || i == 0) { map = wg + i; col = b * 64; c3 = !regs; }
    else if (!regs && k >= 14) { map = 6; ks = b * 4 + k - 14; }
    else { map = 6; col = 64 + (st < 8 ? (st >> 2) * 64 : (st >> 3) * 128 + (b & 1) * 64); ks = (b * 4) ^ o_ks(st); }
  } else if (ROLE == GROLE) {
    const int q = g_unit(wg);
    map = ((q >> 5) + 1) % 3;
    if (i) { map += 3; col = (q & 31) * 128 + (i - 1) * 64; ks = 34; dst = G_W2 + wg * 4096 + (i - 1) * 2048; }
    else { map += 8; c2 = (q & 31) * 2; c3 = !regs; }
  } else {
    const int o = b - N_CHAIN - N_G, ksl = o / 3;
    map = 7; col = ((o % 3) * 3 + (wg + ksl) % 3) * 64; dst = (wg * (regs ? 24 : 20) + i) * 2048;
    ks = (ksl * 11 - max(ksl - 4, 0)) * 4 + (regs ? i / 3 * 5 + i % 3 * 2 : i < 16 ? i / 2 * 5 + 1 + i % 2 * 2 : i + 24);
    c3 = (ks & 1) * 2; ks >>= 1;
  }
  if (SYNC) { col = pinned(col); ks = pinned(ks); bar_sync(B_WG0 + wg, 256); }
  if (on) asm volatile("cp.async.bulk.tensor.5d.shared::cluster.global.tile.mbarrier::complete_tx::bytes [%0], [%1, {%2, %3, %4, %5, %6}], [%7];"
               :: "r"(sb + dst), "l"(&P.map[map]), "r"(col), "r"(0), "r"(c2), "r"(c3), "r"(ks), "r"(mb) : "memory");
}
template <int ROLE, bool SYNC = false> __device__ __forceinline__ void load_wg(const Params& P, uint32_t sb, bool regs, int wg, int quarter) {
  const int i = (threadIdx.x & 31) * 4 + quarter;
  const int n = ROLE == CHAIN ? 36 : ROLE == GROLE ? (regs ? 38 : 36) : regs ? 24 : bid() < N_CHAIN + N_G + 12 ? 20 : 16;
  const bool split = SYNC && wg == 0;
  const uint32_t mb = split && i ? sb + T_BAR : sb + W_BAR + wg * 8;
  load_box<ROLE, SYNC>(P, sb, regs, wg, i, mb, i < (ROLE == CHAIN ? (wg ? 2 : 19) : ROLE == GROLE ? n - 35 : n));
  if (i <= split) mbar_expect(mb, n * (split ? 1024 : 2048));
  __syncwarp();
}
__device__ __forceinline__ uint32_t near_half(uint32_t blk, uint32_t reader) {
  return __ldcg(g_near + (blk >> 3)) ^ (~blk & 1) ^ __ldcg(g_side + (blk >> 3)) ^ __ldcg(g_side + reader);
}

__device__ __forceinline__ uint32_t opaque_tid() { uint32_t t; asm volatile("mov.u32 %0, %%tid.x;" : "=r"(t)); return t; }
__device__ __forceinline__ void m_fetch(uint32_t sb, uint32_t src, uint32_t b, uint32_t mb) {
  bulk_load(sb + C_M + (b ? b * 4096 - 2048 : 0), (const unsigned char*)g_mimg + ((src ^ ((b & 1) * 4096)) + b * 8192), b ? 4096 : 2048, mb);
}
__device__ __forceinline__ uint32_t m_probe(uint32_t lane) { return lane * 32 + (lane & 4) * 4 + (lane >> 3) * 4; }
__device__ __forceinline__ uint32_t m_max(uint32_t a, uint32_t b) {
  return max(max(lds32(a), lds32(a + 1024)), max(lds32(b), lds32(b + 1024)));
}
template <int S0, int N> __device__ __forceinline__ void o_steps(float* d, const uint32_t* a) {
  constexpr int SD = o_ks(S0) != 0;
  if constexpr (o_reg(S0)) wg_rs16<SD>(d, a + (18 + o_slot(S0)) * 4, desc_n16(C_OI + o_ks(S0) * 512));
  else wg_ss16<SD>(d, desc_sw128(C_W + (18 + o_slot(S0)) * 2048), desc_n16(C_OI + o_ks(S0) * 512));
  if constexpr (N > 1) o_steps<S0 + 1, N - 1>(d, a);
}
template <int BASE, int KS, int N> __device__ __forceinline__ void m_steps(float* d, const uint32_t* a, uint32_t oa) {
  wg_rs16<KS != 0>(d, a + (BASE + KS / 2) * 4, desc_m(C_M + KS * 512));
  if constexpr (KS >= 36 - 2 * XR) wg_rs16<1>(d, a + (18 + XR + KS / 2) * 4, desc_m(C_M + KS * 512 + 512));
  else wg_ss16o<1, desc_sw128(C_W + (BASE + KS / 2) * 2048), desc_m(C_M + KS * 512 + 512)>(d, oa, 0);
  if constexpr (N > 2) m_steps<BASE, KS + 2, N - 2>(d, a, oa);
}

template <int I, int R, int S> __device__ __forceinline__ void v_steps(float* d, const uint32_t* a) {
  constexpr bool reg = (VPAT >> I) & 1;
  if constexpr (reg) wg_rs16<1>(d, a + (18 + R) * 4, desc_m(C_M + R * 1024));
  else wg_ss16<1>(d, desc_sw128(C_W + (54 + S) * 2048), desc_m(C_M + S * 1024 + 512));
  if constexpr (I < 31) v_steps<I + 1, R + reg, S + !reg>(d, a);
  else static_assert(R + reg == 18, "pattern");
}

__device__ __forceinline__ void chain_proj(const Params& P, uint32_t sb) {
  const uint32_t c = chain_id(), h = c >> 1, j = c & 1, wid = __shfl_sync(~0u, threadIdx.x >> 5, 0), wg = wid >> 2, w = wid & 3;
  const uint32_t t = threadIdx.x & 127, lane = pinned(t & 31), mine = pinned(sb + t * 16), rb = mapa(sb, j ^ 1);
  const uint32_t theirs = pinned(rb + C_KM2 + w * 512 + lane * 4), oa = wg * 4608;
  uint32_t a[144 + 4 * XR];
  mbar_wait(sb + W_BAR + wg * 8, 0);
  if (threadIdx.x == 0) TS(23);
  load_frags<36>(a, sb + C_W + wg * 73728);
  fence_async_smem();
  bar_arrive(B_WG0 + wg, 256);
  if (threadIdx.x == 0) TS(24);
  bar_sync(B_WG2, 384);
  const uint32_t round = min(w, 2u) + (wg ? 0 : 3), gdly = P.dly[8 + round], ps = t >> 2, pf = j * 16 + (ps >> 1);
  uint4* const dsts = pinned(g_xb + (ps * 4096 + near_half(ps * 8, ps * 2) * 256 + c * 4 + (t & 3)));
  uint4* const dstf = pinned(g_xb + (pf * 4096 + 512 + near_half(pf * 8 + 1, pf * 2) * 256 + h * 8 + (t & 7)));
  const uint32_t* const gsrc = (const uint32_t*)g_xb + (h * 16384 + min(w, 2u) * 4096 + near_half(h * 8 + !wg, h * 2) * 1024 +
                               (wg ? (lane & 28) * 4 + j * 8 + (lane & 3) * 2 : 2048 + (lane & 24) * 4 + j * 16 + (lane & 7) * 2));
  uint32_t* gdst = g_mimg + (16384 + (lane >> 4) * 1024 + (lane & 1) * 8 +
                   (wg ? (round ? 1536 + round * 512 : 0) + h * 16 + (((lane >> 1) ^ c) & 4) + j * 2 + ((lane >> 1) & 1)
                       : (round - 1) * 2048 + c * 16 + (((lane >> 1) ^ (c * 2)) & 4) + ((lane >> 1) & 3)));
  const uint32_t m0 = __ldcg(gdst - 16384);
  mbar_wait(sb + W_BAR + wg * 8, 1);
  load_frags<XR>(a + 144, sb + C_W + wg * 73728 + (18 - XR) * 2048);
  bar_sync(B_INIT, 256);
  if ((threadIdx.x & 127) == 0) TS(4);

  uint32_t ring = 1;
#pragma unroll 1
  for (int n = 0; n < STEPS; n++) {
    float d[8], e[8];
#pragma unroll
    for (int i = 0; i < 8; i++) e[i] = 0.f;
    uint32_t redo = n + 1;
#pragma unroll 1
    do {
      mbar_wait(sb + CB_M, n & 1);
      wg_fence();
      m_steps<0, 0, 4>(d, a, oa);
      wg_commit();
      if (wg) { wg_fence(); m_steps<18, 0, 4>(e, a, 4608); wg_commit(); }
      if (wid == 0) TR(8);
      mbar_wait(sb + CB_M + 8, n & 1);
      wg_fence();
      m_steps<0, 4, 8>(d, a, oa);
      wg_commit();
      mbar_wait(sb + CB_MV, n & 1);
      asm volatile("{.reg .pred p; .reg .u32 t; ld.shared.u32 t, [%1]; setp.eq.u32 p, t, %0; selp.u32 %0, -1, 0, p;}" : "+r"(redo) : "r"(sb + C_BAD) : "memory");
    } while (redo);
    wg_fence();
    m_steps<0, 12, 8>(d, a, oa);
    wg_commit();
    mbar_wait(sb + CB_MV + 16, n & 1);
    wg_fence();
    m_steps<0, 20, 8>(d, a, oa);
    wg_commit();
    mbar_wait(sb + CB_MV + 24, n & 1);
    wg_fence();
    m_steps<0, 28, 8>(d, a, oa);
    wg_commit();
    wg_wait<0>();
    if (w == 0) TR(6 + wg);
    const uint32_t f0 = pack2(d[0], d[1]), f1 = pack2(d[4], d[5]), f2 = pack2(d[2], d[3]), f3 = pack2(d[6], d[7]);
    stsm4(mine + C_QM + wg * 2048, f0, f1, f2, f3);
    bar_arrive(B_QK, 416);
    const uint32_t tag = (n & 1) ^ 1;
    if (n == 0) mbar_wait(sb + T_BAR, 0);
    if (wg) {
      if (n + 1 < STEPS) bar_sync(B_S, 256);
      wg_fence();
      v_steps<0, 2, 2>(e, a);
      wg_commit();
      const uint32_t k0 = j ? f0 : f1, k1 = j ? f2 : f3;
      if (SAFE & 1) mbar_wait(sb + CB_SX, n & 1);
      wg_wait<0>();
      if (w == 0) TR(11);
      const uint32_t v0 = pack2(e[0], e[1]), v1 = pack2(e[4], e[5]), v2 = pack2(e[2], e[3]), v3 = pack2(e[6], e[7]);
      stsm4(mine + C_VM, v0, v1, v2, v3);
      bar_arrive(B_V, 256);
      st_async1(theirs, k0, rb + CB_XX);
      st_async1(theirs + 256, k1, rb + CB_XX);
      st_async1(theirs + 128, j ? v0 : v1, rb + CB_XX);
      st_async1(theirs + 384, j ? v2 : v3, rb + CB_XX);
      if (n + 1 == STEPS) break;
      bar_sync(B_O, 256);
      if (!WFENCE) fence_async_smem();
      wg_fence();
#pragma unroll
      for (int ks = 0; ks < 4; ks++) {
        if (ks == 0) wg_ss16<0>(d, desc_sw128(C_W + 32 * 2048), desc_n16(C_OI));
        else wg_ss16<1>(d, desc_sw128(C_W + (32 + ks) * 2048), desc_n16(C_OI + ks * 512));
      }
      wg_commit();
      bar_arrive(B_X, 256);
      if (w == 0) TR(0);
      wg_wait<0>();
      store_partial(dsts, pack_partial(d, tag));
      bar_arrive(B_M, 160);
      if (w == 0) TR(1);
    } else {
      if (n + 1 == STEPS) break;
      bar_sync(B_X, 256);
      wg_fence();
      o_steps<0, 4>(d, a);
      wg_commit();
      o_steps<4, 4>(e, a);
      wg_commit();
      wg_wait<1>();
      store_partial(dsts + 1024, pack_partial(d, tag));
      if (w == 0) TR(2);
      if (OGAP == 0) { wg_fence(); o_steps<8, 4>(d, a); wg_commit(); wg_wait<1>(); } else wg_wait<0>();
      store_partial(dsts + 2048, pack_partial(e, tag));
      if (w == 0) TR(3);
      wg_fence();
      if (OGAP) o_steps<8, 4>(d, a);
      if (OGAP < 2) o_steps<16, 4>(e, a);
      wg_commit();
      bar_sync(B_T, 256);
      if (w == 0) { TRV(61, 0); TR(12); }
      wg_fence();
      o_steps<12, 4>(d, a);
      wg_commit();
      if (OGAP == 2) o_steps<16, 4>(e, a);
      o_steps<20, 4>(e, a);
      wg_commit();
      wg_wait<1>();
      store_partial(dstf, pack_partial(d, tag));
      if (w == 0) TR(4);
      wg_fence();
      o_steps<24, 8>(d, a);
      wg_commit();
      wg_wait<1>();
      store_partial(dstf + 1024, pack_partial(e, tag));
      bar_arrive(B_OE, 256);
      if (w == 0) TR(5);
      wg_wait<0>();
      store_partial(dstf + 2048, pack_partial(d, tag));
      if (w == 0) TR(15);
    }
    if (w < 3) {
      mbar_wait(sb + CB_REF, n & 1);
      wait_until(lds32(sb + C_REF), gdly);
      gather_reduce(gsrc, gdst, m0, wg, tag, lane, sb, n, 16 + round * 4);
      if (++ring == MRING) { ring = 0; gdst -= MRING * 16384; }
      gdst += 16384;
    }
  }
}

template <int KS> __device__ __forceinline__ void x_scores(float* s, float* sm, const uint4* q, uint32_t ok, uint32_t om) {
  wg_rs32o<1, desc_sw64(C_KV + KS * 1024)>(s, q[KS].x, q[KS].y, q[KS].z, q[KS].w, ok);
  wg_rs8o<1, desc_n16(C_KM + KS * 512)>(sm, q[KS].x, q[KS].y, q[KS].z, q[KS].w, om);
  if constexpr (KS < 3) x_scores<KS + 1>(s, sm, q, ok, om);
}

__device__ __forceinline__ void chain_attn(const Params& P, uint32_t sb) {
  const int c = chain_id(), j = c & 1;
  const int tid = threadIdx.x, lane = tid & 31, w = __shfl_sync(~0u, (tid >> 5) & 3, 0);
  const int l = w >> 1, u = w & 1;
  const uint32_t rb = mapa(sb, j ^ 1);
  const float sc = 0.08838834764831845f * 1.4426950408889634f;
  const uint32_t ones = 0x3F803F80u;
  const uint32_t km_off = C_KM + (lane >> 3) * 256 + l * 128 + (lane & 7) * 16;
  const uint32_t qm_off = C_QM + (lane >> 4) * 256 + l * 128 + (lane & 7) * 16;
  const uint32_t kv_off = C_KV + l * 4096 + (lane & 15) * 64 + (((lane >> 4) ^ (u * 2) ^ ((lane >> 1) & 3)) << 4);

  load_wg<CHAIN, true>(P, sb, false, 1, w);
  if (lane == 0) mbar_arrive(sb + CB_M);
#pragma unroll 1
  for (int n = 0; n < STEPS; n++) {
    const uint32_t kvb = sb + kv_off + (n & 1) * 16384;
    if (w == 0 && elect()) { mbar_expect(sb + CB_SX, 2560); mbar_expect(sb + CB_OX, 2048); mbar_expect(sb + CB_XX, 2048); }
    mbar_wait(sb + CB_FULL + (n & 1) * 8, (n >> 1) & 1);
    if (n < 3 && tid == 256) TS(n ? 20 + n : 5);
    __syncwarp();
    {
      uint32_t km[8];
      uint4 kx[8];
#pragma unroll
      for (int i = 0; i < 8; i++) ldsm4t(kx[i].x, kx[i].y, kx[i].z, kx[i].w, (kvb ^ ((i & 1) * 32)) + (i >> 1) * 1024);
      mbar_wait(sb + CB_VF, n & 1);
      if (w == 1) TRD(60, kx[7].x);
      bar_sync(B_QK, 416);
      if (n + 1 == STEPS) {
        st_async4(rb + C_SX + (tid & 127) * 16, 0.f, 0.f, 0.f, 0.f, rb + CB_SX);
        st_async1(rb + C_SX + 2048 + (tid & 127) * 4, 0, rb + CB_SX);
        bar_sync(B_V, 256);
      } else {
      uint32_t qm[16];
#pragma unroll
      for (int ks = 0; ks < 4; ks++) ldsm4t(qm[4 * ks], qm[4 * ks + 1], qm[4 * ks + 2], qm[4 * ks + 3], sb + qm_off + ks * 512);
      ldsm4t(km[0], km[1], km[2], km[3], sb + km_off);
      ldsm4t(km[4], km[5], km[6], km[7], sb + km_off + 1024);
      float s[5][4];
      uint4 vx[4];
#pragma unroll
      for (int i = 0; i < 5; i++) { s[i][0] = s[i][1] = s[i][2] = s[i][3] = 0.f; }
#pragma unroll
      for (int ks = 0; ks < 4; ks++) {
        const uint32_t* q = qm + 4 * ks;
        if (ks == 1 || ks == 2) {
#pragma unroll
          for (int i = 2 * ks - 2; i < 2 * ks; i++) ldsm4(vx[i].x, vx[i].y, vx[i].z, vx[i].w, ((sb + kv_off) ^ ((i & 1) * 32)) + 8192 + (2 * u + (i >> 1)) * 1024);
        }
        mma16(s[1], q[0], q[1], q[2], q[3], kx[2 * ks].x, kx[2 * ks].y);
        mma16(s[2], q[0], q[1], q[2], q[3], kx[2 * ks].z, kx[2 * ks].w);
        mma16(s[0], q[0], q[1], q[2], q[3], km[2 * ks], km[2 * ks + 1]);
        mma16(s[3], q[0], q[1], q[2], q[3], kx[2 * ks + 1].x, kx[2 * ks + 1].y);
        mma16(s[4], q[0], q[1], q[2], q[3], kx[2 * ks + 1].z, kx[2 * ks + 1].w);
      }
      const uint32_t sx = C_SX + l * 1280;
      st_async4(rb + sx + u * 512 + lane * 16, s[1][0], s[1][1], s[2][0], s[2][1], rb + CB_SX);
      st_async1(rb + sx + 1024 + u * 128 + lane * 4, __float_as_uint(u ? s[0][1] : s[0][0]), rb + CB_SX);
      bar_arrive_after<B_S, 256>(__float_as_uint(s[3][0]), __float_as_uint(s[4][0]));
      mbar_wait(sb + CB_SX, n & 1);
      const uint4 p0 = lds128(sb + sx + u * 512 + lane * 16), p1 = lds128(sb + sx + (u ^ 1) * 512 + lane * 16);
      const uint2 p2 = make_uint2(lds32(sb + sx + 1024 + lane * 4), lds32(sb + sx + 1152 + lane * 4));
      float t[10] = {s[0][0] + __uint_as_float(p2.x), s[0][1] + __uint_as_float(p2.y),
                     s[1][0] + __uint_as_float(p0.x), s[1][1] + __uint_as_float(p0.y),
                     s[2][0] + __uint_as_float(p0.z), s[2][1] + __uint_as_float(p0.w),
                     s[3][0] + __uint_as_float(p1.x), s[3][1] + __uint_as_float(p1.y),
                     s[4][0] + __uint_as_float(p1.z), s[4][1] + __uint_as_float(p1.w)};
      float mx = fmaxf(fmaxf(fmaxf(fmaxf(t[2], t[3]), fmaxf(t[4], t[5])), fmaxf(fmaxf(t[6], t[7]), fmaxf(t[8], t[9]))), fmaxf(t[0], t[1]));
      mx = fmaxf(fmaxf(mx, __shfl_xor_sync(~0u, mx, 1)), fmaxf(__shfl_xor_sync(~0u, mx, 2), __shfl_xor_sync(~0u, mx, 3)));
      const float ms = -mx * sc;
#pragma unroll
      for (int i = 0; i < 10; i++) t[i] = ex2(fmaf(t[i], sc, ms));
      uint32_t p[5];
#pragma unroll
      for (int i = 0; i < 5; i++) p[i] = pack2(t[2 * i], t[2 * i + 1]);
      p[1] |= (p[0] & p[3] & p[4]) & 0x80008000u;
      float o[2][4], z[4] = {0.f, 0.f, 0.f, 0.f};
      mma16(z, ones, ones, ones, ones, p[1], p[2]);
#pragma unroll
      for (int i = 0; i < 2; i++) {
        o[i][0] = o[i][1] = o[i][2] = o[i][3] = 0.f;
        mma16(o[i], vx[2 * i].x, vx[2 * i].y, vx[2 * i].z, vx[2 * i].w, p[1], p[2]);
      }
      mma16(z, ones, ones, ones, ones, p[3], p[4]);
#pragma unroll
      for (int i = 0; i < 2; i++) mma16(o[i], vx[2 * i + 1].x, vx[2 * i + 1].y, vx[2 * i + 1].z, vx[2 * i + 1].w, p[3], p[4]);
      mma8(z, ones, ones, p[0]);
      bar_sync_after<B_V, 256>(p[1]);
      ldsm4(km[0], km[1], km[2], km[3], sb + km_off + (C_VM - C_KM) + u * 1024);
      mma8(o[0], km[0], km[1], p[0]);
      mma8(o[1], km[2], km[3], p[0]);
      const float i0 = rcp(z[0]), i1 = rcp(z[1]);
      const uint32_t oo = C_OI + u * 1024 + l * 128 + lane * 4;
      uint32_t ow[4];
#pragma unroll
      for (int i = 0; i < 2; i++) { ow[2 * i] = pack2(o[i][0] * i0, o[i][1] * i1); ow[2 * i + 1] = pack2(o[i][2] * i0, o[i][3] * i1); }
      stsm4(sb + C_OI + u * 1024 + l * 128 + (lane >> 3) * 256 + (lane & 7) * 16, ow[0], ow[1], ow[2], ow[3]);
      if (WFENCE) fence_async_smem();
      bar_arrive(B_O, 256);
#pragma unroll
      for (int i = 0; i < 4; i++) st_async1(rb + oo + 2048 + i * 256, ow[i], rb + CB_OX);
      }
    }
    {
      const uint32_t lane = opaque_tid() & 31, own = ((n & 1) * 16384 + j * 4096) >> 4;
      float s[16], sm[4];
#pragma unroll
      for (int i = 0; i < 16; i++) s[i] = sm[i & 3] = 0.f;
      {
        uint4 q[4];
        mbar_wait(sb + CB_Q, n & 1);
        auto load_q = [&]() {
#pragma unroll
          for (int ks = 0; ks < 4; ks++) q[ks] = lds128(sb + C_Q + (ks >> 1) * 4096 + w * 1024 + (ks & 1) * 512 + lane * 16);
        };
        if (QPOS == 0) load_q();
        mbar_wait(sb + CB_XX, n & 1);
        if (n + 1 < STEPS) mbar_wait(sb + CB_OX, n & 1);
        fence_async_smem();
        if (n + 1 < STEPS) bar_arrive(B_T, 256);
        if (QPOS == 1) load_q();
        if (n + 1 < STEPS) bar_sync(B_OE, 256);
        if (QPOS == 2) load_q();
        if (w == 1) { TRV(61, 0); TR(9); }
#pragma unroll 1
        for (uint32_t hf = 0; hf < 2; hf++) {
          wg_fence();
          x_scores<0>(s, sm, q, hf ? (C_KV2 - C_KV) >> 4 : own, hf ? (C_KM2 - C_KM) >> 4 : j * 8);
          wg_commit();
          wg_wait<0>();
#pragma unroll
          for (int ks = 0; ks < 4; ks++) asm volatile("mov.b32 %0, %1; mov.b32 %2, %3;" : "+r"(q[ks].x), "+r"(q[ks].y), "+r"(q[ks].z), "+r"(q[ks].w));
        }
      }
      const float neg = -1e9f * 11.313708498984761f;
      const int lim = 8 * (w - (int)(lane & 3)) + (int)(lane >> 2);
      float t[10] = {sm[0], sm[1]};
#pragma unroll
      for (int i = 0; i < 8; i++) t[2 + i] = i > lim ? neg : s[(i >> 1) * 4 + (i & 1)];
      float mx = fmaxf(fmaxf(fmaxf(fmaxf(t[2], t[3]), fmaxf(t[4], t[5])), fmaxf(fmaxf(t[6], t[7]), fmaxf(t[8], t[9]))), fmaxf(t[0], t[1]));
      mx = fmaxf(fmaxf(mx, __shfl_xor_sync(~0u, mx, 1)), fmaxf(__shfl_xor_sync(~0u, mx, 2), __shfl_xor_sync(~0u, mx, 3)));
      const float ms = -mx * sc;
#pragma unroll
      for (int i = 0; i < 10; i++) t[i] = ex2(fmaf(t[i], sc, ms));
      uint32_t p[5];
#pragma unroll
      for (int i = 0; i < 5; i++) p[i] = pack2(t[2 * i], t[2 * i + 1]);
      float z = ((t[0] + t[1]) + (t[2] + t[3])) + ((t[4] + t[5]) + (t[6] + t[7])) + (t[8] + t[9]);
      const uint32_t row = sb + C_OS + w * 1024 + (lane >> 2) * 128 + (((lane & 3) ^ (lane >> 2)) << 4);
#pragma unroll 1
      for (uint32_t hf = 0; hf < 2; hf++) {
        float o[32];
        const uint32_t vo = hf ? (C_KV2 + 4096 - C_KV - 8192) >> 4 : j * 256;
        wg_fence();
        wg_rs64o<0, desc_sw64(C_KV + 8192)>(o, p[1], p[1], p[2], p[2], vo);
        wg_rs64o<1, desc_sw64(C_KV + 8192 + 32)>(o, p[3], p[3], p[4], p[4], vo);
        wg_rs64o<1, mkdesc(C_VM, 128, 256, 0)>(o, p[0], p[0], 0, 0, hf ? (C_VM2 - C_VM) >> 4 : j * 8);
        wg_commit();
        if (hf) {
          if (elect()) mbar_arrive(sb + CB_M);
        } else {
          z += __shfl_xor_sync(~0u, z, 1);
          z = rcp(z + __shfl_xor_sync(~0u, z, 2));
        }
        wg_wait<0>();
#pragma unroll
        for (int qq = 0; qq < 2; qq++) {
          const float* r = o + 16 * qq;
          sts128((row ^ (qq * 64)) + hf * 4096,
                 make_uint4(pack2(r[0] * z, r[1] * z), pack2(r[4] * z, r[5] * z), pack2(r[8] * z, r[9] * z), pack2(r[12] * z, r[13] * z)));
        }
      }
      bar_arrive(B_G, 160);
      if (n + 1 < STEPS) bar_arrive(B_R, 160);
      if (w == 1) TR(10);
    }
  }
  if ((threadIdx.x & 127) == 0) TS(6);
}

__device__ __forceinline__ void chain_aux(const Params& P, uint32_t sb) {
  const uint32_t c = chain_id(), j = c & 1, lane = threadIdx.x & 31, w = __shfl_sync(~0u, (threadIdx.x >> 5) & 3, 0);
  load_wg<CHAIN, true>(P, sb, false, 0, w);
  if (threadIdx.x == 384) TS(25);
  if (threadIdx.x == 384) grid_wait(1, lds32(sb + S_GEN));
  bar_sync(B_WG2, 384);
  if (threadIdx.x == 384) TS(13);
  if (w == 0) {
    const uint32_t* fg = g_fl + FL_G + near_half(XB_F, c) * 1024 + (c >> 1) * 8;
#pragma unroll 1
    for (int n = 0; n < STEPS; n++) {
      const unsigned char* blk = g_qkv + (uint32_t)((n % QRING) * (N_CHAIN * 24576));
      const uint32_t t1 = clk(), kb = sb + CB_FULL + (n & 1) * 8, kv = sb + C_KV + (n & 1) * 16384;
      uint32_t t0 = t1 - 100000, x = 0;
      if (n > 0) {
        wait_until(t1, KMIN);
        do asm volatile("ld.relaxed.gpu.global.u32 %0, [%1];" : "=r"(x) : "l"(fg) : "memory"); while (x <= n && clk() - t1 < KWIN);
        if (NOBULK) x = n + 1;
        if (x > n) {
          asm volatile("fence.acquire.gpu;" ::: "memory");
          fence_async_global();
          if (elect()) { mbar_expect(kb, 8192); bulk_load(kv, blk + c * 24576, 8192, kb); }
        }
        T3(0); CNT(12, 1 + (x <= n));
        mbar_wait(sb + CB_REF, (n - 1) & 1);
        t0 = lds32(sb + C_REF);
        wait_until(t0, DLYK - 500);
      }
      if (!NOBULK) wait_flags(fg + min(lane, 2u) * 256, n + 1);
      T3(2);
      fence_async_global();
      if (n > 0) bar_sync(B_R, 160);
      wait_until(t0, DLYK);
      if (elect()) {
        if (x <= n) { mbar_expect(kb, 8192); bulk_load(kv, blk + c * 24576, 8192, kb); }
        mbar_expect(sb + CB_VF, 8192);
        bulk_load(sb + C_KV + 8192, blk + (c * 24576 + 8192), 8192, sb + CB_VF);
        mbar_expect(sb + CB_Q, 16384);
        bulk_load(sb + C_Q, blk + (c * 24576 + 16384), 8192, sb + CB_Q);
        bulk_load(sb + C_KV2, blk + ((c ^ 1) * 24576 + j * 4096), 4096, sb + CB_Q);
        bulk_load(sb + C_KV2 + 4096, blk + ((c ^ 1) * 24576 + 8192 + j * 4096), 4096, sb + CB_Q);
      }
      T3(1);
      T3(3);
    }
  } else {
    const uint32_t near = __ballot_sync(~0u, near_half(XB_M + min(lane, MRING - 1u) * 8, c));
    uint32_t ring = 0;
    if (w > 1) {
      const uint32_t odd = w & 1, chk = pinned(sb + C_M + odd * 2048 + m_probe(lane)), again = sb + CB_MV + 32 + odd * 8;
      const bool one = elect();
      uint32_t mph = 0;
#pragma unroll 1
      for (int n = 0; n <= STEPS; n++) {
#pragma unroll
        for (int k = 0; k < 3; k++) {
          if (n == STEPS || (k == 2 && odd)) break;
          const uint32_t b = 2 * k + odd, at = chk + (k ? k * 8192 - 2048 + odd * 2048 : 0);
          uint32_t mb = sb + CB_M + b * 8, ph = n & 1;
          int it = 1;
          while (true) {
            mbar_wait(mb, ph);
            const bool bad = __any_sync(~0u, (k ? m_max(at, at + 2048) : max(m_max(at, at ^ 8), odd ? m_max(at + 2048, (at ^ 8) + 2048) : 0)) == SENT);
            if (one && !bad) mbar_arrive(sb + CB_MV + (b > 2 ? b * 8 - 8 : 0));
            if (!bad) break;
            mb = again; ph = mph; mph ^= 1;
            if (one) {
              if (k == 0) sts32(sb + C_BAD, n + 1);
              mbar_expect(mb, b ? 4096 : 2048);
              m_fetch(sb, ring * 65536 + ((near >> ring) & 1) * 4096, b, mb);
            }
            __syncwarp();
            spin_guard(it);
          }
          TR(41 + b * 4); CNT(6 + b, it);
        }
        ring = ring + 1 == MRING ? 0 : ring + 1;
        if (!odd) {
          if (n < STEPS) { TRSYNC(); TRDUMP(n - 2); }
        } else {
          unsigned char* o = g_oimg + (uint32_t)(((n - 1) & (RING - 1)) * (N_CHAIN * 8192) + j * 4096);
          if (n > 0) bar_sync(B_G, 160);
          fence_async_smem();
          if (one) {
            if (n > 0) {
              bulk_store(o + c * 8192, sb + C_OS, 4096);
              bulk_store(o + (c ^ 1) * 8192, sb + C_OS + 4096, 4096);
              asm volatile("cp.async.bulk.commit_group;\ncp.async.bulk.wait_group.read 0;" ::: "memory");
              { const int n_ = n - 1; { const int n = n_; T3(4); (void)n; } }
            }
            mbar_arrive(sb + CB_Q);
            if (n > 0) {
              bulk_done_inc(g_fl + FL_O + c);
              { const int n_ = n - 1; { const int n = n_; T3(5); (void)n; } }
            }
          }
          __syncwarp();
        }
      }
    } else {
      const uint32_t* ts = g_fl + FL_SYNC + near_half(XB_F + 1, c) * 1024 + lane * 2;
      uint32_t t0 = clk() - 100000, last = 0;
      int lag = 0;
#pragma unroll 1
      for (int n = 0; n < STEPS; n++) {
        const uint32_t src = ring * 65536 + ((near >> ring) & 1) * 4096;
        if (lane < 5) mbar_expect(sb + CB_M + lane * 8, lane ? 4096 : 2048);
        __syncwarp();
        if (elect()) {
#pragma unroll
          for (int b = 0; b < 5; b++) {
            wait_until(t0, P.dly[14 + b]);
            m_fetch(sb, src, b, sb + CB_M + b * 8);
            TR(40 + b * 4);
          }
        }
        __syncwarp();
        ring = ring + 1 == MRING ? 0 : ring + 1;
        uint32_t va, vb;
        const uint32_t off = timer_offset(), tag = (uint32_t)(n + 1) << 28;
        if (n > 1) lag += (int)(off - last) - (lag >> 2);
        last = off;
        const uint32_t mine = min(max((lag >> 3) + 256, 0), 511);
        bar_sync(B_QK, 416);
        if (n + 1 == STEPS) break;
        sts32(sb + C_REF + 4, 0);
        const uint32_t c0 = clk(), stamp = c0 + off;
        st_relaxed_if(g_fl + FL_SYNC + lane * 1024 + c, tag | (mine << 19) | (stamp & 0x7FFFF), lane < 2);
        TR(13);
        wait_until(c0, DLYS);
        int it = 0;
        do {
          asm volatile("ld.relaxed.gpu.global.v2.u32 {%0,%1}, [%2];" : "=r"(va), "=r"(vb) : "l"(ts) : "memory");
          spin_guard(it);
        } while (__any_sync(~0u, ((va ^ tag) | (vb ^ tag)) >> 28));
        const int late = __reduce_max_sync(~0u, max((int)((va - stamp) << 13), (int)((vb - stamp) << 13))) >> 13;
        const uint32_t fast = min(((__reduce_max_sync(~0u, max(va, vb)) >> 19) & 511) - mine, 100u) * RATE;
        t0 = c0 + min((uint32_t)late, clk() - c0);
        if (elect()) {
          sts32(sb + C_REF, t0 + (fast * 3 >> 2));
          mbar_arrive(sb + CB_REF);
        }
        st_relaxed_if(g_fl + FL_TICK + lane * 1024, (uint32_t)(n + 1) << 24 | ((t0 + off) & 0xFFFFFF), c == 0 && lane < 2);
        t0 += fast * 5 >> 2;
        TRV(59, fast);
        TR(14); CNT(11, it);
        bar_sync(B_M, 160);
      }
    }
  }
}

template <int WG>
__device__ __forceinline__ void g_math(const Params& P, uint32_t sb) {
  const int q = g_unit(WG);
  const int lane = threadIdx.x & 31, w = (threadIdx.x >> 5) & 3;
  const bool isq = q >= 64;
  uint32_t a[136];
  {
    const uint32_t stage = sb + G_W + WG * 73728;
    mbar_wait(sb + W_BAR + WG * 8, 0);
    if (threadIdx.x == 0) TS(23);
    load_frags<34>(a, stage);
    fence_async_smem();
    bar_sync(B_WG0 + WG, 128);
    if (threadIdx.x == 0) TS(24);
    load_wg<GROLE>(P, sb, false, WG, w);
    if (threadIdx.x == 0) TS(25);
    mbar_wait(sb + W_BAR + WG * 8, 1);
  }
  if ((threadIdx.x & 127) == 0) TS(4);
  const uint32_t off0 = (q & 31) * 49152 + (q >> 5) * 8192 +
                        (isq ? (w >> 1) * 4096 + (w & 1) * 512 + lane * 16 : w * 1024 + (lane >> 2) * 64 + (((lane ^ (lane >> 3)) & 3) << 4));
#pragma unroll 1
  for (int n = 0; n < STEPS; n++) {
    float d0[32], d1[32];
    if (WG == 0 && n >= LOCK0) bar_sync(B_OE, 160);
    if (n > 0) bar_sync(B_V + WG, 256);
#pragma unroll
    for (int ch = 0; ch < 9; ch++) {
      mbar_wait(sb + G_BAR + ch * 8, n & 1);
      if (ch == 0) { if ((threadIdx.x & 127) == 0) T3(5 + WG * 3); __syncwarp(); }
      if (ch == 4) { if ((threadIdx.x & 127) == 0) T3(6 + WG * 3); __syncwarp(); }
      if (ch == 8 && (WG == 0 ? n > 0 : n + 1 < STEPS)) bar_arrive(B_V + (WG ^ 1), 256);
      wg_fence();
#pragma unroll
      for (int kk = 0; kk < (ch < FASTG ? 3 : 4); kk++) {
        const int i = ch * 4 + kk;
        float* d = i & 1 ? d1 : d0;
        const uint64_t db = desc_sw128(G_RING + ch * 8192 + (kk & 2) * 32);
        if (i < 2) wg_rs64<0>(d, a + i * 4, db);
        else if (i < 34) wg_rs64<1>(d, a + i * 4, db);
        else wg_ss64<1>(d, desc_sw128(G_W2 + WG * 4096 + (i - 34) * 2048), db);
        wg_ss64<1>(d, desc_sw128(G_W + WG * 73728 + i * 2048), db + 2);
      }
      wg_commit();
      if (ch > 0) { wg_wait<1>(); if (lane == 0) mbar_arrive(sb + G_BAR + 128 + (ch - 1) * 8); }
    }
    wg_wait<0>();
    if (lane == 0) mbar_arrive(sb + G_BAR + 128 + 8 * 8);
    if ((threadIdx.x & 127) == 0) T3(7 + WG * 3);
    __syncwarp();
    uint32_t tw = clk() + (n == 0 ? -100000 : WG ? 0 : DLYW);
    unsigned char* base = g_qkv + (size_t)(n & (QRING - 1)) * (N_CHAIN * 24576);
    if ((ABL & 1) && d0[0] != 1234.5f) {
    } else if (isq) {
#pragma unroll
      for (int i = 0; i < 8; i++) {
        const float *d = (i < 4 ? d0 : d1) + 4 * i, *e = (i < 4 ? d1 : d0) + 4 * i;
        wait_until(tw, 0); tw += P.dly[2 + WG];
        *(uint4*)(base + off0 + (i >> 2) * 24576 + (i & 3) * 1024) =
          make_uint4(movmat(pack2(d[0], d[1])), movmat(pack2(e[0], e[1])), movmat(pack2(d[2], d[3])), movmat(pack2(e[2], e[3])));
      }
    } else {
#pragma unroll
      for (int i = 0; i < 8; i++) {
        const float* d = (i < 4 ? d0 : d1) + 8 * (i & 2) + 2 * (i & 1);
        wait_until(tw, 0); tw += P.dly[2 + WG];
        *(uint4*)(base + off0 + (i >> 2) * 24576 + (i & 2) * 2048 + (i & 1) * 512) =
          make_uint4(pack2(d[0], d[1]), pack2(d[4], d[5]), pack2(d[8], d[9]), pack2(d[12], d[13]));
      }
    }
    if (SAFE & 2) bar_sync(B_M + WG, 160); else bar_arrive(B_M + WG, 160);
  }
}

__device__ __forceinline__ void fill16(void* p, uint32_t v) {
  asm volatile("st.global.v4.u32 [%0], {%1,%1,%1,%1};" :: "l"(p), "r"(v) : "memory");
}
__device__ __forceinline__ void g_load(const Params& P, uint32_t sb) {
  const int lane = threadIdx.x & 31, w = __shfl_sync(~0u, (threadIdx.x >> 5) & 3, 0);
  if (w == 2) return;
  if (w < 2) { bar_sync(15, 192); fence_async_smem(); }
  uint32_t fl = 0;
#pragma unroll 1
  for (int n = w == 3 ? LOCK0 : 0; n < STEPS; n++) {
    if (w && n == LOCK0) { grid_wait(1, lds32(sb + S_GEN)); fl = near_half(XB_F, bid()) * 1024; }
    if (w == 3) {
      const uint32_t tag = (uint32_t)(n - LOCK0 + 1) << 24;
      uint32_t v; int it = 0;
      do { asm volatile("ld.relaxed.gpu.global.u32 %0, [%1];" : "=r"(v) : "l"(g_fl + fl + FL_TICK) : "memory"); spin_guard(it); } while (!NOCHAIN && v < tag);
      const uint32_t off = timer_offset(), now = clk(), t0 = now - ((v ^ tag) >> 24 ? DLYG : (now + off - v) & 0xFFFFFF);
      asm volatile("fence.acquire.gpu;" ::: "memory");
      if (lane == 0) T3(11);
      __syncwarp();
      wait_until(t0, DLYG);
      if (lane == 0) T3(4);
      bar_sync(B_OE, 160);
      continue;
    }
    if (w == 0 || n == 0) {
      if (n < NSEG) wait_flags(g_lnflag + n * 16 + (lane & 1) * 8, 1);
    } else if (!NOCHAIN && n >= LAG) {
      wait_flags(g_fl + fl + FL_F + (lane & 1) * 8, n - LAG + 1);
    }
    if (w) { if (lane == 0) T3(12); bar_sync(B_X, 96); }
    fence_async_global();
    const unsigned char* src = g_lnimg + (uint32_t)((w ? (n >= LAG ? NSEG + n - LAG : 0) : min(n, NSEG - 1)) * 36864);
#pragma unroll 1
    for (int ch = 0; ch < 9; ch++) {
      const uint32_t full = sb + G_BAR + ch * 8;
      mbar_wait(full + 128, (n & 1) ^ 1);
      if (elect()) {
        mbar_expect(full, ABL & 2 ? 16 : 4096);
        bulk_load(sb + G_RING + ch * 8192 + w * 4096, src + ch * 4096, ABL & 2 ? 16 : 4096, full);
      }
    }
  }
}

__device__ __forceinline__ void g_aux(const Params& P, uint32_t sb) {
  const int lane = threadIdx.x & 31, w = (threadIdx.x >> 5) & 3;
  if (w == 1 || w == 2) {
    const int q = g_unit(w - 1);
    uint32_t* f = g_fl + FL_G + q * 8;
#pragma unroll 1
    for (int n = 0; n < STEPS; n++) {
      const uint32_t ln = opaque_tid() & 31;
      uint4* z = (uint4*)g_oacc + (uint32_t)(((n + 1) % ARING) * (16 * DM) + q * 96 + ln);
      if (!(ABL & 16)) { fill16(z, 0); fill16(z + 32, 0); fill16(z + 64, 0); }
      if (n + 3 >= MRING && q < 80) fill16((uint4*)g_mimg + (uint32_t)(((n + 3) % MRING) * 4096 + q * 32 + ln), SENT);
      bar_sync(B_M + (w - 1), 160);
      if (lane == 0) { T3(w * 2 - 2); fence_async_global(); flag_release(f, n + 1); T3(w * 2 - 1); }
      __syncwarp();
    }
  } else {
    const uint32_t u = (bid() - N_CHAIN) * 2 + (w & 1), r = u / 36 * 16 + (u & 3) * 4 + (lane >> 3);
    uint32_t o = r * (DM / 8) + (u % 36 >> 2) * 8 + ((lane & 7) ^ ((r >> 1) & 3)), fl = 0;
#pragma unroll 1
    for (int k = -LAG - 1; k < STEPS; k++) {
      if (k < NSEG - 1) bar_sync(B_X, 96);
      if (k < LAG || u >= 72) continue;
      if (k == NSEG - 1) { fl = near_half(XB_F, bid()) * 1024; wait_flags(g_fl + fl + FL_F + (lane & 1) * 8, NSEG + 1); }
      const uint4 x = __ldcg((const uint4*)P.out + o);
      if (k >= NSEG - 1) wait_flags(g_fl + fl + FL_OCNT + (max(k, NSEG) % OCRING) * 8, N_O * 3 * (max(k, NSEG) / OCRING + 1));
      const float4* a = (const float4*)g_oacc + ((k % ARING) * (16 * DM) + 8 * DM + u * 64 + lane * 2);
      const float4 p = __ldcg(a), v = __ldcg(a + 1);
      ((uint4*)P.out)[o] = make_uint4(badd2(x.x, pack2(p.x, p.y)), badd2(x.y, pack2(p.z, p.w)), badd2(x.z, pack2(v.x, v.y)), badd2(x.w, pack2(v.z, v.w)));
      o += 4 * DM;
    }
    if ((threadIdx.x & 127) == 0) TS(7);
  }
}

template <int WG, bool HALF, int KS, int N> __device__ __forceinline__ void o_mma(float* d, const uint32_t* a, uint32_t ob) {
  constexpr uint64_t db = desc_sw128(O_RING + (KS >> 2) * 8192 + (KS & 3) * 32);
  constexpr uint64_t da = desc_sw128(O_W + WG * 40960 + (KS < 40 ? KS / 5 * 2 + KS % 5 / 2 : KS - 24) * 2048);
  if constexpr (KS < 40 && !(KS % 5 & 1)) {
    const uint32_t* r = a + (KS / 5 * 3 + KS % 5 / 2) * 4;
    if constexpr (HALF) wg_rs32k<KS != 0, db>(d, r[0], r[1], r[2], r[3], ob); else wg_rs64<KS != 0>(d, r, db);
  } else {
    if constexpr (HALF) wg_ss32k<da, db>(d, ob); else wg_ss64<1>(d, da, db);
  }
  if constexpr (N > 1) o_mma<WG, HALF, KS + 1, N - 1>(d, a, ob);
}
template <int WG, bool HALF, int GR> __device__ __forceinline__ void o_groups(float* d, const uint32_t* a, uint32_t sb, int n, bool more) {
  const uint32_t ob = n < NSEG ? 0 : 256;
  mbar_wait(sb + O_BAR + GR * 8, n & 1);
  if (GR == 0) { if ((threadIdx.x & 127) == 0) T3(13 + WG); __syncwarp(); }
  if (GR == (WG == 0 ? OTURN : 4) && (WG < 2 || n + 1 < STEPS)) bar_arrive(B_V + (WG + 1) % 3, 256);
  wg_fence();
  o_mma<WG, HALF, GR * 8, 8 - 2 * FASTO>(d, a, ob);
  if (GR == 4 && more) o_mma<WG, HALF, 40, 4>(d, a, ob);
  wg_commit();
  if (GR > 0) { wg_wait<1>(); if ((threadIdx.x & 31) == 0) mbar_arrive(sb + O_BAR + 128 + (GR - 1) * 8); }
  if constexpr (GR < 4) o_groups<WG, HALF, GR + 1>(d, a, sb, n, more);
}
template <int WG, bool HALF> __device__ __forceinline__ void o_step(const uint32_t* a, uint32_t sb, uint32_t st0, int n, bool more) {
  float d[HALF ? 16 : 32];
  if (WG > 0 || n > 0) bar_sync(B_V + WG, 256);
  o_groups<WG, HALF, 0>(d, a, sb, n, more);
  wg_wait<0>();
  if ((threadIdx.x & 31) == 0) mbar_arrive(sb + O_BAR + 128 + 4 * 8);
  if ((threadIdx.x & 127) == 0) T3(WG == 0 ? 1 : WG == 1 ? 8 : 12);
  __syncwarp();
#pragma unroll(HALF ? 1 : 2)
  for (int sl = 0; sl < 2; sl++) {
    mbar_wait(sb + OB_ST + WG * 16 + sl * 8, (n & 1) ^ (WG == 0));
    if (!HALF || sl == (n >= NSEG)) {
#pragma unroll
      for (int nb = 0; nb < 4; nb++) {
        const float* r = d + (HALF ? 0 : sl * 16) + nb * 4;
        const uint32_t ad = st0 + sl * 8192 + nb * 2048;
        sts32(ad, __float_as_uint(r[0]));
        sts32(ad + 256, __float_as_uint(r[1]));
        sts32(ad ^ 32, __float_as_uint(r[2]));
        sts32((ad ^ 32) + 256, __float_as_uint(r[3]));
      }
      fence_async_smem();
    }
    bar_arrive((sl ? B_G : B_M) + WG, 160);
  }
}
template <int WG>
__device__ __forceinline__ void o_math(const Params& P, uint32_t sb) {
  const bool more = bid() < N_CHAIN + N_G + 12;
  const int lane = threadIdx.x & 31, w = (threadIdx.x >> 5) & 3, g = lane >> 2, tq = lane & 3;
  uint32_t a[96];
  mbar_wait(sb + W_BAR + WG * 8, 0);
  load_frags<24>(a, sb + WG * 49152);
  fence_async_smem();
  bar_sync(B_INIT, 416);
  load_wg<OROLE>(P, sb, false, WG, w);
  mbar_wait(sb + W_BAR + WG * 8, 1);
  if ((threadIdx.x & 127) == 0) TS(4);
  const uint32_t st0 = sb + O_ST + tq * 512 + ((w * 16 + g) ^ (tq * 8)) * 4;
#pragma unroll 1
  for (int n = 0; n < STEPS; n++) {
    if (n < LAG || n >= NSEG) o_step<WG, true>(a, sb, st0, n, more); else o_step<WG, false>(a, sb, st0, n, more);
  }
}

__device__ __forceinline__ void o_aux(const Params& P, uint32_t sb) {
  const int i = bid() - N_CHAIN - N_G, ksl = i / 3;
  const int c0 = ksl * 11 - max(ksl - 4, 0), nc = ksl < 4 ? 11 : 10;
  const int lane = threadIdx.x & 31, w = __shfl_sync(~0u, (threadIdx.x >> 5) & 3, 0);
  if (w == 0) {
    bar_sync(B_INIT, 416);
    const uint32_t* f = g_fl + FL_O + near_half(XB_F + 1, bid()) * 1024 + min((c0 & ~1) + lane, (c0 + nc - 1) | 1);
#pragma unroll 1
    for (int n = 0; n < STEPS; n++) {
      const unsigned char* src = g_oimg + (uint32_t)(((n % RING) * N_CHAIN + c0) * 8192);
      if (!NOCHAIN) wait_flags(f, n + 1);
      fence_async_global();
      if (lane == 0) T3(0);
#pragma unroll
      for (int gr = 0; gr < 5; gr++) {
        const uint32_t full = sb + O_BAR + gr * 8, bytes = ABL & 4 ? 16 : (gr < 4 ? 2 : nc - 8) * 8192;
        mbar_wait(full + 128, (n & 1) ^ 1);
        if (elect()) {
          if (n < LAG || n >= NSEG) {
            mbar_expect(full, bytes >> 1);
            for (uint32_t o = gr * 16384 + (n < LAG ? 0 : 4096); o < gr * 16384 + bytes; o += 8192) bulk_load(sb + O_RING + o, src + o, 4096, full);
          } else {
            mbar_expect(full, bytes);
            bulk_load(sb + O_RING + gr * 16384, src + gr * 16384, bytes, full);
          }
        }
      }
    }
  } else {
#pragma unroll 1
    for (int n = 0; n < STEPS; n++) {
      float* dst = g_oacc + (uint32_t)((n % ARING) * (64 * DM) + ((i % 3) * 3 + (w - 1 + ksl) % 3) * 1024);
      const bool early = w == 3 && n < NSEG;
      bar_sync(B_M + (w - 1), 160);
      if (lane == 0) {
        T3(w * 2);
        if (n < NSEG && !(ABL & 8)) { bulk_reduce(dst, sb + O_ST, 4096); bulk_reduce(dst + 16 * DM, sb + O_ST + 4096, 4096); }
        asm volatile("cp.async.bulk.commit_group;" ::: "memory");
        if (early) {
          asm volatile("cp.async.bulk.wait_group.read 0;" ::: "memory");
          mbar_arrive(sb + OB_ST);
          T3(8 + w);
          bulk_done_inc(g_fl + FL_OCNT + (n % OCRING) * 8);
          T3(w * 2 + 1);
        }
      }
      __syncwarp();
      bar_sync(B_G + (w - 1), 160);
      if (lane == 0) {
        if (n >= LAG && !(ABL & 8)) { bulk_reduce(dst + 32 * DM, sb + O_ST + 8192, 4096); bulk_reduce(dst + 48 * DM, sb + O_ST + 12288, 4096); }
        asm volatile("cp.async.bulk.commit_group;\ncp.async.bulk.wait_group.read 1;" ::: "memory");
        if (!early) mbar_arrive(sb + OB_ST + (w % 3) * 16);
        asm volatile("cp.async.bulk.wait_group.read 0;" ::: "memory");
        mbar_arrive(sb + OB_ST + (w % 3) * 16 + 8);
        if (!early) {
          T3(8 + w);
          bulk_done_inc(g_fl + FL_OCNT + (n % OCRING) * 8);
          T3(w * 2 + 1);
        }
      }
      __syncwarp();
    }
  }
}

constexpr uint32_t Y_PITCH = 1168, Y_ROWS = 16 * Y_PITCH;
template <int R> __device__ __forceinline__ void y_rows(uint32_t* y, uint32_t src, uint32_t dst, int w, int bar) {
  const int lane = threadIdx.x & 31;
#pragma unroll
  for (int k = 0; k < 2 * R + 1; k++) {
    const int op = w + k * (16 / R);
    if (k == 2 * R && w >= 4) break;
    uint32_t a, b, c, d;
    ldsm4t(a, b, c, d, src + op * 512 + (lane & 16) * 16 + (lane & 7) * 32 + (lane & 8) * 2);
    stsm4(dst + (lane & 15) * Y_PITCH + op * 32 + (lane & 16), a, b, c, d);
  }
  bar_sync(bar, 512 / R);
  const uint32_t row = dst + ((w & 6) * 2 + (w >> 3) * 2 + (w & 1)) * Y_PITCH + lane * 4;
#pragma unroll
  for (int i = 0; i < 9 * R; i++) y[i] = lds32(row + i / 9 * 2 * Y_PITCH + i % 9 * 128);
}

__device__ __forceinline__ void f_role(const Params& P, uint32_t sb) {
  const int lane = threadIdx.x & 31, w = __shfl_sync(~0u, threadIdx.x >> 5, 0), r0 = (bid() - N_CHAIN - N_G - N_O) * 16;
  if (w == 8) {
    const uint32_t* fo = g_fl + FL_OCNT + near_half(XB_F, bid()) * 1024;
    fence_async_global();
#pragma unroll 1
    for (int n = 0; n < NSEG; n++) {
      bar_sync(2, 288);
      if (elect()) {
        mbar_expect(sb + F_BAR, 36864);
        bulk_load(sb + F_XY, P.X + (size_t)(n * 32 + r0) * DM, 18432, sb + F_BAR);
        bulk_load(sb + F_XY + 18432, g_yT + (size_t)(n * 32 + r0) * DM, 18432, sb + F_BAR);
        mbar_expect(sb + F_BAR + 8, 36864);
        T3(1);
      }
      wait_flags(fo + (n % OCRING) * 8, NOCHAIN == 5 ? 0 : N_O * 3 * (n / OCRING + 1));
      fence_async_global();
      if (elect()) { bulk_load(sb + F_A, g_oacc + (uint32_t)((n % ARING) * (64 * DM) + r0 * DM), 36864, sb + F_BAR + 8); T3(0); }
    }
  } else if (w == 9) {
#pragma unroll 1
    for (int n = 0; n < NSEG; n++) {
      const uint32_t st = sb + (n & 1) * 36864;
      unsigned char* p = g_lnimg + (uint32_t)((NSEG + n) * 36864 + r0 * 128);
      bar_sync(1, 288);
      if (elect()) {
        T3(2);
#pragma unroll
        for (int i = 0; i < 9; i++) bulk_store(p + i * 4096, st + F_L + i * 2048, 2048);
        asm volatile("cp.async.bulk.commit_group;" ::: "memory");
        bulk_done_inc(g_fl + FL_F + (bid() & 1) * 8);
        T3(3);
        bulk_store(P.out + (size_t)(n * 32 + r0) * DM, st + F_X, 18432);
        asm volatile("cp.async.bulk.commit_group;\ncp.async.bulk.wait_group.read 0;" ::: "memory");
        if (n + 1 == NSEG) bulk_done_inc(g_fl + FL_F + (bid() & 1) * 8);
      }
      __syncwarp();
    }
  } else if (w < 8) {
    const uint32_t row = sb + w * 1152 + lane * 4, acc = sb + F_A + w * 256 + (lane ^ ((w & 6) * 2)) * 8;
    const uint32_t ln = sb + F_L + w * 128 + (((lane >> 2) ^ w) << 4) + (lane & 3) * 4;
#pragma unroll 1
    for (int n = -1; n < NSEG; n++) {
      const uint32_t st = (n & 1) * 36864;
      uint32_t x[18], y[18], l[18];
      if (n >= 0) mbar_wait(sb + F_BAR, n & 1);
#pragma unroll
      for (int i = 0; i < 18; i++) x[i] = lds32(row + F_XY + i / 9 * 9216 + i % 9 * 128);
      y_rows<2>(y, sb + F_XY + 18432, sb + F_Y, w, 3);
      layernorm9<2>(x, l);
#pragma unroll
      for (int i = 0; i < 18; i++) x[i] = badd2(x[i], bmul2(l[i], y[i]));
      if (n >= 0) mbar_wait(sb + F_BAR + 8, n & 1);
      if (threadIdx.x == 0 && n >= 0) T3(4);
      __syncwarp();
      uint2 a[18];
#pragma unroll
      for (int i = 0; i < 18; i++) a[i] = lds64(acc + i / 9 * 2048 + i % 9 * 4096);
#pragma unroll
      for (int i = 0; i < 18; i++) x[i] = badd2(x[i], pack2(__uint_as_float(a[i].x), __uint_as_float(a[i].y)));
      if (n + 1 < NSEG) bar_arrive(2, 288);
      layernorm9<2>(x, l);
#pragma unroll
      for (int i = 0; i < 18; i++) { x[i] = badd2(x[i], bmul2(l[i], y[i])); sts32(row + st + F_X + i / 9 * 9216 + i % 9 * 128, x[i]); }
      layernorm9<2>(x, l);
#pragma unroll
      for (int i = 0; i < 18; i++) sts32(ln + st + i / 9 * 1024 + i % 9 * 2048, l[i]);
      fence_async_smem();
      if (n >= 0) bar_sync(1, 288); else bar_sync(3, 256);
    }
  }
}

constexpr uint32_t P_CH = 147456, P_CHSZ = 12800, P_H = 4352;
static_assert(P_CH + 6 * P_CHSZ <= G_BAR, "prologue smem");

template <int N>
__device__ __forceinline__ void conv_fold(float (*acc)[4], bool hi, uint32_t mine, uint32_t theirs, int bar, int cnt) {
#pragma unroll
  for (int i = 0; i < N / 2; i++) {
    uint4 v;
    v.x = __float_as_uint(hi ? acc[i][0] : acc[i + N / 2][0]); v.y = __float_as_uint(hi ? acc[i][1] : acc[i + N / 2][1]);
    v.z = __float_as_uint(hi ? acc[i][2] : acc[i + N / 2][2]); v.w = __float_as_uint(hi ? acc[i][3] : acc[i + N / 2][3]);
    sts128(mine + i * 512, v);
  }
  bar_sync(bar, cnt);
#pragma unroll
  for (int i = 0; i < N / 2; i++) {
    const uint4 v = lds128(theirs + i * 512);
    acc[i][0] = (hi ? acc[i + N / 2][0] : acc[i][0]) + __uint_as_float(v.x); acc[i][1] = (hi ? acc[i + N / 2][1] : acc[i][1]) + __uint_as_float(v.y);
    acc[i][2] = (hi ? acc[i + N / 2][2] : acc[i][2]) + __uint_as_float(v.z); acc[i][3] = (hi ? acc[i + N / 2][3] : acc[i][3]) + __uint_as_float(v.w);
  }
}
template <int N>
__device__ __forceinline__ void conv_store(const float (*acc)[4], int tile0, uint32_t su, int d, uint32_t dd) {
  const int lane = threadIdx.x & 31, g = lane >> 2, tq = lane & 3;
#pragma unroll
  for (int i = 0; i < N; i++) {
    const uint32_t ad = su + (8 + (tile0 + i) * 8 + g) * 32 + tq * 4, sw = (g & 4) << 2;
    const uint32_t lo = badd2(movmat(pack2(acc[i][0], acc[i][1])), bmul2(lds32(ad + sw), dd));
    const uint32_t hi = badd2(movmat(pack2(acc[i][2], acc[i][3])), bmul2(lds32(ad + (sw ^ 16)), dd));
    ((uint2*)g_yT)[(((tile0 + i) * 8 + g) * DM + d) * 4 + tq] = make_uint2(lo, hi);
  }
}

__device__ __forceinline__ void prologue(const Params& P, uint32_t sb) {
  const int b = bid(), tid = threadIdx.x, lane = tid & 31, warp = tid >> 5, t0 = b * 16;
  const bool isg = b >= N_CHAIN && b < N_CHAIN + N_G;
  const int nch = isg ? 2 : b < 128 ? 6 : 0, chb = b < N_CHAIN ? b * 6 : isg ? b * 2 + 256 : b * 6 - 192;
  const uint32_t tstart = clk();
  if (tid < 288) {
    if (b < 128) {
      const int c = (tid >> 1) * 4, tt = t0 + (tid & 1) * 8;
      uint2 kr[11], vr[8];
#pragma unroll
      for (int i = 0; i < 11; i++) { const int t = tt + i - 3; kr[i] = t >= 0 ? __ldg((const uint2*)(P.K + (size_t)t * DM + c)) : make_uint2(0, 0); }
#pragma unroll
      for (int i = 0; i < 8; i++) vr[i] = __ldg((const uint2*)(P.V + (size_t)(tt + i) * DM + c));
#pragma unroll
      for (int e = 0; e < 2; e++) {
        const uint4 sh = __ldg((const uint4*)(P.shift + c * 4) + e);
        const uint32_t s0 = __byte_perm(sh.x, sh.z, 0x5410), s1 = __byte_perm(sh.x, sh.z, 0x7632);
        const uint32_t s2 = __byte_perm(sh.y, sh.w, 0x5410), s3 = __byte_perm(sh.y, sh.w, 0x7632);
        uint32_t v[8];
#pragma unroll
        for (int i = 0; i < 8; i++) {
          const uint32_t k3 = e ? kr[i].y : kr[i].x, k2 = e ? kr[i + 1].y : kr[i + 1].x, k1 = e ? kr[i + 2].y : kr[i + 2].x, k0 = e ? kr[i + 3].y : kr[i + 3].x;
          v[i] = bmul2(badd2(badd2(badd2(bmul2(k3, s3), bmul2(k2, s2)), bmul2(k1, s1)), bmul2(k0, s0)), e ? vr[i].y : vr[i].x);
        }
        *(uint4*)(g_kvT + (size_t)(c + 2 * e) * KVP + tt) =
          make_uint4(__byte_perm(v[0], v[1], 0x5410), __byte_perm(v[2], v[3], 0x5410), __byte_perm(v[4], v[5], 0x5410), __byte_perm(v[6], v[7], 0x5410));
        *(uint4*)(g_kvT + (size_t)(c + 2 * e + 1) * KVP + tt) =
          make_uint4(__byte_perm(v[0], v[1], 0x7632), __byte_perm(v[2], v[3], 0x7632), __byte_perm(v[4], v[5], 0x7632), __byte_perm(v[6], v[7], 0x7632));
      }
    }
  } else if (tid < 384) {
    const int t = tid - 288;
    for (int i = b * 96 + t; i < 16 * DM; i += N_CTA * 96) ((uint4*)g_oacc)[i] = make_uint4(0, 0, 0, 0);
    if (b * 96 + t < 128 * 8) g_lnflag[b * 96 + t] = 0;
    if (t == 95) sts32(sb + S_GEN, ld_acquire(g_gbar));
    __syncwarp();
    wait_until(tstart, P.dly[23]);
    for (int i = t; i < 32 * nch; i += 96) asm volatile("prefetch.global.L2 [%0];" :: "l"(P.Hk + (size_t)chb * SEQ + i * 64));
  }
  if (warp < 12) {
    bar_arrive(10, 416);
    if (tid == 128) TS(14);
    const int ch = 5 - (warp >> 1), sub = warp & 1, d = chb + ch;
    const uint32_t su = sb + P_CH + ch * P_CHSZ;
    if (ch < nch) {
      const uint32_t* hs = (const uint32_t*)(P.Hk + (size_t)d * SEQ);
#pragma unroll
      for (int q = sub * 32 + lane; q < 256; q += 64) {
        const uint4 c = __ldg((const uint4*)hs + q);
        const uint32_t prev = q ? __ldg(hs + 4 * q - 1) : 0u;
        sts128(su + P_H + 32 + q * 16, make_uint4(__byte_perm(c.x, prev, 0x7610), __byte_perm(c.y, c.x, 0x7610), __byte_perm(c.z, c.y, 0x7610), __byte_perm(c.w, c.z, 0x7610)));
        sts128(su + P_H + 4224 + q * 16, make_uint4(__byte_perm(c.x, 0, 0x1032), __byte_perm(c.y, 0, 0x1032), __byte_perm(c.z, 0, 0x1032), __byte_perm(c.w, 0, 0x1032)));
      }
      if (sub == 1 && lane == 0) sts32(su + P_CHSZ - 16, __bfloat16_as_ushort(P.Dk[d]) * 0x10001u);
      if (sub == 0 && lane < 20) sts128(su + (lane < 16 ? lane * 16 : P_H + (lane & 2) * 2096 + (lane & 1) * 16), make_uint4(0, 0, 0, 0));
    }
    bar_sync(11, 416);
    if (ch < nch) {
#pragma unroll
      for (int q = sub * 32 + lane; q < 256; q += 64) {
        const int row = (q >> 1) + 8;
        sts128(su + row * 32 + (((q & 1) ^ ((row >> 2) & 1)) << 4), __ldcg((const uint4*)(g_kvT + (size_t)d * KVP) + q));
      }
    }
    const int g = lane >> 2, tq = lane & 3;
    const uint32_t sh = su + P_H + (g & 1) * 4192 + (8 + (g >> 1) - tq) * 4;
    float acc[16][4];
#pragma unroll
    for (int i = 0; i < 16; i++) { acc[i][0] = acc[i][1] = acc[i][2] = acc[i][3] = 0.f; }
    auto u_addr = [&](int res) {
      const int row = 8 - res + ((lane >> 4) << 3) + (lane & 7);
      return su + row * 32 + ((((lane >> 3) & 1) ^ ((row >> 2) & 1)) << 4);
    };
    if (ch < nch) {
      bar_sync(1 + ch, 64);
      if (tid == 352) TS(11);
      if (sub) {
#pragma unroll 4
        for (int res = 0; res < 8; res++) {
          uint32_t b0, b1, b2, b3;
          ldsm4(b0, b1, b2, b3, u_addr(res));
          const uint32_t r0 = lds32(sh + res * 32);
          mma16(acc[0], r0, lds32(sh + res * 32 + 16), lds32(sh + res * 32 - 16), r0, b0, b1);
        }
        conv_store<1>(acc, 0, su, d, lds32(su + P_CHSZ - 16));
      }
    }
    bar_arrive(12, 416);
    if (isg && warp < 8) { while ((int)(clk() - tstart - S1G) < 0) __nanosleep(200); load_wg<GROLE>(P, sb, true, warp >> 2, warp & 3); }
    if (ch < nch) {
#pragma unroll 1
      for (int res = sub * 4; res < sub * 4 + 4; res++) {
        uint32_t bf[16][2];
        const uint32_t ad = u_addr(res);
#pragma unroll
        for (int f = 0; f < 16; f += 2) ldsm4(bf[f][0], bf[f][1], bf[f + 1][0], bf[f + 1][1], ad + f * 256);
#pragma unroll
        for (int k = 0; k < 16; k++) {
          const int jj = k & 1 ? k >> 1 : 15 - (k >> 1);
          const uint32_t ah = sh + (8 * jj + res) * 32;
          const uint32_t r0 = lds32(ah), r1 = lds32(ah + 16), rm = lds32(ah - 16);
#pragma unroll
          for (int i = max(jj, 1); i < 16; i++) mma16(acc[i], r0, r1, rm, r0, bf[i - jj][0], bf[i - jj][1]);
        }
      }
      bar_sync(1 + ch, 64);
      if (tid == 352) TS(12);
      const uint32_t xb = su + P_H + lane * 16, dd = lds32(su + P_CHSZ - 16);
      conv_fold<16>(acc, sub, xb + sub * 4096, xb + (sub ^ 1) * 4096, 1 + ch, 64);
      conv_store<8>(acc, sub * 8, su, d, dd);
    }
  } else {
    for (int i = b; i < 194 + MRING * 5; i += N_CTA) {
      const int n = (i - 194) / 5, r = (i - 194) % 5, blk = i < 192 ? i / 6 * 8 + i % 6 : i < 194 ? XB_F + i - 192 : XB_M + n * 8 + r;
      const uint32_t fill = i < 194 ? 0u : SENT;
#pragma unroll 1
      for (int q = tid - 384; q < 256 && warp < 15; q += 96) {
        uint4 v = make_uint4(fill, fill, fill, fill);
        if (i >= 194 && n == 0 && (r > 0 || q < 128)) {
          const bf16* m = P.mem0 + (max(r * 8 - 4, 0) + (q >> 5)) * 16 + ((q >> 1) & 1) * 8 + ((q >> 2) & 7);
          v.x = pack2(__bfloat162float(m[0]), __bfloat162float(m[DM])); v.y = pack2(__bfloat162float(m[2 * DM]), __bfloat162float(m[3 * DM]));
          v.z = pack2(__bfloat162float(m[4 * DM]), __bfloat162float(m[5 * DM])); v.w = pack2(__bfloat162float(m[6 * DM]), __bfloat162float(m[7 * DM]));
        }
        g_xb[blk * 512 + q] = v;
        g_xb[blk * 512 + 256 + q] = v;
      }
    }
    if (tid < 388) g_xb[XB_REF * 512 + (tid & 2) * 128 + (b & ~1) + (tid & 1)] = make_uint4(0, 0, 0, 0);
    else if (tid < 392 && b < N_GRP) g_xb[(b * 8 + 7) * 512 + (tid & 2) * 128 + (tid & 1)] = make_uint4(0, 0, 0, 0);
    if (warp < 15) { bar_arrive(9, 128); bar_sync(7, 96); }
    if (tid == 384) TS(8);
    if (warp == 12) {
      const bf16* w = lane < 6 ? (lane % 3 == 0 ? P.Wk : lane % 3 == 1 ? P.Wv : P.Wq) + (((b >> 5) * 2 + lane / 3) * 32 + (b & 31)) * 2048
                               : (lane < 8 ? P.Wo + (lane - 6) * (9 * 131072) : P.X) + b * 2048;
      uint32_t t = tstart + P.dly[19];
      if ((int)(clk() - t) > 0) t = clk();
#pragma unroll 1
      for (int st = 0; st < 9 && b < N_CHAIN; st++) {
#pragma unroll 1
        for (int i = 0; i < 9; i++, t += PACE) {
          wait_until(t, 0);
          if (lane == st) asm volatile("cp.async.bulk.prefetch.L2.global [%0], 4096;" :: "l"(w + i * (lane < 6 ? 262144 : 131072)) : "memory");
        }
      }
      if (lane == 0) TS(10);
    } else if (warp == 15) {
      bar_sync(10, 416);
      if (lane == 0) { grid_arrive(0); if (nch) grid_wait(0, lds32(sb + S_GEN)); }
      __syncwarp();
      bar_arrive(11, 416);
      if (lane == 0) TS(1);
      bar_sync(9, 128);
      bar_sync(12, 416);
      if (lane == 0) { TS(16); grid_arrive(2); TS(17); }
    } else if (lane == 0) {
      if (warp == 13 || (warp == 14 && b < N_GRP)) {
        uint32_t* p = (uint32_t*)(g_xb + (warp == 13 ? XB_REF * 512 + b : (b * 8 + 7) * 512));
        int votes = 0;
        for (int rep = 0; rep < 24 && abs(votes) < 7; rep++) {
          uint32_t v0, v1, c0, c1;
          asm volatile("atom.relaxed.gpu.global.add.u32 %0, [%4], 1;\n atom.relaxed.gpu.global.add.u32 %1, [%5], 1;\n"
                       "{.reg .pred p; setp.eq.u32 p, %0, 0x7ffffff3; @p trap; mov.u32 %2, %%clock; setp.eq.u32 p, %1, 0x7ffffff3; @p trap; mov.u32 %3, %%clock;}"
                       : "=&r"(v0), "=&r"(v1), "=&r"(c0), "=&r"(c1) : "l"(p + (rep & 1) * 1024), "l"(p + ((rep & 1) ^ 1) * 1024) : "memory");
          votes += ((c1 - c0 > 80u) == (rep & 1)) ? 1 : -1;
        }
        if (warp == 13) { g_side[b] = votes > 0; TS(9); } else g_near[b] = votes > 0;
      }
    }
    __syncwarp();
    if (warp > 12 && b < N_CHAIN) {
      while ((int)(clk() - tstart - S1DLY) < 0) __nanosleep(200);
      for (int k = warp - 13; k < 8; k += 3) load_wg<CHAIN>(P, sb, true, 1 - k / 4, k & 3);
    }
  }
  if (b < N_CHAIN + N_G && (warp < 8 || (isg && warp >= 12))) bar_arrive(0, 512); else bar_sync(0, 512);
  if (tid == 352) TS(2);
}

__device__ __forceinline__ void publish_y() {
  if (threadIdx.x == 383) { grid_arrive(1); TS(18); }
  __syncwarp();
}

template <int R> __device__ __forceinline__ void ln_tiles(const Params& P, uint32_t sb) {
  const int lane = threadIdx.x & 31, w = (threadIdx.x >> 5) & (16 / R - 1), half = R == 1 ? 0 : threadIdx.x >> 8, u = N_CTA - 1 - bid();
  const int first = R == 1 ? u : 46 - 2 * u + half, step = R == 1 ? 4 : 40, last = R == 1 ? 8 : 128;
  const uint32_t raw = sb + P_CH + half * (18432 + Y_ROWS), mb = sb + T_BAR + (R - 1 + half) * 8;
  const bool lead = w == 16 / R - 1 && lane == 0;
  auto load_y = [&](const bf16* src, int tile) {
    fence_async_global();
    mbar_expect(mb, 18432);
    bulk_load(raw, src + (size_t)tile * 16 * DM, 18432, mb);
  };
  uint32_t nx[9 * R];
  auto load_x = [&](int tile) {
#pragma unroll
    for (int i = 0; i < 9 * R; i++) nx[i] = __ldg((const uint32_t*)(P.X + (size_t)(tile * 16 + w + i / 9 * 8) * DM) + i % 9 * 32 + lane);
  };
  load_x(first);
  if (R == 2) {
    if (lead) { grid_wait(1, lds32(sb + S_GEN)); if (u > 3) TS(13); load_y(g_yT, first); }
    __syncwarp();
  }
#pragma unroll 1
  for (int tile = first, real = R - 1, ph = 0; tile < last; tile += real * step, real = 1, ph ^= 1) {
    uint32_t x[9 * R], l[9 * R], y[9 * R];
    const bool ts = threadIdx.x == 0 && (R == 1 ? tile == first : u > 3 && tile == first + step);
    if (ts) TS(26);
#pragma unroll
    for (int i = 0; i < 9 * R; i++) x[i] = nx[i];
    layernorm9<R>(x, l);
    if (real && tile + step < last) load_x(tile + step);
    if (R == 2 && tile == first + step && u >= N_F && w < 6) load_wg<OROLE>(P, sb, true, w >> 1, half * 2 + (w & 1));
    if (R == 1 && tile == first && lead) {
      if (real) grid_wait(2, lds32(sb + S_GEN));
      TS(13);
      load_y(real ? g_yT : P.Hk, tile);
    }
    bar_sync(13 + half, 512 / R);
    mbar_wait(mb, ph);
    if (ts) TS(28);
    y_rows<R>(y, raw, raw + 18432, w, 13 + half);
    if (ts) TS(29);
    if (lead && real && tile + step < last) { fence_async_smem(); load_y(g_yT, tile + step); }
    __syncwarp();
#pragma unroll
    for (int i = 0; i < 9 * R; i++) x[i] = badd2(x[i], bmul2(l[i], y[i]));
    layernorm9<R>(x, l);
    if (ts && l[0] != 0x12345) TS(30);
#pragma unroll
    for (int r = 0; r < R; r++) store_ln_row(0, tile * 16 + w + r * 8, l + r * 9);
    if (R == 1) {
      __syncthreads();
      if (threadIdx.x == 32 && real) { if (tile < 4) TS(19); st_release(g_lnflag + tile * 8, 1); if (tile < 4) TS(20); }
      __syncwarp();
    }
    if (ts) TS(31);
  }
  if (R == 2) {
    __syncthreads();
    if (threadIdx.x >= 506) {
      asm volatile("fence.acq_rel.gpu;" ::: "memory");
      st_relaxed_if(g_lnflag + ((first ^ (lane & 1)) + (lane - 26) / 2 * step) * 8, 1, true);
    }
    __syncwarp();
    fence_async_smem();
    if (threadIdx.x == 0) TS(15);
  }
}

__global__ void __cluster_dims__(2, 1, 1) __launch_bounds__(512, 1) k_main(const __grid_constant__ Params P) {
  extern __shared__ __align__(1024) unsigned char smem[];
  const uint32_t sb = (uint32_t)__cvta_generic_to_shared(smem);
  const int b = bid(), wg = threadIdx.x >> 7;
  if ((threadIdx.x & 127) == 0) TS(0);
  if (threadIdx.x == 480) {
    if ((sb & 0xFFFFFF) != SBASE) __trap();
    for (int i = 0; i < 6; i++) mbar_init(sb + W_BAR + i * 8, 1);
    if (b < N_CHAIN) {
      mbar_init(sb + CB_FULL, 1); mbar_init(sb + CB_FULL + 8, 1);
      mbar_init(sb + CB_REF, 1);
      mbar_init(sb + CB_SX, 1); mbar_init(sb + CB_OX, 1); mbar_init(sb + CB_XX, 1); mbar_init(sb + CB_Q, 2); mbar_init(sb + CB_VF, 1); mbar_init(sb + CB_VF + 8, 1);
      sts32(sb + C_BAD, 0);
      for (int i = 0; i < 11; i++) mbar_init(sb + CB_M + i * 8, i == 0 ? 5 : i == 5 ? 3 : 1);
    } else if (b < N_CHAIN + N_G) {
      for (int i = 0; i < 9; i++) { mbar_init(sb + G_BAR + i * 8, 2); mbar_init(sb + G_BAR + 128 + i * 8, 8); }
    } else if (b < N_CHAIN + N_G + N_O) {
      for (int i = 0; i < 5; i++) { mbar_init(sb + O_BAR + i * 8, 1); mbar_init(sb + O_BAR + 128 + i * 8, 12); }
      for (int i = 0; i < 6; i++) mbar_init(sb + OB_ST + i * 8, 1);
    } else {
      mbar_init(sb + F_BAR, 1); mbar_init(sb + F_BAR + 8, 1);
    }
    asm volatile("fence.mbarrier_init.release.cluster;" ::: "memory");
    fence_async_smem();
  }
  __syncwarp();
  asm volatile("barrier.cluster.arrive.relaxed.aligned;" ::: "memory");
  prologue(P, sb);
  asm volatile("barrier.cluster.wait.aligned;" ::: "memory");
  fence_async_smem();
  if (b >= N_CHAIN + N_G) publish_y();
  if (b >= 128) ln_tiles<1>(P, sb);
  if (b >= N_CHAIN + N_G) ln_tiles<2>(P, sb);
  if ((threadIdx.x & 127) == 0) TS(3);
  if (b < N_CHAIN) {
    if (wg < 2) { reg_inc<200>(); chain_proj(P, sb); }
    else if (wg == 2) { reg_dec<ATTR>(); publish_y(); chain_attn(P, sb); }
    else { reg_dec<112 - ATTR>(); chain_aux(P, sb); }
  } else if (NOBULK) {
    if (b < N_CHAIN + N_G) publish_y();
    {
      if (wg == 0) {
        float d[4] = {0.f, 0.f, 0.f, 0.f};
        for (int n = 0; n < STEPS - 1; n++) {
          const uint32_t* f = g_fl + FL_TICK;
          uint32_t x;
          do { for (int k = 0; k < 16; k++) mma16(d, 0, 0, 0, 0, 0, 0); asm volatile("ld.relaxed.gpu.global.u32 %0, [%1];" : "=r"(x) : "l"(f) : "memory"); } while ((x >> 24) <= n);
          const int q = (b - N_CHAIN) * 4 + (threadIdx.x >> 5);
          if (n + 5 >= MRING && q < 80) fill16((uint4*)g_mimg + (uint32_t)(((n + 5) % MRING) * 4096 + q * 32 + (threadIdx.x & 31)), SENT);
        }
        if (d[0] == 1.f) P.out[0] = __float2bfloat16(0.f);
      }
    }
  } else if (b < N_CHAIN + N_G) {
    if (wg == 0) { reg_inc<232>(); g_math<0>(P, sb); }
    else if (wg == 1) { reg_inc<232>(); g_math<1>(P, sb); }
    else if (wg == 2) { reg_dec<24>(); bar_arrive(15, 192); publish_y(); g_aux(P, sb); }
    else { reg_dec<24>(); g_load(P, sb); }
  } else if (b < N_CHAIN + N_G + N_O) {
    if (wg == 0) { reg_inc<160>(); o_math<0>(P, sb); }
    else if (wg == 1) { reg_inc<160>(); o_math<1>(P, sb); }
    else if (wg == 2) { reg_inc<160>(); o_math<2>(P, sb); }
    else { reg_dec<32>(); o_aux(P, sb); }
  } else {
    f_role(P, sb);
  }
}

}

extern "C" void kernel_launch(void* const* d_in, const int* in_sizes, int n_in, void* d_out, int out_size) {
  typedef CUresult (*Encode)(CUtensorMap*, CUtensorMapDataType, cuuint32_t, void*, const cuuint64_t*, const cuuint64_t*, const cuuint32_t*, const cuuint32_t*,
                             CUtensorMapInterleave, CUtensorMapSwizzle, CUtensorMapL2promotion, CUtensorMapFloatOOBfill);
  static Encode encode = nullptr;
  if (!encode) cudaGetDriverEntryPoint("cuTensorMapEncodeTiled", (void**)&encode, cudaEnableDefault);
  Params P;
  for (int i = 0; i < 11; i++) {
    const bool wo = i == 6 || i == 7;
    const cuuint64_t cols = wo ? DM : HD, rows = HD + DM - cols, pitch = cols * 2;
    const cuuint64_t dim[4][5] = {{cols, 2, 8, 2, 18}, {cols, 16, 1, 1, rows / 16}, {cols, 2, 4, 4, rows / 32}, {64, 16, 64, 2, 18}};
    const cuuint64_t stride[4][4] = {{8 * pitch, pitch, 16 * pitch, 32 * pitch}, {pitch, pitch, pitch, 16 * pitch},
                                     {pitch, 8 * pitch, 2 * pitch, 32 * pitch}, {pitch, 128, 16 * pitch, 32 * pitch}};
    const cuuint32_t box[4][5] = {{64, 2, 8, 1, 18}, {64, 16, 1, 1, 1}, {64, 2, 4, 2, 1}, {64, 16, 2, 1, 18}}, one[5] = {1, 1, 1, 1, 1};
    const int k = i < 3 ? 0 : i < 7 ? 1 : i < 8 ? 2 : 3;
    encode(&P.map[i], CU_TENSOR_MAP_DATA_TYPE_BFLOAT16, 5, d_in[wo ? 11 : 8 + (i & 7) % 3], dim[k], stride[k], box[k], one,
           CU_TENSOR_MAP_INTERLEAVE_NONE, CU_TENSOR_MAP_SWIZZLE_128B, CU_TENSOR_MAP_L2_PROMOTION_L2_128B, CU_TENSOR_MAP_FLOAT_OOB_FILL_NONE);
  }
  P.X = (const bf16*)d_in[0]; P.K = (const bf16*)d_in[1]; P.V = (const bf16*)d_in[2];
  P.shift = (const bf16*)d_in[3]; P.Hk = (const bf16*)d_in[4]; P.Dk = (const bf16*)d_in[5];
  P.mem0 = (const bf16*)d_in[7];
  P.Wq = (const bf16*)d_in[8]; P.Wk = (const bf16*)d_in[9]; P.Wv = (const bf16*)d_in[10]; P.Wo = (const bf16*)d_in[11];
  P.out = (bf16*)d_out;
  for (int i = 0; i < 24; i++) P.dly[i] = h_dly[i];
  cudaFuncSetAttribute(k_main, cudaFuncAttributeMaxDynamicSharedMemorySize, SMEM_BYTES);
  k_main<<<N_CTA, 512, SMEM_BYTES>>>(P);
}
```

```cpp
#include <cuda.h>
#include <cuda_runtime.h>
#include <cuda_bf16.h>
#include <stdint.h>

namespace {

typedef __nv_bfloat16 bf16;

constexpr int SEQ = 2048, DM = 576, HD = 4096, NSEG = 64;
constexpr int LAG = 7, STEPS = NSEG + LAG, RING = 8;
constexpr int LOCK0 = 3, QRING = LOCK0 + 1;
static_assert(LAG < RING, "ring");
constexpr int N_CHAIN = 64, N_G = 48, N_O = 18, N_F = 2;
constexpr uint32_t SBASE = 1024;
constexpr uint32_t SENT = 0xFFFFFFFFu;
constexpr int SPIN_MAX = 1 << 22;

__device__ __forceinline__ uint32_t bid() {
  uint32_t b;
  asm volatile("mov.u32 %0, %%ctaid.x;" : "=r"(b));
  return b < 6 ? b + 106 : b < 8 ? b + 122 : b < 114 ? b - 8 : b < 130 ? b - 2 : b;
}
__device__ __forceinline__ uint32_t chain_id() { return blockIdx.x - 8; }
constexpr int KVP = SEQ + 64;
__device__ __align__(1024) bf16 g_kvT[DM * KVP];
__device__ __align__(1024) bf16 g_yT[DM * SEQ];
__device__ __align__(1024) unsigned char g_lnimg[2 * NSEG * 9 * 4096];
__device__ __align__(1024) unsigned char g_qkv[QRING * N_CHAIN * 24576];
__device__ __align__(1024) unsigned char g_oimg[RING * N_CHAIN * 8192];
constexpr int ARING = 16;
static_assert(ARING >= LAG + 9, "accumulator ring");
__device__ __align__(1024) float g_oacc[ARING * 64 * DM];
constexpr int MRING = LAG + 4, N_GRP = 32 + MRING + 1;
constexpr int XB_M = 256, XB_F = XB_M + MRING * 8, XB_REF = XB_F + 2, N_CTA = N_CHAIN + N_G + N_O + N_F;
__device__ __align__(65536) uint4 g_xb[N_GRP * 4096];
#define g_mimg ((uint32_t*)(g_xb + XB_M * 512))
__device__ uint32_t g_near[N_GRP];
__device__ uint32_t g_side[N_CTA];
__device__ __align__(128) uint32_t g_gbar[3 * 32];
constexpr int FL_G = 0, FL_F = 96 * 8, FL_OCNT = FL_F + 2 * 8, OCRING = 16, FL_TICK = 992, FL_O = 2048, FL_SYNC = FL_O + 128;
static_assert(FL_OCNT + OCRING * 8 <= FL_TICK, "flag block");
#define g_fl ((uint32_t*)(g_xb + XB_F * 512))
__device__ __align__(1024) uint32_t g_lnflag[128 * 8];
#define TS(slot)

#define CNT(slot, tries)
#define T3(slot)
#define TR(slot)
#define TRV(slot, val)
#define TRD(slot, dep)
#define TRSYNC()
#define TRDUMP(n)
#define CLK(t) "{.reg .b64 x; .reg .b32 h; mov.u64 x, %%clock64; mov.b64 {" t ", h}, x;}"
__device__ __forceinline__ uint32_t clk() { uint32_t t; asm volatile(CLK("%0") : "=r"(t) :: "memory"); return t; }
__device__ __forceinline__ void wait_until(uint32_t t0, uint32_t d) {
  asm volatile("{.reg .pred p; .reg .u32 t;\n"
               "W: " CLK("t") " sub.u32 t, t, %0; setp.lt.s32 p, t, 0; @p bra.uni W;}"
               :: "r"(t0 + d) : "memory");
}
__device__ __forceinline__ uint32_t pack2(float lo, float hi) {
  uint32_t r; asm("cvt.rn.bf16x2.f32 %0, %1, %2;" : "=r"(r) : "f"(hi), "f"(lo)); return r;
}
__device__ __forceinline__ float bf_lo(uint32_t v) { return __uint_as_float(v << 16); }
__device__ __forceinline__ float bf_hi(uint32_t v) { return __uint_as_float(v & 0xFFFF0000u); }

__device__ __forceinline__ void st_b128(void* p, uint32_t a, uint32_t b, uint32_t c, uint32_t d) {
  asm volatile("{.reg .b128 v; mov.b128 v, {%1,%2,%3,%4}; st.relaxed.gpu.global.b128 [%0], v;}" :: "l"(p), "r"(a), "r"(b), "r"(c), "r"(d) : "memory");
}
__device__ __forceinline__ void st_relaxed_if(void* p, uint32_t a, bool on) {
  asm volatile("{.reg .pred p; setp.ne.u32 p, %2, 0; @p st.relaxed.gpu.global.u32 [%0], %1;}" :: "l"(p), "r"(a), "r"((uint32_t)on) : "memory");
}
__device__ __forceinline__ uint32_t ld_acquire(const uint32_t* p) {
  uint32_t v; asm volatile("ld.acquire.gpu.global.u32 %0, [%1];" : "=r"(v) : "l"(p) : "memory"); return v;
}
__device__ __forceinline__ void st_release(uint32_t* p, uint32_t v) {
  asm volatile("st.release.gpu.global.u32 [%0], %1;" :: "l"(p), "r"(v) : "memory");
}
__device__ __forceinline__ void bulk_reduce(float* dst, uint32_t src, uint32_t bytes) {
  asm volatile("cp.reduce.async.bulk.global.shared::cta.bulk_group.add.f32 [%0], [%1], %2;" :: "l"(dst), "r"(src), "r"(bytes) : "memory");
}
__device__ __forceinline__ void bulk_done_inc(uint32_t* p) {
  asm volatile("cp.async.bulk.wait_group 0;\n"
               "fence.proxy.async.global;\nfence.release.gpu;\n"
               "red.relaxed.gpu.global.add.u32 [%0], 1;\nred.relaxed.gpu.global.add.u32 [%0+4096], 1;" :: "l"(p) : "memory");
}
__device__ __forceinline__ void flag_release(uint32_t* p, uint32_t v) {
  asm volatile("fence.release.gpu;\nst.relaxed.gpu.global.u32 [%0], %1;\nst.relaxed.gpu.global.u32 [%0+4096], %1;" :: "l"(p), "r"(v) : "memory");
}
__device__ __forceinline__ void spin_guard(int& it) {
  asm volatile("{.reg .pred p; add.s32 %0, %0, 1; setp.gt.s32 p, %0, %1; @p trap;}" : "+r"(it) : "n"(SPIN_MAX));
}
__device__ __forceinline__ void wait_flags(const uint32_t* p, uint32_t v) {
  int it = 0;
  while (true) {
    uint32_t x; asm volatile("ld.relaxed.gpu.global.u32 %0, [%1];" : "=r"(x) : "l"(p) : "memory");
    if (__all_sync(~0u, x >= v)) break;
    spin_guard(it);
  }
  asm volatile("fence.acquire.gpu;" ::: "memory");
}
__device__ __forceinline__ uint32_t timer_offset() {
  uint32_t g0, g;
  asm volatile("mov.u32 %0, %%globaltimer_lo;" : "=r"(g0) :: "memory");
  do { asm volatile("mov.u32 %0, %%globaltimer_lo;" : "=r"(g) :: "memory"); } while (g == g0);
  return (g >> 5) * 58 - clk();
}
__device__ __forceinline__ void grid_arrive(int i) {
  asm volatile("red.release.gpu.global.add.u32 [%0], %1;" :: "l"(g_gbar + i * 32), "r"(bid() ? 1u : 257u - N_CTA) : "memory");
}
__device__ __forceinline__ void grid_wait(int i, uint32_t gen) {
  int it = 0;
  while (((ld_acquire(g_gbar + i * 32) ^ gen) >> 8) == 0) spin_guard(it);
}
__device__ __forceinline__ bool elect() {
  uint32_t r; asm volatile("{.reg .pred p; elect.sync _|p, -1; selp.u32 %0, 1, 0, p;}" : "=r"(r)); return r;
}
__device__ __forceinline__ void bar_sync(int id, int cnt) { asm volatile("bar.sync %0, %1;" :: "r"(id), "r"(cnt) : "memory"); }
__device__ __forceinline__ void bar_arrive(int id, int cnt) { asm volatile("bar.arrive %0, %1;" :: "r"(id), "r"(cnt) : "memory"); }
template <int id, int cnt> __device__ __forceinline__ void bar_arrive_after(uint32_t a, uint32_t b) {
  asm volatile("{.reg .pred p; setp.ne.u32 p, %2, 0xfff12345; setp.ne.and.u32 p, %3, 0xfff12345, p; @p bar.arrive %0, %1;}" :: "n"(id), "n"(cnt), "r"(a), "r"(b) : "memory");
}
template <int id, int cnt> __device__ __forceinline__ void bar_sync_after(uint32_t a) {
  asm volatile("{.reg .pred p; setp.ne.u32 p, %2, 0xfff12345; @p bar.sync %0, %1;}" :: "n"(id), "n"(cnt), "r"(a) : "memory");
}
__device__ __forceinline__ void fence_async_smem() { asm volatile("fence.proxy.async.shared::cta;" ::: "memory"); }
__device__ __forceinline__ void fence_async_global() { asm volatile("fence.proxy.async.global;" ::: "memory"); }
__device__ __forceinline__ void mbar_init(uint32_t mb, int cnt) { asm volatile("mbarrier.init.shared::cta.b64 [%0], %1;" :: "r"(mb), "r"(cnt) : "memory"); }
__device__ __forceinline__ void mbar_arrive(uint32_t mb) { asm volatile("mbarrier.arrive.shared::cta.b64 _, [%0];" :: "r"(mb) : "memory"); }
__device__ __forceinline__ void mbar_expect(uint32_t mb, uint32_t bytes) {
  asm volatile("mbarrier.arrive.expect_tx.shared::cta.b64 _, [%0], %1;" :: "r"(mb), "r"(bytes) : "memory");
}
__device__ __forceinline__ void mbar_wait(uint32_t mb, uint32_t parity) {
  asm volatile("{.reg .pred p;\nW: mbarrier.try_wait.parity.shared::cta.b64 p, [%0], %1;\n@!p bra W;}" :: "r"(mb), "r"(parity) : "memory");
}
__device__ __forceinline__ void bulk_load(uint32_t dst, const void* src, uint32_t bytes, uint32_t mb) {
  asm volatile("cp.async.bulk.shared::cluster.global.mbarrier::complete_tx::bytes [%0], [%1], %2, [%3];" :: "r"(dst), "l"(src), "r"(bytes), "r"(mb) : "memory");
}
__device__ __forceinline__ void bulk_store(void* dst, uint32_t src, uint32_t bytes) {
  asm volatile("cp.async.bulk.global.shared::cta.bulk_group [%0], [%1], %2;" :: "l"(dst), "r"(src), "r"(bytes) : "memory");
}
__device__ __forceinline__ uint32_t mapa(uint32_t a, uint32_t rank) {
  uint32_t r; asm("mapa.shared::cluster.u32 %0, %1, %2;" : "=r"(r) : "r"(a), "r"(rank)); return r;
}
__device__ __forceinline__ void st_async4(uint32_t dst, float a, float b, float c, float d, uint32_t mb) {
  asm volatile("st.async.shared::cluster.mbarrier::complete_tx::bytes.v4.f32 [%0], {%1,%2,%3,%4}, [%5];" :: "r"(dst), "f"(a), "f"(b), "f"(c), "f"(d), "r"(mb) : "memory");
}
__device__ __forceinline__ void st_async1(uint32_t dst, uint32_t a, uint32_t mb) {
  asm volatile("st.async.shared::cluster.mbarrier::complete_tx::bytes.u32 [%0], %1, [%2];" :: "r"(dst), "r"(a), "r"(mb) : "memory");
}
__device__ __forceinline__ uint4 lds128(uint32_t a) {
  uint4 v; asm volatile("ld.shared.v4.u32 {%0,%1,%2,%3}, [%4];" : "=r"(v.x), "=r"(v.y), "=r"(v.z), "=r"(v.w) : "r"(a) : "memory"); return v;
}
__device__ __forceinline__ uint2 lds64(uint32_t a) {
  uint2 v; asm volatile("ld.shared.v2.u32 {%0,%1}, [%2];" : "=r"(v.x), "=r"(v.y) : "r"(a) : "memory"); return v;
}
__device__ __forceinline__ uint32_t lds32(uint32_t a) {
  uint32_t v; asm volatile("ld.shared.u32 %0, [%1];" : "=r"(v) : "r"(a) : "memory"); return v;
}
__device__ __forceinline__ void sts128(uint32_t a, uint4 v) {
  asm volatile("st.shared.v4.u32 [%0], {%1,%2,%3,%4};" :: "r"(a), "r"(v.x), "r"(v.y), "r"(v.z), "r"(v.w) : "memory");
}
__device__ __forceinline__ void sts32(uint32_t a, uint32_t x) { asm volatile("st.shared.u32 [%0], %1;" :: "r"(a), "r"(x) : "memory"); }
__device__ __forceinline__ void ldsm4(uint32_t& r0, uint32_t& r1, uint32_t& r2, uint32_t& r3, uint32_t a) {
  asm volatile("ldmatrix.sync.aligned.m8n8.x4.shared.b16 {%0,%1,%2,%3}, [%4];" : "=r"(r0), "=r"(r1), "=r"(r2), "=r"(r3) : "r"(a) : "memory");
}
__device__ __forceinline__ void ldsm4t(uint32_t& r0, uint32_t& r1, uint32_t& r2, uint32_t& r3, uint32_t a) {
  asm volatile("ldmatrix.sync.aligned.m8n8.x4.trans.shared.b16 {%0,%1,%2,%3}, [%4];" : "=r"(r0), "=r"(r1), "=r"(r2), "=r"(r3) : "r"(a) : "memory");
}
__device__ __forceinline__ void stsm4(uint32_t a, uint32_t r0, uint32_t r1, uint32_t r2, uint32_t r3) {
  asm volatile("stmatrix.sync.aligned.m8n8.x4.shared.b16 [%0], {%1,%2,%3,%4};" :: "r"(a), "r"(r0), "r"(r1), "r"(r2), "r"(r3) : "memory");
}
__device__ __forceinline__ uint32_t movmat(uint32_t a) {
  uint32_t d; asm volatile("movmatrix.sync.aligned.m8n8.trans.b16 %0, %1;" : "=r"(d) : "r"(a)); return d;
}
__device__ __forceinline__ void mma16(float* d, uint32_t a0, uint32_t a1, uint32_t a2, uint32_t a3, uint32_t b0, uint32_t b1) {
  asm volatile("mma.sync.aligned.m16n8k16.row.col.f32.bf16.bf16.f32 {%0,%1,%2,%3}, {%4,%5,%6,%7}, {%8,%9}, {%0,%1,%2,%3};"
    : "+f"(d[0]), "+f"(d[1]), "+f"(d[2]), "+f"(d[3]) : "r"(a0), "r"(a1), "r"(a2), "r"(a3), "r"(b0), "r"(b1));
}
__device__ __forceinline__ void mma8(float* d, uint32_t a0, uint32_t a1, uint32_t b0) {
  asm volatile("mma.sync.aligned.m16n8k8.row.col.f32.bf16.bf16.f32 {%0,%1,%2,%3}, {%4,%5}, {%6}, {%0,%1,%2,%3};"
    : "+f"(d[0]), "+f"(d[1]), "+f"(d[2]), "+f"(d[3]) : "r"(a0), "r"(a1), "r"(b0));
}
__device__ __forceinline__ float rcp(float x) { float r; asm("rcp.approx.ftz.f32 %0, %1;" : "=f"(r) : "f"(x)); return r; }
__device__ __forceinline__ float ex2(float x) { float r; asm("ex2.approx.ftz.f32 %0, %1;" : "=f"(r) : "f"(x)); return r; }

__host__ __device__ constexpr uint64_t mkdesc(uint32_t off, uint32_t lbo, uint32_t sbo, uint32_t swz) {
  return (uint64_t)((SBASE + off) >> 4) | ((uint64_t)(lbo >> 4) << 16) | ((uint64_t)(sbo >> 4) << 32) | ((uint64_t)swz << 62);
}
__host__ __device__ constexpr uint64_t desc_sw128(uint32_t off) { return mkdesc(off, 16, 1024, 1); }
__host__ __device__ constexpr uint64_t desc_n16(uint32_t off) { return mkdesc(off, 256, 128, 0); }
__host__ __device__ constexpr uint64_t desc_m(uint32_t off) { return mkdesc(off, 16, 256, 3); }

__host__ __device__ constexpr uint64_t desc_sw64(uint32_t off) { return mkdesc(off, 16, 512, 2); }

__device__ __forceinline__ void wg_fence() { asm volatile("wgmma.fence.sync.aligned;" ::: "memory"); }
__device__ __forceinline__ void wg_commit() { asm volatile("wgmma.commit_group.sync.aligned;" ::: "memory"); }
template <int N> __device__ __forceinline__ void wg_wait() { asm volatile("wgmma.wait_group.sync.aligned %0;" :: "n"(N) : "memory"); }

#define ACC8(d) "+f"(d[0]), "+f"(d[1]), "+f"(d[2]), "+f"(d[3]), "+f"(d[4]), "+f"(d[5]), "+f"(d[6]), "+f"(d[7])
#define ACC32(d) ACC8(d), ACC8((d + 8)), ACC8((d + 16)), ACC8((d + 24))
#define R8 "{%0,%1,%2,%3,%4,%5,%6,%7}"
#define R32 "{%0,%1,%2,%3,%4,%5,%6,%7,%8,%9,%10,%11,%12,%13,%14,%15,%16,%17,%18,%19,%20,%21,%22,%23,%24,%25,%26,%27,%28,%29,%30,%31}"
template <int SD> __device__ __forceinline__ void wg_rs16(float* d, const uint32_t* a, uint64_t db) {
  asm volatile("wgmma.mma_async.sync.aligned.m64n16k16.f32.bf16.bf16 " R8 ", {%8,%9,%10,%11}, %12, %13, 1, 1, 1;"
    : ACC8(d) : "r"(a[0]), "r"(a[1]), "r"(a[2]), "r"(a[3]), "l"(db), "n"(SD));
}
template <int SD> __device__ __forceinline__ void wg_ss16(float* d, uint64_t da, uint64_t db) {
  asm volatile("wgmma.mma_async.sync.aligned.m64n16k16.f32.bf16.bf16 " R8 ", %8, %9, %10, 1, 1, 1, 1;"
    : ACC8(d) : "l"(da), "l"(db), "n"(SD));
}
template <int SD, uint64_t DA, uint64_t DB> __device__ __forceinline__ void wg_ss16o(float* d, uint32_t oa, uint32_t ob) {
  asm volatile("{.reg .b32 x, y; .reg .b64 a, b; add.u32 x, %8, %10; add.u32 y, %9, %12; mov.b64 a, {x, %11}; mov.b64 b, {y, %13};\n"
               "wgmma.mma_async.sync.aligned.m64n16k16.f32.bf16.bf16 " R8 ", a, b, %14, 1, 1, 1, 1;}"
    : ACC8(d) : "r"(oa), "r"(ob), "n"((uint32_t)DA), "n"((uint32_t)(DA >> 32)), "n"((uint32_t)DB), "n"((uint32_t)(DB >> 32)), "n"(SD));
}
template <int SD> __device__ __forceinline__ void wg_rs64(float* d, const uint32_t* a, uint64_t db) {
  asm volatile("wgmma.mma_async.sync.aligned.m64n64k16.f32.bf16.bf16 " R32 ", {%32,%33,%34,%35}, %36, %37, 1, 1, 0;"
    : ACC32(d) : "r"(a[0]), "r"(a[1]), "r"(a[2]), "r"(a[3]), "l"(db), "n"(SD));
}
template <int SD> __device__ __forceinline__ void wg_ss64(float* d, uint64_t da, uint64_t db) {
  asm volatile("wgmma.mma_async.sync.aligned.m64n64k16.f32.bf16.bf16 " R32 ", %32, %33, %34, 1, 1, 1, 0;"
    : ACC32(d) : "l"(da), "l"(db), "n"(SD));
}
#define WG_RSO(NAME, SHAPE, REGS, ACC, A, TB) \
template <int SD, uint64_t DB> __device__ __forceinline__ void NAME(float* d, uint32_t a0, uint32_t a1, uint32_t a2, uint32_t a3, uint32_t ob) { \
  asm volatile("{.reg .b64 b; mov.b64 b, {" A(4) ", " A(5) "};\nwgmma.mma_async.sync.aligned." SHAPE ".f32.bf16.bf16 " REGS \
               ", {" A(0) "," A(1) "," A(2) "," A(3) "}, b, " A(6) ", 1, 1, " TB ";}" \
    : ACC(d) : "r"(a0), "r"(a1), "r"(a2), "r"(a3), "r"(ob + (uint32_t)DB), "n"((uint32_t)(DB >> 32)), "n"(SD)); \
}
#define ACC4(d) "+f"(d[0]), "+f"(d[1]), "+f"(d[2]), "+f"(d[3])
#define ACC16(d) ACC8(d), ACC8((d + 8))
#define OP4(i) OP4_##i
#define OP4_0 "%4"
#define OP4_1 "%5"
#define OP4_2 "%6"
#define OP4_3 "%7"
#define OP4_4 "%8"
#define OP4_5 "%9"
#define OP4_6 "%10"
#define OP16(i) OP16_##i
#define OP16_0 "%16"
#define OP16_1 "%17"
#define OP16_2 "%18"
#define OP16_3 "%19"
#define OP16_4 "%20"
#define OP16_5 "%21"
#define OP16_6 "%22"
#define OP32(i) OP32_##i
#define OP32_0 "%32"
#define OP32_1 "%33"
#define OP32_2 "%34"
#define OP32_3 "%35"
#define OP32_4 "%36"
#define OP32_5 "%37"
#define OP32_6 "%38"
WG_RSO(wg_rs8o, "m64n8k16", "{%0,%1,%2,%3}", ACC4, OP4, "1")
#define R16 "{%0,%1,%2,%3,%4,%5,%6,%7,%8,%9,%10,%11,%12,%13,%14,%15}"
WG_RSO(wg_rs32o, "m64n32k16", R16, ACC16, OP16, "1")
WG_RSO(wg_rs64o, "m64n64k16", R32, ACC32, OP32, "0")
WG_RSO(wg_rs32k, "m64n32k16", R16, ACC16, OP16, "0")
template <uint64_t DA, uint64_t DB> __device__ __forceinline__ void wg_ss32k(float* d, uint32_t ob) {
  asm volatile("{.reg .b64 b; mov.b64 b, {%17, %18};\nwgmma.mma_async.sync.aligned.m64n32k16.f32.bf16.bf16 " R16 ", %16, b, 1, 1, 1, 1, 0;}"
    : ACC16(d) : "l"(DA), "r"(ob + (uint32_t)DB), "n"((uint32_t)(DB >> 32)));
}
template <int N> __device__ __forceinline__ void reg_inc() { asm volatile("setmaxnreg.inc.sync.aligned.u32 %0;" :: "n"(N)); }
template <int N> __device__ __forceinline__ void reg_dec() { asm volatile("setmaxnreg.dec.sync.aligned.u32 %0;" :: "n"(N)); }

template <int KS>
__device__ __forceinline__ void load_frags(uint32_t* a, uint32_t src) {
  const int lane = threadIdx.x & 31, w = (threadIdx.x >> 5) & 3;
  const int k = ((lane >> 4) << 3) + (lane & 7), u = w * 2 + ((lane >> 3) & 1);
  const uint32_t base = src + k * 128 + ((u ^ (k & 7)) << 4);
#pragma unroll
  for (int ks = 0; ks < KS; ks++) ldsm4t(a[ks * 4], a[ks * 4 + 1], a[ks * 4 + 2], a[ks * 4 + 3], base + ks * 2048);
}

__device__ __forceinline__ uint32_t badd2(uint32_t a, uint32_t b) { uint32_t r; asm("add.rn.bf16x2 %0, %1, %2;" : "=r"(r) : "r"(a), "r"(b)); return r; }
__device__ __forceinline__ uint32_t bsub2(uint32_t a, uint32_t b) { uint32_t r; asm("sub.rn.bf16x2 %0, %1, %2;" : "=r"(r) : "r"(a), "r"(b)); return r; }
__device__ __forceinline__ uint32_t bmul2(uint32_t a, uint32_t b) { uint32_t r; asm("mul.rn.bf16x2 %0, %1, %2;" : "=r"(r) : "r"(a), "r"(b)); return r; }
__device__ __forceinline__ uint32_t bfma2(uint32_t a, uint32_t b, uint32_t c) { uint32_t r; asm("fma.rn.bf16x2 %0, %1, %2, %3;" : "=r"(r) : "r"(a), "r"(b), "r"(c)); return r; }
template <int R> __device__ __forceinline__ void layernorm9(const uint32_t* x, uint32_t* o) {
  const uint32_t ones = 0x3F803F80u;
  float a[R][3][4], q[R], s[R];
#pragma unroll
  for (int i = 0; i < 9 * R; i++) {
    float* d = a[i % R][i / R % 3];
    if (i < 3 * R) d[0] = d[1] = d[2] = d[3] = 0.f;
    mma8(d, x[i % R * 9 + i / R], ones, x[i % R * 9 + i / R]);
  }
#pragma unroll
  for (int r = 0; r < R; r++) {
    q[r] = threadIdx.x & 4 ? a[r][0][1] + a[r][1][1] + a[r][2][1] : a[r][0][0] + a[r][1][0] + a[r][2][0];
    s[r] = (a[r][0][2] + a[r][0][3]) + (a[r][1][2] + a[r][1][3]) + (a[r][2][2] + a[r][2][3]);
  }
#pragma unroll
  for (int r = 0; r < R; r++) { q[r] += __shfl_xor_sync(~0u, q[r], 4); s[r] += __shfl_xor_sync(~0u, s[r], 1); }
#pragma unroll
  for (int r = 0; r < R; r++) { q[r] += __shfl_xor_sync(~0u, q[r], 9); s[r] += __shfl_xor_sync(~0u, s[r], 2); }
#pragma unroll
  for (int r = 0; r < R; r++) q[r] = __shfl_sync(~0u, q[r], 0) + __shfl_sync(~0u, q[r], 18);
#pragma unroll
  for (int r = 0; r < R; r++) {
    const float mean = s[r] * (1.f / DM), var = fmaxf(fmaf(q[r], 1.f / DM, -mean * mean), 0.f);
    float sd;
    asm("sqrt.approx.ftz.f32 %0, %1;" : "=f"(sd) : "f"(bf_lo(pack2(bf_lo(pack2(var, 0.f)) + 1e-5f, 0.f))));
    const float inv = rcp(bf_lo(pack2(sd, 0.f)));
    const uint32_t mb = pack2(mean, mean), hi = pack2(inv, inv), lo = pack2(inv - bf_lo(hi), inv - bf_lo(hi));
#pragma unroll
    for (int i = r * 9; i < r * 9 + 9; i++) {
      const uint32_t d = bsub2(x[i], mb);
      o[i] = bfma2(d, hi, bmul2(d, lo));
    }
  }
}
__device__ __forceinline__ void store_ln_row(int layer, int tok, const uint32_t* o) {
  const int lane = threadIdx.x & 31, r = tok & 31;
  unsigned char* p = g_lnimg + (size_t)(layer * NSEG + (tok >> 5)) * (9 * 4096) + r * 128 + (((lane >> 2) ^ (r & 7)) << 4) + (lane & 3) * 4;
#pragma unroll
  for (int i = 0; i < 9; i++) *(uint32_t*)(p + i * 4096) = o[i];
}
struct Params { CUtensorMap map[11]; const bf16 *X, *K, *V, *shift, *Hk, *Dk, *mem0, *Wq, *Wk, *Wv, *Wo; bf16* out; uint32_t dly[24]; };
#define DLYS P.dly[0]
#define DLYW P.dly[1]
#define DLYK P.dly[4]
#define DLYG P.dly[5]
#define KWIN P.dly[6]
#define KMIN P.dly[7]
#define PREF0 P.dly[19]
#define PACE P.dly[20]
#define S1G P.dly[21]
#define S1DLY P.dly[22]
#define PREFH P.dly[23]
uint32_t h_dly[24] = {900, 350, 100, 60, 3570, 4120, 2750, 1300, 1600, 1690, 1800, 2120, 2250, 2380, 2950, 3060, 3230, 3380, 3530, 7000, 160, 12500, 20500, 4000};

constexpr uint32_t C_W = 0, C_M = 147456, C_KV = C_M + 18432, C_OS = C_KV + 24576, C_QM = C_KV + 32768, C_KM = C_QM + 2048,
                   C_VM = C_KM + 2048, C_OI = C_VM + 2048, C_SX = C_OI + 4096, C_KM2 = C_SX + 2560, C_VM2 = C_KM2 + 128,
                   C_KV2 = C_KM2 + 2048, C_Q = C_KV2 + 8192, C_BAR = C_Q + 8192;
constexpr uint32_t CB_FULL = C_BAR, CB_REF = C_BAR + 16, CB_SX = C_BAR + 32, CB_OX = C_BAR + 40, CB_XX = C_BAR + 48, CB_Q = C_BAR + 56, C_BAD = C_BAR + 64, W_BAR = C_BAR + 80, T_BAR = W_BAR + 24, S_GEN = C_BAR + 128, C_REF = C_BAR + 132, CB_VF = C_BAR + 144, CB_M = C_BAR + 160, CB_MV = C_BAR + 200;
constexpr uint32_t G_W = 0, G_RING = 147456, G_W2 = G_RING + 9 * 8192, G_BAR = G_W2 + 8192;
constexpr uint32_t O_W = 0, O_RING = 3 * 40960, O_ST = O_RING + 11 * 8192, O_BAR = O_ST + 16384, OB_ST = O_BAR + 64;
constexpr uint32_t F_A = 0, F_XY = 36864, F_L = F_XY + 36864, F_X = F_L + 18432, F_Y = F_L + 2 * 36864, F_BAR = C_BAR;
constexpr uint32_t SMEM_BYTES = C_BAR + 256;
static_assert(G_BAR + 256 <= SMEM_BYTES && O_BAR + 256 <= SMEM_BYTES && F_BAR + 16 <= SMEM_BYTES && SMEM_BYTES <= 232448, "smem map");
enum { B_INIT = 1, B_M, B_QK, B_S, B_V, B_O, B_X, B_WG0, B_WG1, B_WG2, B_G, B_OE, B_T, B_R };

__device__ __forceinline__ uint4 pack_partial(const float* d, uint32_t tag) {
  uint32_t x, z;
  asm("lop3.b32 %0, %2, 1, %4, 0xb8; lop3.b32 %1, %3, 1, %4, 0xb8;" : "=&r"(x), "=&r"(z) : "r"(pack2(d[0], d[1])), "r"(pack2(d[2], d[3])), "r"(tag));
  return make_uint4(x, pack2(d[4], d[5]), z, pack2(d[6], d[7]));
}
__device__ __forceinline__ void store_partial(uint4* p, const uint4& v) { st_b128(p, v.x, v.y, v.z, v.w); }
__device__ __forceinline__ void gather_reduce(const uint32_t* p, uint32_t* dst, uint32_t m0, bool shared, uint32_t tag, uint32_t lane, uint32_t sb, int n, int TS0) {
  int tries = 0;
  bool bad;
  TR(TS0);
  do {
    uint2 x[8];
#pragma unroll
    for (int i = 0; i < 8; i++)
      asm volatile("{.reg .b64 v; ld.relaxed.gpu.global.b64 v, [%2]; mov.b64 {%0, %1}, v;}" : "=r"(x[i].x), "=r"(x[i].y) : "l"(p + i * 128) : "memory");
    spin_guard(tries);
    float a = bf_lo(x[0].x), b = bf_hi(x[0].x), c = bf_lo(x[0].y), d = bf_hi(x[0].y);
    uint32_t t = x[0].x ^ tag;
#pragma unroll
    for (int i = 1; i < 8; i++) {
      a += bf_lo(x[i].x); b += bf_hi(x[i].x); c += bf_lo(x[i].y); d += bf_hi(x[i].y);
      asm("lop3.b32 %0, %0, %1, %2, 0xf6;" : "+r"(t) : "r"(x[i].x), "r"(tag));
    }
    bad = __any_sync(~0u, t & 1);
    const bool up = lane & 8;
    float u = (up ? c : a) + __shfl_xor_sync(~0u, up ? a : c, 8), v = (up ? d : b) + __shfl_xor_sync(~0u, up ? b : d, 8);
    if (shared) { u += __shfl_xor_sync(~0u, u, 4); v += __shfl_xor_sync(~0u, v, 4); }
    u += __shfl_xor_sync(~0u, u, 16);
    v += __shfl_xor_sync(~0u, v, 16);
    st_relaxed_if(dst, n < LAG && up ? m0 : pack2(u, v), !bad);
  } while (bad);
  TR(TS0 + 3); TRV(TS0 + 2, tries);
  CNT((TS0 - 16) >> 2, tries);
}

constexpr int XR = 3;
__host__ __device__ constexpr int o_ks(int s) { return s & (s < 8 ? 3 : 7); }
__host__ __device__ constexpr bool o_reg(int s) { return s < 8 ? (s & 3) != 3 : !(s & 1); }
__host__ __device__ constexpr int o_slot(int s) { return s < 8 ? (o_reg(s) ? s - (s >> 2) : s >> 2) : s & 1 ? (s - 5) >> 1 : (s + 4) >> 1; }
__device__ __forceinline__ int g_unit(int wg) {
  const int i = bid() - N_CHAIN;
  return i < 32 ? wg * 64 + i : 2 * i - 32 + wg;
}
__device__ __forceinline__ uint32_t pinned(uint32_t v) { return __shfl_sync(~0u, v, threadIdx.x & 31); }
template <class T> __device__ __forceinline__ T* pinned(T* p) { return (T*)__shfl_sync(~0u, (unsigned long long)p, threadIdx.x & 31); }
enum { CHAIN, GROLE, OROLE };
template <int ROLE, bool SYNC> __device__ __forceinline__ void load_box(const Params& P, uint32_t sb, bool regs, int wg, int i, uint32_t mb, bool on) {
  const int b = bid();
  int map, col = 0, ks = 0, c2 = 0, c3 = 0;
  uint32_t dst = wg * 73728;
  if (ROLE == CHAIN) {
    const int k = i - 1, st = regs ? (k < 6 ? k + k / 3 : 2 * k - 4) : k < 2 ? 4 * k + 3 : 2 * k + 5;
    dst += i ? (17 + i) * 2048 : 0;
    if (wg || i == 0) { map = wg + i; col = b * 64; c3 = !regs; }
    else if (!regs && k >= 14) { map = 6; ks = b * 4 + k - 14; }
    else { map = 6; col = 64 + (st < 8 ? (st >> 2) * 64 : (st >> 3) * 128 + (b & 1) * 64); ks = (b * 4) ^ o_ks(st); }
  } else if (ROLE == GROLE) {
    const int q = g_unit(wg);
    map = ((q >> 5) + 1) % 3;
    if (i) { map += 3; col = (q & 31) * 128 + (i - 1) * 64; ks = 34; dst = G_W2 + wg * 4096 + (i - 1) * 2048; }
    else { map += 8; c2 = (q & 31) * 2; c3 = !regs; }
  } else {
    const int o = b - N_CHAIN - N_G, ksl = o / 3;
    map = 7; col = ((o % 3) * 3 + (wg + ksl) % 3) * 64; dst = (wg * (regs ? 24 : 20) + i) * 2048;
    ks = (ksl * 11 - max(ksl - 4, 0)) * 4 + (regs ? i / 3 * 5 + i % 3 * 2 : i < 16 ? i / 2 * 5 + 1 + i % 2 * 2 : i + 24);
    c3 = (ks & 1) * 2; ks >>= 1;
  }
  if (SYNC) { col = pinned(col); ks = pinned(ks); bar_sync(B_WG0 + wg, 256); }
  if (on) asm volatile("cp.async.bulk.tensor.5d.shared::cluster.global.tile.mbarrier::complete_tx::bytes [%0], [%1, {%2, %3, %4, %5, %6}], [%7];"
               :: "r"(sb + dst), "l"(&P.map[map]), "r"(col), "r"(0), "r"(c2), "r"(c3), "r"(ks), "r"(mb) : "memory");
}
template <int ROLE, bool SYNC = false> __device__ __forceinline__ void load_wg(const Params& P, uint32_t sb, bool regs, int wg, int quarter) {
  const int i = (threadIdx.x & 31) * 4 + quarter;
  const int n = ROLE == CHAIN ? 36 : ROLE == GROLE ? (regs ? 38 : 36) : regs ? 24 : bid() < N_CHAIN + N_G + 12 ? 20 : 16;
  const bool split = SYNC && wg == 0;
  const uint32_t mb = split && i ? sb + T_BAR : sb + W_BAR + wg * 8;
  load_box<ROLE, SYNC>(P, sb, regs, wg, i, mb, i < (ROLE == CHAIN ? (wg ? 2 : 19) : ROLE == GROLE ? n - 35 : n));
  if (i <= split) mbar_expect(mb, n * (split ? 1024 : 2048));
  __syncwarp();
}
__device__ __forceinline__ uint32_t near_half(uint32_t blk, uint32_t reader) {
  return __ldcg(g_near + (blk >> 3)) ^ (~blk & 1) ^ __ldcg(g_side + (blk >> 3)) ^ __ldcg(g_side + reader);
}

__device__ __forceinline__ uint32_t opaque_tid() { uint32_t t; asm volatile("mov.u32 %0, %%tid.x;" : "=r"(t)); return t; }
__device__ __forceinline__ void m_fetch(uint32_t sb, uint32_t src, uint32_t b, uint32_t mb) {
  bulk_load(sb + C_M + (b ? b * 4096 - 2048 : 0), (const unsigned char*)g_mimg + ((src ^ ((b & 1) * 4096)) + b * 8192), b ? 4096 : 2048, mb);
}
__device__ __forceinline__ uint32_t m_probe(uint32_t lane) { return lane * 32 + (lane & 4) * 4 + (lane >> 3) * 4; }
__device__ __forceinline__ uint32_t m_max(uint32_t a, uint32_t b) {
  return max(max(lds32(a), lds32(a + 1024)), max(lds32(b), lds32(b + 1024)));
}
template <int S0, int N> __device__ __forceinline__ void o_steps(float* d, const uint32_t* a) {
  constexpr int SD = o_ks(S0) != 0;
  if constexpr (o_reg(S0)) wg_rs16<SD>(d, a + (18 + o_slot(S0)) * 4, desc_n16(C_OI + o_ks(S0) * 512));
  else wg_ss16<SD>(d, desc_sw128(C_W + (18 + o_slot(S0)) * 2048), desc_n16(C_OI + o_ks(S0) * 512));
  if constexpr (N > 1) o_steps<S0 + 1, N - 1>(d, a);
}
template <int BASE, int KS, int N> __device__ __forceinline__ void m_steps(float* d, const uint32_t* a, uint32_t oa) {
  wg_rs16<KS != 0>(d, a + (BASE + KS / 2) * 4, desc_m(C_M + KS * 512));
  if constexpr (KS >= 36 - 2 * XR) wg_rs16<1>(d, a + (18 + XR + KS / 2) * 4, desc_m(C_M + KS * 512 + 512));
  else wg_ss16o<1, desc_sw128(C_W + (BASE + KS / 2) * 2048), desc_m(C_M + KS * 512 + 512)>(d, oa, 0);
  if constexpr (N > 2) m_steps<BASE, KS + 2, N - 2>(d, a, oa);
}

constexpr uint32_t VPAT = 0x15bbd249u;
template <int I, int R, int S> __device__ __forceinline__ void v_steps(float* d, const uint32_t* a) {
  constexpr bool reg = (VPAT >> I) & 1;
  if constexpr (reg) wg_rs16<1>(d, a + (18 + R) * 4, desc_m(C_M + R * 1024));
  else wg_ss16<1>(d, desc_sw128(C_W + (54 + S) * 2048), desc_m(C_M + S * 1024 + 512));
  if constexpr (I < 31) v_steps<I + 1, R + reg, S + !reg>(d, a);
  else static_assert(R + reg == 18, "pattern");
}

__device__ __forceinline__ void chain_proj(const Params& P, uint32_t sb) {
  const uint32_t c = chain_id(), h = c >> 1, j = c & 1, wid = __shfl_sync(~0u, threadIdx.x >> 5, 0), wg = wid >> 2, w = wid & 3;
  const uint32_t t = threadIdx.x & 127, lane = pinned(t & 31), mine = pinned(sb + t * 16), rb = mapa(sb, j ^ 1);
  const uint32_t theirs = pinned(rb + C_KM2 + w * 512 + lane * 4), oa = wg * 4608;
  uint32_t a[144 + 4 * XR];
  mbar_wait(sb + W_BAR + wg * 8, 0);
  if (threadIdx.x == 0) TS(23);
  load_frags<36>(a, sb + C_W + wg * 73728);
  fence_async_smem();
  bar_arrive(B_WG0 + wg, 256);
  if (threadIdx.x == 0) TS(24);
  bar_sync(B_WG2, 384);
  const uint32_t round = min(w, 2u) + (wg ? 0 : 3), gdly = P.dly[8 + round], ps = t >> 2, pf = j * 16 + (ps >> 1);
  uint4* const dsts = pinned(g_xb + (ps * 4096 + near_half(ps * 8, ps * 2) * 256 + c * 4 + (t & 3)));
  uint4* const dstf = pinned(g_xb + (pf * 4096 + 512 + near_half(pf * 8 + 1, pf * 2) * 256 + h * 8 + (t & 7)));
  const uint32_t* const gsrc = (const uint32_t*)g_xb + (h * 16384 + min(w, 2u) * 4096 + near_half(h * 8 + !wg, h * 2) * 1024 +
                               (wg ? (lane & 28) * 4 + j * 8 + (lane & 3) * 2 : 2048 + (lane & 24) * 4 + j * 16 + (lane & 7) * 2));
  uint32_t* gdst = g_mimg + (16384 + (lane >> 4) * 1024 + (lane & 1) * 8 +
                   (wg ? (round ? 1536 + round * 512 : 0) + h * 16 + (((lane >> 1) ^ c) & 4) + j * 2 + ((lane >> 1) & 1)
                       : (round - 1) * 2048 + c * 16 + (((lane >> 1) ^ (c * 2)) & 4) + ((lane >> 1) & 3)));
  const uint32_t m0 = __ldcg(gdst - 16384);
  mbar_wait(sb + W_BAR + wg * 8, 1);
  load_frags<XR>(a + 144, sb + C_W + wg * 73728 + (18 - XR) * 2048);
  bar_sync(B_INIT, 256);
  if ((threadIdx.x & 127) == 0) TS(4);

  uint32_t ring = 1;
#pragma unroll 1
  for (int n = 0; n < STEPS; n++) {
    float d[8], e[8];
#pragma unroll
    for (int i = 0; i < 8; i++) e[i] = 0.f;
    uint32_t redo = n + 1;
#pragma unroll 1
    do {
      mbar_wait(sb + CB_M, n & 1);
      wg_fence();
      m_steps<0, 0, 4>(d, a, oa);
      wg_commit();
      if (wg) { wg_fence(); m_steps<18, 0, 4>(e, a, 4608); wg_commit(); }
      if (wid == 0) TR(8);
      mbar_wait(sb + CB_M + 8, n & 1);
      wg_fence();
      m_steps<0, 4, 8>(d, a, oa);
      wg_commit();
      mbar_wait(sb + CB_MV, n & 1);
      asm volatile("{.reg .pred p; .reg .u32 t; ld.shared.u32 t, [%1]; setp.eq.u32 p, t, %0; selp.u32 %0, -1, 0, p;}" : "+r"(redo) : "r"(sb + C_BAD) : "memory");
    } while (redo);
    wg_fence();
    m_steps<0, 12, 8>(d, a, oa);
    wg_commit();
    mbar_wait(sb + CB_MV + 16, n & 1);
    wg_fence();
    m_steps<0, 20, 8>(d, a, oa);
    wg_commit();
    mbar_wait(sb + CB_MV + 24, n & 1);
    wg_fence();
    m_steps<0, 28, 8>(d, a, oa);
    wg_commit();
    wg_wait<0>();
    if (w == 0) TR(6 + wg);
    const uint32_t f0 = pack2(d[0], d[1]), f1 = pack2(d[4], d[5]), f2 = pack2(d[2], d[3]), f3 = pack2(d[6], d[7]);
    stsm4(mine + C_QM + wg * 2048, f0, f1, f2, f3);
    bar_arrive(B_QK, 416);
    const uint32_t tag = (n & 1) ^ 1;
    if (n == 0) mbar_wait(sb + T_BAR, 0);
    if (wg) {
      if (n + 1 < STEPS) bar_sync(B_S, 256);
      wg_fence();
      v_steps<0, 2, 2>(e, a);
      wg_commit();
      const uint32_t k0 = j ? f0 : f1, k1 = j ? f2 : f3;
      mbar_wait(sb + CB_SX, n & 1);
      wg_wait<0>();
      if (w == 0) TR(11);
      const uint32_t v0 = pack2(e[0], e[1]), v1 = pack2(e[4], e[5]), v2 = pack2(e[2], e[3]), v3 = pack2(e[6], e[7]);
      stsm4(mine + C_VM, v0, v1, v2, v3);
      bar_arrive(B_V, 256);
      st_async1(theirs, k0, rb + CB_XX);
      st_async1(theirs + 256, k1, rb + CB_XX);
      st_async1(theirs + 128, j ? v0 : v1, rb + CB_XX);
      st_async1(theirs + 384, j ? v2 : v3, rb + CB_XX);
      if (n + 1 == STEPS) break;
      bar_sync(B_O, 256);
      fence_async_smem();
      wg_fence();
#pragma unroll
      for (int ks = 0; ks < 4; ks++) {
        if (ks == 0) wg_ss16<0>(d, desc_sw128(C_W + 32 * 2048), desc_n16(C_OI));
        else wg_ss16<1>(d, desc_sw128(C_W + (32 + ks) * 2048), desc_n16(C_OI + ks * 512));
      }
      wg_commit();
      bar_arrive(B_X, 256);
      if (w == 0) TR(0);
      wg_wait<0>();
      store_partial(dsts, pack_partial(d, tag));
      bar_arrive(B_M, 160);
      if (w == 0) TR(1);
    } else {
      if (n + 1 == STEPS) break;
      bar_sync(B_X, 256);
      wg_fence();
      o_steps<0, 4>(d, a);
      wg_commit();
      o_steps<4, 4>(e, a);
      wg_commit();
      wg_wait<1>();
      store_partial(dsts + 1024, pack_partial(d, tag));
      if (w == 0) TR(2);
      wg_wait<0>();
      store_partial(dsts + 2048, pack_partial(e, tag));
      if (w == 0) TR(3);
      wg_fence();
      o_steps<8, 4>(d, a);
      wg_commit();
      bar_sync(B_T, 256);
      if (w == 0) { TRV(61, 0); TR(12); }
      wg_fence();
      o_steps<12, 4>(d, a);
      wg_commit();
      o_steps<16, 8>(e, a);
      wg_commit();
      wg_wait<1>();
      store_partial(dstf, pack_partial(d, tag));
      if (w == 0) TR(4);
      wg_fence();
      o_steps<24, 8>(d, a);
      wg_commit();
      wg_wait<1>();
      store_partial(dstf + 1024, pack_partial(e, tag));
      bar_arrive(B_OE, 256);
      if (w == 0) TR(5);
      wg_wait<0>();
      store_partial(dstf + 2048, pack_partial(d, tag));
      if (w == 0) TR(15);
    }
    if (w < 3) {
      mbar_wait(sb + CB_REF, n & 1);
      wait_until(lds32(sb + C_REF), gdly);
      gather_reduce(gsrc, gdst, m0, wg, tag, lane, sb, n, 16 + round * 4);
      if (++ring == MRING) { ring = 0; gdst -= MRING * 16384; }
      gdst += 16384;
    }
  }
}

template <int KS> __device__ __forceinline__ void x_scores(float* s, float* sm, const uint4* q, uint32_t ok, uint32_t om) {
  wg_rs32o<1, desc_sw64(C_KV + KS * 1024)>(s, q[KS].x, q[KS].y, q[KS].z, q[KS].w, ok);
  wg_rs8o<1, desc_n16(C_KM + KS * 512)>(sm, q[KS].x, q[KS].y, q[KS].z, q[KS].w, om);
  if constexpr (KS < 3) x_scores<KS + 1>(s, sm, q, ok, om);
}

__device__ __forceinline__ void chain_attn(const Params& P, uint32_t sb) {
  const int c = chain_id(), j = c & 1;
  const int tid = threadIdx.x, lane = tid & 31, w = __shfl_sync(~0u, (tid >> 5) & 3, 0);
  const int l = w >> 1, u = w & 1;
  const uint32_t rb = mapa(sb, j ^ 1);
  const float sc = 0.08838834764831845f * 1.4426950408889634f;
  const uint32_t ones = 0x3F803F80u;
  const uint32_t km_off = C_KM + (lane >> 3) * 256 + l * 128 + (lane & 7) * 16;
  const uint32_t qm_off = C_QM + (lane >> 4) * 256 + l * 128 + (lane & 7) * 16;
  const uint32_t kv_off = C_KV + l * 4096 + (lane & 15) * 64 + (((lane >> 4) ^ (u * 2) ^ ((lane >> 1) & 3)) << 4);

  load_wg<CHAIN, true>(P, sb, false, 1, w);
  if (lane == 0) mbar_arrive(sb + CB_M);
#pragma unroll 1
  for (int n = 0; n < STEPS; n++) {
    const uint32_t kvb = sb + kv_off + (n & 1) * 16384;
    if (w == 0 && elect()) { mbar_expect(sb + CB_SX, 2560); mbar_expect(sb + CB_OX, 2048); mbar_expect(sb + CB_XX, 2048); }
    mbar_wait(sb + CB_FULL + (n & 1) * 8, (n >> 1) & 1);
    if (n < 3 && tid == 256) TS(n ? 20 + n : 5);
    __syncwarp();
    {
      uint32_t km[8];
      uint4 kx[8];
#pragma unroll
      for (int i = 0; i < 8; i++) ldsm4t(kx[i].x, kx[i].y, kx[i].z, kx[i].w, (kvb ^ ((i & 1) * 32)) + (i >> 1) * 1024);
      mbar_wait(sb + CB_VF, n & 1);
      if (w == 1) TRD(60, kx[7].x);
      bar_sync(B_QK, 416);
      if (n + 1 == STEPS) {
        st_async4(rb + C_SX + (tid & 127) * 16, 0.f, 0.f, 0.f, 0.f, rb + CB_SX);
        st_async1(rb + C_SX + 2048 + (tid & 127) * 4, 0, rb + CB_SX);
        bar_sync(B_V, 256);
      } else {
      uint32_t qm[16];
#pragma unroll
      for (int ks = 0; ks < 4; ks++) ldsm4t(qm[4 * ks], qm[4 * ks + 1], qm[4 * ks + 2], qm[4 * ks + 3], sb + qm_off + ks * 512);
      ldsm4t(km[0], km[1], km[2], km[3], sb + km_off);
      ldsm4t(km[4], km[5], km[6], km[7], sb + km_off + 1024);
      float s[5][4];
      uint4 vx[4];
#pragma unroll
      for (int i = 0; i < 5; i++) { s[i][0] = s[i][1] = s[i][2] = s[i][3] = 0.f; }
#pragma unroll
      for (int ks = 0; ks < 4; ks++) {
        const uint32_t* q = qm + 4 * ks;
        if (ks == 1 || ks == 2) {
#pragma unroll
          for (int i = 2 * ks - 2; i < 2 * ks; i++) ldsm4(vx[i].x, vx[i].y, vx[i].z, vx[i].w, ((sb + kv_off) ^ ((i & 1) * 32)) + 8192 + (2 * u + (i >> 1)) * 1024);
        }
        mma16(s[1], q[0], q[1], q[2], q[3], kx[2 * ks].x, kx[2 * ks].y);
        mma16(s[2], q[0], q[1], q[2], q[3], kx[2 * ks].z, kx[2 * ks].w);
        mma16(s[0], q[0], q[1], q[2], q[3], km[2 * ks], km[2 * ks + 1]);
        mma16(s[3], q[0], q[1], q[2], q[3], kx[2 * ks + 1].x, kx[2 * ks + 1].y);
        mma16(s[4], q[0], q[1], q[2], q[3], kx[2 * ks + 1].z, kx[2 * ks + 1].w);
      }
      const uint32_t sx = C_SX + l * 1280;
      st_async4(rb + sx + u * 512 + lane * 16, s[1][0], s[1][1], s[2][0], s[2][1], rb + CB_SX);
      st_async1(rb + sx + 1024 + u * 128 + lane * 4, __float_as_uint(u ? s[0][1] : s[0][0]), rb + CB_SX);
      bar_arrive_after<B_S, 256>(__float_as_uint(s[3][0]), __float_as_uint(s[4][0]));
      mbar_wait(sb + CB_SX, n & 1);
      const uint4 p0 = lds128(sb + sx + u * 512 + lane * 16), p1 = lds128(sb + sx + (u ^ 1) * 512 + lane * 16);
      const uint2 p2 = make_uint2(lds32(sb + sx + 1024 + lane * 4), lds32(sb + sx + 1152 + lane * 4));
      float t[10] = {s[0][0] + __uint_as_float(p2.x), s[0][1] + __uint_as_float(p2.y),
                     s[1][0] + __uint_as_float(p0.x), s[1][1] + __uint_as_float(p0.y),
                     s[2][0] + __uint_as_float(p0.z), s[2][1] + __uint_as_float(p0.w),
                     s[3][0] + __uint_as_float(p1.x), s[3][1] + __uint_as_float(p1.y),
                     s[4][0] + __uint_as_float(p1.z), s[4][1] + __uint_as_float(p1.w)};
      float mx = fmaxf(fmaxf(fmaxf(fmaxf(t[2], t[3]), fmaxf(t[4], t[5])), fmaxf(fmaxf(t[6], t[7]), fmaxf(t[8], t[9]))), fmaxf(t[0], t[1]));
      mx = fmaxf(fmaxf(mx, __shfl_xor_sync(~0u, mx, 1)), fmaxf(__shfl_xor_sync(~0u, mx, 2), __shfl_xor_sync(~0u, mx, 3)));
      const float ms = -mx * sc;
#pragma unroll
      for (int i = 0; i < 10; i++) t[i] = ex2(fmaf(t[i], sc, ms));
      uint32_t p[5];
#pragma unroll
      for (int i = 0; i < 5; i++) p[i] = pack2(t[2 * i], t[2 * i + 1]);
      p[1] |= (p[0] & p[3] & p[4]) & 0x80008000u;
      float o[2][4], z[4] = {0.f, 0.f, 0.f, 0.f};
      mma16(z, ones, ones, ones, ones, p[1], p[2]);
#pragma unroll
      for (int i = 0; i < 2; i++) {
        o[i][0] = o[i][1] = o[i][2] = o[i][3] = 0.f;
        mma16(o[i], vx[2 * i].x, vx[2 * i].y, vx[2 * i].z, vx[2 * i].w, p[1], p[2]);
      }
      mma16(z, ones, ones, ones, ones, p[3], p[4]);
#pragma unroll
      for (int i = 0; i < 2; i++) mma16(o[i], vx[2 * i + 1].x, vx[2 * i + 1].y, vx[2 * i + 1].z, vx[2 * i + 1].w, p[3], p[4]);
      mma8(z, ones, ones, p[0]);
      bar_sync_after<B_V, 256>(p[1]);
      ldsm4(km[0], km[1], km[2], km[3], sb + km_off + (C_VM - C_KM) + u * 1024);
      mma8(o[0], km[0], km[1], p[0]);
      mma8(o[1], km[2], km[3], p[0]);
      const float i0 = rcp(z[0]), i1 = rcp(z[1]);
      const uint32_t oo = C_OI + u * 1024 + l * 128 + lane * 4;
      uint32_t ow[4];
#pragma unroll
      for (int i = 0; i < 2; i++) { ow[2 * i] = pack2(o[i][0] * i0, o[i][1] * i1); ow[2 * i + 1] = pack2(o[i][2] * i0, o[i][3] * i1); }
      stsm4(sb + C_OI + u * 1024 + l * 128 + (lane >> 3) * 256 + (lane & 7) * 16, ow[0], ow[1], ow[2], ow[3]);
      bar_arrive(B_O, 256);
#pragma unroll
      for (int i = 0; i < 4; i++) st_async1(rb + oo + 2048 + i * 256, ow[i], rb + CB_OX);
      }
    }
    {
      const uint32_t lane = opaque_tid() & 31, own = ((n & 1) * 16384 + j * 4096) >> 4;
      float s[16], sm[4];
#pragma unroll
      for (int i = 0; i < 16; i++) s[i] = sm[i & 3] = 0.f;
      {
        uint4 q[4];
        mbar_wait(sb + CB_Q, n & 1);
#pragma unroll
        for (int ks = 0; ks < 4; ks++) q[ks] = lds128(sb + C_Q + (ks >> 1) * 4096 + w * 1024 + (ks & 1) * 512 + lane * 16);
        mbar_wait(sb + CB_XX, n & 1);
        if (n + 1 < STEPS) mbar_wait(sb + CB_OX, n & 1);
        fence_async_smem();
        if (n + 1 < STEPS) { bar_arrive(B_T, 256); bar_sync(B_OE, 256); }
        if (w == 1) { TRV(61, 0); TR(9); }
#pragma unroll 1
        for (uint32_t hf = 0; hf < 2; hf++) {
          wg_fence();
          x_scores<0>(s, sm, q, hf ? (C_KV2 - C_KV) >> 4 : own, hf ? (C_KM2 - C_KM) >> 4 : j * 8);
          wg_commit();
          wg_wait<0>();
#pragma unroll
          for (int ks = 0; ks < 4; ks++) asm volatile("mov.b32 %0, %1; mov.b32 %2, %3;" : "+r"(q[ks].x), "+r"(q[ks].y), "+r"(q[ks].z), "+r"(q[ks].w));
        }
      }
      const float neg = -1e9f * 11.313708498984761f;
      const int lim = 8 * (w - (int)(lane & 3)) + (int)(lane >> 2);
      float t[10] = {sm[0], sm[1]};
#pragma unroll
      for (int i = 0; i < 8; i++) t[2 + i] = i > lim ? neg : s[(i >> 1) * 4 + (i & 1)];
      float mx = fmaxf(fmaxf(fmaxf(fmaxf(t[2], t[3]), fmaxf(t[4], t[5])), fmaxf(fmaxf(t[6], t[7]), fmaxf(t[8], t[9]))), fmaxf(t[0], t[1]));
      mx = fmaxf(fmaxf(mx, __shfl_xor_sync(~0u, mx, 1)), fmaxf(__shfl_xor_sync(~0u, mx, 2), __shfl_xor_sync(~0u, mx, 3)));
      const float ms = -mx * sc;
#pragma unroll
      for (int i = 0; i < 10; i++) t[i] = ex2(fmaf(t[i], sc, ms));
      uint32_t p[5];
#pragma unroll
      for (int i = 0; i < 5; i++) p[i] = pack2(t[2 * i], t[2 * i + 1]);
      float z = ((t[0] + t[1]) + (t[2] + t[3])) + ((t[4] + t[5]) + (t[6] + t[7])) + (t[8] + t[9]);
      const uint32_t row = sb + C_OS + w * 1024 + (lane >> 2) * 128 + (((lane & 3) ^ (lane >> 2)) << 4);
#pragma unroll 1
      for (uint32_t hf = 0; hf < 2; hf++) {
        float o[32];
        const uint32_t vo = hf ? (C_KV2 + 4096 - C_KV - 8192) >> 4 : j * 256;
        wg_fence();
        wg_rs64o<0, desc_sw64(C_KV + 8192)>(o, p[1], p[1], p[2], p[2], vo);
        wg_rs64o<1, desc_sw64(C_KV + 8192 + 32)>(o, p[3], p[3], p[4], p[4], vo);
        wg_rs64o<1, mkdesc(C_VM, 128, 256, 0)>(o, p[0], p[0], 0, 0, hf ? (C_VM2 - C_VM) >> 4 : j * 8);
        wg_commit();
        if (hf) {
          if (elect()) mbar_arrive(sb + CB_M);
        } else {
          z += __shfl_xor_sync(~0u, z, 1);
          z = rcp(z + __shfl_xor_sync(~0u, z, 2));
        }
        wg_wait<0>();
#pragma unroll
        for (int qq = 0; qq < 2; qq++) {
          const float* r = o + 16 * qq;
          sts128((row ^ (qq * 64)) + hf * 4096,
                 make_uint4(pack2(r[0] * z, r[1] * z), pack2(r[4] * z, r[5] * z), pack2(r[8] * z, r[9] * z), pack2(r[12] * z, r[13] * z)));
        }
      }
      bar_arrive(B_G, 160);
      if (n + 1 < STEPS) bar_arrive(B_R, 160);
      if (w == 1) TR(10);
    }
  }
  if ((threadIdx.x & 127) == 0) TS(6);
}

__device__ __forceinline__ void chain_aux(const Params& P, uint32_t sb) {
  const uint32_t c = chain_id(), j = c & 1, lane = threadIdx.x & 31, w = __shfl_sync(~0u, (threadIdx.x >> 5) & 3, 0);
  load_wg<CHAIN, true>(P, sb, false, 0, w);
  if (threadIdx.x == 384) TS(25);
  if (threadIdx.x == 384) grid_wait(1, lds32(sb + S_GEN));
  bar_sync(B_WG2, 384);
  if (threadIdx.x == 384) TS(13);
  if (w == 0) {
    const uint32_t* fg = g_fl + FL_G + near_half(XB_F, c) * 1024 + (c >> 1) * 8;
#pragma unroll 1
    for (int n = 0; n < STEPS; n++) {
      const unsigned char* blk = g_qkv + (uint32_t)((n % QRING) * (N_CHAIN * 24576));
      const uint32_t t1 = clk(), kb = sb + CB_FULL + (n & 1) * 8, kv = sb + C_KV + (n & 1) * 16384;
      uint32_t t0 = t1 - 100000, x = 0;
      if (n > 0) {
        wait_until(t1, KMIN);
        do asm volatile("ld.relaxed.gpu.global.u32 %0, [%1];" : "=r"(x) : "l"(fg) : "memory"); while (x <= n && clk() - t1 < KWIN);
        if (x > n) {
          asm volatile("fence.acquire.gpu;" ::: "memory");
          fence_async_global();
          if (elect()) { mbar_expect(kb, 8192); bulk_load(kv, blk + c * 24576, 8192, kb); }
        }
        T3(0); CNT(12, 1 + (x <= n));
        mbar_wait(sb + CB_REF, (n - 1) & 1);
        t0 = lds32(sb + C_REF);
        wait_until(t0, DLYK - 500);
      }
      wait_flags(fg + min(lane, 2u) * 256, n + 1);
      T3(2);
      fence_async_global();
      if (n > 0) bar_sync(B_R, 160);
      wait_until(t0, DLYK);
      if (elect()) {
        if (x <= n) { mbar_expect(kb, 8192); bulk_load(kv, blk + c * 24576, 8192, kb); }
        mbar_expect(sb + CB_VF, 8192);
        bulk_load(sb + C_KV + 8192, blk + (c * 24576 + 8192), 8192, sb + CB_VF);
        mbar_expect(sb + CB_Q, 16384);
        bulk_load(sb + C_Q, blk + (c * 24576 + 16384), 8192, sb + CB_Q);
        bulk_load(sb + C_KV2, blk + ((c ^ 1) * 24576 + j * 4096), 4096, sb + CB_Q);
        bulk_load(sb + C_KV2 + 4096, blk + ((c ^ 1) * 24576 + 8192 + j * 4096), 4096, sb + CB_Q);
      }
      T3(1);
      T3(3);
    }
  } else {
    const uint32_t near = __ballot_sync(~0u, near_half(XB_M + min(lane, MRING - 1u) * 8, c));
    uint32_t ring = 0;
    if (w > 1) {
      const uint32_t odd = w & 1, chk = pinned(sb + C_M + odd * 2048 + m_probe(lane)), again = sb + CB_MV + 32 + odd * 8;
      const bool one = elect();
      uint32_t mph = 0;
#pragma unroll 1
      for (int n = 0; n <= STEPS; n++) {
#pragma unroll
        for (int k = 0; k < 3; k++) {
          if (n == STEPS || (k == 2 && odd)) break;
          const uint32_t b = 2 * k + odd, at = chk + (k ? k * 8192 - 2048 + odd * 2048 : 0);
          uint32_t mb = sb + CB_M + b * 8, ph = n & 1;
          int it = 1;
          while (true) {
            mbar_wait(mb, ph);
            const bool bad = __any_sync(~0u, (k ? m_max(at, at + 2048) : max(m_max(at, at ^ 8), odd ? m_max(at + 2048, (at ^ 8) + 2048) : 0)) == SENT);
            if (one && !bad) mbar_arrive(sb + CB_MV + (b > 2 ? b * 8 - 8 : 0));
            if (!bad) break;
            mb = again; ph = mph; mph ^= 1;
            if (one) {
              if (k == 0) sts32(sb + C_BAD, n + 1);
              mbar_expect(mb, b ? 4096 : 2048);
              m_fetch(sb, ring * 65536 + ((near >> ring) & 1) * 4096, b, mb);
            }
            __syncwarp();
            spin_guard(it);
          }
          TR(41 + b * 4); CNT(6 + b, it);
        }
        ring = ring + 1 == MRING ? 0 : ring + 1;
        if (!odd) {
          if (n < STEPS) { TRSYNC(); TRDUMP(n - 2); }
        } else {
          unsigned char* o = g_oimg + (uint32_t)(((n - 1) & (RING - 1)) * (N_CHAIN * 8192) + j * 4096);
          if (n > 0) bar_sync(B_G, 160);
          fence_async_smem();
          if (one) {
            if (n > 0) {
              bulk_store(o + c * 8192, sb + C_OS, 4096);
              bulk_store(o + (c ^ 1) * 8192, sb + C_OS + 4096, 4096);
              asm volatile("cp.async.bulk.commit_group;\ncp.async.bulk.wait_group.read 0;" ::: "memory");
              { const int n_ = n - 1; { const int n = n_; T3(4); (void)n; } }
            }
            mbar_arrive(sb + CB_Q);
            if (n > 0) {
              bulk_done_inc(g_fl + FL_O + c);
              { const int n_ = n - 1; { const int n = n_; T3(5); (void)n; } }
            }
          }
          __syncwarp();
        }
      }
    } else {
      const uint32_t* ts = g_fl + FL_SYNC + near_half(XB_F + 1, c) * 1024 + lane * 2;
      uint32_t t0 = clk() - 100000, last = 0;
      int lag = 0;
#pragma unroll 1
      for (int n = 0; n < STEPS; n++) {
        const uint32_t src = ring * 65536 + ((near >> ring) & 1) * 4096;
        if (lane < 5) mbar_expect(sb + CB_M + lane * 8, lane ? 4096 : 2048);
        __syncwarp();
        if (elect()) {
#pragma unroll
          for (int b = 0; b < 5; b++) {
            wait_until(t0, P.dly[14 + b]);
            m_fetch(sb, src, b, sb + CB_M + b * 8);
            TR(40 + b * 4);
          }
        }
        __syncwarp();
        ring = ring + 1 == MRING ? 0 : ring + 1;
        uint32_t va, vb;
        const uint32_t off = timer_offset(), tag = (uint32_t)(n + 1) << 28;
        if (n > 1) lag += (int)(off - last) - (lag >> 2);
        last = off;
        const uint32_t mine = min(max((lag >> 3) + 256, 0), 511);
        bar_sync(B_QK, 416);
        if (n + 1 == STEPS) break;
        sts32(sb + C_REF + 4, 0);
        const uint32_t c0 = clk(), stamp = c0 + off;
        st_relaxed_if(g_fl + FL_SYNC + lane * 1024 + c, tag | (mine << 19) | (stamp & 0x7FFFF), lane < 2);
        TR(13);
        wait_until(c0, DLYS);
        int it = 0;
        do {
          asm volatile("ld.relaxed.gpu.global.v2.u32 {%0,%1}, [%2];" : "=r"(va), "=r"(vb) : "l"(ts) : "memory");
          spin_guard(it);
        } while (__any_sync(~0u, ((va ^ tag) | (vb ^ tag)) >> 28));
        const int late = __reduce_max_sync(~0u, max((int)((va - stamp) << 13), (int)((vb - stamp) << 13))) >> 13;
        const uint32_t fast = min(((__reduce_max_sync(~0u, max(va, vb)) >> 19) & 511) - mine, 100u);
        t0 = c0 + min((uint32_t)late, clk() - c0);
        if (elect()) {
          sts32(sb + C_REF, t0 + (fast * 3 >> 2));
          mbar_arrive(sb + CB_REF);
        }
        st_relaxed_if(g_fl + FL_TICK + lane * 1024, (uint32_t)(n + 1) << 24 | ((t0 + off) & 0xFFFFFF), c == 0 && lane < 2);
        t0 += fast * 5 >> 2;
        TRV(59, fast);
        TR(14); CNT(11, it);
        bar_sync(B_M, 160);
      }
    }
  }
}

template <int WG>
__device__ __forceinline__ void g_math(const Params& P, uint32_t sb) {
  const int q = g_unit(WG);
  const int lane = threadIdx.x & 31, w = (threadIdx.x >> 5) & 3;
  const bool isq = q >= 64;
  uint32_t a[136];
  {
    const uint32_t stage = sb + G_W + WG * 73728;
    mbar_wait(sb + W_BAR + WG * 8, 0);
    if (threadIdx.x == 0) TS(23);
    load_frags<34>(a, stage);
    fence_async_smem();
    bar_sync(B_WG0 + WG, 128);
    if (threadIdx.x == 0) TS(24);
    load_wg<GROLE>(P, sb, false, WG, w);
    if (threadIdx.x == 0) TS(25);
    mbar_wait(sb + W_BAR + WG * 8, 1);
  }
  if ((threadIdx.x & 127) == 0) TS(4);
  const uint32_t off0 = (q & 31) * 49152 + (q >> 5) * 8192 +
                        (isq ? (w >> 1) * 4096 + (w & 1) * 512 + lane * 16 : w * 1024 + (lane >> 2) * 64 + (((lane ^ (lane >> 3)) & 3) << 4));
#pragma unroll 1
  for (int n = 0; n < STEPS; n++) {
    float d0[32], d1[32];
    if (WG == 0 && n >= LOCK0) bar_sync(B_OE, 160);
    if (n > 0) bar_sync(B_V + WG, 256);
#pragma unroll
    for (int ch = 0; ch < 9; ch++) {
      mbar_wait(sb + G_BAR + ch * 8, n & 1);
      if (ch == 0) { if ((threadIdx.x & 127) == 0) T3(5 + WG * 3); __syncwarp(); }
      if (ch == 4) { if ((threadIdx.x & 127) == 0) T3(6 + WG * 3); __syncwarp(); }
      if (ch == 8 && (WG == 0 ? n > 0 : n + 1 < STEPS)) bar_arrive(B_V + (WG ^ 1), 256);
      wg_fence();
#pragma unroll
      for (int kk = 0; kk < 4; kk++) {
        const int i = ch * 4 + kk;
        float* d = i & 1 ? d1 : d0;
        const uint64_t db = desc_sw128(G_RING + ch * 8192 + (kk & 2) * 32);
        if (i < 2) wg_rs64<0>(d, a + i * 4, db);
        else if (i < 34) wg_rs64<1>(d, a + i * 4, db);
        else wg_ss64<1>(d, desc_sw128(G_W2 + WG * 4096 + (i - 34) * 2048), db);
        wg_ss64<1>(d, desc_sw128(G_W + WG * 73728 + i * 2048), db + 2);
      }
      wg_commit();
      if (ch > 0) { wg_wait<1>(); if (lane == 0) mbar_arrive(sb + G_BAR + 128 + (ch - 1) * 8); }
    }
    wg_wait<0>();
    if (lane == 0) mbar_arrive(sb + G_BAR + 128 + 8 * 8);
    if ((threadIdx.x & 127) == 0) T3(7 + WG * 3);
    __syncwarp();
    uint32_t tw = clk() + (n == 0 ? 0u - 100000u : WG ? 0u : DLYW);
    unsigned char* base = g_qkv + (size_t)(n & (QRING - 1)) * (N_CHAIN * 24576);
    if (isq) {
#pragma unroll
      for (int i = 0; i < 8; i++) {
        const float *d = (i < 4 ? d0 : d1) + 4 * i, *e = (i < 4 ? d1 : d0) + 4 * i;
        wait_until(tw, 0); tw += P.dly[2 + WG];
        *(uint4*)(base + off0 + (i >> 2) * 24576 + (i & 3) * 1024) =
          make_uint4(movmat(pack2(d[0], d[1])), movmat(pack2(e[0], e[1])), movmat(pack2(d[2], d[3])), movmat(pack2(e[2], e[3])));
      }
    } else {
#pragma unroll
      for (int i = 0; i < 8; i++) {
        const float* d = (i < 4 ? d0 : d1) + 8 * (i & 2) + 2 * (i & 1);
        wait_until(tw, 0); tw += P.dly[2 + WG];
        *(uint4*)(base + off0 + (i >> 2) * 24576 + (i & 2) * 2048 + (i & 1) * 512) =
          make_uint4(pack2(d[0], d[1]), pack2(d[4], d[5]), pack2(d[8], d[9]), pack2(d[12], d[13]));
      }
    }
    bar_sync(B_M + WG, 160);
  }
}

__device__ __forceinline__ void fill16(void* p, uint32_t v) {
  asm volatile("st.global.v4.u32 [%0], {%1,%1,%1,%1};" :: "l"(p), "r"(v) : "memory");
}
__device__ __forceinline__ void g_load(const Params& P, uint32_t sb) {
  const int lane = threadIdx.x & 31, w = __shfl_sync(~0u, (threadIdx.x >> 5) & 3, 0);
  if (w == 2) return;
  if (w < 2) { bar_sync(15, 192); fence_async_smem(); }
  uint32_t fl = 0;
#pragma unroll 1
  for (int n = w == 3 ? LOCK0 : 0; n < STEPS; n++) {
    if (w && n == LOCK0) { grid_wait(1, lds32(sb + S_GEN)); fl = near_half(XB_F, bid()) * 1024; }
    if (w == 3) {
      const uint32_t tag = (uint32_t)(n - LOCK0 + 1) << 24;
      uint32_t v; int it = 0;
      do { asm volatile("ld.relaxed.gpu.global.u32 %0, [%1];" : "=r"(v) : "l"(g_fl + fl + FL_TICK) : "memory"); spin_guard(it); } while (v < tag);
      const uint32_t off = timer_offset(), now = clk(), t0 = now - ((v ^ tag) >> 24 ? DLYG : (now + off - v) & 0xFFFFFF);
      asm volatile("fence.acquire.gpu;" ::: "memory");
      if (lane == 0) T3(11);
      __syncwarp();
      wait_until(t0, DLYG);
      if (lane == 0) T3(4);
      bar_sync(B_OE, 160);
      continue;
    }
    if (w == 0 || n == 0) {
      if (n < NSEG) wait_flags(g_lnflag + n * 16 + (lane & 1) * 8, 1);
    } else if (n >= LAG) {
      wait_flags(g_fl + fl + FL_F + (lane & 1) * 8, n - LAG + 1);
    }
    if (w) { if (lane == 0) T3(12); bar_sync(B_X, 96); }
    fence_async_global();
    const unsigned char* src = g_lnimg + (uint32_t)((w ? (n >= LAG ? NSEG + n - LAG : 0) : min(n, NSEG - 1)) * 36864);
#pragma unroll 1
    for (int ch = 0; ch < 9; ch++) {
      const uint32_t full = sb + G_BAR + ch * 8;
      mbar_wait(full + 128, (n & 1) ^ 1);
      if (elect()) {
        mbar_expect(full, 4096);
        bulk_load(sb + G_RING + ch * 8192 + w * 4096, src + ch * 4096, 4096, full);
      }
    }
  }
}

__device__ __forceinline__ void g_aux(const Params& P, uint32_t sb) {
  const int lane = threadIdx.x & 31, w = (threadIdx.x >> 5) & 3;
  if (w == 1 || w == 2) {
    const int q = g_unit(w - 1);
    uint32_t* f = g_fl + FL_G + q * 8;
#pragma unroll 1
    for (int n = 0; n < STEPS; n++) {
      const uint32_t ln = opaque_tid() & 31;
      uint4* z = (uint4*)g_oacc + (uint32_t)(((n + 1) % ARING) * (16 * DM) + q * 96 + ln);
      fill16(z, 0); fill16(z + 32, 0); fill16(z + 64, 0);
      if (n + 3 >= MRING && q < 80) fill16((uint4*)g_mimg + (uint32_t)(((n + 3) % MRING) * 4096 + q * 32 + ln), SENT);
      bar_sync(B_M + (w - 1), 160);
      if (lane == 0) { T3(w * 2 - 2); fence_async_global(); flag_release(f, n + 1); T3(w * 2 - 1); }
      __syncwarp();
    }
  } else {
    const uint32_t u = (bid() - N_CHAIN) * 2 + (w & 1), r = u / 36 * 16 + (u & 3) * 4 + (lane >> 3);
    uint32_t o = r * (DM / 8) + (u % 36 >> 2) * 8 + ((lane & 7) ^ ((r >> 1) & 3)), fl = 0;
#pragma unroll 1
    for (int k = -LAG - 1; k < STEPS; k++) {
      if (k < NSEG - 1) bar_sync(B_X, 96);
      if (k < LAG || u >= 72) continue;
      if (k == NSEG - 1) { fl = near_half(XB_F, bid()) * 1024; wait_flags(g_fl + fl + FL_F + (lane & 1) * 8, NSEG + 1); }
      const uint4 x = __ldcg((const uint4*)P.out + o);
      if (k >= NSEG - 1) wait_flags(g_fl + fl + FL_OCNT + (max(k, NSEG) % OCRING) * 8, N_O * 3 * (max(k, NSEG) / OCRING + 1));
      const float4* a = (const float4*)g_oacc + ((k % ARING) * (16 * DM) + 8 * DM + u * 64 + lane * 2);
      const float4 p = __ldcg(a), v = __ldcg(a + 1);
      ((uint4*)P.out)[o] = make_uint4(badd2(x.x, pack2(p.x, p.y)), badd2(x.y, pack2(p.z, p.w)), badd2(x.z, pack2(v.x, v.y)), badd2(x.w, pack2(v.z, v.w)));
      o += 4 * DM;
    }
    if ((threadIdx.x & 127) == 0) TS(7);
  }
}

template <int WG, bool HALF, int KS, int N> __device__ __forceinline__ void o_mma(float* d, const uint32_t* a, uint32_t ob) {
  constexpr uint64_t db = desc_sw128(O_RING + (KS >> 2) * 8192 + (KS & 3) * 32);
  constexpr uint64_t da = desc_sw128(O_W + WG * 40960 + (KS < 40 ? KS / 5 * 2 + KS % 5 / 2 : KS - 24) * 2048);
  if constexpr (KS < 40 && !(KS % 5 & 1)) {
    const uint32_t* r = a + (KS / 5 * 3 + KS % 5 / 2) * 4;
    if constexpr (HALF) wg_rs32k<KS != 0, db>(d, r[0], r[1], r[2], r[3], ob); else wg_rs64<KS != 0>(d, r, db);
  } else {
    if constexpr (HALF) wg_ss32k<da, db>(d, ob); else wg_ss64<1>(d, da, db);
  }
  if constexpr (N > 1) o_mma<WG, HALF, KS + 1, N - 1>(d, a, ob);
}
template <int WG, bool HALF, int GR> __device__ __forceinline__ void o_groups(float* d, const uint32_t* a, uint32_t sb, int n, bool more) {
  const uint32_t ob = n < NSEG ? 0 : 256;
  mbar_wait(sb + O_BAR + GR * 8, n & 1);
  if (GR == 0) { if ((threadIdx.x & 127) == 0) T3(13 + WG); __syncwarp(); }
  if (GR == (WG == 0 ? 2 : 4) && (WG < 2 || n + 1 < STEPS)) bar_arrive(B_V + (WG + 1) % 3, 256);
  wg_fence();
  o_mma<WG, HALF, GR * 8, 8>(d, a, ob);
  if (GR == 4 && more) o_mma<WG, HALF, 40, 4>(d, a, ob);
  wg_commit();
  if (GR > 0) { wg_wait<1>(); if ((threadIdx.x & 31) == 0) mbar_arrive(sb + O_BAR + 120 + GR * 8); }
  if constexpr (GR < 4) o_groups<WG, HALF, GR + 1>(d, a, sb, n, more);
}
template <int WG, bool HALF> __device__ __forceinline__ void o_step(const uint32_t* a, uint32_t sb, uint32_t st0, int n, bool more) {
  float d[HALF ? 16 : 32];
  if (WG > 0 || n > 0) bar_sync(B_V + WG, 256);
  o_groups<WG, HALF, 0>(d, a, sb, n, more);
  wg_wait<0>();
  if ((threadIdx.x & 31) == 0) mbar_arrive(sb + O_BAR + 128 + 4 * 8);
  if ((threadIdx.x & 127) == 0) T3(WG == 0 ? 1 : WG == 1 ? 8 : 12);
  __syncwarp();
#pragma unroll(HALF ? 1 : 2)
  for (int sl = 0; sl < 2; sl++) {
    mbar_wait(sb + OB_ST + WG * 16 + sl * 8, (n & 1) ^ (WG == 0));
    if (!HALF || sl == (n >= NSEG)) {
#pragma unroll
      for (int nb = 0; nb < 4; nb++) {
        const float* r = d + (HALF ? 0 : sl * 16) + nb * 4;
        const uint32_t ad = st0 + sl * 8192 + nb * 2048;
        sts32(ad, __float_as_uint(r[0]));
        sts32(ad + 256, __float_as_uint(r[1]));
        sts32(ad ^ 32, __float_as_uint(r[2]));
        sts32((ad ^ 32) + 256, __float_as_uint(r[3]));
      }
      fence_async_smem();
    }
    bar_arrive((sl ? B_G : B_M) + WG, 160);
  }
}
template <int WG>
__device__ __forceinline__ void o_math(const Params& P, uint32_t sb) {
  const bool more = bid() < N_CHAIN + N_G + 12;
  const int lane = threadIdx.x & 31, w = (threadIdx.x >> 5) & 3, g = lane >> 2, tq = lane & 3;
  uint32_t a[96];
  mbar_wait(sb + W_BAR + WG * 8, 0);
  load_frags<24>(a, sb + WG * 49152);
  fence_async_smem();
  bar_sync(B_INIT, 416);
  load_wg<OROLE>(P, sb, false, WG, w);
  mbar_wait(sb + W_BAR + WG * 8, 1);
  if ((threadIdx.x & 127) == 0) TS(4);
  const uint32_t st0 = sb + O_ST + tq * 512 + ((w * 16 + g) ^ (tq * 8)) * 4;
#pragma unroll 1
  for (int n = 0; n < STEPS; n++) {
    if (n < LAG || n >= NSEG) o_step<WG, true>(a, sb, st0, n, more); else o_step<WG, false>(a, sb, st0, n, more);
  }
}

__device__ __forceinline__ void o_aux(const Params& P, uint32_t sb) {
  const int i = bid() - N_CHAIN - N_G, ksl = i / 3;
  const int c0 = ksl * 11 - max(ksl - 4, 0), nc = ksl < 4 ? 11 : 10;
  const int lane = threadIdx.x & 31, w = __shfl_sync(~0u, (threadIdx.x >> 5) & 3, 0);
  if (w == 0) {
    bar_sync(B_INIT, 416);
    const uint32_t* f = g_fl + FL_O + near_half(XB_F + 1, bid()) * 1024 + min((c0 & ~1) + lane, (c0 + nc - 1) | 1);
#pragma unroll 1
    for (int n = 0; n < STEPS; n++) {
      const unsigned char* src = g_oimg + (uint32_t)(((n % RING) * N_CHAIN + c0) * 8192);
      wait_flags(f, n + 1);
      fence_async_global();
      if (lane == 0) T3(0);
#pragma unroll
      for (int gr = 0; gr < 5; gr++) {
        const uint32_t full = sb + O_BAR + gr * 8, bytes = (gr < 4 ? 2 : nc - 8) * 8192;
        mbar_wait(full + 128, (n & 1) ^ 1);
        if (elect()) {
          if (n < LAG || n >= NSEG) {
            mbar_expect(full, bytes >> 1);
            for (uint32_t o = gr * 16384 + (n < LAG ? 0 : 4096); o < gr * 16384 + bytes; o += 8192) bulk_load(sb + O_RING + o, src + o, 4096, full);
          } else {
            mbar_expect(full, bytes);
            bulk_load(sb + O_RING + gr * 16384, src + gr * 16384, bytes, full);
          }
        }
      }
    }
  } else {
#pragma unroll 1
    for (int n = 0; n < STEPS; n++) {
      float* dst = g_oacc + (uint32_t)((n % ARING) * (64 * DM) + ((i % 3) * 3 + (w - 1 + ksl) % 3) * 1024);
      const bool early = w == 3 && n < NSEG;
      bar_sync(B_M + (w - 1), 160);
      if (lane == 0) {
        T3(w * 2);
        if (n < NSEG) { bulk_reduce(dst, sb + O_ST, 4096); bulk_reduce(dst + 16 * DM, sb + O_ST + 4096, 4096); }
        asm volatile("cp.async.bulk.commit_group;" ::: "memory");
        if (early) {
          asm volatile("cp.async.bulk.wait_group.read 0;" ::: "memory");
          mbar_arrive(sb + OB_ST);
          T3(8 + w);
          bulk_done_inc(g_fl + FL_OCNT + (n % OCRING) * 8);
          T3(w * 2 + 1);
        }
      }
      __syncwarp();
      bar_sync(B_G + (w - 1), 160);
      if (lane == 0) {
        if (n >= LAG) { bulk_reduce(dst + 32 * DM, sb + O_ST + 8192, 4096); bulk_reduce(dst + 48 * DM, sb + O_ST + 12288, 4096); }
        asm volatile("cp.async.bulk.commit_group;\ncp.async.bulk.wait_group.read 1;" ::: "memory");
        if (!early) mbar_arrive(sb + OB_ST + (w % 3) * 16);
        asm volatile("cp.async.bulk.wait_group.read 0;" ::: "memory");
        mbar_arrive(sb + OB_ST + (w % 3) * 16 + 8);
        if (!early) {
          T3(8 + w);
          bulk_done_inc(g_fl + FL_OCNT + (n % OCRING) * 8);
          T3(w * 2 + 1);
        }
      }
      __syncwarp();
    }
  }
}

constexpr uint32_t Y_PITCH = 1168, Y_ROWS = 16 * Y_PITCH;
template <int R> __device__ __forceinline__ void y_rows(uint32_t* y, uint32_t src, uint32_t dst, int w, int bar) {
  const int lane = threadIdx.x & 31;
#pragma unroll
  for (int k = 0; k < 2 * R + 1; k++) {
    const int op = w + k * (16 / R);
    if (k == 2 * R && w >= 4) break;
    uint32_t a, b, c, d;
    ldsm4t(a, b, c, d, src + op * 512 + (lane & 16) * 16 + (lane & 7) * 32 + (lane & 8) * 2);
    stsm4(dst + (lane & 15) * Y_PITCH + op * 32 + (lane & 16), a, b, c, d);
  }
  bar_sync(bar, 512 / R);
  const uint32_t row = dst + ((w & 6) * 2 + (w >> 3) * 2 + (w & 1)) * Y_PITCH + lane * 4;
#pragma unroll
  for (int i = 0; i < 9 * R; i++) y[i] = lds32(row + i / 9 * 2 * Y_PITCH + i % 9 * 128);
}

__device__ __forceinline__ void f_role(const Params& P, uint32_t sb) {
  const int lane = threadIdx.x & 31, w = __shfl_sync(~0u, threadIdx.x >> 5, 0), r0 = (bid() - N_CHAIN - N_G - N_O) * 16;
  if (w == 8) {
    const uint32_t* fo = g_fl + FL_OCNT + near_half(XB_F, bid()) * 1024;
    fence_async_global();
#pragma unroll 1
    for (int n = 0; n < NSEG; n++) {
      bar_sync(2, 288);
      if (elect()) {
        mbar_expect(sb + F_BAR, 36864);
        bulk_load(sb + F_XY, P.X + (size_t)(n * 32 + r0) * DM, 18432, sb + F_BAR);
        bulk_load(sb + F_XY + 18432, g_yT + (size_t)(n * 32 + r0) * DM, 18432, sb + F_BAR);
        mbar_expect(sb + F_BAR + 8, 36864);
        T3(1);
      }
      wait_flags(fo + (n % OCRING) * 8, N_O * 3 * (n / OCRING + 1));
      fence_async_global();
      if (elect()) { bulk_load(sb + F_A, g_oacc + (uint32_t)((n % ARING) * (64 * DM) + r0 * DM), 36864, sb + F_BAR + 8); T3(0); }
    }
  } else if (w == 9) {
#pragma unroll 1
    for (int n = 0; n < NSEG; n++) {
      const uint32_t st = sb + (n & 1) * 36864;
      unsigned char* p = g_lnimg + (uint32_t)((NSEG + n) * 36864 + r0 * 128);
      bar_sync(1, 288);
      if (elect()) {
        T3(2);
#pragma unroll
        for (int i = 0; i < 9; i++) bulk_store(p + i * 4096, st + F_L + i * 2048, 2048);
        asm volatile("cp.async.bulk.commit_group;" ::: "memory");
        bulk_done_inc(g_fl + FL_F + (bid() & 1) * 8);
        T3(3);
        bulk_store(P.out + (size_t)(n * 32 + r0) * DM, st + F_X, 18432);
        asm volatile("cp.async.bulk.commit_group;\ncp.async.bulk.wait_group.read 0;" ::: "memory");
        if (n + 1 == NSEG) bulk_done_inc(g_fl + FL_F + (bid() & 1) * 8);
      }
      __syncwarp();
    }
  } else if (w < 8) {
    const uint32_t row = sb + w * 1152 + lane * 4, acc = sb + F_A + w * 256 + (lane ^ ((w & 6) * 2)) * 8;
    const uint32_t ln = sb + F_L + w * 128 + (((lane >> 2) ^ w) << 4) + (lane & 3) * 4;
#pragma unroll 1
    for (int n = -1; n < NSEG; n++) {
      const uint32_t st = (n & 1) * 36864;
      uint32_t x[18], y[18], l[18];
      if (n >= 0) mbar_wait(sb + F_BAR, n & 1);
#pragma unroll
      for (int i = 0; i < 18; i++) x[i] = lds32(row + F_XY + i / 9 * 9216 + i % 9 * 128);
      y_rows<2>(y, sb + F_XY + 18432, sb + F_Y, w, 3);
      layernorm9<2>(x, l);
#pragma unroll
      for (int i = 0; i < 18; i++) x[i] = badd2(x[i], bmul2(l[i], y[i]));
      if (n >= 0) mbar_wait(sb + F_BAR + 8, n & 1);
      if (threadIdx.x == 0 && n >= 0) T3(4);
      __syncwarp();
      uint2 a[18];
#pragma unroll
      for (int i = 0; i < 18; i++) a[i] = lds64(acc + i / 9 * 2048 + i % 9 * 4096);
#pragma unroll
      for (int i = 0; i < 18; i++) x[i] = badd2(x[i], pack2(__uint_as_float(a[i].x), __uint_as_float(a[i].y)));
      if (n + 1 < NSEG) bar_arrive(2, 288);
      layernorm9<2>(x, l);
#pragma unroll
      for (int i = 0; i < 18; i++) { x[i] = badd2(x[i], bmul2(l[i], y[i])); sts32(row + st + F_X + i / 9 * 9216 + i % 9 * 128, x[i]); }
      layernorm9<2>(x, l);
#pragma unroll
      for (int i = 0; i < 18; i++) sts32(ln + st + i / 9 * 1024 + i % 9 * 2048, l[i]);
      fence_async_smem();
      if (n >= 0) bar_sync(1, 288); else bar_sync(3, 256);
    }
  }
}

constexpr uint32_t P_CH = 147456, P_CHSZ = 12800, P_H = 4352;
static_assert(P_CH + 6 * P_CHSZ <= G_BAR, "prologue smem");

template <int N>
__device__ __forceinline__ void conv_fold(float (*acc)[4], bool hi, uint32_t mine, uint32_t theirs, int bar, int cnt) {
#pragma unroll
  for (int i = 0; i < N / 2; i++) {
    uint4 v;
    v.x = __float_as_uint(hi ? acc[i][0] : acc[i + N / 2][0]); v.y = __float_as_uint(hi ? acc[i][1] : acc[i + N / 2][1]);
    v.z = __float_as_uint(hi ? acc[i][2] : acc[i + N / 2][2]); v.w = __float_as_uint(hi ? acc[i][3] : acc[i + N / 2][3]);
    sts128(mine + i * 512, v);
  }
  bar_sync(bar, cnt);
#pragma unroll
  for (int i = 0; i < N / 2; i++) {
    const uint4 v = lds128(theirs + i * 512);
    acc[i][0] = (hi ? acc[i + N / 2][0] : acc[i][0]) + __uint_as_float(v.x); acc[i][1] = (hi ? acc[i + N / 2][1] : acc[i][1]) + __uint_as_float(v.y);
    acc[i][2] = (hi ? acc[i + N / 2][2] : acc[i][2]) + __uint_as_float(v.z); acc[i][3] = (hi ? acc[i + N / 2][3] : acc[i][3]) + __uint_as_float(v.w);
  }
}
template <int N>
__device__ __forceinline__ void conv_store(const float (*acc)[4], int tile0, uint32_t su, int d, uint32_t dd) {
  const int lane = threadIdx.x & 31, g = lane >> 2, tq = lane & 3;
#pragma unroll
  for (int i = 0; i < N; i++) {
    const uint32_t ad = su + (8 + (tile0 + i) * 8 + g) * 32 + tq * 4, sw = (g & 4) << 2;
    const uint32_t lo = badd2(movmat(pack2(acc[i][0], acc[i][1])), bmul2(lds32(ad + sw), dd));
    const uint32_t hi = badd2(movmat(pack2(acc[i][2], acc[i][3])), bmul2(lds32(ad + (sw ^ 16)), dd));
    ((uint2*)g_yT)[(((tile0 + i) * 8 + g) * DM + d) * 4 + tq] = make_uint2(lo, hi);
  }
}

__device__ __forceinline__ void prologue(const Params& P, uint32_t sb) {
  const int b = bid(), tid = threadIdx.x, lane = tid & 31, warp = tid >> 5, t0 = b * 16;
  const bool isg = b >= N_CHAIN && b < N_CHAIN + N_G;
  const int nch = isg ? 2 : b < 128 ? 6 : 0, chb = b < N_CHAIN ? b * 6 : isg ? b * 2 + 256 : b * 6 - 192;
  const uint32_t tstart = clk();
  if (tid < 288) {
    if (b < 128) {
      const int c = (tid >> 1) * 4, tt = t0 + (tid & 1) * 8;
      uint2 kr[11], vr[8];
#pragma unroll
      for (int i = 0; i < 11; i++) { const int t = tt + i - 3; kr[i] = t >= 0 ? __ldg((const uint2*)(P.K + (size_t)t * DM + c)) : make_uint2(0, 0); }
#pragma unroll
      for (int i = 0; i < 8; i++) vr[i] = __ldg((const uint2*)(P.V + (size_t)(tt + i) * DM + c));
#pragma unroll
      for (int e = 0; e < 2; e++) {
        const uint4 sh = __ldg((const uint4*)(P.shift + c * 4) + e);
        const uint32_t s0 = __byte_perm(sh.x, sh.z, 0x5410), s1 = __byte_perm(sh.x, sh.z, 0x7632);
        const uint32_t s2 = __byte_perm(sh.y, sh.w, 0x5410), s3 = __byte_perm(sh.y, sh.w, 0x7632);
        uint32_t v[8];
#pragma unroll
        for (int i = 0; i < 8; i++) {
          const uint32_t k3 = e ? kr[i].y : kr[i].x, k2 = e ? kr[i + 1].y : kr[i + 1].x, k1 = e ? kr[i + 2].y : kr[i + 2].x, k0 = e ? kr[i + 3].y : kr[i + 3].x;
          v[i] = bmul2(badd2(badd2(badd2(bmul2(k3, s3), bmul2(k2, s2)), bmul2(k1, s1)), bmul2(k0, s0)), e ? vr[i].y : vr[i].x);
        }
        *(uint4*)(g_kvT + (size_t)(c + 2 * e) * KVP + tt) =
          make_uint4(__byte_perm(v[0], v[1], 0x5410), __byte_perm(v[2], v[3], 0x5410), __byte_perm(v[4], v[5], 0x5410), __byte_perm(v[6], v[7], 0x5410));
        *(uint4*)(g_kvT + (size_t)(c + 2 * e + 1) * KVP + tt) =
          make_uint4(__byte_perm(v[0], v[1], 0x7632), __byte_perm(v[2], v[3], 0x7632), __byte_perm(v[4], v[5], 0x7632), __byte_perm(v[6], v[7], 0x7632));
      }
    }
  } else if (tid < 384) {
    const int t = tid - 288;
    for (int i = b * 96 + t; i < 16 * DM; i += N_CTA * 96) ((uint4*)g_oacc)[i] = make_uint4(0, 0, 0, 0);
    if (b * 96 + t < 128 * 8) g_lnflag[b * 96 + t] = 0;
    if (t == 95) sts32(sb + S_GEN, ld_acquire(g_gbar));
    __syncwarp();
    wait_until(tstart, PREFH);
    for (int i = t; i < 32 * nch; i += 96) asm volatile("prefetch.global.L2 [%0];" :: "l"(P.Hk + (size_t)chb * SEQ + i * 64));
  }
  if (warp < 12) {
    bar_arrive(10, 416);
    if (tid == 128) TS(14);
    const int ch = 5 - (warp >> 1), sub = warp & 1, d = chb + ch;
    const uint32_t su = sb + P_CH + ch * P_CHSZ;
    if (ch < nch) {
      const uint32_t* hs = (const uint32_t*)(P.Hk + (size_t)d * SEQ);
#pragma unroll
      for (int q = sub * 32 + lane; q < 256; q += 64) {
        const uint4 c = __ldg((const uint4*)hs + q);
        const uint32_t prev = q ? __ldg(hs + 4 * q - 1) : 0u;
        sts128(su + P_H + 32 + q * 16, make_uint4(__byte_perm(c.x, prev, 0x7610), __byte_perm(c.y, c.x, 0x7610), __byte_perm(c.z, c.y, 0x7610), __byte_perm(c.w, c.z, 0x7610)));
        sts128(su + P_H + 4224 + q * 16, make_uint4(__byte_perm(c.x, 0, 0x1032), __byte_perm(c.y, 0, 0x1032), __byte_perm(c.z, 0, 0x1032), __byte_perm(c.w, 0, 0x1032)));
      }
      if (sub == 1 && lane == 0) sts32(su + P_CHSZ - 16, __bfloat16_as_ushort(P.Dk[d]) * 0x10001u);
      if (sub == 0 && lane < 20) sts128(su + (lane < 16 ? lane * 16 : P_H + (lane & 2) * 2096 + (lane & 1) * 16), make_uint4(0, 0, 0, 0));
    }
    bar_sync(11, 416);
    if (ch < nch) {
#pragma unroll
      for (int q = sub * 32 + lane; q < 256; q += 64) {
        const int row = (q >> 1) + 8;
        sts128(su + row * 32 + (((q & 1) ^ ((row >> 2) & 1)) << 4), __ldcg((const uint4*)(g_kvT + (size_t)d * KVP) + q));
      }
    }
    const int g = lane >> 2, tq = lane & 3;
    const uint32_t sh = su + P_H + (g & 1) * 4192 + (8 + (g >> 1) - tq) * 4;
    float acc[16][4];
#pragma unroll
    for (int i = 0; i < 16; i++) { acc[i][0] = acc[i][1] = acc[i][2] = acc[i][3] = 0.f; }
    auto u_addr = [&](int res) {
      const int row = 8 - res + ((lane >> 4) << 3) + (lane & 7);
      return su + row * 32 + ((((lane >> 3) & 1) ^ ((row >> 2) & 1)) << 4);
    };
    if (ch < nch) {
      bar_sync(1 + ch, 64);
      if (tid == 352) TS(11);
      if (sub) {
#pragma unroll 4
        for (int res = 0; res < 8; res++) {
          uint32_t b0, b1, b2, b3;
          ldsm4(b0, b1, b2, b3, u_addr(res));
          const uint32_t r0 = lds32(sh + res * 32);
          mma16(acc[0], r0, lds32(sh + res * 32 + 16), lds32(sh + res * 32 - 16), r0, b0, b1);
        }
        conv_store<1>(acc, 0, su, d, lds32(su + P_CHSZ - 16));
      }
    }
    bar_arrive(12, 416);
    if (isg && warp < 8) { while ((int)(clk() - tstart - S1G) < 0) __nanosleep(200); load_wg<GROLE>(P, sb, true, warp >> 2, warp & 3); }
    if (ch < nch) {
#pragma unroll 1
      for (int res = sub * 4; res < sub * 4 + 4; res++) {
        uint32_t bf[16][2];
        const uint32_t ad = u_addr(res);
#pragma unroll
        for (int f = 0; f < 16; f += 2) ldsm4(bf[f][0], bf[f][1], bf[f + 1][0], bf[f + 1][1], ad + f * 256);
#pragma unroll
        for (int k = 0; k < 16; k++) {
          const int jj = k & 1 ? k >> 1 : 15 - (k >> 1);
          const uint32_t ah = sh + (8 * jj + res) * 32;
          const uint32_t r0 = lds32(ah), r1 = lds32(ah + 16), rm = lds32(ah - 16);
#pragma unroll
          for (int i = max(jj, 1); i < 16; i++) mma16(acc[i], r0, r1, rm, r0, bf[i - jj][0], bf[i - jj][1]);
        }
      }
      bar_sync(1 + ch, 64);
      if (tid == 352) TS(12);
      const uint32_t xb = su + P_H + lane * 16, dd = lds32(su + P_CHSZ - 16);
      conv_fold<16>(acc, sub, xb + sub * 4096, xb + (sub ^ 1) * 4096, 1 + ch, 64);
      conv_store<8>(acc, sub * 8, su, d, dd);
    }
  } else {
    for (int i = b; i < 194 + MRING * 5; i += N_CTA) {
      const int n = (i - 194) / 5, r = (i - 194) % 5, blk = i < 192 ? i / 6 * 8 + i % 6 : i < 194 ? XB_F + i - 192 : XB_M + n * 8 + r;
      const uint32_t fill = i < 194 ? 0u : SENT;
#pragma unroll 1
      for (int q = tid - 384; q < 256 && warp < 15; q += 96) {
        uint4 v = make_uint4(fill, fill, fill, fill);
        if (i >= 194 && n == 0 && (r > 0 || q < 128)) {
          const bf16* m = P.mem0 + (max(r * 8 - 4, 0) + (q >> 5)) * 16 + ((q >> 1) & 1) * 8 + ((q >> 2) & 7);
          v.x = pack2(__bfloat162float(m[0]), __bfloat162float(m[DM])); v.y = pack2(__bfloat162float(m[2 * DM]), __bfloat162float(m[3 * DM]));
          v.z = pack2(__bfloat162float(m[4 * DM]), __bfloat162float(m[5 * DM])); v.w = pack2(__bfloat162float(m[6 * DM]), __bfloat162float(m[7 * DM]));
        }
        g_xb[blk * 512 + q] = v;
        g_xb[blk * 512 + 256 + q] = v;
      }
    }
    if (tid < 388) g_xb[XB_REF * 512 + (tid & 2) * 128 + (b & ~1) + (tid & 1)] = make_uint4(0, 0, 0, 0);
    else if (tid < 392 && b < N_GRP) g_xb[(b * 8 + 7) * 512 + (tid & 2) * 128 + (tid & 1)] = make_uint4(0, 0, 0, 0);
    if (warp < 15) { bar_arrive(9, 128); bar_sync(7, 96); }
    if (tid == 384) TS(8);
    if (warp == 12) {
      const bf16* w = lane < 6 ? (lane % 3 == 0 ? P.Wk : lane % 3 == 1 ? P.Wv : P.Wq) + (((b >> 5) * 2 + lane / 3) * 32 + (b & 31)) * 2048
                               : (lane < 8 ? P.Wo + (lane - 6) * (9 * 131072) : P.X) + b * 2048;
      uint32_t t = tstart + PREF0;
      if ((int)(clk() - t) > 0) t = clk();
#pragma unroll 1
      for (int st = 0; st < 9 && b < N_CHAIN; st++) {
#pragma unroll 1
        for (int i = 0; i < 9; i++, t += PACE) {
          wait_until(t, 0);
          if (lane == st) asm volatile("cp.async.bulk.prefetch.L2.global [%0], 4096;" :: "l"(w + i * (lane < 6 ? 262144 : 131072)) : "memory");
        }
      }
      if (lane == 0) TS(10);
    } else if (warp == 15) {
      bar_sync(10, 416);
      if (lane == 0) { grid_arrive(0); if (nch) grid_wait(0, lds32(sb + S_GEN)); }
      __syncwarp();
      bar_arrive(11, 416);
      if (lane == 0) TS(1);
      bar_sync(9, 128);
      bar_sync(12, 416);
      if (lane == 0) { TS(16); grid_arrive(2); TS(17); }
    } else if (lane == 0) {
      if (warp == 13 || (warp == 14 && b < N_GRP)) {
        uint32_t* p = (uint32_t*)(g_xb + (warp == 13 ? XB_REF * 512 + b : (b * 8 + 7) * 512));
        int votes = 0;
        for (int rep = 0; rep < 24 && abs(votes) < 7; rep++) {
          uint32_t v0, v1, c0, c1;
          asm volatile("atom.relaxed.gpu.global.add.u32 %0, [%4], 1;\n atom.relaxed.gpu.global.add.u32 %1, [%5], 1;\n"
                       "{.reg .pred p; setp.eq.u32 p, %0, 0x7ffffff3; @p trap; mov.u32 %2, %%clock; setp.eq.u32 p, %1, 0x7ffffff3; @p trap; mov.u32 %3, %%clock;}"
                       : "=&r"(v0), "=&r"(v1), "=&r"(c0), "=&r"(c1) : "l"(p + (rep & 1) * 1024), "l"(p + ((rep & 1) ^ 1) * 1024) : "memory");
          votes += ((c1 - c0 > 80u) == (rep & 1)) ? 1 : -1;
        }
        if (warp == 13) { g_side[b] = votes > 0; TS(9); } else g_near[b] = votes > 0;
      }
    }
    __syncwarp();
    if (warp > 12 && b < N_CHAIN) {
      while ((int)(clk() - tstart - S1DLY) < 0) __nanosleep(200);
      for (int k = warp - 13; k < 8; k += 3) load_wg<CHAIN>(P, sb, true, 1 - k / 4, k & 3);
    }
  }
  if (b < N_CHAIN + N_G && (warp < 8 || (isg && warp >= 12))) bar_arrive(0, 512); else bar_sync(0, 512);
  if (tid == 352) TS(2);
}

__device__ __forceinline__ void publish_y() {
  if (threadIdx.x == 383) { grid_arrive(1); TS(18); }
  __syncwarp();
}

template <int R> __device__ __forceinline__ void ln_tiles(const Params& P, uint32_t sb) {
  const int lane = threadIdx.x & 31, w = (threadIdx.x >> 5) & (16 / R - 1), half = R == 1 ? 0 : threadIdx.x >> 8, u = N_CTA - 1 - bid();
  const int first = R == 1 ? u : 46 - 2 * u + half, step = R == 1 ? 4 : 40, last = R == 1 ? 8 : 128;
  const uint32_t raw = sb + P_CH + half * (18432 + Y_ROWS), mb = sb + T_BAR + (R - 1 + half) * 8;
  const bool lead = w == 16 / R - 1 && lane == 0;
  auto load_y = [&](const bf16* src, int tile) {
    fence_async_global();
    mbar_expect(mb, 18432);
    bulk_load(raw, src + (size_t)tile * 16 * DM, 18432, mb);
  };
  uint32_t nx[9 * R];
  auto load_x = [&](int tile) {
#pragma unroll
    for (int i = 0; i < 9 * R; i++) nx[i] = __ldg((const uint32_t*)(P.X + (size_t)(tile * 16 + w + i / 9 * 8) * DM) + i % 9 * 32 + lane);
  };
  load_x(first);
  if (R == 2) {
    if (lead) { grid_wait(1, lds32(sb + S_GEN)); if (u > 3) TS(13); load_y(g_yT, first); }
    __syncwarp();
  }
#pragma unroll 1
  for (int tile = first, real = R - 1, ph = 0; tile < last; tile += real * step, real = 1, ph ^= 1) {
    uint32_t x[9 * R], l[9 * R], y[9 * R];
    const bool ts = threadIdx.x == 0 && (R == 1 ? tile == first : u > 3 && tile == first + step);
    if (ts) TS(26);
#pragma unroll
    for (int i = 0; i < 9 * R; i++) x[i] = nx[i];
    layernorm9<R>(x, l);
    if (real && tile + step < last) load_x(tile + step);
    if (R == 2 && tile == first + step && u >= N_F && w < 6) load_wg<OROLE>(P, sb, true, w >> 1, half * 2 + (w & 1));
    if (R == 1 && tile == first && lead) {
      if (real) grid_wait(2, lds32(sb + S_GEN));
      TS(13);
      load_y(real ? g_yT : P.Hk, tile);
    }
    bar_sync(13 + half, 512 / R);
    mbar_wait(mb, ph);
    if (ts) TS(28);
    y_rows<R>(y, raw, raw + 18432, w, 13 + half);
    if (ts) TS(29);
    if (lead && real && tile + step < last) { fence_async_smem(); load_y(g_yT, tile + step); }
    __syncwarp();
#pragma unroll
    for (int i = 0; i < 9 * R; i++) x[i] = badd2(x[i], bmul2(l[i], y[i]));
    layernorm9<R>(x, l);
    if (ts && l[0] != 0x12345) TS(30);
#pragma unroll
    for (int r = 0; r < R; r++) store_ln_row(0, tile * 16 + w + r * 8, l + r * 9);
    if (R == 1) {
      __syncthreads();
      if (threadIdx.x == 32 && real) { if (tile < 4) TS(19); st_release(g_lnflag + tile * 8, 1); if (tile < 4) TS(20); }
      __syncwarp();
    }
    if (ts) TS(31);
  }
  if (R == 2) {
    __syncthreads();
    if (threadIdx.x >= 506) {
      asm volatile("fence.acq_rel.gpu;" ::: "memory");
      st_relaxed_if(g_lnflag + ((first ^ (lane & 1)) + (lane - 26) / 2 * step) * 8, 1, true);
    }
    __syncwarp();
    fence_async_smem();
    if (threadIdx.x == 0) TS(15);
  }
}

__global__ void __cluster_dims__(2, 1, 1) __launch_bounds__(512, 1) k_main(const __grid_constant__ Params P) {
  extern __shared__ __align__(1024) unsigned char smem[];
  const uint32_t sb = (uint32_t)__cvta_generic_to_shared(smem);
  const int b = bid(), wg = threadIdx.x >> 7;
  if ((threadIdx.x & 127) == 0) TS(0);
  if (threadIdx.x == 480) {
    if ((sb & 0xFFFFFF) != SBASE) __trap();
    for (int i = 0; i < 6; i++) mbar_init(sb + W_BAR + i * 8, 1);
    if (b < N_CHAIN) {
      mbar_init(sb + CB_FULL, 1); mbar_init(sb + CB_FULL + 8, 1);
      mbar_init(sb + CB_REF, 1);
      mbar_init(sb + CB_SX, 1); mbar_init(sb + CB_OX, 1); mbar_init(sb + CB_XX, 1); mbar_init(sb + CB_Q, 2); mbar_init(sb + CB_VF, 1);
      sts32(sb + C_BAD, 0);
      for (int i = 0; i < 11; i++) mbar_init(sb + CB_M + i * 8, i == 0 ? 5 : i == 5 ? 3 : 1);
    } else if (b < N_CHAIN + N_G) {
      for (int i = 0; i < 9; i++) { mbar_init(sb + G_BAR + i * 8, 2); mbar_init(sb + G_BAR + 128 + i * 8, 8); }
    } else if (b < N_CHAIN + N_G + N_O) {
      for (int i = 0; i < 5; i++) { mbar_init(sb + O_BAR + i * 8, 1); mbar_init(sb + O_BAR + 128 + i * 8, 12); }
      for (int i = 0; i < 6; i++) mbar_init(sb + OB_ST + i * 8, 1);
    } else {
      mbar_init(sb + F_BAR, 1); mbar_init(sb + F_BAR + 8, 1);
    }
    asm volatile("fence.mbarrier_init.release.cluster;" ::: "memory");
    fence_async_smem();
  }
  __syncwarp();
  asm volatile("barrier.cluster.arrive.relaxed.aligned;" ::: "memory");
  prologue(P, sb);
  asm volatile("barrier.cluster.wait.aligned;" ::: "memory");
  fence_async_smem();
  if (b >= N_CHAIN + N_G) publish_y();
  if (b >= 128) ln_tiles<1>(P, sb);
  if (b >= N_CHAIN + N_G) ln_tiles<2>(P, sb);
  if ((threadIdx.x & 127) == 0) TS(3);
  if (b < N_CHAIN) {
    if (wg < 2) { reg_inc<200>(); chain_proj(P, sb); }
    else if (wg == 2) { reg_dec<80>(); publish_y(); chain_attn(P, sb); }
    else { reg_dec<32>(); chain_aux(P, sb); }
  } else if (b < N_CHAIN + N_G) {
    if (wg == 0) { reg_inc<232>(); g_math<0>(P, sb); }
    else if (wg == 1) { reg_inc<232>(); g_math<1>(P, sb); }
    else if (wg == 2) { reg_dec<24>(); bar_arrive(15, 192); publish_y(); g_aux(P, sb); }
    else { reg_dec<24>(); g_load(P, sb); }
  } else if (b < N_CHAIN + N_G + N_O) {
    if (wg == 0) { reg_inc<160>(); o_math<0>(P, sb); }
    else if (wg == 1) { reg_inc<160>(); o_math<1>(P, sb); }
    else if (wg == 2) { reg_inc<160>(); o_math<2>(P, sb); }
    else { reg_dec<32>(); o_aux(P, sb); }
  } else {
    f_role(P, sb);
  }
}

}

extern "C" void kernel_launch(void* const* d_in, const int* in_sizes, int n_in, void* d_out, int out_size) {
  typedef CUresult (*Encode)(CUtensorMap*, CUtensorMapDataType, cuuint32_t, void*, const cuuint64_t*, const cuuint64_t*, const cuuint32_t*, const cuuint32_t*,
                             CUtensorMapInterleave, CUtensorMapSwizzle, CUtensorMapL2promotion, CUtensorMapFloatOOBfill);
  static Encode encode = nullptr;
  if (!encode) cudaGetDriverEntryPoint("cuTensorMapEncodeTiled", (void**)&encode, cudaEnableDefault);
  Params P;
  for (int i = 0; i < 11; i++) {
    const bool wo = i == 6 || i == 7;
    const cuuint64_t cols = wo ? DM : HD, rows = HD + DM - cols, pitch = cols * 2;
    const cuuint64_t dim[4][5] = {{cols, 2, 8, 2, 18}, {cols, 16, 1, 1, rows / 16}, {cols, 2, 4, 4, rows / 32}, {64, 16, 64, 2, 18}};
    const cuuint64_t stride[4][4] = {{8 * pitch, pitch, 16 * pitch, 32 * pitch}, {pitch, pitch, pitch, 16 * pitch},
                                     {pitch, 8 * pitch, 2 * pitch, 32 * pitch}, {pitch, 128, 16 * pitch, 32 * pitch}};
    const cuuint32_t box[4][5] = {{64, 2, 8, 1, 18}, {64, 16, 1, 1, 1}, {64, 2, 4, 2, 1}, {64, 16, 2, 1, 18}}, one[5] = {1, 1, 1, 1, 1};
    const int k = i < 3 ? 0 : i < 7 ? 1 : i < 8 ? 2 : 3;
    encode(&P.map[i], CU_TENSOR_MAP_DATA_TYPE_BFLOAT16, 5, d_in[wo ? 11 : 8 + (i & 7) % 3], dim[k], stride[k], box[k], one,
           CU_TENSOR_MAP_INTERLEAVE_NONE, CU_TENSOR_MAP_SWIZZLE_128B, CU_TENSOR_MAP_L2_PROMOTION_L2_128B, CU_TENSOR_MAP_FLOAT_OOB_FILL_NONE);
  }
  P.X = (const bf16*)d_in[0]; P.K = (const bf16*)d_in[1]; P.V = (const bf16*)d_in[2];
  P.shift = (const bf16*)d_in[3]; P.Hk = (const bf16*)d_in[4]; P.Dk = (const bf16*)d_in[5];
  P.mem0 = (const bf16*)d_in[7];
  P.Wq = (const bf16*)d_in[8]; P.Wk = (const bf16*)d_in[9]; P.Wv = (const bf16*)d_in[10]; P.Wo = (const bf16*)d_in[11];
  P.out = (bf16*)d_out;
  for (int i = 0; i < 24; i++) P.dly[i] = h_dly[i];
  cudaFuncSetAttribute(k_main, cudaFuncAttributeMaxDynamicSharedMemorySize, SMEM_BYTES);
  k_main<<<N_CTA, 512, SMEM_BYTES>>>(P);
}
```

```cpp
#include <cuda.h>
#include <cuda_runtime.h>
#include <cuda_bf16.h>
#include <stdint.h>

namespace {

typedef __nv_bfloat16 bf16;

constexpr int SEQ = 2048, DM = 576, HD = 4096, NSEG = 64;
constexpr int LAG = 7, STEPS = NSEG + LAG, RING = 8;
constexpr int LOCK0 = 3, QRING = LOCK0 + 1;
static_assert(LAG < RING, "ring");
constexpr int N_CHAIN = 64, N_G = 48, N_O = 18, N_F = 2;
constexpr uint32_t SBASE = 1024;
constexpr uint32_t SENT = 0xFFFFFFFFu;
constexpr int SPIN_MAX = 1 << 22;

__device__ __forceinline__ uint32_t bid() {
  uint32_t b;
  asm volatile("mov.u32 %0, %%ctaid.x;" : "=r"(b));
  return b < 6 ? b + 106 : b < 8 ? b + 122 : b < 114 ? b - 8 : b < 130 ? b - 2 : b;
}
__device__ __forceinline__ uint32_t chain_id() { return blockIdx.x - 8; }
constexpr int KVP = SEQ + 64;
__device__ __align__(1024) bf16 g_kvT[DM * KVP];
__device__ __align__(1024) bf16 g_yT[DM * SEQ];
__device__ __align__(1024) unsigned char g_lnimg[2 * NSEG * 9 * 4096];
__device__ __align__(1024) unsigned char g_qkv[QRING * N_CHAIN * 24576];
__device__ __align__(1024) unsigned char g_oimg[RING * N_CHAIN * 8192];
constexpr int ARING = 16;
static_assert(ARING >= LAG + 9, "accumulator ring");
__device__ __align__(1024) float g_oacc[ARING * 64 * DM];
constexpr int MRING = LAG + 4, N_GRP = 32 + MRING + 1;
constexpr int XB_M = 256, XB_F = XB_M + MRING * 8, XB_REF = XB_F + 2, N_CTA = N_CHAIN + N_G + N_O + N_F;
__device__ __align__(65536) uint4 g_xb[N_GRP * 4096];
#define g_mimg ((uint32_t*)(g_xb + XB_M * 512))
__device__ uint32_t g_near[N_GRP];
__device__ uint32_t g_side[N_CTA];
__device__ __align__(128) uint32_t g_gbar[3 * 32];
constexpr int FL_G = 0, FL_F = 96 * 8, FL_OCNT = FL_F + 2 * 8, OCRING = 16, FL_TICK = 992, FL_O = 2048, FL_SYNC = FL_O + 128;
static_assert(FL_OCNT + OCRING * 8 <= FL_TICK, "flag block");
#define g_fl ((uint32_t*)(g_xb + XB_F * 512))
__device__ __align__(1024) uint32_t g_lnflag[128 * 8];
#define TS(slot)

#define CNT(slot, tries)
#define T3(slot)
#define TR(slot)
#define TRV(slot, val)
#define TRD(slot, dep)
#define TRSYNC()
#define TRDUMP(n)
#define CLK(t) "{.reg .b64 x; .reg .b32 h; mov.u64 x, %%clock64; mov.b64 {" t ", h}, x;}"
__device__ __forceinline__ uint32_t clk() { uint32_t t; asm volatile(CLK("%0") : "=r"(t) :: "memory"); return t; }
__device__ __forceinline__ void wait_until(uint32_t t0, uint32_t d) {
  asm volatile("{.reg .pred p; .reg .u32 t;\n"
               "W: " CLK("t") " sub.u32 t, t, %0; setp.lt.s32 p, t, 0; @p bra.uni W;}"
               :: "r"(t0 + d) : "memory");
}
__device__ __forceinline__ uint32_t pack2(float lo, float hi) {
  uint32_t r; asm("cvt.rn.bf16x2.f32 %0, %1, %2;" : "=r"(r) : "f"(hi), "f"(lo)); return r;
}
__device__ __forceinline__ float bf_lo(uint32_t v) { return __uint_as_float(v << 16); }
__device__ __forceinline__ float bf_hi(uint32_t v) { return __uint_as_float(v & 0xFFFF0000u); }

__device__ __forceinline__ void st_b128(void* p, uint32_t a, uint32_t b, uint32_t c, uint32_t d) {
  asm volatile("{.reg .b128 v; mov.b128 v, {%1,%2,%3,%4}; st.relaxed.gpu.global.b128 [%0], v;}" :: "l"(p), "r"(a), "r"(b), "r"(c), "r"(d) : "memory");
}
__device__ __forceinline__ void st_relaxed_if(void* p, uint32_t a, bool on) {
  asm volatile("{.reg .pred p; setp.ne.u32 p, %2, 0; @p st.relaxed.gpu.global.u32 [%0], %1;}" :: "l"(p), "r"(a), "r"((uint32_t)on) : "memory");
}
__device__ __forceinline__ uint32_t ld_acquire(const uint32_t* p) {
  uint32_t v; asm volatile("ld.acquire.gpu.global.u32 %0, [%1];" : "=r"(v) : "l"(p) : "memory"); return v;
}
__device__ __forceinline__ void st_release(uint32_t* p, uint32_t v) {
  asm volatile("st.release.gpu.global.u32 [%0], %1;" :: "l"(p), "r"(v) : "memory");
}
__device__ __forceinline__ void bulk_reduce(float* dst, uint32_t src, uint32_t bytes) {
  asm volatile("cp.reduce.async.bulk.global.shared::cta.bulk_group.add.f32 [%0], [%1], %2;" :: "l"(dst), "r"(src), "r"(bytes) : "memory");
}
__device__ __forceinline__ void bulk_done_inc(uint32_t* p) {
  asm volatile("cp.async.bulk.wait_group 0;\n"
               "fence.proxy.async.global;\nfence.release.gpu;\n"
               "red.relaxed.gpu.global.add.u32 [%0], 1;\nred.relaxed.gpu.global.add.u32 [%0+4096], 1;" :: "l"(p) : "memory");
}
__device__ __forceinline__ void flag_release(uint32_t* p, uint32_t v) {
  asm volatile("fence.release.gpu;\nst.relaxed.gpu.global.u32 [%0], %1;\nst.relaxed.gpu.global.u32 [%0+4096], %1;" :: "l"(p), "r"(v) : "memory");
}
__device__ __forceinline__ void spin_guard(int& it) {
  asm volatile("{.reg .pred p; add.s32 %0, %0, 1; setp.gt.s32 p, %0, %1; @p trap;}" : "+r"(it) : "n"(SPIN_MAX));
}
__device__ __forceinline__ void wait_flags(const uint32_t* p, uint32_t v) {
  int it = 0;
  while (true) {
    uint32_t x; asm volatile("ld.relaxed.gpu.global.u32 %0, [%1];" : "=r"(x) : "l"(p) : "memory");
    if (__all_sync(~0u, x >= v)) break;
    spin_guard(it);
  }
  asm volatile("fence.acquire.gpu;" ::: "memory");
}
__device__ __forceinline__ uint32_t timer_offset() {
  uint32_t g0, g;
  asm volatile("mov.u32 %0, %%globaltimer_lo;" : "=r"(g0) :: "memory");
  do { asm volatile("mov.u32 %0, %%globaltimer_lo;" : "=r"(g) :: "memory"); } while (g == g0);
  return (g >> 5) * 58 - clk();
}
__device__ __forceinline__ void grid_arrive(int i) {
  asm volatile("red.release.gpu.global.add.u32 [%0], %1;" :: "l"(g_gbar + i * 32), "r"(bid() ? 1u : 257u - N_CTA) : "memory");
}
__device__ __forceinline__ void grid_wait(int i, uint32_t gen) {
  int it = 0;
  while (((ld_acquire(g_gbar + i * 32) ^ gen) >> 8) == 0) spin_guard(it);
}
__device__ __forceinline__ bool elect() {
  uint32_t r; asm volatile("{.reg .pred p; elect.sync _|p, -1; selp.u32 %0, 1, 0, p;}" : "=r"(r)); return r;
}
__device__ __forceinline__ void bar_sync(int id, int cnt) { asm volatile("bar.sync %0, %1;" :: "r"(id), "r"(cnt) : "memory"); }
__device__ __forceinline__ void bar_arrive(int id, int cnt) { asm volatile("bar.arrive %0, %1;" :: "r"(id), "r"(cnt) : "memory"); }
template <int id, int cnt> __device__ __forceinline__ void bar_arrive_after(uint32_t a, uint32_t b) {
  asm volatile("{.reg .pred p; setp.ne.u32 p, %2, 0xfff12345; setp.ne.and.u32 p, %3, 0xfff12345, p; @p bar.arrive %0, %1;}" :: "n"(id), "n"(cnt), "r"(a), "r"(b) : "memory");
}
template <int id, int cnt> __device__ __forceinline__ void bar_sync_after(uint32_t a) {
  asm volatile("{.reg .pred p; setp.ne.u32 p, %2, 0xfff12345; @p bar.sync %0, %1;}" :: "n"(id), "n"(cnt), "r"(a) : "memory");
}
__device__ __forceinline__ void fence_async_smem() { asm volatile("fence.proxy.async.shared::cta;" ::: "memory"); }
__device__ __forceinline__ void fence_async_global() { asm volatile("fence.proxy.async.global;" ::: "memory"); }
__device__ __forceinline__ void mbar_init(uint32_t mb, int cnt) { asm volatile("mbarrier.init.shared::cta.b64 [%0], %1;" :: "r"(mb), "r"(cnt) : "memory"); }
__device__ __forceinline__ void mbar_arrive(uint32_t mb) { asm volatile("mbarrier.arrive.shared::cta.b64 _, [%0];" :: "r"(mb) : "memory"); }
__device__ __forceinline__ void mbar_expect(uint32_t mb, uint32_t bytes) {
  asm volatile("mbarrier.arrive.expect_tx.shared::cta.b64 _, [%0], %1;" :: "r"(mb), "r"(bytes) : "memory");
}
__device__ __forceinline__ void mbar_wait(uint32_t mb, uint32_t parity) {
  asm volatile("{.reg .pred p;\nW: mbarrier.try_wait.parity.shared::cta.b64 p, [%0], %1;\n@!p bra W;}" :: "r"(mb), "r"(parity) : "memory");
}
__device__ __forceinline__ void bulk_load(uint32_t dst, const void* src, uint32_t bytes, uint32_t mb) {
  asm volatile("cp.async.bulk.shared::cluster.global.mbarrier::complete_tx::bytes [%0], [%1], %2, [%3];" :: "r"(dst), "l"(src), "r"(bytes), "r"(mb) : "memory");
}
__device__ __forceinline__ void bulk_store(void* dst, uint32_t src, uint32_t bytes) {
  asm volatile("cp.async.bulk.global.shared::cta.bulk_group [%0], [%1], %2;" :: "l"(dst), "r"(src), "r"(bytes) : "memory");
}
__device__ __forceinline__ uint32_t mapa(uint32_t a, uint32_t rank) {
  uint32_t r; asm("mapa.shared::cluster.u32 %0, %1, %2;" : "=r"(r) : "r"(a), "r"(rank)); return r;
}
__device__ __forceinline__ void st_async4(uint32_t dst, float a, float b, float c, float d, uint32_t mb) {
  asm volatile("st.async.shared::cluster.mbarrier::complete_tx::bytes.v4.f32 [%0], {%1,%2,%3,%4}, [%5];" :: "r"(dst), "f"(a), "f"(b), "f"(c), "f"(d), "r"(mb) : "memory");
}
__device__ __forceinline__ void st_async1(uint32_t dst, uint32_t a, uint32_t mb) {
  asm volatile("st.async.shared::cluster.mbarrier::complete_tx::bytes.u32 [%0], %1, [%2];" :: "r"(dst), "r"(a), "r"(mb) : "memory");
}
__device__ __forceinline__ uint4 lds128(uint32_t a) {
  uint4 v; asm volatile("ld.shared.v4.u32 {%0,%1,%2,%3}, [%4];" : "=r"(v.x), "=r"(v.y), "=r"(v.z), "=r"(v.w) : "r"(a) : "memory"); return v;
}
__device__ __forceinline__ uint2 lds64(uint32_t a) {
  uint2 v; asm volatile("ld.shared.v2.u32 {%0,%1}, [%2];" : "=r"(v.x), "=r"(v.y) : "r"(a) : "memory"); return v;
}
__device__ __forceinline__ uint32_t lds32(uint32_t a) {
  uint32_t v; asm volatile("ld.shared.u32 %0, [%1];" : "=r"(v) : "r"(a) : "memory"); return v;
}
__device__ __forceinline__ void sts128(uint32_t a, uint4 v) {
  asm volatile("st.shared.v4.u32 [%0], {%1,%2,%3,%4};" :: "r"(a), "r"(v.x), "r"(v.y), "r"(v.z), "r"(v.w) : "memory");
}
__device__ __forceinline__ void sts32(uint32_t a, uint32_t x) { asm volatile("st.shared.u32 [%0], %1;" :: "r"(a), "r"(x) : "memory"); }
__device__ __forceinline__ void ldsm4(uint32_t& r0, uint32_t& r1, uint32_t& r2, uint32_t& r3, uint32_t a) {
  asm volatile("ldmatrix.sync.aligned.m8n8.x4.shared.b16 {%0,%1,%2,%3}, [%4];" : "=r"(r0), "=r"(r1), "=r"(r2), "=r"(r3) : "r"(a) : "memory");
}
__device__ __forceinline__ void ldsm4t(uint32_t& r0, uint32_t& r1, uint32_t& r2, uint32_t& r3, uint32_t a) {
  asm volatile("ldmatrix.sync.aligned.m8n8.x4.trans.shared.b16 {%0,%1,%2,%3}, [%4];" : "=r"(r0), "=r"(r1), "=r"(r2), "=r"(r3) : "r"(a) : "memory");
}
__device__ __forceinline__ void stsm4(uint32_t a, uint32_t r0, uint32_t r1, uint32_t r2, uint32_t r3) {
  asm volatile("stmatrix.sync.aligned.m8n8.x4.shared.b16 [%0], {%1,%2,%3,%4};" :: "r"(a), "r"(r0), "r"(r1), "r"(r2), "r"(r3) : "memory");
}
__device__ __forceinline__ uint32_t movmat(uint32_t a) {
  uint32_t d; asm volatile("movmatrix.sync.aligned.m8n8.trans.b16 %0, %1;" : "=r"(d) : "r"(a)); return d;
}
__device__ __forceinline__ void mma16(float* d, uint32_t a0, uint32_t a1, uint32_t a2, uint32_t a3, uint32_t b0, uint32_t b1) {
  asm volatile("mma.sync.aligned.m16n8k16.row.col.f32.bf16.bf16.f32 {%0,%1,%2,%3}, {%4,%5,%6,%7}, {%8,%9}, {%0,%1,%2,%3};"
    : "+f"(d[0]), "+f"(d[1]), "+f"(d[2]), "+f"(d[3]) : "r"(a0), "r"(a1), "r"(a2), "r"(a3), "r"(b0), "r"(b1));
}
__device__ __forceinline__ void mma8(float* d, uint32_t a0, uint32_t a1, uint32_t b0) {
  asm volatile("mma.sync.aligned.m16n8k8.row.col.f32.bf16.bf16.f32 {%0,%1,%2,%3}, {%4,%5}, {%6}, {%0,%1,%2,%3};"
    : "+f"(d[0]), "+f"(d[1]), "+f"(d[2]), "+f"(d[3]) : "r"(a0), "r"(a1), "r"(b0));
}
__device__ __forceinline__ float rcp(float x) { float r; asm("rcp.approx.ftz.f32 %0, %1;" : "=f"(r) : "f"(x)); return r; }
__device__ __forceinline__ float ex2(float x) { float r; asm("ex2.approx.ftz.f32 %0, %1;" : "=f"(r) : "f"(x)); return r; }

__host__ __device__ constexpr uint64_t mkdesc(uint32_t off, uint32_t lbo, uint32_t sbo, uint32_t swz) {
  return (uint64_t)((SBASE + off) >> 4) | ((uint64_t)(lbo >> 4) << 16) | ((uint64_t)(sbo >> 4) << 32) | ((uint64_t)swz << 62);
}
__host__ __device__ constexpr uint64_t desc_sw128(uint32_t off) { return mkdesc(off, 16, 1024, 1); }
__host__ __device__ constexpr uint64_t desc_n16(uint32_t off) { return mkdesc(off, 256, 128, 0); }
__host__ __device__ constexpr uint64_t desc_m(uint32_t off) { return mkdesc(off, 16, 256, 3); }

__host__ __device__ constexpr uint64_t desc_sw64(uint32_t off) { return mkdesc(off, 16, 512, 2); }

__device__ __forceinline__ void wg_fence() { asm volatile("wgmma.fence.sync.aligned;" ::: "memory"); }
__device__ __forceinline__ void wg_commit() { asm volatile("wgmma.commit_group.sync.aligned;" ::: "memory"); }
template <int N> __device__ __forceinline__ void wg_wait() { asm volatile("wgmma.wait_group.sync.aligned %0;" :: "n"(N) : "memory"); }

#define ACC8(d) "+f"(d[0]), "+f"(d[1]), "+f"(d[2]), "+f"(d[3]), "+f"(d[4]), "+f"(d[5]), "+f"(d[6]), "+f"(d[7])
#define ACC32(d) ACC8(d), ACC8((d + 8)), ACC8((d + 16)), ACC8((d + 24))
#define R8 "{%0,%1,%2,%3,%4,%5,%6,%7}"
#define R32 "{%0,%1,%2,%3,%4,%5,%6,%7,%8,%9,%10,%11,%12,%13,%14,%15,%16,%17,%18,%19,%20,%21,%22,%23,%24,%25,%26,%27,%28,%29,%30,%31}"
template <int SD> __device__ __forceinline__ void wg_rs16(float* d, const uint32_t* a, uint64_t db) {
  asm volatile("wgmma.mma_async.sync.aligned.m64n16k16.f32.bf16.bf16 " R8 ", {%8,%9,%10,%11}, %12, %13, 1, 1, 1;"
    : ACC8(d) : "r"(a[0]), "r"(a[1]), "r"(a[2]), "r"(a[3]), "l"(db), "n"(SD));
}
template <int SD> __device__ __forceinline__ void wg_ss16(float* d, uint64_t da, uint64_t db) {
  asm volatile("wgmma.mma_async.sync.aligned.m64n16k16.f32.bf16.bf16 " R8 ", %8, %9, %10, 1, 1, 1, 1;"
    : ACC8(d) : "l"(da), "l"(db), "n"(SD));
}
template <int SD, uint64_t DA, uint64_t DB> __device__ __forceinline__ void wg_ss16o(float* d, uint32_t oa, uint32_t ob) {
  asm volatile("{.reg .b32 x, y; .reg .b64 a, b; add.u32 x, %8, %10; add.u32 y, %9, %12; mov.b64 a, {x, %11}; mov.b64 b, {y, %13};\n"
               "wgmma.mma_async.sync.aligned.m64n16k16.f32.bf16.bf16 " R8 ", a, b, %14, 1, 1, 1, 1;}"
    : ACC8(d) : "r"(oa), "r"(ob), "n"((uint32_t)DA), "n"((uint32_t)(DA >> 32)), "n"((uint32_t)DB), "n"((uint32_t)(DB >> 32)), "n"(SD));
}
template <int SD> __device__ __forceinline__ void wg_rs64(float* d, const uint32_t* a, uint64_t db) {
  asm volatile("wgmma.mma_async.sync.aligned.m64n64k16.f32.bf16.bf16 " R32 ", {%32,%33,%34,%35}, %36, %37, 1, 1, 0;"
    : ACC32(d) : "r"(a[0]), "r"(a[1]), "r"(a[2]), "r"(a[3]), "l"(db), "n"(SD));
}
template <int SD> __device__ __forceinline__ void wg_ss64(float* d, uint64_t da, uint64_t db) {
  asm volatile("wgmma.mma_async.sync.aligned.m64n64k16.f32.bf16.bf16 " R32 ", %32, %33, %34, 1, 1, 1, 0;"
    : ACC32(d) : "l"(da), "l"(db), "n"(SD));
}
#define WG_RSO(NAME, SHAPE, REGS, ACC, A, TB) \
template <int SD, uint64_t DB> __device__ __forceinline__ void NAME(float* d, uint32_t a0, uint32_t a1, uint32_t a2, uint32_t a3, uint32_t ob) { \
  asm volatile("{.reg .b64 b; mov.b64 b, {" A(4) ", " A(5) "};\nwgmma.mma_async.sync.aligned." SHAPE ".f32.bf16.bf16 " REGS \
               ", {" A(0) "," A(1) "," A(2) "," A(3) "}, b, " A(6) ", 1, 1, " TB ";}" \
    : ACC(d) : "r"(a0), "r"(a1), "r"(a2), "r"(a3), "r"(ob + (uint32_t)DB), "n"((uint32_t)(DB >> 32)), "n"(SD)); \
}
#define ACC4(d) "+f"(d[0]), "+f"(d[1]), "+f"(d[2]), "+f"(d[3])
#define ACC16(d) ACC8(d), ACC8((d + 8))
#define OP4(i) OP4_##i
#define OP4_0 "%4"
#define OP4_1 "%5"
#define OP4_2 "%6"
#define OP4_3 "%7"
#define OP4_4 "%8"
#define OP4_5 "%9"
#define OP4_6 "%10"
#define OP16(i) OP16_##i
#define OP16_0 "%16"
#define OP16_1 "%17"
#define OP16_2 "%18"
#define OP16_3 "%19"
#define OP16_4 "%20"
#define OP16_5 "%21"
#define OP16_6 "%22"
#define OP32(i) OP32_##i
#define OP32_0 "%32"
#define OP32_1 "%33"
#define OP32_2 "%34"
#define OP32_3 "%35"
#define OP32_4 "%36"
#define OP32_5 "%37"
#define OP32_6 "%38"
WG_RSO(wg_rs8o, "m64n8k16", "{%0,%1,%2,%3}", ACC4, OP4, "1")
#define R16 "{%0,%1,%2,%3,%4,%5,%6,%7,%8,%9,%10,%11,%12,%13,%14,%15}"
WG_RSO(wg_rs32o, "m64n32k16", R16, ACC16, OP16, "1")
WG_RSO(wg_rs64o, "m64n64k16", R32, ACC32, OP32, "0")
WG_RSO(wg_rs32k, "m64n32k16", R16, ACC16, OP16, "0")
template <uint64_t DA, uint64_t DB> __device__ __forceinline__ void wg_ss32k(float* d, uint32_t ob) {
  asm volatile("{.reg .b64 b; mov.b64 b, {%17, %18};\nwgmma.mma_async.sync.aligned.m64n32k16.f32.bf16.bf16 " R16 ", %16, b, 1, 1, 1, 1, 0;}"
    : ACC16(d) : "l"(DA), "r"(ob + (uint32_t)DB), "n"((uint32_t)(DB >> 32)));
}
template <int N> __device__ __forceinline__ void reg_inc() { asm volatile("setmaxnreg.inc.sync.aligned.u32 %0;" :: "n"(N)); }
template <int N> __device__ __forceinline__ void reg_dec() { asm volatile("setmaxnreg.dec.sync.aligned.u32 %0;" :: "n"(N)); }

template <int KS>
__device__ __forceinline__ void load_frags(uint32_t* a, uint32_t src) {
  const int lane = threadIdx.x & 31, w = (threadIdx.x >> 5) & 3;
  const int k = ((lane >> 4) << 3) + (lane & 7), u = w * 2 + ((lane >> 3) & 1);
  const uint32_t base = src + k * 128 + ((u ^ (k & 7)) << 4);
#pragma unroll
  for (int ks = 0; ks < KS; ks++) ldsm4t(a[ks * 4], a[ks * 4 + 1], a[ks * 4 + 2], a[ks * 4 + 3], base + ks * 2048);
}

__device__ __forceinline__ uint32_t badd2(uint32_t a, uint32_t b) { uint32_t r; asm("add.rn.bf16x2 %0, %1, %2;" : "=r"(r) : "r"(a), "r"(b)); return r; }
__device__ __forceinline__ uint32_t bsub2(uint32_t a, uint32_t b) { uint32_t r; asm("sub.rn.bf16x2 %0, %1, %2;" : "=r"(r) : "r"(a), "r"(b)); return r; }
__device__ __forceinline__ uint32_t bmul2(uint32_t a, uint32_t b) { uint32_t r; asm("mul.rn.bf16x2 %0, %1, %2;" : "=r"(r) : "r"(a), "r"(b)); return r; }
__device__ __forceinline__ uint32_t bfma2(uint32_t a, uint32_t b, uint32_t c) { uint32_t r; asm("fma.rn.bf16x2 %0, %1, %2, %3;" : "=r"(r) : "r"(a), "r"(b), "r"(c)); return r; }
template <int R> __device__ __forceinline__ void layernorm9(const uint32_t* x, uint32_t* o) {
  const uint32_t ones = 0x3F803F80u;
  float a[R][3][4], q[R], s[R];
#pragma unroll
  for (int i = 0; i < 9 * R; i++) {
    float* d = a[i % R][i / R % 3];
    if (i < 3 * R) d[0] = d[1] = d[2] = d[3] = 0.f;
    mma8(d, x[i % R * 9 + i / R], ones, x[i % R * 9 + i / R]);
  }
#pragma unroll
  for (int r = 0; r < R; r++) {
    q[r] = threadIdx.x & 4 ? a[r][0][1] + a[r][1][1] + a[r][2][1] : a[r][0][0] + a[r][1][0] + a[r][2][0];
    s[r] = (a[r][0][2] + a[r][0][3]) + (a[r][1][2] + a[r][1][3]) + (a[r][2][2] + a[r][2][3]);
  }
#pragma unroll
  for (int r = 0; r < R; r++) { q[r] += __shfl_xor_sync(~0u, q[r], 4); s[r] += __shfl_xor_sync(~0u, s[r], 1); }
#pragma unroll
  for (int r = 0; r < R; r++) { q[r] += __shfl_xor_sync(~0u, q[r], 9); s[r] += __shfl_xor_sync(~0u, s[r], 2); }
#pragma unroll
  for (int r = 0; r < R; r++) q[r] = __shfl_sync(~0u, q[r], 0) + __shfl_sync(~0u, q[r], 18);
#pragma unroll
  for (int r = 0; r < R; r++) {
    const float mean = s[r] * (1.f / DM), var = fmaxf(fmaf(q[r], 1.f / DM, -mean * mean), 0.f);
    float sd;
    asm("sqrt.approx.ftz.f32 %0, %1;" : "=f"(sd) : "f"(bf_lo(pack2(bf_lo(pack2(var, 0.f)) + 1e-5f, 0.f))));
    const float inv = rcp(bf_lo(pack2(sd, 0.f)));
    const uint32_t mb = pack2(mean, mean), hi = pack2(inv, inv), lo = pack2(inv - bf_lo(hi), inv - bf_lo(hi));
#pragma unroll
    for (int i = r * 9; i < r * 9 + 9; i++) {
      const uint32_t d = bsub2(x[i], mb);
      o[i] = bfma2(d, hi, bmul2(d, lo));
    }
  }
}
__device__ __forceinline__ void store_ln_row(int layer, int tok, const uint32_t* o) {
  const int lane = threadIdx.x & 31, r = tok & 31;
  unsigned char* p = g_lnimg + (size_t)(layer * NSEG + (tok >> 5)) * (9 * 4096) + r * 128 + (((lane >> 2) ^ (r & 7)) << 4) + (lane & 3) * 4;
#pragma unroll
  for (int i = 0; i < 9; i++) *(uint32_t*)(p + i * 4096) = o[i];
}
struct Params { CUtensorMap map[11]; const bf16 *X, *K, *V, *shift, *Hk, *Dk, *mem0, *Wq, *Wk, *Wv, *Wo; bf16* out; uint32_t dly[24]; };
#define DLYS P.dly[0]
#define DLYW P.dly[1]
#define DLYK P.dly[4]
#define DLYG P.dly[5]
#define KWIN P.dly[6]
#define KMIN P.dly[7]
#define PREF0 P.dly[19]
#define PACE P.dly[20]
#define S1G P.dly[21]
#define S1DLY P.dly[22]
#define PREFH P.dly[23]
uint32_t h_dly[24] = {900, 300, 100, 60, 3565, 4170, 2750, 1300, 1610, 1700, 1810, 2130, 2260, 2390, 2945, 3055, 3225, 3375, 3525, 7000, 160, 12500, 20500, 4000};

constexpr uint32_t C_W = 0, C_M = 147456, C_KV = C_M + 18432, C_OS = C_KV + 24576, C_QM = C_KV + 32768, C_KM = C_QM + 2048,
                   C_VM = C_KM + 2048, C_OI = C_VM + 2048, C_SX = C_OI + 4096, C_KM2 = C_SX + 2560, C_VM2 = C_KM2 + 128,
                   C_KV2 = C_KM2 + 2048, C_Q = C_KV2 + 8192, C_BAR = C_Q + 8192;
constexpr uint32_t CB_FULL = C_BAR, CB_REF = C_BAR + 16, CB_SX = C_BAR + 32, CB_OX = C_BAR + 40, CB_XX = C_BAR + 48, CB_Q = C_BAR + 56, C_BAD = C_BAR + 64, W_BAR = C_BAR + 80, T_BAR = W_BAR + 24, S_GEN = C_BAR + 128, C_REF = C_BAR + 132, CB_VF = C_BAR + 144, CB_M = C_BAR + 160, CB_MV = C_BAR + 200;
constexpr uint32_t G_W = 0, G_RING = 147456, G_W2 = G_RING + 9 * 8192, G_BAR = G_W2 + 8192;
constexpr uint32_t O_W = 0, O_RING = 3 * 40960, O_ST = O_RING + 11 * 8192, O_BAR = O_ST + 16384, OB_ST = O_BAR + 64;
constexpr uint32_t F_A = 0, F_XY = 36864, F_L = F_XY + 36864, F_X = F_L + 18432, F_Y = F_L + 2 * 36864, F_BAR = C_BAR;
constexpr uint32_t SMEM_BYTES = C_BAR + 256;
static_assert(G_BAR + 256 <= SMEM_BYTES && O_BAR + 256 <= SMEM_BYTES && F_BAR + 16 <= SMEM_BYTES && SMEM_BYTES <= 232448, "smem map");
enum { B_INIT = 1, B_M, B_QK, B_S, B_V, B_O, B_X, B_WG0, B_WG1, B_WG2, B_G, B_OE, B_T, B_R };

__device__ __forceinline__ uint4 pack_partial(const float* d, uint32_t tag) {
  uint32_t x, z;
  asm("lop3.b32 %0, %2, 1, %4, 0xb8; lop3.b32 %1, %3, 1, %4, 0xb8;" : "=&r"(x), "=&r"(z) : "r"(pack2(d[0], d[1])), "r"(pack2(d[2], d[3])), "r"(tag));
  return make_uint4(x, pack2(d[4], d[5]), z, pack2(d[6], d[7]));
}
__device__ __forceinline__ void store_partial(uint4* p, const uint4& v) { st_b128(p, v.x, v.y, v.z, v.w); }
__device__ __forceinline__ void gather_reduce(const uint32_t* p, uint32_t* dst, uint32_t m0, bool shared, uint32_t tag, uint32_t lane, uint32_t sb, int n, int TS0) {
  int tries = 0;
  bool bad;
  TR(TS0);
  do {
    uint2 x[8];
#pragma unroll
    for (int i = 0; i < 8; i++)
      asm volatile("{.reg .b64 v; ld.relaxed.gpu.global.b64 v, [%2]; mov.b64 {%0, %1}, v;}" : "=r"(x[i].x), "=r"(x[i].y) : "l"(p + i * 128) : "memory");
    spin_guard(tries);
    float a = bf_lo(x[0].x), b = bf_hi(x[0].x), c = bf_lo(x[0].y), d = bf_hi(x[0].y);
    uint32_t t = x[0].x ^ tag;
#pragma unroll
    for (int i = 1; i < 8; i++) {
      a += bf_lo(x[i].x); b += bf_hi(x[i].x); c += bf_lo(x[i].y); d += bf_hi(x[i].y);
      asm("lop3.b32 %0, %0, %1, %2, 0xf6;" : "+r"(t) : "r"(x[i].x), "r"(tag));
    }
    bad = __any_sync(~0u, t & 1);
    const bool up = lane & 8;
    float u = (up ? c : a) + __shfl_xor_sync(~0u, up ? a : c, 8), v = (up ? d : b) + __shfl_xor_sync(~0u, up ? b : d, 8);
    if (shared) { u += __shfl_xor_sync(~0u, u, 4); v += __shfl_xor_sync(~0u, v, 4); }
    u += __shfl_xor_sync(~0u, u, 16);
    v += __shfl_xor_sync(~0u, v, 16);
    st_relaxed_if(dst, n < LAG && up ? m0 : pack2(u, v), !bad);
  } while (bad);
  TR(TS0 + 3); TRV(TS0 + 2, tries);
  CNT((TS0 - 16) >> 2, tries);
}

constexpr int XR = 3;
__host__ __device__ constexpr int o_ks(int s) { return s & (s < 8 ? 3 : 7); }
__host__ __device__ constexpr bool o_reg(int s) { return s < 8 ? (s & 3) != 3 : !(s & 1); }
__host__ __device__ constexpr int o_slot(int s) { return s < 8 ? (o_reg(s) ? s - (s >> 2) : s >> 2) : s & 1 ? (s - 5) >> 1 : (s + 4) >> 1; }
__device__ __forceinline__ int g_unit(int wg) {
  const int i = bid() - N_CHAIN;
  return i < 32 ? wg * 64 + i : 2 * i - 32 + wg;
}
__device__ __forceinline__ uint32_t pinned(uint32_t v) { return __shfl_sync(~0u, v, threadIdx.x & 31); }
template <class T> __device__ __forceinline__ T* pinned(T* p) { return (T*)__shfl_sync(~0u, (unsigned long long)p, threadIdx.x & 31); }
enum { CHAIN, GROLE, OROLE };
template <int ROLE, bool SYNC> __device__ __forceinline__ void load_box(const Params& P, uint32_t sb, bool regs, int wg, int i, uint32_t mb, bool on) {
  const int b = bid();
  int map, col = 0, ks = 0, c2 = 0, c3 = 0;
  uint32_t dst = wg * 73728;
  if (ROLE == CHAIN) {
    const int k = i - 1, st = regs ? (k < 6 ? k + k / 3 : 2 * k - 4) : k < 2 ? 4 * k + 3 : 2 * k + 5;
    dst += i ? (17 + i) * 2048 : 0;
    if (wg || i == 0) { map = wg + i; col = b * 64; c3 = !regs; }
    else if (!regs && k >= 14) { map = 6; ks = b * 4 + k - 14; }
    else { map = 6; col = 64 + (st < 8 ? (st >> 2) * 64 : (st >> 3) * 128 + (b & 1) * 64); ks = (b * 4) ^ o_ks(st); }
  } else if (ROLE == GROLE) {
    const int q = g_unit(wg);
    map = ((q >> 5) + 1) % 3;
    if (i) { map += 3; col = (q & 31) * 128 + (i - 1) * 64; ks = 34; dst = G_W2 + wg * 4096 + (i - 1) * 2048; }
    else { map += 8; c2 = (q & 31) * 2; c3 = !regs; }
  } else {
    const int o = b - N_CHAIN - N_G, ksl = o / 3;
    map = 7; col = ((o % 3) * 3 + (wg + ksl) % 3) * 64; dst = (wg * (regs ? 24 : 20) + i) * 2048;
    ks = (ksl * 11 - max(ksl - 4, 0)) * 4 + (regs ? i / 3 * 5 + i % 3 * 2 : i < 16 ? i / 2 * 5 + 1 + i % 2 * 2 : i + 24);
    c3 = (ks & 1) * 2; ks >>= 1;
  }
  if (SYNC) { col = pinned(col); ks = pinned(ks); bar_sync(B_WG0 + wg, 256); }
  if (on) asm volatile("cp.async.bulk.tensor.5d.shared::cluster.global.tile.mbarrier::complete_tx::bytes [%0], [%1, {%2, %3, %4, %5, %6}], [%7];"
               :: "r"(sb + dst), "l"(&P.map[map]), "r"(col), "r"(0), "r"(c2), "r"(c3), "r"(ks), "r"(mb) : "memory");
}
template <int ROLE, bool SYNC = false> __device__ __forceinline__ void load_wg(const Params& P, uint32_t sb, bool regs, int wg, int quarter) {
  const int i = (threadIdx.x & 31) * 4 + quarter;
  const int n = ROLE == CHAIN ? 36 : ROLE == GROLE ? (regs ? 38 : 36) : regs ? 24 : bid() < N_CHAIN + N_G + 12 ? 20 : 16;
  const bool split = SYNC && wg == 0;
  const uint32_t mb = split && i ? sb + T_BAR : sb + W_BAR + wg * 8;
  load_box<ROLE, SYNC>(P, sb, regs, wg, i, mb, i < (ROLE == CHAIN ? (wg ? 2 : 19) : ROLE == GROLE ? n - 35 : n));
  if (i <= split) mbar_expect(mb, n * (split ? 1024 : 2048));
  __syncwarp();
}
__device__ __forceinline__ uint32_t near_half(uint32_t blk, uint32_t reader) {
  return __ldcg(g_near + (blk >> 3)) ^ (~blk & 1) ^ __ldcg(g_side + (blk >> 3)) ^ __ldcg(g_side + reader);
}

__device__ __forceinline__ uint32_t opaque_tid() { uint32_t t; asm volatile("mov.u32 %0, %%tid.x;" : "=r"(t)); return t; }
__device__ __forceinline__ void m_fetch(uint32_t sb, uint32_t src, uint32_t b, uint32_t mb) {
  bulk_load(sb + C_M + (b ? b * 4096 - 2048 : 0), (const unsigned char*)g_mimg + ((src ^ ((b & 1) * 4096)) + b * 8192), b ? 4096 : 2048, mb);
}
__device__ __forceinline__ uint32_t m_probe(uint32_t lane) { return lane * 32 + (lane & 4) * 4 + (lane >> 3) * 4; }
__device__ __forceinline__ uint32_t m_max(uint32_t a, uint32_t b) {
  return max(max(lds32(a), lds32(a + 1024)), max(lds32(b), lds32(b + 1024)));
}
template <int S0, int N> __device__ __forceinline__ void o_steps(float* d, const uint32_t* a) {
  constexpr int SD = o_ks(S0) != 0;
  if constexpr (o_reg(S0)) wg_rs16<SD>(d, a + (18 + o_slot(S0)) * 4, desc_n16(C_OI + o_ks(S0) * 512));
  else wg_ss16<SD>(d, desc_sw128(C_W + (18 + o_slot(S0)) * 2048), desc_n16(C_OI + o_ks(S0) * 512));
  if constexpr (N > 1) o_steps<S0 + 1, N - 1>(d, a);
}
template <int BASE, int KS, int N> __device__ __forceinline__ void m_steps(float* d, const uint32_t* a, uint32_t oa) {
  wg_rs16<KS != 0>(d, a + (BASE + KS / 2) * 4, desc_m(C_M + KS * 512));
  if constexpr (KS >= 36 - 2 * XR) wg_rs16<1>(d, a + (18 + XR + KS / 2) * 4, desc_m(C_M + KS * 512 + 512));
  else wg_ss16o<1, desc_sw128(C_W + (BASE + KS / 2) * 2048), desc_m(C_M + KS * 512 + 512)>(d, oa, 0);
  if constexpr (N > 2) m_steps<BASE, KS + 2, N - 2>(d, a, oa);
}

constexpr uint32_t VPAT = 0x15bbd249u;
template <int I, int R, int S> __device__ __forceinline__ void v_steps(float* d, const uint32_t* a) {
  constexpr bool reg = (VPAT >> I) & 1;
  if constexpr (reg) wg_rs16<1>(d, a + (18 + R) * 4, desc_m(C_M + R * 1024));
  else wg_ss16<1>(d, desc_sw128(C_W + (54 + S) * 2048), desc_m(C_M + S * 1024 + 512));
  if constexpr (I < 31) v_steps<I + 1, R + reg, S + !reg>(d, a);
  else static_assert(R + reg == 18, "pattern");
}

__device__ __forceinline__ void chain_proj(const Params& P, uint32_t sb) {
  const uint32_t c = chain_id(), h = c >> 1, j = c & 1, wid = __shfl_sync(~0u, threadIdx.x >> 5, 0), wg = wid >> 2, w = wid & 3;
  const uint32_t t = threadIdx.x & 127, lane = pinned(t & 31), mine = pinned(sb + t * 16), rb = mapa(sb, j ^ 1);
  const uint32_t theirs = pinned(rb + C_KM2 + w * 512 + lane * 4), oa = wg * 4608;
  uint32_t a[144 + 4 * XR];
  mbar_wait(sb + W_BAR + wg * 8, 0);
  if (threadIdx.x == 0) TS(23);
  load_frags<36>(a, sb + C_W + wg * 73728);
  fence_async_smem();
  bar_arrive(B_WG0 + wg, 256);
  if (threadIdx.x == 0) TS(24);
  bar_sync(B_WG2, 384);
  const uint32_t round = min(w, 2u) + (wg ? 0 : 3), gdly = P.dly[8 + round], ps = t >> 2, pf = j * 16 + (ps >> 1);
  uint4* const dsts = pinned(g_xb + (ps * 4096 + near_half(ps * 8, ps * 2) * 256 + c * 4 + (t & 3)));
  uint4* const dstf = pinned(g_xb + (pf * 4096 + 512 + near_half(pf * 8 + 1, pf * 2) * 256 + h * 8 + (t & 7)));
  const uint32_t* const gsrc = (const uint32_t*)g_xb + (h * 16384 + min(w, 2u) * 4096 + near_half(h * 8 + !wg, h * 2) * 1024 +
                               (wg ? lane * 4 + j * 2 : 2048 + (lane & 24) * 4 + j * 16 + (lane & 7) * 2));
  uint32_t* gdst = g_mimg + (16384 + (lane >> 4) * 1024 +
                   (wg ? (round ? 1536 + round * 512 : 0) + c * 8 + (((lane >> 1) ^ c) & 4) + (lane & 3)
                       : (round - 1) * 2048 + c * 16 + (lane & 1) * 8 + (((lane >> 1) ^ (c * 2)) & 4) + ((lane >> 1) & 3)));
  const uint32_t m0 = __ldcg(gdst - 16384);
  mbar_wait(sb + W_BAR + wg * 8, 1);
  load_frags<XR>(a + 144, sb + C_W + wg * 73728 + (18 - XR) * 2048);
  bar_sync(B_INIT, 256);
  if ((threadIdx.x & 127) == 0) TS(4);

  uint32_t ring = 1;
#pragma unroll 1
  for (int n = 0; n < STEPS; n++) {
    float d[8], e[8];
    if (n + 1 == STEPS && !wg) { bar_arrive(B_QK, 416); break; }
#pragma unroll
    for (int i = 0; i < 8; i++) e[i] = 0.f;
    uint32_t redo = n + 1;
#pragma unroll 1
    do {
      mbar_wait(sb + CB_M, n & 1);
      wg_fence();
      m_steps<0, 0, 4>(d, a, oa);
      wg_commit();
      if (wg) { wg_fence(); m_steps<18, 0, 4>(e, a, 4608); wg_commit(); }
      if (wid == 0) TR(8);
      mbar_wait(sb + CB_M + 8, n & 1);
      wg_fence();
      m_steps<0, 4, 8>(d, a, oa);
      wg_commit();
      mbar_wait(sb + CB_MV, n & 1);
      asm volatile("{.reg .pred p; .reg .u32 t; ld.shared.u32 t, [%1]; setp.eq.u32 p, t, %0; selp.u32 %0, -1, 0, p;}" : "+r"(redo) : "r"(sb + C_BAD) : "memory");
    } while (redo);
    wg_fence();
    m_steps<0, 12, 8>(d, a, oa);
    wg_commit();
    mbar_wait(sb + CB_MV + 16, n & 1);
    wg_fence();
    m_steps<0, 20, 8>(d, a, oa);
    wg_commit();
    mbar_wait(sb + CB_MV + 24, n & 1);
    wg_fence();
    m_steps<0, 28, 8>(d, a, oa);
    wg_commit();
    wg_wait<0>();
    if (w == 0) TR(6 + wg);
    const uint32_t f0 = pack2(d[0], d[1]), f1 = pack2(d[4], d[5]), f2 = pack2(d[2], d[3]), f3 = pack2(d[6], d[7]);
    stsm4(mine + C_QM + wg * 2048, f0, f1, f2, f3);
    bar_arrive(B_QK, 416);
    const uint32_t tag = (n & 1) ^ 1;
    if (n == 0) mbar_wait(sb + T_BAR, 0);
    if (wg) {
      if (n + 1 < STEPS) bar_sync(B_S, 256);
      wg_fence();
      v_steps<0, 2, 2>(e, a);
      wg_commit();
      const uint32_t k0 = j ? f0 : f1, k1 = j ? f2 : f3;
      mbar_wait(sb + CB_SX, n & 1);
      wg_wait<0>();
      if (w == 0) TR(11);
      const uint32_t v0 = pack2(e[0], e[1]), v1 = pack2(e[4], e[5]), v2 = pack2(e[2], e[3]), v3 = pack2(e[6], e[7]);
      stsm4(mine + C_VM, v0, v1, v2, v3);
      bar_arrive(B_V, 256);
      st_async1(theirs, k0, rb + CB_XX);
      st_async1(theirs + 256, k1, rb + CB_XX);
      st_async1(theirs + 128, j ? v0 : v1, rb + CB_XX);
      st_async1(theirs + 384, j ? v2 : v3, rb + CB_XX);
      if (n + 1 == STEPS) break;
      bar_sync(B_O, 256);
      fence_async_smem();
      wg_fence();
#pragma unroll
      for (int ks = 0; ks < 4; ks++) {
        if (ks == 0) wg_ss16<0>(d, desc_sw128(C_W + 32 * 2048), desc_n16(C_OI));
        else wg_ss16<1>(d, desc_sw128(C_W + (32 + ks) * 2048), desc_n16(C_OI + ks * 512));
      }
      wg_commit();
      bar_arrive(B_X, 256);
      if (w == 0) TR(0);
      wg_wait<0>();
      store_partial(dsts, pack_partial(d, tag));
      bar_arrive(B_M, 160);
      if (w == 0) TR(1);
    } else {
      bar_sync(B_X, 256);
      wg_fence();
      o_steps<0, 4>(d, a);
      wg_commit();
      o_steps<4, 4>(e, a);
      wg_commit();
      wg_wait<1>();
      store_partial(dsts + 1024, pack_partial(d, tag));
      if (w == 0) TR(2);
      wg_wait<0>();
      store_partial(dsts + 2048, pack_partial(e, tag));
      if (w == 0) TR(3);
      wg_fence();
      o_steps<8, 4>(d, a);
      wg_commit();
      bar_sync(B_T, 256);
      if (w == 0) { TRV(61, 0); TR(12); }
      wg_fence();
      o_steps<12, 4>(d, a);
      wg_commit();
      o_steps<16, 8>(e, a);
      wg_commit();
      wg_wait<1>();
      store_partial(dstf, pack_partial(d, tag));
      if (w == 0) TR(4);
      wg_fence();
      o_steps<24, 8>(d, a);
      wg_commit();
      wg_wait<1>();
      store_partial(dstf + 1024, pack_partial(e, tag));
      bar_arrive(B_OE, 256);
      if (w == 0) TR(5);
      wg_wait<0>();
      store_partial(dstf + 2048, pack_partial(d, tag));
      if (w == 0) TR(15);
    }
    if (w < 3) {
      mbar_wait(sb + CB_REF, n & 1);
      wait_until(lds32(sb + C_REF), gdly);
      gather_reduce(gsrc, gdst, m0, wg, tag, lane, sb, n, 16 + round * 4);
      if (++ring == MRING) { ring = 0; gdst -= MRING * 16384; }
      gdst += 16384;
    }
  }
}

template <int KS> __device__ __forceinline__ void x_scores(float* s, float* sm, const uint4* q, uint32_t ok, uint32_t om) {
  wg_rs32o<1, desc_sw64(C_KV + KS * 1024)>(s, q[KS].x, q[KS].y, q[KS].z, q[KS].w, ok);
  wg_rs8o<1, desc_n16(C_KM + KS * 512)>(sm, q[KS].x, q[KS].y, q[KS].z, q[KS].w, om);
  if constexpr (KS < 3) x_scores<KS + 1>(s, sm, q, ok, om);
}

__device__ __forceinline__ void chain_attn(const Params& P, uint32_t sb) {
  const int c = chain_id(), j = c & 1;
  const int tid = threadIdx.x, lane = tid & 31, w = __shfl_sync(~0u, (tid >> 5) & 3, 0);
  const int l = w >> 1, u = w & 1;
  const uint32_t rb = mapa(sb, j ^ 1);
  const float sc = 0.08838834764831845f * 1.4426950408889634f;
  const uint32_t ones = 0x3F803F80u;
  const uint32_t km_off = C_KM + (lane >> 3) * 256 + l * 128 + (lane & 7) * 16;
  const uint32_t qm_off = C_QM + (lane >> 4) * 256 + l * 128 + (lane & 7) * 16;
  const uint32_t kv_off = C_KV + l * 4096 + (lane & 15) * 64 + (((lane >> 4) ^ (u * 2) ^ ((lane >> 1) & 3)) << 4);

  load_wg<CHAIN, true>(P, sb, false, 1, w);
  if (lane == 0) mbar_arrive(sb + CB_M);
#pragma unroll 1
  for (int n = 0; n < STEPS; n++) {
    const uint32_t kvb = sb + kv_off + (n & 1) * 16384;
    if (w == 0 && elect()) { mbar_expect(sb + CB_SX, 2560); mbar_expect(sb + CB_OX, 2048); mbar_expect(sb + CB_XX, 2048); }
    mbar_wait(sb + CB_FULL + (n & 1) * 8, (n >> 1) & 1);
    if (n < 3 && tid == 256) TS(n ? 20 + n : 5);
    __syncwarp();
    {
      uint32_t km[8];
      uint4 kx[8];
#pragma unroll
      for (int i = 0; i < 8; i++) ldsm4t(kx[i].x, kx[i].y, kx[i].z, kx[i].w, (kvb ^ ((i & 1) * 32)) + (i >> 1) * 1024);
      mbar_wait(sb + CB_VF, n & 1);
      if (w == 1) TRD(60, kx[7].x);
      bar_sync(B_QK, 416);
      if (n + 1 == STEPS) {
        st_async4(rb + C_SX + (tid & 127) * 16, 0.f, 0.f, 0.f, 0.f, rb + CB_SX);
        st_async1(rb + C_SX + 2048 + (tid & 127) * 4, 0, rb + CB_SX);
        bar_sync(B_V, 256);
      } else {
      uint32_t qm[16];
#pragma unroll
      for (int ks = 0; ks < 4; ks++) ldsm4t(qm[4 * ks], qm[4 * ks + 1], qm[4 * ks + 2], qm[4 * ks + 3], sb + qm_off + ks * 512);
      ldsm4t(km[0], km[1], km[2], km[3], sb + km_off);
      ldsm4t(km[4], km[5], km[6], km[7], sb + km_off + 1024);
      float s[5][4];
      uint4 vx[4];
#pragma unroll
      for (int i = 0; i < 5; i++) { s[i][0] = s[i][1] = s[i][2] = s[i][3] = 0.f; }
#pragma unroll
      for (int ks = 0; ks < 4; ks++) {
        const uint32_t* q = qm + 4 * ks;
        if (ks == 1 || ks == 2) {
#pragma unroll
          for (int i = 2 * ks - 2; i < 2 * ks; i++) ldsm4(vx[i].x, vx[i].y, vx[i].z, vx[i].w, ((sb + kv_off) ^ ((i & 1) * 32)) + 8192 + (2 * u + (i >> 1)) * 1024);
        }
        mma16(s[1], q[0], q[1], q[2], q[3], kx[2 * ks].x, kx[2 * ks].y);
        mma16(s[2], q[0], q[1], q[2], q[3], kx[2 * ks].z, kx[2 * ks].w);
        mma16(s[0], q[0], q[1], q[2], q[3], km[2 * ks], km[2 * ks + 1]);
        mma16(s[3], q[0], q[1], q[2], q[3], kx[2 * ks + 1].x, kx[2 * ks + 1].y);
        mma16(s[4], q[0], q[1], q[2], q[3], kx[2 * ks + 1].z, kx[2 * ks + 1].w);
      }
      const uint32_t sx = C_SX + l * 1280;
      st_async4(rb + sx + u * 512 + lane * 16, s[1][0], s[1][1], s[2][0], s[2][1], rb + CB_SX);
      st_async1(rb + sx + 1024 + u * 128 + lane * 4, __float_as_uint(u ? s[0][1] : s[0][0]), rb + CB_SX);
      bar_arrive_after<B_S, 256>(__float_as_uint(s[3][0]), __float_as_uint(s[4][0]));
      mbar_wait(sb + CB_SX, n & 1);
      const uint4 p0 = lds128(sb + sx + u * 512 + lane * 16), p1 = lds128(sb + sx + (u ^ 1) * 512 + lane * 16);
      const uint2 p2 = make_uint2(lds32(sb + sx + 1024 + lane * 4), lds32(sb + sx + 1152 + lane * 4));
      float t[10] = {s[0][0] + __uint_as_float(p2.x), s[0][1] + __uint_as_float(p2.y),
                     s[1][0] + __uint_as_float(p0.x), s[1][1] + __uint_as_float(p0.y),
                     s[2][0] + __uint_as_float(p0.z), s[2][1] + __uint_as_float(p0.w),
                     s[3][0] + __uint_as_float(p1.x), s[3][1] + __uint_as_float(p1.y),
                     s[4][0] + __uint_as_float(p1.z), s[4][1] + __uint_as_float(p1.w)};
      float mx = fmaxf(fmaxf(fmaxf(fmaxf(t[2], t[3]), fmaxf(t[4], t[5])), fmaxf(fmaxf(t[6], t[7]), fmaxf(t[8], t[9]))), fmaxf(t[0], t[1]));
      mx = fmaxf(fmaxf(mx, __shfl_xor_sync(~0u, mx, 1)), fmaxf(__shfl_xor_sync(~0u, mx, 2), __shfl_xor_sync(~0u, mx, 3)));
      const float ms = -mx * sc;
#pragma unroll
      for (int i = 0; i < 10; i++) t[i] = ex2(fmaf(t[i], sc, ms));
      uint32_t p[5];
#pragma unroll
      for (int i = 0; i < 5; i++) p[i] = pack2(t[2 * i], t[2 * i + 1]);
      p[1] |= (p[0] & p[3] & p[4]) & 0x80008000u;
      float o[2][4], z[4] = {0.f, 0.f, 0.f, 0.f};
      mma16(z, ones, ones, ones, ones, p[1], p[2]);
#pragma unroll
      for (int i = 0; i < 2; i++) {
        o[i][0] = o[i][1] = o[i][2] = o[i][3] = 0.f;
        mma16(o[i], vx[2 * i].x, vx[2 * i].y, vx[2 * i].z, vx[2 * i].w, p[1], p[2]);
      }
      mma16(z, ones, ones, ones, ones, p[3], p[4]);
#pragma unroll
      for (int i = 0; i < 2; i++) mma16(o[i], vx[2 * i + 1].x, vx[2 * i + 1].y, vx[2 * i + 1].z, vx[2 * i + 1].w, p[3], p[4]);
      mma8(z, ones, ones, p[0]);
      bar_sync_after<B_V, 256>(p[1]);
      ldsm4(km[0], km[1], km[2], km[3], sb + km_off + (C_VM - C_KM) + u * 1024);
      mma8(o[0], km[0], km[1], p[0]);
      mma8(o[1], km[2], km[3], p[0]);
      const float i0 = rcp(z[0]), i1 = rcp(z[1]);
      const uint32_t oo = C_OI + u * 1024 + l * 128 + lane * 4;
      uint32_t ow[4];
#pragma unroll
      for (int i = 0; i < 2; i++) { ow[2 * i] = pack2(o[i][0] * i0, o[i][1] * i1); ow[2 * i + 1] = pack2(o[i][2] * i0, o[i][3] * i1); }
      stsm4(sb + C_OI + u * 1024 + l * 128 + (lane >> 3) * 256 + (lane & 7) * 16, ow[0], ow[1], ow[2], ow[3]);
      bar_arrive(B_O, 256);
#pragma unroll
      for (int i = 0; i < 4; i++) st_async1(rb + oo + 2048 + i * 256, ow[i], rb + CB_OX);
      }
    }
    {
      const uint32_t lane = opaque_tid() & 31, own = ((n & 1) * 16384 + j * 4096) >> 4;
      float s[16], sm[4];
#pragma unroll
      for (int i = 0; i < 16; i++) s[i] = sm[i & 3] = 0.f;
      {
        uint4 q[4];
        mbar_wait(sb + CB_Q, n & 1);
#pragma unroll
        for (int ks = 0; ks < 4; ks++) q[ks] = lds128(sb + C_Q + (ks >> 1) * 4096 + w * 1024 + (ks & 1) * 512 + lane * 16);
        mbar_wait(sb + CB_XX, n & 1);
        if (n + 1 < STEPS) mbar_wait(sb + CB_OX, n & 1);
        fence_async_smem();
        if (n + 1 < STEPS) { bar_arrive(B_T, 256); bar_sync(B_OE, 256); }
        if (w == 1) { TRV(61, 0); TR(9); }
#pragma unroll 1
        for (uint32_t hf = 0; hf < 2; hf++) {
          wg_fence();
          x_scores<0>(s, sm, q, hf ? (C_KV2 - C_KV) >> 4 : own, hf ? (C_KM2 - C_KM) >> 4 : j * 8);
          wg_commit();
          wg_wait<0>();
#pragma unroll
          for (int ks = 0; ks < 4; ks++) asm volatile("mov.b32 %0, %1; mov.b32 %2, %3;" : "+r"(q[ks].x), "+r"(q[ks].y), "+r"(q[ks].z), "+r"(q[ks].w));
        }
      }
      const float neg = -1e9f * 11.313708498984761f;
      const int lim = 8 * (w - (int)(lane & 3)) + (int)(lane >> 2);
      float t[10] = {sm[0], sm[1]};
#pragma unroll
      for (int i = 0; i < 8; i++) t[2 + i] = i > lim ? neg : s[(i >> 1) * 4 + (i & 1)];
      float mx = fmaxf(fmaxf(fmaxf(fmaxf(t[2], t[3]), fmaxf(t[4], t[5])), fmaxf(fmaxf(t[6], t[7]), fmaxf(t[8], t[9]))), fmaxf(t[0], t[1]));
      mx = fmaxf(fmaxf(mx, __shfl_xor_sync(~0u, mx, 1)), fmaxf(__shfl_xor_sync(~0u, mx, 2), __shfl_xor_sync(~0u, mx, 3)));
      const float ms = -mx * sc;
#pragma unroll
      for (int i = 0; i < 10; i++) t[i] = ex2(fmaf(t[i], sc, ms));
      uint32_t p[5];
#pragma unroll
      for (int i = 0; i < 5; i++) p[i] = pack2(t[2 * i], t[2 * i + 1]);
      float z = ((t[0] + t[1]) + (t[2] + t[3])) + ((t[4] + t[5]) + (t[6] + t[7])) + (t[8] + t[9]);
      const uint32_t row = sb + C_OS + w * 1024 + (lane >> 2) * 128 + (((lane & 3) ^ (lane >> 2)) << 4);
#pragma unroll 1
      for (uint32_t hf = 0; hf < 2; hf++) {
        float o[32];
        const uint32_t vo = hf ? (C_KV2 + 4096 - C_KV - 8192) >> 4 : j * 256;
        wg_fence();
        wg_rs64o<0, desc_sw64(C_KV + 8192)>(o, p[1], p[1], p[2], p[2], vo);
        wg_rs64o<1, desc_sw64(C_KV + 8192 + 32)>(o, p[3], p[3], p[4], p[4], vo);
        wg_rs64o<1, mkdesc(C_VM, 128, 256, 0)>(o, p[0], p[0], 0, 0, hf ? (C_VM2 - C_VM) >> 4 : j * 8);
        wg_commit();
        if (hf) {
          if (elect()) mbar_arrive(sb + CB_M);
        } else {
          z += __shfl_xor_sync(~0u, z, 1);
          z = rcp(z + __shfl_xor_sync(~0u, z, 2));
        }
        wg_wait<0>();
#pragma unroll
        for (int qq = 0; qq < 2; qq++) {
          const float* r = o + 16 * qq;
          sts128((row ^ (qq * 64)) + hf * 4096,
                 make_uint4(pack2(r[0] * z, r[1] * z), pack2(r[4] * z, r[5] * z), pack2(r[8] * z, r[9] * z), pack2(r[12] * z, r[13] * z)));
        }
      }
      bar_arrive(B_G, 160);
      if (n + 1 < STEPS) bar_arrive(B_R, 160);
      if (w == 1) TR(10);
    }
  }
  if ((threadIdx.x & 127) == 0) TS(6);
}

__device__ __forceinline__ void chain_aux(const Params& P, uint32_t sb) {
  const uint32_t c = chain_id(), j = c & 1, lane = threadIdx.x & 31, w = __shfl_sync(~0u, (threadIdx.x >> 5) & 3, 0);
  load_wg<CHAIN, true>(P, sb, false, 0, w);
  if (threadIdx.x == 384) TS(25);
  if (threadIdx.x == 384) grid_wait(1, lds32(sb + S_GEN));
  bar_sync(B_WG2, 384);
  if (threadIdx.x == 384) TS(13);
  if (w == 0) {
    const uint32_t* fg = g_fl + FL_G + near_half(XB_F, c) * 1024 + (c >> 1) * 8;
#pragma unroll 1
    for (int n = 0; n < STEPS; n++) {
      const unsigned char* blk = g_qkv + (uint32_t)((n % QRING) * (N_CHAIN * 24576));
      const uint32_t t1 = clk(), kb = sb + CB_FULL + (n & 1) * 8, kv = sb + C_KV + (n & 1) * 16384;
      uint32_t t0 = t1 - 100000, x = 0;
      if (n > 0) {
        wait_until(t1, KMIN);
        do asm volatile("ld.relaxed.gpu.global.u32 %0, [%1];" : "=r"(x) : "l"(fg) : "memory"); while (x <= n && clk() - t1 < KWIN);
        if (x > n) {
          asm volatile("fence.acquire.gpu;" ::: "memory");
          fence_async_global();
          if (elect()) { mbar_expect(kb, 8192); bulk_load(kv, blk + c * 24576, 8192, kb); }
        }
        T3(0); CNT(12, 1 + (x <= n));
        mbar_wait(sb + CB_REF, (n - 1) & 1);
        t0 = lds32(sb + C_REF);
        wait_until(t0, DLYK - 500);
      }
      wait_flags(fg + min(lane, 2u) * 256, n + 1);
      T3(2);
      fence_async_global();
      if (n > 0) bar_sync(B_R, 160);
      wait_until(t0, DLYK);
      if (elect()) {
        if (x <= n) { mbar_expect(kb, 8192); bulk_load(kv, blk + c * 24576, 8192, kb); }
        mbar_expect(sb + CB_VF, 8192);
        bulk_load(sb + C_KV + 8192, blk + (c * 24576 + 8192), 8192, sb + CB_VF);
        mbar_expect(sb + CB_Q, 16384);
        bulk_load(sb + C_Q, blk + (c * 24576 + 16384), 8192, sb + CB_Q);
        bulk_load(sb + C_KV2, blk + ((c ^ 1) * 24576 + j * 4096), 4096, sb + CB_Q);
        bulk_load(sb + C_KV2 + 4096, blk + ((c ^ 1) * 24576 + 8192 + j * 4096), 4096, sb + CB_Q);
      }
      T3(1);
      T3(3);
    }
  } else {
    const uint32_t near = __ballot_sync(~0u, near_half(XB_M + min(lane, MRING - 1u) * 8, c));
    uint32_t ring = 0;
    if (w > 1) {
      const uint32_t odd = w & 1, chk = pinned(sb + C_M + odd * 2048 + m_probe(lane)), again = sb + CB_MV + 32 + odd * 8;
      const bool one = elect();
      uint32_t mph = 0;
#pragma unroll 1
      for (int n = 0; n <= STEPS; n++) {
#pragma unroll
        for (int k = 0; k < 3; k++) {
          if (n == STEPS || (k == 2 && odd)) break;
          const uint32_t b = 2 * k + odd, at = chk + (k ? k * 8192 - 2048 + odd * 2048 : 0);
          uint32_t mb = sb + CB_M + b * 8, ph = n & 1;
          int it = 1;
          while (true) {
            mbar_wait(mb, ph);
            const bool bad = __any_sync(~0u, m_max(at, b ? at + 2048 : at) == SENT);
            if (one && !bad) mbar_arrive(sb + CB_MV + (b > 2 ? b * 8 - 8 : 0));
            if (!bad) break;
            mb = again; ph = mph; mph ^= 1;
            if (one) {
              if (k == 0) sts32(sb + C_BAD, n + 1);
              mbar_expect(mb, b ? 4096 : 2048);
              m_fetch(sb, ring * 65536 + ((near >> ring) & 1) * 4096, b, mb);
            }
            __syncwarp();
            spin_guard(it);
          }
          TR(41 + b * 4); CNT(6 + b, it);
        }
        ring = ring + 1 == MRING ? 0 : ring + 1;
        if (!odd) {
          if (n < STEPS) { TRSYNC(); TRDUMP(n - 2); }
        } else {
          unsigned char* o = g_oimg + (uint32_t)(((n - 1) & (RING - 1)) * (N_CHAIN * 8192) + j * 4096);
          if (n > 0) bar_sync(B_G, 160);
          fence_async_smem();
          if (one) {
            if (n > 0) {
              bulk_store(o + c * 8192, sb + C_OS, 4096);
              bulk_store(o + (c ^ 1) * 8192, sb + C_OS + 4096, 4096);
              asm volatile("cp.async.bulk.commit_group;\ncp.async.bulk.wait_group.read 0;" ::: "memory");
              { const int n_ = n - 1; { const int n = n_; T3(4); (void)n; } }
            }
            mbar_arrive(sb + CB_Q);
            if (n > 0) {
              bulk_done_inc(g_fl + FL_O + c);
              { const int n_ = n - 1; { const int n = n_; T3(5); (void)n; } }
            }
          }
          __syncwarp();
        }
      }
    } else {
      const uint32_t* ts = g_fl + FL_SYNC + near_half(XB_F + 1, c) * 1024 + lane * 2;
      uint32_t t0 = clk() - 100000, last = 0;
      int lag = 0;
#pragma unroll 1
      for (int n = 0; n < STEPS; n++) {
        const uint32_t src = ring * 65536 + ((near >> ring) & 1) * 4096;
        if (lane < 5) mbar_expect(sb + CB_M + lane * 8, lane ? 4096 : 2048);
        __syncwarp();
        if (elect()) {
#pragma unroll
          for (int b = 0; b < 5; b++) {
            wait_until(t0, P.dly[14 + b]);
            m_fetch(sb, src, b, sb + CB_M + b * 8);
            TR(40 + b * 4);
          }
        }
        __syncwarp();
        ring = ring + 1 == MRING ? 0 : ring + 1;
        uint32_t va, vb;
        const uint32_t off = timer_offset(), tag = (uint32_t)(n + 1) << 28;
        if (n > 1) lag += (int)(off - last) - (lag >> 2);
        last = off;
        const uint32_t mine = min(max((lag >> 3) + 256, 0), 511);
        bar_sync(B_QK, 416);
        if (n + 1 == STEPS) break;
        sts32(sb + C_REF + 4, 0);
        const uint32_t c0 = clk(), stamp = c0 + off;
        st_relaxed_if(g_fl + FL_SYNC + lane * 1024 + c, tag | (mine << 19) | (stamp & 0x7FFFF), lane < 2);
        TR(13);
        wait_until(c0, DLYS);
        int it = 0;
        do {
          asm volatile("ld.relaxed.gpu.global.v2.u32 {%0,%1}, [%2];" : "=r"(va), "=r"(vb) : "l"(ts) : "memory");
          spin_guard(it);
        } while (__any_sync(~0u, ((va ^ tag) | (vb ^ tag)) >> 28));
        const int late = __reduce_max_sync(~0u, max((int)((va - stamp) << 13), (int)((vb - stamp) << 13))) >> 13;
        const uint32_t fast = min(((__reduce_max_sync(~0u, max(va, vb)) >> 19) & 511) - mine, 100u);
        t0 = c0 + min((uint32_t)late, clk() - c0);
        if (elect()) {
          sts32(sb + C_REF, t0 + (fast * 3 >> 2));
          mbar_arrive(sb + CB_REF);
        }
        st_relaxed_if(g_fl + FL_TICK + lane * 1024, (uint32_t)(n + 1) << 24 | ((t0 + off) & 0xFFFFFF), c == 0 && lane < 2);
        t0 += fast * 5 >> 2;
        TRV(59, fast);
        TR(14); CNT(11, it);
        bar_sync(B_M, 160);
      }
    }
  }
}

template <int WG>
__device__ __forceinline__ void g_math(const Params& P, uint32_t sb) {
  const int q = g_unit(WG);
  const int lane = threadIdx.x & 31, w = (threadIdx.x >> 5) & 3;
  const bool isq = q >= 64;
  uint32_t a[136];
  {
    const uint32_t stage = sb + G_W + WG * 73728;
    mbar_wait(sb + W_BAR + WG * 8, 0);
    if (threadIdx.x == 0) TS(23);
    load_frags<34>(a, stage);
    fence_async_smem();
    bar_sync(B_WG0 + WG, 128);
    if (threadIdx.x == 0) TS(24);
    load_wg<GROLE>(P, sb, false, WG, w);
    if (threadIdx.x == 0) TS(25);
    mbar_wait(sb + W_BAR + WG * 8, 1);
  }
  if ((threadIdx.x & 127) == 0) TS(4);
  const uint32_t off0 = (q & 31) * 49152 + (q >> 5) * 8192 +
                        (isq ? (w >> 1) * 4096 + (w & 1) * 512 + lane * 16 : w * 1024 + (lane >> 2) * 64 + (((lane ^ (lane >> 3)) & 3) << 4));
#pragma unroll 1
  for (int n = 0; n < STEPS; n++) {
    float d0[32], d1[32];
    if (WG == 0 && n >= LOCK0) bar_sync(B_OE, 160);
    if (n > 0) bar_sync(B_V + WG, 256);
#pragma unroll
    for (int ch = 0; ch < 9; ch++) {
      mbar_wait(sb + G_BAR + ch * 8, n & 1);
      if (ch == 0) { if ((threadIdx.x & 127) == 0) T3(5 + WG * 3); __syncwarp(); }
      if (ch == 4) { if ((threadIdx.x & 127) == 0) T3(6 + WG * 3); __syncwarp(); }
      if (ch == 8 && (WG == 0 ? n > 0 : n + 1 < STEPS)) bar_arrive(B_V + (WG ^ 1), 256);
      wg_fence();
#pragma unroll
      for (int kk = 0; kk < 4; kk++) {
        const int i = ch * 4 + kk;
        float* d = i & 1 ? d1 : d0;
        const uint64_t db = desc_sw128(G_RING + ch * 8192 + (kk & 2) * 32);
        if (i < 2) wg_rs64<0>(d, a + i * 4, db);
        else if (i < 34) wg_rs64<1>(d, a + i * 4, db);
        else wg_ss64<1>(d, desc_sw128(G_W2 + WG * 4096 + (i - 34) * 2048), db);
        wg_ss64<1>(d, desc_sw128(G_W + WG * 73728 + i * 2048), db + 2);
      }
      wg_commit();
      if (ch > 0) { wg_wait<1>(); if (lane == 0) mbar_arrive(sb + G_BAR + 128 + (ch - 1) * 8); }
    }
    wg_wait<0>();
    if (lane == 0) mbar_arrive(sb + G_BAR + 128 + 8 * 8);
    if ((threadIdx.x & 127) == 0) T3(7 + WG * 3);
    __syncwarp();
    uint32_t tw = clk() + (n == 0 ? 0u - 100000u : WG ? 0u : DLYW);
    unsigned char* base = g_qkv + (size_t)(n & (QRING - 1)) * (N_CHAIN * 24576);
    if (isq) {
#pragma unroll
      for (int i = 0; i < 8; i++) {
        const float *d = (i < 4 ? d0 : d1) + 4 * i, *e = (i < 4 ? d1 : d0) + 4 * i;
        wait_until(tw, 0); tw += P.dly[2 + WG];
        *(uint4*)(base + off0 + (i >> 2) * 24576 + (i & 3) * 1024) =
          make_uint4(movmat(pack2(d[0], d[1])), movmat(pack2(e[0], e[1])), movmat(pack2(d[2], d[3])), movmat(pack2(e[2], e[3])));
      }
    } else {
#pragma unroll
      for (int i = 0; i < 8; i++) {
        const float* d = (i < 4 ? d0 : d1) + 8 * (i & 2) + 2 * (i & 1);
        wait_until(tw, 0); tw += P.dly[2 + WG];
        *(uint4*)(base + off0 + (i >> 2) * 24576 + (i & 2) * 2048 + (i & 1) * 512) =
          make_uint4(pack2(d[0], d[1]), pack2(d[4], d[5]), pack2(d[8], d[9]), pack2(d[12], d[13]));
      }
    }
    bar_sync(B_M + WG, 160);
  }
}

__device__ __forceinline__ void fill16(void* p, uint32_t v) {
  asm volatile("st.global.v4.u32 [%0], {%1,%1,%1,%1};" :: "l"(p), "r"(v) : "memory");
}
__device__ __forceinline__ void g_load(const Params& P, uint32_t sb) {
  const int lane = threadIdx.x & 31, w = __shfl_sync(~0u, (threadIdx.x >> 5) & 3, 0);
  if (w == 2) return;
  if (w < 2) { bar_sync(15, 192); fence_async_smem(); }
  uint32_t fl = 0;
#pragma unroll 1
  for (int n = w == 3 ? LOCK0 : 0; n < STEPS; n++) {
    if (w && n == LOCK0) { grid_wait(1, lds32(sb + S_GEN)); fl = near_half(XB_F, bid()) * 1024; }
    if (w == 3) {
      const uint32_t tag = (uint32_t)(n - LOCK0 + 1) << 24;
      uint32_t v; int it = 0;
      do { asm volatile("ld.relaxed.gpu.global.u32 %0, [%1];" : "=r"(v) : "l"(g_fl + fl + FL_TICK) : "memory"); spin_guard(it); } while (v < tag);
      const uint32_t off = timer_offset(), now = clk(), t0 = now - ((v ^ tag) >> 24 ? DLYG : (now + off - v) & 0xFFFFFF);
      asm volatile("fence.acquire.gpu;" ::: "memory");
      if (lane == 0) T3(11);
      __syncwarp();
      wait_until(t0, DLYG);
      if (lane == 0) T3(4);
      bar_sync(B_OE, 160);
      continue;
    }
    if (w == 0 || n == 0) {
      if (n < NSEG) wait_flags(g_lnflag + n * 16 + (lane & 1) * 8, 1);
    } else if (n >= LAG) {
      wait_flags(g_fl + fl + FL_F + (lane & 1) * 8, n - LAG + 1);
    }
    if (w) { if (lane == 0) T3(12); bar_sync(B_X, 96); }
    fence_async_global();
    const unsigned char* src = g_lnimg + (uint32_t)((w ? (n >= LAG ? NSEG + n - LAG : 0) : min(n, NSEG - 1)) * 36864);
#pragma unroll 1
    for (int ch = 0; ch < 9; ch++) {
      const uint32_t full = sb + G_BAR + ch * 8;
      mbar_wait(full + 128, (n & 1) ^ 1);
      if (elect()) {
        mbar_expect(full, 4096);
        bulk_load(sb + G_RING + ch * 8192 + w * 4096, src + ch * 4096, 4096, full);
      }
    }
  }
}

__device__ __forceinline__ void g_aux(const Params& P, uint32_t sb) {
  const int lane = threadIdx.x & 31, w = (threadIdx.x >> 5) & 3;
  if (w == 1 || w == 2) {
    const int q = g_unit(w - 1);
    uint32_t* f = g_fl + FL_G + q * 8;
#pragma unroll 1
    for (int n = 0; n < STEPS; n++) {
      const uint32_t ln = opaque_tid() & 31;
      uint4* z = (uint4*)g_oacc + (uint32_t)(((n + 1) % ARING) * (16 * DM) + q * 96 + ln);
      fill16(z, 0); fill16(z + 32, 0); fill16(z + 64, 0);
      if (n + 3 >= MRING && q < 80) fill16((uint4*)g_mimg + (uint32_t)(((n + 3) % MRING) * 4096 + q * 32 + ln), SENT);
      bar_sync(B_M + (w - 1), 160);
      if (lane == 0) { T3(w * 2 - 2); fence_async_global(); flag_release(f, n + 1); T3(w * 2 - 1); }
      __syncwarp();
    }
  } else {
    const uint32_t u = (bid() - N_CHAIN) * 2 + (w & 1), r = u / 36 * 16 + (u & 3) * 4 + (lane >> 3);
    uint32_t o = r * (DM / 8) + (u % 36 >> 2) * 8 + ((lane & 7) ^ ((r >> 1) & 3)), fl = 0;
#pragma unroll 1
    for (int k = -LAG - 1; k < STEPS; k++) {
      if (k < NSEG - 1) bar_sync(B_X, 96);
      if (k < LAG || u >= 72) continue;
      if (k == NSEG - 1) { fl = near_half(XB_F, bid()) * 1024; wait_flags(g_fl + fl + FL_F + (lane & 1) * 8, NSEG + 1); }
      const uint4 x = __ldcg((const uint4*)P.out + o);
      if (k >= NSEG - 1) wait_flags(g_fl + fl + FL_OCNT + (max(k, NSEG) % OCRING) * 8, N_O * 3 * (max(k, NSEG) / OCRING + 1));
      const float4* a = (const float4*)g_oacc + ((k % ARING) * (16 * DM) + 8 * DM + u * 64 + lane * 2);
      const float4 p = __ldcg(a), v = __ldcg(a + 1);
      ((uint4*)P.out)[o] = make_uint4(badd2(x.x, pack2(p.x, p.y)), badd2(x.y, pack2(p.z, p.w)), badd2(x.z, pack2(v.x, v.y)), badd2(x.w, pack2(v.z, v.w)));
      o += 4 * DM;
    }
    if ((threadIdx.x & 127) == 0) TS(7);
  }
}

template <int WG, bool HALF, int KS, int N> __device__ __forceinline__ void o_mma(float* d, const uint32_t* a, uint32_t ob) {
  constexpr uint64_t db = desc_sw128(O_RING + (KS >> 2) * 8192 + (KS & 3) * 32);
  constexpr uint64_t da = desc_sw128(O_W + WG * 40960 + (KS < 40 ? KS / 5 * 2 + KS % 5 / 2 : KS - 24) * 2048);
  if constexpr (KS < 40 && !(KS % 5 & 1)) {
    const uint32_t* r = a + (KS / 5 * 3 + KS % 5 / 2) * 4;
    if constexpr (HALF) wg_rs32k<KS != 0, db>(d, r[0], r[1], r[2], r[3], ob); else wg_rs64<KS != 0>(d, r, db);
  } else {
    if constexpr (HALF) wg_ss32k<da, db>(d, ob); else wg_ss64<1>(d, da, db);
  }
  if constexpr (N > 1) o_mma<WG, HALF, KS + 1, N - 1>(d, a, ob);
}
template <int WG, bool HALF, int GR> __device__ __forceinline__ void o_groups(float* d, const uint32_t* a, uint32_t sb, int n, bool more) {
  const uint32_t ob = n < NSEG ? 0 : 256;
  mbar_wait(sb + O_BAR + GR * 8, n & 1);
  if (GR == 0) { if ((threadIdx.x & 127) == 0) T3(13 + WG); __syncwarp(); }
  if (GR == (WG == 0 ? 2 : 4) && (WG < 2 || n + 1 < STEPS)) bar_arrive(B_V + (WG + 1) % 3, 256);
  wg_fence();
  o_mma<WG, HALF, GR * 8, 8>(d, a, ob);
  if (GR == 4 && more) o_mma<WG, HALF, 40, 4>(d, a, ob);
  wg_commit();
  if (GR > 0) { wg_wait<1>(); if ((threadIdx.x & 31) == 0) mbar_arrive(sb + O_BAR + 120 + GR * 8); }
  if constexpr (GR < 4) o_groups<WG, HALF, GR + 1>(d, a, sb, n, more);
}
template <int WG, bool HALF> __device__ __forceinline__ void o_step(const uint32_t* a, uint32_t sb, uint32_t st0, int n, bool more) {
  float d[HALF ? 16 : 32];
  if (WG > 0 || n > 0) bar_sync(B_V + WG, 256);
  o_groups<WG, HALF, 0>(d, a, sb, n, more);
  wg_wait<0>();
  if ((threadIdx.x & 31) == 0) mbar_arrive(sb + O_BAR + 128 + 4 * 8);
  if ((threadIdx.x & 127) == 0) T3(WG == 0 ? 1 : WG == 1 ? 8 : 12);
  __syncwarp();
#pragma unroll(HALF ? 1 : 2)
  for (int sl = 0; sl < 2; sl++) {
    mbar_wait(sb + OB_ST + WG * 16 + sl * 8, (n & 1) ^ (WG == 0));
    if (!HALF || sl == (n >= NSEG)) {
#pragma unroll
      for (int nb = 0; nb < 4; nb++) {
        const float* r = d + (HALF ? 0 : sl * 16) + nb * 4;
        const uint32_t ad = st0 + sl * 8192 + nb * 2048;
        sts32(ad, __float_as_uint(r[0]));
        sts32(ad + 256, __float_as_uint(r[1]));
        sts32(ad ^ 32, __float_as_uint(r[2]));
        sts32((ad ^ 32) + 256, __float_as_uint(r[3]));
      }
      fence_async_smem();
    }
    bar_arrive((sl ? B_G : B_M) + WG, 160);
  }
}
template <int WG>
__device__ __forceinline__ void o_math(const Params& P, uint32_t sb) {
  const bool more = bid() < N_CHAIN + N_G + 12;
  const int lane = threadIdx.x & 31, w = (threadIdx.x >> 5) & 3, g = lane >> 2, tq = lane & 3;
  uint32_t a[96];
  mbar_wait(sb + W_BAR + WG * 8, 0);
  load_frags<24>(a, sb + WG * 49152);
  fence_async_smem();
  bar_sync(B_INIT, 416);
  load_wg<OROLE>(P, sb, false, WG, w);
  mbar_wait(sb + W_BAR + WG * 8, 1);
  if ((threadIdx.x & 127) == 0) TS(4);
  const uint32_t st0 = sb + O_ST + tq * 512 + ((w * 16 + g) ^ (tq * 8)) * 4;
#pragma unroll 1
  for (int n = 0; n < STEPS; n++) {
    if (n < LAG || n >= NSEG) o_step<WG, true>(a, sb, st0, n, more); else o_step<WG, false>(a, sb, st0, n, more);
  }
}

__device__ __forceinline__ void o_aux(const Params& P, uint32_t sb) {
  const int i = bid() - N_CHAIN - N_G, ksl = i / 3;
  const int c0 = ksl * 11 - max(ksl - 4, 0), nc = ksl < 4 ? 11 : 10;
  const int lane = threadIdx.x & 31, w = __shfl_sync(~0u, (threadIdx.x >> 5) & 3, 0);
  if (w == 0) {
    bar_sync(B_INIT, 416);
    const uint32_t* f = g_fl + FL_O + near_half(XB_F + 1, bid()) * 1024 + min((c0 & ~1) + lane, (c0 + nc - 1) | 1);
#pragma unroll 1
    for (int n = 0; n < STEPS; n++) {
      const unsigned char* src = g_oimg + (uint32_t)(((n % RING) * N_CHAIN + c0) * 8192);
      wait_flags(f, n + 1);
      fence_async_global();
      if (lane == 0) T3(0);
#pragma unroll
      for (int gr = 0; gr < 5; gr++) {
        const uint32_t full = sb + O_BAR + gr * 8, bytes = (gr < 4 ? 2 : nc - 8) * 8192;
        mbar_wait(full + 128, (n & 1) ^ 1);
        if (elect()) {
          if (n < LAG || n >= NSEG) {
            mbar_expect(full, bytes >> 1);
            for (uint32_t o = gr * 16384 + (n < LAG ? 0 : 4096); o < gr * 16384 + bytes; o += 8192) bulk_load(sb + O_RING + o, src + o, 4096, full);
          } else {
            mbar_expect(full, bytes);
            bulk_load(sb + O_RING + gr * 16384, src + gr * 16384, bytes, full);
          }
        }
      }
    }
  } else {
#pragma unroll 1
    for (int n = 0; n < STEPS; n++) {
      float* dst = g_oacc + (uint32_t)((n % ARING) * (64 * DM) + ((i % 3) * 3 + (w - 1 + ksl) % 3) * 1024);
      const bool early = w == 3 && n < NSEG;
      bar_sync(B_M + (w - 1), 160);
      if (lane == 0) {
        T3(w * 2);
        if (n < NSEG) { bulk_reduce(dst, sb + O_ST, 4096); bulk_reduce(dst + 16 * DM, sb + O_ST + 4096, 4096); }
        asm volatile("cp.async.bulk.commit_group;" ::: "memory");
        if (early) {
          asm volatile("cp.async.bulk.wait_group.read 0;" ::: "memory");
          mbar_arrive(sb + OB_ST);
          T3(8 + w);
          bulk_done_inc(g_fl + FL_OCNT + (n % OCRING) * 8);
          T3(w * 2 + 1);
        }
      }
      __syncwarp();
      bar_sync(B_G + (w - 1), 160);
      if (lane == 0) {
        if (n >= LAG) { bulk_reduce(dst + 32 * DM, sb + O_ST + 8192, 4096); bulk_reduce(dst + 48 * DM, sb + O_ST + 12288, 4096); }
        asm volatile("cp.async.bulk.commit_group;\ncp.async.bulk.wait_group.read 1;" ::: "memory");
        if (!early) mbar_arrive(sb + OB_ST + (w % 3) * 16);
        asm volatile("cp.async.bulk.wait_group.read 0;" ::: "memory");
        mbar_arrive(sb + OB_ST + (w % 3) * 16 + 8);
        if (!early) {
          T3(8 + w);
          bulk_done_inc(g_fl + FL_OCNT + (n % OCRING) * 8);
          T3(w * 2 + 1);
        }
      }
      __syncwarp();
    }
  }
}

constexpr uint32_t Y_PITCH = 1168, Y_ROWS = 16 * Y_PITCH;
template <int R> __device__ __forceinline__ void y_rows(uint32_t* y, uint32_t src, uint32_t dst, int w, int bar) {
  const int lane = threadIdx.x & 31;
#pragma unroll
  for (int k = 0; k < 2 * R + 1; k++) {
    const int op = w + k * (16 / R);
    if (k == 2 * R && w >= 4) break;
    uint32_t a, b, c, d;
    ldsm4t(a, b, c, d, src + op * 512 + (lane & 16) * 16 + (lane & 7) * 32 + (lane & 8) * 2);
    stsm4(dst + (lane & 15) * Y_PITCH + op * 32 + (lane & 16), a, b, c, d);
  }
  bar_sync(bar, 512 / R);
  const uint32_t row = dst + ((w & 6) * 2 + (w >> 3) * 2 + (w & 1)) * Y_PITCH + lane * 4;
#pragma unroll
  for (int i = 0; i < 9 * R; i++) y[i] = lds32(row + i / 9 * 2 * Y_PITCH + i % 9 * 128);
}

__device__ __forceinline__ void f_role(const Params& P, uint32_t sb) {
  const int lane = threadIdx.x & 31, w = __shfl_sync(~0u, threadIdx.x >> 5, 0), r0 = (bid() - N_CHAIN - N_G - N_O) * 16;
  if (w == 8) {
    const uint32_t* fo = g_fl + FL_OCNT + near_half(XB_F, bid()) * 1024;
    fence_async_global();
#pragma unroll 1
    for (int n = 0; n < NSEG; n++) {
      bar_sync(2, 288);
      if (elect()) {
        mbar_expect(sb + F_BAR, 36864);
        bulk_load(sb + F_XY, P.X + (size_t)(n * 32 + r0) * DM, 18432, sb + F_BAR);
        bulk_load(sb + F_XY + 18432, g_yT + (size_t)(n * 32 + r0) * DM, 18432, sb + F_BAR);
        mbar_expect(sb + F_BAR + 8, 36864);
        T3(1);
      }
      wait_flags(fo + (n % OCRING) * 8, N_O * 3 * (n / OCRING + 1));
      fence_async_global();
      if (elect()) { bulk_load(sb + F_A, g_oacc + (uint32_t)((n % ARING) * (64 * DM) + r0 * DM), 36864, sb + F_BAR + 8); T3(0); }
    }
  } else if (w == 9) {
#pragma unroll 1
    for (int n = 0; n < NSEG; n++) {
      const uint32_t st = sb + (n & 1) * 36864;
      unsigned char* p = g_lnimg + (uint32_t)((NSEG + n) * 36864 + r0 * 128);
      bar_sync(1, 288);
      if (elect()) {
        T3(2);
#pragma unroll
        for (int i = 0; i < 9; i++) bulk_store(p + i * 4096, st + F_L + i * 2048, 2048);
        asm volatile("cp.async.bulk.commit_group;" ::: "memory");
        bulk_done_inc(g_fl + FL_F + (bid() & 1) * 8);
        T3(3);
        bulk_store(P.out + (size_t)(n * 32 + r0) * DM, st + F_X, 18432);
        asm volatile("cp.async.bulk.commit_group;\ncp.async.bulk.wait_group.read 0;" ::: "memory");
        if (n + 1 == NSEG) bulk_done_inc(g_fl + FL_F + (bid() & 1) * 8);
      }
      __syncwarp();
    }
  } else if (w < 8) {
    const uint32_t row = sb + w * 1152 + lane * 4, acc = sb + F_A + w * 256 + (lane ^ ((w & 6) * 2)) * 8;
    const uint32_t ln = sb + F_L + w * 128 + (((lane >> 2) ^ w) << 4) + (lane & 3) * 4;
#pragma unroll 1
    for (int n = -1; n < NSEG; n++) {
      const uint32_t st = (n & 1) * 36864;
      uint32_t x[18], y[18], l[18];
      if (n >= 0) mbar_wait(sb + F_BAR, n & 1);
#pragma unroll
      for (int i = 0; i < 18; i++) x[i] = lds32(row + F_XY + i / 9 * 9216 + i % 9 * 128);
      y_rows<2>(y, sb + F_XY + 18432, sb + F_Y, w, 3);
      layernorm9<2>(x, l);
#pragma unroll
      for (int i = 0; i < 18; i++) x[i] = badd2(x[i], bmul2(l[i], y[i]));
      if (n >= 0) mbar_wait(sb + F_BAR + 8, n & 1);
      if (threadIdx.x == 0 && n >= 0) T3(4);
      __syncwarp();
      uint2 a[18];
#pragma unroll
      for (int i = 0; i < 18; i++) a[i] = lds64(acc + i / 9 * 2048 + i % 9 * 4096);
#pragma unroll
      for (int i = 0; i < 18; i++) x[i] = badd2(x[i], pack2(__uint_as_float(a[i].x), __uint_as_float(a[i].y)));
      if (n + 1 < NSEG) bar_arrive(2, 288);
      layernorm9<2>(x, l);
#pragma unroll
      for (int i = 0; i < 18; i++) { x[i] = badd2(x[i], bmul2(l[i], y[i])); sts32(row + st + F_X + i / 9 * 9216 + i % 9 * 128, x[i]); }
      layernorm9<2>(x, l);
#pragma unroll
      for (int i = 0; i < 18; i++) sts32(ln + st + i / 9 * 1024 + i % 9 * 2048, l[i]);
      fence_async_smem();
      if (n >= 0) bar_sync(1, 288); else bar_sync(3, 256);
    }
  }
}

constexpr uint32_t P_CH = 147456, P_CHSZ = 12800, P_H = 4352;
static_assert(P_CH + 6 * P_CHSZ <= G_BAR, "prologue smem");

template <int N>
__device__ __forceinline__ void conv_fold(float (*acc)[4], bool hi, uint32_t mine, uint32_t theirs, int bar, int cnt) {
#pragma unroll
  for (int i = 0; i < N / 2; i++) {
    uint4 v;
    v.x = __float_as_uint(hi ? acc[i][0] : acc[i + N / 2][0]); v.y = __float_as_uint(hi ? acc[i][1] : acc[i + N / 2][1]);
    v.z = __float_as_uint(hi ? acc[i][2] : acc[i + N / 2][2]); v.w = __float_as_uint(hi ? acc[i][3] : acc[i + N / 2][3]);
    sts128(mine + i * 512, v);
  }
  bar_sync(bar, cnt);
#pragma unroll
  for (int i = 0; i < N / 2; i++) {
    const uint4 v = lds128(theirs + i * 512);
    acc[i][0] = (hi ? acc[i + N / 2][0] : acc[i][0]) + __uint_as_float(v.x); acc[i][1] = (hi ? acc[i + N / 2][1] : acc[i][1]) + __uint_as_float(v.y);
    acc[i][2] = (hi ? acc[i + N / 2][2] : acc[i][2]) + __uint_as_float(v.z); acc[i][3] = (hi ? acc[i + N / 2][3] : acc[i][3]) + __uint_as_float(v.w);
  }
}
template <int N>
__device__ __forceinline__ void conv_store(const float (*acc)[4], int tile0, uint32_t su, int d, uint32_t dd) {
  const int lane = threadIdx.x & 31, g = lane >> 2, tq = lane & 3;
#pragma unroll
  for (int i = 0; i < N; i++) {
    const uint32_t ad = su + (8 + (tile0 + i) * 8 + g) * 32 + tq * 4, sw = (g & 4) << 2;
    const uint32_t lo = badd2(movmat(pack2(acc[i][0], acc[i][1])), bmul2(lds32(ad + sw), dd));
    const uint32_t hi = badd2(movmat(pack2(acc[i][2], acc[i][3])), bmul2(lds32(ad + (sw ^ 16)), dd));
    ((uint2*)g_yT)[(((tile0 + i) * 8 + g) * DM + d) * 4 + tq] = make_uint2(lo, hi);
  }
}

__device__ __forceinline__ void prologue(const Params& P, uint32_t sb) {
  const int b = bid(), tid = threadIdx.x, lane = tid & 31, warp = tid >> 5, t0 = b * 16;
  const bool isg = b >= N_CHAIN && b < N_CHAIN + N_G;
  const int nch = isg ? 2 : b < 128 ? 6 : 0, chb = b < N_CHAIN ? b * 6 : isg ? b * 2 + 256 : b * 6 - 192;
  const uint32_t tstart = clk();
  if (tid < 288) {
    if (b < 128) {
      const int c = (tid >> 1) * 4, tt = t0 + (tid & 1) * 8;
      uint2 kr[11], vr[8];
#pragma unroll
      for (int i = 0; i < 11; i++) { const int t = tt + i - 3; kr[i] = t >= 0 ? __ldg((const uint2*)(P.K + (size_t)t * DM + c)) : make_uint2(0, 0); }
#pragma unroll
      for (int i = 0; i < 8; i++) vr[i] = __ldg((const uint2*)(P.V + (size_t)(tt + i) * DM + c));
#pragma unroll
      for (int e = 0; e < 2; e++) {
        const uint4 sh = __ldg((const uint4*)(P.shift + c * 4) + e);
        const uint32_t s0 = __byte_perm(sh.x, sh.z, 0x5410), s1 = __byte_perm(sh.x, sh.z, 0x7632);
        const uint32_t s2 = __byte_perm(sh.y, sh.w, 0x5410), s3 = __byte_perm(sh.y, sh.w, 0x7632);
        uint32_t v[8];
#pragma unroll
        for (int i = 0; i < 8; i++) {
          const uint32_t k3 = e ? kr[i].y : kr[i].x, k2 = e ? kr[i + 1].y : kr[i + 1].x, k1 = e ? kr[i + 2].y : kr[i + 2].x, k0 = e ? kr[i + 3].y : kr[i + 3].x;
          v[i] = bmul2(badd2(badd2(badd2(bmul2(k3, s3), bmul2(k2, s2)), bmul2(k1, s1)), bmul2(k0, s0)), e ? vr[i].y : vr[i].x);
        }
        *(uint4*)(g_kvT + (size_t)(c + 2 * e) * KVP + tt) =
          make_uint4(__byte_perm(v[0], v[1], 0x5410), __byte_perm(v[2], v[3], 0x5410), __byte_perm(v[4], v[5], 0x5410), __byte_perm(v[6], v[7], 0x5410));
        *(uint4*)(g_kvT + (size_t)(c + 2 * e + 1) * KVP + tt) =
          make_uint4(__byte_perm(v[0], v[1], 0x7632), __byte_perm(v[2], v[3], 0x7632), __byte_perm(v[4], v[5], 0x7632), __byte_perm(v[6], v[7], 0x7632));
      }
    }
  } else if (tid < 384) {
    const int t = tid - 288;
    for (int i = b * 96 + t; i < 16 * DM; i += N_CTA * 96) ((uint4*)g_oacc)[i] = make_uint4(0, 0, 0, 0);
    if (b * 96 + t < 128 * 8) g_lnflag[b * 96 + t] = 0;
    if (t == 95) sts32(sb + S_GEN, ld_acquire(g_gbar));
    __syncwarp();
    wait_until(tstart, PREFH);
    for (int i = t; i < 32 * nch; i += 96) asm volatile("prefetch.global.L2 [%0];" :: "l"(P.Hk + (size_t)chb * SEQ + i * 64));
  }
  if (warp < 12) {
    bar_arrive(10, 416);
    if (tid == 128) TS(14);
    const int ch = 5 - (warp >> 1), sub = warp & 1, d = chb + ch;
    const uint32_t su = sb + P_CH + ch * P_CHSZ;
    if (ch < nch) {
      const uint32_t* hs = (const uint32_t*)(P.Hk + (size_t)d * SEQ);
#pragma unroll
      for (int q = sub * 32 + lane; q < 256; q += 64) {
        const uint4 c = __ldg((const uint4*)hs + q);
        const uint32_t prev = q ? __ldg(hs + 4 * q - 1) : 0u;
        sts128(su + P_H + 32 + q * 16, make_uint4(__byte_perm(c.x, prev, 0x7610), __byte_perm(c.y, c.x, 0x7610), __byte_perm(c.z, c.y, 0x7610), __byte_perm(c.w, c.z, 0x7610)));
        sts128(su + P_H + 4224 + q * 16, make_uint4(__byte_perm(c.x, 0, 0x1032), __byte_perm(c.y, 0, 0x1032), __byte_perm(c.z, 0, 0x1032), __byte_perm(c.w, 0, 0x1032)));
      }
      if (sub == 1 && lane == 0) sts32(su + P_CHSZ - 16, __bfloat16_as_ushort(P.Dk[d]) * 0x10001u);
      if (sub == 0 && lane < 20) sts128(su + (lane < 16 ? lane * 16 : P_H + (lane & 2) * 2096 + (lane & 1) * 16), make_uint4(0, 0, 0, 0));
    }
    bar_sync(11, 416);
    if (ch < nch) {
#pragma unroll
      for (int q = sub * 32 + lane; q < 256; q += 64) {
        const int row = (q >> 1) + 8;
        sts128(su + row * 32 + (((q & 1) ^ ((row >> 2) & 1)) << 4), __ldcg((const uint4*)(g_kvT + (size_t)d * KVP) + q));
      }
    }
    const int g = lane >> 2, tq = lane & 3;
    const uint32_t sh = su + P_H + (g & 1) * 4192 + (8 + (g >> 1) - tq) * 4;
    float acc[16][4];
#pragma unroll
    for (int i = 0; i < 16; i++) { acc[i][0] = acc[i][1] = acc[i][2] = acc[i][3] = 0.f; }
    auto u_addr = [&](int res) {
      const int row = 8 - res + ((lane >> 4) << 3) + (lane & 7);
      return su + row * 32 + ((((lane >> 3) & 1) ^ ((row >> 2) & 1)) << 4);
    };
    if (ch < nch) {
      bar_sync(1 + ch, 64);
      if (tid == 352) TS(11);
      if (sub) {
#pragma unroll 4
        for (int res = 0; res < 8; res++) {
          uint32_t b0, b1, b2, b3;
          ldsm4(b0, b1, b2, b3, u_addr(res));
          const uint32_t r0 = lds32(sh + res * 32);
          mma16(acc[0], r0, lds32(sh + res * 32 + 16), lds32(sh + res * 32 - 16), r0, b0, b1);
        }
        conv_store<1>(acc, 0, su, d, lds32(su + P_CHSZ - 16));
      }
    }
    bar_arrive(12, 416);
    if (isg && warp < 8) { while ((int)(clk() - tstart - S1G) < 0) __nanosleep(200); load_wg<GROLE>(P, sb, true, warp >> 2, warp & 3); }
    if (ch < nch) {
#pragma unroll 1
      for (int res = sub * 4; res < sub * 4 + 4; res++) {
        uint32_t bf[16][2];
        const uint32_t ad = u_addr(res);
#pragma unroll
        for (int f = 0; f < 16; f += 2) ldsm4(bf[f][0], bf[f][1], bf[f + 1][0], bf[f + 1][1], ad + f * 256);
#pragma unroll
        for (int k = 0; k < 16; k++) {
          const int jj = k & 1 ? k >> 1 : 15 - (k >> 1);
          const uint32_t ah = sh + (8 * jj + res) * 32;
          const uint32_t r0 = lds32(ah), r1 = lds32(ah + 16), rm = lds32(ah - 16);
#pragma unroll
          for (int i = max(jj, 1); i < 16; i++) mma16(acc[i], r0, r1, rm, r0, bf[i - jj][0], bf[i - jj][1]);
        }
      }
      bar_sync(1 + ch, 64);
      if (tid == 352) TS(12);
      const uint32_t xb = su + P_H + lane * 16, dd = lds32(su + P_CHSZ - 16);
      conv_fold<16>(acc, sub, xb + sub * 4096, xb + (sub ^ 1) * 4096, 1 + ch, 64);
      conv_store<8>(acc, sub * 8, su, d, dd);
    }
  } else {
    for (int i = b; i < 194 + MRING * 5; i += N_CTA) {
      const int n = (i - 194) / 5, r = (i - 194) % 5, blk = i < 192 ? i / 6 * 8 + i % 6 : i < 194 ? XB_F + i - 192 : XB_M + n * 8 + r;
      const uint32_t fill = i < 194 ? 0u : SENT;
#pragma unroll 1
      for (int q = tid - 384; q < 256 && warp < 15; q += 96) {
        uint4 v = make_uint4(fill, fill, fill, fill);
        if (i >= 194 && n == 0 && (r > 0 || q < 128)) {
          const bf16* m = P.mem0 + (max(r * 8 - 4, 0) + (q >> 5)) * 16 + ((q >> 1) & 1) * 8 + ((q >> 2) & 7);
          v.x = pack2(__bfloat162float(m[0]), __bfloat162float(m[DM])); v.y = pack2(__bfloat162float(m[2 * DM]), __bfloat162float(m[3 * DM]));
          v.z = pack2(__bfloat162float(m[4 * DM]), __bfloat162float(m[5 * DM])); v.w = pack2(__bfloat162float(m[6 * DM]), __bfloat162float(m[7 * DM]));
        }
        g_xb[blk * 512 + q] = v;
        g_xb[blk * 512 + 256 + q] = v;
      }
    }
    if (tid < 388) g_xb[XB_REF * 512 + (tid & 2) * 128 + (b & ~1) + (tid & 1)] = make_uint4(0, 0, 0, 0);
    else if (tid < 392 && b < N_GRP) g_xb[(b * 8 + 7) * 512 + (tid & 2) * 128 + (tid & 1)] = make_uint4(0, 0, 0, 0);
    if (warp < 15) { bar_arrive(9, 128); bar_sync(7, 96); }
    if (tid == 384) TS(8);
    if (warp == 12) {
      const bf16* w = lane < 6 ? (lane % 3 == 0 ? P.Wk : lane % 3 == 1 ? P.Wv : P.Wq) + (((b >> 5) * 2 + lane / 3) * 32 + (b & 31)) * 2048
                               : (lane < 8 ? P.Wo + (lane - 6) * (9 * 131072) : P.X) + b * 2048;
      uint32_t t = tstart + PREF0;
      if ((int)(clk() - t) > 0) t = clk();
#pragma unroll 1
      for (int st = 0; st < 9 && b < N_CHAIN; st++) {
#pragma unroll 1
        for (int i = 0; i < 9; i++, t += PACE) {
          wait_until(t, 0);
          if (lane == st) asm volatile("cp.async.bulk.prefetch.L2.global [%0], 4096;" :: "l"(w + i * (lane < 6 ? 262144 : 131072)) : "memory");
        }
      }
      if (lane == 0) TS(10);
    } else if (warp == 15) {
      bar_sync(10, 416);
      if (lane == 0) { grid_arrive(0); if (nch) grid_wait(0, lds32(sb + S_GEN)); }
      __syncwarp();
      bar_arrive(11, 416);
      if (lane == 0) TS(1);
      bar_sync(9, 128);
      bar_sync(12, 416);
      if (lane == 0) { TS(16); grid_arrive(2); TS(17); }
    } else if (lane == 0) {
      if (warp == 13 || (warp == 14 && b < N_GRP)) {
        uint32_t* p = (uint32_t*)(g_xb + (warp == 13 ? XB_REF * 512 + b : (b * 8 + 7) * 512));
        int votes = 0;
        for (int rep = 0; rep < 24 && abs(votes) < 7; rep++) {
          uint32_t v0, v1, c0, c1;
          asm volatile("atom.relaxed.gpu.global.add.u32 %0, [%4], 1;\n atom.relaxed.gpu.global.add.u32 %1, [%5], 1;\n"
                       "{.reg .pred p; setp.eq.u32 p, %0, 0x7ffffff3; @p trap; mov.u32 %2, %%clock; setp.eq.u32 p, %1, 0x7ffffff3; @p trap; mov.u32 %3, %%clock;}"
                       : "=&r"(v0), "=&r"(v1), "=&r"(c0), "=&r"(c1) : "l"(p + (rep & 1) * 1024), "l"(p + ((rep & 1) ^ 1) * 1024) : "memory");
          votes += ((c1 - c0 > 80u) == (rep & 1)) ? 1 : -1;
        }
        if (warp == 13) { g_side[b] = votes > 0; TS(9); } else g_near[b] = votes > 0;
      }
    }
    __syncwarp();
    if (warp > 12 && b < N_CHAIN) {
      while ((int)(clk() - tstart - S1DLY) < 0) __nanosleep(200);
      for (int k = warp - 13; k < 8; k += 3) load_wg<CHAIN>(P, sb, true, 1 - k / 4, k & 3);
    }
  }
  if (b < N_CHAIN + N_G && (warp < 8 || (isg && warp >= 12))) bar_arrive(0, 512); else bar_sync(0, 512);
  if (tid == 352) TS(2);
}

__device__ __forceinline__ void publish_y() {
  if (threadIdx.x == 383) { grid_arrive(1); TS(18); }
  __syncwarp();
}

template <int R> __device__ __forceinline__ void ln_tiles(const Params& P, uint32_t sb) {
  const int lane = threadIdx.x & 31, w = (threadIdx.x >> 5) & (16 / R - 1), half = R == 1 ? 0 : threadIdx.x >> 8, u = N_CTA - 1 - bid();
  const int first = R == 1 ? u : 46 - 2 * u + half, step = R == 1 ? 4 : 40, last = R == 1 ? 8 : 128;
  const uint32_t raw = sb + P_CH + half * (18432 + Y_ROWS), mb = sb + T_BAR + (R - 1 + half) * 8;
  const bool lead = w == 16 / R - 1 && lane == 0;
  auto load_y = [&](const bf16* src, int tile) {
    fence_async_global();
    mbar_expect(mb, 18432);
    bulk_load(raw, src + (size_t)tile * 16 * DM, 18432, mb);
  };
  uint32_t nx[9 * R];
  auto load_x = [&](int tile) {
#pragma unroll
    for (int i = 0; i < 9 * R; i++) nx[i] = __ldg((const uint32_t*)(P.X + (size_t)(tile * 16 + w + i / 9 * 8) * DM) + i % 9 * 32 + lane);
  };
  load_x(first);
  if (R == 2) {
    if (lead) { grid_wait(1, lds32(sb + S_GEN)); if (u > 3) TS(13); load_y(g_yT, first); }
    __syncwarp();
  }
#pragma unroll 1
  for (int tile = first, real = R - 1, ph = 0; tile < last; tile += real * step, real = 1, ph ^= 1) {
    uint32_t x[9 * R], l[9 * R], y[9 * R];
    const bool ts = threadIdx.x == 0 && (R == 1 ? tile == first : u > 3 && tile == first + step);
    if (ts) TS(26);
#pragma unroll
    for (int i = 0; i < 9 * R; i++) x[i] = nx[i];
    layernorm9<R>(x, l);
    if (real && tile + step < last) load_x(tile + step);
    if (R == 2 && tile == first + step && u >= N_F && w < 6) load_wg<OROLE>(P, sb, true, w >> 1, half * 2 + (w & 1));
    if (R == 1 && tile == first && lead) {
      if (real) grid_wait(2, lds32(sb + S_GEN));
      TS(13);
      load_y(real ? g_yT : P.Hk, tile);
    }
    bar_sync(13 + half, 512 / R);
    mbar_wait(mb, ph);
    if (ts) TS(28);
    y_rows<R>(y, raw, raw + 18432, w, 13 + half);
    if (ts) TS(29);
    if (lead && real && tile + step < last) { fence_async_smem(); load_y(g_yT, tile + step); }
    __syncwarp();
#pragma unroll
    for (int i = 0; i < 9 * R; i++) x[i] = badd2(x[i], bmul2(l[i], y[i]));
    layernorm9<R>(x, l);
    if (ts && l[0] != 0x12345) TS(30);
#pragma unroll
    for (int r = 0; r < R; r++) store_ln_row(0, tile * 16 + w + r * 8, l + r * 9);
    if (R == 1) {
      __syncthreads();
      if (threadIdx.x == 32 && real) { if (tile < 4) TS(19); st_release(g_lnflag + tile * 8, 1); if (tile < 4) TS(20); }
      __syncwarp();
    }
    if (ts) TS(31);
  }
  if (R == 2) {
    __syncthreads();
    if (threadIdx.x >= 506) {
      asm volatile("fence.acq_rel.gpu;" ::: "memory");
      st_relaxed_if(g_lnflag + ((first ^ (lane & 1)) + (lane - 26) / 2 * step) * 8, 1, true);
    }
    __syncwarp();
    fence_async_smem();
    if (threadIdx.x == 0) TS(15);
  }
}

__global__ void __cluster_dims__(2, 1, 1) __launch_bounds__(512, 1) k_main(const __grid_constant__ Params P) {
  extern __shared__ __align__(1024) unsigned char smem[];
  const uint32_t sb = (uint32_t)__cvta_generic_to_shared(smem);
  const int b = bid(), wg = threadIdx.x >> 7;
  if ((threadIdx.x & 127) == 0) TS(0);
  if (threadIdx.x == 480) {
    if ((sb & 0xFFFFFF) != SBASE) __trap();
    for (int i = 0; i < 6; i++) mbar_init(sb + W_BAR + i * 8, 1);
    if (b < N_CHAIN) {
      mbar_init(sb + CB_FULL, 1); mbar_init(sb + CB_FULL + 8, 1);
      mbar_init(sb + CB_REF, 1);
      mbar_init(sb + CB_SX, 1); mbar_init(sb + CB_OX, 1); mbar_init(sb + CB_XX, 1); mbar_init(sb + CB_Q, 2); mbar_init(sb + CB_VF, 1);
      sts32(sb + C_BAD, 0);
      for (int i = 0; i < 11; i++) mbar_init(sb + CB_M + i * 8, i == 0 ? 5 : i == 5 ? 3 : 1);
    } else if (b < N_CHAIN + N_G) {
      for (int i = 0; i < 9; i++) { mbar_init(sb + G_BAR + i * 8, 2); mbar_init(sb + G_BAR + 128 + i * 8, 8); }
    } else if (b < N_CHAIN + N_G + N_O) {
      for (int i = 0; i < 5; i++) { mbar_init(sb + O_BAR + i * 8, 1); mbar_init(sb + O_BAR + 128 + i * 8, 12); }
      for (int i = 0; i < 6; i++) mbar_init(sb + OB_ST + i * 8, 1);
    } else {
      mbar_init(sb + F_BAR, 1); mbar_init(sb + F_BAR + 8, 1);
    }
    asm volatile("fence.mbarrier_init.release.cluster;" ::: "memory");
    fence_async_smem();
  }
  __syncwarp();
  asm volatile("barrier.cluster.arrive.relaxed.aligned;" ::: "memory");
  prologue(P, sb);
  asm volatile("barrier.cluster.wait.aligned;" ::: "memory");
  fence_async_smem();
  if (b >= N_CHAIN + N_G) publish_y();
  if (b >= 128) ln_tiles<1>(P, sb);
  if (b >= N_CHAIN + N_G) ln_tiles<2>(P, sb);
  if ((threadIdx.x & 127) == 0) TS(3);
  if (b < N_CHAIN) {
    if (wg < 2) { reg_inc<200>(); chain_proj(P, sb); }
    else if (wg == 2) { reg_dec<80>(); publish_y(); chain_attn(P, sb); }
    else { reg_dec<32>(); chain_aux(P, sb); }
  } else if (b < N_CHAIN + N_G) {
    if (wg == 0) { reg_inc<232>(); g_math<0>(P, sb); }
    else if (wg == 1) { reg_inc<232>(); g_math<1>(P, sb); }
    else if (wg == 2) { reg_dec<24>(); bar_arrive(15, 192); publish_y(); g_aux(P, sb); }
    else { reg_dec<24>(); g_load(P, sb); }
  } else if (b < N_CHAIN + N_G + N_O) {
    if (wg == 0) { reg_inc<160>(); o_math<0>(P, sb); }
    else if (wg == 1) { reg_inc<160>(); o_math<1>(P, sb); }
    else if (wg == 2) { reg_inc<160>(); o_math<2>(P, sb); }
    else { reg_dec<32>(); o_aux(P, sb); }
  } else {
    f_role(P, sb);
  }
}

}

extern "C" void kernel_launch(void* const* d_in, const int* in_sizes, int n_in, void* d_out, int out_size) {
  typedef CUresult (*Encode)(CUtensorMap*, CUtensorMapDataType, cuuint32_t, void*, const cuuint64_t*, const cuuint64_t*, const cuuint32_t*, const cuuint32_t*,
                             CUtensorMapInterleave, CUtensorMapSwizzle, CUtensorMapL2promotion, CUtensorMapFloatOOBfill);
  static Encode encode = nullptr;
  if (!encode) cudaGetDriverEntryPoint("cuTensorMapEncodeTiled", (void**)&encode, cudaEnableDefault);
  Params P;
  for (int i = 0; i < 11; i++) {
    const bool wo = i == 6 || i == 7;
    const cuuint64_t cols = wo ? DM : HD, rows = HD + DM - cols, pitch = cols * 2;
    const cuuint64_t dim[4][5] = {{cols, 2, 8, 2, 18}, {cols, 16, 1, 1, rows / 16}, {cols, 2, 4, 4, rows / 32}, {64, 16, 64, 2, 18}};
    const cuuint64_t stride[4][4] = {{8 * pitch, pitch, 16 * pitch, 32 * pitch}, {pitch, pitch, pitch, 16 * pitch},
                                     {pitch, 8 * pitch, 2 * pitch, 32 * pitch}, {pitch, 128, 16 * pitch, 32 * pitch}};
    const cuuint32_t box[4][5] = {{64, 2, 8, 1, 18}, {64, 16, 1, 1, 1}, {64, 2, 4, 2, 1}, {64, 16, 2, 1, 18}}, one[5] = {1, 1, 1, 1, 1};
    const int k = i < 3 ? 0 : i < 7 ? 1 : i < 8 ? 2 : 3;
    encode(&P.map[i], CU_TENSOR_MAP_DATA_TYPE_BFLOAT16, 5, d_in[wo ? 11 : 8 + (i & 7) % 3], dim[k], stride[k], box[k], one,
           CU_TENSOR_MAP_INTERLEAVE_NONE, CU_TENSOR_MAP_SWIZZLE_128B, CU_TENSOR_MAP_L2_PROMOTION_L2_128B, CU_TENSOR_MAP_FLOAT_OOB_FILL_NONE);
  }
  P.X = (const bf16*)d_in[0]; P.K = (const bf16*)d_in[1]; P.V = (const bf16*)d_in[2];
  P.shift = (const bf16*)d_in[3]; P.Hk = (const bf16*)d_in[4]; P.Dk = (const bf16*)d_in[5];
  P.mem0 = (const bf16*)d_in[7];
  P.Wq = (const bf16*)d_in[8]; P.Wk = (const bf16*)d_in[9]; P.Wv = (const bf16*)d_in[10]; P.Wo = (const bf16*)d_in[11];
  P.out = (bf16*)d_out;
  for (int i = 0; i < 24; i++) P.dly[i] = h_dly[i];
  cudaFuncSetAttribute(k_main, cudaFuncAttributeMaxDynamicSharedMemorySize, SMEM_BYTES);
  k_main<<<N_CTA, 512, SMEM_BYTES>>>(P);
}
```

```cpp
#include <cuda.h>
#include <cuda_runtime.h>
#include <cuda_bf16.h>
#include <stdint.h>

namespace {

typedef __nv_bfloat16 bf16;

constexpr int SEQ = 2048, DM = 576, HD = 4096, NSEG = 64;
constexpr int LAG = 7, STEPS = NSEG + LAG, RING = 8;
constexpr int LOCK0 = 3, QRING = LOCK0 + 1;
static_assert(LAG < RING, "ring");
constexpr int N_CHAIN = 64, N_G = 48, N_O = 18, N_F = 2;
constexpr uint32_t SBASE = 1024;
constexpr uint32_t SENT = 0xFFFFFFFFu;
constexpr int SPIN_MAX = 1 << 22;

__device__ __forceinline__ uint32_t bid() {
  uint32_t b;
  asm volatile("mov.u32 %0, %%ctaid.x;" : "=r"(b));
  return b < 6 ? b + 106 : b < 8 ? b + 122 : b < 114 ? b - 8 : b < 130 ? b - 2 : b;
}
__device__ __forceinline__ uint32_t chain_id() { return blockIdx.x - 8; }
constexpr int KVP = SEQ + 64;
__device__ __align__(1024) bf16 g_kvT[DM * KVP];
__device__ __align__(1024) bf16 g_yT[DM * SEQ];
__device__ __align__(1024) unsigned char g_lnimg[2 * NSEG * 9 * 4096];
__device__ __align__(1024) unsigned char g_qkv[QRING * N_CHAIN * 24576];
__device__ __align__(1024) unsigned char g_oimg[RING * N_CHAIN * 8192];
constexpr int ARING = 16;
static_assert(ARING >= LAG + 9, "accumulator ring");
__device__ __align__(1024) float g_oacc[ARING * 64 * DM];
constexpr int MRING = LAG + 4, N_GRP = 32 + MRING + 1;
constexpr int XB_M = 256, XB_F = XB_M + MRING * 8, XB_REF = XB_F + 2, N_CTA = N_CHAIN + N_G + N_O + N_F;
__device__ __align__(65536) uint4 g_xb[N_GRP * 4096];
#define g_mimg ((uint32_t*)(g_xb + XB_M * 512))
__device__ uint32_t g_near[N_GRP];
__device__ uint32_t g_side[N_CTA];
__device__ __align__(128) uint32_t g_gbar[3 * 32];
constexpr int FL_G = 0, FL_F = 96 * 8, FL_OCNT = FL_F + 2 * 8, OCRING = 16, FL_TICK = 992, FL_O = 2048, FL_SYNC = FL_O + 128;
static_assert(FL_OCNT + OCRING * 8 <= FL_TICK, "flag block");
#define g_fl ((uint32_t*)(g_xb + XB_F * 512))
__device__ __align__(1024) uint32_t g_lnflag[128 * 8];
#define TS(slot)

#define CNT(slot, tries)
#define T3(slot)
#define TR(slot)
#define TRV(slot, val)
#define TRD(slot, dep)
#define TRSYNC()
#define TRDUMP(n)
#define CLK(t) "{.reg .b64 x; .reg .b32 h; mov.u64 x, %%clock64; mov.b64 {" t ", h}, x;}"
__device__ __forceinline__ uint32_t clk() { uint32_t t; asm volatile(CLK("%0") : "=r"(t) :: "memory"); return t; }
__device__ __forceinline__ void wait_until(uint32_t t0, uint32_t d) {
  asm volatile("{.reg .pred p; .reg .u32 t;\n"
               "W: " CLK("t") " sub.u32 t, t, %0; setp.lt.s32 p, t, 0; @p bra.uni W;}"
               :: "r"(t0 + d) : "memory");
}
__device__ __forceinline__ uint32_t pack2(float lo, float hi) {
  uint32_t r; asm("cvt.rn.bf16x2.f32 %0, %1, %2;" : "=r"(r) : "f"(hi), "f"(lo)); return r;
}
__device__ __forceinline__ float bf_lo(uint32_t v) { return __uint_as_float(v << 16); }
__device__ __forceinline__ float bf_hi(uint32_t v) { return __uint_as_float(v & 0xFFFF0000u); }

__device__ __forceinline__ void st_b128(void* p, uint32_t a, uint32_t b, uint32_t c, uint32_t d) {
  asm volatile("{.reg .b128 v; mov.b128 v, {%1,%2,%3,%4}; st.relaxed.gpu.global.b128 [%0], v;}" :: "l"(p), "r"(a), "r"(b), "r"(c), "r"(d) : "memory");
}
__device__ __forceinline__ void st_relaxed_if(void* p, uint32_t a, bool on) {
  asm volatile("{.reg .pred p; setp.ne.u32 p, %2, 0; @p st.relaxed.gpu.global.u32 [%0], %1;}" :: "l"(p), "r"(a), "r"((uint32_t)on) : "memory");
}
__device__ __forceinline__ uint32_t ld_acquire(const uint32_t* p) {
  uint32_t v; asm volatile("ld.acquire.gpu.global.u32 %0, [%1];" : "=r"(v) : "l"(p) : "memory"); return v;
}
__device__ __forceinline__ void st_release(uint32_t* p, uint32_t v) {
  asm volatile("st.release.gpu.global.u32 [%0], %1;" :: "l"(p), "r"(v) : "memory");
}
__device__ __forceinline__ void bulk_reduce(float* dst, uint32_t src, uint32_t bytes) {
  asm volatile("cp.reduce.async.bulk.global.shared::cta.bulk_group.add.f32 [%0], [%1], %2;" :: "l"(dst), "r"(src), "r"(bytes) : "memory");
}
__device__ __forceinline__ void bulk_done_inc(uint32_t* p) {
  asm volatile("cp.async.bulk.wait_group 0;\n"
               "fence.proxy.async.global;\nfence.release.gpu;\n"
               "red.relaxed.gpu.global.add.u32 [%0], 1;\nred.relaxed.gpu.global.add.u32 [%0+4096], 1;" :: "l"(p) : "memory");
}
__device__ __forceinline__ void flag_release(uint32_t* p, uint32_t v) {
  asm volatile("fence.release.gpu;\nst.relaxed.gpu.global.u32 [%0], %1;\nst.relaxed.gpu.global.u32 [%0+4096], %1;" :: "l"(p), "r"(v) : "memory");
}
__device__ __forceinline__ void spin_guard(int& it) {
  asm volatile("{.reg .pred p; add.s32 %0, %0, 1; setp.gt.s32 p, %0, %1; @p trap;}" : "+r"(it) : "n"(SPIN_MAX));
}
__device__ __forceinline__ void wait_flags(const uint32_t* p, uint32_t v) {
  int it = 0;
  while (true) {
    uint32_t x; asm volatile("ld.relaxed.gpu.global.u32 %0, [%1];" : "=r"(x) : "l"(p) : "memory");
    if (__all_sync(~0u, x >= v)) break;
    spin_guard(it);
  }
  asm volatile("fence.acquire.gpu;" ::: "memory");
}
__device__ __forceinline__ uint32_t timer_offset() {
  uint32_t g0, g;
  asm volatile("mov.u32 %0, %%globaltimer_lo;" : "=r"(g0) :: "memory");
  do { asm volatile("mov.u32 %0, %%globaltimer_lo;" : "=r"(g) :: "memory"); } while (g == g0);
  return (g >> 5) * 58 - clk();
}
__device__ __forceinline__ void grid_arrive(int i) {
  asm volatile("red.release.gpu.global.add.u32 [%0], %1;" :: "l"(g_gbar + i * 32), "r"(bid() ? 1u : 257u - N_CTA) : "memory");
}
__device__ __forceinline__ void grid_wait(int i, uint32_t gen) {
  int it = 0;
  while (((ld_acquire(g_gbar + i * 32) ^ gen) >> 8) == 0) spin_guard(it);
}
__device__ __forceinline__ bool elect() {
  uint32_t r; asm volatile("{.reg .pred p; elect.sync _|p, -1; selp.u32 %0, 1, 0, p;}" : "=r"(r)); return r;
}
__device__ __forceinline__ void bar_sync(int id, int cnt) { asm volatile("bar.sync %0, %1;" :: "r"(id), "r"(cnt) : "memory"); }
__device__ __forceinline__ void bar_arrive(int id, int cnt) { asm volatile("bar.arrive %0, %1;" :: "r"(id), "r"(cnt) : "memory"); }
template <int id, int cnt> __device__ __forceinline__ void bar_arrive_after(uint32_t a, uint32_t b) {
  asm volatile("{.reg .pred p; setp.ne.u32 p, %2, 0xfff12345; setp.ne.and.u32 p, %3, 0xfff12345, p; @p bar.arrive %0, %1;}" :: "n"(id), "n"(cnt), "r"(a), "r"(b) : "memory");
}
template <int id, int cnt> __device__ __forceinline__ void bar_sync_after(uint32_t a) {
  asm volatile("{.reg .pred p; setp.ne.u32 p, %2, 0xfff12345; @p bar.sync %0, %1;}" :: "n"(id), "n"(cnt), "r"(a) : "memory");
}
__device__ __forceinline__ void fence_async_smem() { asm volatile("fence.proxy.async.shared::cta;" ::: "memory"); }
__device__ __forceinline__ void fence_async_global() { asm volatile("fence.proxy.async.global;" ::: "memory"); }
__device__ __forceinline__ void mbar_init(uint32_t mb, int cnt) { asm volatile("mbarrier.init.shared::cta.b64 [%0], %1;" :: "r"(mb), "r"(cnt) : "memory"); }
__device__ __forceinline__ void mbar_arrive(uint32_t mb) { asm volatile("mbarrier.arrive.shared::cta.b64 _, [%0];" :: "r"(mb) : "memory"); }
__device__ __forceinline__ void mbar_expect(uint32_t mb, uint32_t bytes) {
  asm volatile("mbarrier.arrive.expect_tx.shared::cta.b64 _, [%0], %1;" :: "r"(mb), "r"(bytes) : "memory");
}
__device__ __forceinline__ void mbar_wait(uint32_t mb, uint32_t parity) {
  asm volatile("{.reg .pred p;\nW: mbarrier.try_wait.parity.shared::cta.b64 p, [%0], %1;\n@!p bra W;}" :: "r"(mb), "r"(parity) : "memory");
}
__device__ __forceinline__ void bulk_load(uint32_t dst, const void* src, uint32_t bytes, uint32_t mb) {
  asm volatile("cp.async.bulk.shared::cluster.global.mbarrier::complete_tx::bytes [%0], [%1], %2, [%3];" :: "r"(dst), "l"(src), "r"(bytes), "r"(mb) : "memory");
}
__device__ __forceinline__ void bulk_store(void* dst, uint32_t src, uint32_t bytes) {
  asm volatile("cp.async.bulk.global.shared::cta.bulk_group [%0], [%1], %2;" :: "l"(dst), "r"(src), "r"(bytes) : "memory");
}
__device__ __forceinline__ uint32_t mapa(uint32_t a, uint32_t rank) {
  uint32_t r; asm("mapa.shared::cluster.u32 %0, %1, %2;" : "=r"(r) : "r"(a), "r"(rank)); return r;
}
__device__ __forceinline__ void st_async4(uint32_t dst, float a, float b, float c, float d, uint32_t mb) {
  asm volatile("st.async.shared::cluster.mbarrier::complete_tx::bytes.v4.f32 [%0], {%1,%2,%3,%4}, [%5];" :: "r"(dst), "f"(a), "f"(b), "f"(c), "f"(d), "r"(mb) : "memory");
}
__device__ __forceinline__ void st_async1(uint32_t dst, uint32_t a, uint32_t mb) {
  asm volatile("st.async.shared::cluster.mbarrier::complete_tx::bytes.u32 [%0], %1, [%2];" :: "r"(dst), "r"(a), "r"(mb) : "memory");
}
__device__ __forceinline__ uint4 lds128(uint32_t a) {
  uint4 v; asm volatile("ld.shared.v4.u32 {%0,%1,%2,%3}, [%4];" : "=r"(v.x), "=r"(v.y), "=r"(v.z), "=r"(v.w) : "r"(a) : "memory"); return v;
}
__device__ __forceinline__ uint2 lds64(uint32_t a) {
  uint2 v; asm volatile("ld.shared.v2.u32 {%0,%1}, [%2];" : "=r"(v.x), "=r"(v.y) : "r"(a) : "memory"); return v;
}
__device__ __forceinline__ uint32_t lds32(uint32_t a) {
  uint32_t v; asm volatile("ld.shared.u32 %0, [%1];" : "=r"(v) : "r"(a) : "memory"); return v;
}
__device__ __forceinline__ void sts128(uint32_t a, uint4 v) {
  asm volatile("st.shared.v4.u32 [%0], {%1,%2,%3,%4};" :: "r"(a), "r"(v.x), "r"(v.y), "r"(v.z), "r"(v.w) : "memory");
}
__device__ __forceinline__ void sts32(uint32_t a, uint32_t x) { asm volatile("st.shared.u32 [%0], %1;" :: "r"(a), "r"(x) : "memory"); }
__device__ __forceinline__ void ldsm4(uint32_t& r0, uint32_t& r1, uint32_t& r2, uint32_t& r3, uint32_t a) {
  asm volatile("ldmatrix.sync.aligned.m8n8.x4.shared.b16 {%0,%1,%2,%3}, [%4];" : "=r"(r0), "=r"(r1), "=r"(r2), "=r"(r3) : "r"(a) : "memory");
}
__device__ __forceinline__ void ldsm4t(uint32_t& r0, uint32_t& r1, uint32_t& r2, uint32_t& r3, uint32_t a) {
  asm volatile("ldmatrix.sync.aligned.m8n8.x4.trans.shared.b16 {%0,%1,%2,%3}, [%4];" : "=r"(r0), "=r"(r1), "=r"(r2), "=r"(r3) : "r"(a) : "memory");
}
__device__ __forceinline__ void stsm4(uint32_t a, uint32_t r0, uint32_t r1, uint32_t r2, uint32_t r3) {
  asm volatile("stmatrix.sync.aligned.m8n8.x4.shared.b16 [%0], {%1,%2,%3,%4};" :: "r"(a), "r"(r0), "r"(r1), "r"(r2), "r"(r3) : "memory");
}
__device__ __forceinline__ uint32_t movmat(uint32_t a) {
  uint32_t d; asm volatile("movmatrix.sync.aligned.m8n8.trans.b16 %0, %1;" : "=r"(d) : "r"(a)); return d;
}
__device__ __forceinline__ void mma16(float* d, uint32_t a0, uint32_t a1, uint32_t a2, uint32_t a3, uint32_t b0, uint32_t b1) {
  asm volatile("mma.sync.aligned.m16n8k16.row.col.f32.bf16.bf16.f32 {%0,%1,%2,%3}, {%4,%5,%6,%7}, {%8,%9}, {%0,%1,%2,%3};"
    : "+f"(d[0]), "+f"(d[1]), "+f"(d[2]), "+f"(d[3]) : "r"(a0), "r"(a1), "r"(a2), "r"(a3), "r"(b0), "r"(b1));
}
__device__ __forceinline__ void mma8(float* d, uint32_t a0, uint32_t a1, uint32_t b0) {
  asm volatile("mma.sync.aligned.m16n8k8.row.col.f32.bf16.bf16.f32 {%0,%1,%2,%3}, {%4,%5}, {%6}, {%0,%1,%2,%3};"
    : "+f"(d[0]), "+f"(d[1]), "+f"(d[2]), "+f"(d[3]) : "r"(a0), "r"(a1), "r"(b0));
}
__device__ __forceinline__ float rcp(float x) { float r; asm("rcp.approx.ftz.f32 %0, %1;" : "=f"(r) : "f"(x)); return r; }
__device__ __forceinline__ float ex2(float x) { float r; asm("ex2.approx.ftz.f32 %0, %1;" : "=f"(r) : "f"(x)); return r; }

__host__ __device__ constexpr uint64_t mkdesc(uint32_t off, uint32_t lbo, uint32_t sbo, uint32_t swz) {
  return (uint64_t)((SBASE + off) >> 4) | ((uint64_t)(lbo >> 4) << 16) | ((uint64_t)(sbo >> 4) << 32) | ((uint64_t)swz << 62);
}
__host__ __device__ constexpr uint64_t desc_sw128(uint32_t off) { return mkdesc(off, 16, 1024, 1); }
__host__ __device__ constexpr uint64_t desc_n16(uint32_t off) { return mkdesc(off, 256, 128, 0); }
__host__ __device__ constexpr uint64_t desc_m(uint32_t off) { return mkdesc(off, 16, 256, 3); }

__host__ __device__ constexpr uint64_t desc_sw64(uint32_t off) { return mkdesc(off, 16, 512, 2); }

__device__ __forceinline__ void wg_fence() { asm volatile("wgmma.fence.sync.aligned;" ::: "memory"); }
__device__ __forceinline__ void wg_commit() { asm volatile("wgmma.commit_group.sync.aligned;" ::: "memory"); }
template <int N> __device__ __forceinline__ void wg_wait() { asm volatile("wgmma.wait_group.sync.aligned %0;" :: "n"(N) : "memory"); }

#define ACC8(d) "+f"(d[0]), "+f"(d[1]), "+f"(d[2]), "+f"(d[3]), "+f"(d[4]), "+f"(d[5]), "+f"(d[6]), "+f"(d[7])
#define ACC32(d) ACC8(d), ACC8((d + 8)), ACC8((d + 16)), ACC8((d + 24))
#define R8 "{%0,%1,%2,%3,%4,%5,%6,%7}"
#define R32 "{%0,%1,%2,%3,%4,%5,%6,%7,%8,%9,%10,%11,%12,%13,%14,%15,%16,%17,%18,%19,%20,%21,%22,%23,%24,%25,%26,%27,%28,%29,%30,%31}"
template <int SD> __device__ __forceinline__ void wg_rs16(float* d, const uint32_t* a, uint64_t db) {
  asm volatile("wgmma.mma_async.sync.aligned.m64n16k16.f32.bf16.bf16 " R8 ", {%8,%9,%10,%11}, %12, %13, 1, 1, 1;"
    : ACC8(d) : "r"(a[0]), "r"(a[1]), "r"(a[2]), "r"(a[3]), "l"(db), "n"(SD));
}
template <int SD> __device__ __forceinline__ void wg_ss16(float* d, uint64_t da, uint64_t db) {
  asm volatile("wgmma.mma_async.sync.aligned.m64n16k16.f32.bf16.bf16 " R8 ", %8, %9, %10, 1, 1, 1, 1;"
    : ACC8(d) : "l"(da), "l"(db), "n"(SD));
}
template <int SD, uint64_t DA, uint64_t DB> __device__ __forceinline__ void wg_ss16o(float* d, uint32_t oa, uint32_t ob) {
  asm volatile("{.reg .b32 x, y; .reg .b64 a, b; add.u32 x, %8, %10; add.u32 y, %9, %12; mov.b64 a, {x, %11}; mov.b64 b, {y, %13};\n"
               "wgmma.mma_async.sync.aligned.m64n16k16.f32.bf16.bf16 " R8 ", a, b, %14, 1, 1, 1, 1;}"
    : ACC8(d) : "r"(oa), "r"(ob), "n"((uint32_t)DA), "n"((uint32_t)(DA >> 32)), "n"((uint32_t)DB), "n"((uint32_t)(DB >> 32)), "n"(SD));
}
template <int SD> __device__ __forceinline__ void wg_rs64(float* d, const uint32_t* a, uint64_t db) {
  asm volatile("wgmma.mma_async.sync.aligned.m64n64k16.f32.bf16.bf16 " R32 ", {%32,%33,%34,%35}, %36, %37, 1, 1, 0;"
    : ACC32(d) : "r"(a[0]), "r"(a[1]), "r"(a[2]), "r"(a[3]), "l"(db), "n"(SD));
}
template <int SD> __device__ __forceinline__ void wg_ss64(float* d, uint64_t da, uint64_t db) {
  asm volatile("wgmma.mma_async.sync.aligned.m64n64k16.f32.bf16.bf16 " R32 ", %32, %33, %34, 1, 1, 1, 0;"
    : ACC32(d) : "l"(da), "l"(db), "n"(SD));
}
#define WG_RSO(NAME, SHAPE, REGS, ACC, A, TB) \
template <int SD, uint64_t DB> __device__ __forceinline__ void NAME(float* d, uint32_t a0, uint32_t a1, uint32_t a2, uint32_t a3, uint32_t ob) { \
  asm volatile("{.reg .b64 b; mov.b64 b, {" A(4) ", " A(5) "};\nwgmma.mma_async.sync.aligned." SHAPE ".f32.bf16.bf16 " REGS \
               ", {" A(0) "," A(1) "," A(2) "," A(3) "}, b, " A(6) ", 1, 1, " TB ";}" \
    : ACC(d) : "r"(a0), "r"(a1), "r"(a2), "r"(a3), "r"(ob + (uint32_t)DB), "n"((uint32_t)(DB >> 32)), "n"(SD)); \
}
#define ACC4(d) "+f"(d[0]), "+f"(d[1]), "+f"(d[2]), "+f"(d[3])
#define ACC16(d) ACC8(d), ACC8((d + 8))
#define OP4(i) OP4_##i
#define OP4_0 "%4"
#define OP4_1 "%5"
#define OP4_2 "%6"
#define OP4_3 "%7"
#define OP4_4 "%8"
#define OP4_5 "%9"
#define OP4_6 "%10"
#define OP16(i) OP16_##i
#define OP16_0 "%16"
#define OP16_1 "%17"
#define OP16_2 "%18"
#define OP16_3 "%19"
#define OP16_4 "%20"
#define OP16_5 "%21"
#define OP16_6 "%22"
#define OP32(i) OP32_##i
#define OP32_0 "%32"
#define OP32_1 "%33"
#define OP32_2 "%34"
#define OP32_3 "%35"
#define OP32_4 "%36"
#define OP32_5 "%37"
#define OP32_6 "%38"
WG_RSO(wg_rs8o, "m64n8k16", "{%0,%1,%2,%3}", ACC4, OP4, "1")
#define R16 "{%0,%1,%2,%3,%4,%5,%6,%7,%8,%9,%10,%11,%12,%13,%14,%15}"
WG_RSO(wg_rs32o, "m64n32k16", R16, ACC16, OP16, "1")
WG_RSO(wg_rs64o, "m64n64k16", R32, ACC32, OP32, "0")
WG_RSO(wg_rs32k, "m64n32k16", R16, ACC16, OP16, "0")
template <uint64_t DA, uint64_t DB> __device__ __forceinline__ void wg_ss32k(float* d, uint32_t ob) {
  asm volatile("{.reg .b64 b; mov.b64 b, {%17, %18};\nwgmma.mma_async.sync.aligned.m64n32k16.f32.bf16.bf16 " R16 ", %16, b, 1, 1, 1, 1, 0;}"
    : ACC16(d) : "l"(DA), "r"(ob + (uint32_t)DB), "n"((uint32_t)(DB >> 32)));
}
template <int N> __device__ __forceinline__ void reg_inc() { asm volatile("setmaxnreg.inc.sync.aligned.u32 %0;" :: "n"(N)); }
template <int N> __device__ __forceinline__ void reg_dec() { asm volatile("setmaxnreg.dec.sync.aligned.u32 %0;" :: "n"(N)); }

template <int KS>
__device__ __forceinline__ void load_frags(uint32_t* a, uint32_t src) {
  const int lane = threadIdx.x & 31, w = (threadIdx.x >> 5) & 3;
  const int k = ((lane >> 4) << 3) + (lane & 7), u = w * 2 + ((lane >> 3) & 1);
  const uint32_t base = src + k * 128 + ((u ^ (k & 7)) << 4);
#pragma unroll
  for (int ks = 0; ks < KS; ks++) ldsm4t(a[ks * 4], a[ks * 4 + 1], a[ks * 4 + 2], a[ks * 4 + 3], base + ks * 2048);
}

__device__ __forceinline__ uint32_t badd2(uint32_t a, uint32_t b) { uint32_t r; asm("add.rn.bf16x2 %0, %1, %2;" : "=r"(r) : "r"(a), "r"(b)); return r; }
__device__ __forceinline__ uint32_t bsub2(uint32_t a, uint32_t b) { uint32_t r; asm("sub.rn.bf16x2 %0, %1, %2;" : "=r"(r) : "r"(a), "r"(b)); return r; }
__device__ __forceinline__ uint32_t bmul2(uint32_t a, uint32_t b) { uint32_t r; asm("mul.rn.bf16x2 %0, %1, %2;" : "=r"(r) : "r"(a), "r"(b)); return r; }
__device__ __forceinline__ uint32_t bfma2(uint32_t a, uint32_t b, uint32_t c) { uint32_t r; asm("fma.rn.bf16x2 %0, %1, %2, %3;" : "=r"(r) : "r"(a), "r"(b), "r"(c)); return r; }
template <int R> __device__ __forceinline__ void layernorm9(const uint32_t* x, uint32_t* o) {
  const uint32_t ones = 0x3F803F80u;
  float a[R][3][4], q[R], s[R];
#pragma unroll
  for (int i = 0; i < 9 * R; i++) {
    float* d = a[i % R][i / R % 3];
    if (i < 3 * R) d[0] = d[1] = d[2] = d[3] = 0.f;
    mma8(d, x[i % R * 9 + i / R], ones, x[i % R * 9 + i / R]);
  }
#pragma unroll
  for (int r = 0; r < R; r++) {
    q[r] = threadIdx.x & 4 ? a[r][0][1] + a[r][1][1] + a[r][2][1] : a[r][0][0] + a[r][1][0] + a[r][2][0];
    s[r] = (a[r][0][2] + a[r][0][3]) + (a[r][1][2] + a[r][1][3]) + (a[r][2][2] + a[r][2][3]);
  }
#pragma unroll
  for (int r = 0; r < R; r++) { q[r] += __shfl_xor_sync(~0u, q[r], 4); s[r] += __shfl_xor_sync(~0u, s[r], 1); }
#pragma unroll
  for (int r = 0; r < R; r++) { q[r] += __shfl_xor_sync(~0u, q[r], 9); s[r] += __shfl_xor_sync(~0u, s[r], 2); }
#pragma unroll
  for (int r = 0; r < R; r++) q[r] = __shfl_sync(~0u, q[r], 0) + __shfl_sync(~0u, q[r], 18);
#pragma unroll
  for (int r = 0; r < R; r++) {
    const float mean = s[r] * (1.f / DM), var = fmaxf(fmaf(q[r], 1.f / DM, -mean * mean), 0.f);
    float sd;
    asm("sqrt.approx.ftz.f32 %0, %1;" : "=f"(sd) : "f"(bf_lo(pack2(bf_lo(pack2(var, 0.f)) + 1e-5f, 0.f))));
    const float inv = rcp(bf_lo(pack2(sd, 0.f)));
    const uint32_t mb = pack2(mean, mean), hi = pack2(inv, inv), lo = pack2(inv - bf_lo(hi), inv - bf_lo(hi));
#pragma unroll
    for (int i = r * 9; i < r * 9 + 9; i++) {
      const uint32_t d = bsub2(x[i], mb);
      o[i] = bfma2(d, hi, bmul2(d, lo));
    }
  }
}
__device__ __forceinline__ void store_ln_row(int layer, int tok, const uint32_t* o) {
  const int lane = threadIdx.x & 31, r = tok & 31;
  unsigned char* p = g_lnimg + (size_t)(layer * NSEG + (tok >> 5)) * (9 * 4096) + r * 128 + (((lane >> 2) ^ (r & 7)) << 4) + (lane & 3) * 4;
#pragma unroll
  for (int i = 0; i < 9; i++) *(uint32_t*)(p + i * 4096) = o[i];
}
struct Params { CUtensorMap map[11]; const bf16 *X, *K, *V, *shift, *Hk, *Dk, *mem0, *Wq, *Wk, *Wv, *Wo; bf16* out; uint32_t dly[24]; };
#define DLYS P.dly[0]
#define DLYW P.dly[1]
#define DLYK P.dly[4]
#define DLYG P.dly[5]
#define KWIN P.dly[6]
#define KMIN P.dly[7]
#define PREF0 P.dly[19]
#define PACE P.dly[20]
#define S1G P.dly[21]
#define S1DLY P.dly[22]
#define PREFH P.dly[23]
uint32_t h_dly[24] = {900, 120, 150, 160, 3565, 4200, 2750, 1300, 1610, 1700, 1810, 2130, 2260, 2390, 2945, 3055, 3225, 3375, 3525, 7000, 160, 12500, 20500, 4000};

constexpr uint32_t C_W = 0, C_M = 147456, C_KV = C_M + 18432, C_OS = C_KV + 24576, C_QM = C_KV + 32768, C_KM = C_QM + 2048,
                   C_VM = C_KM + 2048, C_OI = C_VM + 2048, C_SX = C_OI + 4096, C_KM2 = C_SX + 2560, C_VM2 = C_KM2 + 128,
                   C_KV2 = C_KM2 + 2048, C_Q = C_KV2 + 8192, C_BAR = C_Q + 8192;
constexpr uint32_t CB_FULL = C_BAR, CB_REF = C_BAR + 16, CB_SX = C_BAR + 32, CB_OX = C_BAR + 40, CB_XX = C_BAR + 48, CB_Q = C_BAR + 56, C_BAD = C_BAR + 64, W_BAR = C_BAR + 80, T_BAR = W_BAR + 24, S_GEN = C_BAR + 128, C_REF = C_BAR + 132, CB_VF = C_BAR + 144, CB_M = C_BAR + 160, CB_MV = C_BAR + 200;
constexpr uint32_t G_W = 0, G_RING = 147456, G_W2 = G_RING + 9 * 8192, G_BAR = G_W2 + 8192;
constexpr uint32_t O_W = 0, O_RING = 3 * 40960, O_ST = O_RING + 11 * 8192, O_BAR = O_ST + 16384, OB_ST = O_BAR + 64;
constexpr uint32_t F_A = 0, F_XY = 36864, F_L = F_XY + 36864, F_X = F_L + 18432, F_Y = F_L + 2 * 36864, F_BAR = C_BAR;
constexpr uint32_t SMEM_BYTES = C_BAR + 256;
static_assert(G_BAR + 256 <= SMEM_BYTES && O_BAR + 256 <= SMEM_BYTES && F_BAR + 16 <= SMEM_BYTES && SMEM_BYTES <= 232448, "smem map");
enum { B_INIT = 1, B_M, B_QK, B_S, B_V, B_O, B_X, B_WG0, B_WG1, B_WG2, B_G, B_OE, B_T, B_R };

__device__ __forceinline__ uint4 pack_partial(const float* d, uint32_t tag) {
  uint32_t x, z;
  asm("lop3.b32 %0, %2, 1, %4, 0xb8; lop3.b32 %1, %3, 1, %4, 0xb8;" : "=&r"(x), "=&r"(z) : "r"(pack2(d[0], d[1])), "r"(pack2(d[2], d[3])), "r"(tag));
  return make_uint4(x, pack2(d[4], d[5]), z, pack2(d[6], d[7]));
}
__device__ __forceinline__ void store_partial(uint4* p, const uint4& v) { st_b128(p, v.x, v.y, v.z, v.w); }
__device__ __forceinline__ void gather_reduce(const uint32_t* p, uint32_t* dst, uint32_t m0, bool shared, uint32_t tag, uint32_t lane, uint32_t sb, int n, int TS0) {
  int tries = 0;
  bool bad;
  TR(TS0);
  do {
    uint2 x[8];
#pragma unroll
    for (int i = 0; i < 8; i++)
      asm volatile("{.reg .b64 v; ld.relaxed.gpu.global.b64 v, [%2]; mov.b64 {%0, %1}, v;}" : "=r"(x[i].x), "=r"(x[i].y) : "l"(p + i * 128) : "memory");
    spin_guard(tries);
    float a = bf_lo(x[0].x), b = bf_hi(x[0].x), c = bf_lo(x[0].y), d = bf_hi(x[0].y);
    uint32_t t = x[0].x ^ tag;
#pragma unroll
    for (int i = 1; i < 8; i++) {
      a += bf_lo(x[i].x); b += bf_hi(x[i].x); c += bf_lo(x[i].y); d += bf_hi(x[i].y);
      asm("lop3.b32 %0, %0, %1, %2, 0xf6;" : "+r"(t) : "r"(x[i].x), "r"(tag));
    }
    bad = __any_sync(~0u, t & 1);
    const bool up = lane & 8;
    float u = (up ? c : a) + __shfl_xor_sync(~0u, up ? a : c, 8), v = (up ? d : b) + __shfl_xor_sync(~0u, up ? b : d, 8);
    if (shared) { u += __shfl_xor_sync(~0u, u, 4); v += __shfl_xor_sync(~0u, v, 4); }
    u += __shfl_xor_sync(~0u, u, 16);
    v += __shfl_xor_sync(~0u, v, 16);
    st_relaxed_if(dst, n < LAG && up ? m0 : pack2(u, v), !bad);
  } while (bad);
  TR(TS0 + 3); TRV(TS0 + 2, tries);
  CNT((TS0 - 16) >> 2, tries);
}

#define ATTR 80
#define XRV 3
constexpr int XR = XRV;
__host__ __device__ constexpr int o_ks(int s) { return s & (s < 8 ? 3 : 7); }
__host__ __device__ constexpr bool o_reg(int s) { return s < 8 ? (s & 3) != 3 : !(s & 1); }
__host__ __device__ constexpr int o_slot(int s) { return s < 8 ? (o_reg(s) ? s - (s >> 2) : s >> 2) : s & 1 ? (s - 5) >> 1 : (s + 4) >> 1; }
__device__ __forceinline__ int g_unit(int wg) {
  const int i = bid() - N_CHAIN;
  return i < 32 ? wg * 64 + i : 2 * i - 32 + wg;
}
__device__ __forceinline__ uint32_t pinned(uint32_t v) { return __shfl_sync(~0u, v, threadIdx.x & 31); }
template <class T> __device__ __forceinline__ T* pinned(T* p) { return (T*)__shfl_sync(~0u, (unsigned long long)p, threadIdx.x & 31); }
enum { CHAIN, GROLE, OROLE };
template <int ROLE, bool SYNC> __device__ __forceinline__ void load_box(const Params& P, uint32_t sb, bool regs, int wg, int i, uint32_t mb, bool on) {
  const int b = bid();
  int map, col = 0, ks = 0, c2 = 0, c3 = 0;
  uint32_t dst = wg * 73728;
  if (ROLE == CHAIN) {
    const int k = i - 1, st = regs ? (k < 6 ? k + k / 3 : 2 * k - 4) : k < 2 ? 4 * k + 3 : 2 * k + 5;
    dst += i ? (17 + i) * 2048 : 0;
    if (wg || i == 0) { map = wg + i; col = b * 64; c3 = !regs; }
    else if (!regs && k >= 14) { map = 6; ks = b * 4 + k - 14; }
    else { map = 6; col = 64 + (st < 8 ? (st >> 2) * 64 : (st >> 3) * 128 + (b & 1) * 64); ks = (b * 4) ^ o_ks(st); }
  } else if (ROLE == GROLE) {
    const int q = g_unit(wg);
    map = ((q >> 5) + 1) % 3;
    if (i) { map += 3; col = (q & 31) * 128 + (i - 1) * 64; ks = 34; dst = G_W2 + wg * 4096 + (i - 1) * 2048; }
    else { map += 8; c2 = (q & 31) * 2; c3 = !regs; }
  } else {
    const int o = b - N_CHAIN - N_G, ksl = o / 3;
    map = 7; col = ((o % 3) * 3 + (wg + ksl) % 3) * 64; dst = (wg * (regs ? 24 : 20) + i) * 2048;
    ks = (ksl * 11 - max(ksl - 4, 0)) * 4 + (regs ? i / 3 * 5 + i % 3 * 2 : i < 16 ? i / 2 * 5 + 1 + i % 2 * 2 : i + 24);
    c3 = (ks & 1) * 2; ks >>= 1;
  }
  if (SYNC) { col = pinned(col); ks = pinned(ks); bar_sync(B_WG0 + wg, 256); }
  if (on) asm volatile("cp.async.bulk.tensor.5d.shared::cluster.global.tile.mbarrier::complete_tx::bytes [%0], [%1, {%2, %3, %4, %5, %6}], [%7];"
               :: "r"(sb + dst), "l"(&P.map[map]), "r"(col), "r"(0), "r"(c2), "r"(c3), "r"(ks), "r"(mb) : "memory");
}
template <int ROLE, bool SYNC = false> __device__ __forceinline__ void load_wg(const Params& P, uint32_t sb, bool regs, int wg, int quarter) {
  const int i = (threadIdx.x & 31) * 4 + quarter;
  const int n = ROLE == CHAIN ? 36 : ROLE == GROLE ? (regs ? 38 : 36) : regs ? 24 : bid() < N_CHAIN + N_G + 12 ? 20 : 16;
  const bool split = SYNC && wg == 0;
  const uint32_t mb = split && i ? sb + T_BAR : sb + W_BAR + wg * 8;
  load_box<ROLE, SYNC>(P, sb, regs, wg, i, mb, i < (ROLE == CHAIN ? (wg ? 2 : 19) : ROLE == GROLE ? n - 35 : n));
  if (i <= split) mbar_expect(mb, n * (split ? 1024 : 2048));
  __syncwarp();
}
__device__ __forceinline__ uint32_t near_half(uint32_t blk, uint32_t reader) {
  return __ldcg(g_near + (blk >> 3)) ^ (~blk & 1) ^ __ldcg(g_side + (blk >> 3)) ^ __ldcg(g_side + reader);
}

__device__ __forceinline__ uint32_t opaque_tid() { uint32_t t; asm volatile("mov.u32 %0, %%tid.x;" : "=r"(t)); return t; }
__device__ __forceinline__ void m_fetch(uint32_t sb, uint32_t src, uint32_t b, uint32_t mb) {
  bulk_load(sb + C_M + (b ? b * 4096 - 2048 : 0), (const unsigned char*)g_mimg + ((src ^ ((b & 1) * 4096)) + b * 8192), b ? 4096 : 2048, mb);
}
__device__ __forceinline__ uint32_t m_probe(uint32_t lane) { return lane * 32 + (lane & 4) * 4 + (lane >> 3) * 4; }
__device__ __forceinline__ uint32_t m_max(uint32_t a, uint32_t b) {
  return max(max(lds32(a), lds32(a + 1024)), max(lds32(b), lds32(b + 1024)));
}
template <int S0, int N> __device__ __forceinline__ void o_steps(float* d, const uint32_t* a) {
  constexpr int SD = o_ks(S0) != 0;
  if constexpr (o_reg(S0)) wg_rs16<SD>(d, a + (18 + o_slot(S0)) * 4, desc_n16(C_OI + o_ks(S0) * 512));
  else wg_ss16<SD>(d, desc_sw128(C_W + (18 + o_slot(S0)) * 2048), desc_n16(C_OI + o_ks(S0) * 512));
  if constexpr (N > 1) o_steps<S0 + 1, N - 1>(d, a);
}
template <int BASE, int KS, int N> __device__ __forceinline__ void m_steps(float* d, const uint32_t* a, uint32_t oa) {
  wg_rs16<KS != 0>(d, a + (BASE + KS / 2) * 4, desc_m(C_M + KS * 512));
  if constexpr (KS >= 36 - 2 * XR) wg_rs16<1>(d, a + (18 + XR + KS / 2) * 4, desc_m(C_M + KS * 512 + 512));
  else wg_ss16o<1, desc_sw128(C_W + (BASE + KS / 2) * 2048), desc_m(C_M + KS * 512 + 512)>(d, oa, 0);
  if constexpr (N > 2) m_steps<BASE, KS + 2, N - 2>(d, a, oa);
}

constexpr uint32_t VPAT = 0x15bbd249u;
template <int I, int R, int S> __device__ __forceinline__ void v_steps(float* d, const uint32_t* a) {
  constexpr bool reg = (VPAT >> I) & 1;
  if constexpr (reg) wg_rs16<1>(d, a + (18 + R) * 4, desc_m(C_M + R * 1024));
  else wg_ss16<1>(d, desc_sw128(C_W + (54 + S) * 2048), desc_m(C_M + S * 1024 + 512));
  if constexpr (I < 31) v_steps<I + 1, R + reg, S + !reg>(d, a);
  else static_assert(R + reg == 18, "pattern");
}

__device__ __forceinline__ void chain_proj(const Params& P, uint32_t sb) {
  const uint32_t c = chain_id(), h = c >> 1, j = c & 1, wid = __shfl_sync(~0u, threadIdx.x >> 5, 0), wg = wid >> 2, w = wid & 3;
  const uint32_t t = threadIdx.x & 127, lane = pinned(t & 31), mine = pinned(sb + t * 16), rb = mapa(sb, j ^ 1);
  const uint32_t theirs = pinned(rb + C_KM2 + w * 512 + lane * 4), oa = wg * 4608;
  uint32_t a[144 + 4 * XR];
  mbar_wait(sb + W_BAR + wg * 8, 0);
  if (threadIdx.x == 0) TS(23);
  load_frags<36>(a, sb + C_W + wg * 73728);
  fence_async_smem();
  bar_arrive(B_WG0 + wg, 256);
  if (threadIdx.x == 0) TS(24);
  bar_sync(B_WG2, 384);
  const uint32_t round = min(w, 2u) + (wg ? 0 : 3), gdly = P.dly[8 + round], ps = t >> 2, pf = j * 16 + (ps >> 1);
  uint4* const dsts = pinned(g_xb + (ps * 4096 + near_half(ps * 8, ps * 2) * 256 + c * 4 + (t & 3)));
  uint4* const dstf = pinned(g_xb + (pf * 4096 + 512 + near_half(pf * 8 + 1, pf * 2) * 256 + h * 8 + (t & 7)));
  const uint32_t* const gsrc = (const uint32_t*)g_xb + (h * 16384 + min(w, 2u) * 4096 + near_half(h * 8 + !wg, h * 2) * 1024 +
                               (wg ? lane * 4 + j * 2 : 2048 + (lane & 24) * 4 + j * 16 + (lane & 7) * 2));
  uint32_t* gdst = g_mimg + (16384 + (lane >> 4) * 1024 +
                   (wg ? (round ? 1536 + round * 512 : 0) + c * 8 + (((lane >> 1) ^ c) & 4) + (lane & 3)
                       : (round - 1) * 2048 + c * 16 + (lane & 1) * 8 + (((lane >> 1) ^ (c * 2)) & 4) + ((lane >> 1) & 3)));
  const uint32_t m0 = __ldcg(gdst - 16384);
  mbar_wait(sb + W_BAR + wg * 8, 1);
  load_frags<XR>(a + 144, sb + C_W + wg * 73728 + (18 - XR) * 2048);
  bar_sync(B_INIT, 256);
  if ((threadIdx.x & 127) == 0) TS(4);

  uint32_t ring = 1;
#pragma unroll 1
  for (int n = 0; n < STEPS; n++) {
    float d[8], e[8];
    if (n + 1 == STEPS && !wg) { bar_arrive(B_QK, 416); break; }
#pragma unroll
    for (int i = 0; i < 8; i++) e[i] = 0.f;
    uint32_t redo = n + 1;
#pragma unroll 1
    do {
      mbar_wait(sb + CB_M, n & 1);
      wg_fence();
      m_steps<0, 0, 4>(d, a, oa);
      wg_commit();
      if (wg) { wg_fence(); m_steps<18, 0, 4>(e, a, 4608); wg_commit(); }
      if (wid == 0) TR(8);
      mbar_wait(sb + CB_M + 8, n & 1);
      wg_fence();
      m_steps<0, 4, 8>(d, a, oa);
      wg_commit();
      mbar_wait(sb + CB_MV, n & 1);
      asm volatile("{.reg .pred p; .reg .u32 t; ld.shared.u32 t, [%1]; setp.eq.u32 p, t, %0; selp.u32 %0, -1, 0, p;}" : "+r"(redo) : "r"(sb + C_BAD) : "memory");
    } while (redo);
    wg_fence();
    m_steps<0, 12, 8>(d, a, oa);
    wg_commit();
    mbar_wait(sb + CB_MV + 16, n & 1);
    wg_fence();
    m_steps<0, 20, 8>(d, a, oa);
    wg_commit();
    mbar_wait(sb + CB_MV + 24, n & 1);
    wg_fence();
    m_steps<0, 28, 8>(d, a, oa);
    wg_commit();
    wg_wait<0>();
    if (w == 0) TR(6 + wg);
    const uint32_t f0 = pack2(d[0], d[1]), f1 = pack2(d[4], d[5]), f2 = pack2(d[2], d[3]), f3 = pack2(d[6], d[7]);
    stsm4(mine + C_QM + wg * 2048, f0, f1, f2, f3);
    bar_arrive(B_QK, 416);
    const uint32_t tag = (n & 1) ^ 1;
    if (n == 0) mbar_wait(sb + T_BAR, 0);
    if (wg) {
      if (n + 1 < STEPS) bar_sync(B_S, 256);
      wg_fence();
      v_steps<0, 2, 2>(e, a);
      wg_commit();
      const uint32_t k0 = j ? f0 : f1, k1 = j ? f2 : f3;
      mbar_wait(sb + CB_SX, n & 1);
      wg_wait<0>();
      if (w == 0) TR(11);
      const uint32_t v0 = pack2(e[0], e[1]), v1 = pack2(e[4], e[5]), v2 = pack2(e[2], e[3]), v3 = pack2(e[6], e[7]);
      stsm4(mine + C_VM, v0, v1, v2, v3);
      bar_arrive(B_V, 256);
      st_async1(theirs, k0, rb + CB_XX);
      st_async1(theirs + 256, k1, rb + CB_XX);
      st_async1(theirs + 128, j ? v0 : v1, rb + CB_XX);
      st_async1(theirs + 384, j ? v2 : v3, rb + CB_XX);
      if (n + 1 == STEPS) break;
      bar_sync(B_O, 256);
      fence_async_smem();
      wg_fence();
#pragma unroll
      for (int ks = 0; ks < 4; ks++) {
        if (ks == 0) wg_ss16<0>(d, desc_sw128(C_W + 32 * 2048), desc_n16(C_OI));
        else wg_ss16<1>(d, desc_sw128(C_W + (32 + ks) * 2048), desc_n16(C_OI + ks * 512));
      }
      wg_commit();
      bar_arrive(B_X, 256);
      if (w == 0) TR(0);
      wg_wait<0>();
      store_partial(dsts, pack_partial(d, tag));
      bar_arrive(B_M, 160);
      if (w == 0) TR(1);
    } else {
      bar_sync(B_X, 256);
      wg_fence();
      o_steps<0, 4>(d, a);
      wg_commit();
      o_steps<4, 4>(e, a);
      wg_commit();
      wg_wait<1>();
      store_partial(dsts + 1024, pack_partial(d, tag));
      if (w == 0) TR(2);
      wg_wait<0>();
      store_partial(dsts + 2048, pack_partial(e, tag));
      if (w == 0) TR(3);
      wg_fence();
      o_steps<8, 4>(d, a);
      wg_commit();
      bar_sync(B_T, 256);
      if (w == 0) { TRV(61, 0); TR(12); }
      wg_fence();
      o_steps<12, 4>(d, a);
      wg_commit();
      o_steps<16, 8>(e, a);
      wg_commit();
      wg_wait<1>();
      store_partial(dstf, pack_partial(d, tag));
      if (w == 0) TR(4);
      wg_fence();
      o_steps<24, 8>(d, a);
      wg_commit();
      wg_wait<1>();
      store_partial(dstf + 1024, pack_partial(e, tag));
      bar_arrive(B_OE, 256);
      if (w == 0) TR(5);
      wg_wait<0>();
      store_partial(dstf + 2048, pack_partial(d, tag));
      if (w == 0) TR(15);
    }
    if (w < 3) {
      mbar_wait(sb + CB_REF, n & 1);
      wait_until(lds32(sb + C_REF), gdly);
      gather_reduce(gsrc, gdst, m0, wg, tag, lane, sb, n, 16 + round * 4);
      if (++ring == MRING) { ring = 0; gdst -= MRING * 16384; }
      gdst += 16384;
    }
  }
}

template <int KS> __device__ __forceinline__ void x_scores(float* s, float* sm, const uint4* q, uint32_t ok, uint32_t om) {
  wg_rs32o<1, desc_sw64(C_KV + KS * 1024)>(s, q[KS].x, q[KS].y, q[KS].z, q[KS].w, ok);
  wg_rs8o<1, desc_n16(C_KM + KS * 512)>(sm, q[KS].x, q[KS].y, q[KS].z, q[KS].w, om);
  if constexpr (KS < 3) x_scores<KS + 1>(s, sm, q, ok, om);
}

__device__ __forceinline__ void chain_attn(const Params& P, uint32_t sb) {
  const int c = chain_id(), j = c & 1;
  const int tid = threadIdx.x, lane = tid & 31, w = __shfl_sync(~0u, (tid >> 5) & 3, 0);
  const int l = w >> 1, u = w & 1;
  const uint32_t rb = mapa(sb, j ^ 1);
  const float sc = 0.08838834764831845f * 1.4426950408889634f;
  const uint32_t ones = 0x3F803F80u, sx = C_SX + l * 1280;
  const uint32_t km_off = C_KM + (lane >> 3) * 256 + l * 128 + (lane & 7) * 16;
  const uint32_t qm_off = C_QM + (lane >> 4) * 256 + l * 128 + (lane & 7) * 16;
  const uint32_t kv_off = C_KV + l * 4096 + (lane & 15) * 64 + (((lane >> 4) ^ (u * 2) ^ ((lane >> 1) & 3)) << 4);

  load_wg<CHAIN, true>(P, sb, false, 1, w);
  if (lane == 0) mbar_arrive(sb + CB_M);
#pragma unroll 1
  for (int n = 0; n < STEPS; n++) {
    const uint32_t kvb = sb + kv_off + (n & 1) * 16384;
    if (w == 0 && elect()) { mbar_expect(sb + CB_SX, 2560); mbar_expect(sb + CB_OX, 2048); mbar_expect(sb + CB_XX, 2048); }
    mbar_wait(sb + CB_FULL + (n & 1) * 8, (n >> 1) & 1);
    if (n < 3 && tid == 256) TS(n ? 20 + n : 5);
    __syncwarp();
    {
      uint32_t km[8];
      uint4 kx[8];
#pragma unroll
      for (int i = 0; i < 8; i++) ldsm4t(kx[i].x, kx[i].y, kx[i].z, kx[i].w, (kvb ^ ((i & 1) * 32)) + (i >> 1) * 1024);
      mbar_wait(sb + CB_VF, n & 1);
      if (w == 1) TRD(60, kx[7].x);
      bar_sync(B_QK, 416);
      if (n + 1 == STEPS) {
        st_async4(rb + sx + u * 512 + lane * 16, 0.f, 0.f, 0.f, 0.f, rb + CB_SX);
        st_async1(rb + sx + 1024 + u * 128 + lane * 4, 0, rb + CB_SX);
        bar_sync(B_V, 256);
      } else {
      uint32_t qm[16];
#pragma unroll
      for (int ks = 0; ks < 4; ks++) ldsm4t(qm[4 * ks], qm[4 * ks + 1], qm[4 * ks + 2], qm[4 * ks + 3], sb + qm_off + ks * 512);
      ldsm4t(km[0], km[1], km[2], km[3], sb + km_off);
      ldsm4t(km[4], km[5], km[6], km[7], sb + km_off + 1024);
      float s[5][4];
      uint4 vx[4];
#pragma unroll
      for (int i = 0; i < 5; i++) { s[i][0] = s[i][1] = s[i][2] = s[i][3] = 0.f; }
#pragma unroll
      for (int ks = 0; ks < 4; ks++) {
        const uint32_t* q = qm + 4 * ks;
        if (ks == 1 || ks == 2) {
#pragma unroll
          for (int i = 2 * ks - 2; i < 2 * ks; i++) ldsm4(vx[i].x, vx[i].y, vx[i].z, vx[i].w, ((sb + kv_off) ^ ((i & 1) * 32)) + 8192 + (2 * u + (i >> 1)) * 1024);
        }
        mma16(s[1], q[0], q[1], q[2], q[3], kx[2 * ks].x, kx[2 * ks].y);
        mma16(s[2], q[0], q[1], q[2], q[3], kx[2 * ks].z, kx[2 * ks].w);
        mma16(s[0], q[0], q[1], q[2], q[3], km[2 * ks], km[2 * ks + 1]);
        mma16(s[3], q[0], q[1], q[2], q[3], kx[2 * ks + 1].x, kx[2 * ks + 1].y);
        mma16(s[4], q[0], q[1], q[2], q[3], kx[2 * ks + 1].z, kx[2 * ks + 1].w);
      }
      st_async4(rb + sx + u * 512 + lane * 16, s[1][0], s[1][1], s[2][0], s[2][1], rb + CB_SX);
      st_async1(rb + sx + 1024 + u * 128 + lane * 4, __float_as_uint(u ? s[0][1] : s[0][0]), rb + CB_SX);
      bar_arrive_after<B_S, 256>(__float_as_uint(s[3][0]), __float_as_uint(s[4][0]));
      mbar_wait(sb + CB_SX, n & 1);
      const uint4 p0 = lds128(sb + sx + u * 512 + lane * 16), p1 = lds128(sb + sx + (u ^ 1) * 512 + lane * 16);
      const uint2 p2 = make_uint2(lds32(sb + sx + 1024 + lane * 4), lds32(sb + sx + 1152 + lane * 4));
      float t[10] = {s[0][0] + __uint_as_float(p2.x), s[0][1] + __uint_as_float(p2.y),
                     s[1][0] + __uint_as_float(p0.x), s[1][1] + __uint_as_float(p0.y),
                     s[2][0] + __uint_as_float(p0.z), s[2][1] + __uint_as_float(p0.w),
                     s[3][0] + __uint_as_float(p1.x), s[3][1] + __uint_as_float(p1.y),
                     s[4][0] + __uint_as_float(p1.z), s[4][1] + __uint_as_float(p1.w)};
      float mx = fmaxf(fmaxf(fmaxf(fmaxf(t[2], t[3]), fmaxf(t[4], t[5])), fmaxf(fmaxf(t[6], t[7]), fmaxf(t[8], t[9]))), fmaxf(t[0], t[1]));
      mx = fmaxf(fmaxf(mx, __shfl_xor_sync(~0u, mx, 1)), fmaxf(__shfl_xor_sync(~0u, mx, 2), __shfl_xor_sync(~0u, mx, 3)));
      const float ms = -mx * sc;
#pragma unroll
      for (int i = 0; i < 10; i++) t[i] = ex2(fmaf(t[i], sc, ms));
      uint32_t p[5];
#pragma unroll
      for (int i = 0; i < 5; i++) p[i] = pack2(t[2 * i], t[2 * i + 1]);
      p[1] |= (p[0] & p[3] & p[4]) & 0x80008000u;
      float o[2][4], z[4] = {0.f, 0.f, 0.f, 0.f};
      mma16(z, ones, ones, ones, ones, p[1], p[2]);
#pragma unroll
      for (int i = 0; i < 2; i++) {
        o[i][0] = o[i][1] = o[i][2] = o[i][3] = 0.f;
        mma16(o[i], vx[2 * i].x, vx[2 * i].y, vx[2 * i].z, vx[2 * i].w, p[1], p[2]);
      }
      mma16(z, ones, ones, ones, ones, p[3], p[4]);
#pragma unroll
      for (int i = 0; i < 2; i++) mma16(o[i], vx[2 * i + 1].x, vx[2 * i + 1].y, vx[2 * i + 1].z, vx[2 * i + 1].w, p[3], p[4]);
      mma8(z, ones, ones, p[0]);
      bar_sync_after<B_V, 256>(p[1]);
      ldsm4(km[0], km[1], km[2], km[3], sb + km_off + (C_VM - C_KM) + u * 1024);
      mma8(o[0], km[0], km[1], p[0]);
      mma8(o[1], km[2], km[3], p[0]);
      const float i0 = rcp(z[0]), i1 = rcp(z[1]);
      const uint32_t oo = C_OI + u * 1024 + l * 128 + lane * 4;
      uint32_t ow[4];
#pragma unroll
      for (int i = 0; i < 2; i++) { ow[2 * i] = pack2(o[i][0] * i0, o[i][1] * i1); ow[2 * i + 1] = pack2(o[i][2] * i0, o[i][3] * i1); }
      stsm4(sb + C_OI + u * 1024 + l * 128 + (lane >> 3) * 256 + (lane & 7) * 16, ow[0], ow[1], ow[2], ow[3]);
      bar_arrive(B_O, 256);
#pragma unroll
      for (int i = 0; i < 4; i++) st_async1(rb + oo + 2048 + i * 256, ow[i], rb + CB_OX);
      }
    }
    {
      const uint32_t lane = opaque_tid() & 31, own = ((n & 1) * 16384 + j * 4096) >> 4;
      float s[16], sm[4];
#pragma unroll
      for (int i = 0; i < 16; i++) s[i] = sm[i & 3] = 0.f;
      {
        uint4 q[4];
        mbar_wait(sb + CB_Q, n & 1);
#pragma unroll
        for (int ks = 0; ks < 4; ks++)
          ldsm4t(q[ks].x, q[ks].y, q[ks].z, q[ks].w, sb + C_Q + (lane & 8) * 512 + ks * 1024 + (lane & 16) * 32 + (lane & 7) * 64 + (((w ^ (lane >> 1)) & 3) << 4));
        mbar_wait(sb + CB_XX, n & 1);
        if (n + 1 < STEPS) mbar_wait(sb + CB_OX, n & 1);
        fence_async_smem();
        if (n + 1 < STEPS) { bar_arrive(B_T, 256); bar_sync(B_OE, 256); }
        if (w == 1) { TRV(61, 0); TR(9); }
#pragma unroll 1
        for (uint32_t hf = 0; hf < 2; hf++) {
          wg_fence();
          x_scores<0>(s, sm, q, hf ? (C_KV2 - C_KV) >> 4 : own, hf ? (C_KM2 - C_KM) >> 4 : j * 8);
          wg_commit();
          wg_wait<0>();
#pragma unroll
          for (int ks = 0; ks < 4; ks++) asm volatile("mov.b32 %0, %1; mov.b32 %2, %3;" : "+r"(q[ks].x), "+r"(q[ks].y), "+r"(q[ks].z), "+r"(q[ks].w));
        }
      }
      const float neg = -1e9f * 11.313708498984761f;
      const int tok = (lane & 24) + 2 * w + ((lane >> 2) & 1), lim = tok - 8 * (int)(lane & 3);
      float t[10] = {sm[0], sm[1]};
#pragma unroll
      for (int i = 0; i < 8; i++) t[2 + i] = i > lim ? neg : s[(i >> 1) * 4 + (i & 1)];
      float mx = fmaxf(fmaxf(fmaxf(fmaxf(t[2], t[3]), fmaxf(t[4], t[5])), fmaxf(fmaxf(t[6], t[7]), fmaxf(t[8], t[9]))), fmaxf(t[0], t[1]));
      mx = fmaxf(fmaxf(mx, __shfl_xor_sync(~0u, mx, 1)), fmaxf(__shfl_xor_sync(~0u, mx, 2), __shfl_xor_sync(~0u, mx, 3)));
      const float ms = -mx * sc;
#pragma unroll
      for (int i = 0; i < 10; i++) t[i] = ex2(fmaf(t[i], sc, ms));
      uint32_t p[5];
#pragma unroll
      for (int i = 0; i < 5; i++) p[i] = pack2(t[2 * i], t[2 * i + 1]);
      float z = ((t[0] + t[1]) + (t[2] + t[3])) + ((t[4] + t[5]) + (t[6] + t[7])) + (t[8] + t[9]);
      const uint32_t row = sb + C_OS + tok * 128 + (((lane & 3) ^ (tok & 7)) << 4);
#pragma unroll 1
      for (uint32_t hf = 0; hf < 2; hf++) {
        float o[32];
        const uint32_t vo = hf ? (C_KV2 + 4096 - C_KV - 8192) >> 4 : j * 256;
        wg_fence();
        wg_rs64o<0, desc_sw64(C_KV + 8192)>(o, p[1], p[1], p[2], p[2], vo);
        wg_rs64o<1, desc_sw64(C_KV + 8192 + 32)>(o, p[3], p[3], p[4], p[4], vo);
        wg_rs64o<1, mkdesc(C_VM, 128, 256, 0)>(o, p[0], p[0], 0, 0, hf ? (C_VM2 - C_VM) >> 4 : j * 8);
        wg_commit();
        if (hf) {
          if (elect()) mbar_arrive(sb + CB_M);
        } else {
          z += __shfl_xor_sync(~0u, z, 1);
          z = rcp(z + __shfl_xor_sync(~0u, z, 2));
        }
        wg_wait<0>();
#pragma unroll
        for (int qq = 0; qq < 2; qq++) {
          const float* r = o + 16 * qq;
          sts128((row ^ (qq * 64)) + hf * 4096,
                 make_uint4(pack2(r[0] * z, r[1] * z), pack2(r[4] * z, r[5] * z), pack2(r[8] * z, r[9] * z), pack2(r[12] * z, r[13] * z)));
        }
      }
      bar_arrive(B_G, 160);
      if (n + 1 < STEPS) bar_arrive(B_R, 160);
      if (w == 1) TR(10);
    }
  }
  if ((threadIdx.x & 127) == 0) TS(6);
}

__device__ __forceinline__ void chain_aux(const Params& P, uint32_t sb) {
  const uint32_t c = chain_id(), j = c & 1, lane = threadIdx.x & 31, w = __shfl_sync(~0u, (threadIdx.x >> 5) & 3, 0);
  load_wg<CHAIN, true>(P, sb, false, 0, w);
  if (threadIdx.x == 384) TS(25);
  if (threadIdx.x == 384) grid_wait(1, lds32(sb + S_GEN));
  bar_sync(B_WG2, 384);
  if (threadIdx.x == 384) TS(13);
  if (w == 0) {
    const uint32_t* fg = g_fl + FL_G + near_half(XB_F, c) * 1024 + (c >> 1) * 8;
#pragma unroll 1
    for (int n = 0; n < STEPS; n++) {
      const unsigned char* blk = g_qkv + (uint32_t)((n % QRING) * (N_CHAIN * 24576));
      const uint32_t t1 = clk(), kb = sb + CB_FULL + (n & 1) * 8, kv = sb + C_KV + (n & 1) * 16384;
      uint32_t t0 = t1 - 100000, x = 0;
      if (n > 0) {
        wait_until(t1, KMIN);
        do asm volatile("ld.relaxed.gpu.global.u32 %0, [%1];" : "=r"(x) : "l"(fg) : "memory"); while (x <= n && clk() - t1 < KWIN);
        if (x > n) {
          asm volatile("fence.acquire.gpu;" ::: "memory");
          fence_async_global();
          if (elect()) { mbar_expect(kb, 8192); bulk_load(kv, blk + c * 24576, 8192, kb); }
        }
        T3(0); CNT(12, 1 + (x <= n));
        mbar_wait(sb + CB_REF, (n - 1) & 1);
        t0 = lds32(sb + C_REF);
        wait_until(t0, DLYK - 500);
      }
      wait_flags(fg + min(lane, 2u) * 256, n + 1);
      T3(2);
      fence_async_global();
      if (n > 0) bar_sync(B_R, 160);
      wait_until(t0, DLYK);
      if (elect()) {
        if (x <= n) { mbar_expect(kb, 8192); bulk_load(kv, blk + c * 24576, 8192, kb); }
        mbar_expect(sb + CB_VF, 8192);
        bulk_load(sb + C_KV + 8192, blk + (c * 24576 + 8192), 8192, sb + CB_VF);
        mbar_expect(sb + CB_Q, 16384);
        bulk_load(sb + C_Q, blk + (c * 24576 + 16384), 8192, sb + CB_Q);
        bulk_load(sb + C_KV2, blk + ((c ^ 1) * 24576 + j * 4096), 4096, sb + CB_Q);
        bulk_load(sb + C_KV2 + 4096, blk + ((c ^ 1) * 24576 + 8192 + j * 4096), 4096, sb + CB_Q);
      }
      T3(1);
      T3(3);
    }
  } else {
    const uint32_t near = __ballot_sync(~0u, near_half(XB_M + min(lane, MRING - 1u) * 8, c));
    uint32_t ring = 0;
    if (w > 1) {
      const uint32_t odd = w & 1, chk = pinned(sb + C_M + odd * 2048 + m_probe(lane)), again = sb + CB_MV + 32 + odd * 8;
      const bool one = elect();
      uint32_t mph = 0;
#pragma unroll 1
      for (int n = 0; n <= STEPS; n++) {
#pragma unroll
        for (int k = 0; k < 3; k++) {
          if (n == STEPS || (k == 2 && odd)) break;
          const uint32_t b = 2 * k + odd, at = chk + (k ? k * 8192 - 2048 + odd * 2048 : 0);
          uint32_t mb = sb + CB_M + b * 8, ph = n & 1;
          int it = 1;
          while (true) {
            mbar_wait(mb, ph);
            const bool bad = __any_sync(~0u, m_max(at, b ? at + 2048 : at) == SENT);
            if (one && !bad) mbar_arrive(sb + CB_MV + (b > 2 ? b * 8 - 8 : 0));
            if (!bad) break;
            mb = again; ph = mph; mph ^= 1;
            if (one) {
              if (k == 0) sts32(sb + C_BAD, n + 1);
              mbar_expect(mb, b ? 4096 : 2048);
              m_fetch(sb, ring * 65536 + ((near >> ring) & 1) * 4096, b, mb);
            }
            __syncwarp();
            spin_guard(it);
          }
          TR(41 + b * 4); CNT(6 + b, it);
        }
        ring = ring + 1 == MRING ? 0 : ring + 1;
        if (!odd) {
          if (n < STEPS) { TRSYNC(); TRDUMP(n - 2); }
        } else {
          unsigned char* o = g_oimg + (uint32_t)(((n - 1) & (RING - 1)) * (N_CHAIN * 8192) + j * 4096);
          if (n > 0) bar_sync(B_G, 160);
          fence_async_smem();
          if (one) {
            if (n > 0) {
              bulk_store(o + c * 8192, sb + C_OS, 4096);
              bulk_store(o + (c ^ 1) * 8192, sb + C_OS + 4096, 4096);
              asm volatile("cp.async.bulk.commit_group;\ncp.async.bulk.wait_group.read 0;" ::: "memory");
              { const int n_ = n - 1; { const int n = n_; T3(4); (void)n; } }
            }
            mbar_arrive(sb + CB_Q);
            if (n > 0) {
              bulk_done_inc(g_fl + FL_O + c);
              { const int n_ = n - 1; { const int n = n_; T3(5); (void)n; } }
            }
          }
          __syncwarp();
        }
      }
    } else {
      const uint32_t* ts = g_fl + FL_SYNC + near_half(XB_F + 1, c) * 1024 + lane * 2;
      uint32_t t0 = clk() - 100000, last = 0;
      int lag = 0;
#pragma unroll 1
      for (int n = 0; n < STEPS; n++) {
        const uint32_t src = ring * 65536 + ((near >> ring) & 1) * 4096;
        if (lane < 5) mbar_expect(sb + CB_M + lane * 8, lane ? 4096 : 2048);
        __syncwarp();
        if (elect()) {
#pragma unroll
          for (int b = 0; b < 5; b++) {
            wait_until(t0, P.dly[14 + b]);
            m_fetch(sb, src, b, sb + CB_M + b * 8);
            TR(40 + b * 4);
          }
        }
        __syncwarp();
        ring = ring + 1 == MRING ? 0 : ring + 1;
        uint32_t va, vb;
        const uint32_t off = timer_offset(), tag = (uint32_t)(n + 1) << 28;
        if (n > 1) lag += (int)(off - last) - (lag >> 2);
        last = off;
        const uint32_t mine = min(max((lag >> 3) + 256, 0), 511);
        bar_sync(B_QK, 416);
        if (n + 1 == STEPS) break;
        sts32(sb + C_REF + 4, 0);
        const uint32_t c0 = clk(), stamp = c0 + off;
        st_relaxed_if(g_fl + FL_SYNC + lane * 1024 + c, tag | (mine << 19) | (stamp & 0x7FFFF), lane < 2);
        TR(13);
        wait_until(c0, DLYS);
        int it = 0;
        do {
          asm volatile("ld.relaxed.gpu.global.v2.u32 {%0,%1}, [%2];" : "=r"(va), "=r"(vb) : "l"(ts) : "memory");
          spin_guard(it);
        } while (__any_sync(~0u, ((va ^ tag) | (vb ^ tag)) >> 28));
        const int late = __reduce_max_sync(~0u, max((int)((va - stamp) << 13), (int)((vb - stamp) << 13))) >> 13;
        const uint32_t fast = min(((__reduce_max_sync(~0u, max(va, vb)) >> 19) & 511) - mine, 100u);
        t0 = c0 + min((uint32_t)late, clk() - c0);
        if (elect()) {
          sts32(sb + C_REF, t0 + (fast * 3 >> 2));
          mbar_arrive(sb + CB_REF);
        }
        st_relaxed_if(g_fl + FL_TICK + lane * 1024, (uint32_t)(n + 1) << 24 | ((t0 + off) & 0xFFFFFF), c == 0 && lane < 2);
        t0 += fast * 5 >> 2;
        TRV(59, fast);
        TR(14); CNT(11, it);
        bar_sync(B_M, 160);
      }
    }
  }
}

template <int WG>
__device__ __forceinline__ void g_math(const Params& P, uint32_t sb) {
  const int q = g_unit(WG);
  const int lane = threadIdx.x & 31, w = (threadIdx.x >> 5) & 3;
  uint32_t a[136];
  {
    const uint32_t stage = sb + G_W + WG * 73728;
    mbar_wait(sb + W_BAR + WG * 8, 0);
    if (threadIdx.x == 0) TS(23);
    load_frags<34>(a, stage);
    fence_async_smem();
    bar_sync(B_WG0 + WG, 128);
    if (threadIdx.x == 0) TS(24);
    load_wg<GROLE>(P, sb, false, WG, w);
    if (threadIdx.x == 0) TS(25);
    mbar_wait(sb + W_BAR + WG * 8, 1);
  }
  if ((threadIdx.x & 127) == 0) TS(4);
  const uint32_t off0 = (q & 31) * 49152 + (q >> 5) * 8192 + w * 1024 + (lane >> 2) * 64 + (((lane ^ (lane >> 3)) & 3) << 4);
  const uint32_t isq = q >> 6;
#pragma unroll 1
  for (int n = 0; n < STEPS; n++) {
    float d0[32], d1[32];
    if (WG == 0 && n >= LOCK0) bar_sync(B_OE, 160);
    if (n > 0) bar_sync(B_V + WG, 256);
#pragma unroll
    for (int ch = 0; ch < 9; ch++) {
      mbar_wait(sb + G_BAR + ch * 8, n & 1);
      if (ch == 0) { if ((threadIdx.x & 127) == 0) T3(5 + WG * 3); __syncwarp(); }
      if (ch == 4) { if ((threadIdx.x & 127) == 0) T3(6 + WG * 3); __syncwarp(); }
      if (ch == 8 && (WG == 0 ? n > 0 : n + 1 < STEPS)) bar_arrive(B_V + (WG ^ 1), 256);
      wg_fence();
#pragma unroll
      for (int kk = 0; kk < 4; kk++) {
        const int i = ch * 4 + kk;
        float* d = i & 1 ? d1 : d0;
        const uint64_t db = desc_sw128(G_RING + ch * 8192 + (kk & 2) * 32);
        if (i < 2) wg_rs64<0>(d, a + i * 4, db);
        else if (i < 34) wg_rs64<1>(d, a + i * 4, db);
        else wg_ss64<1>(d, desc_sw128(G_W2 + WG * 4096 + (i - 34) * 2048), db);
        wg_ss64<1>(d, desc_sw128(G_W + WG * 73728 + i * 2048), db + 2);
      }
      wg_commit();
      if (ch > 0) { wg_wait<1>(); if (lane == 0) mbar_arrive(sb + G_BAR + 128 + (ch - 1) * 8); }
    }
    wg_wait<0>();
    if (lane == 0) mbar_arrive(sb + G_BAR + 128 + 8 * 8);
    if ((threadIdx.x & 127) == 0) T3(7 + WG * 3);
    __syncwarp();
    uint32_t tw = clk() + (n == 0 ? 0u - 100000u : WG ? 0u : DLYW);
    unsigned char* base = g_qkv + (size_t)(n & (QRING - 1)) * (N_CHAIN * 24576);
#pragma unroll
    for (int i = 0; i < 8; i++) {
      const float* d = (i < 4 ? d0 : d1) + 8 * (i & 2) + 2 * (i & 1);
      wait_until(tw, 0); tw += P.dly[2 + WG];
      *(uint4*)(base + (off0 + (i < 2 ? 0 : i < 4 ? 4096 + isq * 24576 : i < 6 ? 24576 - isq * 20480 : 28672 - isq * 4096)) + (i & 1) * 512) =
        make_uint4(pack2(d[0], d[1]), pack2(d[4], d[5]), pack2(d[8], d[9]), pack2(d[12], d[13]));
    }
    bar_sync(B_M + WG, 160);
  }
}

__device__ __forceinline__ void fill16(void* p, uint32_t v) {
  asm volatile("st.global.v4.u32 [%0], {%1,%1,%1,%1};" :: "l"(p), "r"(v) : "memory");
}
__device__ __forceinline__ void g_load(const Params& P, uint32_t sb) {
  const int lane = threadIdx.x & 31, w = __shfl_sync(~0u, (threadIdx.x >> 5) & 3, 0);
  if (w == 2) return;
  if (w < 2) { bar_sync(15, 192); fence_async_smem(); }
  uint32_t fl = 0;
#pragma unroll 1
  for (int n = w == 3 ? LOCK0 : 0; n < STEPS; n++) {
    if (w && n == LOCK0) { grid_wait(1, lds32(sb + S_GEN)); fl = near_half(XB_F, bid()) * 1024; }
    if (w == 3) {
      const uint32_t tag = (uint32_t)(n - LOCK0 + 1) << 24;
      uint32_t v; int it = 0;
      do { asm volatile("ld.relaxed.gpu.global.u32 %0, [%1];" : "=r"(v) : "l"(g_fl + fl + FL_TICK) : "memory"); spin_guard(it); } while (v < tag);
      const uint32_t off = timer_offset(), now = clk(), t0 = now - ((v ^ tag) >> 24 ? DLYG : (now + off - v) & 0xFFFFFF);
      asm volatile("fence.acquire.gpu;" ::: "memory");
      if (lane == 0) T3(11);
      __syncwarp();
      wait_until(t0, DLYG);
      if (lane == 0) T3(4);
      bar_sync(B_OE, 160);
      continue;
    }
    if (w == 0 || n == 0) {
      if (n < NSEG) wait_flags(g_lnflag + n * 16 + (lane & 1) * 8, 1);
    } else if (n >= LAG) {
      wait_flags(g_fl + fl + FL_F + (lane & 1) * 8, n - LAG + 1);
    }
    if (w) { if (lane == 0) T3(12); bar_sync(B_X, 96); }
    fence_async_global();
    const unsigned char* src = g_lnimg + (uint32_t)((w ? (n >= LAG ? NSEG + n - LAG : 0) : min(n, NSEG - 1)) * 36864);
#pragma unroll 1
    for (int ch = 0; ch < 9; ch++) {
      const uint32_t full = sb + G_BAR + ch * 8;
      mbar_wait(full + 128, (n & 1) ^ 1);
      if (elect()) {
        mbar_expect(full, 4096);
        bulk_load(sb + G_RING + ch * 8192 + w * 4096, src + ch * 4096, 4096, full);
      }
    }
  }
}

__device__ __forceinline__ void g_aux(const Params& P, uint32_t sb) {
  const int lane = threadIdx.x & 31, w = (threadIdx.x >> 5) & 3;
  if (w == 1 || w == 2) {
    const int q = g_unit(w - 1);
    uint32_t* f = g_fl + FL_G + q * 8;
#pragma unroll 1
    for (int n = 0; n < STEPS; n++) {
      const uint32_t ln = opaque_tid() & 31;
      uint4* z = (uint4*)g_oacc + (uint32_t)(((n + 1) % ARING) * (16 * DM) + q * 96 + ln);
      fill16(z, 0); fill16(z + 32, 0); fill16(z + 64, 0);
      if (n + 3 >= MRING && q < 80) fill16((uint4*)g_mimg + (uint32_t)(((n + 3) % MRING) * 4096 + q * 32 + ln), SENT);
      bar_sync(B_M + (w - 1), 160);
      if (lane == 0) { T3(w * 2 - 2); fence_async_global(); flag_release(f, n + 1); T3(w * 2 - 1); }
      __syncwarp();
    }
  } else {
    const uint32_t u = (bid() - N_CHAIN) * 2 + (w & 1), r = u / 36 * 16 + (u & 3) * 4 + (lane >> 3);
    uint32_t o = r * (DM / 8) + (u % 36 >> 2) * 8 + ((lane & 7) ^ ((r >> 1) & 3)), fl = 0;
#pragma unroll 1
    for (int k = -LAG - 1; k < STEPS; k++) {
      if (k < NSEG - 1) bar_sync(B_X, 96);
      if (k < LAG || u >= 72) continue;
      if (k == NSEG - 1) { fl = near_half(XB_F, bid()) * 1024; wait_flags(g_fl + fl + FL_F + (lane & 1) * 8, NSEG + 1); }
      const uint4 x = __ldcg((const uint4*)P.out + o);
      if (k >= NSEG - 1) wait_flags(g_fl + fl + FL_OCNT + (max(k, NSEG) % OCRING) * 8, N_O * 3 * (max(k, NSEG) / OCRING + 1));
      const float4* a = (const float4*)g_oacc + ((k % ARING) * (16 * DM) + 8 * DM + u * 64 + lane * 2);
      const float4 p = __ldcg(a), v = __ldcg(a + 1);
      ((uint4*)P.out)[o] = make_uint4(badd2(x.x, pack2(p.x, p.y)), badd2(x.y, pack2(p.z, p.w)), badd2(x.z, pack2(v.x, v.y)), badd2(x.w, pack2(v.z, v.w)));
      o += 4 * DM;
    }
    if ((threadIdx.x & 127) == 0) TS(7);
  }
}

template <int WG, bool HALF, int KS, int N> __device__ __forceinline__ void o_mma(float* d, const uint32_t* a, uint32_t ob) {
  constexpr uint64_t db = desc_sw128(O_RING + (KS >> 2) * 8192 + (KS & 3) * 32);
  constexpr uint64_t da = desc_sw128(O_W + WG * 40960 + (KS < 40 ? KS / 5 * 2 + KS % 5 / 2 : KS - 24) * 2048);
  if constexpr (KS < 40 && !(KS % 5 & 1)) {
    const uint32_t* r = a + (KS / 5 * 3 + KS % 5 / 2) * 4;
    if constexpr (HALF) wg_rs32k<KS != 0, db>(d, r[0], r[1], r[2], r[3], ob); else wg_rs64<KS != 0>(d, r, db);
  } else {
    if constexpr (HALF) wg_ss32k<da, db>(d, ob); else wg_ss64<1>(d, da, db);
  }
  if constexpr (N > 1) o_mma<WG, HALF, KS + 1, N - 1>(d, a, ob);
}
template <int WG, bool HALF, int GR> __device__ __forceinline__ void o_groups(float* d, const uint32_t* a, uint32_t sb, int n, bool more) {
  const uint32_t ob = n < NSEG ? 0 : 256;
  mbar_wait(sb + O_BAR + GR * 8, n & 1);
  if (GR == 0) { if ((threadIdx.x & 127) == 0) T3(13 + WG); __syncwarp(); }
  if (GR == (WG == 0 ? 2 : 4) && (WG < 2 || n + 1 < STEPS)) bar_arrive(B_V + (WG + 1) % 3, 256);
  wg_fence();
  o_mma<WG, HALF, GR * 8, 8>(d, a, ob);
  if (GR == 4 && more) o_mma<WG, HALF, 40, 4>(d, a, ob);
  wg_commit();
  if (GR > 0) { wg_wait<1>(); if ((threadIdx.x & 31) == 0) mbar_arrive(sb + O_BAR + 120 + GR * 8); }
  if constexpr (GR < 4) o_groups<WG, HALF, GR + 1>(d, a, sb, n, more);
}
template <int WG, bool HALF> __device__ __forceinline__ void o_step(const uint32_t* a, uint32_t sb, uint32_t st0, int n, bool more) {
  float d[HALF ? 16 : 32];
  if (WG > 0 || n > 0) bar_sync(B_V + WG, 256);
  o_groups<WG, HALF, 0>(d, a, sb, n, more);
  wg_wait<0>();
  if ((threadIdx.x & 31) == 0) mbar_arrive(sb + O_BAR + 128 + 4 * 8);
  if ((threadIdx.x & 127) == 0) T3(WG == 0 ? 1 : WG == 1 ? 8 : 12);
  __syncwarp();
#pragma unroll(HALF ? 1 : 2)
  for (int sl = 0; sl < 2; sl++) {
    mbar_wait(sb + OB_ST + WG * 16 + sl * 8, (n & 1) ^ (WG == 0));
    if (!HALF || sl == (n >= NSEG)) {
#pragma unroll
      for (int nb = 0; nb < 4; nb++) {
        const float* r = d + (HALF ? 0 : sl * 16) + nb * 4;
        const uint32_t ad = st0 + sl * 8192 + nb * 2048;
        sts32(ad, __float_as_uint(r[0]));
        sts32(ad + 256, __float_as_uint(r[1]));
        sts32(ad ^ 32, __float_as_uint(r[2]));
        sts32((ad ^ 32) + 256, __float_as_uint(r[3]));
      }
      fence_async_smem();
    }
    bar_arrive((sl ? B_G : B_M) + WG, 160);
  }
}
template <int WG>
__device__ __forceinline__ void o_math(const Params& P, uint32_t sb) {
  const bool more = bid() < N_CHAIN + N_G + 12;
  const int lane = threadIdx.x & 31, w = (threadIdx.x >> 5) & 3, g = lane >> 2, tq = lane & 3;
  uint32_t a[96];
  mbar_wait(sb + W_BAR + WG * 8, 0);
  load_frags<24>(a, sb + WG * 49152);
  fence_async_smem();
  bar_sync(B_INIT, 416);
  load_wg<OROLE>(P, sb, false, WG, w);
  mbar_wait(sb + W_BAR + WG * 8, 1);
  if ((threadIdx.x & 127) == 0) TS(4);
  const uint32_t st0 = sb + O_ST + tq * 512 + ((w * 16 + g) ^ (tq * 8)) * 4;
#pragma unroll 1
  for (int n = 0; n < STEPS; n++) {
    if (n < LAG || n >= NSEG) o_step<WG, true>(a, sb, st0, n, more); else o_step<WG, false>(a, sb, st0, n, more);
  }
}

__device__ __forceinline__ void o_aux(const Params& P, uint32_t sb) {
  const int i = bid() - N_CHAIN - N_G, ksl = i / 3;
  const int c0 = ksl * 11 - max(ksl - 4, 0), nc = ksl < 4 ? 11 : 10;
  const int lane = threadIdx.x & 31, w = __shfl_sync(~0u, (threadIdx.x >> 5) & 3, 0);
  if (w == 0) {
    bar_sync(B_INIT, 416);
    const uint32_t* f = g_fl + FL_O + near_half(XB_F + 1, bid()) * 1024 + min((c0 & ~1) + lane, (c0 + nc - 1) | 1);
#pragma unroll 1
    for (int n = 0; n < STEPS; n++) {
      const unsigned char* src = g_oimg + (uint32_t)(((n % RING) * N_CHAIN + c0) * 8192);
      wait_flags(f, n + 1);
      fence_async_global();
      if (lane == 0) T3(0);
#pragma unroll
      for (int gr = 0; gr < 5; gr++) {
        const uint32_t full = sb + O_BAR + gr * 8, bytes = (gr < 4 ? 2 : nc - 8) * 8192;
        mbar_wait(full + 128, (n & 1) ^ 1);
        if (elect()) {
          if (n < LAG || n >= NSEG) {
            mbar_expect(full, bytes >> 1);
            for (uint32_t o = gr * 16384 + (n < LAG ? 0 : 4096); o < gr * 16384 + bytes; o += 8192) bulk_load(sb + O_RING + o, src + o, 4096, full);
          } else {
            mbar_expect(full, bytes);
            bulk_load(sb + O_RING + gr * 16384, src + gr * 16384, bytes, full);
          }
        }
      }
    }
  } else {
#pragma unroll 1
    for (int n = 0; n < STEPS; n++) {
      float* dst = g_oacc + (uint32_t)((n % ARING) * (64 * DM) + ((i % 3) * 3 + (w - 1 + ksl) % 3) * 1024);
      const bool early = w == 3 && n < NSEG;
      bar_sync(B_M + (w - 1), 160);
      if (lane == 0) {
        T3(w * 2);
        if (n < NSEG) { bulk_reduce(dst, sb + O_ST, 4096); bulk_reduce(dst + 16 * DM, sb + O_ST + 4096, 4096); }
        asm volatile("cp.async.bulk.commit_group;" ::: "memory");
        if (early) {
          asm volatile("cp.async.bulk.wait_group.read 0;" ::: "memory");
          mbar_arrive(sb + OB_ST);
          T3(8 + w);
          bulk_done_inc(g_fl + FL_OCNT + (n % OCRING) * 8);
          T3(w * 2 + 1);
        }
      }
      __syncwarp();
      bar_sync(B_G + (w - 1), 160);
      if (lane == 0) {
        if (n >= LAG) { bulk_reduce(dst + 32 * DM, sb + O_ST + 8192, 4096); bulk_reduce(dst + 48 * DM, sb + O_ST + 12288, 4096); }
        asm volatile("cp.async.bulk.commit_group;\ncp.async.bulk.wait_group.read 1;" ::: "memory");
        if (!early) mbar_arrive(sb + OB_ST + (w % 3) * 16);
        asm volatile("cp.async.bulk.wait_group.read 0;" ::: "memory");
        mbar_arrive(sb + OB_ST + (w % 3) * 16 + 8);
        if (!early) {
          T3(8 + w);
          bulk_done_inc(g_fl + FL_OCNT + (n % OCRING) * 8);
          T3(w * 2 + 1);
        }
      }
      __syncwarp();
    }
  }
}

constexpr uint32_t Y_PITCH = 1168, Y_ROWS = 16 * Y_PITCH;
template <int R> __device__ __forceinline__ void y_rows(uint32_t* y, uint32_t src, uint32_t dst, int w, int bar) {
  const int lane = threadIdx.x & 31;
#pragma unroll
  for (int k = 0; k < 2 * R + 1; k++) {
    const int op = w + k * (16 / R);
    if (k == 2 * R && w >= 4) break;
    uint32_t a, b, c, d;
    ldsm4t(a, b, c, d, src + op * 512 + (lane & 16) * 16 + (lane & 7) * 32 + (lane & 8) * 2);
    stsm4(dst + (lane & 15) * Y_PITCH + op * 32 + (lane & 16), a, b, c, d);
  }
  bar_sync(bar, 512 / R);
  const uint32_t row = dst + ((w & 6) * 2 + (w >> 3) * 2 + (w & 1)) * Y_PITCH + lane * 4;
#pragma unroll
  for (int i = 0; i < 9 * R; i++) y[i] = lds32(row + i / 9 * 2 * Y_PITCH + i % 9 * 128);
}

__device__ __forceinline__ void f_role(const Params& P, uint32_t sb) {
  const int lane = threadIdx.x & 31, w = __shfl_sync(~0u, threadIdx.x >> 5, 0), r0 = (bid() - N_CHAIN - N_G - N_O) * 16;
  if (w == 8) {
    const uint32_t* fo = g_fl + FL_OCNT + near_half(XB_F, bid()) * 1024;
    fence_async_global();
#pragma unroll 1
    for (int n = 0; n < NSEG; n++) {
      bar_sync(2, 288);
      if (elect()) {
        mbar_expect(sb + F_BAR, 36864);
        bulk_load(sb + F_XY, P.X + (size_t)(n * 32 + r0) * DM, 18432, sb + F_BAR);
        bulk_load(sb + F_XY + 18432, g_yT + (size_t)(n * 32 + r0) * DM, 18432, sb + F_BAR);
        mbar_expect(sb + F_BAR + 8, 36864);
        T3(1);
      }
      wait_flags(fo + (n % OCRING) * 8, N_O * 3 * (n / OCRING + 1));
      fence_async_global();
      if (elect()) { bulk_load(sb + F_A, g_oacc + (uint32_t)((n % ARING) * (64 * DM) + r0 * DM), 36864, sb + F_BAR + 8); T3(0); }
    }
  } else if (w == 9) {
#pragma unroll 1
    for (int n = 0; n < NSEG; n++) {
      const uint32_t st = sb + (n & 1) * 36864;
      unsigned char* p = g_lnimg + (uint32_t)((NSEG + n) * 36864 + r0 * 128);
      bar_sync(1, 288);
      if (elect()) {
        T3(2);
#pragma unroll
        for (int i = 0; i < 9; i++) bulk_store(p + i * 4096, st + F_L + i * 2048, 2048);
        asm volatile("cp.async.bulk.commit_group;" ::: "memory");
        bulk_done_inc(g_fl + FL_F + (bid() & 1) * 8);
        T3(3);
        bulk_store(P.out + (size_t)(n * 32 + r0) * DM, st + F_X, 18432);
        asm volatile("cp.async.bulk.commit_group;\ncp.async.bulk.wait_group.read 0;" ::: "memory");
        if (n + 1 == NSEG) bulk_done_inc(g_fl + FL_F + (bid() & 1) * 8);
      }
      __syncwarp();
    }
  } else if (w < 8) {
    const uint32_t row = sb + w * 1152 + lane * 4, acc = sb + F_A + w * 256 + (lane ^ ((w & 6) * 2)) * 8;
    const uint32_t ln = sb + F_L + w * 128 + (((lane >> 2) ^ w) << 4) + (lane & 3) * 4;
#pragma unroll 1
    for (int n = -1; n < NSEG; n++) {
      const uint32_t st = (n & 1) * 36864;
      uint32_t x[18], y[18], l[18];
      if (n >= 0) mbar_wait(sb + F_BAR, n & 1);
#pragma unroll
      for (int i = 0; i < 18; i++) x[i] = lds32(row + F_XY + i / 9 * 9216 + i % 9 * 128);
      y_rows<2>(y, sb + F_XY + 18432, sb + F_Y, w, 3);
      layernorm9<2>(x, l);
#pragma unroll
      for (int i = 0; i < 18; i++) x[i] = badd2(x[i], bmul2(l[i], y[i]));
      if (n >= 0) mbar_wait(sb + F_BAR + 8, n & 1);
      if (threadIdx.x == 0 && n >= 0) T3(4);
      __syncwarp();
      uint2 a[18];
#pragma unroll
      for (int i = 0; i < 18; i++) a[i] = lds64(acc + i / 9 * 2048 + i % 9 * 4096);
#pragma unroll
      for (int i = 0; i < 18; i++) x[i] = badd2(x[i], pack2(__uint_as_float(a[i].x), __uint_as_float(a[i].y)));
      if (n + 1 < NSEG) bar_arrive(2, 288);
      layernorm9<2>(x, l);
#pragma unroll
      for (int i = 0; i < 18; i++) { x[i] = badd2(x[i], bmul2(l[i], y[i])); sts32(row + st + F_X + i / 9 * 9216 + i % 9 * 128, x[i]); }
      layernorm9<2>(x, l);
#pragma unroll
      for (int i = 0; i < 18; i++) sts32(ln + st + i / 9 * 1024 + i % 9 * 2048, l[i]);
      fence_async_smem();
      if (n >= 0) bar_sync(1, 288); else bar_sync(3, 256);
    }
  }
}

constexpr uint32_t P_CH = 147456, P_CHSZ = 12800, P_H = 4352;
static_assert(P_CH + 6 * P_CHSZ <= G_BAR, "prologue smem");

template <int N>
__device__ __forceinline__ void conv_fold(float (*acc)[4], bool hi, uint32_t mine, uint32_t theirs, int bar, int cnt) {
#pragma unroll
  for (int i = 0; i < N / 2; i++) {
    uint4 v;
    v.x = __float_as_uint(hi ? acc[i][0] : acc[i + N / 2][0]); v.y = __float_as_uint(hi ? acc[i][1] : acc[i + N / 2][1]);
    v.z = __float_as_uint(hi ? acc[i][2] : acc[i + N / 2][2]); v.w = __float_as_uint(hi ? acc[i][3] : acc[i + N / 2][3]);
    sts128(mine + i * 512, v);
  }
  bar_sync(bar, cnt);
#pragma unroll
  for (int i = 0; i < N / 2; i++) {
    const uint4 v = lds128(theirs + i * 512);
    acc[i][0] = (hi ? acc[i + N / 2][0] : acc[i][0]) + __uint_as_float(v.x); acc[i][1] = (hi ? acc[i + N / 2][1] : acc[i][1]) + __uint_as_float(v.y);
    acc[i][2] = (hi ? acc[i + N / 2][2] : acc[i][2]) + __uint_as_float(v.z); acc[i][3] = (hi ? acc[i + N / 2][3] : acc[i][3]) + __uint_as_float(v.w);
  }
}
template <int N>
__device__ __forceinline__ void conv_store(const float (*acc)[4], int tile0, uint32_t su, int d, uint32_t dd) {
  const int lane = threadIdx.x & 31, g = lane >> 2, tq = lane & 3;
#pragma unroll
  for (int i = 0; i < N; i++) {
    const uint32_t ad = su + (8 + (tile0 + i) * 8 + g) * 32 + tq * 4, sw = (g & 4) << 2;
    const uint32_t lo = badd2(movmat(pack2(acc[i][0], acc[i][1])), bmul2(lds32(ad + sw), dd));
    const uint32_t hi = badd2(movmat(pack2(acc[i][2], acc[i][3])), bmul2(lds32(ad + (sw ^ 16)), dd));
    ((uint2*)g_yT)[(((tile0 + i) * 8 + g) * DM + d) * 4 + tq] = make_uint2(lo, hi);
  }
}

__device__ __forceinline__ void prologue(const Params& P, uint32_t sb) {
  const int b = bid(), tid = threadIdx.x, lane = tid & 31, warp = tid >> 5, t0 = b * 16;
  const bool isg = b >= N_CHAIN && b < N_CHAIN + N_G;
  const int nch = isg ? 2 : b < 128 ? 6 : 0, chb = b < N_CHAIN ? b * 6 : isg ? b * 2 + 256 : b * 6 - 192;
  const uint32_t tstart = clk();
  if (tid < 288) {
    if (b < 128) {
      const int c = (tid >> 1) * 4, tt = t0 + (tid & 1) * 8;
      uint2 kr[11], vr[8];
#pragma unroll
      for (int i = 0; i < 11; i++) { const int t = tt + i - 3; kr[i] = t >= 0 ? __ldg((const uint2*)(P.K + (size_t)t * DM + c)) : make_uint2(0, 0); }
#pragma unroll
      for (int i = 0; i < 8; i++) vr[i] = __ldg((const uint2*)(P.V + (size_t)(tt + i) * DM + c));
#pragma unroll
      for (int e = 0; e < 2; e++) {
        const uint4 sh = __ldg((const uint4*)(P.shift + c * 4) + e);
        const uint32_t s0 = __byte_perm(sh.x, sh.z, 0x5410), s1 = __byte_perm(sh.x, sh.z, 0x7632);
        const uint32_t s2 = __byte_perm(sh.y, sh.w, 0x5410), s3 = __byte_perm(sh.y, sh.w, 0x7632);
        uint32_t v[8];
#pragma unroll
        for (int i = 0; i < 8; i++) {
          const uint32_t k3 = e ? kr[i].y : kr[i].x, k2 = e ? kr[i + 1].y : kr[i + 1].x, k1 = e ? kr[i + 2].y : kr[i + 2].x, k0 = e ? kr[i + 3].y : kr[i + 3].x;
          v[i] = bmul2(badd2(badd2(badd2(bmul2(k3, s3), bmul2(k2, s2)), bmul2(k1, s1)), bmul2(k0, s0)), e ? vr[i].y : vr[i].x);
        }
        *(uint4*)(g_kvT + (size_t)(c + 2 * e) * KVP + tt) =
          make_uint4(__byte_perm(v[0], v[1], 0x5410), __byte_perm(v[2], v[3], 0x5410), __byte_perm(v[4], v[5], 0x5410), __byte_perm(v[6], v[7], 0x5410));
        *(uint4*)(g_kvT + (size_t)(c + 2 * e + 1) * KVP + tt) =
          make_uint4(__byte_perm(v[0], v[1], 0x7632), __byte_perm(v[2], v[3], 0x7632), __byte_perm(v[4], v[5], 0x7632), __byte_perm(v[6], v[7], 0x7632));
      }
    }
  } else if (tid < 384) {
    const int t = tid - 288;
    for (int i = b * 96 + t; i < 16 * DM; i += N_CTA * 96) ((uint4*)g_oacc)[i] = make_uint4(0, 0, 0, 0);
    if (b * 96 + t < 128 * 8) g_lnflag[b * 96 + t] = 0;
    if (t == 95) sts32(sb + S_GEN, ld_acquire(g_gbar));
    __syncwarp();
    wait_until(tstart, PREFH);
    for (int i = t; i < 32 * nch; i += 96) asm volatile("prefetch.global.L2 [%0];" :: "l"(P.Hk + (size_t)chb * SEQ + i * 64));
  }
  if (warp < 12) {
    bar_arrive(10, 416);
    if (tid == 128) TS(14);
    const int ch = 5 - (warp >> 1), sub = warp & 1, d = chb + ch;
    const uint32_t su = sb + P_CH + ch * P_CHSZ;
    if (ch < nch) {
      const uint32_t* hs = (const uint32_t*)(P.Hk + (size_t)d * SEQ);
#pragma unroll
      for (int q = sub * 32 + lane; q < 256; q += 64) {
        const uint4 c = __ldg((const uint4*)hs + q);
        const uint32_t prev = q ? __ldg(hs + 4 * q - 1) : 0u;
        sts128(su + P_H + 32 + q * 16, make_uint4(__byte_perm(c.x, prev, 0x7610), __byte_perm(c.y, c.x, 0x7610), __byte_perm(c.z, c.y, 0x7610), __byte_perm(c.w, c.z, 0x7610)));
        sts128(su + P_H + 4224 + q * 16, make_uint4(__byte_perm(c.x, 0, 0x1032), __byte_perm(c.y, 0, 0x1032), __byte_perm(c.z, 0, 0x1032), __byte_perm(c.w, 0, 0x1032)));
      }
      if (sub == 1 && lane == 0) sts32(su + P_CHSZ - 16, __bfloat16_as_ushort(P.Dk[d]) * 0x10001u);
      if (sub == 0 && lane < 20) sts128(su + (lane < 16 ? lane * 16 : P_H + (lane & 2) * 2096 + (lane & 1) * 16), make_uint4(0, 0, 0, 0));
    }
    bar_sync(11, 416);
    if (ch < nch) {
#pragma unroll
      for (int q = sub * 32 + lane; q < 256; q += 64) {
        const int row = (q >> 1) + 8;
        sts128(su + row * 32 + (((q & 1) ^ ((row >> 2) & 1)) << 4), __ldcg((const uint4*)(g_kvT + (size_t)d * KVP) + q));
      }
    }
    const int g = lane >> 2, tq = lane & 3;
    const uint32_t sh = su + P_H + (g & 1) * 4192 + (8 + (g >> 1) - tq) * 4;
    float acc[16][4];
#pragma unroll
    for (int i = 0; i < 16; i++) { acc[i][0] = acc[i][1] = acc[i][2] = acc[i][3] = 0.f; }
    auto u_addr = [&](int res) {
      const int row = 8 - res + ((lane >> 4) << 3) + (lane & 7);
      return su + row * 32 + ((((lane >> 3) & 1) ^ ((row >> 2) & 1)) << 4);
    };
    if (ch < nch) {
      bar_sync(1 + ch, 64);
      if (tid == 352) TS(11);
      if (sub) {
#pragma unroll 4
        for (int res = 0; res < 8; res++) {
          uint32_t b0, b1, b2, b3;
          ldsm4(b0, b1, b2, b3, u_addr(res));
          const uint32_t r0 = lds32(sh + res * 32);
          mma16(acc[0], r0, lds32(sh + res * 32 + 16), lds32(sh + res * 32 - 16), r0, b0, b1);
        }
        conv_store<1>(acc, 0, su, d, lds32(su + P_CHSZ - 16));
      }
    }
    bar_arrive(12, 416);
    if (isg && warp < 8) { while ((int)(clk() - tstart - S1G) < 0) __nanosleep(200); load_wg<GROLE>(P, sb, true, warp >> 2, warp & 3); }
    if (ch < nch) {
#pragma unroll 1
      for (int res = sub * 4; res < sub * 4 + 4; res++) {
        uint32_t bf[16][2];
        const uint32_t ad = u_addr(res);
#pragma unroll
        for (int f = 0; f < 16; f += 2) ldsm4(bf[f][0], bf[f][1], bf[f + 1][0], bf[f + 1][1], ad + f * 256);
#pragma unroll
        for (int k = 0; k < 16; k++) {
          const int jj = k & 1 ? k >> 1 : 15 - (k >> 1);
          const uint32_t ah = sh + (8 * jj + res) * 32;
          const uint32_t r0 = lds32(ah), r1 = lds32(ah + 16), rm = lds32(ah - 16);
#pragma unroll
          for (int i = max(jj, 1); i < 16; i++) mma16(acc[i], r0, r1, rm, r0, bf[i - jj][0], bf[i - jj][1]);
        }
      }
      bar_sync(1 + ch, 64);
      if (tid == 352) TS(12);
      const uint32_t xb = su + P_H + lane * 16, dd = lds32(su + P_CHSZ - 16);
      conv_fold<16>(acc, sub, xb + sub * 4096, xb + (sub ^ 1) * 4096, 1 + ch, 64);
      conv_store<8>(acc, sub * 8, su, d, dd);
    }
  } else {
    for (int i = b; i < 194 + MRING * 5; i += N_CTA) {
      const int n = (i - 194) / 5, r = (i - 194) % 5, blk = i < 192 ? i / 6 * 8 + i % 6 : i < 194 ? XB_F + i - 192 : XB_M + n * 8 + r;
      const uint32_t fill = i < 194 ? 0u : SENT;
#pragma unroll 1
      for (int q = tid - 384; q < 256 && warp < 15; q += 96) {
        uint4 v = make_uint4(fill, fill, fill, fill);
        if (i >= 194 && n == 0 && (r > 0 || q < 128)) {
          const bf16* m = P.mem0 + (max(r * 8 - 4, 0) + (q >> 5)) * 16 + ((q >> 1) & 1) * 8 + ((q >> 2) & 7);
          v.x = pack2(__bfloat162float(m[0]), __bfloat162float(m[DM])); v.y = pack2(__bfloat162float(m[2 * DM]), __bfloat162float(m[3 * DM]));
          v.z = pack2(__bfloat162float(m[4 * DM]), __bfloat162float(m[5 * DM])); v.w = pack2(__bfloat162float(m[6 * DM]), __bfloat162float(m[7 * DM]));
        }
        g_xb[blk * 512 + q] = v;
        g_xb[blk * 512 + 256 + q] = v;
      }
    }
    if (tid < 388) g_xb[XB_REF * 512 + (tid & 2) * 128 + (b & ~1) + (tid & 1)] = make_uint4(0, 0, 0, 0);
    else if (tid < 392 && b < N_GRP) g_xb[(b * 8 + 7) * 512 + (tid & 2) * 128 + (tid & 1)] = make_uint4(0, 0, 0, 0);
    if (warp < 15) { bar_arrive(9, 128); bar_sync(7, 96); }
    if (tid == 384) TS(8);
    if (warp == 12) {
      const bf16* w = lane < 6 ? (lane % 3 == 0 ? P.Wk : lane % 3 == 1 ? P.Wv : P.Wq) + (((b >> 5) * 2 + lane / 3) * 32 + (b & 31)) * 2048
                               : (lane < 8 ? P.Wo + (lane - 6) * (9 * 131072) : P.X) + b * 2048;
      uint32_t t = tstart + PREF0;
      if ((int)(clk() - t) > 0) t = clk();
#pragma unroll 1
      for (int st = 0; st < 9 && b < N_CHAIN; st++) {
#pragma unroll 1
        for (int i = 0; i < 9; i++, t += PACE) {
          wait_until(t, 0);
          if (lane == st) asm volatile("cp.async.bulk.prefetch.L2.global [%0], 4096;" :: "l"(w + i * (lane < 6 ? 262144 : 131072)) : "memory");
        }
      }
      if (lane == 0) TS(10);
    } else if (warp == 15) {
      bar_sync(10, 416);
      if (lane == 0) { grid_arrive(0); if (nch) grid_wait(0, lds32(sb + S_GEN)); }
      __syncwarp();
      bar_arrive(11, 416);
      if (lane == 0) TS(1);
      bar_sync(9, 128);
      bar_sync(12, 416);
      if (lane == 0) { TS(16); grid_arrive(2); TS(17); }
    } else if (lane == 0) {
      if (warp == 13 || (warp == 14 && b < N_GRP)) {
        uint32_t* p = (uint32_t*)(g_xb + (warp == 13 ? XB_REF * 512 + b : (b * 8 + 7) * 512));
        int votes = 0;
        for (int rep = 0; rep < 24 && abs(votes) < 7; rep++) {
          uint32_t v0, v1, c0, c1;
          asm volatile("atom.relaxed.gpu.global.add.u32 %0, [%4], 1;\n atom.relaxed.gpu.global.add.u32 %1, [%5], 1;\n"
                       "{.reg .pred p; setp.eq.u32 p, %0, 0x7ffffff3; @p trap; mov.u32 %2, %%clock; setp.eq.u32 p, %1, 0x7ffffff3; @p trap; mov.u32 %3, %%clock;}"
                       : "=&r"(v0), "=&r"(v1), "=&r"(c0), "=&r"(c1) : "l"(p + (rep & 1) * 1024), "l"(p + ((rep & 1) ^ 1) * 1024) : "memory");
          votes += ((c1 - c0 > 80u) == (rep & 1)) ? 1 : -1;
        }
        if (warp == 13) { g_side[b] = votes > 0; TS(9); } else g_near[b] = votes > 0;
      }
    }
    __syncwarp();
    if (warp > 12 && b < N_CHAIN) {
      while ((int)(clk() - tstart - S1DLY) < 0) __nanosleep(200);
      for (int k = warp - 13; k < 8; k += 3) load_wg<CHAIN>(P, sb, true, 1 - k / 4, k & 3);
    }
  }
  if (b < N_CHAIN + N_G && (warp < 8 || (isg && warp >= 12))) bar_arrive(0, 512); else bar_sync(0, 512);
  if (tid == 352) TS(2);
}

__device__ __forceinline__ void publish_y() {
  if (threadIdx.x == 383) { grid_arrive(1); TS(18); }
  __syncwarp();
}

template <int R> __device__ __forceinline__ void ln_tiles(const Params& P, uint32_t sb) {
  const int lane = threadIdx.x & 31, w = (threadIdx.x >> 5) & (16 / R - 1), half = R == 1 ? 0 : threadIdx.x >> 8, u = N_CTA - 1 - bid();
  const int first = R == 1 ? u : 46 - 2 * u + half, step = R == 1 ? 4 : 40, last = R == 1 ? 8 : 128;
  const uint32_t raw = sb + P_CH + half * (18432 + Y_ROWS), mb = sb + T_BAR + (R - 1 + half) * 8;
  const bool lead = w == 16 / R - 1 && lane == 0;
  auto load_y = [&](const bf16* src, int tile) {
    fence_async_global();
    mbar_expect(mb, 18432);
    bulk_load(raw, src + (size_t)tile * 16 * DM, 18432, mb);
  };
  uint32_t nx[9 * R];
  auto load_x = [&](int tile) {
#pragma unroll
    for (int i = 0; i < 9 * R; i++) nx[i] = __ldg((const uint32_t*)(P.X + (size_t)(tile * 16 + w + i / 9 * 8) * DM) + i % 9 * 32 + lane);
  };
  load_x(first);
  if (R == 2) {
    if (lead) { grid_wait(1, lds32(sb + S_GEN)); if (u > 3) TS(13); load_y(g_yT, first); }
    __syncwarp();
  }
#pragma unroll 1
  for (int tile = first, real = R - 1, ph = 0; tile < last; tile += real * step, real = 1, ph ^= 1) {
    uint32_t x[9 * R], l[9 * R], y[9 * R];
    const bool ts = threadIdx.x == 0 && (R == 1 ? tile == first : u > 3 && tile == first + step);
    if (ts) TS(26);
#pragma unroll
    for (int i = 0; i < 9 * R; i++) x[i] = nx[i];
    layernorm9<R>(x, l);
    if (real && tile + step < last) load_x(tile + step);
    if (R == 2 && tile == first + step && u >= N_F && w < 6) load_wg<OROLE>(P, sb, true, w >> 1, half * 2 + (w & 1));
    if (R == 1 && tile == first && lead) {
      if (real) grid_wait(2, lds32(sb + S_GEN));
      TS(13);
      load_y(real ? g_yT : P.Hk, tile);
    }
    bar_sync(13 + half, 512 / R);
    mbar_wait(mb, ph);
    if (ts) TS(28);
    y_rows<R>(y, raw, raw + 18432, w, 13 + half);
    if (ts) TS(29);
    if (lead && real && tile + step < last) { fence_async_smem(); load_y(g_yT, tile + step); }
    __syncwarp();
#pragma unroll
    for (int i = 0; i < 9 * R; i++) x[i] = badd2(x[i], bmul2(l[i], y[i]));
    layernorm9<R>(x, l);
    if (ts && l[0] != 0x12345) TS(30);
#pragma unroll
    for (int r = 0; r < R; r++) store_ln_row(0, tile * 16 + w + r * 8, l + r * 9);
    if (R == 1) {
      __syncthreads();
      if (threadIdx.x == 32 && real) { if (tile < 4) TS(19); st_release(g_lnflag + tile * 8, 1); if (tile < 4) TS(20); }
      __syncwarp();
    }
    if (ts) TS(31);
  }
  if (R == 2) {
    __syncthreads();
    if (threadIdx.x >= 506) {
      asm volatile("fence.acq_rel.gpu;" ::: "memory");
      st_relaxed_if(g_lnflag + ((first ^ (lane & 1)) + (lane - 26) / 2 * step) * 8, 1, true);
    }
    __syncwarp();
    fence_async_smem();
    if (threadIdx.x == 0) TS(15);
  }
}

__global__ void __cluster_dims__(2, 1, 1) __launch_bounds__(512, 1) k_main(const __grid_constant__ Params P) {
  extern __shared__ __align__(1024) unsigned char smem[];
  const uint32_t sb = (uint32_t)__cvta_generic_to_shared(smem);
  const int b = bid(), wg = threadIdx.x >> 7;
  if ((threadIdx.x & 127) == 0) TS(0);
  if (threadIdx.x == 480) {
    if ((sb & 0xFFFFFF) != SBASE) __trap();
    for (int i = 0; i < 6; i++) mbar_init(sb + W_BAR + i * 8, 1);
    if (b < N_CHAIN) {
      mbar_init(sb + CB_FULL, 1); mbar_init(sb + CB_FULL + 8, 1);
      mbar_init(sb + CB_REF, 1);
      mbar_init(sb + CB_SX, 1); mbar_init(sb + CB_OX, 1); mbar_init(sb + CB_XX, 1); mbar_init(sb + CB_Q, 2); mbar_init(sb + CB_VF, 1);
      sts32(sb + C_BAD, 0);
      for (int i = 0; i < 11; i++) mbar_init(sb + CB_M + i * 8, i == 0 ? 5 : i == 5 ? 3 : 1);
    } else if (b < N_CHAIN + N_G) {
      for (int i = 0; i < 9; i++) { mbar_init(sb + G_BAR + i * 8, 2); mbar_init(sb + G_BAR + 128 + i * 8, 8); }
    } else if (b < N_CHAIN + N_G + N_O) {
      for (int i = 0; i < 5; i++) { mbar_init(sb + O_BAR + i * 8, 1); mbar_init(sb + O_BAR + 128 + i * 8, 12); }
      for (int i = 0; i < 6; i++) mbar_init(sb + OB_ST + i * 8, 1);
    } else {
      mbar_init(sb + F_BAR, 1); mbar_init(sb + F_BAR + 8, 1);
    }
    asm volatile("fence.mbarrier_init.release.cluster;" ::: "memory");
    fence_async_smem();
  }
  __syncwarp();
  asm volatile("barrier.cluster.arrive.relaxed.aligned;" ::: "memory");
  prologue(P, sb);
  asm volatile("barrier.cluster.wait.aligned;" ::: "memory");
  fence_async_smem();
  if (b >= N_CHAIN + N_G) publish_y();
  if (b >= 128) ln_tiles<1>(P, sb);
  if (b >= N_CHAIN + N_G) ln_tiles<2>(P, sb);
  if ((threadIdx.x & 127) == 0) TS(3);
  if (b < N_CHAIN) {
    if (wg < 2) { reg_inc<200>(); chain_proj(P, sb); }
    else if (wg == 2) { reg_dec<ATTR>(); publish_y(); chain_attn(P, sb); }
    else { reg_dec<112 - ATTR>(); chain_aux(P, sb); }
  } else if (b < N_CHAIN + N_G) {
    if (wg == 0) { reg_inc<232>(); g_math<0>(P, sb); }
    else if (wg == 1) { reg_inc<232>(); g_math<1>(P, sb); }
    else if (wg == 2) { reg_dec<24>(); bar_arrive(15, 192); publish_y(); g_aux(P, sb); }
    else { reg_dec<24>(); g_load(P, sb); }
  } else if (b < N_CHAIN + N_G + N_O) {
    if (wg == 0) { reg_inc<160>(); o_math<0>(P, sb); }
    else if (wg == 1) { reg_inc<160>(); o_math<1>(P, sb); }
    else if (wg == 2) { reg_inc<160>(); o_math<2>(P, sb); }
    else { reg_dec<32>(); o_aux(P, sb); }
  } else {
    f_role(P, sb);
  }
}

}

extern "C" void kernel_launch(void* const* d_in, const int* in_sizes, int n_in, void* d_out, int out_size) {
  typedef CUresult (*Encode)(CUtensorMap*, CUtensorMapDataType, cuuint32_t, void*, const cuuint64_t*, const cuuint64_t*, const cuuint32_t*, const cuuint32_t*,
                             CUtensorMapInterleave, CUtensorMapSwizzle, CUtensorMapL2promotion, CUtensorMapFloatOOBfill);
  static Encode encode = nullptr;
  if (!encode) cudaGetDriverEntryPoint("cuTensorMapEncodeTiled", (void**)&encode, cudaEnableDefault);
  Params P;
  for (int i = 0; i < 11; i++) {
    const bool wo = i == 6 || i == 7;
    const cuuint64_t cols = wo ? DM : HD, rows = HD + DM - cols, pitch = cols * 2;
    const cuuint64_t dim[4][5] = {{cols, 2, 8, 2, 18}, {cols, 16, 1, 1, rows / 16}, {cols, 2, 4, 4, rows / 32}, {64, 16, 64, 2, 18}};
    const cuuint64_t stride[4][4] = {{8 * pitch, pitch, 16 * pitch, 32 * pitch}, {pitch, pitch, pitch, 16 * pitch},
                                     {pitch, 8 * pitch, 2 * pitch, 32 * pitch}, {pitch, 128, 16 * pitch, 32 * pitch}};
    const cuuint32_t box[4][5] = {{64, 2, 8, 1, 18}, {64, 16, 1, 1, 1}, {64, 2, 4, 2, 1}, {64, 16, 2, 1, 18}}, one[5] = {1, 1, 1, 1, 1};
    const int k = i < 3 ? 0 : i < 7 ? 1 : i < 8 ? 2 : 3;
    encode(&P.map[i], CU_TENSOR_MAP_DATA_TYPE_BFLOAT16, 5, d_in[wo ? 11 : 8 + (i & 7) % 3], dim[k], stride[k], box[k], one,
           CU_TENSOR_MAP_INTERLEAVE_NONE, CU_TENSOR_MAP_SWIZZLE_128B, CU_TENSOR_MAP_L2_PROMOTION_L2_128B, CU_TENSOR_MAP_FLOAT_OOB_FILL_NONE);
  }
  P.X = (const bf16*)d_in[0]; P.K = (const bf16*)d_in[1]; P.V = (const bf16*)d_in[2];
  P.shift = (const bf16*)d_in[3]; P.Hk = (const bf16*)d_in[4]; P.Dk = (const bf16*)d_in[5];
  P.mem0 = (const bf16*)d_in[7];
  P.Wq = (const bf16*)d_in[8]; P.Wk = (const bf16*)d_in[9]; P.Wv = (const bf16*)d_in[10]; P.Wo = (const bf16*)d_in[11];
  P.out = (bf16*)d_out;
  for (int i = 0; i < 24; i++) P.dly[i] = h_dly[i];
  cudaFuncSetAttribute(k_main, cudaFuncAttributeMaxDynamicSharedMemorySize, SMEM_BYTES);
  k_main<<<N_CTA, 512, SMEM_BYTES>>>(P);
}
```

```cpp
#include <cuda.h>
#include <cuda_runtime.h>
#include <cuda_bf16.h>
#include <stdint.h>

namespace {

typedef __nv_bfloat16 bf16;

constexpr int SEQ = 2048, DM = 576, HD = 4096, NSEG = 64;
constexpr int LAG = 7, STEPS = NSEG + LAG, RING = 8;
constexpr int LOCK0 = 3, QRING = LOCK0 + 1;
static_assert(LAG < RING, "ring");
constexpr int N_CHAIN = 64, N_G = 48, N_O = 18, N_F = 2;
constexpr uint32_t SBASE = 1024;
constexpr uint32_t SENT = 0xFFFFFFFFu;
constexpr int SPIN_MAX = 1 << 22;

__device__ __forceinline__ uint32_t bid() {
  uint32_t b;
  asm volatile("mov.u32 %0, %%ctaid.x;" : "=r"(b));
  return b < 6 ? b + 106 : b < 8 ? b + 122 : b < 114 ? b - 8 : b < 130 ? b - 2 : b;
}
__device__ __forceinline__ uint32_t chain_id() { return blockIdx.x - 8; }
constexpr int KVP = SEQ + 64;
__device__ __align__(1024) bf16 g_kvT[DM * KVP];
__device__ __align__(1024) bf16 g_yT[DM * SEQ];
__device__ __align__(1024) unsigned char g_lnimg[2 * NSEG * 9 * 4096];
__device__ __align__(1024) unsigned char g_qkv[QRING * N_CHAIN * 24576];
__device__ __align__(1024) unsigned char g_oimg[RING * N_CHAIN * 8192];
constexpr int ARING = 16;
static_assert(ARING >= LAG + 9, "accumulator ring");
__device__ __align__(1024) float g_oacc[ARING * 64 * DM];
constexpr int MRING = LAG + 4, N_GRP = 32 + MRING + 1;
constexpr int XB_M = 256, XB_F = XB_M + MRING * 8, XB_REF = XB_F + 2, N_CTA = N_CHAIN + N_G + N_O + N_F;
__device__ __align__(65536) uint4 g_xb[N_GRP * 4096];
#define g_mimg ((uint32_t*)(g_xb + XB_M * 512))
__device__ uint32_t g_near[N_GRP];
__device__ uint32_t g_side[N_CTA];
__device__ __align__(128) uint32_t g_gbar[3 * 32];
constexpr int FL_G = 0, FL_F = 96 * 8, FL_OCNT = FL_F + 2 * 8, OCRING = 16, FL_TICK = 992, FL_O = 2048, FL_SYNC = FL_O + 128;
static_assert(FL_OCNT + OCRING * 8 <= FL_TICK, "flag block");
#define g_fl ((uint32_t*)(g_xb + XB_F * 512))
__device__ __align__(1024) uint32_t g_lnflag[128 * 8];
#define TS(slot)

#define CNT(slot, tries)
#define T3(slot)
#define TR(slot)
#define TRV(slot, val)
#define TRD(slot, dep)
#define TRSYNC()
#define TRDUMP(n)
#define CLK(t) "{.reg .b64 x; .reg .b32 h; mov.u64 x, %%clock64; mov.b64 {" t ", h}, x;}"
__device__ __forceinline__ uint32_t clk() { uint32_t t; asm volatile(CLK("%0") : "=r"(t) :: "memory"); return t; }
__device__ __forceinline__ void wait_until(uint32_t t0, uint32_t d) {
  asm volatile("{.reg .pred p; .reg .u32 t;\n"
               "W: " CLK("t") " sub.u32 t, t, %0; setp.lt.s32 p, t, 0; @p bra.uni W;}"
               :: "r"(t0 + d) : "memory");
}
__device__ __forceinline__ uint32_t pack2(float lo, float hi) {
  uint32_t r; asm("cvt.rn.bf16x2.f32 %0, %1, %2;" : "=r"(r) : "f"(hi), "f"(lo)); return r;
}
__device__ __forceinline__ float bf_lo(uint32_t v) { return __uint_as_float(v << 16); }
__device__ __forceinline__ float bf_hi(uint32_t v) { return __uint_as_float(v & 0xFFFF0000u); }

__device__ __forceinline__ void st_b128(void* p, uint32_t a, uint32_t b, uint32_t c, uint32_t d) {
  asm volatile("{.reg .b128 v; mov.b128 v, {%1,%2,%3,%4}; st.relaxed.gpu.global.b128 [%0], v;}" :: "l"(p), "r"(a), "r"(b), "r"(c), "r"(d) : "memory");
}
__device__ __forceinline__ void st_relaxed_if(void* p, uint32_t a, bool on) {
  asm volatile("{.reg .pred p; setp.ne.u32 p, %2, 0; @p st.relaxed.gpu.global.u32 [%0], %1;}" :: "l"(p), "r"(a), "r"((uint32_t)on) : "memory");
}
__device__ __forceinline__ uint32_t ld_acquire(const uint32_t* p) {
  uint32_t v; asm volatile("ld.acquire.gpu.global.u32 %0, [%1];" : "=r"(v) : "l"(p) : "memory"); return v;
}
__device__ __forceinline__ void st_release(uint32_t* p, uint32_t v) {
  asm volatile("st.release.gpu.global.u32 [%0], %1;" :: "l"(p), "r"(v) : "memory");
}
__device__ __forceinline__ void bulk_reduce(float* dst, uint32_t src, uint32_t bytes) {
  asm volatile("cp.reduce.async.bulk.global.shared::cta.bulk_group.add.f32 [%0], [%1], %2;" :: "l"(dst), "r"(src), "r"(bytes) : "memory");
}
__device__ __forceinline__ void bulk_done_inc(uint32_t* p) {
  asm volatile("cp.async.bulk.wait_group 0;\n"
               "fence.proxy.async.global;\nfence.release.gpu;\n"
               "red.relaxed.gpu.global.add.u32 [%0], 1;\nred.relaxed.gpu.global.add.u32 [%0+4096], 1;" :: "l"(p) : "memory");
}
__device__ __forceinline__ void flag_release(uint32_t* p, uint32_t v) {
  asm volatile("fence.release.gpu;\nst.relaxed.gpu.global.u32 [%0], %1;\nst.relaxed.gpu.global.u32 [%0+4096], %1;" :: "l"(p), "r"(v) : "memory");
}
__device__ __forceinline__ void spin_guard(int& it) {
  asm volatile("{.reg .pred p; add.s32 %0, %0, 1; setp.gt.s32 p, %0, %1; @p trap;}" : "+r"(it) : "n"(SPIN_MAX));
}
__device__ __forceinline__ void wait_flags(const uint32_t* p, uint32_t v) {
  int it = 0;
  while (true) {
    uint32_t x; asm volatile("ld.relaxed.gpu.global.u32 %0, [%1];" : "=r"(x) : "l"(p) : "memory");
    if (__all_sync(~0u, x >= v)) break;
    spin_guard(it);
  }
  asm volatile("fence.acquire.gpu;" ::: "memory");
}
__device__ __forceinline__ uint32_t timer_offset() {
  uint32_t g0, g;
  asm volatile("mov.u32 %0, %%globaltimer_lo;" : "=r"(g0) :: "memory");
  do { asm volatile("mov.u32 %0, %%globaltimer_lo;" : "=r"(g) :: "memory"); } while (g == g0);
  return (g >> 5) * 58 - clk();
}
__device__ __forceinline__ void grid_arrive(int i) {
  asm volatile("red.release.gpu.global.add.u32 [%0], %1;" :: "l"(g_gbar + i * 32), "r"(bid() ? 1u : 257u - N_CTA) : "memory");
}
__device__ __forceinline__ void grid_wait(int i, uint32_t gen) {
  int it = 0;
  while (((ld_acquire(g_gbar + i * 32) ^ gen) >> 8) == 0) spin_guard(it);
}
__device__ __forceinline__ bool elect() {
  uint32_t r; asm volatile("{.reg .pred p; elect.sync _|p, -1; selp.u32 %0, 1, 0, p;}" : "=r"(r)); return r;
}
__device__ __forceinline__ void bar_sync(int id, int cnt) { asm volatile("bar.sync %0, %1;" :: "r"(id), "r"(cnt) : "memory"); }
__device__ __forceinline__ void bar_arrive(int id, int cnt) { asm volatile("bar.arrive %0, %1;" :: "r"(id), "r"(cnt) : "memory"); }
template <int id, int cnt> __device__ __forceinline__ void bar_arrive_after(uint32_t a, uint32_t b) {
  asm volatile("{.reg .pred p; setp.ne.u32 p, %2, 0xfff12345; setp.ne.and.u32 p, %3, 0xfff12345, p; @p bar.arrive %0, %1;}" :: "n"(id), "n"(cnt), "r"(a), "r"(b) : "memory");
}
template <int id, int cnt> __device__ __forceinline__ void bar_sync_after(uint32_t a) {
  asm volatile("{.reg .pred p; setp.ne.u32 p, %2, 0xfff12345; @p bar.sync %0, %1;}" :: "n"(id), "n"(cnt), "r"(a) : "memory");
}
__device__ __forceinline__ void fence_async_smem() { asm volatile("fence.proxy.async.shared::cta;" ::: "memory"); }
__device__ __forceinline__ void fence_async_global() { asm volatile("fence.proxy.async.global;" ::: "memory"); }
__device__ __forceinline__ void mbar_init(uint32_t mb, int cnt) { asm volatile("mbarrier.init.shared::cta.b64 [%0], %1;" :: "r"(mb), "r"(cnt) : "memory"); }
__device__ __forceinline__ void mbar_arrive(uint32_t mb) { asm volatile("mbarrier.arrive.shared::cta.b64 _, [%0];" :: "r"(mb) : "memory"); }
__device__ __forceinline__ void mbar_expect(uint32_t mb, uint32_t bytes) {
  asm volatile("mbarrier.arrive.expect_tx.shared::cta.b64 _, [%0], %1;" :: "r"(mb), "r"(bytes) : "memory");
}
__device__ __forceinline__ void mbar_wait(uint32_t mb, uint32_t parity) {
  asm volatile("{.reg .pred p;\nW: mbarrier.try_wait.parity.shared::cta.b64 p, [%0], %1;\n@!p bra W;}" :: "r"(mb), "r"(parity) : "memory");
}
__device__ __forceinline__ void bulk_load(uint32_t dst, const void* src, uint32_t bytes, uint32_t mb) {
  asm volatile("cp.async.bulk.shared::cluster.global.mbarrier::complete_tx::bytes [%0], [%1], %2, [%3];" :: "r"(dst), "l"(src), "r"(bytes), "r"(mb) : "memory");
}
__device__ __forceinline__ void bulk_store(void* dst, uint32_t src, uint32_t bytes) {
  asm volatile("cp.async.bulk.global.shared::cta.bulk_group [%0], [%1], %2;" :: "l"(dst), "r"(src), "r"(bytes) : "memory");
}
__device__ __forceinline__ uint32_t mapa(uint32_t a, uint32_t rank) {
  uint32_t r; asm("mapa.shared::cluster.u32 %0, %1, %2;" : "=r"(r) : "r"(a), "r"(rank)); return r;
}
__device__ __forceinline__ void st_async4(uint32_t dst, float a, float b, float c, float d, uint32_t mb) {
  asm volatile("st.async.shared::cluster.mbarrier::complete_tx::bytes.v4.f32 [%0], {%1,%2,%3,%4}, [%5];" :: "r"(dst), "f"(a), "f"(b), "f"(c), "f"(d), "r"(mb) : "memory");
}
__device__ __forceinline__ void st_async1(uint32_t dst, uint32_t a, uint32_t mb) {
  asm volatile("st.async.shared::cluster.mbarrier::complete_tx::bytes.u32 [%0], %1, [%2];" :: "r"(dst), "r"(a), "r"(mb) : "memory");
}
__device__ __forceinline__ uint4 lds128(uint32_t a) {
  uint4 v; asm volatile("ld.shared.v4.u32 {%0,%1,%2,%3}, [%4];" : "=r"(v.x), "=r"(v.y), "=r"(v.z), "=r"(v.w) : "r"(a) : "memory"); return v;
}
__device__ __forceinline__ uint2 lds64(uint32_t a) {
  uint2 v; asm volatile("ld.shared.v2.u32 {%0,%1}, [%2];" : "=r"(v.x), "=r"(v.y) : "r"(a) : "memory"); return v;
}
__device__ __forceinline__ uint32_t lds32(uint32_t a) {
  uint32_t v; asm volatile("ld.shared.u32 %0, [%1];" : "=r"(v) : "r"(a) : "memory"); return v;
}
__device__ __forceinline__ void sts128(uint32_t a, uint4 v) {
  asm volatile("st.shared.v4.u32 [%0], {%1,%2,%3,%4};" :: "r"(a), "r"(v.x), "r"(v.y), "r"(v.z), "r"(v.w) : "memory");
}
__device__ __forceinline__ void sts32(uint32_t a, uint32_t x) { asm volatile("st.shared.u32 [%0], %1;" :: "r"(a), "r"(x) : "memory"); }
__device__ __forceinline__ void ldsm4(uint32_t& r0, uint32_t& r1, uint32_t& r2, uint32_t& r3, uint32_t a) {
  asm volatile("ldmatrix.sync.aligned.m8n8.x4.shared.b16 {%0,%1,%2,%3}, [%4];" : "=r"(r0), "=r"(r1), "=r"(r2), "=r"(r3) : "r"(a) : "memory");
}
__device__ __forceinline__ void ldsm4t(uint32_t& r0, uint32_t& r1, uint32_t& r2, uint32_t& r3, uint32_t a) {
  asm volatile("ldmatrix.sync.aligned.m8n8.x4.trans.shared.b16 {%0,%1,%2,%3}, [%4];" : "=r"(r0), "=r"(r1), "=r"(r2), "=r"(r3) : "r"(a) : "memory");
}
__device__ __forceinline__ void stsm4(uint32_t a, uint32_t r0, uint32_t r1, uint32_t r2, uint32_t r3) {
  asm volatile("stmatrix.sync.aligned.m8n8.x4.shared.b16 [%0], {%1,%2,%3,%4};" :: "r"(a), "r"(r0), "r"(r1), "r"(r2), "r"(r3) : "memory");
}
__device__ __forceinline__ uint32_t movmat(uint32_t a) {
  uint32_t d; asm volatile("movmatrix.sync.aligned.m8n8.trans.b16 %0, %1;" : "=r"(d) : "r"(a)); return d;
}
__device__ __forceinline__ void mma16(float* d, uint32_t a0, uint32_t a1, uint32_t a2, uint32_t a3, uint32_t b0, uint32_t b1) {
  asm volatile("mma.sync.aligned.m16n8k16.row.col.f32.bf16.bf16.f32 {%0,%1,%2,%3}, {%4,%5,%6,%7}, {%8,%9}, {%0,%1,%2,%3};"
    : "+f"(d[0]), "+f"(d[1]), "+f"(d[2]), "+f"(d[3]) : "r"(a0), "r"(a1), "r"(a2), "r"(a3), "r"(b0), "r"(b1));
}
__device__ __forceinline__ void mma8(float* d, uint32_t a0, uint32_t a1, uint32_t b0) {
  asm volatile("mma.sync.aligned.m16n8k8.row.col.f32.bf16.bf16.f32 {%0,%1,%2,%3}, {%4,%5}, {%6}, {%0,%1,%2,%3};"
    : "+f"(d[0]), "+f"(d[1]), "+f"(d[2]), "+f"(d[3]) : "r"(a0), "r"(a1), "r"(b0));
}
__device__ __forceinline__ float rcp(float x) { float r; asm("rcp.approx.ftz.f32 %0, %1;" : "=f"(r) : "f"(x)); return r; }
__device__ __forceinline__ float ex2(float x) { float r; asm("ex2.approx.ftz.f32 %0, %1;" : "=f"(r) : "f"(x)); return r; }

__host__ __device__ constexpr uint64_t mkdesc(uint32_t off, uint32_t lbo, uint32_t sbo, uint32_t swz) {
  return (uint64_t)((SBASE + off) >> 4) | ((uint64_t)(lbo >> 4) << 16) | ((uint64_t)(sbo >> 4) << 32) | ((uint64_t)swz << 62);
}
__host__ __device__ constexpr uint64_t desc_sw128(uint32_t off) { return mkdesc(off, 16, 1024, 1); }
__host__ __device__ constexpr uint64_t desc_n16(uint32_t off) { return mkdesc(off, 256, 128, 0); }
__host__ __device__ constexpr uint64_t desc_m(uint32_t off) { return mkdesc(off, 16, 256, 3); }

__host__ __device__ constexpr uint64_t desc_sw64(uint32_t off) { return mkdesc(off, 16, 512, 2); }

__device__ __forceinline__ void wg_fence() { asm volatile("wgmma.fence.sync.aligned;" ::: "memory"); }
__device__ __forceinline__ void wg_commit() { asm volatile("wgmma.commit_group.sync.aligned;" ::: "memory"); }
template <int N> __device__ __forceinline__ void wg_wait() { asm volatile("wgmma.wait_group.sync.aligned %0;" :: "n"(N) : "memory"); }

#define ACC8(d) "+f"(d[0]), "+f"(d[1]), "+f"(d[2]), "+f"(d[3]), "+f"(d[4]), "+f"(d[5]), "+f"(d[6]), "+f"(d[7])
#define ACC32(d) ACC8(d), ACC8((d + 8)), ACC8((d + 16)), ACC8((d + 24))
#define R8 "{%0,%1,%2,%3,%4,%5,%6,%7}"
#define R32 "{%0,%1,%2,%3,%4,%5,%6,%7,%8,%9,%10,%11,%12,%13,%14,%15,%16,%17,%18,%19,%20,%21,%22,%23,%24,%25,%26,%27,%28,%29,%30,%31}"
template <int SD> __device__ __forceinline__ void wg_rs16(float* d, const uint32_t* a, uint64_t db) {
  asm volatile("wgmma.mma_async.sync.aligned.m64n16k16.f32.bf16.bf16 " R8 ", {%8,%9,%10,%11}, %12, %13, 1, 1, 1;"
    : ACC8(d) : "r"(a[0]), "r"(a[1]), "r"(a[2]), "r"(a[3]), "l"(db), "n"(SD));
}
template <int SD> __device__ __forceinline__ void wg_ss16(float* d, uint64_t da, uint64_t db) {
  asm volatile("wgmma.mma_async.sync.aligned.m64n16k16.f32.bf16.bf16 " R8 ", %8, %9, %10, 1, 1, 1, 1;"
    : ACC8(d) : "l"(da), "l"(db), "n"(SD));
}
template <int SD, uint64_t DA, uint64_t DB> __device__ __forceinline__ void wg_ss16o(float* d, uint32_t oa, uint32_t ob) {
  asm volatile("{.reg .b32 x, y; .reg .b64 a, b; add.u32 x, %8, %10; add.u32 y, %9, %12; mov.b64 a, {x, %11}; mov.b64 b, {y, %13};\n"
               "wgmma.mma_async.sync.aligned.m64n16k16.f32.bf16.bf16 " R8 ", a, b, %14, 1, 1, 1, 1;}"
    : ACC8(d) : "r"(oa), "r"(ob), "n"((uint32_t)DA), "n"((uint32_t)(DA >> 32)), "n"((uint32_t)DB), "n"((uint32_t)(DB >> 32)), "n"(SD));
}
template <int SD> __device__ __forceinline__ void wg_rs64(float* d, const uint32_t* a, uint64_t db) {
  asm volatile("wgmma.mma_async.sync.aligned.m64n64k16.f32.bf16.bf16 " R32 ", {%32,%33,%34,%35}, %36, %37, 1, 1, 0;"
    : ACC32(d) : "r"(a[0]), "r"(a[1]), "r"(a[2]), "r"(a[3]), "l"(db), "n"(SD));
}
template <int SD> __device__ __forceinline__ void wg_ss64(float* d, uint64_t da, uint64_t db) {
  asm volatile("wgmma.mma_async.sync.aligned.m64n64k16.f32.bf16.bf16 " R32 ", %32, %33, %34, 1, 1, 1, 0;"
    : ACC32(d) : "l"(da), "l"(db), "n"(SD));
}
#define WG_RSO(NAME, SHAPE, REGS, ACC, A, TB) \
template <int SD, uint64_t DB> __device__ __forceinline__ void NAME(float* d, uint32_t a0, uint32_t a1, uint32_t a2, uint32_t a3, uint32_t ob) { \
  asm volatile("{.reg .b64 b; mov.b64 b, {" A(4) ", " A(5) "};\nwgmma.mma_async.sync.aligned." SHAPE ".f32.bf16.bf16 " REGS \
               ", {" A(0) "," A(1) "," A(2) "," A(3) "}, b, " A(6) ", 1, 1, " TB ";}" \
    : ACC(d) : "r"(a0), "r"(a1), "r"(a2), "r"(a3), "r"(ob + (uint32_t)DB), "n"((uint32_t)(DB >> 32)), "n"(SD)); \
}
#define ACC4(d) "+f"(d[0]), "+f"(d[1]), "+f"(d[2]), "+f"(d[3])
#define ACC16(d) ACC8(d), ACC8((d + 8))
#define OP4(i) OP4_##i
#define OP4_0 "%4"
#define OP4_1 "%5"
#define OP4_2 "%6"
#define OP4_3 "%7"
#define OP4_4 "%8"
#define OP4_5 "%9"
#define OP4_6 "%10"
#define OP16(i) OP16_##i
#define OP16_0 "%16"
#define OP16_1 "%17"
#define OP16_2 "%18"
#define OP16_3 "%19"
#define OP16_4 "%20"
#define OP16_5 "%21"
#define OP16_6 "%22"
#define OP32(i) OP32_##i
#define OP32_0 "%32"
#define OP32_1 "%33"
#define OP32_2 "%34"
#define OP32_3 "%35"
#define OP32_4 "%36"
#define OP32_5 "%37"
#define OP32_6 "%38"
WG_RSO(wg_rs8o, "m64n8k16", "{%0,%1,%2,%3}", ACC4, OP4, "1")
#define R16 "{%0,%1,%2,%3,%4,%5,%6,%7,%8,%9,%10,%11,%12,%13,%14,%15}"
WG_RSO(wg_rs32o, "m64n32k16", R16, ACC16, OP16, "1")
WG_RSO(wg_rs64o, "m64n64k16", R32, ACC32, OP32, "0")
WG_RSO(wg_rs32k, "m64n32k16", R16, ACC16, OP16, "0")
template <uint64_t DA, uint64_t DB> __device__ __forceinline__ void wg_ss32k(float* d, uint32_t ob) {
  asm volatile("{.reg .b64 b; mov.b64 b, {%17, %18};\nwgmma.mma_async.sync.aligned.m64n32k16.f32.bf16.bf16 " R16 ", %16, b, 1, 1, 1, 1, 0;}"
    : ACC16(d) : "l"(DA), "r"(ob + (uint32_t)DB), "n"((uint32_t)(DB >> 32)));
}
template <int N> __device__ __forceinline__ void reg_inc() { asm volatile("setmaxnreg.inc.sync.aligned.u32 %0;" :: "n"(N)); }
template <int N> __device__ __forceinline__ void reg_dec() { asm volatile("setmaxnreg.dec.sync.aligned.u32 %0;" :: "n"(N)); }

template <int KS>
__device__ __forceinline__ void load_frags(uint32_t* a, uint32_t src) {
  const int lane = threadIdx.x & 31, w = (threadIdx.x >> 5) & 3;
  const int k = ((lane >> 4) << 3) + (lane & 7), u = w * 2 + ((lane >> 3) & 1);
  const uint32_t base = src + k * 128 + ((u ^ (k & 7)) << 4);
#pragma unroll
  for (int ks = 0; ks < KS; ks++) ldsm4t(a[ks * 4], a[ks * 4 + 1], a[ks * 4 + 2], a[ks * 4 + 3], base + ks * 2048);
}

__device__ __forceinline__ uint32_t badd2(uint32_t a, uint32_t b) { uint32_t r; asm("add.rn.bf16x2 %0, %1, %2;" : "=r"(r) : "r"(a), "r"(b)); return r; }
__device__ __forceinline__ uint32_t bsub2(uint32_t a, uint32_t b) { uint32_t r; asm("sub.rn.bf16x2 %0, %1, %2;" : "=r"(r) : "r"(a), "r"(b)); return r; }
__device__ __forceinline__ uint32_t bmul2(uint32_t a, uint32_t b) { uint32_t r; asm("mul.rn.bf16x2 %0, %1, %2;" : "=r"(r) : "r"(a), "r"(b)); return r; }
__device__ __forceinline__ uint32_t bfma2(uint32_t a, uint32_t b, uint32_t c) { uint32_t r; asm("fma.rn.bf16x2 %0, %1, %2, %3;" : "=r"(r) : "r"(a), "r"(b), "r"(c)); return r; }
template <int R> __device__ __forceinline__ void layernorm9(const uint32_t* x, uint32_t* o) {
  const uint32_t ones = 0x3F803F80u;
  float a[R][3][4], q[R], s[R];
#pragma unroll
  for (int i = 0; i < 9 * R; i++) {
    float* d = a[i % R][i / R % 3];
    if (i < 3 * R) d[0] = d[1] = d[2] = d[3] = 0.f;
    mma8(d, x[i % R * 9 + i / R], ones, x[i % R * 9 + i / R]);
  }
#pragma unroll
  for (int r = 0; r < R; r++) {
    q[r] = threadIdx.x & 4 ? a[r][0][1] + a[r][1][1] + a[r][2][1] : a[r][0][0] + a[r][1][0] + a[r][2][0];
    s[r] = (a[r][0][2] + a[r][0][3]) + (a[r][1][2] + a[r][1][3]) + (a[r][2][2] + a[r][2][3]);
  }
#pragma unroll
  for (int r = 0; r < R; r++) { q[r] += __shfl_xor_sync(~0u, q[r], 4); s[r] += __shfl_xor_sync(~0u, s[r], 1); }
#pragma unroll
  for (int r = 0; r < R; r++) { q[r] += __shfl_xor_sync(~0u, q[r], 9); s[r] += __shfl_xor_sync(~0u, s[r], 2); }
#pragma unroll
  for (int r = 0; r < R; r++) q[r] = __shfl_sync(~0u, q[r], 0) + __shfl_sync(~0u, q[r], 18);
#pragma unroll
  for (int r = 0; r < R; r++) {
    const float mean = s[r] * (1.f / DM), var = fmaxf(fmaf(q[r], 1.f / DM, -mean * mean), 0.f);
    float sd;
    asm("sqrt.approx.ftz.f32 %0, %1;" : "=f"(sd) : "f"(bf_lo(pack2(bf_lo(pack2(var, 0.f)) + 1e-5f, 0.f))));
    const float inv = rcp(bf_lo(pack2(sd, 0.f)));
    const uint32_t mb = pack2(mean, mean), hi = pack2(inv, inv), lo = pack2(inv - bf_lo(hi), inv - bf_lo(hi));
#pragma unroll
    for (int i = r * 9; i < r * 9 + 9; i++) {
      const uint32_t d = bsub2(x[i], mb);
      o[i] = bfma2(d, hi, bmul2(d, lo));
    }
  }
}
__device__ __forceinline__ void store_ln_row(int layer, int tok, const uint32_t* o) {
  const int lane = threadIdx.x & 31, r = tok & 31;
  unsigned char* p = g_lnimg + (size_t)(layer * NSEG + (tok >> 5)) * (9 * 4096) + r * 128 + (((lane >> 2) ^ (r & 7)) << 4) + (lane & 3) * 4;
#pragma unroll
  for (int i = 0; i < 9; i++) *(uint32_t*)(p + i * 4096) = o[i];
}
struct Params { CUtensorMap map[11]; const bf16 *X, *K, *V, *shift, *Hk, *Dk, *mem0, *Wq, *Wk, *Wv, *Wo; bf16* out; uint32_t dly[24]; };
#define DLYS P.dly[0]
#define DLYW P.dly[1]
#define DLYK P.dly[4]
#define DLYG P.dly[5]
#define KWIN P.dly[6]
#define KMIN P.dly[7]
#define PREF0 P.dly[19]
#define PACE P.dly[20]
#define S1G P.dly[21]
#define S1DLY P.dly[22]
#define PREFH P.dly[23]
uint32_t h_dly[24] = {900, 120, 150, 160, 3565, 4200, 2750, 1300, 1610, 1700, 1810, 2130, 2260, 2390, 2945, 3055, 3225, 3375, 3525, 7000, 160, 12500, 20500, 4000};

constexpr uint32_t C_W = 0, C_M = 147456, C_KV = C_M + 18432, C_OS = C_KV + 24576, C_QM = C_KV + 32768, C_KM = C_QM + 2048,
                   C_VM = C_KM + 2048, C_OI = C_VM + 2048, C_SX = C_OI + 4096, C_KM2 = C_SX + 2560, C_VM2 = C_KM2 + 128,
                   C_KV2 = C_KM2 + 2048, C_Q = C_KV2 + 8192, C_BAR = C_Q + 8192;
constexpr uint32_t CB_FULL = C_BAR, CB_REF = C_BAR + 16, CB_SX = C_BAR + 32, CB_OX = C_BAR + 40, CB_XX = C_BAR + 48, CB_Q = C_BAR + 56, C_BAD = C_BAR + 64, W_BAR = C_BAR + 80, T_BAR = W_BAR + 24, S_GEN = C_BAR + 128, C_REF = C_BAR + 132, CB_VF = C_BAR + 144, CB_M = C_BAR + 160, CB_MV = C_BAR + 200;
constexpr uint32_t G_W = 0, G_RING = 147456, G_W2 = G_RING + 9 * 8192, G_BAR = G_W2 + 8192;
constexpr uint32_t O_W = 0, O_RING = 3 * 40960, O_ST = O_RING + 11 * 8192, O_BAR = O_ST + 16384, OB_ST = O_BAR + 64;
constexpr uint32_t F_A = 0, F_XY = 36864, F_L = F_XY + 36864, F_X = F_L + 18432, F_Y = F_L + 2 * 36864, F_BAR = C_BAR;
constexpr uint32_t SMEM_BYTES = C_BAR + 256;
static_assert(G_BAR + 256 <= SMEM_BYTES && O_BAR + 256 <= SMEM_BYTES && F_BAR + 16 <= SMEM_BYTES && SMEM_BYTES <= 232448, "smem map");
enum { B_INIT = 1, B_M, B_QK, B_S, B_V, B_O, B_X, B_WG0, B_WG1, B_WG2, B_G, B_OE, B_T, B_R };

__device__ __forceinline__ uint4 pack_partial(const float* d, uint32_t tag) {
  uint32_t x, z;
  asm("lop3.b32 %0, %2, 1, %4, 0xb8; lop3.b32 %1, %3, 1, %4, 0xb8;" : "=&r"(x), "=&r"(z) : "r"(pack2(d[0], d[1])), "r"(pack2(d[2], d[3])), "r"(tag));
  return make_uint4(x, pack2(d[4], d[5]), z, pack2(d[6], d[7]));
}
__device__ __forceinline__ void store_partial(uint4* p, const uint4& v) { st_b128(p, v.x, v.y, v.z, v.w); }
__device__ __forceinline__ void gather_reduce(const uint32_t* p, uint32_t* dst, uint32_t m0, bool shared, uint32_t tag, uint32_t lane, uint32_t sb, int n, int TS0) {
  int tries = 0;
  bool bad;
  TR(TS0);
  do {
    uint2 x[8];
#pragma unroll
    for (int i = 0; i < 8; i++)
      asm volatile("{.reg .b64 v; ld.relaxed.gpu.global.b64 v, [%2]; mov.b64 {%0, %1}, v;}" : "=r"(x[i].x), "=r"(x[i].y) : "l"(p + i * 128) : "memory");
    spin_guard(tries);
    float a = bf_lo(x[0].x), b = bf_hi(x[0].x), c = bf_lo(x[0].y), d = bf_hi(x[0].y);
    uint32_t t = x[0].x ^ tag;
#pragma unroll
    for (int i = 1; i < 8; i++) {
      a += bf_lo(x[i].x); b += bf_hi(x[i].x); c += bf_lo(x[i].y); d += bf_hi(x[i].y);
      asm("lop3.b32 %0, %0, %1, %2, 0xf6;" : "+r"(t) : "r"(x[i].x), "r"(tag));
    }
    bad = __any_sync(~0u, t & 1);
    const bool up = lane & 8;
    float u = (up ? c : a) + __shfl_xor_sync(~0u, up ? a : c, 8), v = (up ? d : b) + __shfl_xor_sync(~0u, up ? b : d, 8);
    if (shared) { u += __shfl_xor_sync(~0u, u, 4); v += __shfl_xor_sync(~0u, v, 4); }
    u += __shfl_xor_sync(~0u, u, 16);
    v += __shfl_xor_sync(~0u, v, 16);
    st_relaxed_if(dst, n < LAG && up ? m0 : pack2(u, v), !bad);
  } while (bad);
  TR(TS0 + 3); TRV(TS0 + 2, tries);
  CNT((TS0 - 16) >> 2, tries);
}

#define ATTR 80
#define SEPV 1
#define XRV 3
constexpr int XR = XRV;
__host__ __device__ constexpr int o_ks(int s) { return s & (s < 8 ? 3 : 7); }
#define OPAT 0x55555577u
__host__ __device__ constexpr bool o_reg(int s) { return (OPAT >> s) & 1; }
__host__ __device__ constexpr int o_slot(int s) { int k = 0; for (int i = 0; i < s; i++) k += o_reg(i) == o_reg(s); return k; }
__device__ __forceinline__ int g_unit(int wg) {
  const int i = bid() - N_CHAIN;
  return i < 32 ? wg * 64 + i : 2 * i - 32 + wg;
}
__device__ __forceinline__ uint32_t pinned(uint32_t v) { return __shfl_sync(~0u, v, threadIdx.x & 31); }
template <class T> __device__ __forceinline__ T* pinned(T* p) { return (T*)__shfl_sync(~0u, (unsigned long long)p, threadIdx.x & 31); }
enum { CHAIN, GROLE, OROLE };
template <int ROLE, bool SYNC> __device__ __forceinline__ void load_box(const Params& P, uint32_t sb, bool regs, int wg, int i, uint32_t mb, bool on) {
  const int b = bid();
  int map, col = 0, ks = 0, c2 = 0, c3 = 0;
  uint32_t dst = wg * 73728;
  if (ROLE == CHAIN) {
    const int k = i - 1, st = __fns(regs ? OPAT : ~OPAT, 0, i) & 31;
    dst += i ? (17 + i) * 2048 : 0;
    if (wg || i == 0) { map = wg + i; col = b * 64; c3 = !regs; }
    else if (!regs && k >= 14) { map = 6; ks = b * 4 + k - 14; }
    else { map = 6; col = 64 + (st < 8 ? (st >> 2) * 64 : (st >> 3) * 128 + (b & 1) * 64); ks = (b * 4) ^ o_ks(st); }
  } else if (ROLE == GROLE) {
    const int q = g_unit(wg);
    map = ((q >> 5) + 1) % 3;
    if (i) { map += 3; col = (q & 31) * 128 + (i - 1) * 64; ks = 34; dst = G_W2 + wg * 4096 + (i - 1) * 2048; }
    else { map += 8; c2 = (q & 31) * 2; c3 = !regs; }
  } else {
    const int o = b - N_CHAIN - N_G, ksl = o / 3;
    map = 7; col = ((o % 3) * 3 + (wg + ksl) % 3) * 64; dst = (wg * (regs ? 24 : 20) + i) * 2048;
    ks = (ksl * 11 - max(ksl - 4, 0)) * 4 + (regs ? i / 3 * 5 + i % 3 * 2 : i < 16 ? i / 2 * 5 + 1 + i % 2 * 2 : i + 24);
    c3 = (ks & 1) * 2; ks >>= 1;
  }
  if (SYNC) { col = pinned(col); ks = pinned(ks); bar_sync(B_WG0 + wg, 256); }
  if (on) asm volatile("cp.async.bulk.tensor.5d.shared::cluster.global.tile.mbarrier::complete_tx::bytes [%0], [%1, {%2, %3, %4, %5, %6}], [%7];"
               :: "r"(sb + dst), "l"(&P.map[map]), "r"(col), "r"(0), "r"(c2), "r"(c3), "r"(ks), "r"(mb) : "memory");
}
template <int ROLE, bool SYNC = false> __device__ __forceinline__ void load_wg(const Params& P, uint32_t sb, bool regs, int wg, int quarter) {
  const int i = (threadIdx.x & 31) * 4 + quarter;
  const int n = ROLE == CHAIN ? 36 : ROLE == GROLE ? (regs ? 38 : 36) : regs ? 24 : bid() < N_CHAIN + N_G + 12 ? 20 : 16;
  const bool split = SYNC && wg == 0;
  const uint32_t mb = split && i ? sb + T_BAR : sb + W_BAR + wg * 8;
  load_box<ROLE, SYNC>(P, sb, regs, wg, i, mb, i < (ROLE == CHAIN ? (wg ? 2 : 19) : ROLE == GROLE ? n - 35 : n));
  if (i <= split) mbar_expect(mb, n * (split ? 1024 : 2048));
  __syncwarp();
}
__device__ __forceinline__ uint32_t near_half(uint32_t blk, uint32_t reader) {
  return __ldcg(g_near + (blk >> 3)) ^ (~blk & 1) ^ __ldcg(g_side + (blk >> 3)) ^ __ldcg(g_side + reader);
}

__device__ __forceinline__ uint32_t opaque_tid() { uint32_t t; asm volatile("mov.u32 %0, %%tid.x;" : "=r"(t)); return t; }
__device__ __forceinline__ void m_fetch(uint32_t sb, uint32_t src, uint32_t b, uint32_t mb) {
  bulk_load(sb + C_M + (b ? b * 4096 - 2048 : 0), (const unsigned char*)g_mimg + ((src ^ ((b & 1) * 4096)) + b * 8192), b ? 4096 : 2048, mb);
}
__device__ __forceinline__ uint32_t m_probe(uint32_t lane) { return lane * 32 + (lane & 4) * 4 + (lane >> 3) * 4; }
__device__ __forceinline__ uint32_t m_max(uint32_t a, uint32_t b) {
  return max(max(lds32(a), lds32(a + 1024)), max(lds32(b), lds32(b + 1024)));
}
template <int S0, int N> __device__ __forceinline__ void o_steps(float* d, const uint32_t* a) {
  constexpr int SD = o_ks(S0) != 0;
  if constexpr (o_reg(S0)) wg_rs16<SD>(d, a + (18 + o_slot(S0)) * 4, desc_n16(C_OI + o_ks(S0) * 512));
  else wg_ss16<SD>(d, desc_sw128(C_W + (18 + o_slot(S0)) * 2048), desc_n16(C_OI + o_ks(S0) * 512));
  if constexpr (N > 1) o_steps<S0 + 1, N - 1>(d, a);
}
template <int BASE, int KS, int N> __device__ __forceinline__ void m_steps(float* d, const uint32_t* a, uint32_t oa) {
  wg_rs16<KS != 0>(d, a + (BASE + KS / 2) * 4, desc_m(C_M + KS * 512));
  if constexpr (KS >= 36 - 2 * XR) wg_rs16<1>(d, a + (18 + XR + KS / 2) * 4, desc_m(C_M + KS * 512 + 512));
  else wg_ss16o<1, desc_sw128(C_W + (BASE + KS / 2) * 2048), desc_m(C_M + KS * 512 + 512)>(d, oa, 0);
  if constexpr (N > 2) m_steps<BASE, KS + 2, N - 2>(d, a, oa);
}

constexpr uint32_t VPAT = 0x15bbd249u;
template <int I, int R, int S> __device__ __forceinline__ void v_steps(float* d, const uint32_t* a) {
  constexpr bool reg = (VPAT >> I) & 1;
  if constexpr (reg) wg_rs16<1>(d, a + (18 + R) * 4, desc_m(C_M + R * 1024));
  else wg_ss16<1>(d, desc_sw128(C_W + (54 + S) * 2048), desc_m(C_M + S * 1024 + 512));
  if constexpr (I < 31) v_steps<I + 1, R + reg, S + !reg>(d, a);
  else static_assert(R + reg == 18, "pattern");
}

__device__ __forceinline__ void chain_proj(const Params& P, uint32_t sb) {
  const uint32_t c = chain_id(), h = c >> 1, j = c & 1, wid = __shfl_sync(~0u, threadIdx.x >> 5, 0), wg = wid >> 2, w = wid & 3;
  const uint32_t t = threadIdx.x & 127, lane = pinned(t & 31), mine = pinned(sb + t * 16), rb = mapa(sb, j ^ 1);
  const uint32_t theirs = pinned(rb + C_KM2 + w * 512 + lane * 4), oa = wg * 4608;
  uint32_t a[144 + 4 * XR];
  mbar_wait(sb + W_BAR + wg * 8, 0);
  if (threadIdx.x == 0) TS(23);
  load_frags<36>(a, sb + C_W + wg * 73728);
  fence_async_smem();
  bar_arrive(B_WG0 + wg, 256);
  if (threadIdx.x == 0) TS(24);
  bar_sync(B_WG2, 384);
  const uint32_t round = min(w, 2u) + (wg ? 0 : 3), gdly = P.dly[8 + round], ps = t >> 2, pf = j * 16 + (ps >> 1);
  uint4* const dsts = pinned(g_xb + (ps * 4096 + near_half(ps * 8, ps * 2) * 256 + c * 4 + (t & 3)));
  uint4* const dstf = pinned(g_xb + (pf * 4096 + 512 + near_half(pf * 8 + 1, pf * 2) * 256 + h * 8 + (t & 7)));
  const uint32_t* const gsrc = (const uint32_t*)g_xb + (h * 16384 + min(w, 2u) * 4096 + near_half(h * 8 + !wg, h * 2) * 1024 +
                               (wg ? lane * 4 + j * 2 : 2048 + (lane & 24) * 4 + j * 16 + (lane & 7) * 2));
  uint32_t* gdst = g_mimg + (16384 + (lane >> 4) * 1024 +
                   (wg ? (round ? 1536 + round * 512 : 0) + c * 8 + (((lane >> 1) ^ c) & 4) + (lane & 3)
                       : (round - 1) * 2048 + c * 16 + (lane & 1) * 8 + (((lane >> 1) ^ (c * 2)) & 4) + ((lane >> 1) & 3)));
  const uint32_t m0 = __ldcg(gdst - 16384);
  mbar_wait(sb + W_BAR + wg * 8, 1);
  load_frags<XR>(a + 144, sb + C_W + wg * 73728 + (18 - XR) * 2048);
  bar_sync(B_INIT, 256);
  if ((threadIdx.x & 127) == 0) TS(4);

  uint32_t ring = 1;
#pragma unroll 1
  for (int n = 0; n < STEPS; n++) {
    float d[8], e[8];
    if (n + 1 == STEPS && !wg) { bar_arrive(B_QK, 416); break; }
#pragma unroll
    for (int i = 0; i < 8; i++) e[i] = 0.f;
    uint32_t redo = n + 1;
#pragma unroll 1
    do {
      mbar_wait(sb + CB_M, n & 1);
      wg_fence();
      m_steps<0, 0, 4>(d, a, oa);
      wg_commit();
      if (wg) { wg_fence(); m_steps<18, 0, 4>(e, a, 4608); wg_commit(); }
      if (wid == 0) TR(8);
      mbar_wait(sb + CB_M + 8, n & 1);
      wg_fence();
      m_steps<0, 4, 8>(d, a, oa);
      wg_commit();
      mbar_wait(sb + CB_MV, n & 1);
      asm volatile("{.reg .pred p; .reg .u32 t; ld.shared.u32 t, [%1]; setp.eq.u32 p, t, %0; selp.u32 %0, -1, 0, p;}" : "+r"(redo) : "r"(sb + C_BAD) : "memory");
    } while (redo);
    if (SEPV) mbar_wait(sb + CB_MV + 8, n & 1);
    wg_fence();
    m_steps<0, 12, 8>(d, a, oa);
    wg_commit();
    mbar_wait(sb + CB_MV + 16, n & 1);
    wg_fence();
    m_steps<0, 20, 8>(d, a, oa);
    wg_commit();
    mbar_wait(sb + CB_MV + 24, n & 1);
    wg_fence();
    m_steps<0, 28, 8>(d, a, oa);
    wg_commit();
    wg_wait<0>();
    if (w == 0) TR(6 + wg);
    const uint32_t f0 = pack2(d[0], d[1]), f1 = pack2(d[4], d[5]), f2 = pack2(d[2], d[3]), f3 = pack2(d[6], d[7]);
    stsm4(mine + C_QM + wg * 2048, f0, f1, f2, f3);
    bar_arrive(B_QK, 416);
    const uint32_t tag = (n & 1) ^ 1;
    if (n == 0) mbar_wait(sb + T_BAR, 0);
    if (wg) {
      if (n + 1 < STEPS) bar_sync(B_S, 256);
      wg_fence();
      v_steps<0, 2, 2>(e, a);
      wg_commit();
      const uint32_t k0 = j ? f0 : f1, k1 = j ? f2 : f3;
      mbar_wait(sb + CB_SX, n & 1);
      wg_wait<0>();
      if (w == 0) TR(11);
      const uint32_t v0 = pack2(e[0], e[1]), v1 = pack2(e[4], e[5]), v2 = pack2(e[2], e[3]), v3 = pack2(e[6], e[7]);
      stsm4(mine + C_VM, v0, v1, v2, v3);
      bar_arrive(B_V, 256);
      st_async1(theirs, k0, rb + CB_XX);
      st_async1(theirs + 256, k1, rb + CB_XX);
      st_async1(theirs + 128, j ? v0 : v1, rb + CB_XX);
      st_async1(theirs + 384, j ? v2 : v3, rb + CB_XX);
      if (n + 1 == STEPS) break;
      bar_sync(B_O, 256);
      fence_async_smem();
      wg_fence();
#pragma unroll
      for (int ks = 0; ks < 4; ks++) {
        if (ks == 0) wg_ss16<0>(d, desc_sw128(C_W + 32 * 2048), desc_n16(C_OI));
        else wg_ss16<1>(d, desc_sw128(C_W + (32 + ks) * 2048), desc_n16(C_OI + ks * 512));
      }
      wg_commit();
      bar_arrive(B_X, 256);
      if (w == 0) TR(0);
      wg_wait<0>();
      store_partial(dsts, pack_partial(d, tag));
      bar_arrive(B_M, 160);
      if (w == 0) TR(1);
    } else {
      bar_sync(B_X, 256);
      wg_fence();
      o_steps<0, 4>(d, a);
      wg_commit();
      o_steps<4, 4>(e, a);
      wg_commit();
      wg_wait<1>();
      store_partial(dsts + 1024, pack_partial(d, tag));
      if (w == 0) TR(2);
      wg_wait<0>();
      store_partial(dsts + 2048, pack_partial(e, tag));
      if (w == 0) TR(3);
      wg_fence();
      o_steps<8, 4>(d, a);
      wg_commit();
      bar_sync(B_T, 256);
      if (w == 0) { TRV(61, 0); TR(12); }
      wg_fence();
      o_steps<12, 4>(d, a);
      wg_commit();
      o_steps<16, 8>(e, a);
      wg_commit();
      wg_wait<1>();
      store_partial(dstf, pack_partial(d, tag));
      if (w == 0) TR(4);
      wg_fence();
      o_steps<24, 8>(d, a);
      wg_commit();
      wg_wait<1>();
      store_partial(dstf + 1024, pack_partial(e, tag));
      bar_arrive(B_OE, 256);
      if (w == 0) TR(5);
      wg_wait<0>();
      store_partial(dstf + 2048, pack_partial(d, tag));
      if (w == 0) TR(15);
    }
    if (w < 3) {
      mbar_wait(sb + CB_REF, n & 1);
      wait_until(lds32(sb + C_REF), gdly);
      gather_reduce(gsrc, gdst, m0, wg, tag, lane, sb, n, 16 + round * 4);
      if (++ring == MRING) { ring = 0; gdst -= MRING * 16384; }
      gdst += 16384;
    }
  }
}

template <int KS> __device__ __forceinline__ void x_scores(float* s, float* sm, const uint4* q, uint32_t ok, uint32_t om) {
  wg_rs32o<1, desc_sw64(C_KV + KS * 1024)>(s, q[KS].x, q[KS].y, q[KS].z, q[KS].w, ok);
  wg_rs8o<1, desc_n16(C_KM + KS * 512)>(sm, q[KS].x, q[KS].y, q[KS].z, q[KS].w, om);
  if constexpr (KS < 3) x_scores<KS + 1>(s, sm, q, ok, om);
}

__device__ __forceinline__ void chain_attn(const Params& P, uint32_t sb) {
  const int c = chain_id(), j = c & 1;
  const int tid = threadIdx.x, lane = tid & 31, w = __shfl_sync(~0u, (tid >> 5) & 3, 0);
  const int l = w >> 1, u = w & 1;
  const uint32_t rb = mapa(sb, j ^ 1);
  const float sc = 0.08838834764831845f * 1.4426950408889634f;
  const uint32_t ones = 0x3F803F80u, sx = C_SX + l * 1280;
  const uint32_t km_off = C_KM + (lane >> 3) * 256 + l * 128 + (lane & 7) * 16;
  const uint32_t qm_off = C_QM + (lane >> 4) * 256 + l * 128 + (lane & 7) * 16;
  const uint32_t kv_off = C_KV + l * 4096 + (lane & 15) * 64 + (((lane >> 4) ^ (u * 2) ^ ((lane >> 1) & 3)) << 4);

  load_wg<CHAIN, true>(P, sb, false, 1, w);
  if (lane == 0) mbar_arrive(sb + CB_M);
#pragma unroll 1
  for (int n = 0; n < STEPS; n++) {
    const uint32_t kvb = sb + kv_off + (n & 1) * 16384;
    if (w == 0 && elect()) { mbar_expect(sb + CB_SX, 2560); mbar_expect(sb + CB_OX, 2048); mbar_expect(sb + CB_XX, 2048); }
    mbar_wait(sb + CB_FULL + (n & 1) * 8, (n >> 1) & 1);
    if (n < 3 && tid == 256) TS(n ? 20 + n : 5);
    __syncwarp();
    {
      uint32_t km[8];
      uint4 kx[8];
#pragma unroll
      for (int i = 0; i < 8; i++) ldsm4t(kx[i].x, kx[i].y, kx[i].z, kx[i].w, (kvb ^ ((i & 1) * 32)) + (i >> 1) * 1024);
      mbar_wait(sb + CB_VF, n & 1);
      if (w == 1) TRD(60, kx[7].x);
      bar_sync(B_QK, 416);
      if (n + 1 == STEPS) {
        st_async4(rb + sx + u * 512 + lane * 16, 0.f, 0.f, 0.f, 0.f, rb + CB_SX);
        st_async1(rb + sx + 1024 + u * 128 + lane * 4, 0, rb + CB_SX);
        bar_sync(B_V, 256);
      } else {
      uint32_t qm[16];
#pragma unroll
      for (int ks = 0; ks < 4; ks++) ldsm4t(qm[4 * ks], qm[4 * ks + 1], qm[4 * ks + 2], qm[4 * ks + 3], sb + qm_off + ks * 512);
      ldsm4t(km[0], km[1], km[2], km[3], sb + km_off);
      ldsm4t(km[4], km[5], km[6], km[7], sb + km_off + 1024);
      float s[5][4];
      uint4 vx[4];
#pragma unroll
      for (int i = 0; i < 5; i++) { s[i][0] = s[i][1] = s[i][2] = s[i][3] = 0.f; }
#pragma unroll
      for (int ks = 0; ks < 4; ks++) {
        const uint32_t* q = qm + 4 * ks;
        if (ks == 1 || ks == 2) {
#pragma unroll
          for (int i = 2 * ks - 2; i < 2 * ks; i++) ldsm4(vx[i].x, vx[i].y, vx[i].z, vx[i].w, ((sb + kv_off) ^ ((i & 1) * 32)) + 8192 + (2 * u + (i >> 1)) * 1024);
        }
        mma16(s[1], q[0], q[1], q[2], q[3], kx[2 * ks].x, kx[2 * ks].y);
        mma16(s[2], q[0], q[1], q[2], q[3], kx[2 * ks].z, kx[2 * ks].w);
        mma16(s[0], q[0], q[1], q[2], q[3], km[2 * ks], km[2 * ks + 1]);
        mma16(s[3], q[0], q[1], q[2], q[3], kx[2 * ks + 1].x, kx[2 * ks + 1].y);
        mma16(s[4], q[0], q[1], q[2], q[3], kx[2 * ks + 1].z, kx[2 * ks + 1].w);
      }
      st_async4(rb + sx + u * 512 + lane * 16, s[1][0], s[1][1], s[2][0], s[2][1], rb + CB_SX);
      st_async1(rb + sx + 1024 + u * 128 + lane * 4, __float_as_uint(u ? s[0][1] : s[0][0]), rb + CB_SX);
      bar_arrive_after<B_S, 256>(__float_as_uint(s[3][0]), __float_as_uint(s[4][0]));
      mbar_wait(sb + CB_SX, n & 1);
      const uint4 p0 = lds128(sb + sx + u * 512 + lane * 16), p1 = lds128(sb + sx + (u ^ 1) * 512 + lane * 16);
      const uint2 p2 = make_uint2(lds32(sb + sx + 1024 + lane * 4), lds32(sb + sx + 1152 + lane * 4));
      float t[10] = {s[0][0] + __uint_as_float(p2.x), s[0][1] + __uint_as_float(p2.y),
                     s[1][0] + __uint_as_float(p0.x), s[1][1] + __uint_as_float(p0.y),
                     s[2][0] + __uint_as_float(p0.z), s[2][1] + __uint_as_float(p0.w),
                     s[3][0] + __uint_as_float(p1.x), s[3][1] + __uint_as_float(p1.y),
                     s[4][0] + __uint_as_float(p1.z), s[4][1] + __uint_as_float(p1.w)};
      float mx = fmaxf(fmaxf(fmaxf(fmaxf(t[2], t[3]), fmaxf(t[4], t[5])), fmaxf(fmaxf(t[6], t[7]), fmaxf(t[8], t[9]))), fmaxf(t[0], t[1]));
      mx = fmaxf(fmaxf(mx, __shfl_xor_sync(~0u, mx, 1)), fmaxf(__shfl_xor_sync(~0u, mx, 2), __shfl_xor_sync(~0u, mx, 3)));
      const float ms = -mx * sc;
#pragma unroll
      for (int i = 0; i < 10; i++) t[i] = ex2(fmaf(t[i], sc, ms));
      uint32_t p[5];
#pragma unroll
      for (int i = 0; i < 5; i++) p[i] = pack2(t[2 * i], t[2 * i + 1]);
      p[1] |= (p[0] & p[3] & p[4]) & 0x80008000u;
      float o[2][4], z[4] = {0.f, 0.f, 0.f, 0.f};
      mma16(z, ones, ones, ones, ones, p[1], p[2]);
#pragma unroll
      for (int i = 0; i < 2; i++) {
        o[i][0] = o[i][1] = o[i][2] = o[i][3] = 0.f;
        mma16(o[i], vx[2 * i].x, vx[2 * i].y, vx[2 * i].z, vx[2 * i].w, p[1], p[2]);
      }
      mma16(z, ones, ones, ones, ones, p[3], p[4]);
#pragma unroll
      for (int i = 0; i < 2; i++) mma16(o[i], vx[2 * i + 1].x, vx[2 * i + 1].y, vx[2 * i + 1].z, vx[2 * i + 1].w, p[3], p[4]);
      mma8(z, ones, ones, p[0]);
      bar_sync_after<B_V, 256>(p[1]);
      ldsm4(km[0], km[1], km[2], km[3], sb + km_off + (C_VM - C_KM) + u * 1024);
      mma8(o[0], km[0], km[1], p[0]);
      mma8(o[1], km[2], km[3], p[0]);
      const float i0 = rcp(z[0]), i1 = rcp(z[1]);
      const uint32_t oo = C_OI + u * 1024 + l * 128 + lane * 4;
      uint32_t ow[4];
#pragma unroll
      for (int i = 0; i < 2; i++) { ow[2 * i] = pack2(o[i][0] * i0, o[i][1] * i1); ow[2 * i + 1] = pack2(o[i][2] * i0, o[i][3] * i1); }
      stsm4(sb + C_OI + u * 1024 + l * 128 + (lane >> 3) * 256 + (lane & 7) * 16, ow[0], ow[1], ow[2], ow[3]);
      bar_arrive(B_O, 256);
#pragma unroll
      for (int i = 0; i < 4; i++) st_async1(rb + oo + 2048 + i * 256, ow[i], rb + CB_OX);
      }
    }
    {
      const uint32_t lane = opaque_tid() & 31, own = ((n & 1) * 16384 + j * 4096) >> 4;
      float s[16], sm[4];
#pragma unroll
      for (int i = 0; i < 16; i++) s[i] = sm[i & 3] = 0.f;
      {
        uint4 q[4];
        mbar_wait(sb + CB_Q, n & 1);
#pragma unroll
        for (int ks = 0; ks < 4; ks++)
          ldsm4t(q[ks].x, q[ks].y, q[ks].z, q[ks].w, sb + C_Q + (lane & 8) * 512 + ks * 1024 + (lane & 16) * 32 + (lane & 7) * 64 + (((w ^ (lane >> 1)) & 3) << 4));
        mbar_wait(sb + CB_XX, n & 1);
        if (n + 1 < STEPS) mbar_wait(sb + CB_OX, n & 1);
        fence_async_smem();
        if (n + 1 < STEPS) { bar_arrive(B_T, 256); bar_sync(B_OE, 256); }
        if (w == 1) { TRV(61, 0); TR(9); }
#pragma unroll 1
        for (uint32_t hf = 0; hf < 2; hf++) {
          wg_fence();
          x_scores<0>(s, sm, q, hf ? (C_KV2 - C_KV) >> 4 : own, hf ? (C_KM2 - C_KM) >> 4 : j * 8);
          wg_commit();
          wg_wait<0>();
#pragma unroll
          for (int ks = 0; ks < 4; ks++) asm volatile("mov.b32 %0, %1; mov.b32 %2, %3;" : "+r"(q[ks].x), "+r"(q[ks].y), "+r"(q[ks].z), "+r"(q[ks].w));
        }
      }
      const float neg = -1e9f * 11.313708498984761f;
      const int tok = (lane & 24) + 2 * w + ((lane >> 2) & 1), lim = tok - 8 * (int)(lane & 3);
      float t[10] = {sm[0], sm[1]};
#pragma unroll
      for (int i = 0; i < 8; i++) t[2 + i] = i > lim ? neg : s[(i >> 1) * 4 + (i & 1)];
      float mx = fmaxf(fmaxf(fmaxf(fmaxf(t[2], t[3]), fmaxf(t[4], t[5])), fmaxf(fmaxf(t[6], t[7]), fmaxf(t[8], t[9]))), fmaxf(t[0], t[1]));
      mx = fmaxf(fmaxf(mx, __shfl_xor_sync(~0u, mx, 1)), fmaxf(__shfl_xor_sync(~0u, mx, 2), __shfl_xor_sync(~0u, mx, 3)));
      const float ms = -mx * sc;
#pragma unroll
      for (int i = 0; i < 10; i++) t[i] = ex2(fmaf(t[i], sc, ms));
      uint32_t p[5];
#pragma unroll
      for (int i = 0; i < 5; i++) p[i] = pack2(t[2 * i], t[2 * i + 1]);
      float z = ((t[0] + t[1]) + (t[2] + t[3])) + ((t[4] + t[5]) + (t[6] + t[7])) + (t[8] + t[9]);
      const uint32_t row = sb + C_OS + tok * 128 + (((lane & 3) ^ (tok & 7)) << 4);
#pragma unroll 1
      for (uint32_t hf = 0; hf < 2; hf++) {
        float o[32];
        const uint32_t vo = hf ? (C_KV2 + 4096 - C_KV - 8192) >> 4 : j * 256;
        wg_fence();
        wg_rs64o<0, desc_sw64(C_KV + 8192)>(o, p[1], p[1], p[2], p[2], vo);
        wg_rs64o<1, desc_sw64(C_KV + 8192 + 32)>(o, p[3], p[3], p[4], p[4], vo);
        wg_rs64o<1, mkdesc(C_VM, 128, 256, 0)>(o, p[0], p[0], 0, 0, hf ? (C_VM2 - C_VM) >> 4 : j * 8);
        wg_commit();
        if (hf) {
          if (elect()) mbar_arrive(sb + CB_M);
        } else {
          z += __shfl_xor_sync(~0u, z, 1);
          z = rcp(z + __shfl_xor_sync(~0u, z, 2));
        }
        wg_wait<0>();
#pragma unroll
        for (int qq = 0; qq < 2; qq++) {
          const float* r = o + 16 * qq;
          sts128((row ^ (qq * 64)) + hf * 4096,
                 make_uint4(pack2(r[0] * z, r[1] * z), pack2(r[4] * z, r[5] * z), pack2(r[8] * z, r[9] * z), pack2(r[12] * z, r[13] * z)));
        }
      }
      bar_arrive(B_G, 160);
      if (n + 1 < STEPS) bar_arrive(B_R, 160);
      if (w == 1) TR(10);
    }
  }
  if ((threadIdx.x & 127) == 0) TS(6);
}

__device__ __forceinline__ void chain_aux(const Params& P, uint32_t sb) {
  const uint32_t c = chain_id(), j = c & 1, lane = threadIdx.x & 31, w = __shfl_sync(~0u, (threadIdx.x >> 5) & 3, 0);
  load_wg<CHAIN, true>(P, sb, false, 0, w);
  if (threadIdx.x == 384) TS(25);
  if (threadIdx.x == 384) grid_wait(1, lds32(sb + S_GEN));
  bar_sync(B_WG2, 384);
  if (threadIdx.x == 384) TS(13);
  if (w == 0) {
    const uint32_t* fg = g_fl + FL_G + near_half(XB_F, c) * 1024 + (c >> 1) * 8;
#pragma unroll 1
    for (int n = 0; n < STEPS; n++) {
      const unsigned char* blk = g_qkv + (uint32_t)((n % QRING) * (N_CHAIN * 24576));
      const uint32_t t1 = clk(), kb = sb + CB_FULL + (n & 1) * 8, kv = sb + C_KV + (n & 1) * 16384;
      uint32_t t0 = t1 - 100000, x = 0;
      if (n > 0) {
        wait_until(t1, KMIN);
        do asm volatile("ld.relaxed.gpu.global.u32 %0, [%1];" : "=r"(x) : "l"(fg) : "memory"); while (x <= n && clk() - t1 < KWIN);
        if (x > n) {
          asm volatile("fence.acquire.gpu;" ::: "memory");
          fence_async_global();
          if (elect()) { mbar_expect(kb, 8192); bulk_load(kv, blk + c * 24576, 8192, kb); }
        }
        T3(0); CNT(12, 1 + (x <= n));
        mbar_wait(sb + CB_REF, (n - 1) & 1);
        t0 = lds32(sb + C_REF);
        wait_until(t0, DLYK - 500);
      }
      wait_flags(fg + min(lane, 2u) * 256, n + 1);
      T3(2);
      fence_async_global();
      if (n > 0) bar_sync(B_R, 160);
      wait_until(t0, DLYK);
      if (elect()) {
        if (x <= n) { mbar_expect(kb, 8192); bulk_load(kv, blk + c * 24576, 8192, kb); }
        mbar_expect(sb + CB_VF, 8192);
        bulk_load(sb + C_KV + 8192, blk + (c * 24576 + 8192), 8192, sb + CB_VF);
        mbar_expect(sb + CB_Q, 16384);
        bulk_load(sb + C_Q, blk + (c * 24576 + 16384), 8192, sb + CB_Q);
        bulk_load(sb + C_KV2, blk + ((c ^ 1) * 24576 + j * 4096), 4096, sb + CB_Q);
        bulk_load(sb + C_KV2 + 4096, blk + ((c ^ 1) * 24576 + 8192 + j * 4096), 4096, sb + CB_Q);
      }
      T3(1);
      T3(3);
    }
  } else {
    const uint32_t near = __ballot_sync(~0u, near_half(XB_M + min(lane, MRING - 1u) * 8, c));
    uint32_t ring = 0;
    if (w > 1) {
      const uint32_t odd = w & 1, chk = pinned(sb + C_M + odd * 2048 + m_probe(lane)), again = sb + CB_MV + 32 + odd * 8;
      const bool one = elect();
      uint32_t mph = 0;
#pragma unroll 1
      for (int n = 0; n <= STEPS; n++) {
#pragma unroll
        for (int k = 0; k < 3; k++) {
          if (n == STEPS || (k == 2 && odd)) break;
          const uint32_t b = 2 * k + odd, at = chk + (k ? k * 8192 - 2048 + odd * 2048 : 0);
          uint32_t mb = sb + CB_M + b * 8, ph = n & 1;
          int it = 1;
          while (true) {
            mbar_wait(mb, ph);
            const bool bad = __any_sync(~0u, m_max(at, b ? at + 2048 : at) == SENT);
            if (one && !bad) mbar_arrive(sb + CB_MV + (b > 2 - SEPV ? b * 8 - 8 : 0));
            if (!bad) break;
            mb = again; ph = mph; mph ^= 1;
            if (one) {
              if (k == 0) sts32(sb + C_BAD, n + 1);
              mbar_expect(mb, b ? 4096 : 2048);
              m_fetch(sb, ring * 65536 + ((near >> ring) & 1) * 4096, b, mb);
            }
            __syncwarp();
            spin_guard(it);
          }
          TR(41 + b * 4); CNT(6 + b, it);
        }
        ring = ring + 1 == MRING ? 0 : ring + 1;
        if (!odd) {
          if (n < STEPS) { TRSYNC(); TRDUMP(n - 2); }
        } else {
          unsigned char* o = g_oimg + (uint32_t)(((n - 1) & (RING - 1)) * (N_CHAIN * 8192) + j * 4096);
          if (n > 0) bar_sync(B_G, 160);
          fence_async_smem();
          if (one) {
            if (n > 0) {
              bulk_store(o + c * 8192, sb + C_OS, 4096);
              bulk_store(o + (c ^ 1) * 8192, sb + C_OS + 4096, 4096);
              asm volatile("cp.async.bulk.commit_group;\ncp.async.bulk.wait_group.read 0;" ::: "memory");
              { const int n_ = n - 1; { const int n = n_; T3(4); (void)n; } }
            }
            mbar_arrive(sb + CB_Q);
            if (n > 0) {
              bulk_done_inc(g_fl + FL_O + c);
              { const int n_ = n - 1; { const int n = n_; T3(5); (void)n; } }
            }
          }
          __syncwarp();
        }
      }
    } else {
      const uint32_t* ts = g_fl + FL_SYNC + near_half(XB_F + 1, c) * 1024 + lane * 2;
      uint32_t t0 = clk() - 100000, last = 0;
      int lag = 0;
#pragma unroll 1
      for (int n = 0; n < STEPS; n++) {
        const uint32_t src = ring * 65536 + ((near >> ring) & 1) * 4096;
        if (lane < 5) mbar_expect(sb + CB_M + lane * 8, lane ? 4096 : 2048);
        __syncwarp();
        if (elect()) {
#pragma unroll
          for (int b = 0; b < 5; b++) {
            wait_until(t0, P.dly[14 + b]);
            m_fetch(sb, src, b, sb + CB_M + b * 8);
            TR(40 + b * 4);
          }
        }
        __syncwarp();
        ring = ring + 1 == MRING ? 0 : ring + 1;
        uint32_t va, vb;
        const uint32_t off = timer_offset(), tag = (uint32_t)(n + 1) << 28;
        if (n > 1) lag += (int)(off - last) - (lag >> 2);
        last = off;
        const uint32_t mine = min(max((lag >> 3) + 256, 0), 511);
        bar_sync(B_QK, 416);
        if (n + 1 == STEPS) break;
        sts32(sb + C_REF + 4, 0);
        const uint32_t c0 = clk(), stamp = c0 + off;
        st_relaxed_if(g_fl + FL_SYNC + lane * 1024 + c, tag | (mine << 19) | (stamp & 0x7FFFF), lane < 2);
        TR(13);
        wait_until(c0, DLYS);
        int it = 0;
        do {
          asm volatile("ld.relaxed.gpu.global.v2.u32 {%0,%1}, [%2];" : "=r"(va), "=r"(vb) : "l"(ts) : "memory");
          spin_guard(it);
        } while (__any_sync(~0u, ((va ^ tag) | (vb ^ tag)) >> 28));
        const int late = __reduce_max_sync(~0u, max((int)((va - stamp) << 13), (int)((vb - stamp) << 13))) >> 13;
        const uint32_t fast = min(((__reduce_max_sync(~0u, max(va, vb)) >> 19) & 511) - mine, 100u);
        t0 = c0 + min((uint32_t)late, clk() - c0);
        if (elect()) {
          sts32(sb + C_REF, t0 + (fast * 3 >> 2));
          mbar_arrive(sb + CB_REF);
        }
        st_relaxed_if(g_fl + FL_TICK + lane * 1024, (uint32_t)(n + 1) << 24 | ((t0 + off) & 0xFFFFFF), c == 0 && lane < 2);
        t0 += fast * 5 >> 2;
        TRV(59, fast);
        TR(14); CNT(11, it);
        bar_sync(B_M, 160);
      }
    }
  }
}

template <int WG>
__device__ __forceinline__ void g_math(const Params& P, uint32_t sb) {
  const int q = g_unit(WG);
  const int lane = threadIdx.x & 31, w = (threadIdx.x >> 5) & 3;
  uint32_t a[136];
  {
    const uint32_t stage = sb + G_W + WG * 73728;
    mbar_wait(sb + W_BAR + WG * 8, 0);
    if (threadIdx.x == 0) TS(23);
    load_frags<34>(a, stage);
    fence_async_smem();
    bar_sync(B_WG0 + WG, 128);
    if (threadIdx.x == 0) TS(24);
    load_wg<GROLE>(P, sb, false, WG, w);
    if (threadIdx.x == 0) TS(25);
    mbar_wait(sb + W_BAR + WG * 8, 1);
  }
  if ((threadIdx.x & 127) == 0) TS(4);
  const uint32_t off0 = (q & 31) * 49152 + (q >> 5) * 8192 + w * 1024 + (lane >> 2) * 64 + (((lane ^ (lane >> 3)) & 3) << 4);
  const uint32_t isq = q >> 6;
#pragma unroll 1
  for (int n = 0; n < STEPS; n++) {
    float d0[32], d1[32];
    if (WG == 0 && n >= LOCK0) bar_sync(B_OE, 160);
    if (n > 0) bar_sync(B_V + WG, 256);
#pragma unroll
    for (int ch = 0; ch < 9; ch++) {
      mbar_wait(sb + G_BAR + ch * 8, n & 1);
      if (ch == 0) { if ((threadIdx.x & 127) == 0) T3(5 + WG * 3); __syncwarp(); }
      if (ch == 4) { if ((threadIdx.x & 127) == 0) T3(6 + WG * 3); __syncwarp(); }
      if (ch == 8 && (WG == 0 ? n > 0 : n + 1 < STEPS)) bar_arrive(B_V + (WG ^ 1), 256);
      wg_fence();
#pragma unroll
      for (int kk = 0; kk < 4; kk++) {
        const int i = ch * 4 + kk;
        float* d = i & 1 ? d1 : d0;
        const uint64_t db = desc_sw128(G_RING + ch * 8192 + (kk & 2) * 32);
        if (i < 2) wg_rs64<0>(d, a + i * 4, db);
        else if (i < 34) wg_rs64<1>(d, a + i * 4, db);
        else wg_ss64<1>(d, desc_sw128(G_W2 + WG * 4096 + (i - 34) * 2048), db);
        wg_ss64<1>(d, desc_sw128(G_W + WG * 73728 + i * 2048), db + 2);
      }
      wg_commit();
      if (ch > 0) { wg_wait<1>(); if (lane == 0) mbar_arrive(sb + G_BAR + 128 + (ch - 1) * 8); }
    }
    wg_wait<0>();
    if (lane == 0) mbar_arrive(sb + G_BAR + 128 + 8 * 8);
    if ((threadIdx.x & 127) == 0) T3(7 + WG * 3);
    __syncwarp();
    uint32_t tw = clk() + (n == 0 ? 0u - 100000u : WG ? 0u : DLYW);
    unsigned char* base = g_qkv + (size_t)(n & (QRING - 1)) * (N_CHAIN * 24576);
#pragma unroll
    for (int i = 0; i < 8; i++) {
      const float* d = (i < 4 ? d0 : d1) + 8 * (i & 2) + 2 * (i & 1);
      wait_until(tw, 0); tw += P.dly[2 + WG];
      *(uint4*)(base + (off0 + (i < 2 ? 0 : i < 4 ? 4096 + isq * 24576 : i < 6 ? 24576 - isq * 20480 : 28672 - isq * 4096)) + (i & 1) * 512) =
        make_uint4(pack2(d[0], d[1]), pack2(d[4], d[5]), pack2(d[8], d[9]), pack2(d[12], d[13]));
    }
    bar_sync(B_M + WG, 160);
  }
}

__device__ __forceinline__ void fill16(void* p, uint32_t v) {
  asm volatile("st.global.v4.u32 [%0], {%1,%1,%1,%1};" :: "l"(p), "r"(v) : "memory");
}
__device__ __forceinline__ void g_load(const Params& P, uint32_t sb) {
  const int lane = threadIdx.x & 31, w = __shfl_sync(~0u, (threadIdx.x >> 5) & 3, 0);
  if (w == 2) return;
  if (w < 2) { bar_sync(15, 192); fence_async_smem(); }
  uint32_t fl = 0;
#pragma unroll 1
  for (int n = w == 3 ? LOCK0 : 0; n < STEPS; n++) {
    if (w && n == LOCK0) { grid_wait(1, lds32(sb + S_GEN)); fl = near_half(XB_F, bid()) * 1024; }
    if (w == 3) {
      const uint32_t tag = (uint32_t)(n - LOCK0 + 1) << 24;
      uint32_t v; int it = 0;
      do { asm volatile("ld.relaxed.gpu.global.u32 %0, [%1];" : "=r"(v) : "l"(g_fl + fl + FL_TICK) : "memory"); spin_guard(it); } while (v < tag);
      const uint32_t off = timer_offset(), now = clk(), t0 = now - ((v ^ tag) >> 24 ? DLYG : (now + off - v) & 0xFFFFFF);
      asm volatile("fence.acquire.gpu;" ::: "memory");
      if (lane == 0) T3(11);
      __syncwarp();
      wait_until(t0, DLYG);
      if (lane == 0) T3(4);
      bar_sync(B_OE, 160);
      continue;
    }
    if (w == 0 || n == 0) {
      if (n < NSEG) wait_flags(g_lnflag + n * 16 + (lane & 1) * 8, 1);
    } else if (n >= LAG) {
      wait_flags(g_fl + fl + FL_F + (lane & 1) * 8, n - LAG + 1);
    }
    if (w) { if (lane == 0) T3(12); bar_sync(B_X, 96); }
    fence_async_global();
    const unsigned char* src = g_lnimg + (uint32_t)((w ? (n >= LAG ? NSEG + n - LAG : 0) : min(n, NSEG - 1)) * 36864);
#pragma unroll 1
    for (int ch = 0; ch < 9; ch++) {
      const uint32_t full = sb + G_BAR + ch * 8;
      mbar_wait(full + 128, (n & 1) ^ 1);
      if (elect()) {
        mbar_expect(full, 4096);
        bulk_load(sb + G_RING + ch * 8192 + w * 4096, src + ch * 4096, 4096, full);
      }
    }
  }
}

__device__ __forceinline__ void g_aux(const Params& P, uint32_t sb) {
  const int lane = threadIdx.x & 31, w = (threadIdx.x >> 5) & 3;
  if (w == 1 || w == 2) {
    const int q = g_unit(w - 1);
    uint32_t* f = g_fl + FL_G + q * 8;
#pragma unroll 1
    for (int n = 0; n < STEPS; n++) {
      const uint32_t ln = opaque_tid() & 31;
      uint4* z = (uint4*)g_oacc + (uint32_t)(((n + 1) % ARING) * (16 * DM) + q * 96 + ln);
      fill16(z, 0); fill16(z + 32, 0); fill16(z + 64, 0);
      if (n + 3 >= MRING && q < 80) fill16((uint4*)g_mimg + (uint32_t)(((n + 3) % MRING) * 4096 + q * 32 + ln), SENT);
      bar_sync(B_M + (w - 1), 160);
      if (lane == 0) { T3(w * 2 - 2); fence_async_global(); flag_release(f, n + 1); T3(w * 2 - 1); }
      __syncwarp();
    }
  } else {
    const uint32_t u = (bid() - N_CHAIN) * 2 + (w & 1), r = u / 36 * 16 + (u & 3) * 4 + (lane >> 3);
    uint32_t o = r * (DM / 8) + (u % 36 >> 2) * 8 + ((lane & 7) ^ ((r >> 1) & 3)), fl = 0;
#pragma unroll 1
    for (int k = -LAG - 1; k < STEPS; k++) {
      if (k < NSEG - 1) bar_sync(B_X, 96);
      if (k < LAG || u >= 72) continue;
      if (k == NSEG - 1) { fl = near_half(XB_F, bid()) * 1024; wait_flags(g_fl + fl + FL_F + (lane & 1) * 8, NSEG + 1); }
      const uint4 x = __ldcg((const uint4*)P.out + o);
      if (k >= NSEG - 1) wait_flags(g_fl + fl + FL_OCNT + (max(k, NSEG) % OCRING) * 8, N_O * 3 * (max(k, NSEG) / OCRING + 1));
      const float4* a = (const float4*)g_oacc + ((k % ARING) * (16 * DM) + 8 * DM + u * 64 + lane * 2);
      const float4 p = __ldcg(a), v = __ldcg(a + 1);
      ((uint4*)P.out)[o] = make_uint4(badd2(x.x, pack2(p.x, p.y)), badd2(x.y, pack2(p.z, p.w)), badd2(x.z, pack2(v.x, v.y)), badd2(x.w, pack2(v.z, v.w)));
      o += 4 * DM;
    }
    if ((threadIdx.x & 127) == 0) TS(7);
  }
}

template <int WG, bool HALF, int KS, int N> __device__ __forceinline__ void o_mma(float* d, const uint32_t* a, uint32_t ob) {
  constexpr uint64_t db = desc_sw128(O_RING + (KS >> 2) * 8192 + (KS & 3) * 32);
  constexpr uint64_t da = desc_sw128(O_W + WG * 40960 + (KS < 40 ? KS / 5 * 2 + KS % 5 / 2 : KS - 24) * 2048);
  if constexpr (KS < 40 && !(KS % 5 & 1)) {
    const uint32_t* r = a + (KS / 5 * 3 + KS % 5 / 2) * 4;
    if constexpr (HALF) wg_rs32k<KS != 0, db>(d, r[0], r[1], r[2], r[3], ob); else wg_rs64<KS != 0>(d, r, db);
  } else {
    if constexpr (HALF) wg_ss32k<da, db>(d, ob); else wg_ss64<1>(d, da, db);
  }
  if constexpr (N > 1) o_mma<WG, HALF, KS + 1, N - 1>(d, a, ob);
}
template <int WG, bool HALF, int GR> __device__ __forceinline__ void o_groups(float* d, const uint32_t* a, uint32_t sb, int n, bool more) {
  const uint32_t ob = n < NSEG ? 0 : 256;
  mbar_wait(sb + O_BAR + GR * 8, n & 1);
  if (GR == 0) { if ((threadIdx.x & 127) == 0) T3(13 + WG); __syncwarp(); }
  if (GR == (WG == 0 ? 2 : 4) && (WG < 2 || n + 1 < STEPS)) bar_arrive(B_V + (WG + 1) % 3, 256);
  wg_fence();
  o_mma<WG, HALF, GR * 8, 8>(d, a, ob);
  if (GR == 4 && more) o_mma<WG, HALF, 40, 4>(d, a, ob);
  wg_commit();
  if (GR > 0) { wg_wait<1>(); if ((threadIdx.x & 31) == 0) mbar_arrive(sb + O_BAR + 120 + GR * 8); }
  if constexpr (GR < 4) o_groups<WG, HALF, GR + 1>(d, a, sb, n, more);
}
template <int WG, bool HALF> __device__ __forceinline__ void o_step(const uint32_t* a, uint32_t sb, uint32_t st0, int n, bool more) {
  float d[HALF ? 16 : 32];
  if (WG > 0 || n > 0) bar_sync(B_V + WG, 256);
  o_groups<WG, HALF, 0>(d, a, sb, n, more);
  wg_wait<0>();
  if ((threadIdx.x & 31) == 0) mbar_arrive(sb + O_BAR + 128 + 4 * 8);
  if ((threadIdx.x & 127) == 0) T3(WG == 0 ? 1 : WG == 1 ? 8 : 12);
  __syncwarp();
#pragma unroll(HALF ? 1 : 2)
  for (int sl = 0; sl < 2; sl++) {
    mbar_wait(sb + OB_ST + WG * 16 + sl * 8, (n & 1) ^ (WG == 0));
    if (!HALF || sl == (n >= NSEG)) {
#pragma unroll
      for (int nb = 0; nb < 4; nb++) {
        const float* r = d + (HALF ? 0 : sl * 16) + nb * 4;
        const uint32_t ad = st0 + sl * 8192 + nb * 2048;
        sts32(ad, __float_as_uint(r[0]));
        sts32(ad + 256, __float_as_uint(r[1]));
        sts32(ad ^ 32, __float_as_uint(r[2]));
        sts32((ad ^ 32) + 256, __float_as_uint(r[3]));
      }
      fence_async_smem();
    }
    bar_arrive((sl ? B_G : B_M) + WG, 160);
  }
}
template <int WG>
__device__ __forceinline__ void o_math(const Params& P, uint32_t sb) {
  const bool more = bid() < N_CHAIN + N_G + 12;
  const int lane = threadIdx.x & 31, w = (threadIdx.x >> 5) & 3, g = lane >> 2, tq = lane & 3;
  uint32_t a[96];
  mbar_wait(sb + W_BAR + WG * 8, 0);
  load_frags<24>(a, sb + WG * 49152);
  fence_async_smem();
  bar_sync(B_INIT, 416);
  load_wg<OROLE>(P, sb, false, WG, w);
  mbar_wait(sb + W_BAR + WG * 8, 1);
  if ((threadIdx.x & 127) == 0) TS(4);
  const uint32_t st0 = sb + O_ST + tq * 512 + ((w * 16 + g) ^ (tq * 8)) * 4;
#pragma unroll 1
  for (int n = 0; n < STEPS; n++) {
    if (n < LAG || n >= NSEG) o_step<WG, true>(a, sb, st0, n, more); else o_step<WG, false>(a, sb, st0, n, more);
  }
}

__device__ __forceinline__ void o_aux(const Params& P, uint32_t sb) {
  const int i = bid() - N_CHAIN - N_G, ksl = i / 3;
  const int c0 = ksl * 11 - max(ksl - 4, 0), nc = ksl < 4 ? 11 : 10;
  const int lane = threadIdx.x & 31, w = __shfl_sync(~0u, (threadIdx.x >> 5) & 3, 0);
  if (w == 0) {
    bar_sync(B_INIT, 416);
    const uint32_t* f = g_fl + FL_O + near_half(XB_F + 1, bid()) * 1024 + min((c0 & ~1) + lane, (c0 + nc - 1) | 1);
#pragma unroll 1
    for (int n = 0; n < STEPS; n++) {
      const unsigned char* src = g_oimg + (uint32_t)(((n % RING) * N_CHAIN + c0) * 8192);
      wait_flags(f, n + 1);
      fence_async_global();
      if (lane == 0) T3(0);
#pragma unroll
      for (int gr = 0; gr < 5; gr++) {
        const uint32_t full = sb + O_BAR + gr * 8, bytes = (gr < 4 ? 2 : nc - 8) * 8192;
        mbar_wait(full + 128, (n & 1) ^ 1);
        if (elect()) {
          if (n < LAG || n >= NSEG) {
            mbar_expect(full, bytes >> 1);
            for (uint32_t o = gr * 16384 + (n < LAG ? 0 : 4096); o < gr * 16384 + bytes; o += 8192) bulk_load(sb + O_RING + o, src + o, 4096, full);
          } else {
            mbar_expect(full, bytes);
            bulk_load(sb + O_RING + gr * 16384, src + gr * 16384, bytes, full);
          }
        }
      }
    }
  } else {
#pragma unroll 1
    for (int n = 0; n < STEPS; n++) {
      float* dst = g_oacc + (uint32_t)((n % ARING) * (64 * DM) + ((i % 3) * 3 + (w - 1 + ksl) % 3) * 1024);
      const bool early = w == 3 && n < NSEG;
      bar_sync(B_M + (w - 1), 160);
      if (lane == 0) {
        T3(w * 2);
        if (n < NSEG) { bulk_reduce(dst, sb + O_ST, 4096); bulk_reduce(dst + 16 * DM, sb + O_ST + 4096, 4096); }
        asm volatile("cp.async.bulk.commit_group;" ::: "memory");
        if (early) {
          asm volatile("cp.async.bulk.wait_group.read 0;" ::: "memory");
          mbar_arrive(sb + OB_ST);
          T3(8 + w);
          bulk_done_inc(g_fl + FL_OCNT + (n % OCRING) * 8);
          T3(w * 2 + 1);
        }
      }
      __syncwarp();
      bar_sync(B_G + (w - 1), 160);
      if (lane == 0) {
        if (n >= LAG) { bulk_reduce(dst + 32 * DM, sb + O_ST + 8192, 4096); bulk_reduce(dst + 48 * DM, sb + O_ST + 12288, 4096); }
        asm volatile("cp.async.bulk.commit_group;\ncp.async.bulk.wait_group.read 1;" ::: "memory");
        if (!early) mbar_arrive(sb + OB_ST + (w % 3) * 16);
        asm volatile("cp.async.bulk.wait_group.read 0;" ::: "memory");
        mbar_arrive(sb + OB_ST + (w % 3) * 16 + 8);
        if (!early) {
          T3(8 + w);
          bulk_done_inc(g_fl + FL_OCNT + (n % OCRING) * 8);
          T3(w * 2 + 1);
        }
      }
      __syncwarp();
    }
  }
}

constexpr uint32_t Y_PITCH = 1168, Y_ROWS = 16 * Y_PITCH;
template <int R> __device__ __forceinline__ void y_rows(uint32_t* y, uint32_t src, uint32_t dst, int w, int bar) {
  const int lane = threadIdx.x & 31;
#pragma unroll
  for (int k = 0; k < 2 * R + 1; k++) {
    const int op = w + k * (16 / R);
    if (k == 2 * R && w >= 4) break;
    uint32_t a, b, c, d;
    ldsm4t(a, b, c, d, src + op * 512 + (lane & 16) * 16 + (lane & 7) * 32 + (lane & 8) * 2);
    stsm4(dst + (lane & 15) * Y_PITCH + op * 32 + (lane & 16), a, b, c, d);
  }
  bar_sync(bar, 512 / R);
  const uint32_t row = dst + ((w & 6) * 2 + (w >> 3) * 2 + (w & 1)) * Y_PITCH + lane * 4;
#pragma unroll
  for (int i = 0; i < 9 * R; i++) y[i] = lds32(row + i / 9 * 2 * Y_PITCH + i % 9 * 128);
}

__device__ __forceinline__ void f_role(const Params& P, uint32_t sb) {
  const int lane = threadIdx.x & 31, w = __shfl_sync(~0u, threadIdx.x >> 5, 0), r0 = (bid() - N_CHAIN - N_G - N_O) * 16;
  if (w == 8) {
    const uint32_t* fo = g_fl + FL_OCNT + near_half(XB_F, bid()) * 1024;
    fence_async_global();
#pragma unroll 1
    for (int n = 0; n < NSEG; n++) {
      bar_sync(2, 288);
      if (elect()) {
        mbar_expect(sb + F_BAR, 36864);
        bulk_load(sb + F_XY, P.X + (size_t)(n * 32 + r0) * DM, 18432, sb + F_BAR);
        bulk_load(sb + F_XY + 18432, g_yT + (size_t)(n * 32 + r0) * DM, 18432, sb + F_BAR);
        mbar_expect(sb + F_BAR + 8, 36864);
        T3(1);
      }
      wait_flags(fo + (n % OCRING) * 8, N_O * 3 * (n / OCRING + 1));
      fence_async_global();
      if (elect()) { bulk_load(sb + F_A, g_oacc + (uint32_t)((n % ARING) * (64 * DM) + r0 * DM), 36864, sb + F_BAR + 8); T3(0); }
    }
  } else if (w == 9) {
#pragma unroll 1
    for (int n = 0; n < NSEG; n++) {
      const uint32_t st = sb + (n & 1) * 36864;
      unsigned char* p = g_lnimg + (uint32_t)((NSEG + n) * 36864 + r0 * 128);
      bar_sync(1, 288);
      if (elect()) {
        T3(2);
#pragma unroll
        for (int i = 0; i < 9; i++) bulk_store(p + i * 4096, st + F_L + i * 2048, 2048);
        asm volatile("cp.async.bulk.commit_group;" ::: "memory");
        bulk_done_inc(g_fl + FL_F + (bid() & 1) * 8);
        T3(3);
        bulk_store(P.out + (size_t)(n * 32 + r0) * DM, st + F_X, 18432);
        asm volatile("cp.async.bulk.commit_group;\ncp.async.bulk.wait_group.read 0;" ::: "memory");
        if (n + 1 == NSEG) bulk_done_inc(g_fl + FL_F + (bid() & 1) * 8);
      }
      __syncwarp();
    }
  } else if (w < 8) {
    const uint32_t row = sb + w * 1152 + lane * 4, acc = sb + F_A + w * 256 + (lane ^ ((w & 6) * 2)) * 8;
    const uint32_t ln = sb + F_L + w * 128 + (((lane >> 2) ^ w) << 4) + (lane & 3) * 4;
#pragma unroll 1
    for (int n = -1; n < NSEG; n++) {
      const uint32_t st = (n & 1) * 36864;
      uint32_t x[18], y[18], l[18];
      if (n >= 0) mbar_wait(sb + F_BAR, n & 1);
#pragma unroll
      for (int i = 0; i < 18; i++) x[i] = lds32(row + F_XY + i / 9 * 9216 + i % 9 * 128);
      y_rows<2>(y, sb + F_XY + 18432, sb + F_Y, w, 3);
      layernorm9<2>(x, l);
#pragma unroll
      for (int i = 0; i < 18; i++) x[i] = badd2(x[i], bmul2(l[i], y[i]));
      if (n >= 0) mbar_wait(sb + F_BAR + 8, n & 1);
      if (threadIdx.x == 0 && n >= 0) T3(4);
      __syncwarp();
      uint2 a[18];
#pragma unroll
      for (int i = 0; i < 18; i++) a[i] = lds64(acc + i / 9 * 2048 + i % 9 * 4096);
#pragma unroll
      for (int i = 0; i < 18; i++) x[i] = badd2(x[i], pack2(__uint_as_float(a[i].x), __uint_as_float(a[i].y)));
      if (n + 1 < NSEG) bar_arrive(2, 288);
      layernorm9<2>(x, l);
#pragma unroll
      for (int i = 0; i < 18; i++) { x[i] = badd2(x[i], bmul2(l[i], y[i])); sts32(row + st + F_X + i / 9 * 9216 + i % 9 * 128, x[i]); }
      layernorm9<2>(x, l);
#pragma unroll
      for (int i = 0; i < 18; i++) sts32(ln + st + i / 9 * 1024 + i % 9 * 2048, l[i]);
      fence_async_smem();
      if (n >= 0) bar_sync(1, 288); else bar_sync(3, 256);
    }
  }
}

constexpr uint32_t P_CH = 147456, P_CHSZ = 12800, P_H = 4352;
static_assert(P_CH + 6 * P_CHSZ <= G_BAR, "prologue smem");

template <int N>
__device__ __forceinline__ void conv_fold(float (*acc)[4], bool hi, uint32_t mine, uint32_t theirs, int bar, int cnt) {
#pragma unroll
  for (int i = 0; i < N / 2; i++) {
    uint4 v;
    v.x = __float_as_uint(hi ? acc[i][0] : acc[i + N / 2][0]); v.y = __float_as_uint(hi ? acc[i][1] : acc[i + N / 2][1]);
    v.z = __float_as_uint(hi ? acc[i][2] : acc[i + N / 2][2]); v.w = __float_as_uint(hi ? acc[i][3] : acc[i + N / 2][3]);
    sts128(mine + i * 512, v);
  }
  bar_sync(bar, cnt);
#pragma unroll
  for (int i = 0; i < N / 2; i++) {
    const uint4 v = lds128(theirs + i * 512);
    acc[i][0] = (hi ? acc[i + N / 2][0] : acc[i][0]) + __uint_as_float(v.x); acc[i][1] = (hi ? acc[i + N / 2][1] : acc[i][1]) + __uint_as_float(v.y);
    acc[i][2] = (hi ? acc[i + N / 2][2] : acc[i][2]) + __uint_as_float(v.z); acc[i][3] = (hi ? acc[i + N / 2][3] : acc[i][3]) + __uint_as_float(v.w);
  }
}
template <int N>
__device__ __forceinline__ void conv_store(const float (*acc)[4], int tile0, uint32_t su, int d, uint32_t dd) {
  const int lane = threadIdx.x & 31, g = lane >> 2, tq = lane & 3;
#pragma unroll
  for (int i = 0; i < N; i++) {
    const uint32_t ad = su + (8 + (tile0 + i) * 8 + g) * 32 + tq * 4, sw = (g & 4) << 2;
    const uint32_t lo = badd2(movmat(pack2(acc[i][0], acc[i][1])), bmul2(lds32(ad + sw), dd));
    const uint32_t hi = badd2(movmat(pack2(acc[i][2], acc[i][3])), bmul2(lds32(ad + (sw ^ 16)), dd));
    ((uint2*)g_yT)[(((tile0 + i) * 8 + g) * DM + d) * 4 + tq] = make_uint2(lo, hi);
  }
}

__device__ __forceinline__ void prologue(const Params& P, uint32_t sb) {
  const int b = bid(), tid = threadIdx.x, lane = tid & 31, warp = tid >> 5, t0 = b * 16;
  const bool isg = b >= N_CHAIN && b < N_CHAIN + N_G;
  const int nch = isg ? 2 : b < 128 ? 6 : 0, chb = b < N_CHAIN ? b * 6 : isg ? b * 2 + 256 : b * 6 - 192;
  const uint32_t tstart = clk();
  if (tid < 288) {
    if (b < 128) {
      const int c = (tid >> 1) * 4, tt = t0 + (tid & 1) * 8;
      uint2 kr[11], vr[8];
#pragma unroll
      for (int i = 0; i < 11; i++) { const int t = tt + i - 3; kr[i] = t >= 0 ? __ldg((const uint2*)(P.K + (size_t)t * DM + c)) : make_uint2(0, 0); }
#pragma unroll
      for (int i = 0; i < 8; i++) vr[i] = __ldg((const uint2*)(P.V + (size_t)(tt + i) * DM + c));
#pragma unroll
      for (int e = 0; e < 2; e++) {
        const uint4 sh = __ldg((const uint4*)(P.shift + c * 4) + e);
        const uint32_t s0 = __byte_perm(sh.x, sh.z, 0x5410), s1 = __byte_perm(sh.x, sh.z, 0x7632);
        const uint32_t s2 = __byte_perm(sh.y, sh.w, 0x5410), s3 = __byte_perm(sh.y, sh.w, 0x7632);
        uint32_t v[8];
#pragma unroll
        for (int i = 0; i < 8; i++) {
          const uint32_t k3 = e ? kr[i].y : kr[i].x, k2 = e ? kr[i + 1].y : kr[i + 1].x, k1 = e ? kr[i + 2].y : kr[i + 2].x, k0 = e ? kr[i + 3].y : kr[i + 3].x;
          v[i] = bmul2(badd2(badd2(badd2(bmul2(k3, s3), bmul2(k2, s2)), bmul2(k1, s1)), bmul2(k0, s0)), e ? vr[i].y : vr[i].x);
        }
        *(uint4*)(g_kvT + (size_t)(c + 2 * e) * KVP + tt) =
          make_uint4(__byte_perm(v[0], v[1], 0x5410), __byte_perm(v[2], v[3], 0x5410), __byte_perm(v[4], v[5], 0x5410), __byte_perm(v[6], v[7], 0x5410));
        *(uint4*)(g_kvT + (size_t)(c + 2 * e + 1) * KVP + tt) =
          make_uint4(__byte_perm(v[0], v[1], 0x7632), __byte_perm(v[2], v[3], 0x7632), __byte_perm(v[4], v[5], 0x7632), __byte_perm(v[6], v[7], 0x7632));
      }
    }
  } else if (tid < 384) {
    const int t = tid - 288;
    for (int i = b * 96 + t; i < 16 * DM; i += N_CTA * 96) ((uint4*)g_oacc)[i] = make_uint4(0, 0, 0, 0);
    if (b * 96 + t < 128 * 8) g_lnflag[b * 96 + t] = 0;
    if (t == 95) sts32(sb + S_GEN, ld_acquire(g_gbar));
    __syncwarp();
    wait_until(tstart, PREFH);
    for (int i = t; i < 32 * nch; i += 96) asm volatile("prefetch.global.L2 [%0];" :: "l"(P.Hk + (size_t)chb * SEQ + i * 64));
  }
  if (warp < 12) {
    bar_arrive(10, 416);
    if (tid == 128) TS(14);
    const int ch = 5 - (warp >> 1), sub = warp & 1, d = chb + ch;
    const uint32_t su = sb + P_CH + ch * P_CHSZ;
    if (ch < nch) {
      const uint32_t* hs = (const uint32_t*)(P.Hk + (size_t)d * SEQ);
#pragma unroll
      for (int q = sub * 32 + lane; q < 256; q += 64) {
        const uint4 c = __ldg((const uint4*)hs + q);
        const uint32_t prev = q ? __ldg(hs + 4 * q - 1) : 0u;
        sts128(su + P_H + 32 + q * 16, make_uint4(__byte_perm(c.x, prev, 0x7610), __byte_perm(c.y, c.x, 0x7610), __byte_perm(c.z, c.y, 0x7610), __byte_perm(c.w, c.z, 0x7610)));
        sts128(su + P_H + 4224 + q * 16, make_uint4(__byte_perm(c.x, 0, 0x1032), __byte_perm(c.y, 0, 0x1032), __byte_perm(c.z, 0, 0x1032), __byte_perm(c.w, 0, 0x1032)));
      }
      if (sub == 1 && lane == 0) sts32(su + P_CHSZ - 16, __bfloat16_as_ushort(P.Dk[d]) * 0x10001u);
      if (sub == 0 && lane < 20) sts128(su + (lane < 16 ? lane * 16 : P_H + (lane & 2) * 2096 + (lane & 1) * 16), make_uint4(0, 0, 0, 0));
    }
    bar_sync(11, 416);
    if (ch < nch) {
#pragma unroll
      for (int q = sub * 32 + lane; q < 256; q += 64) {
        const int row = (q >> 1) + 8;
        sts128(su + row * 32 + (((q & 1) ^ ((row >> 2) & 1)) << 4), __ldcg((const uint4*)(g_kvT + (size_t)d * KVP) + q));
      }
    }
    const int g = lane >> 2, tq = lane & 3;
    const uint32_t sh = su + P_H + (g & 1) * 4192 + (8 + (g >> 1) - tq) * 4;
    float acc[16][4];
#pragma unroll
    for (int i = 0; i < 16; i++) { acc[i][0] = acc[i][1] = acc[i][2] = acc[i][3] = 0.f; }
    auto u_addr = [&](int res) {
      const int row = 8 - res + ((lane >> 4) << 3) + (lane & 7);
      return su + row * 32 + ((((lane >> 3) & 1) ^ ((row >> 2) & 1)) << 4);
    };
    if (ch < nch) {
      bar_sync(1 + ch, 64);
      if (tid == 352) TS(11);
      if (sub) {
#pragma unroll 4
        for (int res = 0; res < 8; res++) {
          uint32_t b0, b1, b2, b3;
          ldsm4(b0, b1, b2, b3, u_addr(res));
          const uint32_t r0 = lds32(sh + res * 32);
          mma16(acc[0], r0, lds32(sh + res * 32 + 16), lds32(sh + res * 32 - 16), r0, b0, b1);
        }
        conv_store<1>(acc, 0, su, d, lds32(su + P_CHSZ - 16));
      }
    }
    bar_arrive(12, 416);
    if (isg && warp < 8) { while ((int)(clk() - tstart - S1G) < 0) __nanosleep(200); load_wg<GROLE>(P, sb, true, warp >> 2, warp & 3); }
    if (ch < nch) {
#pragma unroll 1
      for (int res = sub * 4; res < sub * 4 + 4; res++) {
        uint32_t bf[16][2];
        const uint32_t ad = u_addr(res);
#pragma unroll
        for (int f = 0; f < 16; f += 2) ldsm4(bf[f][0], bf[f][1], bf[f + 1][0], bf[f + 1][1], ad + f * 256);
#pragma unroll
        for (int k = 0; k < 16; k++) {
          const int jj = k & 1 ? k >> 1 : 15 - (k >> 1);
          const uint32_t ah = sh + (8 * jj + res) * 32;
          const uint32_t r0 = lds32(ah), r1 = lds32(ah + 16), rm = lds32(ah - 16);
#pragma unroll
          for (int i = max(jj, 1); i < 16; i++) mma16(acc[i], r0, r1, rm, r0, bf[i - jj][0], bf[i - jj][1]);
        }
      }
      bar_sync(1 + ch, 64);
      if (tid == 352) TS(12);
      const uint32_t xb = su + P_H + lane * 16, dd = lds32(su + P_CHSZ - 16);
      conv_fold<16>(acc, sub, xb + sub * 4096, xb + (sub ^ 1) * 4096, 1 + ch, 64);
      conv_store<8>(acc, sub * 8, su, d, dd);
    }
  } else {
    for (int i = b; i < 194 + MRING * 5; i += N_CTA) {
      const int n = (i - 194) / 5, r = (i - 194) % 5, blk = i < 192 ? i / 6 * 8 + i % 6 : i < 194 ? XB_F + i - 192 : XB_M + n * 8 + r;
      const uint32_t fill = i < 194 ? 0u : SENT;
#pragma unroll 1
      for (int q = tid - 384; q < 256 && warp < 15; q += 96) {
        uint4 v = make_uint4(fill, fill, fill, fill);
        if (i >= 194 && n == 0 && (r > 0 || q < 128)) {
          const bf16* m = P.mem0 + (max(r * 8 - 4, 0) + (q >> 5)) * 16 + ((q >> 1) & 1) * 8 + ((q >> 2) & 7);
          v.x = pack2(__bfloat162float(m[0]), __bfloat162float(m[DM])); v.y = pack2(__bfloat162float(m[2 * DM]), __bfloat162float(m[3 * DM]));
          v.z = pack2(__bfloat162float(m[4 * DM]), __bfloat162float(m[5 * DM])); v.w = pack2(__bfloat162float(m[6 * DM]), __bfloat162float(m[7 * DM]));
        }
        g_xb[blk * 512 + q] = v;
        g_xb[blk * 512 + 256 + q] = v;
      }
    }
    if (tid < 388) g_xb[XB_REF * 512 + (tid & 2) * 128 + (b & ~1) + (tid & 1)] = make_uint4(0, 0, 0, 0);
    else if (tid < 392 && b < N_GRP) g_xb[(b * 8 + 7) * 512 + (tid & 2) * 128 + (tid & 1)] = make_uint4(0, 0, 0, 0);
    if (warp < 15) { bar_arrive(9, 128); bar_sync(7, 96); }
    if (tid == 384) TS(8);
    if (warp == 12) {
      const bf16* w = lane < 6 ? (lane % 3 == 0 ? P.Wk : lane % 3 == 1 ? P.Wv : P.Wq) + (((b >> 5) * 2 + lane / 3) * 32 + (b & 31)) * 2048
                               : (lane < 8 ? P.Wo + (lane - 6) * (9 * 131072) : P.X) + b * 2048;
      uint32_t t = tstart + PREF0;
      if ((int)(clk() - t) > 0) t = clk();
#pragma unroll 1
      for (int st = 0; st < 9 && b < N_CHAIN; st++) {
#pragma unroll 1
        for (int i = 0; i < 9; i++, t += PACE) {
          wait_until(t, 0);
          if (lane == st) asm volatile("cp.async.bulk.prefetch.L2.global [%0], 4096;" :: "l"(w + i * (lane < 6 ? 262144 : 131072)) : "memory");
        }
      }
      if (lane == 0) TS(10);
    } else if (warp == 15) {
      bar_sync(10, 416);
      if (lane == 0) { grid_arrive(0); if (nch) grid_wait(0, lds32(sb + S_GEN)); }
      __syncwarp();
      bar_arrive(11, 416);
      if (lane == 0) TS(1);
      bar_sync(9, 128);
      bar_sync(12, 416);
      if (lane == 0) { TS(16); grid_arrive(2); TS(17); }
    } else if (lane == 0) {
      if (warp == 13 || (warp == 14 && b < N_GRP)) {
        uint32_t* p = (uint32_t*)(g_xb + (warp == 13 ? XB_REF * 512 + b : (b * 8 + 7) * 512));
        int votes = 0;
        for (int rep = 0; rep < 24 && abs(votes) < 7; rep++) {
          uint32_t v0, v1, c0, c1;
          asm volatile("atom.relaxed.gpu.global.add.u32 %0, [%4], 1;\n atom.relaxed.gpu.global.add.u32 %1, [%5], 1;\n"
                       "{.reg .pred p; setp.eq.u32 p, %0, 0x7ffffff3; @p trap; mov.u32 %2, %%clock; setp.eq.u32 p, %1, 0x7ffffff3; @p trap; mov.u32 %3, %%clock;}"
                       : "=&r"(v0), "=&r"(v1), "=&r"(c0), "=&r"(c1) : "l"(p + (rep & 1) * 1024), "l"(p + ((rep & 1) ^ 1) * 1024) : "memory");
          votes += ((c1 - c0 > 80u) == (rep & 1)) ? 1 : -1;
        }
        if (warp == 13) { g_side[b] = votes > 0; TS(9); } else g_near[b] = votes > 0;
      }
    }
    __syncwarp();
    if (warp > 12 && b < N_CHAIN) {
      while ((int)(clk() - tstart - S1DLY) < 0) __nanosleep(200);
      for (int k = warp - 13; k < 8; k += 3) load_wg<CHAIN>(P, sb, true, 1 - k / 4, k & 3);
    }
  }
  if (b < N_CHAIN + N_G && (warp < 8 || (isg && warp >= 12))) bar_arrive(0, 512); else bar_sync(0, 512);
  if (tid == 352) TS(2);
}

__device__ __forceinline__ void publish_y() {
  if (threadIdx.x == 383) { grid_arrive(1); TS(18); }
  __syncwarp();
}

template <int R> __device__ __forceinline__ void ln_tiles(const Params& P, uint32_t sb) {
  const int lane = threadIdx.x & 31, w = (threadIdx.x >> 5) & (16 / R - 1), half = R == 1 ? 0 : threadIdx.x >> 8, u = N_CTA - 1 - bid();
  const int first = R == 1 ? u : 46 - 2 * u + half, step = R == 1 ? 4 : 40, last = R == 1 ? 8 : 128;
  const uint32_t raw = sb + P_CH + half * (18432 + Y_ROWS), mb = sb + T_BAR + (R - 1 + half) * 8;
  const bool lead = w == 16 / R - 1 && lane == 0;
  auto load_y = [&](const bf16* src, int tile) {
    fence_async_global();
    mbar_expect(mb, 18432);
    bulk_load(raw, src + (size_t)tile * 16 * DM, 18432, mb);
  };
  uint32_t nx[9 * R];
  auto load_x = [&](int tile) {
#pragma unroll
    for (int i = 0; i < 9 * R; i++) nx[i] = __ldg((const uint32_t*)(P.X + (size_t)(tile * 16 + w + i / 9 * 8) * DM) + i % 9 * 32 + lane);
  };
  load_x(first);
  if (R == 2) {
    if (lead) { grid_wait(1, lds32(sb + S_GEN)); if (u > 3) TS(13); load_y(g_yT, first); }
    __syncwarp();
  }
#pragma unroll 1
  for (int tile = first, real = R - 1, ph = 0; tile < last; tile += real * step, real = 1, ph ^= 1) {
    uint32_t x[9 * R], l[9 * R], y[9 * R];
    const bool ts = threadIdx.x == 0 && (R == 1 ? tile == first : u > 3 && tile == first + step);
    if (ts) TS(26);
#pragma unroll
    for (int i = 0; i < 9 * R; i++) x[i] = nx[i];
    layernorm9<R>(x, l);
    if (real && tile + step < last) load_x(tile + step);
    if (R == 2 && tile == first + step && u >= N_F && w < 6) load_wg<OROLE>(P, sb, true, w >> 1, half * 2 + (w & 1));
    if (R == 1 && tile == first && lead) {
      if (real) grid_wait(2, lds32(sb + S_GEN));
      TS(13);
      load_y(real ? g_yT : P.Hk, tile);
    }
    bar_sync(13 + half, 512 / R);
    mbar_wait(mb, ph);
    if (ts) TS(28);
    y_rows<R>(y, raw, raw + 18432, w, 13 + half);
    if (ts) TS(29);
    if (lead && real && tile + step < last) { fence_async_smem(); load_y(g_yT, tile + step); }
    __syncwarp();
#pragma unroll
    for (int i = 0; i < 9 * R; i++) x[i] = badd2(x[i], bmul2(l[i], y[i]));
    layernorm9<R>(x, l);
    if (ts && l[0] != 0x12345) TS(30);
#pragma unroll
    for (int r = 0; r < R; r++) store_ln_row(0, tile * 16 + w + r * 8, l + r * 9);
    if (R == 1) {
      __syncthreads();
      if (threadIdx.x == 32 && real) { if (tile < 4) TS(19); st_release(g_lnflag + tile * 8, 1); if (tile < 4) TS(20); }
      __syncwarp();
    }
    if (ts) TS(31);
  }
  if (R == 2) {
    __syncthreads();
    if (threadIdx.x >= 506) {
      asm volatile("fence.acq_rel.gpu;" ::: "memory");
      st_relaxed_if(g_lnflag + ((first ^ (lane & 1)) + (lane - 26) / 2 * step) * 8, 1, true);
    }
    __syncwarp();
    fence_async_smem();
    if (threadIdx.x == 0) TS(15);
  }
}

__global__ void __cluster_dims__(2, 1, 1) __launch_bounds__(512, 1) k_main(const __grid_constant__ Params P) {
  extern __shared__ __align__(1024) unsigned char smem[];
  const uint32_t sb = (uint32_t)__cvta_generic_to_shared(smem);
  const int b = bid(), wg = threadIdx.x >> 7;
  if ((threadIdx.x & 127) == 0) TS(0);
  if (threadIdx.x == 480) {
    if ((sb & 0xFFFFFF) != SBASE) __trap();
    for (int i = 0; i < 6; i++) mbar_init(sb + W_BAR + i * 8, 1);
    if (b < N_CHAIN) {
      mbar_init(sb + CB_FULL, 1); mbar_init(sb + CB_FULL + 8, 1);
      mbar_init(sb + CB_REF, 1);
      mbar_init(sb + CB_SX, 1); mbar_init(sb + CB_OX, 1); mbar_init(sb + CB_XX, 1); mbar_init(sb + CB_Q, 2); mbar_init(sb + CB_VF, 1);
      sts32(sb + C_BAD, 0);
      for (int i = 0; i < 11; i++) mbar_init(sb + CB_M + i * 8, i == 0 ? 5 : i == 5 ? 3 - SEPV : 1);
    } else if (b < N_CHAIN + N_G) {
      for (int i = 0; i < 9; i++) { mbar_init(sb + G_BAR + i * 8, 2); mbar_init(sb + G_BAR + 128 + i * 8, 8); }
    } else if (b < N_CHAIN + N_G + N_O) {
      for (int i = 0; i < 5; i++) { mbar_init(sb + O_BAR + i * 8, 1); mbar_init(sb + O_BAR + 128 + i * 8, 12); }
      for (int i = 0; i < 6; i++) mbar_init(sb + OB_ST + i * 8, 1);
    } else {
      mbar_init(sb + F_BAR, 1); mbar_init(sb + F_BAR + 8, 1);
    }
    asm volatile("fence.mbarrier_init.release.cluster;" ::: "memory");
    fence_async_smem();
  }
  __syncwarp();
  asm volatile("barrier.cluster.arrive.relaxed.aligned;" ::: "memory");
  prologue(P, sb);
  asm volatile("barrier.cluster.wait.aligned;" ::: "memory");
  fence_async_smem();
  if (b >= N_CHAIN + N_G) publish_y();
  if (b >= 128) ln_tiles<1>(P, sb);
  if (b >= N_CHAIN + N_G) ln_tiles<2>(P, sb);
  if ((threadIdx.x & 127) == 0) TS(3);
  if (b < N_CHAIN) {
    if (wg < 2) { reg_inc<200>(); chain_proj(P, sb); }
    else if (wg == 2) { reg_dec<ATTR>(); publish_y(); chain_attn(P, sb); }
    else { reg_dec<112 - ATTR>(); chain_aux(P, sb); }
  } else if (b < N_CHAIN + N_G) {
    if (wg == 0) { reg_inc<232>(); g_math<0>(P, sb); }
    else if (wg == 1) { reg_inc<232>(); g_math<1>(P, sb); }
    else if (wg == 2) { reg_dec<24>(); bar_arrive(15, 192); publish_y(); g_aux(P, sb); }
    else { reg_dec<24>(); g_load(P, sb); }
  } else if (b < N_CHAIN + N_G + N_O) {
    if (wg == 0) { reg_inc<160>(); o_math<0>(P, sb); }
    else if (wg == 1) { reg_inc<160>(); o_math<1>(P, sb); }
    else if (wg == 2) { reg_inc<160>(); o_math<2>(P, sb); }
    else { reg_dec<32>(); o_aux(P, sb); }
  } else {
    f_role(P, sb);
  }
}

}

extern "C" void kernel_launch(void* const* d_in, const int* in_sizes, int n_in, void* d_out, int out_size) {
  typedef CUresult (*Encode)(CUtensorMap*, CUtensorMapDataType, cuuint32_t, void*, const cuuint64_t*, const cuuint64_t*, const cuuint32_t*, const cuuint32_t*,
                             CUtensorMapInterleave, CUtensorMapSwizzle, CUtensorMapL2promotion, CUtensorMapFloatOOBfill);
  static Encode encode = nullptr;
  if (!encode) cudaGetDriverEntryPoint("cuTensorMapEncodeTiled", (void**)&encode, cudaEnableDefault);
  Params P;
  for (int i = 0; i < 11; i++) {
    const bool wo = i == 6 || i == 7;
    const cuuint64_t cols = wo ? DM : HD, rows = HD + DM - cols, pitch = cols * 2;
    const cuuint64_t dim[4][5] = {{cols, 2, 8, 2, 18}, {cols, 16, 1, 1, rows / 16}, {cols, 2, 4, 4, rows / 32}, {64, 16, 64, 2, 18}};
    const cuuint64_t stride[4][4] = {{8 * pitch, pitch, 16 * pitch, 32 * pitch}, {pitch, pitch, pitch, 16 * pitch},
                                     {pitch, 8 * pitch, 2 * pitch, 32 * pitch}, {pitch, 128, 16 * pitch, 32 * pitch}};
    const cuuint32_t box[4][5] = {{64, 2, 8, 1, 18}, {64, 16, 1, 1, 1}, {64, 2, 4, 2, 1}, {64, 16, 2, 1, 18}}, one[5] = {1, 1, 1, 1, 1};
    const int k = i < 3 ? 0 : i < 7 ? 1 : i < 8 ? 2 : 3;
    encode(&P.map[i], CU_TENSOR_MAP_DATA_TYPE_BFLOAT16, 5, d_in[wo ? 11 : 8 + (i & 7) % 3], dim[k], stride[k], box[k], one,
           CU_TENSOR_MAP_INTERLEAVE_NONE, CU_TENSOR_MAP_SWIZZLE_128B, CU_TENSOR_MAP_L2_PROMOTION_L2_128B, CU_TENSOR_MAP_FLOAT_OOB_FILL_NONE);
  }
  P.X = (const bf16*)d_in[0]; P.K = (const bf16*)d_in[1]; P.V = (const bf16*)d_in[2];
  P.shift = (const bf16*)d_in[3]; P.Hk = (const bf16*)d_in[4]; P.Dk = (const bf16*)d_in[5];
  P.mem0 = (const bf16*)d_in[7];
  P.Wq = (const bf16*)d_in[8]; P.Wk = (const bf16*)d_in[9]; P.Wv = (const bf16*)d_in[10]; P.Wo = (const bf16*)d_in[11];
  P.out = (bf16*)d_out;
  for (int i = 0; i < 24; i++) P.dly[i] = h_dly[i];
  cudaFuncSetAttribute(k_main, cudaFuncAttributeMaxDynamicSharedMemorySize, SMEM_BYTES);
  k_main<<<N_CTA, 512, SMEM_BYTES>>>(P);
}
```

```cpp
#include <cuda.h>
#include <cuda_runtime.h>
#include <cuda_bf16.h>
#include <stdint.h>

namespace {

typedef __nv_bfloat16 bf16;

constexpr int SEQ = 2048, DM = 576, HD = 4096, NSEG = 64;
constexpr int LAG = 7, STEPS = NSEG + LAG, RING = 8;
constexpr int LOCK0 = 3, QRING = LOCK0 + 1;
static_assert(LAG < RING, "ring");
constexpr int N_CHAIN = 64, N_G = 48, N_O = 18, N_F = 2;
constexpr uint32_t SBASE = 1024;
constexpr uint32_t SENT = 0xFFFFFFFFu;
constexpr int SPIN_MAX = 1 << 22;

__device__ __forceinline__ uint32_t bid() {
  uint32_t b;
  asm volatile("mov.u32 %0, %%ctaid.x;" : "=r"(b));
  return b < 6 ? b + 106 : b < 8 ? b + 122 : b < 114 ? b - 8 : b < 130 ? b - 2 : b;
}
__device__ __forceinline__ uint32_t chain_id() { return blockIdx.x - 8; }
constexpr int KVP = SEQ + 64;
__device__ __align__(1024) bf16 g_kvT[DM * KVP];
__device__ __align__(1024) bf16 g_yT[DM * SEQ];
__device__ __align__(1024) unsigned char g_lnimg[2 * NSEG * 9 * 4096];
__device__ __align__(1024) unsigned char g_qkv[QRING * N_CHAIN * 24576];
__device__ __align__(1024) unsigned char g_oimg[RING * N_CHAIN * 8192];
constexpr int ARING = 16;
static_assert(ARING >= LAG + 9, "accumulator ring");
__device__ __align__(1024) float g_oacc[ARING * 64 * DM];
constexpr int MRING = LAG + 4, N_GRP = 32 + MRING + 1;
constexpr int XB_M = 256, XB_F = XB_M + MRING * 8, XB_REF = XB_F + 2, N_CTA = N_CHAIN + N_G + N_O + N_F;
__device__ __align__(65536) uint4 g_xb[N_GRP * 4096];
#define g_mimg ((uint32_t*)(g_xb + XB_M * 512))
__device__ uint32_t g_near[N_GRP];
__device__ uint32_t g_side[N_CTA];
__device__ __align__(128) uint32_t g_gbar[3 * 32];
constexpr int FL_G = 0, FL_F = 96 * 8, FL_OCNT = FL_F + 2 * 8, OCRING = 16, FL_TICK = 992, FL_O = 2048, FL_SYNC = FL_O + 128;
static_assert(FL_OCNT + OCRING * 8 <= FL_TICK, "flag block");
#define g_fl ((uint32_t*)(g_xb + XB_F * 512))
__device__ __align__(1024) uint32_t g_lnflag[128 * 8];
#define TS(slot)

#define CNT(slot, tries)
#define T3(slot)
#define TR(slot)
#define TRV(slot, val)
#define TRD(slot, dep)
#define TRSYNC()
#define TRDUMP(n)
#define CLK(t) "{.reg .b64 x; .reg .b32 h; mov.u64 x, %%clock64; mov.b64 {" t ", h}, x;}"
__device__ __forceinline__ uint32_t clk() { uint32_t t; asm volatile(CLK("%0") : "=r"(t) :: "memory"); return t; }
__device__ __forceinline__ void wait_until(uint32_t t0, uint32_t d) {
  asm volatile("{.reg .pred p; .reg .u32 t;\n"
               "W: " CLK("t") " sub.u32 t, t, %0; setp.lt.s32 p, t, 0; @p bra.uni W;}"
               :: "r"(t0 + d) : "memory");
}
__device__ __forceinline__ uint32_t pack2(float lo, float hi) {
  uint32_t r; asm("cvt.rn.bf16x2.f32 %0, %1, %2;" : "=r"(r) : "f"(hi), "f"(lo)); return r;
}
__device__ __forceinline__ float bf_lo(uint32_t v) { return __uint_as_float(v << 16); }
__device__ __forceinline__ float bf_hi(uint32_t v) { return __uint_as_float(v & 0xFFFF0000u); }

__device__ __forceinline__ void st_b128(void* p, uint32_t a, uint32_t b, uint32_t c, uint32_t d) {
  asm volatile("{.reg .b128 v; mov.b128 v, {%1,%2,%3,%4}; st.relaxed.gpu.global.b128 [%0], v;}" :: "l"(p), "r"(a), "r"(b), "r"(c), "r"(d) : "memory");
}
__device__ __forceinline__ void st_relaxed_if(void* p, uint32_t a, bool on) {
  asm volatile("{.reg .pred p; setp.ne.u32 p, %2, 0; @p st.relaxed.gpu.global.u32 [%0], %1;}" :: "l"(p), "r"(a), "r"((uint32_t)on) : "memory");
}
__device__ __forceinline__ uint32_t ld_acquire(const uint32_t* p) {
  uint32_t v; asm volatile("ld.acquire.gpu.global.u32 %0, [%1];" : "=r"(v) : "l"(p) : "memory"); return v;
}
__device__ __forceinline__ void st_release(uint32_t* p, uint32_t v) {
  asm volatile("st.release.gpu.global.u32 [%0], %1;" :: "l"(p), "r"(v) : "memory");
}
__device__ __forceinline__ void bulk_reduce(float* dst, uint32_t src, uint32_t bytes) {
  asm volatile("cp.reduce.async.bulk.global.shared::cta.bulk_group.add.f32 [%0], [%1], %2;" :: "l"(dst), "r"(src), "r"(bytes) : "memory");
}
__device__ __forceinline__ void bulk_done_inc(uint32_t* p) {
  asm volatile("cp.async.bulk.wait_group 0;\n"
               "fence.proxy.async.global;\nfence.release.gpu;\n"
               "red.relaxed.gpu.global.add.u32 [%0], 1;\nred.relaxed.gpu.global.add.u32 [%0+4096], 1;" :: "l"(p) : "memory");
}
__device__ __forceinline__ void flag_release(uint32_t* p, uint32_t v) {
  asm volatile("fence.release.gpu;\nst.relaxed.gpu.global.u32 [%0], %1;\nst.relaxed.gpu.global.u32 [%0+4096], %1;" :: "l"(p), "r"(v) : "memory");
}
__device__ __forceinline__ void spin_guard(int& it) {
  asm volatile("{.reg .pred p; add.s32 %0, %0, 1; setp.gt.s32 p, %0, %1; @p trap;}" : "+r"(it) : "n"(SPIN_MAX));
}
__device__ __forceinline__ void wait_flags(const uint32_t* p, uint32_t v) {
  int it = 0;
  while (true) {
    uint32_t x; asm volatile("ld.relaxed.gpu.global.u32 %0, [%1];" : "=r"(x) : "l"(p) : "memory");
    if (__all_sync(~0u, x >= v)) break;
    spin_guard(it);
  }
  asm volatile("fence.acquire.gpu;" ::: "memory");
}
__device__ __forceinline__ uint32_t timer_offset() {
  uint32_t g0, g;
  asm volatile("mov.u32 %0, %%globaltimer_lo;" : "=r"(g0) :: "memory");
  do { asm volatile("mov.u32 %0, %%globaltimer_lo;" : "=r"(g) :: "memory"); } while (g == g0);
  return (g >> 5) * 58 - clk();
}
__device__ __forceinline__ void grid_arrive(int i) {
  asm volatile("red.release.gpu.global.add.u32 [%0], %1;" :: "l"(g_gbar + i * 32), "r"(bid() ? 1u : 257u - N_CTA) : "memory");
}
__device__ __forceinline__ void grid_wait(int i, uint32_t gen) {
  int it = 0;
  while (((ld_acquire(g_gbar + i * 32) ^ gen) >> 8) == 0) spin_guard(it);
}
__device__ __forceinline__ bool elect() {
  uint32_t r; asm volatile("{.reg .pred p; elect.sync _|p, -1; selp.u32 %0, 1, 0, p;}" : "=r"(r)); return r;
}
__device__ __forceinline__ void bar_sync(int id, int cnt) { asm volatile("bar.sync %0, %1;" :: "r"(id), "r"(cnt) : "memory"); }
__device__ __forceinline__ void bar_arrive(int id, int cnt) { asm volatile("bar.arrive %0, %1;" :: "r"(id), "r"(cnt) : "memory"); }
template <int id, int cnt> __device__ __forceinline__ void bar_arrive_after(uint32_t a, uint32_t b) {
  asm volatile("{.reg .pred p; setp.ne.u32 p, %2, 0xfff12345; setp.ne.and.u32 p, %3, 0xfff12345, p; @p bar.arrive %0, %1;}" :: "n"(id), "n"(cnt), "r"(a), "r"(b) : "memory");
}
template <int id, int cnt> __device__ __forceinline__ void bar_sync_after(uint32_t a) {
  asm volatile("{.reg .pred p; setp.ne.u32 p, %2, 0xfff12345; @p bar.sync %0, %1;}" :: "n"(id), "n"(cnt), "r"(a) : "memory");
}
__device__ __forceinline__ void fence_async_smem() { asm volatile("fence.proxy.async.shared::cta;" ::: "memory"); }
__device__ __forceinline__ void fence_async_global() { asm volatile("fence.proxy.async.global;" ::: "memory"); }
__device__ __forceinline__ void mbar_init(uint32_t mb, int cnt) { asm volatile("mbarrier.init.shared::cta.b64 [%0], %1;" :: "r"(mb), "r"(cnt) : "memory"); }
__device__ __forceinline__ void mbar_arrive(uint32_t mb) { asm volatile("mbarrier.arrive.shared::cta.b64 _, [%0];" :: "r"(mb) : "memory"); }
__device__ __forceinline__ void mbar_expect(uint32_t mb, uint32_t bytes) {
  asm volatile("mbarrier.arrive.expect_tx.shared::cta.b64 _, [%0], %1;" :: "r"(mb), "r"(bytes) : "memory");
}
__device__ __forceinline__ void mbar_wait(uint32_t mb, uint32_t parity) {
  asm volatile("{.reg .pred p;\nW: mbarrier.try_wait.parity.shared::cta.b64 p, [%0], %1;\n@!p bra W;}" :: "r"(mb), "r"(parity) : "memory");
}
__device__ __forceinline__ void bulk_load(uint32_t dst, const void* src, uint32_t bytes, uint32_t mb) {
  asm volatile("cp.async.bulk.shared::cluster.global.mbarrier::complete_tx::bytes [%0], [%1], %2, [%3];" :: "r"(dst), "l"(src), "r"(bytes), "r"(mb) : "memory");
}
__device__ __forceinline__ void bulk_store(void* dst, uint32_t src, uint32_t bytes) {
  asm volatile("cp.async.bulk.global.shared::cta.bulk_group [%0], [%1], %2;" :: "l"(dst), "r"(src), "r"(bytes) : "memory");
}
__device__ __forceinline__ uint32_t mapa(uint32_t a, uint32_t rank) {
  uint32_t r; asm("mapa.shared::cluster.u32 %0, %1, %2;" : "=r"(r) : "r"(a), "r"(rank)); return r;
}
__device__ __forceinline__ void st_async4(uint32_t dst, float a, float b, float c, float d, uint32_t mb) {
  asm volatile("st.async.shared::cluster.mbarrier::complete_tx::bytes.v4.f32 [%0], {%1,%2,%3,%4}, [%5];" :: "r"(dst), "f"(a), "f"(b), "f"(c), "f"(d), "r"(mb) : "memory");
}
__device__ __forceinline__ void st_async1(uint32_t dst, uint32_t a, uint32_t mb) {
  asm volatile("st.async.shared::cluster.mbarrier::complete_tx::bytes.u32 [%0], %1, [%2];" :: "r"(dst), "r"(a), "r"(mb) : "memory");
}
__device__ __forceinline__ uint4 lds128(uint32_t a) {
  uint4 v; asm volatile("ld.shared.v4.u32 {%0,%1,%2,%3}, [%4];" : "=r"(v.x), "=r"(v.y), "=r"(v.z), "=r"(v.w) : "r"(a) : "memory"); return v;
}
__device__ __forceinline__ uint2 lds64(uint32_t a) {
  uint2 v; asm volatile("ld.shared.v2.u32 {%0,%1}, [%2];" : "=r"(v.x), "=r"(v.y) : "r"(a) : "memory"); return v;
}
__device__ __forceinline__ uint32_t lds32(uint32_t a) {
  uint32_t v; asm volatile("ld.shared.u32 %0, [%1];" : "=r"(v) : "r"(a) : "memory"); return v;
}
__device__ __forceinline__ void sts128(uint32_t a, uint4 v) {
  asm volatile("st.shared.v4.u32 [%0], {%1,%2,%3,%4};" :: "r"(a), "r"(v.x), "r"(v.y), "r"(v.z), "r"(v.w) : "memory");
}
__device__ __forceinline__ void sts32(uint32_t a, uint32_t x) { asm volatile("st.shared.u32 [%0], %1;" :: "r"(a), "r"(x) : "memory"); }
__device__ __forceinline__ void ldsm4(uint32_t& r0, uint32_t& r1, uint32_t& r2, uint32_t& r3, uint32_t a) {
  asm volatile("ldmatrix.sync.aligned.m8n8.x4.shared.b16 {%0,%1,%2,%3}, [%4];" : "=r"(r0), "=r"(r1), "=r"(r2), "=r"(r3) : "r"(a) : "memory");
}
__device__ __forceinline__ void ldsm4t(uint32_t& r0, uint32_t& r1, uint32_t& r2, uint32_t& r3, uint32_t a) {
  asm volatile("ldmatrix.sync.aligned.m8n8.x4.trans.shared.b16 {%0,%1,%2,%3}, [%4];" : "=r"(r0), "=r"(r1), "=r"(r2), "=r"(r3) : "r"(a) : "memory");
}
__device__ __forceinline__ void stsm4(uint32_t a, uint32_t r0, uint32_t r1, uint32_t r2, uint32_t r3) {
  asm volatile("stmatrix.sync.aligned.m8n8.x4.shared.b16 [%0], {%1,%2,%3,%4};" :: "r"(a), "r"(r0), "r"(r1), "r"(r2), "r"(r3) : "memory");
}
__device__ __forceinline__ uint32_t movmat(uint32_t a) {
  uint32_t d; asm volatile("movmatrix.sync.aligned.m8n8.trans.b16 %0, %1;" : "=r"(d) : "r"(a)); return d;
}
__device__ __forceinline__ void mma16(float* d, uint32_t a0, uint32_t a1, uint32_t a2, uint32_t a3, uint32_t b0, uint32_t b1) {
  asm volatile("mma.sync.aligned.m16n8k16.row.col.f32.bf16.bf16.f32 {%0,%1,%2,%3}, {%4,%5,%6,%7}, {%8,%9}, {%0,%1,%2,%3};"
    : "+f"(d[0]), "+f"(d[1]), "+f"(d[2]), "+f"(d[3]) : "r"(a0), "r"(a1), "r"(a2), "r"(a3), "r"(b0), "r"(b1));
}
__device__ __forceinline__ void mma8(float* d, uint32_t a0, uint32_t a1, uint32_t b0) {
  asm volatile("mma.sync.aligned.m16n8k8.row.col.f32.bf16.bf16.f32 {%0,%1,%2,%3}, {%4,%5}, {%6}, {%0,%1,%2,%3};"
    : "+f"(d[0]), "+f"(d[1]), "+f"(d[2]), "+f"(d[3]) : "r"(a0), "r"(a1), "r"(b0));
}
__device__ __forceinline__ float rcp(float x) { float r; asm("rcp.approx.ftz.f32 %0, %1;" : "=f"(r) : "f"(x)); return r; }
__device__ __forceinline__ float ex2(float x) { float r; asm("ex2.approx.ftz.f32 %0, %1;" : "=f"(r) : "f"(x)); return r; }

__host__ __device__ constexpr uint64_t mkdesc(uint32_t off, uint32_t lbo, uint32_t sbo, uint32_t swz) {
  return (uint64_t)((SBASE + off) >> 4) | ((uint64_t)(lbo >> 4) << 16) | ((uint64_t)(sbo >> 4) << 32) | ((uint64_t)swz << 62);
}
__host__ __device__ constexpr uint64_t desc_sw128(uint32_t off) { return mkdesc(off, 16, 1024, 1); }
__host__ __device__ constexpr uint64_t desc_n16(uint32_t off) { return mkdesc(off, 256, 128, 0); }
__host__ __device__ constexpr uint64_t desc_m(uint32_t off) { return mkdesc(off, 16, 256, 3); }

__host__ __device__ constexpr uint64_t desc_sw64(uint32_t off) { return mkdesc(off, 16, 512, 2); }

__device__ __forceinline__ void wg_fence() { asm volatile("wgmma.fence.sync.aligned;" ::: "memory"); }
__device__ __forceinline__ void wg_commit() { asm volatile("wgmma.commit_group.sync.aligned;" ::: "memory"); }
template <int N> __device__ __forceinline__ void wg_wait() { asm volatile("wgmma.wait_group.sync.aligned %0;" :: "n"(N) : "memory"); }

#define ACC8(d) "+f"(d[0]), "+f"(d[1]), "+f"(d[2]), "+f"(d[3]), "+f"(d[4]), "+f"(d[5]), "+f"(d[6]), "+f"(d[7])
#define ACC32(d) ACC8(d), ACC8((d + 8)), ACC8((d + 16)), ACC8((d + 24))
#define R8 "{%0,%1,%2,%3,%4,%5,%6,%7}"
#define R32 "{%0,%1,%2,%3,%4,%5,%6,%7,%8,%9,%10,%11,%12,%13,%14,%15,%16,%17,%18,%19,%20,%21,%22,%23,%24,%25,%26,%27,%28,%29,%30,%31}"
template <int SD> __device__ __forceinline__ void wg_rs16(float* d, const uint32_t* a, uint64_t db) {
  asm volatile("wgmma.mma_async.sync.aligned.m64n16k16.f32.bf16.bf16 " R8 ", {%8,%9,%10,%11}, %12, %13, 1, 1, 1;"
    : ACC8(d) : "r"(a[0]), "r"(a[1]), "r"(a[2]), "r"(a[3]), "l"(db), "n"(SD));
}
template <int SD> __device__ __forceinline__ void wg_ss16(float* d, uint64_t da, uint64_t db) {
  asm volatile("wgmma.mma_async.sync.aligned.m64n16k16.f32.bf16.bf16 " R8 ", %8, %9, %10, 1, 1, 1, 1;"
    : ACC8(d) : "l"(da), "l"(db), "n"(SD));
}
template <int SD, uint64_t DA, uint64_t DB> __device__ __forceinline__ void wg_ss16o(float* d, uint32_t oa, uint32_t ob) {
  asm volatile("{.reg .b32 x, y; .reg .b64 a, b; add.u32 x, %8, %10; add.u32 y, %9, %12; mov.b64 a, {x, %11}; mov.b64 b, {y, %13};\n"
               "wgmma.mma_async.sync.aligned.m64n16k16.f32.bf16.bf16 " R8 ", a, b, %14, 1, 1, 1, 1;}"
    : ACC8(d) : "r"(oa), "r"(ob), "n"((uint32_t)DA), "n"((uint32_t)(DA >> 32)), "n"((uint32_t)DB), "n"((uint32_t)(DB >> 32)), "n"(SD));
}
template <int SD> __device__ __forceinline__ void wg_rs64(float* d, const uint32_t* a, uint64_t db) {
  asm volatile("wgmma.mma_async.sync.aligned.m64n64k16.f32.bf16.bf16 " R32 ", {%32,%33,%34,%35}, %36, %37, 1, 1, 0;"
    : ACC32(d) : "r"(a[0]), "r"(a[1]), "r"(a[2]), "r"(a[3]), "l"(db), "n"(SD));
}
template <int SD> __device__ __forceinline__ void wg_ss64(float* d, uint64_t da, uint64_t db) {
  asm volatile("wgmma.mma_async.sync.aligned.m64n64k16.f32.bf16.bf16 " R32 ", %32, %33, %34, 1, 1, 1, 0;"
    : ACC32(d) : "l"(da), "l"(db), "n"(SD));
}
#define WG_RSO(NAME, SHAPE, REGS, ACC, A, TB) \
template <int SD, uint64_t DB> __device__ __forceinline__ void NAME(float* d, uint32_t a0, uint32_t a1, uint32_t a2, uint32_t a3, uint32_t ob) { \
  asm volatile("{.reg .b64 b; mov.b64 b, {" A(4) ", " A(5) "};\nwgmma.mma_async.sync.aligned." SHAPE ".f32.bf16.bf16 " REGS \
               ", {" A(0) "," A(1) "," A(2) "," A(3) "}, b, " A(6) ", 1, 1, " TB ";}" \
    : ACC(d) : "r"(a0), "r"(a1), "r"(a2), "r"(a3), "r"(ob + (uint32_t)DB), "n"((uint32_t)(DB >> 32)), "n"(SD)); \
}
#define ACC4(d) "+f"(d[0]), "+f"(d[1]), "+f"(d[2]), "+f"(d[3])
#define ACC16(d) ACC8(d), ACC8((d + 8))
#define OP4(i) OP4_##i
#define OP4_0 "%4"
#define OP4_1 "%5"
#define OP4_2 "%6"
#define OP4_3 "%7"
#define OP4_4 "%8"
#define OP4_5 "%9"
#define OP4_6 "%10"
#define OP16(i) OP16_##i
#define OP16_0 "%16"
#define OP16_1 "%17"
#define OP16_2 "%18"
#define OP16_3 "%19"
#define OP16_4 "%20"
#define OP16_5 "%21"
#define OP16_6 "%22"
#define OP32(i) OP32_##i
#define OP32_0 "%32"
#define OP32_1 "%33"
#define OP32_2 "%34"
#define OP32_3 "%35"
#define OP32_4 "%36"
#define OP32_5 "%37"
#define OP32_6 "%38"
WG_RSO(wg_rs8o, "m64n8k16", "{%0,%1,%2,%3}", ACC4, OP4, "1")
#define R16 "{%0,%1,%2,%3,%4,%5,%6,%7,%8,%9,%10,%11,%12,%13,%14,%15}"
WG_RSO(wg_rs32o, "m64n32k16", R16, ACC16, OP16, "1")
WG_RSO(wg_rs64o, "m64n64k16", R32, ACC32, OP32, "0")
WG_RSO(wg_rs32k, "m64n32k16", R16, ACC16, OP16, "0")
template <uint64_t DA, uint64_t DB> __device__ __forceinline__ void wg_ss32k(float* d, uint32_t ob) {
  asm volatile("{.reg .b64 b; mov.b64 b, {%17, %18};\nwgmma.mma_async.sync.aligned.m64n32k16.f32.bf16.bf16 " R16 ", %16, b, 1, 1, 1, 1, 0;}"
    : ACC16(d) : "l"(DA), "r"(ob + (uint32_t)DB), "n"((uint32_t)(DB >> 32)));
}
template <int N> __device__ __forceinline__ void reg_inc() { asm volatile("setmaxnreg.inc.sync.aligned.u32 %0;" :: "n"(N)); }
template <int N> __device__ __forceinline__ void reg_dec() { asm volatile("setmaxnreg.dec.sync.aligned.u32 %0;" :: "n"(N)); }

template <int KS>
__device__ __forceinline__ void load_frags(uint32_t* a, uint32_t src) {
  const int lane = threadIdx.x & 31, w = (threadIdx.x >> 5) & 3;
  const int k = ((lane >> 4) << 3) + (lane & 7), u = w * 2 + ((lane >> 3) & 1);
  const uint32_t base = src + k * 128 + ((u ^ (k & 7)) << 4);
#pragma unroll
  for (int ks = 0; ks < KS; ks++) ldsm4t(a[ks * 4], a[ks * 4 + 1], a[ks * 4 + 2], a[ks * 4 + 3], base + ks * 2048);
}

__device__ __forceinline__ uint32_t badd2(uint32_t a, uint32_t b) { uint32_t r; asm("add.rn.bf16x2 %0, %1, %2;" : "=r"(r) : "r"(a), "r"(b)); return r; }
__device__ __forceinline__ uint32_t bsub2(uint32_t a, uint32_t b) { uint32_t r; asm("sub.rn.bf16x2 %0, %1, %2;" : "=r"(r) : "r"(a), "r"(b)); return r; }
__device__ __forceinline__ uint32_t bmul2(uint32_t a, uint32_t b) { uint32_t r; asm("mul.rn.bf16x2 %0, %1, %2;" : "=r"(r) : "r"(a), "r"(b)); return r; }
__device__ __forceinline__ uint32_t bfma2(uint32_t a, uint32_t b, uint32_t c) { uint32_t r; asm("fma.rn.bf16x2 %0, %1, %2, %3;" : "=r"(r) : "r"(a), "r"(b), "r"(c)); return r; }
template <int R> __device__ __forceinline__ void layernorm9(const uint32_t* x, uint32_t* o) {
  const uint32_t ones = 0x3F803F80u;
  float a[R][3][4], q[R], s[R];
#pragma unroll
  for (int i = 0; i < 9 * R; i++) {
    float* d = a[i % R][i / R % 3];
    if (i < 3 * R) d[0] = d[1] = d[2] = d[3] = 0.f;
    mma8(d, x[i % R * 9 + i / R], ones, x[i % R * 9 + i / R]);
  }
#pragma unroll
  for (int r = 0; r < R; r++) {
    q[r] = threadIdx.x & 4 ? a[r][0][1] + a[r][1][1] + a[r][2][1] : a[r][0][0] + a[r][1][0] + a[r][2][0];
    s[r] = (a[r][0][2] + a[r][0][3]) + (a[r][1][2] + a[r][1][3]) + (a[r][2][2] + a[r][2][3]);
  }
#pragma unroll
  for (int r = 0; r < R; r++) { q[r] += __shfl_xor_sync(~0u, q[r], 4); s[r] += __shfl_xor_sync(~0u, s[r], 1); }
#pragma unroll
  for (int r = 0; r < R; r++) { q[r] += __shfl_xor_sync(~0u, q[r], 9); s[r] += __shfl_xor_sync(~0u, s[r], 2); }
#pragma unroll
  for (int r = 0; r < R; r++) q[r] = __shfl_sync(~0u, q[r], 0) + __shfl_sync(~0u, q[r], 18);
#pragma unroll
  for (int r = 0; r < R; r++) {
    const float mean = s[r] * (1.f / DM), var = fmaxf(fmaf(q[r], 1.f / DM, -mean * mean), 0.f);
    float sd;
    asm("sqrt.approx.ftz.f32 %0, %1;" : "=f"(sd) : "f"(bf_lo(pack2(bf_lo(pack2(var, 0.f)) + 1e-5f, 0.f))));
    const float inv = rcp(bf_lo(pack2(sd, 0.f)));
    const uint32_t mb = pack2(mean, mean), hi = pack2(inv, inv), lo = pack2(inv - bf_lo(hi), inv - bf_lo(hi));
#pragma unroll
    for (int i = r * 9; i < r * 9 + 9; i++) {
      const uint32_t d = bsub2(x[i], mb);
      o[i] = bfma2(d, hi, bmul2(d, lo));
    }
  }
}
__device__ __forceinline__ void store_ln_row(int layer, int tok, const uint32_t* o) {
  const int lane = threadIdx.x & 31, r = tok & 31;
  unsigned char* p = g_lnimg + (size_t)(layer * NSEG + (tok >> 5)) * (9 * 4096) + r * 128 + (((lane >> 2) ^ (r & 7)) << 4) + (lane & 3) * 4;
#pragma unroll
  for (int i = 0; i < 9; i++) *(uint32_t*)(p + i * 4096) = o[i];
}
struct Params { CUtensorMap map[11]; const bf16 *X, *K, *V, *shift, *Hk, *Dk, *mem0, *Wq, *Wk, *Wv, *Wo; bf16* out; uint32_t dly[24]; };
#define DLYS P.dly[0]
#define DLYW P.dly[1]
#define DLYK P.dly[4]
#define DLYG P.dly[5]
#define KWIN P.dly[6]
#define KMIN P.dly[7]
#define PREF0 P.dly[19]
#define PACE P.dly[20]
#define S1G P.dly[21]
#define S1DLY P.dly[22]
#define PREFH P.dly[23]
uint32_t h_dly[24] = {800, 120, 150, 160, 3550, 4230, 2750, 1300, 1595, 1680, 1770, 2110, 2230, 2340, 2930, 3050, 3210, 3360, 3510, 7000, 160, 12500, 20500, 4000};

constexpr uint32_t C_W = 0, C_M = 147456, C_KV = C_M + 18432, C_OS = C_KV + 24576, C_QM = C_KV + 32768, C_KM = C_QM + 2048,
                   C_VM = C_KM + 2048, C_OI = C_VM + 2048, C_SX = C_OI + 4096, C_KM2 = C_SX + 2560, C_VM2 = C_KM2 + 128,
                   C_KV2 = C_KM2 + 2048, C_Q = C_KV2 + 8192, C_BAR = C_Q + 8192;
constexpr uint32_t CB_FULL = C_BAR, CB_REF = C_BAR + 16, CB_SX = C_BAR + 32, CB_OX = C_BAR + 40, CB_XX = C_BAR + 48, CB_Q = C_BAR + 56, C_BAD = C_BAR + 64, W_BAR = C_BAR + 80, T_BAR = W_BAR + 24, S_GEN = C_BAR + 128, C_REF = C_BAR + 132, CB_VF = C_BAR + 144, CB_M = C_BAR + 160, CB_MV = C_BAR + 200;
constexpr uint32_t G_W = 0, G_RING = 147456, G_W2 = G_RING + 9 * 8192, G_BAR = G_W2 + 8192;
constexpr uint32_t O_W = 0, O_RING = 3 * 40960, O_ST = O_RING + 11 * 8192, O_BAR = O_ST + 16384, OB_ST = O_BAR + 64;
constexpr uint32_t F_A = 0, F_XY = 36864, F_L = F_XY + 36864, F_X = F_L + 18432, F_Y = F_L + 2 * 36864, F_BAR = C_BAR;
constexpr uint32_t SMEM_BYTES = C_BAR + 256;
static_assert(G_BAR + 256 <= SMEM_BYTES && O_BAR + 256 <= SMEM_BYTES && F_BAR + 16 <= SMEM_BYTES && SMEM_BYTES <= 232448, "smem map");
enum { B_INIT = 1, B_M, B_QK, B_S, B_V, B_O, B_X, B_WG0, B_WG1, B_WG2, B_G, B_OE, B_T, B_R };

__device__ __forceinline__ uint4 pack_partial(const float* d, uint32_t tag) {
  uint32_t x, z;
  asm("lop3.b32 %0, %2, 1, %4, 0xb8; lop3.b32 %1, %3, 1, %4, 0xb8;" : "=&r"(x), "=&r"(z) : "r"(pack2(d[0], d[1])), "r"(pack2(d[2], d[3])), "r"(tag));
  return make_uint4(x, pack2(d[4], d[5]), z, pack2(d[6], d[7]));
}
__device__ __forceinline__ void store_partial(uint4* p, const uint4& v) { st_b128(p, v.x, v.y, v.z, v.w); }
__device__ __forceinline__ void gather_reduce(const uint32_t* p, uint32_t* dst, uint32_t m0, bool shared, uint32_t tag, uint32_t lane, uint32_t sb, int n, int TS0) {
  int tries = 0;
  bool bad;
  TR(TS0);
  do {
    uint2 x[8];
#pragma unroll
    for (int i = 0; i < 8; i++)
      asm volatile("{.reg .b64 v; ld.relaxed.gpu.global.b64 v, [%2]; mov.b64 {%0, %1}, v;}" : "=r"(x[i].x), "=r"(x[i].y) : "l"(p + i * 128) : "memory");
    spin_guard(tries);
    float a = bf_lo(x[0].x), b = bf_hi(x[0].x), c = bf_lo(x[0].y), d = bf_hi(x[0].y);
    uint32_t t = x[0].x ^ tag;
#pragma unroll
    for (int i = 1; i < 8; i++) {
      a += bf_lo(x[i].x); b += bf_hi(x[i].x); c += bf_lo(x[i].y); d += bf_hi(x[i].y);
      asm("lop3.b32 %0, %0, %1, %2, 0xf6;" : "+r"(t) : "r"(x[i].x), "r"(tag));
    }
    bad = __any_sync(~0u, t & 1);
    const bool up = lane & 8;
    float u = (up ? c : a) + __shfl_xor_sync(~0u, up ? a : c, 8), v = (up ? d : b) + __shfl_xor_sync(~0u, up ? b : d, 8);
    if (shared) { u += __shfl_xor_sync(~0u, u, 4); v += __shfl_xor_sync(~0u, v, 4); }
    u += __shfl_xor_sync(~0u, u, 16);
    v += __shfl_xor_sync(~0u, v, 16);
    st_relaxed_if(dst, n < LAG && up ? m0 : pack2(u, v), !bad);
  } while (bad);
  TR(TS0 + 3); TRV(TS0 + 2, tries);
  CNT((TS0 - 16) >> 2, tries);
}

#define ATTR 80
#define SEPV 1
#define GRN 34
#define XRV 3
constexpr int XR = XRV;
__host__ __device__ constexpr int o_ks(int s) { return s & (s < 8 ? 3 : 7); }
#define OPAT 0x55555577u
__host__ __device__ constexpr bool o_reg(int s) { return (OPAT >> s) & 1; }
__host__ __device__ constexpr int o_slot(int s) { int k = 0; for (int i = 0; i < s; i++) k += o_reg(i) == o_reg(s); return k; }
__device__ __forceinline__ int g_unit(int wg) {
  const int i = bid() - N_CHAIN;
  return i < 32 ? wg * 64 + i : 2 * i - 32 + wg;
}
__device__ __forceinline__ uint32_t pinned(uint32_t v) { return __shfl_sync(~0u, v, threadIdx.x & 31); }
template <class T> __device__ __forceinline__ T* pinned(T* p) { return (T*)__shfl_sync(~0u, (unsigned long long)p, threadIdx.x & 31); }
enum { CHAIN, GROLE, OROLE };
template <int ROLE, bool SYNC> __device__ __forceinline__ void load_box(const Params& P, uint32_t sb, bool regs, int wg, int i, uint32_t mb, bool on) {
  const int b = bid();
  int map, col = 0, ks = 0, c2 = 0, c3 = 0;
  uint32_t dst = wg * 73728;
  if (ROLE == CHAIN) {
    const int k = i - 1, st = __fns(regs ? OPAT : ~OPAT, 0, i) & 31;
    dst += i ? (17 + i) * 2048 : 0;
    if (wg || i == 0) { map = wg + i; col = b * 64; c3 = !regs; }
    else if (!regs && k >= 14) { map = 6; ks = b * 4 + k - 14; }
    else { map = 6; col = 64 + (st < 8 ? (st >> 2) * 64 : (st >> 3) * 128 + (b & 1) * 64); ks = (b * 4) ^ o_ks(st); }
  } else if (ROLE == GROLE) {
    const int q = g_unit(wg);
    map = ((q >> 5) + 1) % 3;
    if (i) { map += 3; col = (q & 31) * 128 + (i - 1) * 64; ks = 34; dst = G_W2 + wg * 4096 + (i - 1) * 2048; }
    else { map += 8; c2 = (q & 31) * 2; c3 = !regs; }
  } else {
    const int o = b - N_CHAIN - N_G, ksl = o / 3;
    map = 7; col = ((o % 3) * 3 + (wg + ksl) % 3) * 64; dst = (wg * (regs ? 24 : 20) + i) * 2048;
    ks = (ksl * 11 - max(ksl - 4, 0)) * 4 + (regs ? i / 3 * 5 + i % 3 * 2 : i < 16 ? i / 2 * 5 + 1 + i % 2 * 2 : i + 24);
    c3 = (ks & 1) * 2; ks >>= 1;
  }
  if (SYNC) { col = pinned(col); ks = pinned(ks); bar_sync(B_WG0 + wg, 256); }
  if (on) asm volatile("cp.async.bulk.tensor.5d.shared::cluster.global.tile.mbarrier::complete_tx::bytes [%0], [%1, {%2, %3, %4, %5, %6}], [%7];"
               :: "r"(sb + dst), "l"(&P.map[map]), "r"(col), "r"(0), "r"(c2), "r"(c3), "r"(ks), "r"(mb) : "memory");
}
template <int ROLE, bool SYNC = false> __device__ __forceinline__ void load_wg(const Params& P, uint32_t sb, bool regs, int wg, int quarter) {
  const int i = (threadIdx.x & 31) * 4 + quarter;
  const int n = ROLE == CHAIN ? 36 : ROLE == GROLE ? (regs ? 38 : 36) : regs ? 24 : bid() < N_CHAIN + N_G + 12 ? 20 : 16;
  const bool split = SYNC && wg == 0;
  const uint32_t mb = split && i ? sb + T_BAR : sb + W_BAR + wg * 8;
  load_box<ROLE, SYNC>(P, sb, regs, wg, i, mb, i < (ROLE == CHAIN ? (wg ? 2 : 19) : ROLE == GROLE ? n - 35 : n));
  if (i <= split) mbar_expect(mb, n * (split ? 1024 : 2048));
  __syncwarp();
}
__device__ __forceinline__ uint32_t near_half(uint32_t blk, uint32_t reader) {
  return __ldcg(g_near + (blk >> 3)) ^ (~blk & 1) ^ __ldcg(g_side + (blk >> 3)) ^ __ldcg(g_side + reader);
}

__device__ __forceinline__ uint32_t opaque_tid() { uint32_t t; asm volatile("mov.u32 %0, %%tid.x;" : "=r"(t)); return t; }
__device__ __forceinline__ void m_fetch(uint32_t sb, uint32_t src, uint32_t b, uint32_t mb) {
  bulk_load(sb + C_M + (b ? b * 4096 - 2048 : 0), (const unsigned char*)g_mimg + ((src ^ ((b & 1) * 4096)) + b * 8192), b ? 4096 : 2048, mb);
}
__device__ __forceinline__ uint32_t m_probe(uint32_t lane) { return lane * 32 + (lane & 4) * 4 + (lane >> 3) * 4; }
__device__ __forceinline__ uint32_t m_max(uint32_t a, uint32_t b) {
  return max(max(lds32(a), lds32(a + 1024)), max(lds32(b), lds32(b + 1024)));
}
template <int S0, int N> __device__ __forceinline__ void o_steps(float* d, const uint32_t* a) {
  constexpr int SD = o_ks(S0) != 0;
  if constexpr (o_reg(S0)) wg_rs16<SD>(d, a + (18 + o_slot(S0)) * 4, desc_n16(C_OI + o_ks(S0) * 512));
  else wg_ss16<SD>(d, desc_sw128(C_W + (18 + o_slot(S0)) * 2048), desc_n16(C_OI + o_ks(S0) * 512));
  if constexpr (N > 1) o_steps<S0 + 1, N - 1>(d, a);
}
template <int BASE, int KS, int N> __device__ __forceinline__ void m_steps(float* d, const uint32_t* a, uint32_t oa) {
  wg_rs16<KS != 0>(d, a + (BASE + KS / 2) * 4, desc_m(C_M + KS * 512));
  if constexpr (KS >= 36 - 2 * XR) wg_rs16<1>(d, a + (18 + XR + KS / 2) * 4, desc_m(C_M + KS * 512 + 512));
  else wg_ss16o<1, desc_sw128(C_W + (BASE + KS / 2) * 2048), desc_m(C_M + KS * 512 + 512)>(d, oa, 0);
  if constexpr (N > 2) m_steps<BASE, KS + 2, N - 2>(d, a, oa);
}

constexpr uint32_t VPAT = 0x15bbd249u;
template <int I, int R, int S> __device__ __forceinline__ void v_steps(float* d, const uint32_t* a) {
  constexpr bool reg = (VPAT >> I) & 1;
  if constexpr (reg) wg_rs16<1>(d, a + (18 + R) * 4, desc_m(C_M + R * 1024));
  else wg_ss16<1>(d, desc_sw128(C_W + (54 + S) * 2048), desc_m(C_M + S * 1024 + 512));
  if constexpr (I < 31) v_steps<I + 1, R + reg, S + !reg>(d, a);
  else static_assert(R + reg == 18, "pattern");
}

__device__ __forceinline__ void chain_proj(const Params& P, uint32_t sb) {
  const uint32_t c = chain_id(), h = c >> 1, j = c & 1, wid = __shfl_sync(~0u, threadIdx.x >> 5, 0), wg = wid >> 2, w = wid & 3;
  const uint32_t t = threadIdx.x & 127, lane = pinned(t & 31), mine = pinned(sb + t * 16), rb = mapa(sb, j ^ 1);
  const uint32_t theirs = pinned(rb + C_KM2 + w * 512 + lane * 4), oa = wg * 4608;
  uint32_t a[144 + 4 * XR];
  mbar_wait(sb + W_BAR + wg * 8, 0);
  if (threadIdx.x == 0) TS(23);
  load_frags<36>(a, sb + C_W + wg * 73728);
  fence_async_smem();
  bar_arrive(B_WG0 + wg, 256);
  if (threadIdx.x == 0) TS(24);
  bar_sync(B_WG2, 384);
  const uint32_t round = min(w, 2u) + (wg ? 0 : 3), gdly = P.dly[8 + round], ps = t >> 2, pf = j * 16 + (ps >> 1);
  uint4* const dsts = pinned(g_xb + (ps * 4096 + near_half(ps * 8, ps * 2) * 256 + c * 4 + (t & 3)));
  uint4* const dstf = pinned(g_xb + (pf * 4096 + 512 + near_half(pf * 8 + 1, pf * 2) * 256 + h * 8 + (t & 7)));
  const uint32_t* const gsrc = (const uint32_t*)g_xb + (h * 16384 + min(w, 2u) * 4096 + near_half(h * 8 + !wg, h * 2) * 1024 +
                               (wg ? lane * 4 + j * 2 : 2048 + (lane & 24) * 4 + j * 16 + (lane & 7) * 2));
  uint32_t* gdst = g_mimg + (16384 + (lane >> 4) * 1024 +
                   (wg ? (round ? 1536 + round * 512 : 0) + c * 8 + (((lane >> 1) ^ c) & 4) + (lane & 3)
                       : (round - 1) * 2048 + c * 16 + (lane & 1) * 8 + (((lane >> 1) ^ (c * 2)) & 4) + ((lane >> 1) & 3)));
  const uint32_t m0 = __ldcg(gdst - 16384);
  mbar_wait(sb + W_BAR + wg * 8, 1);
  load_frags<XR>(a + 144, sb + C_W + wg * 73728 + (18 - XR) * 2048);
  bar_sync(B_INIT, 256);
  if ((threadIdx.x & 127) == 0) TS(4);

  uint32_t ring = 1;
#pragma unroll 1
  for (int n = 0; n < STEPS; n++) {
    float d[8], e[8];
    if (n + 1 == STEPS && !wg) { bar_arrive(B_QK, 416); break; }
#pragma unroll
    for (int i = 0; i < 8; i++) e[i] = 0.f;
    uint32_t redo = n + 1;
#pragma unroll 1
    do {
      mbar_wait(sb + CB_M, n & 1);
      wg_fence();
      m_steps<0, 0, 4>(d, a, oa);
      wg_commit();
      if (wg) { wg_fence(); m_steps<18, 0, 4>(e, a, 4608); wg_commit(); }
      if (wid == 0) TR(8);
      mbar_wait(sb + CB_M + 8, n & 1);
      wg_fence();
      m_steps<0, 4, 8>(d, a, oa);
      wg_commit();
      mbar_wait(sb + CB_MV, n & 1);
      asm volatile("{.reg .pred p; .reg .u32 t; ld.shared.u32 t, [%1]; setp.eq.u32 p, t, %0; selp.u32 %0, -1, 0, p;}" : "+r"(redo) : "r"(sb + C_BAD) : "memory");
    } while (redo);
    if (SEPV) mbar_wait(sb + CB_MV + 8, n & 1);
    wg_fence();
    m_steps<0, 12, 8>(d, a, oa);
    wg_commit();
    mbar_wait(sb + CB_MV + 16, n & 1);
    wg_fence();
    m_steps<0, 20, 8>(d, a, oa);
    wg_commit();
    mbar_wait(sb + CB_MV + 24, n & 1);
    wg_fence();
    m_steps<0, 28, 8>(d, a, oa);
    wg_commit();
    wg_wait<0>();
    if (w == 0) TR(6 + wg);
    const uint32_t f0 = pack2(d[0], d[1]), f1 = pack2(d[4], d[5]), f2 = pack2(d[2], d[3]), f3 = pack2(d[6], d[7]);
    stsm4(mine + C_QM + wg * 2048, f0, f1, f2, f3);
    bar_arrive(B_QK, 416);
    const uint32_t tag = (n & 1) ^ 1;
    if (n == 0) mbar_wait(sb + T_BAR, 0);
    if (wg) {
      if (n + 1 < STEPS) bar_sync(B_S, 256);
      wg_fence();
      v_steps<0, 2, 2>(e, a);
      wg_commit();
      const uint32_t k0 = j ? f0 : f1, k1 = j ? f2 : f3;
      mbar_wait(sb + CB_SX, n & 1);
      wg_wait<0>();
      if (w == 0) TR(11);
      const uint32_t v0 = pack2(e[0], e[1]), v1 = pack2(e[4], e[5]), v2 = pack2(e[2], e[3]), v3 = pack2(e[6], e[7]);
      stsm4(mine + C_VM, v0, v1, v2, v3);
      bar_arrive(B_V, 256);
      st_async1(theirs, k0, rb + CB_XX);
      st_async1(theirs + 256, k1, rb + CB_XX);
      st_async1(theirs + 128, j ? v0 : v1, rb + CB_XX);
      st_async1(theirs + 384, j ? v2 : v3, rb + CB_XX);
      if (n + 1 == STEPS) break;
      bar_sync(B_O, 256);
      fence_async_smem();
      wg_fence();
#pragma unroll
      for (int ks = 0; ks < 4; ks++) {
        if (ks == 0) wg_ss16<0>(d, desc_sw128(C_W + 32 * 2048), desc_n16(C_OI));
        else wg_ss16<1>(d, desc_sw128(C_W + (32 + ks) * 2048), desc_n16(C_OI + ks * 512));
      }
      wg_commit();
      bar_arrive(B_X, 256);
      if (w == 0) TR(0);
      wg_wait<0>();
      store_partial(dsts, pack_partial(d, tag));
      bar_arrive(B_M, 160);
      if (w == 0) TR(1);
    } else {
      bar_sync(B_X, 256);
      wg_fence();
      o_steps<0, 4>(d, a);
      wg_commit();
      o_steps<4, 4>(e, a);
      wg_commit();
      wg_wait<1>();
      store_partial(dsts + 1024, pack_partial(d, tag));
      if (w == 0) TR(2);
      wg_wait<0>();
      store_partial(dsts + 2048, pack_partial(e, tag));
      if (w == 0) TR(3);
      wg_fence();
      o_steps<8, 4>(d, a);
      wg_commit();
      bar_sync(B_T, 256);
      if (w == 0) { TRV(61, 0); TR(12); }
      wg_fence();
      o_steps<12, 4>(d, a);
      wg_commit();
      o_steps<16, 8>(e, a);
      wg_commit();
      wg_wait<1>();
      store_partial(dstf, pack_partial(d, tag));
      if (w == 0) TR(4);
      wg_fence();
      o_steps<24, 8>(d, a);
      wg_commit();
      wg_wait<1>();
      store_partial(dstf + 1024, pack_partial(e, tag));
      bar_arrive(B_OE, 256);
      if (w == 0) TR(5);
      wg_wait<0>();
      store_partial(dstf + 2048, pack_partial(d, tag));
      if (w == 0) TR(15);
    }
    if (w < 3) {
      mbar_wait(sb + CB_REF, n & 1);
      wait_until(lds32(sb + C_REF), gdly);
      gather_reduce(gsrc, gdst, m0, wg, tag, lane, sb, n, 16 + round * 4);
      if (++ring == MRING) { ring = 0; gdst -= MRING * 16384; }
      gdst += 16384;
    }
  }
}

template <int KS> __device__ __forceinline__ void x_scores(float* s, float* sm, const uint4* q, uint32_t ok, uint32_t om) {
  wg_rs32o<1, desc_sw64(C_KV + KS * 1024)>(s, q[KS].x, q[KS].y, q[KS].z, q[KS].w, ok);
  wg_rs8o<1, desc_n16(C_KM + KS * 512)>(sm, q[KS].x, q[KS].y, q[KS].z, q[KS].w, om);
  if constexpr (KS < 3) x_scores<KS + 1>(s, sm, q, ok, om);
}

__device__ __forceinline__ void chain_attn(const Params& P, uint32_t sb) {
  const int c = chain_id(), j = c & 1;
  const int tid = threadIdx.x, lane = tid & 31, w = __shfl_sync(~0u, (tid >> 5) & 3, 0);
  const int l = w >> 1, u = w & 1;
  const uint32_t rb = mapa(sb, j ^ 1);
  const float sc = 0.08838834764831845f * 1.4426950408889634f;
  const uint32_t ones = 0x3F803F80u, sx = C_SX + l * 1280;
  const uint32_t km_off = C_KM + (lane >> 3) * 256 + l * 128 + (lane & 7) * 16;
  const uint32_t qm_off = C_QM + (lane >> 4) * 256 + l * 128 + (lane & 7) * 16;
  const uint32_t kv_off = C_KV + l * 4096 + (lane & 15) * 64 + (((lane >> 4) ^ (u * 2) ^ ((lane >> 1) & 3)) << 4);

  load_wg<CHAIN, true>(P, sb, false, 1, w);
  if (lane == 0) mbar_arrive(sb + CB_M);
#pragma unroll 1
  for (int n = 0; n < STEPS; n++) {
    const uint32_t kvb = sb + kv_off + (n & 1) * 16384;
    mbar_wait(sb + CB_FULL + (n & 1) * 8, (n >> 1) & 1);
    if (n < 3 && tid == 256) TS(n ? 20 + n : 5);
    __syncwarp();
    {
      uint32_t km[8];
      uint4 kx[8];
#pragma unroll
      for (int i = 0; i < 8; i++) ldsm4t(kx[i].x, kx[i].y, kx[i].z, kx[i].w, (kvb ^ ((i & 1) * 32)) + (i >> 1) * 1024);
      mbar_wait(sb + CB_VF, n & 1);
      if (w == 1) TRD(60, kx[7].x);
      bar_sync(B_QK, 416);
      if (n + 1 == STEPS) {
        st_async4(rb + sx + u * 512 + lane * 16, 0.f, 0.f, 0.f, 0.f, rb + CB_SX);
        st_async1(rb + sx + 1024 + u * 128 + lane * 4, 0, rb + CB_SX);
        bar_sync(B_V, 256);
      } else {
      uint32_t qm[16];
#pragma unroll
      for (int ks = 0; ks < 4; ks++) ldsm4t(qm[4 * ks], qm[4 * ks + 1], qm[4 * ks + 2], qm[4 * ks + 3], sb + qm_off + ks * 512);
      ldsm4t(km[0], km[1], km[2], km[3], sb + km_off);
      ldsm4t(km[4], km[5], km[6], km[7], sb + km_off + 1024);
      float s[5][4];
      uint4 vx[4];
#pragma unroll
      for (int i = 0; i < 5; i++) { s[i][0] = s[i][1] = s[i][2] = s[i][3] = 0.f; }
#pragma unroll
      for (int ks = 0; ks < 4; ks++) {
        const uint32_t* q = qm + 4 * ks;
        if (ks == 1 || ks == 2) {
#pragma unroll
          for (int i = 2 * ks - 2; i < 2 * ks; i++) ldsm4(vx[i].x, vx[i].y, vx[i].z, vx[i].w, ((sb + kv_off) ^ ((i & 1) * 32)) + 8192 + (2 * u + (i >> 1)) * 1024);
        }
        mma16(s[1], q[0], q[1], q[2], q[3], kx[2 * ks].x, kx[2 * ks].y);
        mma16(s[2], q[0], q[1], q[2], q[3], kx[2 * ks].z, kx[2 * ks].w);
        mma16(s[0], q[0], q[1], q[2], q[3], km[2 * ks], km[2 * ks + 1]);
        mma16(s[3], q[0], q[1], q[2], q[3], kx[2 * ks + 1].x, kx[2 * ks + 1].y);
        mma16(s[4], q[0], q[1], q[2], q[3], kx[2 * ks + 1].z, kx[2 * ks + 1].w);
      }
      st_async4(rb + sx + u * 512 + lane * 16, s[1][0], s[1][1], s[2][0], s[2][1], rb + CB_SX);
      st_async1(rb + sx + 1024 + u * 128 + lane * 4, __float_as_uint(u ? s[0][1] : s[0][0]), rb + CB_SX);
      bar_arrive_after<B_S, 256>(__float_as_uint(s[3][0]), __float_as_uint(s[4][0]));
      mbar_wait(sb + CB_SX, n & 1);
      const uint4 p0 = lds128(sb + sx + u * 512 + lane * 16), p1 = lds128(sb + sx + (u ^ 1) * 512 + lane * 16);
      const uint2 p2 = make_uint2(lds32(sb + sx + 1024 + lane * 4), lds32(sb + sx + 1152 + lane * 4));
      float t[10] = {s[0][0] + __uint_as_float(p2.x), s[0][1] + __uint_as_float(p2.y),
                     s[1][0] + __uint_as_float(p0.x), s[1][1] + __uint_as_float(p0.y),
                     s[2][0] + __uint_as_float(p0.z), s[2][1] + __uint_as_float(p0.w),
                     s[3][0] + __uint_as_float(p1.x), s[3][1] + __uint_as_float(p1.y),
                     s[4][0] + __uint_as_float(p1.z), s[4][1] + __uint_as_float(p1.w)};
      float mx = fmaxf(fmaxf(fmaxf(fmaxf(t[2], t[3]), fmaxf(t[4], t[5])), fmaxf(fmaxf(t[6], t[7]), fmaxf(t[8], t[9]))), fmaxf(t[0], t[1]));
      mx = fmaxf(fmaxf(mx, __shfl_xor_sync(~0u, mx, 1)), fmaxf(__shfl_xor_sync(~0u, mx, 2), __shfl_xor_sync(~0u, mx, 3)));
      const float ms = -mx * sc;
#pragma unroll
      for (int i = 0; i < 10; i++) t[i] = ex2(fmaf(t[i], sc, ms));
      uint32_t p[5];
#pragma unroll
      for (int i = 0; i < 5; i++) p[i] = pack2(t[2 * i], t[2 * i + 1]);
      p[1] |= (p[0] & p[3] & p[4]) & 0x80008000u;
      float o[2][4], z[4] = {0.f, 0.f, 0.f, 0.f};
      mma16(z, ones, ones, ones, ones, p[1], p[2]);
#pragma unroll
      for (int i = 0; i < 2; i++) {
        o[i][0] = o[i][1] = o[i][2] = o[i][3] = 0.f;
        mma16(o[i], vx[2 * i].x, vx[2 * i].y, vx[2 * i].z, vx[2 * i].w, p[1], p[2]);
      }
      mma16(z, ones, ones, ones, ones, p[3], p[4]);
#pragma unroll
      for (int i = 0; i < 2; i++) mma16(o[i], vx[2 * i + 1].x, vx[2 * i + 1].y, vx[2 * i + 1].z, vx[2 * i + 1].w, p[3], p[4]);
      mma8(z, ones, ones, p[0]);
      bar_sync_after<B_V, 256>(p[1]);
      ldsm4(km[0], km[1], km[2], km[3], sb + km_off + (C_VM - C_KM) + u * 1024);
      mma8(o[0], km[0], km[1], p[0]);
      mma8(o[1], km[2], km[3], p[0]);
      const float i0 = rcp(z[0]), i1 = rcp(z[1]);
      const uint32_t oo = C_OI + u * 1024 + l * 128 + lane * 4;
      uint32_t ow[4];
#pragma unroll
      for (int i = 0; i < 2; i++) { ow[2 * i] = pack2(o[i][0] * i0, o[i][1] * i1); ow[2 * i + 1] = pack2(o[i][2] * i0, o[i][3] * i1); }
      stsm4(sb + C_OI + u * 1024 + l * 128 + (lane >> 3) * 256 + (lane & 7) * 16, ow[0], ow[1], ow[2], ow[3]);
      bar_arrive(B_O, 256);
#pragma unroll
      for (int i = 0; i < 4; i++) st_async1(rb + oo + 2048 + i * 256, ow[i], rb + CB_OX);
      }
    }
    {
      const uint32_t lane = opaque_tid() & 31, own = ((n & 1) * 16384 + j * 4096) >> 4;
      float s[16], sm[4];
#pragma unroll
      for (int i = 0; i < 16; i++) s[i] = sm[i & 3] = 0.f;
      {
        uint4 q[4];
        mbar_wait(sb + CB_Q, n & 1);
#pragma unroll
        for (int ks = 0; ks < 4; ks++)
          ldsm4t(q[ks].x, q[ks].y, q[ks].z, q[ks].w, sb + C_Q + (lane & 8) * 512 + ks * 1024 + (lane & 16) * 32 + (lane & 7) * 64 + (((w ^ (lane >> 1)) & 3) << 4));
        mbar_wait(sb + CB_XX, n & 1);
        if (n + 1 < STEPS) mbar_wait(sb + CB_OX, n & 1);
        fence_async_smem();
        if (n + 1 < STEPS) { bar_arrive(B_T, 256); bar_sync(B_OE, 256); }
        if (w == 1) { TRV(61, 0); TR(9); }
#pragma unroll 1
        for (uint32_t hf = 0; hf < 2; hf++) {
          wg_fence();
          x_scores<0>(s, sm, q, hf ? (C_KV2 - C_KV) >> 4 : own, hf ? (C_KM2 - C_KM) >> 4 : j * 8);
          wg_commit();
          wg_wait<0>();
#pragma unroll
          for (int ks = 0; ks < 4; ks++) asm volatile("mov.b32 %0, %1; mov.b32 %2, %3;" : "+r"(q[ks].x), "+r"(q[ks].y), "+r"(q[ks].z), "+r"(q[ks].w));
        }
      }
      const float neg = -1e9f * 11.313708498984761f;
      const int tok = (lane & 24) + 2 * w + ((lane >> 2) & 1), lim = tok - 8 * (int)(lane & 3);
      float t[10] = {sm[0], sm[1]};
#pragma unroll
      for (int i = 0; i < 8; i++) t[2 + i] = i > lim ? neg : s[(i >> 1) * 4 + (i & 1)];
      float mx = fmaxf(fmaxf(fmaxf(fmaxf(t[2], t[3]), fmaxf(t[4], t[5])), fmaxf(fmaxf(t[6], t[7]), fmaxf(t[8], t[9]))), fmaxf(t[0], t[1]));
      mx = fmaxf(fmaxf(mx, __shfl_xor_sync(~0u, mx, 1)), fmaxf(__shfl_xor_sync(~0u, mx, 2), __shfl_xor_sync(~0u, mx, 3)));
      const float ms = -mx * sc;
#pragma unroll
      for (int i = 0; i < 10; i++) t[i] = ex2(fmaf(t[i], sc, ms));
      uint32_t p[5];
#pragma unroll
      for (int i = 0; i < 5; i++) p[i] = pack2(t[2 * i], t[2 * i + 1]);
      float z = ((t[0] + t[1]) + (t[2] + t[3])) + ((t[4] + t[5]) + (t[6] + t[7])) + (t[8] + t[9]);
      const uint32_t row = sb + C_OS + tok * 128 + (((lane & 3) ^ (tok & 7)) << 4);
#pragma unroll 1
      for (uint32_t hf = 0; hf < 2; hf++) {
        float o[32];
        const uint32_t vo = hf ? (C_KV2 + 4096 - C_KV - 8192) >> 4 : j * 256;
        wg_fence();
        wg_rs64o<0, desc_sw64(C_KV + 8192)>(o, p[1], p[1], p[2], p[2], vo);
        wg_rs64o<1, desc_sw64(C_KV + 8192 + 32)>(o, p[3], p[3], p[4], p[4], vo);
        wg_rs64o<1, mkdesc(C_VM, 128, 256, 0)>(o, p[0], p[0], 0, 0, hf ? (C_VM2 - C_VM) >> 4 : j * 8);
        wg_commit();
        if (hf) {
          if (elect()) mbar_arrive(sb + CB_M);
        } else {
          z = rcp((z + __shfl_xor_sync(~0u, z, 1)) + (__shfl_xor_sync(~0u, z, 2) + __shfl_xor_sync(~0u, z, 3)));
        }
        wg_wait<0>();
#pragma unroll
        for (int qq = 0; qq < 2; qq++) {
          const float* r = o + 16 * qq;
          sts128((row ^ (qq * 64)) + hf * 4096,
                 make_uint4(pack2(r[0] * z, r[1] * z), pack2(r[4] * z, r[5] * z), pack2(r[8] * z, r[9] * z), pack2(r[12] * z, r[13] * z)));
        }
      }
      bar_arrive(B_G, 160);
      if (n + 1 < STEPS) bar_arrive(B_R, 160);
      if (w == 1) TR(10);
    }
  }
  if ((threadIdx.x & 127) == 0) TS(6);
}

__device__ __forceinline__ void chain_aux(const Params& P, uint32_t sb) {
  const uint32_t c = chain_id(), j = c & 1, lane = threadIdx.x & 31, w = __shfl_sync(~0u, (threadIdx.x >> 5) & 3, 0);
  load_wg<CHAIN, true>(P, sb, false, 0, w);
  if (threadIdx.x == 384) TS(25);
  if (threadIdx.x == 384) grid_wait(1, lds32(sb + S_GEN));
  bar_sync(B_WG2, 384);
  if (threadIdx.x == 384) TS(13);
  if (w == 0) {
    const uint32_t* fg = g_fl + FL_G + near_half(XB_F, c) * 1024 + (c >> 1) * 8;
#pragma unroll 1
    for (int n = 0; n < STEPS; n++) {
      const unsigned char* blk = g_qkv + (uint32_t)((n % QRING) * (N_CHAIN * 24576));
      const uint32_t t1 = clk(), kb = sb + CB_FULL + (n & 1) * 8, kv = sb + C_KV + (n & 1) * 16384;
      uint32_t t0 = t1 - 100000, x = 0;
      if (n > 0) {
        wait_until(t1, KMIN);
        do asm volatile("ld.relaxed.gpu.global.u32 %0, [%1];" : "=r"(x) : "l"(fg) : "memory"); while (x <= n && clk() - t1 < KWIN);
        if (x > n) {
          asm volatile("fence.acquire.gpu;" ::: "memory");
          fence_async_global();
          if (elect()) { mbar_expect(kb, 8192); bulk_load(kv, blk + c * 24576, 8192, kb); }
        }
        T3(0); CNT(12, 1 + (x <= n));
        mbar_wait(sb + CB_REF, (n - 1) & 1);
        t0 = lds32(sb + C_REF);
        wait_until(t0, DLYK - 500);
      }
      wait_flags(fg + min(lane, 2u) * 256, n + 1);
      T3(2);
      fence_async_global();
      if (n > 0) bar_sync(B_R, 160);
      if (lane < 3) mbar_expect(sb + CB_SX + lane * 8, lane ? 2048 : 2560);
      __syncwarp();
      wait_until(t0, DLYK);
      if (elect()) {
        if (x <= n) { mbar_expect(kb, 8192); bulk_load(kv, blk + c * 24576, 8192, kb); }
        mbar_expect(sb + CB_VF, 8192);
        bulk_load(sb + C_KV + 8192, blk + (c * 24576 + 8192), 8192, sb + CB_VF);
        mbar_expect(sb + CB_Q, 16384);
        bulk_load(sb + C_Q, blk + (c * 24576 + 16384), 8192, sb + CB_Q);
        bulk_load(sb + C_KV2, blk + ((c ^ 1) * 24576 + j * 4096), 4096, sb + CB_Q);
        bulk_load(sb + C_KV2 + 4096, blk + ((c ^ 1) * 24576 + 8192 + j * 4096), 4096, sb + CB_Q);
      }
      T3(1);
      T3(3);
    }
  } else {
    const uint32_t near = __ballot_sync(~0u, near_half(XB_M + min(lane, MRING - 1u) * 8, c));
    uint32_t ring = 0;
    if (w > 1) {
      const uint32_t odd = w & 1, chk = pinned(sb + C_M + odd * 2048 + m_probe(lane)), again = sb + CB_MV + 32 + odd * 8;
      const bool one = elect();
      uint32_t mph = 0;
#pragma unroll 1
      for (int n = 0; n <= STEPS; n++) {
#pragma unroll
        for (int k = 0; k < 3; k++) {
          if (n == STEPS || (k == 2 && odd)) break;
          const uint32_t b = 2 * k + odd, at = chk + (k ? k * 8192 - 2048 + odd * 2048 : 0);
          uint32_t mb = sb + CB_M + b * 8, ph = n & 1;
          int it = 1;
          while (true) {
            mbar_wait(mb, ph);
            const bool bad = __any_sync(~0u, m_max(at, b ? at + 2048 : at) == SENT);
            if (one && !bad) mbar_arrive(sb + CB_MV + (b > 2 - SEPV ? b * 8 - 8 : 0));
            if (!bad) break;
            mb = again; ph = mph; mph ^= 1;
            if (one) {
              if (k == 0) sts32(sb + C_BAD, n + 1);
              mbar_expect(mb, b ? 4096 : 2048);
              m_fetch(sb, ring * 65536 + ((near >> ring) & 1) * 4096, b, mb);
            }
            __syncwarp();
            spin_guard(it);
          }
          TR(41 + b * 4); CNT(6 + b, it);
        }
        ring = ring + 1 == MRING ? 0 : ring + 1;
        if (!odd) {
          if (n < STEPS) { TRSYNC(); TRDUMP(n - 2); }
        } else {
          unsigned char* o = g_oimg + (uint32_t)(((n - 1) & (RING - 1)) * (N_CHAIN * 8192) + j * 4096);
          if (n > 0) bar_sync(B_G, 160);
          fence_async_smem();
          if (one) {
            if (n > 0) {
              bulk_store(o + c * 8192, sb + C_OS, 4096);
              bulk_store(o + (c ^ 1) * 8192, sb + C_OS + 4096, 4096);
              asm volatile("cp.async.bulk.commit_group;\ncp.async.bulk.wait_group.read 0;" ::: "memory");
              { const int n_ = n - 1; { const int n = n_; T3(4); (void)n; } }
            }
            mbar_arrive(sb + CB_Q);
            if (n > 0) {
              bulk_done_inc(g_fl + FL_O + c);
              { const int n_ = n - 1; { const int n = n_; T3(5); (void)n; } }
            }
          }
          __syncwarp();
        }
      }
    } else {
      const uint32_t* ts = g_fl + FL_SYNC + near_half(XB_F + 1, c) * 1024 + lane * 2;
      uint32_t t0 = clk() - 100000, last = 0;
      int lag = 0;
#pragma unroll 1
      for (int n = 0; n < STEPS; n++) {
        const uint32_t src = ring * 65536 + ((near >> ring) & 1) * 4096;
        if (lane < 5) mbar_expect(sb + CB_M + lane * 8, lane ? 4096 : 2048);
        __syncwarp();
        if (elect()) {
#pragma unroll
          for (int b = 0; b < 5; b++) {
            wait_until(t0, P.dly[14 + b]);
            m_fetch(sb, src, b, sb + CB_M + b * 8);
            TR(40 + b * 4);
          }
        }
        __syncwarp();
        ring = ring + 1 == MRING ? 0 : ring + 1;
        uint32_t va, vb;
        const uint32_t off = timer_offset(), tag = (uint32_t)(n + 1) << 28;
        if (n > 1) lag += (int)(off - last) - (lag >> 2);
        last = off;
        const uint32_t mine = min(max((lag >> 3) + 256, 0), 511);
        bar_sync(B_QK, 416);
        if (n + 1 == STEPS) break;
        sts32(sb + C_REF + 4, 0);
        const uint32_t c0 = clk(), stamp = c0 + off;
        st_relaxed_if(g_fl + FL_SYNC + lane * 1024 + c, tag | (mine << 19) | (stamp & 0x7FFFF), lane < 2);
        TR(13);
        wait_until(c0, DLYS);
        int it = 0;
        do {
          asm volatile("ld.relaxed.gpu.global.v2.u32 {%0,%1}, [%2];" : "=r"(va), "=r"(vb) : "l"(ts) : "memory");
          spin_guard(it);
        } while (__any_sync(~0u, ((va ^ tag) | (vb ^ tag)) >> 28));
        const int late = __reduce_max_sync(~0u, max((int)((va - stamp) << 13), (int)((vb - stamp) << 13))) >> 13;
        const uint32_t fast = min(((__reduce_max_sync(~0u, max(va, vb)) >> 19) & 511) - mine, 100u);
        t0 = c0 + min((uint32_t)late, clk() - c0);
        if (elect()) {
          sts32(sb + C_REF, t0 + (fast * 3 >> 2));
          mbar_arrive(sb + CB_REF);
        }
        st_relaxed_if(g_fl + FL_TICK + lane * 1024, (uint32_t)(n + 1) << 24 | ((t0 + off) & 0xFFFFFF), c == 0 && lane < 2);
        t0 += fast * 5 >> 2;
        TRV(59, fast);
        TR(14); CNT(11, it);
        bar_sync(B_M, 160);
      }
    }
  }
}

template <int WG>
__device__ __forceinline__ void g_math(const Params& P, uint32_t sb) {
  const int q = g_unit(WG);
  const int lane = threadIdx.x & 31, w = (threadIdx.x >> 5) & 3;
  uint32_t a[GRN * 4];
  {
    const uint32_t stage = sb + G_W + WG * 73728;
    mbar_wait(sb + W_BAR + WG * 8, 0);
    if (threadIdx.x == 0) TS(23);
    load_frags<GRN>(a, stage);
    fence_async_smem();
    bar_sync(B_WG0 + WG, 128);
    if (threadIdx.x == 0) TS(24);
    load_wg<GROLE>(P, sb, false, WG, w);
    if (threadIdx.x == 0) TS(25);
    mbar_wait(sb + W_BAR + WG * 8, 1);
  }
  if ((threadIdx.x & 127) == 0) TS(4);
  const uint32_t off0 = (q & 31) * 49152 + (q >> 5) * 8192 + w * 1024 + (lane >> 2) * 64 + (((lane ^ (lane >> 3)) & 3) << 4);
  const uint32_t isq = q >> 6;
#pragma unroll 1
  for (int n = 0; n < STEPS; n++) {
    float d0[32], d1[32];
    if (WG == 0 && n >= LOCK0) bar_sync(B_OE, 160);
    if (n > 0) bar_sync(B_V + WG, 256);
#pragma unroll
    for (int ch = 0; ch < 9; ch++) {
      mbar_wait(sb + G_BAR + ch * 8, n & 1);
      if (ch == 0) { if ((threadIdx.x & 127) == 0) T3(5 + WG * 3); __syncwarp(); }
      if (ch == 4) { if ((threadIdx.x & 127) == 0) T3(6 + WG * 3); __syncwarp(); }
      if (ch == 8 && (WG == 0 ? n > 0 : n + 1 < STEPS)) bar_arrive(B_V + (WG ^ 1), 256);
      wg_fence();
#pragma unroll
      for (int kk = 0; kk < 4; kk++) {
        const int i = ch * 4 + kk;
        float* d = i & 1 ? d1 : d0;
        const uint64_t db = desc_sw128(G_RING + ch * 8192 + (kk & 2) * 32);
        if (i < 2) wg_rs64<0>(d, a + i * 4, db);
        else if (i < GRN) wg_rs64<1>(d, a + i * 4, db);
        else wg_ss64<1>(d, desc_sw128(G_W2 + WG * 4096 + (i - 34) * 2048), db);
        wg_ss64<1>(d, desc_sw128(G_W + WG * 73728 + i * 2048), db + 2);
      }
      wg_commit();
      if (ch > 0) { wg_wait<1>(); if (lane == 0) mbar_arrive(sb + G_BAR + 128 + (ch - 1) * 8); }
    }
    wg_wait<0>();
    if (lane == 0) mbar_arrive(sb + G_BAR + 128 + 8 * 8);
    if ((threadIdx.x & 127) == 0) T3(7 + WG * 3);
    __syncwarp();
    uint32_t tw = clk() + (n == 0 ? 0u - 100000u : WG ? 0u : DLYW);
    unsigned char* base = g_qkv + (size_t)(n & (QRING - 1)) * (N_CHAIN * 24576);
#pragma unroll
    for (int i = 0; i < 8; i++) {
      const float* d = (i < 4 ? d0 : d1) + 8 * (i & 2) + 2 * (i & 1);
      wait_until(tw, 0); tw += P.dly[2 + WG];
      *(uint4*)(base + (off0 + (i < 2 ? 0 : i < 4 ? 4096 + isq * 24576 : i < 6 ? 24576 - isq * 20480 : 28672 - isq * 4096)) + (i & 1) * 512) =
        make_uint4(pack2(d[0], d[1]), pack2(d[4], d[5]), pack2(d[8], d[9]), pack2(d[12], d[13]));
    }
    bar_sync(B_M + WG, 160);
  }
}

__device__ __forceinline__ void fill16(void* p, uint32_t v) {
  asm volatile("st.global.v4.u32 [%0], {%1,%1,%1,%1};" :: "l"(p), "r"(v) : "memory");
}
__device__ __forceinline__ void g_load(const Params& P, uint32_t sb) {
  const int lane = threadIdx.x & 31, w = __shfl_sync(~0u, (threadIdx.x >> 5) & 3, 0);
  if (w == 2) return;
  if (w < 2) { bar_sync(15, 192); fence_async_smem(); }
  uint32_t fl = 0;
#pragma unroll 1
  for (int n = w == 3 ? LOCK0 : 0; n < STEPS; n++) {
    if (w && n == LOCK0) { grid_wait(1, lds32(sb + S_GEN)); fl = near_half(XB_F, bid()) * 1024; }
    if (w == 3) {
      const uint32_t tag = (uint32_t)(n - LOCK0 + 1) << 24;
      uint32_t v; int it = 0;
      do { asm volatile("ld.relaxed.gpu.global.u32 %0, [%1];" : "=r"(v) : "l"(g_fl + fl + FL_TICK) : "memory"); spin_guard(it); } while (v < tag);
      const uint32_t off = timer_offset(), now = clk(), t0 = now - ((v ^ tag) >> 24 ? DLYG : (now + off - v) & 0xFFFFFF);
      asm volatile("fence.acquire.gpu;" ::: "memory");
      if (lane == 0) T3(11);
      __syncwarp();
      wait_until(t0, DLYG);
      if (lane == 0) T3(4);
      bar_sync(B_OE, 160);
      continue;
    }
    if (w == 0 || n == 0) {
      if (n < NSEG) wait_flags(g_lnflag + n * 16 + (lane & 1) * 8, 1);
    } else if (n >= LAG) {
      wait_flags(g_fl + fl + FL_F + (lane & 1) * 8, n - LAG + 1);
    }
    if (w) { if (lane == 0) T3(12); bar_sync(B_X, 96); }
    fence_async_global();
    const unsigned char* src = g_lnimg + (uint32_t)((w ? (n >= LAG ? NSEG + n - LAG : 0) : min(n, NSEG - 1)) * 36864);
#pragma unroll 1
    for (int ch = 0; ch < 9; ch++) {
      const uint32_t full = sb + G_BAR + ch * 8;
      mbar_wait(full + 128, (n & 1) ^ 1);
      if (elect()) {
        mbar_expect(full, 4096);
        bulk_load(sb + G_RING + ch * 8192 + w * 4096, src + ch * 4096, 4096, full);
      }
    }
  }
}

__device__ __forceinline__ void g_aux(const Params& P, uint32_t sb) {
  const int lane = threadIdx.x & 31, w = (threadIdx.x >> 5) & 3;
  if (w == 1 || w == 2) {
    const int q = g_unit(w - 1);
    uint32_t* f = g_fl + FL_G + q * 8;
#pragma unroll 1
    for (int n = 0; n < STEPS; n++) {
      const uint32_t ln = opaque_tid() & 31;
      uint4* z = (uint4*)g_oacc + (uint32_t)(((n + 1) % ARING) * (16 * DM) + q * 96 + ln);
      fill16(z, 0); fill16(z + 32, 0); fill16(z + 64, 0);
      if (n + 3 >= MRING && q < 80) fill16((uint4*)g_mimg + (uint32_t)(((n + 3) % MRING) * 4096 + q * 32 + ln), SENT);
      bar_sync(B_M + (w - 1), 160);
      if (lane == 0) { T3(w * 2 - 2); fence_async_global(); flag_release(f, n + 1); T3(w * 2 - 1); }
      __syncwarp();
    }
  } else {
    const uint32_t u = (bid() - N_CHAIN) * 2 + (w & 1), r = u / 36 * 16 + (u & 3) * 4 + (lane >> 3);
    uint32_t o = r * (DM / 8) + (u % 36 >> 2) * 8 + ((lane & 7) ^ ((r >> 1) & 3)), fl = 0;
#pragma unroll 1
    for (int k = -LAG - 1; k < STEPS; k++) {
      if (k < NSEG - 1) bar_sync(B_X, 96);
      if (k < LAG || u >= 72) continue;
      if (k == NSEG - 1) { fl = near_half(XB_F, bid()) * 1024; wait_flags(g_fl + fl + FL_F + (lane & 1) * 8, NSEG + 1); }
      const uint4 x = __ldcg((const uint4*)P.out + o);
      if (k >= NSEG - 1) wait_flags(g_fl + fl + FL_OCNT + (max(k, NSEG) % OCRING) * 8, N_O * 3 * (max(k, NSEG) / OCRING + 1));
      const float4* a = (const float4*)g_oacc + ((k % ARING) * (16 * DM) + 8 * DM + u * 64 + lane * 2);
      const float4 p = __ldcg(a), v = __ldcg(a + 1);
      ((uint4*)P.out)[o] = make_uint4(badd2(x.x, pack2(p.x, p.y)), badd2(x.y, pack2(p.z, p.w)), badd2(x.z, pack2(v.x, v.y)), badd2(x.w, pack2(v.z, v.w)));
      o += 4 * DM;
    }
    if ((threadIdx.x & 127) == 0) TS(7);
  }
}

template <int WG, bool HALF, int KS, int N> __device__ __forceinline__ void o_mma(float* d, const uint32_t* a, uint32_t ob) {
  constexpr uint64_t db = desc_sw128(O_RING + (KS >> 2) * 8192 + (KS & 3) * 32);
  constexpr uint64_t da = desc_sw128(O_W + WG * 40960 + (KS < 40 ? KS / 5 * 2 + KS % 5 / 2 : KS - 24) * 2048);
  if constexpr (KS < 40 && !(KS % 5 & 1)) {
    const uint32_t* r = a + (KS / 5 * 3 + KS % 5 / 2) * 4;
    if constexpr (HALF) wg_rs32k<KS != 0, db>(d, r[0], r[1], r[2], r[3], ob); else wg_rs64<KS != 0>(d, r, db);
  } else {
    if constexpr (HALF) wg_ss32k<da, db>(d, ob); else wg_ss64<1>(d, da, db);
  }
  if constexpr (N > 1) o_mma<WG, HALF, KS + 1, N - 1>(d, a, ob);
}
template <int WG, bool HALF, int GR> __device__ __forceinline__ void o_groups(float* d, const uint32_t* a, uint32_t sb, int n, bool more) {
  const uint32_t ob = n < NSEG ? 0 : 256;
  mbar_wait(sb + O_BAR + GR * 8, n & 1);
  if (GR == 0) { if ((threadIdx.x & 127) == 0) T3(13 + WG); __syncwarp(); }
  if (GR == (WG == 0 ? 2 : 4) && (WG < 2 || n + 1 < STEPS)) bar_arrive(B_V + (WG + 1) % 3, 256);
  wg_fence();
  o_mma<WG, HALF, GR * 8, 8>(d, a, ob);
  if (GR == 4 && more) o_mma<WG, HALF, 40, 4>(d, a, ob);
  wg_commit();
  if (GR > 0) { wg_wait<1>(); if ((threadIdx.x & 31) == 0) mbar_arrive(sb + O_BAR + 120 + GR * 8); }
  if constexpr (GR < 4) o_groups<WG, HALF, GR + 1>(d, a, sb, n, more);
}
template <int WG, bool HALF> __device__ __forceinline__ void o_step(const uint32_t* a, uint32_t sb, uint32_t st0, int n, bool more) {
  float d[HALF ? 16 : 32];
  if (WG > 0 || n > 0) bar_sync(B_V + WG, 256);
  o_groups<WG, HALF, 0>(d, a, sb, n, more);
  wg_wait<0>();
  if ((threadIdx.x & 31) == 0) mbar_arrive(sb + O_BAR + 128 + 4 * 8);
  if ((threadIdx.x & 127) == 0) T3(WG == 0 ? 1 : WG == 1 ? 8 : 12);
  __syncwarp();
#pragma unroll(HALF ? 1 : 2)
  for (int sl = 0; sl < 2; sl++) {
    mbar_wait(sb + OB_ST + WG * 16 + sl * 8, (n & 1) ^ (WG == 0));
    if (!HALF || sl == (n >= NSEG)) {
#pragma unroll
      for (int nb = 0; nb < 4; nb++) {
        const float* r = d + (HALF ? 0 : sl * 16) + nb * 4;
        const uint32_t ad = st0 + sl * 8192 + nb * 2048;
        sts32(ad, __float_as_uint(r[0]));
        sts32(ad + 256, __float_as_uint(r[1]));
        sts32(ad ^ 32, __float_as_uint(r[2]));
        sts32((ad ^ 32) + 256, __float_as_uint(r[3]));
      }
      fence_async_smem();
    }
    bar_arrive((sl ? B_G : B_M) + WG, 160);
  }
}
template <int WG>
__device__ __forceinline__ void o_math(const Params& P, uint32_t sb) {
  const bool more = bid() < N_CHAIN + N_G + 12;
  const int lane = threadIdx.x & 31, w = (threadIdx.x >> 5) & 3, g = lane >> 2, tq = lane & 3;
  uint32_t a[96];
  mbar_wait(sb + W_BAR + WG * 8, 0);
  load_frags<24>(a, sb + WG * 49152);
  fence_async_smem();
  bar_sync(B_INIT, 416);
  load_wg<OROLE>(P, sb, false, WG, w);
  mbar_wait(sb + W_BAR + WG * 8, 1);
  if ((threadIdx.x & 127) == 0) TS(4);
  const uint32_t st0 = sb + O_ST + tq * 512 + ((w * 16 + g) ^ (tq * 8)) * 4;
#pragma unroll 1
  for (int n = 0; n < STEPS; n++) {
    if (n < LAG || n >= NSEG) o_step<WG, true>(a, sb, st0, n, more); else o_step<WG, false>(a, sb, st0, n, more);
  }
}

__device__ __forceinline__ void o_aux(const Params& P, uint32_t sb) {
  const int i = bid() - N_CHAIN - N_G, ksl = i / 3;
  const int c0 = ksl * 11 - max(ksl - 4, 0), nc = ksl < 4 ? 11 : 10;
  const int lane = threadIdx.x & 31, w = __shfl_sync(~0u, (threadIdx.x >> 5) & 3, 0);
  if (w == 0) {
    bar_sync(B_INIT, 416);
    const uint32_t* f = g_fl + FL_O + near_half(XB_F + 1, bid()) * 1024 + min((c0 & ~1) + lane, (c0 + nc - 1) | 1);
#pragma unroll 1
    for (int n = 0; n < STEPS; n++) {
      const unsigned char* src = g_oimg + (uint32_t)(((n % RING) * N_CHAIN + c0) * 8192);
      wait_flags(f, n + 1);
      fence_async_global();
      if (lane == 0) T3(0);
#pragma unroll
      for (int gr = 0; gr < 5; gr++) {
        const uint32_t full = sb + O_BAR + gr * 8, bytes = (gr < 4 ? 2 : nc - 8) * 8192;
        mbar_wait(full + 128, (n & 1) ^ 1);
        if (elect()) {
          if (n < LAG || n >= NSEG) {
            mbar_expect(full, bytes >> 1);
            for (uint32_t o = gr * 16384 + (n < LAG ? 0 : 4096); o < gr * 16384 + bytes; o += 8192) bulk_load(sb + O_RING + o, src + o, 4096, full);
          } else {
            mbar_expect(full, bytes);
            bulk_load(sb + O_RING + gr * 16384, src + gr * 16384, bytes, full);
          }
        }
      }
    }
  } else {
#pragma unroll 1
    for (int n = 0; n < STEPS; n++) {
      float* dst = g_oacc + (uint32_t)((n % ARING) * (64 * DM) + ((i % 3) * 3 + (w - 1 + ksl) % 3) * 1024);
      const bool early = w == 3 && n < NSEG;
      bar_sync(B_M + (w - 1), 160);
      if (lane == 0) {
        T3(w * 2);
        if (n < NSEG) { bulk_reduce(dst, sb + O_ST, 4096); bulk_reduce(dst + 16 * DM, sb + O_ST + 4096, 4096); }
        asm volatile("cp.async.bulk.commit_group;" ::: "memory");
        if (early) {
          asm volatile("cp.async.bulk.wait_group.read 0;" ::: "memory");
          mbar_arrive(sb + OB_ST);
          T3(8 + w);
          bulk_done_inc(g_fl + FL_OCNT + (n % OCRING) * 8);
          T3(w * 2 + 1);
        }
      }
      __syncwarp();
      bar_sync(B_G + (w - 1), 160);
      if (lane == 0) {
        if (n >= LAG) { bulk_reduce(dst + 32 * DM, sb + O_ST + 8192, 4096); bulk_reduce(dst + 48 * DM, sb + O_ST + 12288, 4096); }
        asm volatile("cp.async.bulk.commit_group;\ncp.async.bulk.wait_group.read 1;" ::: "memory");
        if (!early) mbar_arrive(sb + OB_ST + (w % 3) * 16);
        asm volatile("cp.async.bulk.wait_group.read 0;" ::: "memory");
        mbar_arrive(sb + OB_ST + (w % 3) * 16 + 8);
        if (!early) {
          T3(8 + w);
          bulk_done_inc(g_fl + FL_OCNT + (n % OCRING) * 8);
          T3(w * 2 + 1);
        }
      }
      __syncwarp();
    }
  }
}

constexpr uint32_t Y_PITCH = 1168, Y_ROWS = 16 * Y_PITCH;
template <int R> __device__ __forceinline__ void y_rows(uint32_t* y, uint32_t src, uint32_t dst, int w, int bar) {
  const int lane = threadIdx.x & 31;
#pragma unroll
  for (int k = 0; k < 2 * R + 1; k++) {
    const int op = w + k * (16 / R);
    if (k == 2 * R && w >= 4) break;
    uint32_t a, b, c, d;
    ldsm4t(a, b, c, d, src + op * 512 + (lane & 16) * 16 + (lane & 7) * 32 + (lane & 8) * 2);
    stsm4(dst + (lane & 15) * Y_PITCH + op * 32 + (lane & 16), a, b, c, d);
  }
  bar_sync(bar, 512 / R);
  const uint32_t row = dst + ((w & 6) * 2 + (w >> 3) * 2 + (w & 1)) * Y_PITCH + lane * 4;
#pragma unroll
  for (int i = 0; i < 9 * R; i++) y[i] = lds32(row + i / 9 * 2 * Y_PITCH + i % 9 * 128);
}

__device__ __forceinline__ void f_role(const Params& P, uint32_t sb) {
  const int lane = threadIdx.x & 31, w = __shfl_sync(~0u, threadIdx.x >> 5, 0), r0 = (bid() - N_CHAIN - N_G - N_O) * 16;
  if (w == 8) {
    const uint32_t* fo = g_fl + FL_OCNT + near_half(XB_F, bid()) * 1024;
    fence_async_global();
#pragma unroll 1
    for (int n = 0; n < NSEG; n++) {
      bar_sync(2, 288);
      if (elect()) {
        mbar_expect(sb + F_BAR, 36864);
        bulk_load(sb + F_XY, P.X + (size_t)(n * 32 + r0) * DM, 18432, sb + F_BAR);
        bulk_load(sb + F_XY + 18432, g_yT + (size_t)(n * 32 + r0) * DM, 18432, sb + F_BAR);
        mbar_expect(sb + F_BAR + 8, 36864);
        T3(1);
      }
      wait_flags(fo + (n % OCRING) * 8, N_O * 3 * (n / OCRING + 1));
      fence_async_global();
      if (elect()) { bulk_load(sb + F_A, g_oacc + (uint32_t)((n % ARING) * (64 * DM) + r0 * DM), 36864, sb + F_BAR + 8); T3(0); }
    }
  } else if (w == 9) {
#pragma unroll 1
    for (int n = 0; n < NSEG; n++) {
      const uint32_t st = sb + (n & 1) * 36864;
      unsigned char* p = g_lnimg + (uint32_t)((NSEG + n) * 36864 + r0 * 128);
      bar_sync(1, 288);
      if (elect()) {
        T3(2);
#pragma unroll
        for (int i = 0; i < 9; i++) bulk_store(p + i * 4096, st + F_L + i * 2048, 2048);
        asm volatile("cp.async.bulk.commit_group;" ::: "memory");
        bulk_done_inc(g_fl + FL_F + (bid() & 1) * 8);
        T3(3);
        bulk_store(P.out + (size_t)(n * 32 + r0) * DM, st + F_X, 18432);
        asm volatile("cp.async.bulk.commit_group;\ncp.async.bulk.wait_group.read 0;" ::: "memory");
        if (n + 1 == NSEG) bulk_done_inc(g_fl + FL_F + (bid() & 1) * 8);
      }
      __syncwarp();
    }
  } else if (w < 8) {
    const uint32_t row = sb + w * 1152 + lane * 4, acc = sb + F_A + w * 256 + (lane ^ ((w & 6) * 2)) * 8;
    const uint32_t ln = sb + F_L + w * 128 + (((lane >> 2) ^ w) << 4) + (lane & 3) * 4;
#pragma unroll 1
    for (int n = -1; n < NSEG; n++) {
      const uint32_t st = (n & 1) * 36864;
      uint32_t x[18], y[18], l[18];
      if (n >= 0) mbar_wait(sb + F_BAR, n & 1);
#pragma unroll
      for (int i = 0; i < 18; i++) x[i] = lds32(row + F_XY + i / 9 * 9216 + i % 9 * 128);
      y_rows<2>(y, sb + F_XY + 18432, sb + F_Y, w, 3);
      layernorm9<2>(x, l);
#pragma unroll
      for (int i = 0; i < 18; i++) x[i] = badd2(x[i], bmul2(l[i], y[i]));
      if (n >= 0) mbar_wait(sb + F_BAR + 8, n & 1);
      if (threadIdx.x == 0 && n >= 0) T3(4);
      __syncwarp();
      uint2 a[18];
#pragma unroll
      for (int i = 0; i < 18; i++) a[i] = lds64(acc + i / 9 * 2048 + i % 9 * 4096);
#pragma unroll
      for (int i = 0; i < 18; i++) x[i] = badd2(x[i], pack2(__uint_as_float(a[i].x), __uint_as_float(a[i].y)));
      if (n + 1 < NSEG) bar_arrive(2, 288);
      layernorm9<2>(x, l);
#pragma unroll
      for (int i = 0; i < 18; i++) { x[i] = badd2(x[i], bmul2(l[i], y[i])); sts32(row + st + F_X + i / 9 * 9216 + i % 9 * 128, x[i]); }
      layernorm9<2>(x, l);
#pragma unroll
      for (int i = 0; i < 18; i++) sts32(ln + st + i / 9 * 1024 + i % 9 * 2048, l[i]);
      fence_async_smem();
      if (n >= 0) bar_sync(1, 288); else bar_sync(3, 256);
    }
  }
}

constexpr uint32_t P_CH = 147456, P_CHSZ = 12800, P_H = 4352;
static_assert(P_CH + 6 * P_CHSZ <= G_BAR, "prologue smem");

template <int N>
__device__ __forceinline__ void conv_fold(float (*acc)[4], bool hi, uint32_t mine, uint32_t theirs, int bar, int cnt) {
#pragma unroll
  for (int i = 0; i < N / 2; i++) {
    uint4 v;
    v.x = __float_as_uint(hi ? acc[i][0] : acc[i + N / 2][0]); v.y = __float_as_uint(hi ? acc[i][1] : acc[i + N / 2][1]);
    v.z = __float_as_uint(hi ? acc[i][2] : acc[i + N / 2][2]); v.w = __float_as_uint(hi ? acc[i][3] : acc[i + N / 2][3]);
    sts128(mine + i * 512, v);
  }
  bar_sync(bar, cnt);
#pragma unroll
  for (int i = 0; i < N / 2; i++) {
    const uint4 v = lds128(theirs + i * 512);
    acc[i][0] = (hi ? acc[i + N / 2][0] : acc[i][0]) + __uint_as_float(v.x); acc[i][1] = (hi ? acc[i + N / 2][1] : acc[i][1]) + __uint_as_float(v.y);
    acc[i][2] = (hi ? acc[i + N / 2][2] : acc[i][2]) + __uint_as_float(v.z); acc[i][3] = (hi ? acc[i + N / 2][3] : acc[i][3]) + __uint_as_float(v.w);
  }
}
template <int N>
__device__ __forceinline__ void conv_store(const float (*acc)[4], int tile0, uint32_t su, int d, uint32_t dd) {
  const int lane = threadIdx.x & 31, g = lane >> 2, tq = lane & 3;
#pragma unroll
  for (int i = 0; i < N; i++) {
    const uint32_t ad = su + (8 + (tile0 + i) * 8 + g) * 32 + tq * 4, sw = (g & 4) << 2;
    const uint32_t lo = badd2(movmat(pack2(acc[i][0], acc[i][1])), bmul2(lds32(ad + sw), dd));
    const uint32_t hi = badd2(movmat(pack2(acc[i][2], acc[i][3])), bmul2(lds32(ad + (sw ^ 16)), dd));
    ((uint2*)g_yT)[(((tile0 + i) * 8 + g) * DM + d) * 4 + tq] = make_uint2(lo, hi);
  }
}

__device__ __forceinline__ void prologue(const Params& P, uint32_t sb) {
  const int b = bid(), tid = threadIdx.x, lane = tid & 31, warp = tid >> 5, t0 = b * 16;
  const bool isg = b >= N_CHAIN && b < N_CHAIN + N_G;
  const int nch = isg ? 2 : b < 128 ? 6 : 0, chb = b < N_CHAIN ? b * 6 : isg ? b * 2 + 256 : b * 6 - 192;
  const uint32_t tstart = clk();
  if (tid < 288) {
    if (b < 128) {
      const int c = (tid >> 1) * 4, tt = t0 + (tid & 1) * 8;
      uint2 kr[11], vr[8];
#pragma unroll
      for (int i = 0; i < 11; i++) { const int t = tt + i - 3; kr[i] = t >= 0 ? __ldg((const uint2*)(P.K + (size_t)t * DM + c)) : make_uint2(0, 0); }
#pragma unroll
      for (int i = 0; i < 8; i++) vr[i] = __ldg((const uint2*)(P.V + (size_t)(tt + i) * DM + c));
#pragma unroll
      for (int e = 0; e < 2; e++) {
        const uint4 sh = __ldg((const uint4*)(P.shift + c * 4) + e);
        const uint32_t s0 = __byte_perm(sh.x, sh.z, 0x5410), s1 = __byte_perm(sh.x, sh.z, 0x7632);
        const uint32_t s2 = __byte_perm(sh.y, sh.w, 0x5410), s3 = __byte_perm(sh.y, sh.w, 0x7632);
        uint32_t v[8];
#pragma unroll
        for (int i = 0; i < 8; i++) {
          const uint32_t k3 = e ? kr[i].y : kr[i].x, k2 = e ? kr[i + 1].y : kr[i + 1].x, k1 = e ? kr[i + 2].y : kr[i + 2].x, k0 = e ? kr[i + 3].y : kr[i + 3].x;
          v[i] = bmul2(badd2(badd2(badd2(bmul2(k3, s3), bmul2(k2, s2)), bmul2(k1, s1)), bmul2(k0, s0)), e ? vr[i].y : vr[i].x);
        }
        *(uint4*)(g_kvT + (size_t)(c + 2 * e) * KVP + tt) =
          make_uint4(__byte_perm(v[0], v[1], 0x5410), __byte_perm(v[2], v[3], 0x5410), __byte_perm(v[4], v[5], 0x5410), __byte_perm(v[6], v[7], 0x5410));
        *(uint4*)(g_kvT + (size_t)(c + 2 * e + 1) * KVP + tt) =
          make_uint4(__byte_perm(v[0], v[1], 0x7632), __byte_perm(v[2], v[3], 0x7632), __byte_perm(v[4], v[5], 0x7632), __byte_perm(v[6], v[7], 0x7632));
      }
    }
  } else if (tid < 384) {
    const int t = tid - 288;
    for (int i = b * 96 + t; i < 16 * DM; i += N_CTA * 96) ((uint4*)g_oacc)[i] = make_uint4(0, 0, 0, 0);
    if (b * 96 + t < 128 * 8) g_lnflag[b * 96 + t] = 0;
    if (t == 95) sts32(sb + S_GEN, ld_acquire(g_gbar));
    __syncwarp();
    wait_until(tstart, PREFH);
    for (int i = t; i < 32 * nch; i += 96) asm volatile("prefetch.global.L2 [%0];" :: "l"(P.Hk + (size_t)chb * SEQ + i * 64));
  }
  if (warp < 12) {
    bar_arrive(10, 416);
    if (tid == 128) TS(14);
    const int ch = 5 - (warp >> 1), sub = warp & 1, d = chb + ch;
    const uint32_t su = sb + P_CH + ch * P_CHSZ;
    if (ch < nch) {
      const uint32_t* hs = (const uint32_t*)(P.Hk + (size_t)d * SEQ);
#pragma unroll
      for (int q = sub * 32 + lane; q < 256; q += 64) {
        const uint4 c = __ldg((const uint4*)hs + q);
        const uint32_t prev = q ? __ldg(hs + 4 * q - 1) : 0u;
        sts128(su + P_H + 32 + q * 16, make_uint4(__byte_perm(c.x, prev, 0x7610), __byte_perm(c.y, c.x, 0x7610), __byte_perm(c.z, c.y, 0x7610), __byte_perm(c.w, c.z, 0x7610)));
        sts128(su + P_H + 4224 + q * 16, make_uint4(__byte_perm(c.x, 0, 0x1032), __byte_perm(c.y, 0, 0x1032), __byte_perm(c.z, 0, 0x1032), __byte_perm(c.w, 0, 0x1032)));
      }
      if (sub == 1 && lane == 0) sts32(su + P_CHSZ - 16, __bfloat16_as_ushort(P.Dk[d]) * 0x10001u);
      if (sub == 0 && lane < 20) sts128(su + (lane < 16 ? lane * 16 : P_H + (lane & 2) * 2096 + (lane & 1) * 16), make_uint4(0, 0, 0, 0));
    }
    bar_sync(11, 416);
    if (ch < nch) {
#pragma unroll
      for (int q = sub * 32 + lane; q < 256; q += 64) {
        const int row = (q >> 1) + 8;
        sts128(su + row * 32 + (((q & 1) ^ ((row >> 2) & 1)) << 4), __ldcg((const uint4*)(g_kvT + (size_t)d * KVP) + q));
      }
    }
    const int g = lane >> 2, tq = lane & 3;
    const uint32_t sh = su + P_H + (g & 1) * 4192 + (8 + (g >> 1) - tq) * 4;
    float acc[16][4];
#pragma unroll
    for (int i = 0; i < 16; i++) { acc[i][0] = acc[i][1] = acc[i][2] = acc[i][3] = 0.f; }
    auto u_addr = [&](int res) {
      const int row = 8 - res + ((lane >> 4) << 3) + (lane & 7);
      return su + row * 32 + ((((lane >> 3) & 1) ^ ((row >> 2) & 1)) << 4);
    };
    if (ch < nch) {
      bar_sync(1 + ch, 64);
      if (tid == 352) TS(11);
      if (sub) {
#pragma unroll 4
        for (int res = 0; res < 8; res++) {
          uint32_t b0, b1, b2, b3;
          ldsm4(b0, b1, b2, b3, u_addr(res));
          const uint32_t r0 = lds32(sh + res * 32);
          mma16(acc[0], r0, lds32(sh + res * 32 + 16), lds32(sh + res * 32 - 16), r0, b0, b1);
        }
        conv_store<1>(acc, 0, su, d, lds32(su + P_CHSZ - 16));
      }
    }
    bar_arrive(12, 416);
    if (isg && warp < 8) { while ((int)(clk() - tstart - S1G) < 0) __nanosleep(200); load_wg<GROLE>(P, sb, true, warp >> 2, warp & 3); }
    if (ch < nch) {
#pragma unroll 1
      for (int res = sub * 4; res < sub * 4 + 4; res++) {
        uint32_t bf[16][2];
        const uint32_t ad = u_addr(res);
#pragma unroll
        for (int f = 0; f < 16; f += 2) ldsm4(bf[f][0], bf[f][1], bf[f + 1][0], bf[f + 1][1], ad + f * 256);
#pragma unroll
        for (int k = 0; k < 16; k++) {
          const int jj = k & 1 ? k >> 1 : 15 - (k >> 1);
          const uint32_t ah = sh + (8 * jj + res) * 32;
          const uint32_t r0 = lds32(ah), r1 = lds32(ah + 16), rm = lds32(ah - 16);
#pragma unroll
          for (int i = max(jj, 1); i < 16; i++) mma16(acc[i], r0, r1, rm, r0, bf[i - jj][0], bf[i - jj][1]);
        }
      }
      bar_sync(1 + ch, 64);
      if (tid == 352) TS(12);
      const uint32_t xb = su + P_H + lane * 16, dd = lds32(su + P_CHSZ - 16);
      conv_fold<16>(acc, sub, xb + sub * 4096, xb + (sub ^ 1) * 4096, 1 + ch, 64);
      conv_store<8>(acc, sub * 8, su, d, dd);
    }
  } else {
    for (int i = b; i < 194 + MRING * 5; i += N_CTA) {
      const int n = (i - 194) / 5, r = (i - 194) % 5, blk = i < 192 ? i / 6 * 8 + i % 6 : i < 194 ? XB_F + i - 192 : XB_M + n * 8 + r;
      const uint32_t fill = i < 194 ? 0u : SENT;
#pragma unroll 1
      for (int q = tid - 384; q < 256 && warp < 15; q += 96) {
        uint4 v = make_uint4(fill, fill, fill, fill);
        if (i >= 194 && n == 0 && (r > 0 || q < 128)) {
          const bf16* m = P.mem0 + (max(r * 8 - 4, 0) + (q >> 5)) * 16 + ((q >> 1) & 1) * 8 + ((q >> 2) & 7);
          v.x = pack2(__bfloat162float(m[0]), __bfloat162float(m[DM])); v.y = pack2(__bfloat162float(m[2 * DM]), __bfloat162float(m[3 * DM]));
          v.z = pack2(__bfloat162float(m[4 * DM]), __bfloat162float(m[5 * DM])); v.w = pack2(__bfloat162float(m[6 * DM]), __bfloat162float(m[7 * DM]));
        }
        g_xb[blk * 512 + q] = v;
        g_xb[blk * 512 + 256 + q] = v;
      }
    }
    if (tid < 388) g_xb[XB_REF * 512 + (tid & 2) * 128 + (b & ~1) + (tid & 1)] = make_uint4(0, 0, 0, 0);
    else if (tid < 392 && b < N_GRP) g_xb[(b * 8 + 7) * 512 + (tid & 2) * 128 + (tid & 1)] = make_uint4(0, 0, 0, 0);
    if (warp < 15) { bar_arrive(9, 128); bar_sync(7, 96); }
    if (tid == 384) TS(8);
    if (warp == 12) {
      const bf16* w = lane < 6 ? (lane % 3 == 0 ? P.Wk : lane % 3 == 1 ? P.Wv : P.Wq) + (((b >> 5) * 2 + lane / 3) * 32 + (b & 31)) * 2048
                               : (lane < 8 ? P.Wo + (lane - 6) * (9 * 131072) : P.X) + b * 2048;
      uint32_t t = tstart + PREF0;
      if ((int)(clk() - t) > 0) t = clk();
#pragma unroll 1
      for (int st = 0; st < 9 && b < N_CHAIN; st++) {
#pragma unroll 1
        for (int i = 0; i < 9; i++, t += PACE) {
          wait_until(t, 0);
          if (lane == st) asm volatile("cp.async.bulk.prefetch.L2.global [%0], 4096;" :: "l"(w + i * (lane < 6 ? 262144 : 131072)) : "memory");
        }
      }
      if (lane == 0) TS(10);
    } else if (warp == 15) {
      bar_sync(10, 416);
      if (lane == 0) { grid_arrive(0); if (nch) grid_wait(0, lds32(sb + S_GEN)); }
      __syncwarp();
      bar_arrive(11, 416);
      if (lane == 0) TS(1);
      bar_sync(9, 128);
      bar_sync(12, 416);
      if (lane == 0) { TS(16); grid_arrive(2); TS(17); }
    } else if (lane == 0) {
      if (warp == 13 || (warp == 14 && b < N_GRP)) {
        uint32_t* p = (uint32_t*)(g_xb + (warp == 13 ? XB_REF * 512 + b : (b * 8 + 7) * 512));
        int votes = 0;
        for (int rep = 0; rep < 24 && abs(votes) < 7; rep++) {
          uint32_t v0, v1, c0, c1;
          asm volatile("atom.relaxed.gpu.global.add.u32 %0, [%4], 1;\n atom.relaxed.gpu.global.add.u32 %1, [%5], 1;\n"
                       "{.reg .pred p; setp.eq.u32 p, %0, 0x7ffffff3; @p trap; mov.u32 %2, %%clock; setp.eq.u32 p, %1, 0x7ffffff3; @p trap; mov.u32 %3, %%clock;}"
                       : "=&r"(v0), "=&r"(v1), "=&r"(c0), "=&r"(c1) : "l"(p + (rep & 1) * 1024), "l"(p + ((rep & 1) ^ 1) * 1024) : "memory");
          votes += ((c1 - c0 > 80u) == (rep & 1)) ? 1 : -1;
        }
        if (warp == 13) { g_side[b] = votes > 0; TS(9); } else g_near[b] = votes > 0;
      }
    }
    __syncwarp();
    if (warp > 12 && b < N_CHAIN) {
      while ((int)(clk() - tstart - S1DLY) < 0) __nanosleep(200);
      for (int k = warp - 13; k < 8; k += 3) load_wg<CHAIN>(P, sb, true, 1 - k / 4, k & 3);
    }
  }
  if (b < N_CHAIN + N_G && (warp < 8 || (isg && warp >= 12))) bar_arrive(0, 512); else bar_sync(0, 512);
  if (tid == 352) TS(2);
}

__device__ __forceinline__ void publish_y() {
  if (threadIdx.x == 383) { grid_arrive(1); TS(18); }
  __syncwarp();
}

template <int R> __device__ __forceinline__ void ln_tiles(const Params& P, uint32_t sb) {
  const int lane = threadIdx.x & 31, w = (threadIdx.x >> 5) & (16 / R - 1), half = R == 1 ? 0 : threadIdx.x >> 8, u = N_CTA - 1 - bid();
  const int first = R == 1 ? u : 46 - 2 * u + half, step = R == 1 ? 4 : 40, last = R == 1 ? 8 : 128;
  const uint32_t raw = sb + P_CH + half * (18432 + Y_ROWS), mb = sb + T_BAR + (R - 1 + half) * 8;
  const bool lead = w == 16 / R - 1 && lane == 0;
  auto load_y = [&](const bf16* src, int tile) {
    fence_async_global();
    mbar_expect(mb, 18432);
    bulk_load(raw, src + (size_t)tile * 16 * DM, 18432, mb);
  };
  uint32_t nx[9 * R];
  auto load_x = [&](int tile) {
#pragma unroll
    for (int i = 0; i < 9 * R; i++) nx[i] = __ldg((const uint32_t*)(P.X + (size_t)(tile * 16 + w + i / 9 * 8) * DM) + i % 9 * 32 + lane);
  };
  load_x(first);
  if (R == 2) {
    if (lead) { grid_wait(1, lds32(sb + S_GEN)); if (u > 3) TS(13); load_y(g_yT, first); }
    __syncwarp();
  }
#pragma unroll 1
  for (int tile = first, real = R - 1, ph = 0; tile < last; tile += real * step, real = 1, ph ^= 1) {
    uint32_t x[9 * R], l[9 * R], y[9 * R];
    const bool ts = threadIdx.x == 0 && (R == 1 ? tile == first : u > 3 && tile == first + step);
    if (ts) TS(26);
#pragma unroll
    for (int i = 0; i < 9 * R; i++) x[i] = nx[i];
    layernorm9<R>(x, l);
    if (real && tile + step < last) load_x(tile + step);
    if (R == 2 && tile == first + step && u >= N_F && w < 6) load_wg<OROLE>(P, sb, true, w >> 1, half * 2 + (w & 1));
    if (R == 1 && tile == first && lead) {
      if (real) grid_wait(2, lds32(sb + S_GEN));
      TS(13);
      load_y(real ? g_yT : P.Hk, tile);
    }
    bar_sync(13 + half, 512 / R);
    mbar_wait(mb, ph);
    if (ts) TS(28);
    y_rows<R>(y, raw, raw + 18432, w, 13 + half);
    if (ts) TS(29);
    if (lead && real && tile + step < last) { fence_async_smem(); load_y(g_yT, tile + step); }
    __syncwarp();
#pragma unroll
    for (int i = 0; i < 9 * R; i++) x[i] = badd2(x[i], bmul2(l[i], y[i]));
    layernorm9<R>(x, l);
    if (ts && l[0] != 0x12345) TS(30);
#pragma unroll
    for (int r = 0; r < R; r++) store_ln_row(0, tile * 16 + w + r * 8, l + r * 9);
    if (R == 1) {
      __syncthreads();
      if (threadIdx.x == 32 && real) { if (tile < 4) TS(19); st_release(g_lnflag + tile * 8, 1); if (tile < 4) TS(20); }
      __syncwarp();
    }
    if (ts) TS(31);
  }
  if (R == 2) {
    __syncthreads();
    if (threadIdx.x >= 506) {
      asm volatile("fence.acq_rel.gpu;" ::: "memory");
      st_relaxed_if(g_lnflag + ((first ^ (lane & 1)) + (lane - 26) / 2 * step) * 8, 1, true);
    }
    __syncwarp();
    fence_async_smem();
    if (threadIdx.x == 0) TS(15);
  }
}

__global__ void __cluster_dims__(2, 1, 1) __launch_bounds__(512, 1) k_main(const __grid_constant__ Params P) {
  extern __shared__ __align__(1024) unsigned char smem[];
  const uint32_t sb = (uint32_t)__cvta_generic_to_shared(smem);
  const int b = bid(), wg = threadIdx.x >> 7;
  if ((threadIdx.x & 127) == 0) TS(0);
  if (threadIdx.x == 480) {
    if ((sb & 0xFFFFFF) != SBASE) __trap();
    for (int i = 0; i < 6; i++) mbar_init(sb + W_BAR + i * 8, 1);
    if (b < N_CHAIN) {
      mbar_init(sb + CB_FULL, 1); mbar_init(sb + CB_FULL + 8, 1);
      mbar_init(sb + CB_REF, 1);
      mbar_init(sb + CB_SX, 1); mbar_init(sb + CB_OX, 1); mbar_init(sb + CB_XX, 1); mbar_init(sb + CB_Q, 2); mbar_init(sb + CB_VF, 1);
      sts32(sb + C_BAD, 0);
      for (int i = 0; i < 11; i++) mbar_init(sb + CB_M + i * 8, i == 0 ? 5 : i == 5 ? 3 - SEPV : 1);
    } else if (b < N_CHAIN + N_G) {
      for (int i = 0; i < 9; i++) { mbar_init(sb + G_BAR + i * 8, 2); mbar_init(sb + G_BAR + 128 + i * 8, 8); }
    } else if (b < N_CHAIN + N_G + N_O) {
      for (int i = 0; i < 5; i++) { mbar_init(sb + O_BAR + i * 8, 1); mbar_init(sb + O_BAR + 128 + i * 8, 12); }
      for (int i = 0; i < 6; i++) mbar_init(sb + OB_ST + i * 8, 1);
    } else {
      mbar_init(sb + F_BAR, 1); mbar_init(sb + F_BAR + 8, 1);
    }
    asm volatile("fence.mbarrier_init.release.cluster;" ::: "memory");
    fence_async_smem();
  }
  __syncwarp();
  asm volatile("barrier.cluster.arrive.relaxed.aligned;" ::: "memory");
  prologue(P, sb);
  asm volatile("barrier.cluster.wait.aligned;" ::: "memory");
  fence_async_smem();
  if (b >= N_CHAIN + N_G) publish_y();
  if (b >= 128) ln_tiles<1>(P, sb);
  if (b >= N_CHAIN + N_G) ln_tiles<2>(P, sb);
  if ((threadIdx.x & 127) == 0) TS(3);
  if (b < N_CHAIN) {
    if (wg < 2) { reg_inc<200>(); chain_proj(P, sb); }
    else if (wg == 2) { reg_dec<ATTR>(); publish_y(); chain_attn(P, sb); }
    else { reg_dec<112 - ATTR>(); chain_aux(P, sb); }
  } else if (b < N_CHAIN + N_G) {
    if (wg == 0) { reg_inc<232>(); g_math<0>(P, sb); }
    else if (wg == 1) { reg_inc<232>(); g_math<1>(P, sb); }
    else if (wg == 2) { reg_dec<24>(); bar_arrive(15, 192); publish_y(); g_aux(P, sb); }
    else { reg_dec<24>(); g_load(P, sb); }
  } else if (b < N_CHAIN + N_G + N_O) {
    if (wg == 0) { reg_inc<160>(); o_math<0>(P, sb); }
    else if (wg == 1) { reg_inc<160>(); o_math<1>(P, sb); }
    else if (wg == 2) { reg_inc<160>(); o_math<2>(P, sb); }
    else { reg_dec<32>(); o_aux(P, sb); }
  } else {
    f_role(P, sb);
  }
}

}

extern "C" void kernel_launch(void* const* d_in, const int* in_sizes, int n_in, void* d_out, int out_size) {
  typedef CUresult (*Encode)(CUtensorMap*, CUtensorMapDataType, cuuint32_t, void*, const cuuint64_t*, const cuuint64_t*, const cuuint32_t*, const cuuint32_t*,
                             CUtensorMapInterleave, CUtensorMapSwizzle, CUtensorMapL2promotion, CUtensorMapFloatOOBfill);
  static Encode encode = nullptr;
  if (!encode) cudaGetDriverEntryPoint("cuTensorMapEncodeTiled", (void**)&encode, cudaEnableDefault);
  Params P;
  for (int i = 0; i < 11; i++) {
    const bool wo = i == 6 || i == 7;
    const cuuint64_t cols = wo ? DM : HD, rows = HD + DM - cols, pitch = cols * 2;
    const cuuint64_t dim[4][5] = {{cols, 2, 8, 2, 18}, {cols, 16, 1, 1, rows / 16}, {cols, 2, 4, 4, rows / 32}, {64, 16, 64, 2, 18}};
    const cuuint64_t stride[4][4] = {{8 * pitch, pitch, 16 * pitch, 32 * pitch}, {pitch, pitch, pitch, 16 * pitch},
                                     {pitch, 8 * pitch, 2 * pitch, 32 * pitch}, {pitch, 128, 16 * pitch, 32 * pitch}};
    const cuuint32_t box[4][5] = {{64, 2, 8, 1, 18}, {64, 16, 1, 1, 1}, {64, 2, 4, 2, 1}, {64, 16, 2, 1, 18}}, one[5] = {1, 1, 1, 1, 1};
    const int k = i < 3 ? 0 : i < 7 ? 1 : i < 8 ? 2 : 3;
    encode(&P.map[i], CU_TENSOR_MAP_DATA_TYPE_BFLOAT16, 5, d_in[wo ? 11 : 8 + (i & 7) % 3], dim[k], stride[k], box[k], one,
           CU_TENSOR_MAP_INTERLEAVE_NONE, CU_TENSOR_MAP_SWIZZLE_128B, CU_TENSOR_MAP_L2_PROMOTION_L2_128B, CU_TENSOR_MAP_FLOAT_OOB_FILL_NONE);
  }
  P.X = (const bf16*)d_in[0]; P.K = (const bf16*)d_in[1]; P.V = (const bf16*)d_in[2];
  P.shift = (const bf16*)d_in[3]; P.Hk = (const bf16*)d_in[4]; P.Dk = (const bf16*)d_in[5];
  P.mem0 = (const bf16*)d_in[7];
  P.Wq = (const bf16*)d_in[8]; P.Wk = (const bf16*)d_in[9]; P.Wv = (const bf16*)d_in[10]; P.Wo = (const bf16*)d_in[11];
  P.out = (bf16*)d_out;
  for (int i = 0; i < 24; i++) P.dly[i] = h_dly[i];
  cudaFuncSetAttribute(k_main, cudaFuncAttributeMaxDynamicSharedMemorySize, SMEM_BYTES);
  k_main<<<N_CTA, 512, SMEM_BYTES>>>(P);
}
```

```cpp
#include <cuda.h>
#include <cuda_runtime.h>
#include <cuda_bf16.h>
#include <stdint.h>

namespace {

typedef __nv_bfloat16 bf16;

constexpr int SEQ = 2048, DM = 576, HD = 4096, NSEG = 64;
constexpr int LAG = 7, STEPS = NSEG + LAG, RING = 8;
constexpr int LOCK0 = 3, QRING = LOCK0 + 1;
static_assert(LAG < RING, "ring");
constexpr int N_CHAIN = 64, N_G = 48, N_O = 18, N_F = 2;
constexpr uint32_t SBASE = 1024;
constexpr uint32_t SENT = 0xFFFFFFFFu;
constexpr int SPIN_MAX = 1 << 22;

__device__ __forceinline__ uint32_t bid() {
  uint32_t b;
  asm volatile("mov.u32 %0, %%ctaid.x;" : "=r"(b));
  return b < 6 ? b + 106 : b < 8 ? b + 122 : b < 114 ? b - 8 : b < 130 ? b - 2 : b;
}
__device__ __forceinline__ uint32_t chain_id() { return blockIdx.x - 8; }
constexpr int KVP = SEQ + 64;
__device__ __align__(1024) bf16 g_kvT[DM * KVP];
__device__ __align__(1024) bf16 g_yT[DM * SEQ];
__device__ __align__(1024) unsigned char g_lnimg[2 * NSEG * 9 * 4096];
__device__ __align__(1024) unsigned char g_qkv[QRING * N_CHAIN * 24576];
__device__ __align__(1024) unsigned char g_oimg[RING * N_CHAIN * 8192];
constexpr int ARING = 16;
static_assert(ARING >= LAG + 9, "accumulator ring");
__device__ __align__(1024) float g_oacc[ARING * 64 * DM];
constexpr int MRING = LAG + 4, N_GRP = 32 + MRING + 1;
constexpr int XB_M = 256, XB_F = XB_M + MRING * 8, XB_REF = XB_F + 2, N_CTA = N_CHAIN + N_G + N_O + N_F;
__device__ __align__(65536) uint4 g_xb[N_GRP * 4096];
#define g_mimg ((uint32_t*)(g_xb + XB_M * 512))
__device__ uint32_t g_near[N_GRP];
__device__ uint32_t g_side[N_CTA];
__device__ __align__(128) uint32_t g_gbar[3 * 32];
constexpr int FL_G = 0, FL_F = 96 * 8, FL_OCNT = FL_F + 2 * 8, OCRING = 16, FL_TICK = 992, FL_O = 2048, FL_SYNC = FL_O + 128;
static_assert(FL_OCNT + OCRING * 8 <= FL_TICK, "flag block");
#define g_fl ((uint32_t*)(g_xb + XB_F * 512))
__device__ __align__(1024) uint32_t g_lnflag[128 * 8];
#define TS(slot)

#define CNT(slot, tries)
#define T3(slot)
#define TR(slot)
#define TRV(slot, val)
#define TRD(slot, dep)
#define TRSYNC()
#define TRDUMP(n)
#define CLK(t) "{.reg .b64 x; .reg .b32 h; mov.u64 x, %%clock64; mov.b64 {" t ", h}, x;}"
__device__ __forceinline__ uint32_t clk() { uint32_t t; asm volatile(CLK("%0") : "=r"(t) :: "memory"); return t; }
__device__ __forceinline__ void wait_until(uint32_t t0, uint32_t d) {
  asm volatile("{.reg .pred p; .reg .u32 t;\n"
               "W: " CLK("t") " sub.u32 t, t, %0; setp.lt.s32 p, t, 0; @p bra.uni W;}"
               :: "r"(t0 + d) : "memory");
}
__device__ __forceinline__ uint32_t pack2(float lo, float hi) {
  uint32_t r; asm("cvt.rn.bf16x2.f32 %0, %1, %2;" : "=r"(r) : "f"(hi), "f"(lo)); return r;
}
__device__ __forceinline__ float bf_lo(uint32_t v) { return __uint_as_float(v << 16); }
__device__ __forceinline__ float bf_hi(uint32_t v) { return __uint_as_float(v & 0xFFFF0000u); }

__device__ __forceinline__ void st_b128(void* p, uint32_t a, uint32_t b, uint32_t c, uint32_t d) {
  asm volatile("{.reg .b128 v; mov.b128 v, {%1,%2,%3,%4}; st.relaxed.gpu.global.b128 [%0], v;}" :: "l"(p), "r"(a), "r"(b), "r"(c), "r"(d) : "memory");
}
__device__ __forceinline__ void st_relaxed_if(void* p, uint32_t a, bool on) {
  asm volatile("{.reg .pred p; setp.ne.u32 p, %2, 0; @p st.relaxed.gpu.global.u32 [%0], %1;}" :: "l"(p), "r"(a), "r"((uint32_t)on) : "memory");
}
__device__ __forceinline__ uint32_t ld_acquire(const uint32_t* p) {
  uint32_t v; asm volatile("ld.acquire.gpu.global.u32 %0, [%1];" : "=r"(v) : "l"(p) : "memory"); return v;
}
__device__ __forceinline__ void st_release(uint32_t* p, uint32_t v) {
  asm volatile("st.release.gpu.global.u32 [%0], %1;" :: "l"(p), "r"(v) : "memory");
}
__device__ __forceinline__ void bulk_reduce(float* dst, uint32_t src, uint32_t bytes) {
  asm volatile("cp.reduce.async.bulk.global.shared::cta.bulk_group.add.f32 [%0], [%1], %2;" :: "l"(dst), "r"(src), "r"(bytes) : "memory");
}
__device__ __forceinline__ void bulk_done_inc(uint32_t* p) {
  asm volatile("cp.async.bulk.wait_group 0;\n"
               "fence.proxy.async.global;\nfence.release.gpu;\n"
               "red.relaxed.gpu.global.add.u32 [%0], 1;\nred.relaxed.gpu.global.add.u32 [%0+4096], 1;" :: "l"(p) : "memory");
}
__device__ __forceinline__ void flag_release(uint32_t* p, uint32_t v) {
  asm volatile("fence.release.gpu;\nst.relaxed.gpu.global.u32 [%0], %1;\nst.relaxed.gpu.global.u32 [%0+4096], %1;" :: "l"(p), "r"(v) : "memory");
}
__device__ __forceinline__ void spin_guard(int& it) {
  asm volatile("{.reg .pred p; add.s32 %0, %0, 1; setp.gt.s32 p, %0, %1; @p trap;}" : "+r"(it) : "n"(SPIN_MAX));
}
__device__ __forceinline__ void wait_flags(const uint32_t* p, uint32_t v) {
  int it = 0;
  while (true) {
    uint32_t x; asm volatile("ld.relaxed.gpu.global.u32 %0, [%1];" : "=r"(x) : "l"(p) : "memory");
    if (__all_sync(~0u, x >= v)) break;
    spin_guard(it);
  }
  asm volatile("fence.acquire.gpu;" ::: "memory");
}
__device__ __forceinline__ uint32_t timer_sample() {
  uint32_t g;
  asm volatile("{.reg .b64 x; .reg .b32 h; mov.u64 x, %%globaltimer; mov.b64 {%0, h}, x;}" : "=r"(g) :: "memory");
  return (g >> 5) * 57 - clk();
}
template <int N> __device__ __forceinline__ uint32_t timer_offset() {
  const uint32_t base = timer_sample();
  int best = 0;
#pragma unroll 1
  for (int i = 0; i < N; i++) {
    const int a = timer_sample() - base, b = timer_sample() - base, c = timer_sample() - base;
    best = max(max(best, a), max(b, c));
  }
  return base + best;
}
__device__ __forceinline__ void grid_arrive(int i) {
  asm volatile("red.release.gpu.global.add.u32 [%0], %1;" :: "l"(g_gbar + i * 32), "r"(bid() ? 1u : 257u - N_CTA) : "memory");
}
__device__ __forceinline__ void grid_wait(int i, uint32_t gen) {
  int it = 0;
  while (((ld_acquire(g_gbar + i * 32) ^ gen) >> 8) == 0) spin_guard(it);
}
__device__ __forceinline__ bool elect() {
  uint32_t r; asm volatile("{.reg .pred p; elect.sync _|p, -1; selp.u32 %0, 1, 0, p;}" : "=r"(r)); return r;
}
__device__ __forceinline__ void bar_sync(int id, int cnt) { asm volatile("bar.sync %0, %1;" :: "r"(id), "r"(cnt) : "memory"); }
__device__ __forceinline__ void bar_arrive(int id, int cnt) { asm volatile("bar.arrive %0, %1;" :: "r"(id), "r"(cnt) : "memory"); }
template <int id, int cnt> __device__ __forceinline__ void bar_arrive_after(uint32_t a, uint32_t b) {
  asm volatile("{.reg .pred p; setp.ne.u32 p, %2, 0xfff12345; setp.ne.and.u32 p, %3, 0xfff12345, p; @p bar.arrive %0, %1;}" :: "n"(id), "n"(cnt), "r"(a), "r"(b) : "memory");
}
template <int id, int cnt> __device__ __forceinline__ void bar_sync_after(uint32_t a) {
  asm volatile("{.reg .pred p; setp.ne.u32 p, %2, 0xfff12345; @p bar.sync %0, %1;}" :: "n"(id), "n"(cnt), "r"(a) : "memory");
}
__device__ __forceinline__ void fence_async_smem() { asm volatile("fence.proxy.async.shared::cta;" ::: "memory"); }
__device__ __forceinline__ void fence_async_global() { asm volatile("fence.proxy.async.global;" ::: "memory"); }
__device__ __forceinline__ void mbar_init(uint32_t mb, int cnt) { asm volatile("mbarrier.init.shared::cta.b64 [%0], %1;" :: "r"(mb), "r"(cnt) : "memory"); }
__device__ __forceinline__ void mbar_arrive(uint32_t mb) { asm volatile("mbarrier.arrive.shared::cta.b64 _, [%0];" :: "r"(mb) : "memory"); }
__device__ __forceinline__ void mbar_expect(uint32_t mb, uint32_t bytes) {
  asm volatile("mbarrier.arrive.expect_tx.shared::cta.b64 _, [%0], %1;" :: "r"(mb), "r"(bytes) : "memory");
}
__device__ __forceinline__ void mbar_wait(uint32_t mb, uint32_t parity) {
  asm volatile("{.reg .pred p;\nW: mbarrier.try_wait.parity.shared::cta.b64 p, [%0], %1;\n@!p bra W;}" :: "r"(mb), "r"(parity) : "memory");
}
__device__ __forceinline__ void bulk_load(uint32_t dst, const void* src, uint32_t bytes, uint32_t mb) {
  asm volatile("cp.async.bulk.shared::cluster.global.mbarrier::complete_tx::bytes [%0], [%1], %2, [%3];" :: "r"(dst), "l"(src), "r"(bytes), "r"(mb) : "memory");
}
__device__ __forceinline__ void bulk_store(void* dst, uint32_t src, uint32_t bytes) {
  asm volatile("cp.async.bulk.global.shared::cta.bulk_group [%0], [%1], %2;" :: "l"(dst), "r"(src), "r"(bytes) : "memory");
}
__device__ __forceinline__ uint32_t mapa(uint32_t a, uint32_t rank) {
  uint32_t r; asm("mapa.shared::cluster.u32 %0, %1, %2;" : "=r"(r) : "r"(a), "r"(rank)); return r;
}
__device__ __forceinline__ void st_async4(uint32_t dst, float a, float b, float c, float d, uint32_t mb) {
  asm volatile("st.async.shared::cluster.mbarrier::complete_tx::bytes.v4.f32 [%0], {%1,%2,%3,%4}, [%5];" :: "r"(dst), "f"(a), "f"(b), "f"(c), "f"(d), "r"(mb) : "memory");
}
__device__ __forceinline__ void st_async1(uint32_t dst, uint32_t a, uint32_t mb) {
  asm volatile("st.async.shared::cluster.mbarrier::complete_tx::bytes.u32 [%0], %1, [%2];" :: "r"(dst), "r"(a), "r"(mb) : "memory");
}
__device__ __forceinline__ uint4 lds128(uint32_t a) {
  uint4 v; asm volatile("ld.shared.v4.u32 {%0,%1,%2,%3}, [%4];" : "=r"(v.x), "=r"(v.y), "=r"(v.z), "=r"(v.w) : "r"(a) : "memory"); return v;
}
__device__ __forceinline__ uint2 lds64(uint32_t a) {
  uint2 v; asm volatile("ld.shared.v2.u32 {%0,%1}, [%2];" : "=r"(v.x), "=r"(v.y) : "r"(a) : "memory"); return v;
}
__device__ __forceinline__ uint32_t lds32(uint32_t a) {
  uint32_t v; asm volatile("ld.shared.u32 %0, [%1];" : "=r"(v) : "r"(a) : "memory"); return v;
}
__device__ __forceinline__ void sts128(uint32_t a, uint4 v) {
  asm volatile("st.shared.v4.u32 [%0], {%1,%2,%3,%4};" :: "r"(a), "r"(v.x), "r"(v.y), "r"(v.z), "r"(v.w) : "memory");
}
__device__ __forceinline__ void sts32(uint32_t a, uint32_t x) { asm volatile("st.shared.u32 [%0], %1;" :: "r"(a), "r"(x) : "memory"); }
__device__ __forceinline__ void ldsm4(uint32_t& r0, uint32_t& r1, uint32_t& r2, uint32_t& r3, uint32_t a) {
  asm volatile("ldmatrix.sync.aligned.m8n8.x4.shared.b16 {%0,%1,%2,%3}, [%4];" : "=r"(r0), "=r"(r1), "=r"(r2), "=r"(r3) : "r"(a) : "memory");
}
__device__ __forceinline__ void ldsm4t(uint32_t& r0, uint32_t& r1, uint32_t& r2, uint32_t& r3, uint32_t a) {
  asm volatile("ldmatrix.sync.aligned.m8n8.x4.trans.shared.b16 {%0,%1,%2,%3}, [%4];" : "=r"(r0), "=r"(r1), "=r"(r2), "=r"(r3) : "r"(a) : "memory");
}
__device__ __forceinline__ void stsm4(uint32_t a, uint32_t r0, uint32_t r1, uint32_t r2, uint32_t r3) {
  asm volatile("stmatrix.sync.aligned.m8n8.x4.shared.b16 [%0], {%1,%2,%3,%4};" :: "r"(a), "r"(r0), "r"(r1), "r"(r2), "r"(r3) : "memory");
}
__device__ __forceinline__ uint32_t movmat(uint32_t a) {
  uint32_t d; asm volatile("movmatrix.sync.aligned.m8n8.trans.b16 %0, %1;" : "=r"(d) : "r"(a)); return d;
}
__device__ __forceinline__ void mma16(float* d, uint32_t a0, uint32_t a1, uint32_t a2, uint32_t a3, uint32_t b0, uint32_t b1) {
  asm volatile("mma.sync.aligned.m16n8k16.row.col.f32.bf16.bf16.f32 {%0,%1,%2,%3}, {%4,%5,%6,%7}, {%8,%9}, {%0,%1,%2,%3};"
    : "+f"(d[0]), "+f"(d[1]), "+f"(d[2]), "+f"(d[3]) : "r"(a0), "r"(a1), "r"(a2), "r"(a3), "r"(b0), "r"(b1));
}
__device__ __forceinline__ void mma8(float* d, uint32_t a0, uint32_t a1, uint32_t b0) {
  asm volatile("mma.sync.aligned.m16n8k8.row.col.f32.bf16.bf16.f32 {%0,%1,%2,%3}, {%4,%5}, {%6}, {%0,%1,%2,%3};"
    : "+f"(d[0]), "+f"(d[1]), "+f"(d[2]), "+f"(d[3]) : "r"(a0), "r"(a1), "r"(b0));
}
__device__ __forceinline__ float rcp(float x) { float r; asm("rcp.approx.ftz.f32 %0, %1;" : "=f"(r) : "f"(x)); return r; }
__device__ __forceinline__ float ex2(float x) { float r; asm("ex2.approx.ftz.f32 %0, %1;" : "=f"(r) : "f"(x)); return r; }

__host__ __device__ constexpr uint64_t mkdesc(uint32_t off, uint32_t lbo, uint32_t sbo, uint32_t swz) {
  return (uint64_t)((SBASE + off) >> 4) | ((uint64_t)(lbo >> 4) << 16) | ((uint64_t)(sbo >> 4) << 32) | ((uint64_t)swz << 62);
}
__host__ __device__ constexpr uint64_t desc_sw128(uint32_t off) { return mkdesc(off, 16, 1024, 1); }
__host__ __device__ constexpr uint64_t desc_n16(uint32_t off) { return mkdesc(off, 256, 128, 0); }
__host__ __device__ constexpr uint64_t desc_m(uint32_t off) { return mkdesc(off, 16, 256, 3); }

__host__ __device__ constexpr uint64_t desc_sw64(uint32_t off) { return mkdesc(off, 16, 512, 2); }

__device__ __forceinline__ void wg_fence() { asm volatile("wgmma.fence.sync.aligned;" ::: "memory"); }
__device__ __forceinline__ void wg_commit() { asm volatile("wgmma.commit_group.sync.aligned;" ::: "memory"); }
template <int N> __device__ __forceinline__ void wg_wait() { asm volatile("wgmma.wait_group.sync.aligned %0;" :: "n"(N) : "memory"); }

#define ACC8(d) "+f"(d[0]), "+f"(d[1]), "+f"(d[2]), "+f"(d[3]), "+f"(d[4]), "+f"(d[5]), "+f"(d[6]), "+f"(d[7])
#define ACC32(d) ACC8(d), ACC8((d + 8)), ACC8((d + 16)), ACC8((d + 24))
#define R8 "{%0,%1,%2,%3,%4,%5,%6,%7}"
#define R32 "{%0,%1,%2,%3,%4,%5,%6,%7,%8,%9,%10,%11,%12,%13,%14,%15,%16,%17,%18,%19,%20,%21,%22,%23,%24,%25,%26,%27,%28,%29,%30,%31}"
template <int SD> __device__ __forceinline__ void wg_rs16(float* d, const uint32_t* a, uint64_t db) {
  asm volatile("wgmma.mma_async.sync.aligned.m64n16k16.f32.bf16.bf16 " R8 ", {%8,%9,%10,%11}, %12, %13, 1, 1, 1;"
    : ACC8(d) : "r"(a[0]), "r"(a[1]), "r"(a[2]), "r"(a[3]), "l"(db), "n"(SD));
}
template <int SD> __device__ __forceinline__ void wg_ss16(float* d, uint64_t da, uint64_t db) {
  asm volatile("wgmma.mma_async.sync.aligned.m64n16k16.f32.bf16.bf16 " R8 ", %8, %9, %10, 1, 1, 1, 1;"
    : ACC8(d) : "l"(da), "l"(db), "n"(SD));
}
template <int SD, uint64_t DA, uint64_t DB> __device__ __forceinline__ void wg_ss16o(float* d, uint32_t oa, uint32_t ob) {
  asm volatile("{.reg .b32 x, y; .reg .b64 a, b; add.u32 x, %8, %10; add.u32 y, %9, %12; mov.b64 a, {x, %11}; mov.b64 b, {y, %13};\n"
               "wgmma.mma_async.sync.aligned.m64n16k16.f32.bf16.bf16 " R8 ", a, b, %14, 1, 1, 1, 1;}"
    : ACC8(d) : "r"(oa), "r"(ob), "n"((uint32_t)DA), "n"((uint32_t)(DA >> 32)), "n"((uint32_t)DB), "n"((uint32_t)(DB >> 32)), "n"(SD));
}
template <int SD> __device__ __forceinline__ void wg_rs64(float* d, const uint32_t* a, uint64_t db) {
  asm volatile("wgmma.mma_async.sync.aligned.m64n64k16.f32.bf16.bf16 " R32 ", {%32,%33,%34,%35}, %36, %37, 1, 1, 0;"
    : ACC32(d) : "r"(a[0]), "r"(a[1]), "r"(a[2]), "r"(a[3]), "l"(db), "n"(SD));
}
template <int SD> __device__ __forceinline__ void wg_ss64(float* d, uint64_t da, uint64_t db) {
  asm volatile("wgmma.mma_async.sync.aligned.m64n64k16.f32.bf16.bf16 " R32 ", %32, %33, %34, 1, 1, 1, 0;"
    : ACC32(d) : "l"(da), "l"(db), "n"(SD));
}
#define WG_RSO(NAME, SHAPE, REGS, ACC, A, TB) \
template <int SD, uint64_t DB> __device__ __forceinline__ void NAME(float* d, uint32_t a0, uint32_t a1, uint32_t a2, uint32_t a3, uint32_t ob) { \
  asm volatile("{.reg .b64 b; mov.b64 b, {" A(4) ", " A(5) "};\nwgmma.mma_async.sync.aligned." SHAPE ".f32.bf16.bf16 " REGS \
               ", {" A(0) "," A(1) "," A(2) "," A(3) "}, b, " A(6) ", 1, 1, " TB ";}" \
    : ACC(d) : "r"(a0), "r"(a1), "r"(a2), "r"(a3), "r"(ob + (uint32_t)DB), "n"((uint32_t)(DB >> 32)), "n"(SD)); \
}
#define ACC4(d) "+f"(d[0]), "+f"(d[1]), "+f"(d[2]), "+f"(d[3])
#define ACC16(d) ACC8(d), ACC8((d + 8))
#define OP4(i) OP4_##i
#define OP4_0 "%4"
#define OP4_1 "%5"
#define OP4_2 "%6"
#define OP4_3 "%7"
#define OP4_4 "%8"
#define OP4_5 "%9"
#define OP4_6 "%10"
#define OP16(i) OP16_##i
#define OP16_0 "%16"
#define OP16_1 "%17"
#define OP16_2 "%18"
#define OP16_3 "%19"
#define OP16_4 "%20"
#define OP16_5 "%21"
#define OP16_6 "%22"
#define OP32(i) OP32_##i
#define OP32_0 "%32"
#define OP32_1 "%33"
#define OP32_2 "%34"
#define OP32_3 "%35"
#define OP32_4 "%36"
#define OP32_5 "%37"
#define OP32_6 "%38"
WG_RSO(wg_rs8o, "m64n8k16", "{%0,%1,%2,%3}", ACC4, OP4, "1")
#define R16 "{%0,%1,%2,%3,%4,%5,%6,%7,%8,%9,%10,%11,%12,%13,%14,%15}"
WG_RSO(wg_rs32o, "m64n32k16", R16, ACC16, OP16, "1")
WG_RSO(wg_rs64o, "m64n64k16", R32, ACC32, OP32, "0")
WG_RSO(wg_rs32k, "m64n32k16", R16, ACC16, OP16, "0")
template <uint64_t DA, uint64_t DB> __device__ __forceinline__ void wg_ss32k(float* d, uint32_t ob) {
  asm volatile("{.reg .b64 b; mov.b64 b, {%17, %18};\nwgmma.mma_async.sync.aligned.m64n32k16.f32.bf16.bf16 " R16 ", %16, b, 1, 1, 1, 1, 0;}"
    : ACC16(d) : "l"(DA), "r"(ob + (uint32_t)DB), "n"((uint32_t)(DB >> 32)));
}
template <int N> __device__ __forceinline__ void reg_inc() { asm volatile("setmaxnreg.inc.sync.aligned.u32 %0;" :: "n"(N)); }
template <int N> __device__ __forceinline__ void reg_dec() { asm volatile("setmaxnreg.dec.sync.aligned.u32 %0;" :: "n"(N)); }

template <int KS>
__device__ __forceinline__ void load_frags(uint32_t* a, uint32_t src) {
  const int lane = threadIdx.x & 31, w = (threadIdx.x >> 5) & 3;
  const int k = ((lane >> 4) << 3) + (lane & 7), u = w * 2 + ((lane >> 3) & 1);
  const uint32_t base = src + k * 128 + ((u ^ (k & 7)) << 4);
#pragma unroll
  for (int ks = 0; ks < KS; ks++) ldsm4t(a[ks * 4], a[ks * 4 + 1], a[ks * 4 + 2], a[ks * 4 + 3], base + ks * 2048);
}

__device__ __forceinline__ uint32_t badd2(uint32_t a, uint32_t b) { uint32_t r; asm("add.rn.bf16x2 %0, %1, %2;" : "=r"(r) : "r"(a), "r"(b)); return r; }
__device__ __forceinline__ uint32_t bsub2(uint32_t a, uint32_t b) { uint32_t r; asm("sub.rn.bf16x2 %0, %1, %2;" : "=r"(r) : "r"(a), "r"(b)); return r; }
__device__ __forceinline__ uint32_t bmul2(uint32_t a, uint32_t b) { uint32_t r; asm("mul.rn.bf16x2 %0, %1, %2;" : "=r"(r) : "r"(a), "r"(b)); return r; }
__device__ __forceinline__ uint32_t bfma2(uint32_t a, uint32_t b, uint32_t c) { uint32_t r; asm("fma.rn.bf16x2 %0, %1, %2, %3;" : "=r"(r) : "r"(a), "r"(b), "r"(c)); return r; }
template <int R> __device__ __forceinline__ void layernorm9(const uint32_t* x, uint32_t* o) {
  const uint32_t ones = 0x3F803F80u;
  float a[R][3][4], q[R], s[R];
#pragma unroll
  for (int i = 0; i < 9 * R; i++) {
    float* d = a[i % R][i / R % 3];
    if (i < 3 * R) d[0] = d[1] = d[2] = d[3] = 0.f;
    mma8(d, x[i % R * 9 + i / R], ones, x[i % R * 9 + i / R]);
  }
#pragma unroll
  for (int r = 0; r < R; r++) {
    q[r] = threadIdx.x & 4 ? a[r][0][1] + a[r][1][1] + a[r][2][1] : a[r][0][0] + a[r][1][0] + a[r][2][0];
    s[r] = (a[r][0][2] + a[r][0][3]) + (a[r][1][2] + a[r][1][3]) + (a[r][2][2] + a[r][2][3]);
  }
#pragma unroll
  for (int r = 0; r < R; r++) { q[r] += __shfl_xor_sync(~0u, q[r], 4); s[r] += __shfl_xor_sync(~0u, s[r], 1); }
#pragma unroll
  for (int r = 0; r < R; r++) { q[r] += __shfl_xor_sync(~0u, q[r], 9); s[r] += __shfl_xor_sync(~0u, s[r], 2); }
#pragma unroll
  for (int r = 0; r < R; r++) q[r] = __shfl_sync(~0u, q[r], 0) + __shfl_sync(~0u, q[r], 18);
#pragma unroll
  for (int r = 0; r < R; r++) {
    const float mean = s[r] * (1.f / DM), var = fmaxf(fmaf(q[r], 1.f / DM, -mean * mean), 0.f);
    float sd;
    asm("sqrt.approx.ftz.f32 %0, %1;" : "=f"(sd) : "f"(bf_lo(pack2(bf_lo(pack2(var, 0.f)) + 1e-5f, 0.f))));
    const float inv = rcp(bf_lo(pack2(sd, 0.f)));
    const uint32_t mb = pack2(mean, mean), hi = pack2(inv, inv), lo = pack2(inv - bf_lo(hi), inv - bf_lo(hi));
#pragma unroll
    for (int i = r * 9; i < r * 9 + 9; i++) {
      const uint32_t d = bsub2(x[i], mb);
      o[i] = bfma2(d, hi, bmul2(d, lo));
    }
  }
}
__device__ __forceinline__ void store_ln_row(int layer, int tok, const uint32_t* o) {
  const int lane = threadIdx.x & 31, r = tok & 31;
  unsigned char* p = g_lnimg + (size_t)(layer * NSEG + (tok >> 5)) * (9 * 4096) + r * 128 + (((lane >> 2) ^ (r & 7)) << 4) + (lane & 3) * 4;
#pragma unroll
  for (int i = 0; i < 9; i++) *(uint32_t*)(p + i * 4096) = o[i];
}
struct Params { CUtensorMap map[11]; const bf16 *X, *K, *V, *shift, *Hk, *Dk, *mem0, *Wq, *Wk, *Wv, *Wo; bf16* out; uint32_t dly[24]; };
#define DLYS P.dly[0]
#define DLYW P.dly[1]
#define DLYK P.dly[4]
#define DLYG P.dly[5]
#define KWIN P.dly[6]
#define KMIN P.dly[7]
#define PREF0 P.dly[19]
#define PACE P.dly[20]
#define S1G P.dly[21]
#define S1DLY P.dly[22]
#define PREFH P.dly[23]
uint32_t h_dly[24] = {800, 120, 150, 160, 3500, 4220, 2750, 1300, 1585, 1670, 1760, 2090, 2210, 2310, 2880, 3000, 3160, 3310, 3460, 7000, 160, 12500, 20500, 4000};

constexpr uint32_t C_W = 0, C_M = 147456, C_KV = C_M + 18432, C_OS = C_KV + 24576, C_QM = C_KV + 32768, C_KM = C_QM + 2048,
                   C_VM = C_KM + 2048, C_OI = C_VM + 2048, C_SX = C_OI + 4096, C_KM2 = C_SX + 2560, C_VM2 = C_KM2 + 128,
                   C_KV2 = C_KM2 + 2048, C_Q = C_KV2 + 8192, C_BAR = C_Q + 8192;
constexpr uint32_t CB_FULL = C_BAR, CB_REF = C_BAR + 16, CB_SX = C_BAR + 32, CB_OX = C_BAR + 40, CB_XX = C_BAR + 48, CB_Q = C_BAR + 56, C_BAD = C_BAR + 64, W_BAR = C_BAR + 80, T_BAR = W_BAR + 24, S_GEN = C_BAR + 128, C_REF = C_BAR + 132, CB_VF = C_BAR + 144, CB_M = C_BAR + 160, CB_MV = C_BAR + 200;
constexpr uint32_t G_W = 0, G_RING = 147456, G_W2 = G_RING + 9 * 8192, G_BAR = G_W2 + 8192;
constexpr uint32_t O_W = 0, O_RING = 3 * 40960, O_ST = O_RING + 11 * 8192, O_BAR = O_ST + 16384, OB_ST = O_BAR + 64;
constexpr uint32_t F_A = 0, F_XY = 36864, F_L = F_XY + 36864, F_X = F_L + 18432, F_Y = F_L + 2 * 36864, F_BAR = C_BAR;
constexpr uint32_t SMEM_BYTES = C_BAR + 256;
static_assert(G_BAR + 256 <= SMEM_BYTES && O_BAR + 256 <= SMEM_BYTES && F_BAR + 16 <= SMEM_BYTES && SMEM_BYTES <= 232448, "smem map");
enum { B_INIT = 1, B_M, B_QK, B_S, B_V, B_O, B_X, B_WG0, B_WG1, B_WG2, B_G, B_OE, B_T, B_R };

__device__ __forceinline__ uint4 pack_partial(const float* d, uint32_t tag) {
  uint32_t x, z;
  asm("lop3.b32 %0, %2, 1, %4, 0xb8; lop3.b32 %1, %3, 1, %4, 0xb8;" : "=&r"(x), "=&r"(z) : "r"(pack2(d[0], d[1])), "r"(pack2(d[2], d[3])), "r"(tag));
  return make_uint4(x, pack2(d[4], d[5]), z, pack2(d[6], d[7]));
}
__device__ __forceinline__ void store_partial(uint4* p, const uint4& v) { st_b128(p, v.x, v.y, v.z, v.w); }
__device__ __forceinline__ void gather_reduce(const uint32_t* p, uint32_t* dst, uint32_t m0, bool shared, uint32_t tag, uint32_t lane, uint32_t sb, int n, int TS0) {
  int tries = 0;
  bool bad;
  TR(TS0);
  do {
    uint2 x[8];
#pragma unroll
    for (int i = 0; i < 8; i++)
      asm volatile("{.reg .b64 v; ld.relaxed.gpu.global.b64 v, [%2]; mov.b64 {%0, %1}, v;}" : "=r"(x[i].x), "=r"(x[i].y) : "l"(p + i * 128) : "memory");
    spin_guard(tries);
    float a = bf_lo(x[0].x), b = bf_hi(x[0].x), c = bf_lo(x[0].y), d = bf_hi(x[0].y);
    uint32_t t = x[0].x ^ tag;
#pragma unroll
    for (int i = 1; i < 8; i++) {
      a += bf_lo(x[i].x); b += bf_hi(x[i].x); c += bf_lo(x[i].y); d += bf_hi(x[i].y);
      asm("lop3.b32 %0, %0, %1, %2, 0xf6;" : "+r"(t) : "r"(x[i].x), "r"(tag));
    }
    bad = __any_sync(~0u, t & 1);
    const bool up = lane & 8;
    float u = (up ? c : a) + __shfl_xor_sync(~0u, up ? a : c, 8), v = (up ? d : b) + __shfl_xor_sync(~0u, up ? b : d, 8);
    if (shared) { u += __shfl_xor_sync(~0u, u, 4); v += __shfl_xor_sync(~0u, v, 4); }
    u += __shfl_xor_sync(~0u, u, 16);
    v += __shfl_xor_sync(~0u, v, 16);
    st_relaxed_if(dst, n < LAG && up ? m0 : pack2(u, v), !bad);
  } while (bad);
  TR(TS0 + 3); TRV(TS0 + 2, tries);
  CNT((TS0 - 16) >> 2, tries);
}

#define ATTR 80
#define SEPV 1
#define GRN 34
#define XRV 3
constexpr int XR = XRV;
__host__ __device__ constexpr int o_ks(int s) { return s & (s < 8 ? 3 : 7); }
#define OPAT 0x55555577u
__host__ __device__ constexpr bool o_reg(int s) { return (OPAT >> s) & 1; }
__host__ __device__ constexpr int o_slot(int s) { int k = 0; for (int i = 0; i < s; i++) k += o_reg(i) == o_reg(s); return k; }
__device__ __forceinline__ int g_unit(int wg) {
  const int i = bid() - N_CHAIN;
  return i < 32 ? wg * 64 + i : 2 * i - 32 + wg;
}
__device__ __forceinline__ uint32_t pinned(uint32_t v) { return __shfl_sync(~0u, v, threadIdx.x & 31); }
template <class T> __device__ __forceinline__ T* pinned(T* p) { return (T*)__shfl_sync(~0u, (unsigned long long)p, threadIdx.x & 31); }
enum { CHAIN, GROLE, OROLE };
template <int ROLE, bool SYNC> __device__ __forceinline__ void load_box(const Params& P, uint32_t sb, bool regs, int wg, int i, uint32_t mb, bool on) {
  const int b = bid();
  int map, col = 0, ks = 0, c2 = 0, c3 = 0;
  uint32_t dst = wg * 73728;
  if (ROLE == CHAIN) {
    const int k = i - 1, st = __fns(regs ? OPAT : ~OPAT, 0, i) & 31;
    dst += i ? (17 + i) * 2048 : 0;
    if (wg || i == 0) { map = wg + i; col = b * 64; c3 = !regs; }
    else if (!regs && k >= 14) { map = 6; ks = b * 4 + k - 14; }
    else { map = 6; col = 64 + (st < 8 ? (st >> 2) * 64 : (st >> 3) * 128 + (b & 1) * 64); ks = (b * 4) ^ o_ks(st); }
  } else if (ROLE == GROLE) {
    const int q = g_unit(wg);
    map = ((q >> 5) + 1) % 3;
    if (i) { map += 3; col = (q & 31) * 128 + (i - 1) * 64; ks = 34; dst = G_W2 + wg * 4096 + (i - 1) * 2048; }
    else { map += 8; c2 = (q & 31) * 2; c3 = !regs; }
  } else {
    const int o = b - N_CHAIN - N_G, ksl = o / 3;
    map = 7; col = ((o % 3) * 3 + (wg + ksl) % 3) * 64; dst = (wg * (regs ? 24 : 20) + i) * 2048;
    ks = (ksl * 11 - max(ksl - 4, 0)) * 4 + (regs ? i / 3 * 5 + i % 3 * 2 : i < 16 ? i / 2 * 5 + 1 + i % 2 * 2 : i + 24);
    c3 = (ks & 1) * 2; ks >>= 1;
  }
  if (SYNC) { col = pinned(col); ks = pinned(ks); bar_sync(B_WG0 + wg, 256); }
  if (on) asm volatile("cp.async.bulk.tensor.5d.shared::cluster.global.tile.mbarrier::complete_tx::bytes [%0], [%1, {%2, %3, %4, %5, %6}], [%7];"
               :: "r"(sb + dst), "l"(&P.map[map]), "r"(col), "r"(0), "r"(c2), "r"(c3), "r"(ks), "r"(mb) : "memory");
}
template <int ROLE, bool SYNC = false> __device__ __forceinline__ void load_wg(const Params& P, uint32_t sb, bool regs, int wg, int quarter) {
  const int i = (threadIdx.x & 31) * 4 + quarter;
  const int n = ROLE == CHAIN ? 36 : ROLE == GROLE ? (regs ? 38 : 36) : regs ? 24 : bid() < N_CHAIN + N_G + 12 ? 20 : 16;
  const bool split = SYNC && wg == 0;
  const uint32_t mb = split && i ? sb + T_BAR : sb + W_BAR + wg * 8;
  load_box<ROLE, SYNC>(P, sb, regs, wg, i, mb, i < (ROLE == CHAIN ? (wg ? 2 : 19) : ROLE == GROLE ? n - 35 : n));
  if (i <= split) mbar_expect(mb, n * (split ? 1024 : 2048));
  __syncwarp();
}
__device__ __forceinline__ uint32_t near_half(uint32_t blk, uint32_t reader) {
  return __ldcg(g_near + (blk >> 3)) ^ (~blk & 1) ^ __ldcg(g_side + (blk >> 3)) ^ __ldcg(g_side + reader);
}

__device__ __forceinline__ uint32_t opaque_tid() { uint32_t t; asm volatile("mov.u32 %0, %%tid.x;" : "=r"(t)); return t; }
__device__ __forceinline__ void m_fetch(uint32_t sb, uint32_t src, uint32_t b, uint32_t mb) {
  bulk_load(sb + C_M + (b ? b * 4096 - 2048 : 0), (const unsigned char*)g_mimg + ((src ^ ((b & 1) * 4096)) + b * 8192), b ? 4096 : 2048, mb);
}
__device__ __forceinline__ uint32_t m_probe(uint32_t lane) { return lane * 32 + (lane & 4) * 4 + (lane >> 3) * 4; }
__device__ __forceinline__ uint32_t m_max(uint32_t a, uint32_t b) {
  return max(max(lds32(a), lds32(a + 1024)), max(lds32(b), lds32(b + 1024)));
}
template <int S0, int N> __device__ __forceinline__ void o_steps(float* d, const uint32_t* a) {
  constexpr int SD = o_ks(S0) != 0;
  if constexpr (o_reg(S0)) wg_rs16<SD>(d, a + (18 + o_slot(S0)) * 4, desc_n16(C_OI + o_ks(S0) * 512));
  else wg_ss16<SD>(d, desc_sw128(C_W + (18 + o_slot(S0)) * 2048), desc_n16(C_OI + o_ks(S0) * 512));
  if constexpr (N > 1) o_steps<S0 + 1, N - 1>(d, a);
}
template <int BASE, int KS, int N> __device__ __forceinline__ void m_steps(float* d, const uint32_t* a, uint32_t oa) {
  wg_rs16<KS != 0>(d, a + (BASE + KS / 2) * 4, desc_m(C_M + KS * 512));
  if constexpr (KS >= 36 - 2 * XR) wg_rs16<1>(d, a + (18 + XR + KS / 2) * 4, desc_m(C_M + KS * 512 + 512));
  else wg_ss16o<1, desc_sw128(C_W + (BASE + KS / 2) * 2048), desc_m(C_M + KS * 512 + 512)>(d, oa, 0);
  if constexpr (N > 2) m_steps<BASE, KS + 2, N - 2>(d, a, oa);
}

constexpr uint32_t VPAT = 0x15bbd249u;
template <int I, int R, int S> __device__ __forceinline__ void v_steps(float* d, const uint32_t* a) {
  constexpr bool reg = (VPAT >> I) & 1;
  if constexpr (reg) wg_rs16<1>(d, a + (18 + R) * 4, desc_m(C_M + R * 1024));
  else wg_ss16<1>(d, desc_sw128(C_W + (54 + S) * 2048), desc_m(C_M + S * 1024 + 512));
  if constexpr (I < 31) v_steps<I + 1, R + reg, S + !reg>(d, a);
  else static_assert(R + reg == 18, "pattern");
}

__device__ __forceinline__ void chain_proj(const Params& P, uint32_t sb) {
  const uint32_t c = chain_id(), h = c >> 1, j = c & 1, wid = __shfl_sync(~0u, threadIdx.x >> 5, 0), wg = wid >> 2, w = wid & 3;
  const uint32_t t = threadIdx.x & 127, lane = pinned(t & 31), mine = pinned(sb + t * 16), rb = mapa(sb, j ^ 1);
  const uint32_t theirs = pinned(rb + C_KM2 + w * 512 + lane * 4), oa = wg * 4608;
  uint32_t a[144 + 4 * XR];
  mbar_wait(sb + W_BAR + wg * 8, 0);
  if (threadIdx.x == 0) TS(23);
  load_frags<36>(a, sb + C_W + wg * 73728);
  fence_async_smem();
  bar_arrive(B_WG0 + wg, 256);
  if (threadIdx.x == 0) TS(24);
  bar_sync(B_WG2, 384);
  const uint32_t round = min(w, 2u) + (wg ? 0 : 3), gdly = P.dly[8 + round], ps = t >> 2, pf = j * 16 + (ps >> 1);
  uint4* const dsts = pinned(g_xb + (ps * 4096 + near_half(ps * 8, ps * 2) * 256 + c * 4 + (t & 3)));
  uint4* const dstf = pinned(g_xb + (pf * 4096 + 512 + near_half(pf * 8 + 1, pf * 2) * 256 + h * 8 + (t & 7)));
  const uint32_t* const gsrc = (const uint32_t*)g_xb + (h * 16384 + min(w, 2u) * 4096 + near_half(h * 8 + !wg, h * 2) * 1024 +
                               (wg ? lane * 4 + j * 2 : 2048 + (lane & 24) * 4 + j * 16 + (lane & 7) * 2));
  uint32_t* gdst = g_mimg + (16384 + (lane >> 4) * 1024 +
                   (wg ? (round ? 1536 + round * 512 : 0) + c * 8 + (((lane >> 1) ^ c) & 4) + (lane & 3)
                       : (round - 1) * 2048 + c * 16 + (lane & 1) * 8 + (((lane >> 1) ^ (c * 2)) & 4) + ((lane >> 1) & 3)));
  const uint32_t m0 = __ldcg(gdst - 16384);
  mbar_wait(sb + W_BAR + wg * 8, 1);
  load_frags<XR>(a + 144, sb + C_W + wg * 73728 + (18 - XR) * 2048);
  bar_sync(B_INIT, 256);
  if ((threadIdx.x & 127) == 0) TS(4);

  uint32_t ring = 1;
#pragma unroll 1
  for (int n = 0; n < STEPS; n++) {
    float d[8], e[8];
    if (n + 1 == STEPS && !wg) { bar_arrive(B_QK, 416); break; }
#pragma unroll
    for (int i = 0; i < 8; i++) e[i] = 0.f;
    uint32_t redo = n + 1;
#pragma unroll 1
    do {
      mbar_wait(sb + CB_M, n & 1);
      wg_fence();
      m_steps<0, 0, 4>(d, a, oa);
      wg_commit();
      if (wg) { wg_fence(); m_steps<18, 0, 4>(e, a, 4608); wg_commit(); }
      if (wid == 0) TR(8);
      mbar_wait(sb + CB_M + 8, n & 1);
      wg_fence();
      m_steps<0, 4, 8>(d, a, oa);
      wg_commit();
      mbar_wait(sb + CB_MV, n & 1);
      asm volatile("{.reg .pred p; .reg .u32 t; ld.shared.u32 t, [%1]; setp.eq.u32 p, t, %0; selp.u32 %0, -1, 0, p;}" : "+r"(redo) : "r"(sb + C_BAD) : "memory");
    } while (redo);
    if (SEPV) mbar_wait(sb + CB_MV + 8, n & 1);
    wg_fence();
    m_steps<0, 12, 8>(d, a, oa);
    wg_commit();
    mbar_wait(sb + CB_MV + 16, n & 1);
    wg_fence();
    m_steps<0, 20, 8>(d, a, oa);
    wg_commit();
    mbar_wait(sb + CB_MV + 24, n & 1);
    wg_fence();
    m_steps<0, 28, 8>(d, a, oa);
    wg_commit();
    wg_wait<0>();
    if (w == 0) TR(6 + wg);
    const uint32_t f0 = pack2(d[0], d[1]), f1 = pack2(d[4], d[5]), f2 = pack2(d[2], d[3]), f3 = pack2(d[6], d[7]);
    stsm4(mine + C_QM + wg * 2048, f0, f1, f2, f3);
    bar_arrive(B_QK, 416);
    const uint32_t tag = (n & 1) ^ 1;
    if (n == 0) mbar_wait(sb + T_BAR, 0);
    if (wg) {
      if (n + 1 < STEPS) bar_sync(B_S, 256);
      wg_fence();
      v_steps<0, 2, 2>(e, a);
      wg_commit();
      const uint32_t k0 = j ? f0 : f1, k1 = j ? f2 : f3;
      mbar_wait(sb + CB_SX, n & 1);
      wg_wait<0>();
      if (w == 0) TR(11);
      const uint32_t v0 = pack2(e[0], e[1]), v1 = pack2(e[4], e[5]), v2 = pack2(e[2], e[3]), v3 = pack2(e[6], e[7]);
      stsm4(mine + C_VM, v0, v1, v2, v3);
      bar_arrive(B_V, 256);
      st_async1(theirs, k0, rb + CB_XX);
      st_async1(theirs + 256, k1, rb + CB_XX);
      st_async1(theirs + 128, j ? v0 : v1, rb + CB_XX);
      st_async1(theirs + 384, j ? v2 : v3, rb + CB_XX);
      if (n + 1 == STEPS) break;
      bar_sync(B_O, 256);
      fence_async_smem();
      wg_fence();
#pragma unroll
      for (int ks = 0; ks < 4; ks++) {
        if (ks == 0) wg_ss16<0>(d, desc_sw128(C_W + 32 * 2048), desc_n16(C_OI));
        else wg_ss16<1>(d, desc_sw128(C_W + (32 + ks) * 2048), desc_n16(C_OI + ks * 512));
      }
      wg_commit();
      bar_arrive(B_X, 256);
      if (w == 0) TR(0);
      wg_wait<0>();
      store_partial(dsts, pack_partial(d, tag));
      bar_arrive(B_M, 160);
      if (w == 0) TR(1);
    } else {
      bar_sync(B_X, 256);
      wg_fence();
      o_steps<0, 4>(d, a);
      wg_commit();
      o_steps<4, 4>(e, a);
      wg_commit();
      wg_wait<1>();
      store_partial(dsts + 1024, pack_partial(d, tag));
      if (w == 0) TR(2);
      wg_wait<0>();
      store_partial(dsts + 2048, pack_partial(e, tag));
      if (w == 0) TR(3);
      wg_fence();
      o_steps<8, 4>(d, a);
      wg_commit();
      bar_sync(B_T, 256);
      if (w == 0) { TRV(61, 0); TR(12); }
      wg_fence();
      o_steps<12, 4>(d, a);
      wg_commit();
      o_steps<16, 8>(e, a);
      wg_commit();
      wg_wait<1>();
      store_partial(dstf, pack_partial(d, tag));
      if (w == 0) TR(4);
      wg_fence();
      o_steps<24, 8>(d, a);
      wg_commit();
      wg_wait<1>();
      store_partial(dstf + 1024, pack_partial(e, tag));
      bar_arrive(B_OE, 256);
      if (w == 0) TR(5);
      wg_wait<0>();
      store_partial(dstf + 2048, pack_partial(d, tag));
      if (w == 0) TR(15);
    }
    if (w < 3) {
      mbar_wait(sb + CB_REF, n & 1);
      wait_until(lds32(sb + C_REF), gdly);
      gather_reduce(gsrc, gdst, m0, wg, tag, lane, sb, n, 16 + round * 4);
      if (++ring == MRING) { ring = 0; gdst -= MRING * 16384; }
      gdst += 16384;
    }
  }
}

template <int KS> __device__ __forceinline__ void x_scores(float* s, float* sm, const uint4* q, uint32_t ok, uint32_t om) {
  wg_rs32o<1, desc_sw64(C_KV + KS * 1024)>(s, q[KS].x, q[KS].y, q[KS].z, q[KS].w, ok);
  wg_rs8o<1, desc_n16(C_KM + KS * 512)>(sm, q[KS].x, q[KS].y, q[KS].z, q[KS].w, om);
  if constexpr (KS < 3) x_scores<KS + 1>(s, sm, q, ok, om);
}

__device__ __forceinline__ void chain_attn(const Params& P, uint32_t sb) {
  const int c = chain_id(), j = c & 1;
  const int tid = threadIdx.x, lane = tid & 31, w = __shfl_sync(~0u, (tid >> 5) & 3, 0);
  const int l = w >> 1, u = w & 1;
  const uint32_t rb = mapa(sb, j ^ 1);
  const float sc = 0.08838834764831845f * 1.4426950408889634f;
  const uint32_t ones = 0x3F803F80u, sx = C_SX + l * 1280;
  const uint32_t km_off = C_KM + (lane >> 3) * 256 + l * 128 + (lane & 7) * 16;
  const uint32_t qm_off = C_QM + (lane >> 4) * 256 + l * 128 + (lane & 7) * 16;
  const uint32_t kv_off = C_KV + l * 4096 + (lane & 15) * 64 + (((lane >> 4) ^ (u * 2) ^ ((lane >> 1) & 3)) << 4);

  load_wg<CHAIN, true>(P, sb, false, 1, w);
  if (lane == 0) mbar_arrive(sb + CB_M);
#pragma unroll 1
  for (int n = 0; n < STEPS; n++) {
    const uint32_t kvb = sb + kv_off + (n & 1) * 16384;
    mbar_wait(sb + CB_FULL + (n & 1) * 8, (n >> 1) & 1);
    if (n < 3 && tid == 256) TS(n ? 20 + n : 5);
    __syncwarp();
    {
      uint32_t km[8];
      uint4 kx[8];
#pragma unroll
      for (int i = 0; i < 8; i++) ldsm4t(kx[i].x, kx[i].y, kx[i].z, kx[i].w, (kvb ^ ((i & 1) * 32)) + (i >> 1) * 1024);
      mbar_wait(sb + CB_VF, n & 1);
      if (w == 1) TRD(60, kx[7].x);
      bar_sync(B_QK, 416);
      if (n + 1 == STEPS) {
        st_async4(rb + sx + u * 512 + lane * 16, 0.f, 0.f, 0.f, 0.f, rb + CB_SX);
        st_async1(rb + sx + 1024 + u * 128 + lane * 4, 0, rb + CB_SX);
        bar_sync(B_V, 256);
      } else {
      uint32_t qm[16];
#pragma unroll
      for (int ks = 0; ks < 4; ks++) ldsm4t(qm[4 * ks], qm[4 * ks + 1], qm[4 * ks + 2], qm[4 * ks + 3], sb + qm_off + ks * 512);
      ldsm4t(km[0], km[1], km[2], km[3], sb + km_off);
      ldsm4t(km[4], km[5], km[6], km[7], sb + km_off + 1024);
      float s[5][4];
      uint4 vx[4];
#pragma unroll
      for (int i = 0; i < 5; i++) { s[i][0] = s[i][1] = s[i][2] = s[i][3] = 0.f; }
#pragma unroll
      for (int ks = 0; ks < 4; ks++) {
        const uint32_t* q = qm + 4 * ks;
        if (ks == 1 || ks == 2) {
#pragma unroll
          for (int i = 2 * ks - 2; i < 2 * ks; i++) ldsm4(vx[i].x, vx[i].y, vx[i].z, vx[i].w, ((sb + kv_off) ^ ((i & 1) * 32)) + 8192 + (2 * u + (i >> 1)) * 1024);
        }
        mma16(s[1], q[0], q[1], q[2], q[3], kx[2 * ks].x, kx[2 * ks].y);
        mma16(s[2], q[0], q[1], q[2], q[3], kx[2 * ks].z, kx[2 * ks].w);
        mma16(s[0], q[0], q[1], q[2], q[3], km[2 * ks], km[2 * ks + 1]);
        mma16(s[3], q[0], q[1], q[2], q[3], kx[2 * ks + 1].x, kx[2 * ks + 1].y);
        mma16(s[4], q[0], q[1], q[2], q[3], kx[2 * ks + 1].z, kx[2 * ks + 1].w);
      }
      st_async4(rb + sx + u * 512 + lane * 16, s[1][0], s[1][1], s[2][0], s[2][1], rb + CB_SX);
      st_async1(rb + sx + 1024 + u * 128 + lane * 4, __float_as_uint(u ? s[0][1] : s[0][0]), rb + CB_SX);
      bar_arrive_after<B_S, 256>(__float_as_uint(s[3][0]), __float_as_uint(s[4][0]));
      mbar_wait(sb + CB_SX, n & 1);
      const uint4 p0 = lds128(sb + sx + u * 512 + lane * 16), p1 = lds128(sb + sx + (u ^ 1) * 512 + lane * 16);
      const uint2 p2 = make_uint2(lds32(sb + sx + 1024 + lane * 4), lds32(sb + sx + 1152 + lane * 4));
      float t[10] = {s[0][0] + __uint_as_float(p2.x), s[0][1] + __uint_as_float(p2.y),
                     s[1][0] + __uint_as_float(p0.x), s[1][1] + __uint_as_float(p0.y),
                     s[2][0] + __uint_as_float(p0.z), s[2][1] + __uint_as_float(p0.w),
                     s[3][0] + __uint_as_float(p1.x), s[3][1] + __uint_as_float(p1.y),
                     s[4][0] + __uint_as_float(p1.z), s[4][1] + __uint_as_float(p1.w)};
      float mx = fmaxf(fmaxf(fmaxf(fmaxf(t[2], t[3]), fmaxf(t[4], t[5])), fmaxf(fmaxf(t[6], t[7]), fmaxf(t[8], t[9]))), fmaxf(t[0], t[1]));
      mx = fmaxf(fmaxf(mx, __shfl_xor_sync(~0u, mx, 1)), fmaxf(__shfl_xor_sync(~0u, mx, 2), __shfl_xor_sync(~0u, mx, 3)));
      const float ms = -mx * sc;
#pragma unroll
      for (int i = 0; i < 10; i++) t[i] = ex2(fmaf(t[i], sc, ms));
      uint32_t p[5];
#pragma unroll
      for (int i = 0; i < 5; i++) p[i] = pack2(t[2 * i], t[2 * i + 1]);
      p[1] |= (p[0] & p[3] & p[4]) & 0x80008000u;
      float o[2][4], z[4] = {0.f, 0.f, 0.f, 0.f};
      mma16(z, ones, ones, ones, ones, p[1], p[2]);
#pragma unroll
      for (int i = 0; i < 2; i++) {
        o[i][0] = o[i][1] = o[i][2] = o[i][3] = 0.f;
        mma16(o[i], vx[2 * i].x, vx[2 * i].y, vx[2 * i].z, vx[2 * i].w, p[1], p[2]);
      }
      mma16(z, ones, ones, ones, ones, p[3], p[4]);
#pragma unroll
      for (int i = 0; i < 2; i++) mma16(o[i], vx[2 * i + 1].x, vx[2 * i + 1].y, vx[2 * i + 1].z, vx[2 * i + 1].w, p[3], p[4]);
      mma8(z, ones, ones, p[0]);
      bar_sync_after<B_V, 256>(p[1]);
      ldsm4(km[0], km[1], km[2], km[3], sb + km_off + (C_VM - C_KM) + u * 1024);
      mma8(o[0], km[0], km[1], p[0]);
      mma8(o[1], km[2], km[3], p[0]);
      const float i0 = rcp(z[0]), i1 = rcp(z[1]);
      const uint32_t oo = C_OI + u * 1024 + l * 128 + lane * 4;
      uint32_t ow[4];
#pragma unroll
      for (int i = 0; i < 2; i++) { ow[2 * i] = pack2(o[i][0] * i0, o[i][1] * i1); ow[2 * i + 1] = pack2(o[i][2] * i0, o[i][3] * i1); }
      stsm4(sb + C_OI + u * 1024 + l * 128 + (lane >> 3) * 256 + (lane & 7) * 16, ow[0], ow[1], ow[2], ow[3]);
      bar_arrive(B_O, 256);
#pragma unroll
      for (int i = 0; i < 4; i++) st_async1(rb + oo + 2048 + i * 256, ow[i], rb + CB_OX);
      }
    }
    {
      const uint32_t lane = opaque_tid() & 31, own = ((n & 1) * 16384 + j * 4096) >> 4;
      float s[16], sm[4];
#pragma unroll
      for (int i = 0; i < 16; i++) s[i] = sm[i & 3] = 0.f;
      {
        uint4 q[4];
        mbar_wait(sb + CB_Q, n & 1);
#pragma unroll
        for (int ks = 0; ks < 4; ks++)
          ldsm4t(q[ks].x, q[ks].y, q[ks].z, q[ks].w, sb + C_Q + (lane & 8) * 512 + ks * 1024 + (lane & 16) * 32 + (lane & 7) * 64 + (((w ^ (lane >> 1)) & 3) << 4));
        mbar_wait(sb + CB_XX, n & 1);
        if (n + 1 < STEPS) mbar_wait(sb + CB_OX, n & 1);
        fence_async_smem();
        if (n + 1 < STEPS) { bar_arrive(B_T, 256); bar_sync(B_OE, 256); }
        if (w == 1) { TRV(61, 0); TR(9); }
#pragma unroll 1
        for (uint32_t hf = 0; hf < 2; hf++) {
          wg_fence();
          x_scores<0>(s, sm, q, hf ? (C_KV2 - C_KV) >> 4 : own, hf ? (C_KM2 - C_KM) >> 4 : j * 8);
          wg_commit();
          wg_wait<0>();
#pragma unroll
          for (int ks = 0; ks < 4; ks++) asm volatile("mov.b32 %0, %1; mov.b32 %2, %3;" : "+r"(q[ks].x), "+r"(q[ks].y), "+r"(q[ks].z), "+r"(q[ks].w));
        }
      }
      const float neg = -1e9f * 11.313708498984761f;
      const int tok = (lane & 24) + 2 * w + ((lane >> 2) & 1), lim = tok - 8 * (int)(lane & 3);
      float t[10] = {sm[0], sm[1]};
#pragma unroll
      for (int i = 0; i < 8; i++) t[2 + i] = i > lim ? neg : s[(i >> 1) * 4 + (i & 1)];
      float mx = fmaxf(fmaxf(fmaxf(fmaxf(t[2], t[3]), fmaxf(t[4], t[5])), fmaxf(fmaxf(t[6], t[7]), fmaxf(t[8], t[9]))), fmaxf(t[0], t[1]));
      mx = fmaxf(fmaxf(mx, __shfl_xor_sync(~0u, mx, 1)), fmaxf(__shfl_xor_sync(~0u, mx, 2), __shfl_xor_sync(~0u, mx, 3)));
      const float ms = -mx * sc;
#pragma unroll
      for (int i = 0; i < 10; i++) t[i] = ex2(fmaf(t[i], sc, ms));
      uint32_t p[5];
#pragma unroll
      for (int i = 0; i < 5; i++) p[i] = pack2(t[2 * i], t[2 * i + 1]);
      float z = ((t[0] + t[1]) + (t[2] + t[3])) + ((t[4] + t[5]) + (t[6] + t[7])) + (t[8] + t[9]);
      const uint32_t row = sb + C_OS + tok * 128 + (((lane & 3) ^ (tok & 7)) << 4);
#pragma unroll 1
      for (uint32_t hf = 0; hf < 2; hf++) {
        float o[32];
        const uint32_t vo = hf ? (C_KV2 + 4096 - C_KV - 8192) >> 4 : j * 256;
        wg_fence();
        wg_rs64o<0, desc_sw64(C_KV + 8192)>(o, p[1], p[1], p[2], p[2], vo);
        wg_rs64o<1, desc_sw64(C_KV + 8192 + 32)>(o, p[3], p[3], p[4], p[4], vo);
        wg_rs64o<1, mkdesc(C_VM, 128, 256, 0)>(o, p[0], p[0], 0, 0, hf ? (C_VM2 - C_VM) >> 4 : j * 8);
        wg_commit();
        if (hf) {
          if (elect()) mbar_arrive(sb + CB_M);
        } else {
          z = rcp((z + __shfl_xor_sync(~0u, z, 1)) + (__shfl_xor_sync(~0u, z, 2) + __shfl_xor_sync(~0u, z, 3)));
        }
        wg_wait<0>();
#pragma unroll
        for (int qq = 0; qq < 2; qq++) {
          const float* r = o + 16 * qq;
          sts128((row ^ (qq * 64)) + hf * 4096,
                 make_uint4(pack2(r[0] * z, r[1] * z), pack2(r[4] * z, r[5] * z), pack2(r[8] * z, r[9] * z), pack2(r[12] * z, r[13] * z)));
        }
      }
      bar_arrive(B_G, 160);
      if (n + 1 < STEPS) bar_arrive(B_R, 160);
      if (w == 1) TR(10);
    }
  }
  if ((threadIdx.x & 127) == 0) TS(6);
}

__device__ __forceinline__ void chain_aux(const Params& P, uint32_t sb) {
  const uint32_t c = chain_id(), j = c & 1, lane = threadIdx.x & 31, w = __shfl_sync(~0u, (threadIdx.x >> 5) & 3, 0);
  load_wg<CHAIN, true>(P, sb, false, 0, w);
  if (threadIdx.x == 384) TS(25);
  if (threadIdx.x == 384) grid_wait(1, lds32(sb + S_GEN));
  bar_sync(B_WG2, 384);
  if (threadIdx.x == 384) TS(13);
  if (w == 0) {
    const uint32_t* fg = g_fl + FL_G + near_half(XB_F, c) * 1024 + (c >> 1) * 8;
#pragma unroll 1
    for (int n = 0; n < STEPS; n++) {
      const unsigned char* blk = g_qkv + (uint32_t)((n % QRING) * (N_CHAIN * 24576));
      const uint32_t t1 = clk(), kb = sb + CB_FULL + (n & 1) * 8, kv = sb + C_KV + (n & 1) * 16384;
      uint32_t t0 = t1 - 100000, x = 0;
      if (n > 0) {
        wait_until(t1, KMIN);
        do asm volatile("ld.relaxed.gpu.global.u32 %0, [%1];" : "=r"(x) : "l"(fg) : "memory"); while (x <= n && clk() - t1 < KWIN);
        if (x > n) {
          asm volatile("fence.acquire.gpu;" ::: "memory");
          fence_async_global();
          if (elect()) { mbar_expect(kb, 8192); bulk_load(kv, blk + c * 24576, 8192, kb); }
        }
        T3(0); CNT(12, 1 + (x <= n));
        mbar_wait(sb + CB_REF, (n - 1) & 1);
        t0 = lds32(sb + C_REF);
        wait_until(t0, DLYK - 500);
      }
      wait_flags(fg + min(lane, 2u) * 256, n + 1);
      T3(2);
      fence_async_global();
      if (n > 0) bar_sync(B_R, 160);
      if (lane < 3) mbar_expect(sb + CB_SX + lane * 8, lane ? 2048 : 2560);
      __syncwarp();
      wait_until(t0, DLYK);
      if (elect()) {
        if (x <= n) { mbar_expect(kb, 8192); bulk_load(kv, blk + c * 24576, 8192, kb); }
        mbar_expect(sb + CB_VF, 8192);
        bulk_load(sb + C_KV + 8192, blk + (c * 24576 + 8192), 8192, sb + CB_VF);
        mbar_expect(sb + CB_Q, 16384);
        bulk_load(sb + C_Q, blk + (c * 24576 + 16384), 8192, sb + CB_Q);
        bulk_load(sb + C_KV2, blk + ((c ^ 1) * 24576 + j * 4096), 4096, sb + CB_Q);
        bulk_load(sb + C_KV2 + 4096, blk + ((c ^ 1) * 24576 + 8192 + j * 4096), 4096, sb + CB_Q);
      }
      T3(1);
      T3(3);
    }
  } else {
    const uint32_t near = __ballot_sync(~0u, near_half(XB_M + min(lane, MRING - 1u) * 8, c));
    uint32_t ring = 0;
    if (w > 1) {
      const uint32_t odd = w & 1, chk = pinned(sb + C_M + odd * 2048 + m_probe(lane)), again = sb + CB_MV + 32 + odd * 8;
      const bool one = elect();
      uint32_t mph = 0;
#pragma unroll 1
      for (int n = 0; n <= STEPS; n++) {
#pragma unroll
        for (int k = 0; k < 3; k++) {
          if (n == STEPS || (k == 2 && odd)) break;
          const uint32_t b = 2 * k + odd, at = chk + (k ? k * 8192 - 2048 + odd * 2048 : 0);
          uint32_t mb = sb + CB_M + b * 8, ph = n & 1;
          int it = 1;
          while (true) {
            mbar_wait(mb, ph);
            const bool bad = __any_sync(~0u, m_max(at, b ? at + 2048 : at) == SENT);
            if (one && !bad) mbar_arrive(sb + CB_MV + (b > 2 - SEPV ? b * 8 - 8 : 0));
            if (!bad) break;
            mb = again; ph = mph; mph ^= 1;
            if (one) {
              if (k == 0) sts32(sb + C_BAD, n + 1);
              mbar_expect(mb, b ? 4096 : 2048);
              m_fetch(sb, ring * 65536 + ((near >> ring) & 1) * 4096, b, mb);
            }
            __syncwarp();
            spin_guard(it);
          }
          TR(41 + b * 4); CNT(6 + b, it);
        }
        ring = ring + 1 == MRING ? 0 : ring + 1;
        if (!odd) {
          if (n < STEPS) { TRSYNC(); TRDUMP(n - 2); }
        } else {
          unsigned char* o = g_oimg + (uint32_t)(((n - 1) & (RING - 1)) * (N_CHAIN * 8192) + j * 4096);
          if (n > 0) bar_sync(B_G, 160);
          fence_async_smem();
          if (one) {
            if (n > 0) {
              bulk_store(o + c * 8192, sb + C_OS, 4096);
              bulk_store(o + (c ^ 1) * 8192, sb + C_OS + 4096, 4096);
              asm volatile("cp.async.bulk.commit_group;\ncp.async.bulk.wait_group.read 0;" ::: "memory");
              { const int n_ = n - 1; { const int n = n_; T3(4); (void)n; } }
            }
            mbar_arrive(sb + CB_Q);
            if (n > 0) {
              bulk_done_inc(g_fl + FL_O + c);
              { const int n_ = n - 1; { const int n = n_; T3(5); (void)n; } }
            }
          }
          __syncwarp();
        }
      }
    } else {
      const uint32_t* ts = g_fl + FL_SYNC + near_half(XB_F + 1, c) * 1024 + lane * 2;
      uint32_t t0 = clk() - 100000, last = 0;
      int lag = 0;
#pragma unroll 1
      for (int n = 0; n < STEPS; n++) {
        const uint32_t src = ring * 65536 + ((near >> ring) & 1) * 4096;
        if (lane < 5) mbar_expect(sb + CB_M + lane * 8, lane ? 4096 : 2048);
        __syncwarp();
        if (elect()) {
#pragma unroll
          for (int b = 0; b < 5; b++) {
            wait_until(t0, P.dly[14 + b]);
            m_fetch(sb, src, b, sb + CB_M + b * 8);
            TR(40 + b * 4);
          }
        }
        __syncwarp();
        ring = ring + 1 == MRING ? 0 : ring + 1;
        uint32_t va, vb;
        const uint32_t off = timer_offset<4>(), tag = (uint32_t)(n + 1) << 28;
        if (n > 1) lag += (int)(off - last) - (lag >> 2);
        last = off;
        const uint32_t mine = min(max((lag >> 3) + 256, 0), 511);
        bar_sync(B_QK, 416);
        if (n + 1 == STEPS) break;
        sts32(sb + C_REF + 4, 0);
        const uint32_t c0 = clk(), stamp = c0 + off;
        st_relaxed_if(g_fl + FL_SYNC + lane * 1024 + c, tag | (mine << 19) | (stamp & 0x7FFFF), lane < 2);
        TR(13);
        wait_until(c0, DLYS);
        int it = 0;
        do {
          asm volatile("ld.relaxed.gpu.global.v2.u32 {%0,%1}, [%2];" : "=r"(va), "=r"(vb) : "l"(ts) : "memory");
          spin_guard(it);
        } while (__any_sync(~0u, ((va ^ tag) | (vb ^ tag)) >> 28));
        const int late = __reduce_max_sync(~0u, max((int)((va - stamp) << 13), (int)((vb - stamp) << 13))) >> 13;
        const uint32_t fast = min(((__reduce_max_sync(~0u, max(va, vb)) >> 19) & 511) - mine, 100u);
        t0 = c0 + min((uint32_t)late, clk() - c0);
        if (elect()) {
          sts32(sb + C_REF, t0 + (fast * 9 >> 3));
          mbar_arrive(sb + CB_REF);
        }
        st_relaxed_if(g_fl + FL_TICK + lane * 1024, (uint32_t)(n + 1) << 24 | ((t0 + off) & 0xFFFFFF), c == 0 && lane < 2);
        t0 += fast * 13 >> 3;
        TRV(59, fast);
        TR(14); CNT(11, it);
        bar_sync(B_M, 160);
      }
    }
  }
}

template <int WG>
__device__ __forceinline__ void g_math(const Params& P, uint32_t sb) {
  const int q = g_unit(WG);
  const int lane = threadIdx.x & 31, w = (threadIdx.x >> 5) & 3;
  uint32_t a[GRN * 4];
  {
    const uint32_t stage = sb + G_W + WG * 73728;
    mbar_wait(sb + W_BAR + WG * 8, 0);
    if (threadIdx.x == 0) TS(23);
    load_frags<GRN>(a, stage);
    fence_async_smem();
    bar_sync(B_WG0 + WG, 128);
    if (threadIdx.x == 0) TS(24);
    load_wg<GROLE>(P, sb, false, WG, w);
    if (threadIdx.x == 0) TS(25);
    mbar_wait(sb + W_BAR + WG * 8, 1);
  }
  if ((threadIdx.x & 127) == 0) TS(4);
  const uint32_t off0 = (q & 31) * 49152 + (q >> 5) * 8192 + w * 1024 + (lane >> 2) * 64 + (((lane ^ (lane >> 3)) & 3) << 4);
  const uint32_t isq = q >> 6;
#pragma unroll 1
  for (int n = 0; n < STEPS; n++) {
    float d0[32], d1[32];
    if (WG == 0 && n >= LOCK0) bar_sync(B_OE, 160);
    if (n > 0) bar_sync(B_V + WG, 256);
#pragma unroll
    for (int ch = 0; ch < 9; ch++) {
      mbar_wait(sb + G_BAR + ch * 8, n & 1);
      if (ch == 0) { if ((threadIdx.x & 127) == 0) T3(5 + WG * 3); __syncwarp(); }
      if (ch == 4) { if ((threadIdx.x & 127) == 0) T3(6 + WG * 3); __syncwarp(); }
      if (ch == 8 && (WG == 0 ? n > 0 : n + 1 < STEPS)) bar_arrive(B_V + (WG ^ 1), 256);
      wg_fence();
#pragma unroll
      for (int kk = 0; kk < 4; kk++) {
        const int i = ch * 4 + kk;
        float* d = i & 1 ? d1 : d0;
        const uint64_t db = desc_sw128(G_RING + ch * 8192 + (kk & 2) * 32);
        if (i < 2) wg_rs64<0>(d, a + i * 4, db);
        else if (i < GRN) wg_rs64<1>(d, a + i * 4, db);
        else wg_ss64<1>(d, desc_sw128(G_W2 + WG * 4096 + (i - 34) * 2048), db);
        wg_ss64<1>(d, desc_sw128(G_W + WG * 73728 + i * 2048), db + 2);
      }
      wg_commit();
      if (ch > 0) { wg_wait<1>(); if (lane == 0) mbar_arrive(sb + G_BAR + 128 + (ch - 1) * 8); }
    }
    wg_wait<0>();
    if (lane == 0) mbar_arrive(sb + G_BAR + 128 + 8 * 8);
    if ((threadIdx.x & 127) == 0) T3(7 + WG * 3);
    __syncwarp();
    uint32_t tw = clk() + (n == 0 ? 0u - 100000u : WG ? 0u : DLYW);
    unsigned char* base = g_qkv + (size_t)(n & (QRING - 1)) * (N_CHAIN * 24576);
#pragma unroll
    for (int i = 0; i < 8; i++) {
      const float* d = (i < 4 ? d0 : d1) + 8 * (i & 2) + 2 * (i & 1);
      wait_until(tw, 0); tw += P.dly[2 + WG];
      *(uint4*)(base + (off0 + (i < 2 ? 0 : i < 4 ? 4096 + isq * 24576 : i < 6 ? 24576 - isq * 20480 : 28672 - isq * 4096)) + (i & 1) * 512) =
        make_uint4(pack2(d[0], d[1]), pack2(d[4], d[5]), pack2(d[8], d[9]), pack2(d[12], d[13]));
    }
    bar_sync(B_M + WG, 160);
  }
}

__device__ __forceinline__ void fill16(void* p, uint32_t v) {
  asm volatile("st.global.v4.u32 [%0], {%1,%1,%1,%1};" :: "l"(p), "r"(v) : "memory");
}
__device__ __forceinline__ void g_load(const Params& P, uint32_t sb) {
  const int lane = threadIdx.x & 31, w = __shfl_sync(~0u, (threadIdx.x >> 5) & 3, 0);
  if (w == 2) return;
  if (w < 2) { bar_sync(15, 192); fence_async_smem(); }
  uint32_t fl = 0;
#pragma unroll 1
  for (int n = w == 3 ? LOCK0 : 0; n < STEPS; n++) {
    if (w && n == LOCK0) { grid_wait(1, lds32(sb + S_GEN)); fl = near_half(XB_F, bid()) * 1024; }
    if (w == 3) {
      const uint32_t tag = (uint32_t)(n - LOCK0 + 1) << 24;
      uint32_t v; int it = 0;
      do { asm volatile("ld.relaxed.gpu.global.u32 %0, [%1];" : "=r"(v) : "l"(g_fl + fl + FL_TICK) : "memory"); spin_guard(it); } while (v < tag);
      const uint32_t off = timer_offset<2>(), now = clk(), t0 = now - ((v ^ tag) >> 24 ? DLYG : (now + off - v) & 0xFFFFFF);
      asm volatile("fence.acquire.gpu;" ::: "memory");
      if (lane == 0) T3(11);
      __syncwarp();
      wait_until(t0, DLYG);
      if (lane == 0) T3(4);
      bar_sync(B_OE, 160);
      continue;
    }
    if (w == 0 || n == 0) {
      if (n < NSEG) wait_flags(g_lnflag + n * 16 + (lane & 1) * 8, 1);
    } else if (n >= LAG) {
      wait_flags(g_fl + fl + FL_F + (lane & 1) * 8, n - LAG + 1);
    }
    if (w) { if (lane == 0) T3(12); bar_sync(B_X, 96); }
    fence_async_global();
    const unsigned char* src = g_lnimg + (uint32_t)((w ? (n >= LAG ? NSEG + n - LAG : 0) : min(n, NSEG - 1)) * 36864);
#pragma unroll 1
    for (int ch = 0; ch < 9; ch++) {
      const uint32_t full = sb + G_BAR + ch * 8;
      mbar_wait(full + 128, (n & 1) ^ 1);
      if (elect()) {
        mbar_expect(full, 4096);
        bulk_load(sb + G_RING + ch * 8192 + w * 4096, src + ch * 4096, 4096, full);
      }
    }
  }
}

__device__ __forceinline__ void g_aux(const Params& P, uint32_t sb) {
  const int lane = threadIdx.x & 31, w = (threadIdx.x >> 5) & 3;
  if (w == 1 || w == 2) {
    const int q = g_unit(w - 1);
    uint32_t* f = g_fl + FL_G + q * 8;
#pragma unroll 1
    for (int n = 0; n < STEPS; n++) {
      const uint32_t ln = opaque_tid() & 31;
      uint4* z = (uint4*)g_oacc + (uint32_t)(((n + 1) % ARING) * (16 * DM) + q * 96 + ln);
      fill16(z, 0); fill16(z + 32, 0); fill16(z + 64, 0);
      if (n + 3 >= MRING && q < 80) fill16((uint4*)g_mimg + (uint32_t)(((n + 3) % MRING) * 4096 + q * 32 + ln), SENT);
      bar_sync(B_M + (w - 1), 160);
      if (lane == 0) { T3(w * 2 - 2); fence_async_global(); flag_release(f, n + 1); T3(w * 2 - 1); }
      __syncwarp();
    }
  } else {
    const uint32_t u = (bid() - N_CHAIN) * 2 + (w & 1), r = u / 36 * 16 + (u & 3) * 4 + (lane >> 3);
    uint32_t o = r * (DM / 8) + (u % 36 >> 2) * 8 + ((lane & 7) ^ ((r >> 1) & 3)), fl = 0;
#pragma unroll 1
    for (int k = -LAG - 1; k < STEPS; k++) {
      if (k < NSEG - 1) bar_sync(B_X, 96);
      if (k < LAG || u >= 72) continue;
      if (k == NSEG - 1) { fl = near_half(XB_F, bid()) * 1024; wait_flags(g_fl + fl + FL_F + (lane & 1) * 8, NSEG + 1); }
      const uint4 x = __ldcg((const uint4*)P.out + o);
      if (k >= NSEG - 1) wait_flags(g_fl + fl + FL_OCNT + (max(k, NSEG) % OCRING) * 8, N_O * 3 * (max(k, NSEG) / OCRING + 1));
      const float4* a = (const float4*)g_oacc + ((k % ARING) * (16 * DM) + 8 * DM + u * 64 + lane * 2);
      const float4 p = __ldcg(a), v = __ldcg(a + 1);
      ((uint4*)P.out)[o] = make_uint4(badd2(x.x, pack2(p.x, p.y)), badd2(x.y, pack2(p.z, p.w)), badd2(x.z, pack2(v.x, v.y)), badd2(x.w, pack2(v.z, v.w)));
      o += 4 * DM;
    }
    if ((threadIdx.x & 127) == 0) TS(7);
  }
}

template <int WG, bool HALF, int KS, int N> __device__ __forceinline__ void o_mma(float* d, const uint32_t* a, uint32_t ob) {
  constexpr uint64_t db = desc_sw128(O_RING + (KS >> 2) * 8192 + (KS & 3) * 32);
  constexpr uint64_t da = desc_sw128(O_W + WG * 40960 + (KS < 40 ? KS / 5 * 2 + KS % 5 / 2 : KS - 24) * 2048);
  if constexpr (KS < 40 && !(KS % 5 & 1)) {
    const uint32_t* r = a + (KS / 5 * 3 + KS % 5 / 2) * 4;
    if constexpr (HALF) wg_rs32k<KS != 0, db>(d, r[0], r[1], r[2], r[3], ob); else wg_rs64<KS != 0>(d, r, db);
  } else {
    if constexpr (HALF) wg_ss32k<da, db>(d, ob); else wg_ss64<1>(d, da, db);
  }
  if constexpr (N > 1) o_mma<WG, HALF, KS + 1, N - 1>(d, a, ob);
}
template <int WG, bool HALF, int GR> __device__ __forceinline__ void o_groups(float* d, const uint32_t* a, uint32_t sb, int n, bool more) {
  const uint32_t ob = n < NSEG ? 0 : 256;
  mbar_wait(sb + O_BAR + GR * 8, n & 1);
  if (GR == 0) { if ((threadIdx.x & 127) == 0) T3(13 + WG); __syncwarp(); }
  if (GR == (WG == 0 ? 2 : 4) && (WG < 2 || n + 1 < STEPS)) bar_arrive(B_V + (WG + 1) % 3, 256);
  wg_fence();
  o_mma<WG, HALF, GR * 8, 8>(d, a, ob);
  if (GR == 4 && more) o_mma<WG, HALF, 40, 4>(d, a, ob);
  wg_commit();
  if (GR > 0) { wg_wait<1>(); if ((threadIdx.x & 31) == 0) mbar_arrive(sb + O_BAR + 120 + GR * 8); }
  if constexpr (GR < 4) o_groups<WG, HALF, GR + 1>(d, a, sb, n, more);
}
template <int WG, bool HALF> __device__ __forceinline__ void o_step(const uint32_t* a, uint32_t sb, uint32_t st0, int n, bool more) {
  float d[HALF ? 16 : 32];
  if (WG > 0 || n > 0) bar_sync(B_V + WG, 256);
  o_groups<WG, HALF, 0>(d, a, sb, n, more);
  wg_wait<0>();
  if ((threadIdx.x & 31) == 0) mbar_arrive(sb + O_BAR + 128 + 4 * 8);
  if ((threadIdx.x & 127) == 0) T3(WG == 0 ? 1 : WG == 1 ? 8 : 12);
  __syncwarp();
#pragma unroll(HALF ? 1 : 2)
  for (int sl = 0; sl < 2; sl++) {
    mbar_wait(sb + OB_ST + WG * 16 + sl * 8, (n & 1) ^ (WG == 0));
    if (!HALF || sl == (n >= NSEG)) {
#pragma unroll
      for (int nb = 0; nb < 4; nb++) {
        const float* r = d + (HALF ? 0 : sl * 16) + nb * 4;
        const uint32_t ad = st0 + sl * 8192 + nb * 2048;
        sts32(ad, __float_as_uint(r[0]));
        sts32(ad + 256, __float_as_uint(r[1]));
        sts32(ad ^ 32, __float_as_uint(r[2]));
        sts32((ad ^ 32) + 256, __float_as_uint(r[3]));
      }
      fence_async_smem();
    }
    bar_arrive((sl ? B_G : B_M) + WG, 160);
  }
}
template <int WG>
__device__ __forceinline__ void o_math(const Params& P, uint32_t sb) {
  const bool more = bid() < N_CHAIN + N_G + 12;
  const int lane = threadIdx.x & 31, w = (threadIdx.x >> 5) & 3, g = lane >> 2, tq = lane & 3;
  uint32_t a[96];
  mbar_wait(sb + W_BAR + WG * 8, 0);
  load_frags<24>(a, sb + WG * 49152);
  fence_async_smem();
  bar_sync(B_INIT, 416);
  load_wg<OROLE>(P, sb, false, WG, w);
  mbar_wait(sb + W_BAR + WG * 8, 1);
  if ((threadIdx.x & 127) == 0) TS(4);
  const uint32_t st0 = sb + O_ST + tq * 512 + ((w * 16 + g) ^ (tq * 8)) * 4;
#pragma unroll 1
  for (int n = 0; n < STEPS; n++) {
    if (n < LAG || n >= NSEG) o_step<WG, true>(a, sb, st0, n, more); else o_step<WG, false>(a, sb, st0, n, more);
  }
}

__device__ __forceinline__ void o_aux(const Params& P, uint32_t sb) {
  const int i = bid() - N_CHAIN - N_G, ksl = i / 3;
  const int c0 = ksl * 11 - max(ksl - 4, 0), nc = ksl < 4 ? 11 : 10;
  const int lane = threadIdx.x & 31, w = __shfl_sync(~0u, (threadIdx.x >> 5) & 3, 0);
  if (w == 0) {
    bar_sync(B_INIT, 416);
    const uint32_t* f = g_fl + FL_O + near_half(XB_F + 1, bid()) * 1024 + min((c0 & ~1) + lane, (c0 + nc - 1) | 1);
#pragma unroll 1
    for (int n = 0; n < STEPS; n++) {
      const unsigned char* src = g_oimg + (uint32_t)(((n % RING) * N_CHAIN + c0) * 8192);
      wait_flags(f, n + 1);
      fence_async_global();
      if (lane == 0) T3(0);
#pragma unroll
      for (int gr = 0; gr < 5; gr++) {
        const uint32_t full = sb + O_BAR + gr * 8, bytes = (gr < 4 ? 2 : nc - 8) * 8192;
        mbar_wait(full + 128, (n & 1) ^ 1);
        if (elect()) {
          if (n < LAG || n >= NSEG) {
            mbar_expect(full, bytes >> 1);
            for (uint32_t o = gr * 16384 + (n < LAG ? 0 : 4096); o < gr * 16384 + bytes; o += 8192) bulk_load(sb + O_RING + o, src + o, 4096, full);
          } else {
            mbar_expect(full, bytes);
            bulk_load(sb + O_RING + gr * 16384, src + gr * 16384, bytes, full);
          }
        }
      }
    }
  } else {
#pragma unroll 1
    for (int n = 0; n < STEPS; n++) {
      float* dst = g_oacc + (uint32_t)((n % ARING) * (64 * DM) + ((i % 3) * 3 + (w - 1 + ksl) % 3) * 1024);
      const bool early = w == 3 && n < NSEG;
      bar_sync(B_M + (w - 1), 160);
      if (lane == 0) {
        T3(w * 2);
        if (n < NSEG) { bulk_reduce(dst, sb + O_ST, 4096); bulk_reduce(dst + 16 * DM, sb + O_ST + 4096, 4096); }
        asm volatile("cp.async.bulk.commit_group;" ::: "memory");
        if (early) {
          asm volatile("cp.async.bulk.wait_group.read 0;" ::: "memory");
          mbar_arrive(sb + OB_ST);
          T3(8 + w);
          bulk_done_inc(g_fl + FL_OCNT + (n % OCRING) * 8);
          T3(w * 2 + 1);
        }
      }
      __syncwarp();
      bar_sync(B_G + (w - 1), 160);
      if (lane == 0) {
        if (n >= LAG) { bulk_reduce(dst + 32 * DM, sb + O_ST + 8192, 4096); bulk_reduce(dst + 48 * DM, sb + O_ST + 12288, 4096); }
        asm volatile("cp.async.bulk.commit_group;\ncp.async.bulk.wait_group.read 1;" ::: "memory");
        if (!early) mbar_arrive(sb + OB_ST + (w % 3) * 16);
        asm volatile("cp.async.bulk.wait_group.read 0;" ::: "memory");
        mbar_arrive(sb + OB_ST + (w % 3) * 16 + 8);
        if (!early) {
          T3(8 + w);
          bulk_done_inc(g_fl + FL_OCNT + (n % OCRING) * 8);
          T3(w * 2 + 1);
        }
      }
      __syncwarp();
    }
  }
}

constexpr uint32_t Y_PITCH = 1168, Y_ROWS = 16 * Y_PITCH;
template <int R> __device__ __forceinline__ void y_rows(uint32_t* y, uint32_t src, uint32_t dst, int w, int bar) {
  const int lane = threadIdx.x & 31;
#pragma unroll
  for (int k = 0; k < 2 * R + 1; k++) {
    const int op = w + k * (16 / R);
    if (k == 2 * R && w >= 4) break;
    uint32_t a, b, c, d;
    ldsm4t(a, b, c, d, src + op * 512 + (lane & 16) * 16 + (lane & 7) * 32 + (lane & 8) * 2);
    stsm4(dst + (lane & 15) * Y_PITCH + op * 32 + (lane & 16), a, b, c, d);
  }
  bar_sync(bar, 512 / R);
  const uint32_t row = dst + ((w & 6) * 2 + (w >> 3) * 2 + (w & 1)) * Y_PITCH + lane * 4;
#pragma unroll
  for (int i = 0; i < 9 * R; i++) y[i] = lds32(row + i / 9 * 2 * Y_PITCH + i % 9 * 128);
}

__device__ __forceinline__ void f_role(const Params& P, uint32_t sb) {
  const int lane = threadIdx.x & 31, w = __shfl_sync(~0u, threadIdx.x >> 5, 0), r0 = (bid() - N_CHAIN - N_G - N_O) * 16;
  if (w == 8) {
    const uint32_t* fo = g_fl + FL_OCNT + near_half(XB_F, bid()) * 1024;
    fence_async_global();
#pragma unroll 1
    for (int n = 0; n < NSEG; n++) {
      bar_sync(2, 288);
      if (elect()) {
        mbar_expect(sb + F_BAR, 36864);
        bulk_load(sb + F_XY, P.X + (size_t)(n * 32 + r0) * DM, 18432, sb + F_BAR);
        bulk_load(sb + F_XY + 18432, g_yT + (size_t)(n * 32 + r0) * DM, 18432, sb + F_BAR);
        mbar_expect(sb + F_BAR + 8, 36864);
        T3(1);
      }
      wait_flags(fo + (n % OCRING) * 8, N_O * 3 * (n / OCRING + 1));
      fence_async_global();
      if (elect()) { bulk_load(sb + F_A, g_oacc + (uint32_t)((n % ARING) * (64 * DM) + r0 * DM), 36864, sb + F_BAR + 8); T3(0); }
    }
  } else if (w == 9) {
#pragma unroll 1
    for (int n = 0; n < NSEG; n++) {
      const uint32_t st = sb + (n & 1) * 36864;
      unsigned char* p = g_lnimg + (uint32_t)((NSEG + n) * 36864 + r0 * 128);
      bar_sync(1, 288);
      if (elect()) {
        T3(2);
#pragma unroll
        for (int i = 0; i < 9; i++) bulk_store(p + i * 4096, st + F_L + i * 2048, 2048);
        asm volatile("cp.async.bulk.commit_group;" ::: "memory");
        bulk_done_inc(g_fl + FL_F + (bid() & 1) * 8);
        T3(3);
        bulk_store(P.out + (size_t)(n * 32 + r0) * DM, st + F_X, 18432);
        asm volatile("cp.async.bulk.commit_group;\ncp.async.bulk.wait_group.read 0;" ::: "memory");
        if (n + 1 == NSEG) bulk_done_inc(g_fl + FL_F + (bid() & 1) * 8);
      }
      __syncwarp();
    }
  } else if (w < 8) {
    const uint32_t row = sb + w * 1152 + lane * 4, acc = sb + F_A + w * 256 + (lane ^ ((w & 6) * 2)) * 8;
    const uint32_t ln = sb + F_L + w * 128 + (((lane >> 2) ^ w) << 4) + (lane & 3) * 4;
#pragma unroll 1
    for (int n = -1; n < NSEG; n++) {
      const uint32_t st = (n & 1) * 36864;
      uint32_t x[18], y[18], l[18];
      if (n >= 0) mbar_wait(sb + F_BAR, n & 1);
#pragma unroll
      for (int i = 0; i < 18; i++) x[i] = lds32(row + F_XY + i / 9 * 9216 + i % 9 * 128);
      y_rows<2>(y, sb + F_XY + 18432, sb + F_Y, w, 3);
      layernorm9<2>(x, l);
#pragma unroll
      for (int i = 0; i < 18; i++) x[i] = badd2(x[i], bmul2(l[i], y[i]));
      if (n >= 0) mbar_wait(sb + F_BAR + 8, n & 1);
      if (threadIdx.x == 0 && n >= 0) T3(4);
      __syncwarp();
      uint2 a[18];
#pragma unroll
      for (int i = 0; i < 18; i++) a[i] = lds64(acc + i / 9 * 2048 + i % 9 * 4096);
#pragma unroll
      for (int i = 0; i < 18; i++) x[i] = badd2(x[i], pack2(__uint_as_float(a[i].x), __uint_as_float(a[i].y)));
      if (n + 1 < NSEG) bar_arrive(2, 288);
      layernorm9<2>(x, l);
#pragma unroll
      for (int i = 0; i < 18; i++) { x[i] = badd2(x[i], bmul2(l[i], y[i])); sts32(row + st + F_X + i / 9 * 9216 + i % 9 * 128, x[i]); }
      layernorm9<2>(x, l);
#pragma unroll
      for (int i = 0; i < 18; i++) sts32(ln + st + i / 9 * 1024 + i % 9 * 2048, l[i]);
      fence_async_smem();
      if (n >= 0) bar_sync(1, 288); else bar_sync(3, 256);
    }
  }
}

constexpr uint32_t P_CH = 147456, P_CHSZ = 12800, P_H = 4352;
static_assert(P_CH + 6 * P_CHSZ <= G_BAR, "prologue smem");

template <int N>
__device__ __forceinline__ void conv_fold(float (*acc)[4], bool hi, uint32_t mine, uint32_t theirs, int bar, int cnt) {
#pragma unroll
  for (int i = 0; i < N / 2; i++) {
    uint4 v;
    v.x = __float_as_uint(hi ? acc[i][0] : acc[i + N / 2][0]); v.y = __float_as_uint(hi ? acc[i][1] : acc[i + N / 2][1]);
    v.z = __float_as_uint(hi ? acc[i][2] : acc[i + N / 2][2]); v.w = __float_as_uint(hi ? acc[i][3] : acc[i + N / 2][3]);
    sts128(mine + i * 512, v);
  }
  bar_sync(bar, cnt);
#pragma unroll
  for (int i = 0; i < N / 2; i++) {
    const uint4 v = lds128(theirs + i * 512);
    acc[i][0] = (hi ? acc[i + N / 2][0] : acc[i][0]) + __uint_as_float(v.x); acc[i][1] = (hi ? acc[i + N / 2][1] : acc[i][1]) + __uint_as_float(v.y);
    acc[i][2] = (hi ? acc[i + N / 2][2] : acc[i][2]) + __uint_as_float(v.z); acc[i][3] = (hi ? acc[i + N / 2][3] : acc[i][3]) + __uint_as_float(v.w);
  }
}
template <int N>
__device__ __forceinline__ void conv_store(const float (*acc)[4], int tile0, uint32_t su, int d, uint32_t dd) {
  const int lane = threadIdx.x & 31, g = lane >> 2, tq = lane & 3;
#pragma unroll
  for (int i = 0; i < N; i++) {
    const uint32_t ad = su + (8 + (tile0 + i) * 8 + g) * 32 + tq * 4, sw = (g & 4) << 2;
    const uint32_t lo = badd2(movmat(pack2(acc[i][0], acc[i][1])), bmul2(lds32(ad + sw), dd));
    const uint32_t hi = badd2(movmat(pack2(acc[i][2], acc[i][3])), bmul2(lds32(ad + (sw ^ 16)), dd));
    ((uint2*)g_yT)[(((tile0 + i) * 8 + g) * DM + d) * 4 + tq] = make_uint2(lo, hi);
  }
}

__device__ __forceinline__ void prologue(const Params& P, uint32_t sb) {
  const int b = bid(), tid = threadIdx.x, lane = tid & 31, warp = tid >> 5, t0 = b * 16;
  const bool isg = b >= N_CHAIN && b < N_CHAIN + N_G;
  const int nch = isg ? 2 : b < 128 ? 6 : 0, chb = b < N_CHAIN ? b * 6 : isg ? b * 2 + 256 : b * 6 - 192;
  const uint32_t tstart = clk();
  if (tid < 288) {
    if (b < 128) {
      const int c = (tid >> 1) * 4, tt = t0 + (tid & 1) * 8;
      uint2 kr[11], vr[8];
#pragma unroll
      for (int i = 0; i < 11; i++) { const int t = tt + i - 3; kr[i] = t >= 0 ? __ldg((const uint2*)(P.K + (size_t)t * DM + c)) : make_uint2(0, 0); }
#pragma unroll
      for (int i = 0; i < 8; i++) vr[i] = __ldg((const uint2*)(P.V + (size_t)(tt + i) * DM + c));
#pragma unroll
      for (int e = 0; e < 2; e++) {
        const uint4 sh = __ldg((const uint4*)(P.shift + c * 4) + e);
        const uint32_t s0 = __byte_perm(sh.x, sh.z, 0x5410), s1 = __byte_perm(sh.x, sh.z, 0x7632);
        const uint32_t s2 = __byte_perm(sh.y, sh.w, 0x5410), s3 = __byte_perm(sh.y, sh.w, 0x7632);
        uint32_t v[8];
#pragma unroll
        for (int i = 0; i < 8; i++) {
          const uint32_t k3 = e ? kr[i].y : kr[i].x, k2 = e ? kr[i + 1].y : kr[i + 1].x, k1 = e ? kr[i + 2].y : kr[i + 2].x, k0 = e ? kr[i + 3].y : kr[i + 3].x;
          v[i] = bmul2(badd2(badd2(badd2(bmul2(k3, s3), bmul2(k2, s2)), bmul2(k1, s1)), bmul2(k0, s0)), e ? vr[i].y : vr[i].x);
        }
        *(uint4*)(g_kvT + (size_t)(c + 2 * e) * KVP + tt) =
          make_uint4(__byte_perm(v[0], v[1], 0x5410), __byte_perm(v[2], v[3], 0x5410), __byte_perm(v[4], v[5], 0x5410), __byte_perm(v[6], v[7], 0x5410));
        *(uint4*)(g_kvT + (size_t)(c + 2 * e + 1) * KVP + tt) =
          make_uint4(__byte_perm(v[0], v[1], 0x7632), __byte_perm(v[2], v[3], 0x7632), __byte_perm(v[4], v[5], 0x7632), __byte_perm(v[6], v[7], 0x7632));
      }
    }
  } else if (tid < 384) {
    const int t = tid - 288;
    for (int i = b * 96 + t; i < 16 * DM; i += N_CTA * 96) ((uint4*)g_oacc)[i] = make_uint4(0, 0, 0, 0);
    if (b * 96 + t < 128 * 8) g_lnflag[b * 96 + t] = 0;
    if (t == 95) sts32(sb + S_GEN, ld_acquire(g_gbar));
    __syncwarp();
    wait_until(tstart, PREFH);
    for (int i = t; i < 32 * nch; i += 96) asm volatile("prefetch.global.L2 [%0];" :: "l"(P.Hk + (size_t)chb * SEQ + i * 64));
  }
  if (warp < 12) {
    bar_arrive(10, 416);
    if (tid == 128) TS(14);
    const int ch = 5 - (warp >> 1), sub = warp & 1, d = chb + ch;
    const uint32_t su = sb + P_CH + ch * P_CHSZ;
    if (ch < nch) {
      const uint32_t* hs = (const uint32_t*)(P.Hk + (size_t)d * SEQ);
#pragma unroll
      for (int q = sub * 32 + lane; q < 256; q += 64) {
        const uint4 c = __ldg((const uint4*)hs + q);
        const uint32_t prev = q ? __ldg(hs + 4 * q - 1) : 0u;
        sts128(su + P_H + 32 + q * 16, make_uint4(__byte_perm(c.x, prev, 0x7610), __byte_perm(c.y, c.x, 0x7610), __byte_perm(c.z, c.y, 0x7610), __byte_perm(c.w, c.z, 0x7610)));
        sts128(su + P_H + 4224 + q * 16, make_uint4(__byte_perm(c.x, 0, 0x1032), __byte_perm(c.y, 0, 0x1032), __byte_perm(c.z, 0, 0x1032), __byte_perm(c.w, 0, 0x1032)));
      }
      if (sub == 1 && lane == 0) sts32(su + P_CHSZ - 16, __bfloat16_as_ushort(P.Dk[d]) * 0x10001u);
      if (sub == 0 && lane < 20) sts128(su + (lane < 16 ? lane * 16 : P_H + (lane & 2) * 2096 + (lane & 1) * 16), make_uint4(0, 0, 0, 0));
    }
    bar_sync(11, 416);
    if (ch < nch) {
#pragma unroll
      for (int q = sub * 32 + lane; q < 256; q += 64) {
        const int row = (q >> 1) + 8;
        sts128(su + row * 32 + (((q & 1) ^ ((row >> 2) & 1)) << 4), __ldcg((const uint4*)(g_kvT + (size_t)d * KVP) + q));
      }
    }
    const int g = lane >> 2, tq = lane & 3;
    const uint32_t sh = su + P_H + (g & 1) * 4192 + (8 + (g >> 1) - tq) * 4;
    float acc[16][4];
#pragma unroll
    for (int i = 0; i < 16; i++) { acc[i][0] = acc[i][1] = acc[i][2] = acc[i][3] = 0.f; }
    auto u_addr = [&](int res) {
      const int row = 8 - res + ((lane >> 4) << 3) + (lane & 7);
      return su + row * 32 + ((((lane >> 3) & 1) ^ ((row >> 2) & 1)) << 4);
    };
    if (ch < nch) {
      bar_sync(1 + ch, 64);
      if (tid == 352) TS(11);
      if (sub) {
#pragma unroll 4
        for (int res = 0; res < 8; res++) {
          uint32_t b0, b1, b2, b3;
          ldsm4(b0, b1, b2, b3, u_addr(res));
          const uint32_t r0 = lds32(sh + res * 32);
          mma16(acc[0], r0, lds32(sh + res * 32 + 16), lds32(sh + res * 32 - 16), r0, b0, b1);
        }
        conv_store<1>(acc, 0, su, d, lds32(su + P_CHSZ - 16));
      }
    }
    bar_arrive(12, 416);
    if (isg && warp < 8) { while ((int)(clk() - tstart - S1G) < 0) __nanosleep(200); load_wg<GROLE>(P, sb, true, warp >> 2, warp & 3); }
    if (ch < nch) {
#pragma unroll 1
      for (int res = sub * 4; res < sub * 4 + 4; res++) {
        uint32_t bf[16][2];
        const uint32_t ad = u_addr(res);
#pragma unroll
        for (int f = 0; f < 16; f += 2) ldsm4(bf[f][0], bf[f][1], bf[f + 1][0], bf[f + 1][1], ad + f * 256);
#pragma unroll
        for (int k = 0; k < 16; k++) {
          const int jj = k & 1 ? k >> 1 : 15 - (k >> 1);
          const uint32_t ah = sh + (8 * jj + res) * 32;
          const uint32_t r0 = lds32(ah), r1 = lds32(ah + 16), rm = lds32(ah - 16);
#pragma unroll
          for (int i = max(jj, 1); i < 16; i++) mma16(acc[i], r0, r1, rm, r0, bf[i - jj][0], bf[i - jj][1]);
        }
      }
      bar_sync(1 + ch, 64);
      if (tid == 352) TS(12);
      const uint32_t xb = su + P_H + lane * 16, dd = lds32(su + P_CHSZ - 16);
      conv_fold<16>(acc, sub, xb + sub * 4096, xb + (sub ^ 1) * 4096, 1 + ch, 64);
      conv_store<8>(acc, sub * 8, su, d, dd);
    }
  } else {
    for (int i = b; i < 194 + MRING * 5; i += N_CTA) {
      const int n = (i - 194) / 5, r = (i - 194) % 5, blk = i < 192 ? i / 6 * 8 + i % 6 : i < 194 ? XB_F + i - 192 : XB_M + n * 8 + r;
      const uint32_t fill = i < 194 ? 0u : SENT;
#pragma unroll 1
      for (int q = tid - 384; q < 256 && warp < 15; q += 96) {
        uint4 v = make_uint4(fill, fill, fill, fill);
        if (i >= 194 && n == 0 && (r > 0 || q < 128)) {
          const bf16* m = P.mem0 + (max(r * 8 - 4, 0) + (q >> 5)) * 16 + ((q >> 1) & 1) * 8 + ((q >> 2) & 7);
          v.x = pack2(__bfloat162float(m[0]), __bfloat162float(m[DM])); v.y = pack2(__bfloat162float(m[2 * DM]), __bfloat162float(m[3 * DM]));
          v.z = pack2(__bfloat162float(m[4 * DM]), __bfloat162float(m[5 * DM])); v.w = pack2(__bfloat162float(m[6 * DM]), __bfloat162float(m[7 * DM]));
        }
        g_xb[blk * 512 + q] = v;
        g_xb[blk * 512 + 256 + q] = v;
      }
    }
    if (tid < 388) g_xb[XB_REF * 512 + (tid & 2) * 128 + (b & ~1) + (tid & 1)] = make_uint4(0, 0, 0, 0);
    else if (tid < 392 && b < N_GRP) g_xb[(b * 8 + 7) * 512 + (tid & 2) * 128 + (tid & 1)] = make_uint4(0, 0, 0, 0);
    if (warp < 15) { bar_arrive(9, 128); bar_sync(7, 96); }
    if (tid == 384) TS(8);
    if (warp == 12) {
      const bf16* w = lane < 6 ? (lane % 3 == 0 ? P.Wk : lane % 3 == 1 ? P.Wv : P.Wq) + (((b >> 5) * 2 + lane / 3) * 32 + (b & 31)) * 2048
                               : (lane < 8 ? P.Wo + (lane - 6) * (9 * 131072) : P.X) + b * 2048;
      uint32_t t = tstart + PREF0;
      if ((int)(clk() - t) > 0) t = clk();
#pragma unroll 1
      for (int st = 0; st < 9 && b < N_CHAIN; st++) {
#pragma unroll 1
        for (int i = 0; i < 9; i++, t += PACE) {
          wait_until(t, 0);
          if (lane == st) asm volatile("cp.async.bulk.prefetch.L2.global [%0], 4096;" :: "l"(w + i * (lane < 6 ? 262144 : 131072)) : "memory");
        }
      }
      if (lane == 0) TS(10);
    } else if (warp == 15) {
      bar_sync(10, 416);
      if (lane == 0) { grid_arrive(0); if (nch) grid_wait(0, lds32(sb + S_GEN)); }
      __syncwarp();
      bar_arrive(11, 416);
      if (lane == 0) TS(1);
      bar_sync(9, 128);
      bar_sync(12, 416);
      if (lane == 0) { TS(16); grid_arrive(2); TS(17); }
    } else if (lane == 0) {
      if (warp == 13 || (warp == 14 && b < N_GRP)) {
        uint32_t* p = (uint32_t*)(g_xb + (warp == 13 ? XB_REF * 512 + b : (b * 8 + 7) * 512));
        int votes = 0;
        for (int rep = 0; rep < 24 && abs(votes) < 7; rep++) {
          uint32_t v0, v1, c0, c1;
          asm volatile("atom.relaxed.gpu.global.add.u32 %0, [%4], 1;\n atom.relaxed.gpu.global.add.u32 %1, [%5], 1;\n"
                       "{.reg .pred p; setp.eq.u32 p, %0, 0x7ffffff3; @p trap; mov.u32 %2, %%clock; setp.eq.u32 p, %1, 0x7ffffff3; @p trap; mov.u32 %3, %%clock;}"
                       : "=&r"(v0), "=&r"(v1), "=&r"(c0), "=&r"(c1) : "l"(p + (rep & 1) * 1024), "l"(p + ((rep & 1) ^ 1) * 1024) : "memory");
          votes += ((c1 - c0 > 80u) == (rep & 1)) ? 1 : -1;
        }
        if (warp == 13) { g_side[b] = votes > 0; TS(9); } else g_near[b] = votes > 0;
      }
    }
    __syncwarp();
    if (warp > 12 && b < N_CHAIN) {
      while ((int)(clk() - tstart - S1DLY) < 0) __nanosleep(200);
      for (int k = warp - 13; k < 8; k += 3) load_wg<CHAIN>(P, sb, true, 1 - k / 4, k & 3);
    }
  }
  if (b < N_CHAIN + N_G && (warp < 8 || (isg && warp >= 12))) bar_arrive(0, 512); else bar_sync(0, 512);
  if (tid == 352) TS(2);
}

__device__ __forceinline__ void publish_y() {
  if (threadIdx.x == 383) { grid_arrive(1); TS(18); }
  __syncwarp();
}

template <int R> __device__ __forceinline__ void ln_tiles(const Params& P, uint32_t sb) {
  const int lane = threadIdx.x & 31, w = (threadIdx.x >> 5) & (16 / R - 1), half = R == 1 ? 0 : threadIdx.x >> 8, u = N_CTA - 1 - bid();
  const int first = R == 1 ? u : 46 - 2 * u + half, step = R == 1 ? 4 : 40, last = R == 1 ? 8 : 128;
  const uint32_t raw = sb + P_CH + half * (18432 + Y_ROWS), mb = sb + T_BAR + (R - 1 + half) * 8;
  const bool lead = w == 16 / R - 1 && lane == 0;
  auto load_y = [&](const bf16* src, int tile) {
    fence_async_global();
    mbar_expect(mb, 18432);
    bulk_load(raw, src + (size_t)tile * 16 * DM, 18432, mb);
  };
  uint32_t nx[9 * R];
  auto load_x = [&](int tile) {
#pragma unroll
    for (int i = 0; i < 9 * R; i++) nx[i] = __ldg((const uint32_t*)(P.X + (size_t)(tile * 16 + w + i / 9 * 8) * DM) + i % 9 * 32 + lane);
  };
  load_x(first);
  if (R == 2) {
    if (lead) { grid_wait(1, lds32(sb + S_GEN)); if (u > 3) TS(13); load_y(g_yT, first); }
    __syncwarp();
  }
#pragma unroll 1
  for (int tile = first, real = R - 1, ph = 0; tile < last; tile += real * step, real = 1, ph ^= 1) {
    uint32_t x[9 * R], l[9 * R], y[9 * R];
    const bool ts = threadIdx.x == 0 && (R == 1 ? tile == first : u > 3 && tile == first + step);
    if (ts) TS(26);
#pragma unroll
    for (int i = 0; i < 9 * R; i++) x[i] = nx[i];
    layernorm9<R>(x, l);
    if (real && tile + step < last) load_x(tile + step);
    if (R == 2 && tile == first + step && u >= N_F && w < 6) load_wg<OROLE>(P, sb, true, w >> 1, half * 2 + (w & 1));
    if (R == 1 && tile == first && lead) {
      if (real) grid_wait(2, lds32(sb + S_GEN));
      TS(13);
      load_y(real ? g_yT : P.Hk, tile);
    }
    bar_sync(13 + half, 512 / R);
    mbar_wait(mb, ph);
    if (ts) TS(28);
    y_rows<R>(y, raw, raw + 18432, w, 13 + half);
    if (ts) TS(29);
    if (lead && real && tile + step < last) { fence_async_smem(); load_y(g_yT, tile + step); }
    __syncwarp();
#pragma unroll
    for (int i = 0; i < 9 * R; i++) x[i] = badd2(x[i], bmul2(l[i], y[i]));
    layernorm9<R>(x, l);
    if (ts && l[0] != 0x12345) TS(30);
#pragma unroll
    for (int r = 0; r < R; r++) store_ln_row(0, tile * 16 + w + r * 8, l + r * 9);
    if (R == 1) {
      __syncthreads();
      if (threadIdx.x == 32 && real) { if (tile < 4) TS(19); st_release(g_lnflag + tile * 8, 1); if (tile < 4) TS(20); }
      __syncwarp();
    }
    if (ts) TS(31);
  }
  if (R == 2) {
    __syncthreads();
    if (threadIdx.x >= 506) {
      asm volatile("fence.acq_rel.gpu;" ::: "memory");
      st_relaxed_if(g_lnflag + ((first ^ (lane & 1)) + (lane - 26) / 2 * step) * 8, 1, true);
    }
    __syncwarp();
    fence_async_smem();
    if (threadIdx.x == 0) TS(15);
  }
}

__global__ void __cluster_dims__(2, 1, 1) __launch_bounds__(512, 1) k_main(const __grid_constant__ Params P) {
  extern __shared__ __align__(1024) unsigned char smem[];
  const uint32_t sb = (uint32_t)__cvta_generic_to_shared(smem);
  const int b = bid(), wg = threadIdx.x >> 7;
  if ((threadIdx.x & 127) == 0) TS(0);
  if (threadIdx.x == 480) {
    if ((sb & 0xFFFFFF) != SBASE) __trap();
    for (int i = 0; i < 6; i++) mbar_init(sb + W_BAR + i * 8, 1);
    if (b < N_CHAIN) {
      mbar_init(sb + CB_FULL, 1); mbar_init(sb + CB_FULL + 8, 1);
      mbar_init(sb + CB_REF, 1);
      mbar_init(sb + CB_SX, 1); mbar_init(sb + CB_OX, 1); mbar_init(sb + CB_XX, 1); mbar_init(sb + CB_Q, 2); mbar_init(sb + CB_VF, 1);
      sts32(sb + C_BAD, 0);
      for (int i = 0; i < 11; i++) mbar_init(sb + CB_M + i * 8, i == 0 ? 5 : i == 5 ? 3 - SEPV : 1);
    } else if (b < N_CHAIN + N_G) {
      for (int i = 0; i < 9; i++) { mbar_init(sb + G_BAR + i * 8, 2); mbar_init(sb + G_BAR + 128 + i * 8, 8); }
    } else if (b < N_CHAIN + N_G + N_O) {
      for (int i = 0; i < 5; i++) { mbar_init(sb + O_BAR + i * 8, 1); mbar_init(sb + O_BAR + 128 + i * 8, 12); }
      for (int i = 0; i < 6; i++) mbar_init(sb + OB_ST + i * 8, 1);
    } else {
      mbar_init(sb + F_BAR, 1); mbar_init(sb + F_BAR + 8, 1);
    }
    asm volatile("fence.mbarrier_init.release.cluster;" ::: "memory");
    fence_async_smem();
  }
  __syncwarp();
  asm volatile("barrier.cluster.arrive.relaxed.aligned;" ::: "memory");
  prologue(P, sb);
  asm volatile("barrier.cluster.wait.aligned;" ::: "memory");
  fence_async_smem();
  if (b >= N_CHAIN + N_G) publish_y();
  if (b >= 128) ln_tiles<1>(P, sb);
  if (b >= N_CHAIN + N_G) ln_tiles<2>(P, sb);
  if ((threadIdx.x & 127) == 0) TS(3);
  if (b < N_CHAIN) {
    if (wg < 2) { reg_inc<200>(); chain_proj(P, sb); }
    else if (wg == 2) { reg_dec<ATTR>(); publish_y(); chain_attn(P, sb); }
    else { reg_dec<112 - ATTR>(); chain_aux(P, sb); }
  } else if (b < N_CHAIN + N_G) {
    if (wg == 0) { reg_inc<232>(); g_math<0>(P, sb); }
    else if (wg == 1) { reg_inc<232>(); g_math<1>(P, sb); }
    else if (wg == 2) { reg_dec<24>(); bar_arrive(15, 192); publish_y(); g_aux(P, sb); }
    else { reg_dec<24>(); g_load(P, sb); }
  } else if (b < N_CHAIN + N_G + N_O) {
    if (wg == 0) { reg_inc<160>(); o_math<0>(P, sb); }
    else if (wg == 1) { reg_inc<160>(); o_math<1>(P, sb); }
    else if (wg == 2) { reg_inc<160>(); o_math<2>(P, sb); }
    else { reg_dec<32>(); o_aux(P, sb); }
  } else {
    f_role(P, sb);
  }
}

}

extern "C" void kernel_launch(void* const* d_in, const int* in_sizes, int n_in, void* d_out, int out_size) {
  typedef CUresult (*Encode)(CUtensorMap*, CUtensorMapDataType, cuuint32_t, void*, const cuuint64_t*, const cuuint64_t*, const cuuint32_t*, const cuuint32_t*,
                             CUtensorMapInterleave, CUtensorMapSwizzle, CUtensorMapL2promotion, CUtensorMapFloatOOBfill);
  static Encode encode = nullptr;
  if (!encode) cudaGetDriverEntryPoint("cuTensorMapEncodeTiled", (void**)&encode, cudaEnableDefault);
  Params P;
  for (int i = 0; i < 11; i++) {
    const bool wo = i == 6 || i == 7;
    const cuuint64_t cols = wo ? DM : HD, rows = HD + DM - cols, pitch = cols * 2;
    const cuuint64_t dim[4][5] = {{cols, 2, 8, 2, 18}, {cols, 16, 1, 1, rows / 16}, {cols, 2, 4, 4, rows / 32}, {64, 16, 64, 2, 18}};
    const cuuint64_t stride[4][4] = {{8 * pitch, pitch, 16 * pitch, 32 * pitch}, {pitch, pitch, pitch, 16 * pitch},
                                     {pitch, 8 * pitch, 2 * pitch, 32 * pitch}, {pitch, 128, 16 * pitch, 32 * pitch}};
    const cuuint32_t box[4][5] = {{64, 2, 8, 1, 18}, {64, 16, 1, 1, 1}, {64, 2, 4, 2, 1}, {64, 16, 2, 1, 18}}, one[5] = {1, 1, 1, 1, 1};
    const int k = i < 3 ? 0 : i < 7 ? 1 : i < 8 ? 2 : 3;
    encode(&P.map[i], CU_TENSOR_MAP_DATA_TYPE_BFLOAT16, 5, d_in[wo ? 11 : 8 + (i & 7) % 3], dim[k], stride[k], box[k], one,
           CU_TENSOR_MAP_INTERLEAVE_NONE, CU_TENSOR_MAP_SWIZZLE_128B, CU_TENSOR_MAP_L2_PROMOTION_L2_128B, CU_TENSOR_MAP_FLOAT_OOB_FILL_NONE);
  }
  P.X = (const bf16*)d_in[0]; P.K = (const bf16*)d_in[1]; P.V = (const bf16*)d_in[2];
  P.shift = (const bf16*)d_in[3]; P.Hk = (const bf16*)d_in[4]; P.Dk = (const bf16*)d_in[5];
  P.mem0 = (const bf16*)d_in[7];
  P.Wq = (const bf16*)d_in[8]; P.Wk = (const bf16*)d_in[9]; P.Wv = (const bf16*)d_in[10]; P.Wo = (const bf16*)d_in[11];
  P.out = (bf16*)d_out;
  for (int i = 0; i < 24; i++) P.dly[i] = h_dly[i];
  cudaFuncSetAttribute(k_main, cudaFuncAttributeMaxDynamicSharedMemorySize, SMEM_BYTES);
  k_main<<<N_CTA, 512, SMEM_BYTES>>>(P);
}
```

```cpp
#include <cuda.h>
#include <cuda_runtime.h>
#include <cuda_bf16.h>
#include <stdint.h>

namespace {

typedef __nv_bfloat16 bf16;

constexpr int SEQ = 2048, DM = 576, HD = 4096, NSEG = 64;
constexpr int LAG = 7, STEPS = NSEG + LAG, RING = 8;
constexpr int LOCK0 = 3, QRING = LOCK0 + 1;
static_assert(LAG < RING, "ring");
constexpr int N_CHAIN = 64, N_G = 48, N_O = 18, N_F = 2;
constexpr uint32_t SBASE = 1024;
constexpr uint32_t SENT = 0xFFFFFFFFu;
constexpr int SPIN_MAX = 1 << 22;

__device__ __forceinline__ uint32_t bid() {
  uint32_t b;
  asm volatile("mov.u32 %0, %%ctaid.x;" : "=r"(b));
  return b < 6 ? b + 106 : b < 8 ? b + 122 : b < 114 ? b - 8 : b < 130 ? b - 2 : b;
}
__device__ __forceinline__ uint32_t chain_id() { return blockIdx.x - 8; }
constexpr int KVP = SEQ + 64;
__device__ __align__(1024) bf16 g_kvT[DM * KVP];
__device__ __align__(1024) bf16 g_yT[DM * SEQ];
__device__ __align__(1024) unsigned char g_lnimg[2 * NSEG * 9 * 4096];
__device__ __align__(1024) unsigned char g_qkv[QRING * N_CHAIN * 24576];
__device__ __align__(1024) unsigned char g_oimg[RING * N_CHAIN * 8192];
constexpr int ARING = 16;
static_assert(ARING >= LAG + 9, "accumulator ring");
__device__ __align__(1024) float g_oacc[ARING * 64 * DM];
constexpr int MRING = LAG + 4, N_GRP = 32 + MRING + 1;
constexpr int XB_M = 256, XB_F = XB_M + MRING * 8, XB_REF = XB_F + 2, N_CTA = N_CHAIN + N_G + N_O + N_F;
__device__ __align__(65536) uint4 g_xb[N_GRP * 4096];
#define g_mimg ((uint32_t*)(g_xb + XB_M * 512))
__device__ uint32_t g_near[N_GRP];
__device__ uint32_t g_side[N_CTA];
__device__ __align__(128) uint32_t g_gbar[3 * 32];
constexpr int FL_G = 0, FL_F = 96 * 8, FL_OCNT = FL_F + 2 * 8, OCRING = 16, FL_TICK = 992, FL_O = 2048, FL_SYNC = FL_O + 128;
static_assert(FL_OCNT + OCRING * 8 <= FL_TICK, "flag block");
#define g_fl ((uint32_t*)(g_xb + XB_F * 512))
__device__ __align__(1024) uint32_t g_lnflag[128 * 8];
#define TS(slot)

#define CNT(slot, tries)
#define T3(slot)
#define TR(slot)
#define TRV(slot, val)
#define TRD(slot, dep)
#define TRSYNC()
#define TRDUMP(n)
#define CLK(t) "{.reg .b64 x; .reg .b32 h; mov.u64 x, %%clock64; mov.b64 {" t ", h}, x;}"
__device__ __forceinline__ uint32_t clk() { uint32_t t; asm volatile(CLK("%0") : "=r"(t) :: "memory"); return t; }
__device__ __forceinline__ void wait_until(uint32_t t0, uint32_t d) {
  asm volatile("{.reg .pred p; .reg .u32 t;\n"
               "W: " CLK("t") " sub.u32 t, t, %0; setp.lt.s32 p, t, 0; @p bra.uni W;}"
               :: "r"(t0 + d) : "memory");
}
__device__ __forceinline__ uint32_t pack2(float lo, float hi) {
  uint32_t r; asm("cvt.rn.bf16x2.f32 %0, %1, %2;" : "=r"(r) : "f"(hi), "f"(lo)); return r;
}
__device__ __forceinline__ float bf_lo(uint32_t v) { return __uint_as_float(v << 16); }
__device__ __forceinline__ float bf_hi(uint32_t v) { return __uint_as_float(v & 0xFFFF0000u); }

__device__ __forceinline__ void st_b128(void* p, uint32_t a, uint32_t b, uint32_t c, uint32_t d) {
  asm volatile("{.reg .b128 v; mov.b128 v, {%1,%2,%3,%4}; st.relaxed.gpu.global.b128 [%0], v;}" :: "l"(p), "r"(a), "r"(b), "r"(c), "r"(d) : "memory");
}
__device__ __forceinline__ void st_relaxed_if(void* p, uint32_t a, bool on) {
  asm volatile("{.reg .pred p; setp.ne.u32 p, %2, 0; @p st.relaxed.gpu.global.u32 [%0], %1;}" :: "l"(p), "r"(a), "r"((uint32_t)on) : "memory");
}
__device__ __forceinline__ uint32_t ld_acquire(const uint32_t* p) {
  uint32_t v; asm volatile("ld.acquire.gpu.global.u32 %0, [%1];" : "=r"(v) : "l"(p) : "memory"); return v;
}
__device__ __forceinline__ void st_release(uint32_t* p, uint32_t v) {
  asm volatile("st.release.gpu.global.u32 [%0], %1;" :: "l"(p), "r"(v) : "memory");
}
__device__ __forceinline__ void bulk_reduce(float* dst, uint32_t src, uint32_t bytes) {
  asm volatile("cp.reduce.async.bulk.global.shared::cta.bulk_group.add.f32 [%0], [%1], %2;" :: "l"(dst), "r"(src), "r"(bytes) : "memory");
}
__device__ __forceinline__ void bulk_done_inc(uint32_t* p) {
  asm volatile("cp.async.bulk.wait_group 0;\n"
               "fence.proxy.async.global;\nfence.release.gpu;\n"
               "red.relaxed.gpu.global.add.u32 [%0], 1;\nred.relaxed.gpu.global.add.u32 [%0+4096], 1;" :: "l"(p) : "memory");
}
__device__ __forceinline__ void flag_release(uint32_t* p, uint32_t v) {
  asm volatile("fence.release.gpu;\nst.relaxed.gpu.global.u32 [%0], %1;\nst.relaxed.gpu.global.u32 [%0+4096], %1;" :: "l"(p), "r"(v) : "memory");
}
__device__ __forceinline__ void spin_guard(int& it) {
  asm volatile("{.reg .pred p; add.s32 %0, %0, 1; setp.gt.s32 p, %0, %1; @p trap;}" : "+r"(it) : "n"(SPIN_MAX));
}
__device__ __forceinline__ void wait_flags(const uint32_t* p, uint32_t v) {
  int it = 0;
  while (true) {
    uint32_t x; asm volatile("ld.relaxed.gpu.global.u32 %0, [%1];" : "=r"(x) : "l"(p) : "memory");
    if (__all_sync(~0u, x >= v)) break;
    spin_guard(it);
  }
  asm volatile("fence.acquire.gpu;" ::: "memory");
}
__device__ __forceinline__ uint32_t timer_sample() {
  uint32_t g;
  asm volatile("{.reg .b64 x; .reg .b32 h; mov.u64 x, %%globaltimer; mov.b64 {%0, h}, x;}" : "=r"(g) :: "memory");
  return (g >> 5) * 57 - clk();
}
template <int N> __device__ __forceinline__ uint32_t timer_offset() {
  const uint32_t base = timer_sample();
  int best = 0;
#pragma unroll 1
  for (int i = 0; i < N; i++) {
    const int a = timer_sample() - base, b = timer_sample() - base, c = timer_sample() - base;
    best = max(max(best, a), max(b, c));
  }
  return base + best;
}
__device__ __forceinline__ void grid_arrive(int i) {
  asm volatile("red.release.gpu.global.add.u32 [%0], %1;" :: "l"(g_gbar + i * 32), "r"(bid() ? 1u : 257u - N_CTA) : "memory");
}
__device__ __forceinline__ void grid_wait(int i, uint32_t gen) {
  int it = 0;
  while (((ld_acquire(g_gbar + i * 32) ^ gen) >> 8) == 0) spin_guard(it);
}
__device__ __forceinline__ bool elect() {
  uint32_t r; asm volatile("{.reg .pred p; elect.sync _|p, -1; selp.u32 %0, 1, 0, p;}" : "=r"(r)); return r;
}
__device__ __forceinline__ void bar_sync(int id, int cnt) { asm volatile("bar.sync %0, %1;" :: "r"(id), "r"(cnt) : "memory"); }
__device__ __forceinline__ void bar_arrive(int id, int cnt) { asm volatile("bar.arrive %0, %1;" :: "r"(id), "r"(cnt) : "memory"); }
template <int id, int cnt> __device__ __forceinline__ void bar_arrive_after(uint32_t a, uint32_t b) {
  asm volatile("{.reg .pred p; setp.ne.u32 p, %2, 0xfff12345; setp.ne.and.u32 p, %3, 0xfff12345, p; @p bar.arrive %0, %1;}" :: "n"(id), "n"(cnt), "r"(a), "r"(b) : "memory");
}
template <int id, int cnt> __device__ __forceinline__ void bar_sync_after(uint32_t a) {
  asm volatile("{.reg .pred p; setp.ne.u32 p, %2, 0xfff12345; @p bar.sync %0, %1;}" :: "n"(id), "n"(cnt), "r"(a) : "memory");
}
__device__ __forceinline__ void fence_async_smem() { asm volatile("fence.proxy.async.shared::cta;" ::: "memory"); }
__device__ __forceinline__ void fence_async_global() { asm volatile("fence.proxy.async.global;" ::: "memory"); }
__device__ __forceinline__ void mbar_init(uint32_t mb, int cnt) { asm volatile("mbarrier.init.shared::cta.b64 [%0], %1;" :: "r"(mb), "r"(cnt) : "memory"); }
__device__ __forceinline__ void mbar_arrive(uint32_t mb) { asm volatile("mbarrier.arrive.shared::cta.b64 _, [%0];" :: "r"(mb) : "memory"); }
__device__ __forceinline__ void mbar_expect(uint32_t mb, uint32_t bytes) {
  asm volatile("mbarrier.arrive.expect_tx.shared::cta.b64 _, [%0], %1;" :: "r"(mb), "r"(bytes) : "memory");
}
__device__ __forceinline__ void mbar_wait(uint32_t mb, uint32_t parity) {
  asm volatile("{.reg .pred p;\nW: mbarrier.try_wait.parity.shared::cta.b64 p, [%0], %1;\n@!p bra W;}" :: "r"(mb), "r"(parity) : "memory");
}
template <int K> __device__ __forceinline__ void mbar_wait_step(uint32_t mb, int n) {
  asm volatile("{.reg .pred p; .reg .b32 t; add.u32 t, %1, %2; and.b32 t, t, 1;\nW: mbarrier.try_wait.parity.shared::cta.b64 p, [%0], t;\n@!p bra W;}" :: "r"(mb), "r"(n), "n"(2 * K) : "memory");
}
__device__ __forceinline__ void bulk_load(uint32_t dst, const void* src, uint32_t bytes, uint32_t mb) {
  asm volatile("cp.async.bulk.shared::cluster.global.mbarrier::complete_tx::bytes [%0], [%1], %2, [%3];" :: "r"(dst), "l"(src), "r"(bytes), "r"(mb) : "memory");
}
__device__ __forceinline__ void bulk_store(void* dst, uint32_t src, uint32_t bytes) {
  asm volatile("cp.async.bulk.global.shared::cta.bulk_group [%0], [%1], %2;" :: "l"(dst), "r"(src), "r"(bytes) : "memory");
}
__device__ __forceinline__ uint32_t mapa(uint32_t a, uint32_t rank) {
  uint32_t r; asm("mapa.shared::cluster.u32 %0, %1, %2;" : "=r"(r) : "r"(a), "r"(rank)); return r;
}
__device__ __forceinline__ void st_async4(uint32_t dst, float a, float b, float c, float d, uint32_t mb) {
  asm volatile("st.async.shared::cluster.mbarrier::complete_tx::bytes.v4.f32 [%0], {%1,%2,%3,%4}, [%5];" :: "r"(dst), "f"(a), "f"(b), "f"(c), "f"(d), "r"(mb) : "memory");
}
__device__ __forceinline__ void st_async1(uint32_t dst, uint32_t a, uint32_t mb) {
  asm volatile("st.async.shared::cluster.mbarrier::complete_tx::bytes.u32 [%0], %1, [%2];" :: "r"(dst), "r"(a), "r"(mb) : "memory");
}
__device__ __forceinline__ uint4 lds128(uint32_t a) {
  uint4 v; asm volatile("ld.shared.v4.u32 {%0,%1,%2,%3}, [%4];" : "=r"(v.x), "=r"(v.y), "=r"(v.z), "=r"(v.w) : "r"(a) : "memory"); return v;
}
__device__ __forceinline__ uint2 lds64(uint32_t a) {
  uint2 v; asm volatile("ld.shared.v2.u32 {%0,%1}, [%2];" : "=r"(v.x), "=r"(v.y) : "r"(a) : "memory"); return v;
}
__device__ __forceinline__ uint32_t lds32(uint32_t a) {
  uint32_t v; asm volatile("ld.shared.u32 %0, [%1];" : "=r"(v) : "r"(a) : "memory"); return v;
}
__device__ __forceinline__ void sts128(uint32_t a, uint4 v) {
  asm volatile("st.shared.v4.u32 [%0], {%1,%2,%3,%4};" :: "r"(a), "r"(v.x), "r"(v.y), "r"(v.z), "r"(v.w) : "memory");
}
__device__ __forceinline__ void sts32(uint32_t a, uint32_t x) { asm volatile("st.shared.u32 [%0], %1;" :: "r"(a), "r"(x) : "memory"); }
__device__ __forceinline__ void ldsm4(uint32_t& r0, uint32_t& r1, uint32_t& r2, uint32_t& r3, uint32_t a) {
  asm volatile("ldmatrix.sync.aligned.m8n8.x4.shared.b16 {%0,%1,%2,%3}, [%4];" : "=r"(r0), "=r"(r1), "=r"(r2), "=r"(r3) : "r"(a) : "memory");
}
__device__ __forceinline__ void ldsm4t(uint32_t& r0, uint32_t& r1, uint32_t& r2, uint32_t& r3, uint32_t a) {
  asm volatile("ldmatrix.sync.aligned.m8n8.x4.trans.shared.b16 {%0,%1,%2,%3}, [%4];" : "=r"(r0), "=r"(r1), "=r"(r2), "=r"(r3) : "r"(a) : "memory");
}
__device__ __forceinline__ void stsm4(uint32_t a, uint32_t r0, uint32_t r1, uint32_t r2, uint32_t r3) {
  asm volatile("stmatrix.sync.aligned.m8n8.x4.shared.b16 [%0], {%1,%2,%3,%4};" :: "r"(a), "r"(r0), "r"(r1), "r"(r2), "r"(r3) : "memory");
}
__device__ __forceinline__ uint32_t movmat(uint32_t a) {
  uint32_t d; asm volatile("movmatrix.sync.aligned.m8n8.trans.b16 %0, %1;" : "=r"(d) : "r"(a)); return d;
}
__device__ __forceinline__ void mma16(float* d, uint32_t a0, uint32_t a1, uint32_t a2, uint32_t a3, uint32_t b0, uint32_t b1) {
  asm volatile("mma.sync.aligned.m16n8k16.row.col.f32.bf16.bf16.f32 {%0,%1,%2,%3}, {%4,%5,%6,%7}, {%8,%9}, {%0,%1,%2,%3};"
    : "+f"(d[0]), "+f"(d[1]), "+f"(d[2]), "+f"(d[3]) : "r"(a0), "r"(a1), "r"(a2), "r"(a3), "r"(b0), "r"(b1));
}
__device__ __forceinline__ void mma8(float* d, uint32_t a0, uint32_t a1, uint32_t b0) {
  asm volatile("mma.sync.aligned.m16n8k8.row.col.f32.bf16.bf16.f32 {%0,%1,%2,%3}, {%4,%5}, {%6}, {%0,%1,%2,%3};"
    : "+f"(d[0]), "+f"(d[1]), "+f"(d[2]), "+f"(d[3]) : "r"(a0), "r"(a1), "r"(b0));
}
__device__ __forceinline__ float rcp(float x) { float r; asm("rcp.approx.ftz.f32 %0, %1;" : "=f"(r) : "f"(x)); return r; }
__device__ __forceinline__ float ex2(float x) { float r; asm("ex2.approx.ftz.f32 %0, %1;" : "=f"(r) : "f"(x)); return r; }

__host__ __device__ constexpr uint64_t mkdesc(uint32_t off, uint32_t lbo, uint32_t sbo, uint32_t swz) {
  return (uint64_t)((SBASE + off) >> 4) | ((uint64_t)(lbo >> 4) << 16) | ((uint64_t)(sbo >> 4) << 32) | ((uint64_t)swz << 62);
}
__host__ __device__ constexpr uint64_t desc_sw128(uint32_t off) { return mkdesc(off, 16, 1024, 1); }
__host__ __device__ constexpr uint64_t desc_n16(uint32_t off) { return mkdesc(off, 256, 128, 0); }
__host__ __device__ constexpr uint64_t desc_m(uint32_t off) { return mkdesc(off, 16, 256, 3); }

__host__ __device__ constexpr uint64_t desc_sw64(uint32_t off) { return mkdesc(off, 16, 512, 2); }

__device__ __forceinline__ void wg_fence() { asm volatile("wgmma.fence.sync.aligned;" ::: "memory"); }
__device__ __forceinline__ void wg_commit() { asm volatile("wgmma.commit_group.sync.aligned;" ::: "memory"); }
template <int N> __device__ __forceinline__ void wg_wait() { asm volatile("wgmma.wait_group.sync.aligned %0;" :: "n"(N) : "memory"); }

#define ACC8(d) "+f"(d[0]), "+f"(d[1]), "+f"(d[2]), "+f"(d[3]), "+f"(d[4]), "+f"(d[5]), "+f"(d[6]), "+f"(d[7])
#define ACC32(d) ACC8(d), ACC8((d + 8)), ACC8((d + 16)), ACC8((d + 24))
#define R8 "{%0,%1,%2,%3,%4,%5,%6,%7}"
#define R32 "{%0,%1,%2,%3,%4,%5,%6,%7,%8,%9,%10,%11,%12,%13,%14,%15,%16,%17,%18,%19,%20,%21,%22,%23,%24,%25,%26,%27,%28,%29,%30,%31}"
template <int SD> __device__ __forceinline__ void wg_rs16(float* d, const uint32_t* a, uint64_t db) {
  asm volatile("wgmma.mma_async.sync.aligned.m64n16k16.f32.bf16.bf16 " R8 ", {%8,%9,%10,%11}, %12, %13, 1, 1, 1;"
    : ACC8(d) : "r"(a[0]), "r"(a[1]), "r"(a[2]), "r"(a[3]), "l"(db), "n"(SD));
}
template <int SD> __device__ __forceinline__ void wg_ss16(float* d, uint64_t da, uint64_t db) {
  asm volatile("wgmma.mma_async.sync.aligned.m64n16k16.f32.bf16.bf16 " R8 ", %8, %9, %10, 1, 1, 1, 1;"
    : ACC8(d) : "l"(da), "l"(db), "n"(SD));
}
template <int SD, uint64_t DA, uint64_t DB> __device__ __forceinline__ void wg_ss16o(float* d, uint32_t oa, uint32_t ob) {
  asm volatile("{.reg .b32 x, y; .reg .b64 a, b; add.u32 x, %8, %10; add.u32 y, %9, %12; mov.b64 a, {x, %11}; mov.b64 b, {y, %13};\n"
               "wgmma.mma_async.sync.aligned.m64n16k16.f32.bf16.bf16 " R8 ", a, b, %14, 1, 1, 1, 1;}"
    : ACC8(d) : "r"(oa), "r"(ob), "n"((uint32_t)DA), "n"((uint32_t)(DA >> 32)), "n"((uint32_t)DB), "n"((uint32_t)(DB >> 32)), "n"(SD));
}
template <int SD> __device__ __forceinline__ void wg_rs64(float* d, const uint32_t* a, uint64_t db) {
  asm volatile("wgmma.mma_async.sync.aligned.m64n64k16.f32.bf16.bf16 " R32 ", {%32,%33,%34,%35}, %36, %37, 1, 1, 0;"
    : ACC32(d) : "r"(a[0]), "r"(a[1]), "r"(a[2]), "r"(a[3]), "l"(db), "n"(SD));
}
template <int SD> __device__ __forceinline__ void wg_ss64(float* d, uint64_t da, uint64_t db) {
  asm volatile("wgmma.mma_async.sync.aligned.m64n64k16.f32.bf16.bf16 " R32 ", %32, %33, %34, 1, 1, 1, 0;"
    : ACC32(d) : "l"(da), "l"(db), "n"(SD));
}
#define WG_RSO(NAME, SHAPE, REGS, ACC, A, TB) \
template <int SD, uint64_t DB> __device__ __forceinline__ void NAME(float* d, uint32_t a0, uint32_t a1, uint32_t a2, uint32_t a3, uint32_t ob) { \
  asm volatile("{.reg .b64 b; mov.b64 b, {" A(4) ", " A(5) "};\nwgmma.mma_async.sync.aligned." SHAPE ".f32.bf16.bf16 " REGS \
               ", {" A(0) "," A(1) "," A(2) "," A(3) "}, b, " A(6) ", 1, 1, " TB ";}" \
    : ACC(d) : "r"(a0), "r"(a1), "r"(a2), "r"(a3), "r"(ob + (uint32_t)DB), "n"((uint32_t)(DB >> 32)), "n"(SD)); \
}
#define ACC4(d) "+f"(d[0]), "+f"(d[1]), "+f"(d[2]), "+f"(d[3])
#define ACC16(d) ACC8(d), ACC8((d + 8))
#define OP4(i) OP4_##i
#define OP4_0 "%4"
#define OP4_1 "%5"
#define OP4_2 "%6"
#define OP4_3 "%7"
#define OP4_4 "%8"
#define OP4_5 "%9"
#define OP4_6 "%10"
#define OP16(i) OP16_##i
#define OP16_0 "%16"
#define OP16_1 "%17"
#define OP16_2 "%18"
#define OP16_3 "%19"
#define OP16_4 "%20"
#define OP16_5 "%21"
#define OP16_6 "%22"
#define OP32(i) OP32_##i
#define OP32_0 "%32"
#define OP32_1 "%33"
#define OP32_2 "%34"
#define OP32_3 "%35"
#define OP32_4 "%36"
#define OP32_5 "%37"
#define OP32_6 "%38"
WG_RSO(wg_rs8o, "m64n8k16", "{%0,%1,%2,%3}", ACC4, OP4, "1")
#define R16 "{%0,%1,%2,%3,%4,%5,%6,%7,%8,%9,%10,%11,%12,%13,%14,%15}"
WG_RSO(wg_rs32o, "m64n32k16", R16, ACC16, OP16, "1")
WG_RSO(wg_rs64o, "m64n64k16", R32, ACC32, OP32, "0")
WG_RSO(wg_rs32k, "m64n32k16", R16, ACC16, OP16, "0")
template <uint64_t DA, uint64_t DB> __device__ __forceinline__ void wg_ss32k(float* d, uint32_t ob) {
  asm volatile("{.reg .b64 b; mov.b64 b, {%17, %18};\nwgmma.mma_async.sync.aligned.m64n32k16.f32.bf16.bf16 " R16 ", %16, b, 1, 1, 1, 1, 0;}"
    : ACC16(d) : "l"(DA), "r"(ob + (uint32_t)DB), "n"((uint32_t)(DB >> 32)));
}
template <int N> __device__ __forceinline__ void reg_inc() { asm volatile("setmaxnreg.inc.sync.aligned.u32 %0;" :: "n"(N)); }
template <int N> __device__ __forceinline__ void reg_dec() { asm volatile("setmaxnreg.dec.sync.aligned.u32 %0;" :: "n"(N)); }

template <int KS>
__device__ __forceinline__ void load_frags(uint32_t* a, uint32_t src) {
  const int lane = threadIdx.x & 31, w = (threadIdx.x >> 5) & 3;
  const int k = ((lane >> 4) << 3) + (lane & 7), u = w * 2 + ((lane >> 3) & 1);
  const uint32_t base = src + k * 128 + ((u ^ (k & 7)) << 4);
#pragma unroll
  for (int ks = 0; ks < KS; ks++) ldsm4t(a[ks * 4], a[ks * 4 + 1], a[ks * 4 + 2], a[ks * 4 + 3], base + ks * 2048);
}

__device__ __forceinline__ uint32_t badd2(uint32_t a, uint32_t b) { uint32_t r; asm("add.rn.bf16x2 %0, %1, %2;" : "=r"(r) : "r"(a), "r"(b)); return r; }
__device__ __forceinline__ uint32_t bsub2(uint32_t a, uint32_t b) { uint32_t r; asm("sub.rn.bf16x2 %0, %1, %2;" : "=r"(r) : "r"(a), "r"(b)); return r; }
__device__ __forceinline__ uint32_t bmul2(uint32_t a, uint32_t b) { uint32_t r; asm("mul.rn.bf16x2 %0, %1, %2;" : "=r"(r) : "r"(a), "r"(b)); return r; }
__device__ __forceinline__ uint32_t bfma2(uint32_t a, uint32_t b, uint32_t c) { uint32_t r; asm("fma.rn.bf16x2 %0, %1, %2, %3;" : "=r"(r) : "r"(a), "r"(b), "r"(c)); return r; }
template <int R> __device__ __forceinline__ void layernorm9(const uint32_t* x, uint32_t* o) {
  const uint32_t ones = 0x3F803F80u;
  float a[R][3][4], q[R], s[R];
#pragma unroll
  for (int i = 0; i < 9 * R; i++) {
    float* d = a[i % R][i / R % 3];
    if (i < 3 * R) d[0] = d[1] = d[2] = d[3] = 0.f;
    mma8(d, x[i % R * 9 + i / R], ones, x[i % R * 9 + i / R]);
  }
#pragma unroll
  for (int r = 0; r < R; r++) {
    q[r] = threadIdx.x & 4 ? a[r][0][1] + a[r][1][1] + a[r][2][1] : a[r][0][0] + a[r][1][0] + a[r][2][0];
    s[r] = (a[r][0][2] + a[r][0][3]) + (a[r][1][2] + a[r][1][3]) + (a[r][2][2] + a[r][2][3]);
  }
#pragma unroll
  for (int r = 0; r < R; r++) { q[r] += __shfl_xor_sync(~0u, q[r], 4); s[r] += __shfl_xor_sync(~0u, s[r], 1); }
#pragma unroll
  for (int r = 0; r < R; r++) { q[r] += __shfl_xor_sync(~0u, q[r], 9); s[r] += __shfl_xor_sync(~0u, s[r], 2); }
#pragma unroll
  for (int r = 0; r < R; r++) q[r] = __shfl_sync(~0u, q[r], 0) + __shfl_sync(~0u, q[r], 18);
#pragma unroll
  for (int r = 0; r < R; r++) {
    const float mean = s[r] * (1.f / DM), var = fmaxf(fmaf(q[r], 1.f / DM, -mean * mean), 0.f);
    float sd;
    asm("sqrt.approx.ftz.f32 %0, %1;" : "=f"(sd) : "f"(bf_lo(pack2(bf_lo(pack2(var, 0.f)) + 1e-5f, 0.f))));
    const float inv = rcp(bf_lo(pack2(sd, 0.f)));
    const uint32_t mb = pack2(mean, mean), hi = pack2(inv, inv), lo = pack2(inv - bf_lo(hi), inv - bf_lo(hi));
#pragma unroll
    for (int i = r * 9; i < r * 9 + 9; i++) {
      const uint32_t d = bsub2(x[i], mb);
      o[i] = bfma2(d, hi, bmul2(d, lo));
    }
  }
}
__device__ __forceinline__ void store_ln_row(int layer, int tok, const uint32_t* o) {
  const int lane = threadIdx.x & 31, r = tok & 31;
  unsigned char* p = g_lnimg + (size_t)(layer * NSEG + (tok >> 5)) * (9 * 4096) + r * 128 + (((lane >> 2) ^ (r & 7)) << 4) + (lane & 3) * 4;
#pragma unroll
  for (int i = 0; i < 9; i++) *(uint32_t*)(p + i * 4096) = o[i];
}
struct Params { CUtensorMap map[11]; const bf16 *X, *K, *V, *shift, *Hk, *Dk, *mem0, *Wq, *Wk, *Wv, *Wo; bf16* out; uint32_t dly[25]; };
#define DLYS P.dly[0]
#define DLYW P.dly[1]
#define DLYV P.dly[24]
#define DLYK P.dly[4]
#define DLYG P.dly[5]
#define KWIN P.dly[6]
#define KMIN P.dly[7]
#define PREF0 P.dly[19]
#define PACE P.dly[20]
#define S1G P.dly[21]
#define S1DLY P.dly[22]
#define PREFH P.dly[23]
uint32_t h_dly[25] = {800, 120, 150, 160, 3640, 4160, 2750, 1300, 1585, 1670, 1760, 2090, 2210, 2310, 2820, 2930, 3185, 3330, 3500, 7000, 160, 12500, 20500, 4000, 3540};

constexpr uint32_t C_W = 0, C_M = 147456, C_KV = C_M + 18432, C_OS = C_KV + 24576, C_QM = C_KV + 32768, C_KM = C_QM + 2048,
                   C_VM = C_KM + 2048, C_OI = C_VM + 2048, C_SX = C_OI + 4096, C_KM2 = C_SX + 2560, C_VM2 = C_KM2 + 128,
                   C_KV2 = C_KM2 + 2048, C_Q = C_KV2 + 8192, C_BAR = C_Q + 8192;
constexpr uint32_t CB_FULL = C_BAR, CB_REF = C_BAR + 16, CB_SX = C_BAR + 32, CB_OX = C_BAR + 40, CB_XX = C_BAR + 48, CB_Q = C_BAR + 56, C_BAD = C_BAR + 64, W_BAR = C_BAR + 80, T_BAR = W_BAR + 24, S_GEN = C_BAR + 128, C_REF = C_BAR + 132, CB_VF = C_BAR + 144, CB_M = C_BAR + 160, CB_MV = C_BAR + 200;
constexpr uint32_t G_W = 0, G_RING = 147456, G_W2 = G_RING + 9 * 8192, G_BAR = G_W2 + 8192;
constexpr uint32_t O_W = 0, O_RING = 3 * 40960, O_ST = O_RING + 11 * 8192, O_BAR = O_ST + 16384, OB_ST = O_BAR + 64;
constexpr uint32_t F_A = 0, F_XY = 36864, F_L = F_XY + 36864, F_X = F_L + 18432, F_Y = F_L + 2 * 36864, F_BAR = C_BAR;
constexpr uint32_t SMEM_BYTES = C_BAR + 256;
static_assert(G_BAR + 256 <= SMEM_BYTES && O_BAR + 256 <= SMEM_BYTES && F_BAR + 16 <= SMEM_BYTES && SMEM_BYTES <= 232448, "smem map");
enum { B_INIT = 1, B_M, B_QK, B_S, B_V, B_O, B_X, B_WG0, B_WG1, B_WG2, B_G, B_OE, B_T, B_R };

__device__ __forceinline__ uint4 pack_partial(const float* d, uint32_t tag) {
  uint32_t x, z;
  asm("lop3.b32 %0, %2, 1, %4, 0xb8; lop3.b32 %1, %3, 1, %4, 0xb8;" : "=&r"(x), "=&r"(z) : "r"(pack2(d[0], d[1])), "r"(pack2(d[2], d[3])), "r"(tag));
  return make_uint4(x, pack2(d[4], d[5]), z, pack2(d[6], d[7]));
}
__device__ __forceinline__ void store_partial(uint4* p, const uint4& v) { st_b128(p, v.x, v.y, v.z, v.w); }
__device__ __forceinline__ void gather_reduce(const uint32_t* p, uint32_t* dst, uint32_t m0, bool shared, uint32_t tag, uint32_t lane, uint32_t sb, int n, int TS0) {
  int tries = 0;
  bool bad;
  TR(TS0);
  do {
    uint2 x[8];
#pragma unroll
    for (int i = 0; i < 8; i++)
      asm volatile("{.reg .b64 v; ld.relaxed.gpu.global.b64 v, [%2]; mov.b64 {%0, %1}, v;}" : "=r"(x[i].x), "=r"(x[i].y) : "l"(p + i * 128) : "memory");
    spin_guard(tries);
    float a = bf_lo(x[0].x), b = bf_hi(x[0].x), c = bf_lo(x[0].y), d = bf_hi(x[0].y);
    uint32_t t = x[0].x ^ tag;
#pragma unroll
    for (int i = 1; i < 8; i++) {
      a += bf_lo(x[i].x); b += bf_hi(x[i].x); c += bf_lo(x[i].y); d += bf_hi(x[i].y);
      asm("lop3.b32 %0, %0, %1, %2, 0xf6;" : "+r"(t) : "r"(x[i].x), "r"(tag));
    }
    bad = __any_sync(~0u, t & 1);
    const bool up = lane & 8;
    float u = (up ? c : a) + __shfl_xor_sync(~0u, up ? a : c, 8), v = (up ? d : b) + __shfl_xor_sync(~0u, up ? b : d, 8);
    if (shared) { u += __shfl_xor_sync(~0u, u, 4); v += __shfl_xor_sync(~0u, v, 4); }
    u += __shfl_xor_sync(~0u, u, 16);
    v += __shfl_xor_sync(~0u, v, 16);
    st_relaxed_if(dst, n < LAG && up ? m0 : pack2(u, v), !bad);
  } while (bad);
  if (shared) bar_arrive(B_WG2, 224);
  TR(TS0 + 3); TRV(TS0 + 2, tries);
  CNT((TS0 - 16) >> 2, tries);
}

constexpr int XR = 3;
__host__ __device__ constexpr int o_ks(int s) { return s & (s < 8 ? 3 : 7); }
constexpr uint32_t OPAT = 0x55555577u;
__host__ __device__ constexpr bool o_reg(int s) { return (OPAT >> s) & 1; }
__host__ __device__ constexpr int o_slot(int s) { int k = 0; for (int i = 0; i < s; i++) k += o_reg(i) == o_reg(s); return k; }
__device__ __forceinline__ int g_unit(int wg) {
  const int i = bid() - N_CHAIN;
  return i < 32 ? wg * 64 + i : 2 * i - 32 + wg;
}
__device__ __forceinline__ uint32_t pinned(uint32_t v) { return __shfl_sync(~0u, v, threadIdx.x & 31); }
template <class T> __device__ __forceinline__ T* pinned(T* p) { return (T*)__shfl_sync(~0u, (unsigned long long)p, threadIdx.x & 31); }
enum { CHAIN, GROLE, OROLE };
template <int ROLE, bool SYNC> __device__ __forceinline__ void load_box(const Params& P, uint32_t sb, bool regs, int wg, int i, uint32_t mb, bool on) {
  const int b = bid();
  int map, col = 0, ks = 0, c2 = 0, c3 = 0;
  uint32_t dst = wg * 73728;
  if (ROLE == CHAIN) {
    const int k = i - 1, st = __fns(regs ? OPAT : ~OPAT, 0, i) & 31;
    dst += i ? (17 + i) * 2048 : 0;
    if (wg || i == 0) { map = wg + i; col = b * 64; c3 = !regs; }
    else if (!regs && k >= 14) { map = 6; ks = b * 4 + k - 14; }
    else { map = 6; col = 64 + (st < 8 ? (st >> 2) * 64 : (st >> 3) * 128 + (b & 1) * 64); ks = (b * 4) ^ o_ks(st); }
  } else if (ROLE == GROLE) {
    const int q = g_unit(wg);
    map = ((q >> 5) + 1) % 3;
    if (i) { map += 3; col = (q & 31) * 128 + (i - 1) * 64; ks = 34; dst = G_W2 + wg * 4096 + (i - 1) * 2048; }
    else { map += 8; c2 = (q & 31) * 2; c3 = !regs; }
  } else {
    const int o = b - N_CHAIN - N_G, ksl = o / 3;
    map = 7; col = ((o % 3) * 3 + (wg + ksl) % 3) * 64; dst = (wg * (regs ? 24 : 20) + i) * 2048;
    ks = (ksl * 11 - max(ksl - 4, 0)) * 4 + (regs ? i / 3 * 5 + i % 3 * 2 : i < 16 ? i / 2 * 5 + 1 + i % 2 * 2 : i + 24);
    c3 = (ks & 1) * 2; ks >>= 1;
  }
  if (SYNC) { col = pinned(col); ks = pinned(ks); bar_sync(B_WG0 + wg, 256); }
  if (on) asm volatile("cp.async.bulk.tensor.5d.shared::cluster.global.tile.mbarrier::complete_tx::bytes [%0], [%1, {%2, %3, %4, %5, %6}], [%7];"
               :: "r"(sb + dst), "l"(&P.map[map]), "r"(col), "r"(0), "r"(c2), "r"(c3), "r"(ks), "r"(mb) : "memory");
}
template <int ROLE, bool SYNC = false> __device__ __forceinline__ void load_wg(const Params& P, uint32_t sb, bool regs, int wg, int quarter) {
  const int i = (threadIdx.x & 31) * 4 + quarter;
  const int n = ROLE == CHAIN ? 36 : ROLE == GROLE ? (regs ? 38 : 36) : regs ? 24 : bid() < N_CHAIN + N_G + 12 ? 20 : 16;
  const bool split = SYNC && wg == 0;
  const uint32_t mb = split && i ? sb + T_BAR : sb + W_BAR + wg * 8;
  load_box<ROLE, SYNC>(P, sb, regs, wg, i, mb, i < (ROLE == CHAIN ? (wg ? 2 : 19) : ROLE == GROLE ? n - 35 : n));
  if (i <= split) mbar_expect(mb, n * (split ? 1024 : 2048));
  __syncwarp();
}
__device__ __forceinline__ uint32_t near_half(uint32_t blk, uint32_t reader) {
  return __ldcg(g_near + (blk >> 3)) ^ (~blk & 1) ^ __ldcg(g_side + (blk >> 3)) ^ __ldcg(g_side + reader);
}

__device__ __forceinline__ uint32_t opaque_tid() { uint32_t t; asm volatile("mov.u32 %0, %%tid.x;" : "=r"(t)); return t; }
__device__ __forceinline__ void m_fetch(uint32_t sb, uint32_t src, uint32_t b, uint32_t mb) {
  bulk_load(sb + C_M + (b ? b * 4096 - 2048 : 0), (const unsigned char*)g_mimg + ((src ^ ((b & 1) * 4096)) + b * 8192), b ? 4096 : 2048, mb);
}
__device__ __forceinline__ uint32_t m_probe(uint32_t lane) { return lane * 32 + (lane & 4) * 4 + (lane >> 3) * 4; }
__device__ __forceinline__ uint32_t m_max(uint32_t a, uint32_t b) {
  return max(max(lds32(a), lds32(a + 1024)), max(lds32(b), lds32(b + 1024)));
}
template <int S0, int N> __device__ __forceinline__ void o_steps(float* d, const uint32_t* a) {
  constexpr int SD = o_ks(S0) != 0;
  if constexpr (o_reg(S0)) wg_rs16<SD>(d, a + (18 + o_slot(S0)) * 4, desc_n16(C_OI + o_ks(S0) * 512));
  else wg_ss16<SD>(d, desc_sw128(C_W + (18 + o_slot(S0)) * 2048), desc_n16(C_OI + o_ks(S0) * 512));
  if constexpr (N > 1) o_steps<S0 + 1, N - 1>(d, a);
}
template <int BASE, int KS, int N> __device__ __forceinline__ void m_steps(float* d, const uint32_t* a, uint32_t oa) {
  wg_rs16<KS != 0>(d, a + (BASE + KS / 2) * 4, desc_m(C_M + KS * 512));
  if constexpr (KS >= 36 - 2 * XR) wg_rs16<1>(d, a + (18 + XR + KS / 2) * 4, desc_m(C_M + KS * 512 + 512));
  else wg_ss16o<1, desc_sw128(C_W + (BASE + KS / 2) * 2048), desc_m(C_M + KS * 512 + 512)>(d, oa, 0);
  if constexpr (N > 2) m_steps<BASE, KS + 2, N - 2>(d, a, oa);
}

constexpr uint32_t VPAT = 0x15bbd249u;
template <int I, int R, int S> __device__ __forceinline__ void v_steps(float* d, const uint32_t* a) {
  constexpr bool reg = (VPAT >> I) & 1;
  if constexpr (reg) wg_rs16<1>(d, a + (18 + R) * 4, desc_m(C_M + R * 1024));
  else wg_ss16<1>(d, desc_sw128(C_W + (54 + S) * 2048), desc_m(C_M + S * 1024 + 512));
  if constexpr (I < 31) v_steps<I + 1, R + reg, S + !reg>(d, a);
  else static_assert(R + reg == 18, "pattern");
}

__device__ __forceinline__ void chain_proj(const Params& P, uint32_t sb) {
  const uint32_t c = chain_id(), h = c >> 1, j = c & 1, wid = __shfl_sync(~0u, threadIdx.x >> 5, 0), wg = wid >> 2, w = wid & 3;
  const uint32_t t = threadIdx.x & 127, lane = pinned(t & 31), mine = pinned(sb + t * 16), rb = mapa(sb, j ^ 1);
  const uint32_t theirs = pinned(rb + C_KM2 + w * 512 + lane * 4), oa = wg * 4608;
  uint32_t a[144 + 4 * XR];
  mbar_wait(sb + W_BAR + wg * 8, 0);
  if (threadIdx.x == 0) TS(23);
  load_frags<36>(a, sb + C_W + wg * 73728);
  fence_async_smem();
  bar_arrive(B_WG0 + wg, 256);
  if (threadIdx.x == 0) TS(24);
  bar_sync(B_WG2, 384);
  const uint32_t round = min(wid ^ 4, 5u), gdly = P.dly[8 + round], ps = t >> 2, pf = j * 16 + (ps >> 1);
  const bool shared = round < 3;
  uint4* const dsts = pinned(g_xb + (ps * 4096 + near_half(ps * 8, ps * 2) * 256 + c * 4 + (t & 3)));
  uint4* const dstf = pinned(g_xb + (pf * 4096 + 512 + near_half(pf * 8 + 1, pf * 2) * 256 + h * 8 + (t & 7)));
  const uint32_t* const gsrc = (const uint32_t*)g_xb + (h * 16384 + round % 3 * 4096 + near_half(h * 8 + !shared, h * 2) * 1024 +
                               (shared ? lane * 4 + j * 2 : 2048 + (lane & 24) * 4 + j * 16 + (lane & 7) * 2));
  uint32_t* gdst = g_mimg + (16384 + (lane >> 4) * 1024 +
                   (shared ? (round ? 1536 + round * 512 : 0) + c * 8 + (((lane >> 1) ^ c) & 4) + (lane & 3)
                           : (round - 1) * 2048 + c * 16 + (lane & 1) * 8 + (((lane >> 1) ^ (c * 2)) & 4) + ((lane >> 1) & 3)));
  const uint32_t m0 = __ldcg(gdst - 16384);
  mbar_wait(sb + W_BAR + wg * 8, 1);
  load_frags<XR>(a + 144, sb + C_W + wg * 73728 + (18 - XR) * 2048);
  bar_sync(B_INIT, 256);
  if ((threadIdx.x & 127) == 0) TS(4);

  uint32_t ring = 1;
#pragma unroll 1
  for (int n = 0; n < STEPS; n++) {
    float d[8], e[8];
    if (n + 1 == STEPS && !wg) { bar_arrive(B_QK, 416); break; }
#pragma unroll
    for (int i = 0; i < 8; i++) e[i] = 0.f;
    uint32_t redo = n + 1;
#pragma unroll 1
    do {
      mbar_wait(sb + CB_M, n & 1);
      wg_fence();
      m_steps<0, 0, 4>(d, a, oa);
      wg_commit();
      if (wg) { wg_fence(); m_steps<18, 0, 4>(e, a, 4608); wg_commit(); }
      if (wid == 0) TR(8);
      mbar_wait(sb + CB_M + 8, n & 1);
      wg_fence();
      m_steps<0, 4, 8>(d, a, oa);
      wg_commit();
      mbar_wait(sb + CB_MV, n & 1);
      asm volatile("{.reg .pred p; .reg .u32 t; ld.shared.u32 t, [%1]; setp.eq.u32 p, t, %0; selp.u32 %0, -1, 0, p;}" : "+r"(redo) : "r"(sb + C_BAD) : "memory");
    } while (redo);
    mbar_wait(sb + CB_MV + 8, n & 1);
    wg_fence();
    m_steps<0, 12, 8>(d, a, oa);
    wg_commit();
    mbar_wait(sb + CB_MV + 16, n & 1);
    wg_fence();
    m_steps<0, 20, 8>(d, a, oa);
    wg_commit();
    mbar_wait(sb + CB_MV + 24, n & 1);
    wg_fence();
    m_steps<0, 28, 8>(d, a, oa);
    wg_commit();
    wg_wait<0>();
    if (w == 0) TR(6 + wg);
    const uint32_t f0 = pack2(d[0], d[1]), f1 = pack2(d[4], d[5]), f2 = pack2(d[2], d[3]), f3 = pack2(d[6], d[7]);
    stsm4(mine + C_QM + wg * 2048, f0, f1, f2, f3);
    bar_arrive(B_QK, 416);
    const uint32_t tag = (n & 1) ^ 1;
    if (n == 0) mbar_wait(sb + T_BAR, 0);
    if (wg) {
      if (n + 1 < STEPS) bar_sync(B_S, 256);
      wg_fence();
      v_steps<0, 2, 2>(e, a);
      wg_commit();
      const uint32_t k0 = j ? f0 : f1, k1 = j ? f2 : f3;
      mbar_wait(sb + CB_SX, n & 1);
      wg_wait<0>();
      if (w == 0) TR(11);
      const uint32_t v0 = pack2(e[0], e[1]), v1 = pack2(e[4], e[5]), v2 = pack2(e[2], e[3]), v3 = pack2(e[6], e[7]);
      stsm4(mine + C_VM, v0, v1, v2, v3);
      bar_arrive(B_V, 256);
      st_async1(theirs, k0, rb + CB_XX);
      st_async1(theirs + 256, k1, rb + CB_XX);
      st_async1(theirs + 128, j ? v0 : v1, rb + CB_XX);
      st_async1(theirs + 384, j ? v2 : v3, rb + CB_XX);
      if (n + 1 == STEPS) break;
      bar_sync(B_O, 256);
      fence_async_smem();
      wg_fence();
#pragma unroll
      for (int ks = 0; ks < 4; ks++) {
        if (ks == 0) wg_ss16<0>(d, desc_sw128(C_W + 32 * 2048), desc_n16(C_OI));
        else wg_ss16<1>(d, desc_sw128(C_W + (32 + ks) * 2048), desc_n16(C_OI + ks * 512));
      }
      wg_commit();
      bar_arrive(B_X, 256);
      if (w == 0) TR(0);
      wg_wait<0>();
      store_partial(dsts, pack_partial(d, tag));
      bar_arrive(B_M, 160);
      if (w == 0) TR(1);
    } else {
      bar_sync(B_X, 256);
      wg_fence();
      o_steps<0, 4>(d, a);
      wg_commit();
      o_steps<4, 4>(e, a);
      wg_commit();
      wg_wait<1>();
      store_partial(dsts + 1024, pack_partial(d, tag));
      if (w == 0) TR(2);
      wg_wait<0>();
      store_partial(dsts + 2048, pack_partial(e, tag));
      if (w == 0) TR(3);
      wg_fence();
      o_steps<8, 4>(d, a);
      wg_commit();
      bar_sync(B_T, 256);
      if (w == 0) { TRV(61, 0); TR(12); }
      wg_fence();
      o_steps<12, 4>(d, a);
      wg_commit();
      o_steps<16, 8>(e, a);
      wg_commit();
      wg_wait<1>();
      store_partial(dstf, pack_partial(d, tag));
      if (w == 0) TR(4);
      wg_fence();
      o_steps<24, 8>(d, a);
      wg_commit();
      wg_wait<1>();
      store_partial(dstf + 1024, pack_partial(e, tag));
      bar_arrive(B_OE, 256);
      if (w == 0) TR(5);
      wg_wait<0>();
      store_partial(dstf + 2048, pack_partial(d, tag));
      if (w == 0) TR(15);
    }
    if ((wid ^ 4) < 6) {
      mbar_wait(sb + CB_REF, n & 1);
      wait_until(lds32(sb + C_REF), gdly);
      gather_reduce(gsrc, gdst, m0, shared, tag, lane, sb, n, 16 + round * 4);
      if (++ring == MRING) { ring = 0; gdst -= MRING * 16384; }
      gdst += 16384;
    }
  }
}

template <int KS> __device__ __forceinline__ void x_scores(float* s, float* sm, const uint4* q, uint32_t ok, uint32_t om) {
  wg_rs32o<KS != 0, desc_sw64(C_KV + KS * 1024)>(s, q[KS].x, q[KS].y, q[KS].z, q[KS].w, ok);
  wg_rs8o<KS != 0, desc_n16(C_KM + KS * 512)>(sm, q[KS].x, q[KS].y, q[KS].z, q[KS].w, om);
  if constexpr (KS < 3) x_scores<KS + 1>(s, sm, q, ok, om);
}

__device__ __forceinline__ void chain_attn(const Params& P, uint32_t sb) {
  const int c = chain_id(), j = c & 1;
  const int tid = threadIdx.x, lane = tid & 31, w = __shfl_sync(~0u, (tid >> 5) & 3, 0);
  const int l = w >> 1, u = w & 1;
  const uint32_t rb = mapa(sb, j ^ 1);
  const float sc = 0.08838834764831845f * 1.4426950408889634f;
  const uint32_t ones = 0x3F803F80u, sx = C_SX + l * 1280;
  const uint32_t km_off = C_KM + (lane >> 3) * 256 + l * 128 + (lane & 7) * 16;
  const uint32_t qm_off = C_QM + (lane >> 4) * 256 + l * 128 + (lane & 7) * 16, kmu = pinned(sb + km_off + u * 1024);
  const uint32_t kv_off = C_KV + l * 4096 + (lane & 15) * 64 + (((lane >> 4) ^ (u * 2) ^ ((lane >> 1) & 3)) << 4);

  load_wg<CHAIN, true>(P, sb, false, 1, w);
  if (lane == 0) mbar_arrive(sb + CB_M);
#pragma unroll 1
  for (int n = 0; n < STEPS; n++) {
    const uint32_t kvb = sb + kv_off + (n & 1) * 16384;
    mbar_wait(sb + CB_FULL + (n & 1) * 8, (n >> 1) & 1);
    if (n < 3 && tid == 256) TS(n ? 20 + n : 5);
    __syncwarp();
    {
      uint32_t km[8];
      uint4 kx[8];
#pragma unroll
      for (int i = 0; i < 8; i++) ldsm4t(kx[i].x, kx[i].y, kx[i].z, kx[i].w, (kvb ^ ((i & 1) * 32)) + (i >> 1) * 1024);
      mbar_wait_step<1>(sb + CB_VF, n);
      if (w == 1) TRD(60, kx[7].x);
      bar_sync(B_QK, 416);
      if (n + 1 == STEPS) {
        st_async4(rb + sx + u * 512 + lane * 16, 0.f, 0.f, 0.f, 0.f, rb + CB_SX);
        st_async1(rb + sx + 1024 + u * 128 + lane * 4, 0, rb + CB_SX);
        bar_sync(B_V, 256);
      } else {
      uint32_t qm[16];
#pragma unroll
      for (int ks = 0; ks < 4; ks++) ldsm4t(qm[4 * ks], qm[4 * ks + 1], qm[4 * ks + 2], qm[4 * ks + 3], sb + qm_off + ks * 512);
      ldsm4t(km[0], km[1], km[2], km[3], sb + km_off);
      ldsm4t(km[4], km[5], km[6], km[7], sb + km_off + 1024);
      float s[5][4];
      uint4 vx[4];
#pragma unroll
      for (int i = 0; i < 5; i++) { s[i][0] = s[i][1] = s[i][2] = s[i][3] = 0.f; }
#pragma unroll
      for (int ks = 0; ks < 4; ks++) {
        const uint32_t* q = qm + 4 * ks;
        if (ks == 1 || ks == 2) {
#pragma unroll
          for (int i = 2 * ks - 2; i < 2 * ks; i++) ldsm4(vx[i].x, vx[i].y, vx[i].z, vx[i].w, ((sb + kv_off) ^ ((i & 1) * 32)) + 8192 + (2 * u + (i >> 1)) * 1024);
        }
        mma16(s[1], q[0], q[1], q[2], q[3], kx[2 * ks].x, kx[2 * ks].y);
        mma16(s[2], q[0], q[1], q[2], q[3], kx[2 * ks].z, kx[2 * ks].w);
        mma16(s[0], q[0], q[1], q[2], q[3], km[2 * ks], km[2 * ks + 1]);
        mma16(s[3], q[0], q[1], q[2], q[3], kx[2 * ks + 1].x, kx[2 * ks + 1].y);
        mma16(s[4], q[0], q[1], q[2], q[3], kx[2 * ks + 1].z, kx[2 * ks + 1].w);
      }
      st_async4(rb + sx + u * 512 + lane * 16, s[1][0], s[1][1], s[2][0], s[2][1], rb + CB_SX);
      st_async1(rb + sx + 1024 + u * 128 + lane * 4, __float_as_uint(u ? s[0][1] : s[0][0]), rb + CB_SX);
      bar_arrive_after<B_S, 256>(__float_as_uint(s[3][0]), __float_as_uint(s[4][0]));
      mbar_wait_step<2>(sb + CB_SX, n);
      const uint4 p0 = lds128(sb + sx + u * 512 + lane * 16), p1 = lds128(sb + sx + (u ^ 1) * 512 + lane * 16);
      const uint2 p2 = make_uint2(lds32(sb + sx + 1024 + lane * 4), lds32(sb + sx + 1152 + lane * 4));
      float t[10] = {s[0][0] + __uint_as_float(p2.x), s[0][1] + __uint_as_float(p2.y),
                     s[1][0] + __uint_as_float(p0.x), s[1][1] + __uint_as_float(p0.y),
                     s[2][0] + __uint_as_float(p0.z), s[2][1] + __uint_as_float(p0.w),
                     s[3][0] + __uint_as_float(p1.x), s[3][1] + __uint_as_float(p1.y),
                     s[4][0] + __uint_as_float(p1.z), s[4][1] + __uint_as_float(p1.w)};
      float mx = fmaxf(fmaxf(fmaxf(fmaxf(t[2], t[3]), fmaxf(t[4], t[5])), fmaxf(fmaxf(t[6], t[7]), fmaxf(t[8], t[9]))), fmaxf(t[0], t[1]));
      mx = fmaxf(fmaxf(mx, __shfl_xor_sync(~0u, mx, 1)), fmaxf(__shfl_xor_sync(~0u, mx, 2), __shfl_xor_sync(~0u, mx, 3)));
      const float ms = -mx * sc;
#pragma unroll
      for (int i = 0; i < 10; i++) t[i] = ex2(fmaf(t[i], sc, ms));
      uint32_t p[5];
#pragma unroll
      for (int i = 0; i < 5; i++) p[i] = pack2(t[2 * i], t[2 * i + 1]);
      p[1] |= (p[0] & p[3] & p[4]) & 0x80008000u;
      float o[2][4], z[4] = {0.f, 0.f, 0.f, 0.f};
      mma16(z, ones, ones, ones, ones, p[1], p[2]);
#pragma unroll
      for (int i = 0; i < 2; i++) {
        o[i][0] = o[i][1] = o[i][2] = o[i][3] = 0.f;
        mma16(o[i], vx[2 * i].x, vx[2 * i].y, vx[2 * i].z, vx[2 * i].w, p[1], p[2]);
      }
      mma16(z, ones, ones, ones, ones, p[3], p[4]);
#pragma unroll
      for (int i = 0; i < 2; i++) mma16(o[i], vx[2 * i + 1].x, vx[2 * i + 1].y, vx[2 * i + 1].z, vx[2 * i + 1].w, p[3], p[4]);
      mma8(z, ones, ones, p[0]);
      bar_sync_after<B_V, 256>(p[1]);
      ldsm4(km[0], km[1], km[2], km[3], kmu + (C_VM - C_KM));
      mma8(o[0], km[0], km[1], p[0]);
      mma8(o[1], km[2], km[3], p[0]);
      const float i0 = rcp(z[0]), i1 = rcp(z[1]);
      const uint32_t oo = C_OI + u * 1024 + l * 128 + lane * 4;
      uint32_t ow[4];
#pragma unroll
      for (int i = 0; i < 2; i++) { ow[2 * i] = pack2(o[i][0] * i0, o[i][1] * i1); ow[2 * i + 1] = pack2(o[i][2] * i0, o[i][3] * i1); }
      stsm4(kmu + (C_OI - C_KM), ow[0], ow[1], ow[2], ow[3]);
      bar_arrive(B_O, 256);
#pragma unroll
      for (int i = 0; i < 4; i++) st_async1(rb + oo + 2048 + i * 256, ow[i], rb + CB_OX);
      }
    }
    {
      const uint32_t lane = opaque_tid() & 31, own = ((n & 1) * 16384 + j * 4096) >> 4;
      float s[16], sm[4], r[16], rm[4];
      {
        uint4 q[4];
        mbar_wait_step<3>(sb + CB_Q, n);
#pragma unroll
        for (int ks = 0; ks < 4; ks++)
          ldsm4t(q[ks].x, q[ks].y, q[ks].z, q[ks].w, sb + C_Q + (lane & 8) * 512 + ks * 1024 + (lane & 16) * 32 + (lane & 7) * 64 + (((w ^ (lane >> 1)) & 3) << 4));
        mbar_wait_step<3>(sb + CB_XX, n);
        if (n + 1 < STEPS) mbar_wait_step<3>(sb + CB_OX, n);
        fence_async_smem();
        if (n + 1 < STEPS) { bar_arrive(B_T, 256); bar_sync(B_OE, 256); }
        if (w == 1) { TRV(61, 0); TR(9); }
        wg_fence();
        x_scores<0>(s, sm, q, own, j * 8);
        x_scores<0>(r, rm, q, (C_KV2 - C_KV) >> 4, (C_KM2 - C_KM) >> 4);
        wg_commit();
        wg_wait<0>();
      }
      const float neg = -1e9f * 11.313708498984761f;
      const int tok = (lane & 24) + 2 * w + ((lane >> 2) & 1), lim = tok - 8 * (int)(lane & 3);
      float t[10] = {sm[0] + rm[2], sm[1] + rm[3]};
#pragma unroll
      for (int i = 0; i < 8; i++) t[2 + i] = i > lim ? neg : s[(i >> 1) * 4 + (i & 1)] + r[(i >> 1) * 4 + (i & 1) + 2];
      float mx = fmaxf(fmaxf(fmaxf(fmaxf(t[2], t[3]), fmaxf(t[4], t[5])), fmaxf(fmaxf(t[6], t[7]), fmaxf(t[8], t[9]))), fmaxf(t[0], t[1]));
      mx = fmaxf(fmaxf(mx, __shfl_xor_sync(~0u, mx, 1)), fmaxf(__shfl_xor_sync(~0u, mx, 2), __shfl_xor_sync(~0u, mx, 3)));
      const float ms = -mx * sc;
#pragma unroll
      for (int i = 0; i < 10; i++) t[i] = ex2(fmaf(t[i], sc, ms));
      uint32_t p[5];
#pragma unroll
      for (int i = 0; i < 5; i++) p[i] = pack2(t[2 * i], t[2 * i + 1]);
      float z = ((t[0] + t[1]) + (t[2] + t[3])) + ((t[4] + t[5]) + (t[6] + t[7])) + (t[8] + t[9]);
      const uint32_t row = sb + C_OS + tok * 128 + (((lane & 3) ^ (tok & 7)) << 4);
      z = rcp((z + __shfl_xor_sync(~0u, z, 1)) + (__shfl_xor_sync(~0u, z, 2) + __shfl_xor_sync(~0u, z, 3)));
      float o[32];
      bar_sync_after<B_WG2, 224>(n + 1 < STEPS ? __float_as_uint(z) : 0xfff12345u);
      wg_fence();
      wg_rs64o<0, desc_sw64(C_KV + 8192)>(o, p[1], 0, p[2], 0, j * 256);
      wg_rs64o<1, desc_sw64(C_KV + 8192 + 32)>(o, p[3], 0, p[4], 0, j * 256);
      wg_rs64o<1, mkdesc(C_VM, 128, 256, 0)>(o, p[0], 0, 0, 0, j * 8);
      wg_rs64o<1, desc_sw64(C_KV2 + 4096)>(o, 0, p[1], 0, p[2], 0);
      wg_rs64o<1, desc_sw64(C_KV2 + 4096 + 32)>(o, 0, p[3], 0, p[4], 0);
      wg_rs64o<1, mkdesc(C_VM2, 128, 256, 0)>(o, 0, p[0], 0, 0, 0);
      wg_commit();
      if (elect()) mbar_arrive(sb + CB_M);
      wg_wait<0>();
#pragma unroll
      for (int i = 0; i < 4; i++) {
        const float* v = o + 16 * (i & 1) + (i & 2);
        sts128((row ^ ((i & 1) * 64)) + (i & 2) * 2048,
               make_uint4(pack2(v[0] * z, v[1] * z), pack2(v[4] * z, v[5] * z), pack2(v[8] * z, v[9] * z), pack2(v[12] * z, v[13] * z)));
      }
      bar_arrive(B_G, 160);
      if (n + 1 < STEPS) bar_arrive(B_R, 160);
      if (w == 1) TR(10);
    }
  }
  if ((threadIdx.x & 127) == 0) TS(6);
}

__device__ __forceinline__ void chain_aux(const Params& P, uint32_t sb) {
  const uint32_t c = chain_id(), j = c & 1, lane = threadIdx.x & 31, w = __shfl_sync(~0u, (threadIdx.x >> 5) & 3, 0);
  load_wg<CHAIN, true>(P, sb, false, 0, w);
  if (threadIdx.x == 384) TS(25);
  if (threadIdx.x == 384) grid_wait(1, lds32(sb + S_GEN));
  bar_sync(B_WG2, 384);
  if (threadIdx.x == 384) TS(13);
  if (w == 0) {
    const uint32_t* fg = g_fl + FL_G + near_half(XB_F, c) * 1024 + (c >> 1) * 8;
#pragma unroll 1
    for (int n = 0; n < STEPS; n++) {
      const unsigned char* blk = g_qkv + (uint32_t)((n % QRING) * (N_CHAIN * 24576));
      const uint32_t t1 = clk(), kb = sb + CB_FULL + (n & 1) * 8, kv = sb + C_KV + (n & 1) * 16384;
      uint32_t t0 = t1 - 100000, x = 0;
      if (n > 0) {
        wait_until(t1, KMIN);
        do asm volatile("ld.relaxed.gpu.global.u32 %0, [%1];" : "=r"(x) : "l"(fg) : "memory"); while (x <= n && clk() - t1 < KWIN);
        if (x > n) {
          asm volatile("fence.acquire.gpu;" ::: "memory");
          fence_async_global();
          if (elect()) { mbar_expect(kb, 8192); bulk_load(kv, blk + c * 24576, 8192, kb); }
        }
        T3(0); CNT(12, 1 + (x <= n));
        mbar_wait(sb + CB_REF, (n - 1) & 1);
        t0 = lds32(sb + C_REF);
        wait_until(t0, DLYV - 500);
      }
      wait_flags(fg + min(lane, 2u) * 256, n + 1);
      T3(2);
      fence_async_global();
      if (n > 0) bar_sync(B_R, 160);
      if (lane < 3) mbar_expect(sb + CB_SX + lane * 8, lane ? 2048 : 2560);
      __syncwarp();
      wait_until(t0, DLYV);
      if (elect()) {
        if (x <= n) { mbar_expect(kb, 8192); bulk_load(kv, blk + c * 24576, 8192, kb); }
        mbar_expect(sb + CB_VF, 8192);
        bulk_load(sb + C_KV + 8192, blk + (c * 24576 + 8192), 8192, sb + CB_VF);
        mbar_expect(sb + CB_Q, 16384);
        wait_until(t0, DLYK);
        bulk_load(sb + C_Q, blk + (c * 24576 + 16384), 8192, sb + CB_Q);
        bulk_load(sb + C_KV2, blk + ((c ^ 1) * 24576 + j * 4096), 4096, sb + CB_Q);
        bulk_load(sb + C_KV2 + 4096, blk + ((c ^ 1) * 24576 + 8192 + j * 4096), 4096, sb + CB_Q);
      }
      T3(1);
      T3(3);
    }
  } else {
    const uint32_t near = __ballot_sync(~0u, near_half(XB_M + min(lane, MRING - 1u) * 8, c));
    uint32_t ring = 0;
    if (w > 1) {
      const uint32_t odd = w & 1, chk = pinned(sb + C_M + odd * 2048 + m_probe(lane)), again = sb + CB_MV + 32 + odd * 8;
      const bool one = elect();
      uint32_t mph = 0;
#pragma unroll 1
      for (int n = 0; n <= STEPS; n++) {
#pragma unroll
        for (int k = 0; k < 3; k++) {
          if (n == STEPS || (k == 2 && odd)) break;
          const uint32_t b = 2 * k + odd, at = chk + (k ? k * 8192 - 2048 + odd * 2048 : 0);
          uint32_t mb = sb + CB_M + b * 8, ph = n & 1;
          int it = 1;
          while (true) {
            mbar_wait(mb, ph);
            const bool bad = __any_sync(~0u, m_max(at, b ? at + 2048 : at) == SENT);
            if (one && !bad) mbar_arrive(sb + CB_MV + (b > 1 ? b * 8 - 8 : 0));
            if (!bad) break;
            mb = again; ph = mph; mph ^= 1;
            if (one) {
              if (k == 0) sts32(sb + C_BAD, n + 1);
              mbar_expect(mb, b ? 4096 : 2048);
              m_fetch(sb, ring * 65536 + ((near >> ring) & 1) * 4096, b, mb);
            }
            __syncwarp();
            spin_guard(it);
          }
          TR(41 + b * 4); CNT(6 + b, it);
        }
        ring = ring + 1 == MRING ? 0 : ring + 1;
        if (!odd) {
          if (n < STEPS) { TRSYNC(); TRDUMP(n - 2); }
        } else {
          unsigned char* o = g_oimg + (uint32_t)(((n - 1) & (RING - 1)) * (N_CHAIN * 8192) + j * 4096);
          if (n > 0) bar_sync(B_G, 160);
          fence_async_smem();
          if (one) {
            if (n > 0) {
              bulk_store(o + c * 8192, sb + C_OS, 4096);
              bulk_store(o + (c ^ 1) * 8192, sb + C_OS + 4096, 4096);
              asm volatile("cp.async.bulk.commit_group;\ncp.async.bulk.wait_group.read 0;" ::: "memory");
              { const int n_ = n - 1; { const int n = n_; T3(4); (void)n; } }
            }
            mbar_arrive(sb + CB_Q);
            if (n > 0) {
              bulk_done_inc(g_fl + FL_O + c);
              { const int n_ = n - 1; { const int n = n_; T3(5); (void)n; } }
            }
          }
          __syncwarp();
        }
      }
    } else {
      const uint32_t* ts = g_fl + FL_SYNC + near_half(XB_F + 1, c) * 1024 + lane * 2;
      uint32_t t0 = clk() - 100000, last = 0;
      int lag = 0;
#pragma unroll 1
      for (int n = 0; n < STEPS; n++) {
        const uint32_t src = ring * 65536 + ((near >> ring) & 1) * 4096;
        if (lane < 5) mbar_expect(sb + CB_M + lane * 8, lane ? 4096 : 2048);
        __syncwarp();
        if (elect()) {
#pragma unroll
          for (int b = 0; b < 5; b++) {
            wait_until(t0, P.dly[14 + b]);
            m_fetch(sb, src, b, sb + CB_M + b * 8);
            TR(40 + b * 4);
          }
        }
        __syncwarp();
        ring = ring + 1 == MRING ? 0 : ring + 1;
        uint32_t va, vb;
        const uint32_t off = timer_offset<4>(), tag = (uint32_t)(n + 1) << 28;
        if (n > 1) lag += (int)(off - last) - (lag >> 2);
        last = off;
        const uint32_t mine = min(max((lag >> 3) + 256, 0), 511);
        bar_sync(B_QK, 416);
        if (n + 1 == STEPS) break;
        sts32(sb + C_REF + 4, 0);
        const uint32_t c0 = clk(), stamp = c0 + off;
        st_relaxed_if(g_fl + FL_SYNC + lane * 1024 + c, tag | (mine << 19) | (stamp & 0x7FFFF), lane < 2);
        TR(13);
        wait_until(c0, DLYS);
        int it = 0;
        do {
          asm volatile("ld.relaxed.gpu.global.v2.u32 {%0,%1}, [%2];" : "=r"(va), "=r"(vb) : "l"(ts) : "memory");
          spin_guard(it);
        } while (__any_sync(~0u, ((va ^ tag) | (vb ^ tag)) >> 28));
        const int late = __reduce_max_sync(~0u, max((int)((va - stamp) << 13), (int)((vb - stamp) << 13))) >> 13;
        const uint32_t fast = min(((__reduce_max_sync(~0u, max(va, vb)) >> 19) & 511) - mine, 100u);
        t0 = c0 + min((uint32_t)late, clk() - c0);
        if (elect()) {
          sts32(sb + C_REF, t0 + (fast * 9 >> 3));
          mbar_arrive(sb + CB_REF);
        }
        st_relaxed_if(g_fl + FL_TICK + lane * 1024, (uint32_t)(n + 1) << 24 | ((t0 + off) & 0xFFFFFF), c == 0 && lane < 2);
        t0 += fast * 13 >> 3;
        TRV(59, fast);
        TR(14); CNT(11, it);
        bar_sync(B_M, 160);
      }
    }
  }
}

template <int WG>
__device__ __forceinline__ void g_math(const Params& P, uint32_t sb) {
  const int q = g_unit(WG);
  const int lane = threadIdx.x & 31, w = (threadIdx.x >> 5) & 3;
  uint32_t a[136];
  {
    const uint32_t stage = sb + G_W + WG * 73728;
    mbar_wait(sb + W_BAR + WG * 8, 0);
    if (threadIdx.x == 0) TS(23);
    load_frags<34>(a, stage);
    fence_async_smem();
    bar_sync(B_WG0 + WG, 128);
    if (threadIdx.x == 0) TS(24);
    load_wg<GROLE>(P, sb, false, WG, w);
    if (threadIdx.x == 0) TS(25);
    mbar_wait(sb + W_BAR + WG * 8, 1);
  }
  if ((threadIdx.x & 127) == 0) TS(4);
  const uint32_t off0 = (q & 31) * 49152 + (q >> 5) * 8192 + w * 1024 + (lane >> 2) * 64 + (((lane ^ (lane >> 3)) & 3) << 4);
  const uint32_t isq = q >> 6;
#pragma unroll 1
  for (int n = 0; n < STEPS; n++) {
    float d0[32], d1[32];
    if (WG == 0 && n >= LOCK0) bar_sync(B_OE, 160);
    if (n > 0) bar_sync(B_V + WG, 256);
#pragma unroll
    for (int ch = 0; ch < 9; ch++) {
      mbar_wait(sb + G_BAR + ch * 8, n & 1);
      if (ch == 0) { if ((threadIdx.x & 127) == 0) T3(5 + WG * 3); __syncwarp(); }
      if (ch == 4) { if ((threadIdx.x & 127) == 0) T3(6 + WG * 3); __syncwarp(); }
      if (ch == 8 && (WG == 0 ? n > 0 : n + 1 < STEPS)) bar_arrive(B_V + (WG ^ 1), 256);
      wg_fence();
#pragma unroll
      for (int kk = 0; kk < 4; kk++) {
        const int i = ch * 4 + kk;
        float* d = i & 1 ? d1 : d0;
        const uint64_t db = desc_sw128(G_RING + ch * 8192 + (kk & 2) * 32);
        if (i < 2) wg_rs64<0>(d, a + i * 4, db);
        else if (i < 34) wg_rs64<1>(d, a + i * 4, db);
        else wg_ss64<1>(d, desc_sw128(G_W2 + WG * 4096 + (i - 34) * 2048), db);
        wg_ss64<1>(d, desc_sw128(G_W + WG * 73728 + i * 2048), db + 2);
      }
      wg_commit();
      if (ch > 0) { wg_wait<1>(); if (lane == 0) mbar_arrive(sb + G_BAR + 128 + (ch - 1) * 8); }
    }
    wg_wait<0>();
    if (lane == 0) mbar_arrive(sb + G_BAR + 128 + 8 * 8);
    if ((threadIdx.x & 127) == 0) T3(7 + WG * 3);
    __syncwarp();
    uint32_t tw = clk() + (n == 0 ? 0u - 100000u : WG ? 0u : DLYW);
    unsigned char* base = g_qkv + (size_t)(n & (QRING - 1)) * (N_CHAIN * 24576);
#pragma unroll
    for (int i = 0; i < 8; i++) {
      const float* d = (i < 4 ? d0 : d1) + 8 * (i & 2) + 2 * (i & 1);
      wait_until(tw, 0); tw += P.dly[2 + WG];
      *(uint4*)(base + (off0 + (i < 2 ? 0 : i < 4 ? 4096 + isq * 24576 : i < 6 ? 24576 - isq * 20480 : 28672 - isq * 4096)) + (i & 1) * 512) =
        make_uint4(pack2(d[0], d[1]), pack2(d[4], d[5]), pack2(d[8], d[9]), pack2(d[12], d[13]));
    }
    bar_sync(B_M + WG, 160);
  }
}

__device__ __forceinline__ void fill16(void* p, uint32_t v) {
  asm volatile("st.global.v4.u32 [%0], {%1,%1,%1,%1};" :: "l"(p), "r"(v) : "memory");
}
__device__ __forceinline__ void g_load(const Params& P, uint32_t sb) {
  const int lane = threadIdx.x & 31, w = __shfl_sync(~0u, (threadIdx.x >> 5) & 3, 0);
  if (w == 2) return;
  if (w < 2) { bar_sync(15, 192); fence_async_smem(); }
  uint32_t fl = 0;
#pragma unroll 1
  for (int n = w == 3 ? LOCK0 : 0; n < STEPS; n++) {
    if (w && n == LOCK0) { grid_wait(1, lds32(sb + S_GEN)); fl = near_half(XB_F, bid()) * 1024; }
    if (w == 3) {
      const uint32_t tag = (uint32_t)(n - LOCK0 + 1) << 24;
      uint32_t v; int it = 0;
      do { asm volatile("ld.relaxed.gpu.global.u32 %0, [%1];" : "=r"(v) : "l"(g_fl + fl + FL_TICK) : "memory"); spin_guard(it); } while (v < tag);
      const uint32_t off = timer_offset<2>(), now = clk(), t0 = now - ((v ^ tag) >> 24 ? DLYG : (now + off - v) & 0xFFFFFF);
      asm volatile("fence.acquire.gpu;" ::: "memory");
      if (lane == 0) T3(11);
      __syncwarp();
      wait_until(t0, DLYG);
      if (lane == 0) T3(4);
      bar_sync(B_OE, 160);
      continue;
    }
    if (w == 0 || n == 0) {
      if (n < NSEG) wait_flags(g_lnflag + n * 16 + (lane & 1) * 8, 1);
    } else if (n >= LAG) {
      wait_flags(g_fl + fl + FL_F + (lane & 1) * 8, n - LAG + 1);
    }
    if (w) { if (lane == 0) T3(12); bar_sync(B_X, 96); }
    fence_async_global();
    const unsigned char* src = g_lnimg + (uint32_t)((w ? (n >= LAG ? NSEG + n - LAG : 0) : min(n, NSEG - 1)) * 36864);
#pragma unroll 1
    for (int ch = 0; ch < 9; ch++) {
      const uint32_t full = sb + G_BAR + ch * 8;
      mbar_wait(full + 128, (n & 1) ^ 1);
      if (elect()) {
        mbar_expect(full, 4096);
        bulk_load(sb + G_RING + ch * 8192 + w * 4096, src + ch * 4096, 4096, full);
      }
    }
  }
}

__device__ __forceinline__ void g_aux(const Params& P, uint32_t sb) {
  const int lane = threadIdx.x & 31, w = (threadIdx.x >> 5) & 3;
  if (w == 1 || w == 2) {
    const int q = g_unit(w - 1);
    uint32_t* f = g_fl + FL_G + q * 8;
#pragma unroll 1
    for (int n = 0; n < STEPS; n++) {
      const uint32_t ln = opaque_tid() & 31;
      uint4* z = (uint4*)g_oacc + (uint32_t)(((n + 1) % ARING) * (16 * DM) + q * 96 + ln);
      fill16(z, 0); fill16(z + 32, 0); fill16(z + 64, 0);
      if (n + 3 >= MRING && q < 80) fill16((uint4*)g_mimg + (uint32_t)(((n + 3) % MRING) * 4096 + q * 32 + ln), SENT);
      bar_sync(B_M + (w - 1), 160);
      if (lane == 0) { T3(w * 2 - 2); fence_async_global(); flag_release(f, n + 1); T3(w * 2 - 1); }
      __syncwarp();
    }
  } else {
    const uint32_t u = (bid() - N_CHAIN) * 2 + (w & 1), r = u / 36 * 16 + (u & 3) * 4 + (lane >> 3);
    uint32_t o = r * (DM / 8) + (u % 36 >> 2) * 8 + ((lane & 7) ^ ((r >> 1) & 3)), fl = 0;
#pragma unroll 1
    for (int k = -LAG - 1; k < STEPS; k++) {
      if (k < NSEG - 1) bar_sync(B_X, 96);
      if (k < LAG || u >= 72) continue;
      if (k == NSEG - 1) { fl = near_half(XB_F, bid()) * 1024; wait_flags(g_fl + fl + FL_F + (lane & 1) * 8, NSEG + 1); }
      const uint4 x = __ldcg((const uint4*)P.out + o);
      if (k >= NSEG - 1) wait_flags(g_fl + fl + FL_OCNT + (max(k, NSEG) % OCRING) * 8, N_O * 3 * (max(k, NSEG) / OCRING + 1));
      const float4* a = (const float4*)g_oacc + ((k % ARING) * (16 * DM) + 8 * DM + u * 64 + lane * 2);
      const float4 p = __ldcg(a), v = __ldcg(a + 1);
      ((uint4*)P.out)[o] = make_uint4(badd2(x.x, pack2(p.x, p.y)), badd2(x.y, pack2(p.z, p.w)), badd2(x.z, pack2(v.x, v.y)), badd2(x.w, pack2(v.z, v.w)));
      o += 4 * DM;
    }
    if ((threadIdx.x & 127) == 0) TS(7);
  }
}

template <int WG, bool HALF, int KS, int N> __device__ __forceinline__ void o_mma(float* d, const uint32_t* a, uint32_t ob) {
  constexpr uint64_t db = desc_sw128(O_RING + (KS >> 2) * 8192 + (KS & 3) * 32);
  constexpr uint64_t da = desc_sw128(O_W + WG * 40960 + (KS < 40 ? KS / 5 * 2 + KS % 5 / 2 : KS - 24) * 2048);
  if constexpr (KS < 40 && !(KS % 5 & 1)) {
    const uint32_t* r = a + (KS / 5 * 3 + KS % 5 / 2) * 4;
    if constexpr (HALF) wg_rs32k<KS != 0, db>(d, r[0], r[1], r[2], r[3], ob); else wg_rs64<KS != 0>(d, r, db);
  } else {
    if constexpr (HALF) wg_ss32k<da, db>(d, ob); else wg_ss64<1>(d, da, db);
  }
  if constexpr (N > 1) o_mma<WG, HALF, KS + 1, N - 1>(d, a, ob);
}
template <int WG, bool HALF, int GR> __device__ __forceinline__ void o_groups(float* d, const uint32_t* a, uint32_t sb, int n, bool more) {
  const uint32_t ob = n < NSEG ? 0 : 256;
  mbar_wait(sb + O_BAR + GR * 8, n & 1);
  if (GR == 0) { if ((threadIdx.x & 127) == 0) T3(13 + WG); __syncwarp(); }
  if (GR == (WG == 0 ? 2 : 4) && (WG < 2 || n + 1 < STEPS)) bar_arrive(B_V + (WG + 1) % 3, 256);
  wg_fence();
  o_mma<WG, HALF, GR * 8, 8>(d, a, ob);
  if (GR == 4 && more) o_mma<WG, HALF, 40, 4>(d, a, ob);
  wg_commit();
  if (GR > 0) { wg_wait<1>(); if ((threadIdx.x & 31) == 0) mbar_arrive(sb + O_BAR + 120 + GR * 8); }
  if constexpr (GR < 4) o_groups<WG, HALF, GR + 1>(d, a, sb, n, more);
}
template <int WG, bool HALF> __device__ __forceinline__ void o_step(const uint32_t* a, uint32_t sb, uint32_t st0, int n, bool more) {
  float d[HALF ? 16 : 32];
  if (WG > 0 || n > 0) bar_sync(B_V + WG, 256);
  o_groups<WG, HALF, 0>(d, a, sb, n, more);
  wg_wait<0>();
  if ((threadIdx.x & 31) == 0) mbar_arrive(sb + O_BAR + 128 + 4 * 8);
  if ((threadIdx.x & 127) == 0) T3(WG == 0 ? 1 : WG == 1 ? 8 : 12);
  __syncwarp();
#pragma unroll(HALF ? 1 : 2)
  for (int sl = 0; sl < 2; sl++) {
    mbar_wait(sb + OB_ST + WG * 16 + sl * 8, (n & 1) ^ (WG == 0));
    if (!HALF || sl == (n >= NSEG)) {
#pragma unroll
      for (int nb = 0; nb < 4; nb++) {
        const float* r = d + (HALF ? 0 : sl * 16) + nb * 4;
        const uint32_t ad = st0 + sl * 8192 + nb * 2048;
        sts32(ad, __float_as_uint(r[0]));
        sts32(ad + 256, __float_as_uint(r[1]));
        sts32(ad ^ 32, __float_as_uint(r[2]));
        sts32((ad ^ 32) + 256, __float_as_uint(r[3]));
      }
      fence_async_smem();
    }
    bar_arrive((sl ? B_G : B_M) + WG, 160);
  }
}
template <int WG>
__device__ __forceinline__ void o_math(const Params& P, uint32_t sb) {
  const bool more = bid() < N_CHAIN + N_G + 12;
  const int lane = threadIdx.x & 31, w = (threadIdx.x >> 5) & 3, g = lane >> 2, tq = lane & 3;
  uint32_t a[96];
  mbar_wait(sb + W_BAR + WG * 8, 0);
  load_frags<24>(a, sb + WG * 49152);
  fence_async_smem();
  bar_sync(B_INIT, 416);
  load_wg<OROLE>(P, sb, false, WG, w);
  mbar_wait(sb + W_BAR + WG * 8, 1);
  if ((threadIdx.x & 127) == 0) TS(4);
  const uint32_t st0 = sb + O_ST + tq * 512 + ((w * 16 + g) ^ (tq * 8)) * 4;
#pragma unroll 1
  for (int n = 0; n < STEPS; n++) {
    if (n < LAG || n >= NSEG) o_step<WG, true>(a, sb, st0, n, more); else o_step<WG, false>(a, sb, st0, n, more);
  }
}

__device__ __forceinline__ void o_aux(const Params& P, uint32_t sb) {
  const int i = bid() - N_CHAIN - N_G, ksl = i / 3;
  const int c0 = ksl * 11 - max(ksl - 4, 0), nc = ksl < 4 ? 11 : 10;
  const int lane = threadIdx.x & 31, w = __shfl_sync(~0u, (threadIdx.x >> 5) & 3, 0);
  if (w == 0) {
    bar_sync(B_INIT, 416);
    const uint32_t* f = g_fl + FL_O + near_half(XB_F + 1, bid()) * 1024 + min((c0 & ~1) + lane, (c0 + nc - 1) | 1);
#pragma unroll 1
    for (int n = 0; n < STEPS; n++) {
      const unsigned char* src = g_oimg + (uint32_t)(((n % RING) * N_CHAIN + c0) * 8192);
      wait_flags(f, n + 1);
      fence_async_global();
      if (lane == 0) T3(0);
#pragma unroll
      for (int gr = 0; gr < 5; gr++) {
        const uint32_t full = sb + O_BAR + gr * 8, bytes = (gr < 4 ? 2 : nc - 8) * 8192;
        mbar_wait(full + 128, (n & 1) ^ 1);
        if (elect()) {
          if (n < LAG || n >= NSEG) {
            mbar_expect(full, bytes >> 1);
            for (uint32_t o = gr * 16384 + (n < LAG ? 0 : 4096); o < gr * 16384 + bytes; o += 8192) bulk_load(sb + O_RING + o, src + o, 4096, full);
          } else {
            mbar_expect(full, bytes);
            bulk_load(sb + O_RING + gr * 16384, src + gr * 16384, bytes, full);
          }
        }
      }
    }
  } else {
#pragma unroll 1
    for (int n = 0; n < STEPS; n++) {
      float* dst = g_oacc + (uint32_t)((n % ARING) * (64 * DM) + ((i % 3) * 3 + (w - 1 + ksl) % 3) * 1024);
      const bool early = w == 3 && n < NSEG;
      bar_sync(B_M + (w - 1), 160);
      if (lane == 0) {
        T3(w * 2);
        if (n < NSEG) { bulk_reduce(dst, sb + O_ST, 4096); bulk_reduce(dst + 16 * DM, sb + O_ST + 4096, 4096); }
        asm volatile("cp.async.bulk.commit_group;" ::: "memory");
        if (early) {
          asm volatile("cp.async.bulk.wait_group.read 0;" ::: "memory");
          mbar_arrive(sb + OB_ST);
          T3(8 + w);
          bulk_done_inc(g_fl + FL_OCNT + (n % OCRING) * 8);
          T3(w * 2 + 1);
        }
      }
      __syncwarp();
      bar_sync(B_G + (w - 1), 160);
      if (lane == 0) {
        if (n >= LAG) { bulk_reduce(dst + 32 * DM, sb + O_ST + 8192, 4096); bulk_reduce(dst + 48 * DM, sb + O_ST + 12288, 4096); }
        asm volatile("cp.async.bulk.commit_group;\ncp.async.bulk.wait_group.read 1;" ::: "memory");
        if (!early) mbar_arrive(sb + OB_ST + (w % 3) * 16);
        asm volatile("cp.async.bulk.wait_group.read 0;" ::: "memory");
        mbar_arrive(sb + OB_ST + (w % 3) * 16 + 8);
        if (!early) {
          T3(8 + w);
          bulk_done_inc(g_fl + FL_OCNT + (n % OCRING) * 8);
          T3(w * 2 + 1);
        }
      }
      __syncwarp();
    }
  }
}

constexpr uint32_t Y_PITCH = 1168, Y_ROWS = 16 * Y_PITCH;
template <int R> __device__ __forceinline__ void y_rows(uint32_t* y, uint32_t src, uint32_t dst, int w, int bar) {
  const int lane = threadIdx.x & 31;
#pragma unroll
  for (int k = 0; k < 2 * R + 1; k++) {
    const int op = w + k * (16 / R);
    if (k == 2 * R && w >= 4) break;
    uint32_t a, b, c, d;
    ldsm4t(a, b, c, d, src + op * 512 + (lane & 16) * 16 + (lane & 7) * 32 + (lane & 8) * 2);
    stsm4(dst + (lane & 15) * Y_PITCH + op * 32 + (lane & 16), a, b, c, d);
  }
  bar_sync(bar, 512 / R);
  const uint32_t row = dst + ((w & 6) * 2 + (w >> 3) * 2 + (w & 1)) * Y_PITCH + lane * 4;
#pragma unroll
  for (int i = 0; i < 9 * R; i++) y[i] = lds32(row + i / 9 * 2 * Y_PITCH + i % 9 * 128);
}

__device__ __forceinline__ void f_role(const Params& P, uint32_t sb) {
  const int lane = threadIdx.x & 31, w = __shfl_sync(~0u, threadIdx.x >> 5, 0), r0 = (bid() - N_CHAIN - N_G - N_O) * 16;
  if (w == 8) {
    const uint32_t* fo = g_fl + FL_OCNT + near_half(XB_F, bid()) * 1024;
    fence_async_global();
#pragma unroll 1
    for (int n = 0; n < NSEG; n++) {
      bar_sync(2, 288);
      if (elect()) {
        mbar_expect(sb + F_BAR, 36864);
        bulk_load(sb + F_XY, P.X + (size_t)(n * 32 + r0) * DM, 18432, sb + F_BAR);
        bulk_load(sb + F_XY + 18432, g_yT + (size_t)(n * 32 + r0) * DM, 18432, sb + F_BAR);
        mbar_expect(sb + F_BAR + 8, 36864);
        T3(1);
      }
      wait_flags(fo + (n % OCRING) * 8, N_O * 3 * (n / OCRING + 1));
      fence_async_global();
      if (elect()) { bulk_load(sb + F_A, g_oacc + (uint32_t)((n % ARING) * (64 * DM) + r0 * DM), 36864, sb + F_BAR + 8); T3(0); }
    }
  } else if (w == 9) {
#pragma unroll 1
    for (int n = 0; n < NSEG; n++) {
      const uint32_t st = sb + (n & 1) * 36864;
      unsigned char* p = g_lnimg + (uint32_t)((NSEG + n) * 36864 + r0 * 128);
      bar_sync(1, 288);
      if (elect()) {
        T3(2);
#pragma unroll
        for (int i = 0; i < 9; i++) bulk_store(p + i * 4096, st + F_L + i * 2048, 2048);
        asm volatile("cp.async.bulk.commit_group;" ::: "memory");
        bulk_done_inc(g_fl + FL_F + (bid() & 1) * 8);
        T3(3);
        bulk_store(P.out + (size_t)(n * 32 + r0) * DM, st + F_X, 18432);
        asm volatile("cp.async.bulk.commit_group;\ncp.async.bulk.wait_group.read 0;" ::: "memory");
        if (n + 1 == NSEG) bulk_done_inc(g_fl + FL_F + (bid() & 1) * 8);
      }
      __syncwarp();
    }
  } else if (w < 8) {
    const uint32_t row = sb + w * 1152 + lane * 4, acc = sb + F_A + w * 256 + (lane ^ ((w & 6) * 2)) * 8;
    const uint32_t ln = sb + F_L + w * 128 + (((lane >> 2) ^ w) << 4) + (lane & 3) * 4;
#pragma unroll 1
    for (int n = -1; n < NSEG; n++) {
      const uint32_t st = (n & 1) * 36864;
      uint32_t x[18], y[18], l[18];
      if (n >= 0) mbar_wait(sb + F_BAR, n & 1);
#pragma unroll
      for (int i = 0; i < 18; i++) x[i] = lds32(row + F_XY + i / 9 * 9216 + i % 9 * 128);
      y_rows<2>(y, sb + F_XY + 18432, sb + F_Y, w, 3);
      layernorm9<2>(x, l);
#pragma unroll
      for (int i = 0; i < 18; i++) x[i] = badd2(x[i], bmul2(l[i], y[i]));
      if (n >= 0) mbar_wait(sb + F_BAR + 8, n & 1);
      if (threadIdx.x == 0 && n >= 0) T3(4);
      __syncwarp();
      uint2 a[18];
#pragma unroll
      for (int i = 0; i < 18; i++) a[i] = lds64(acc + i / 9 * 2048 + i % 9 * 4096);
#pragma unroll
      for (int i = 0; i < 18; i++) x[i] = badd2(x[i], pack2(__uint_as_float(a[i].x), __uint_as_float(a[i].y)));
      if (n + 1 < NSEG) bar_arrive(2, 288);
      layernorm9<2>(x, l);
#pragma unroll
      for (int i = 0; i < 18; i++) { x[i] = badd2(x[i], bmul2(l[i], y[i])); sts32(row + st + F_X + i / 9 * 9216 + i % 9 * 128, x[i]); }
      layernorm9<2>(x, l);
#pragma unroll
      for (int i = 0; i < 18; i++) sts32(ln + st + i / 9 * 1024 + i % 9 * 2048, l[i]);
      fence_async_smem();
      if (n >= 0) bar_sync(1, 288); else bar_sync(3, 256);
    }
  }
}

constexpr uint32_t P_CH = 147456, P_CHSZ = 12800, P_H = 4352;
static_assert(P_CH + 6 * P_CHSZ <= G_BAR, "prologue smem");

template <int N>
__device__ __forceinline__ void conv_fold(float (*acc)[4], bool hi, uint32_t mine, uint32_t theirs, int bar, int cnt) {
#pragma unroll
  for (int i = 0; i < N / 2; i++) {
    uint4 v;
    v.x = __float_as_uint(hi ? acc[i][0] : acc[i + N / 2][0]); v.y = __float_as_uint(hi ? acc[i][1] : acc[i + N / 2][1]);
    v.z = __float_as_uint(hi ? acc[i][2] : acc[i + N / 2][2]); v.w = __float_as_uint(hi ? acc[i][3] : acc[i + N / 2][3]);
    sts128(mine + i * 512, v);
  }
  bar_sync(bar, cnt);
#pragma unroll
  for (int i = 0; i < N / 2; i++) {
    const uint4 v = lds128(theirs + i * 512);
    acc[i][0] = (hi ? acc[i + N / 2][0] : acc[i][0]) + __uint_as_float(v.x); acc[i][1] = (hi ? acc[i + N / 2][1] : acc[i][1]) + __uint_as_float(v.y);
    acc[i][2] = (hi ? acc[i + N / 2][2] : acc[i][2]) + __uint_as_float(v.z); acc[i][3] = (hi ? acc[i + N / 2][3] : acc[i][3]) + __uint_as_float(v.w);
  }
}
template <int N>
__device__ __forceinline__ void conv_store(const float (*acc)[4], int tile0, uint32_t su, int d, uint32_t dd) {
  const int lane = threadIdx.x & 31, g = lane >> 2, tq = lane & 3;
#pragma unroll
  for (int i = 0; i < N; i++) {
    const uint32_t ad = su + (8 + (tile0 + i) * 8 + g) * 32 + tq * 4, sw = (g & 4) << 2;
    const uint32_t lo = badd2(movmat(pack2(acc[i][0], acc[i][1])), bmul2(lds32(ad + sw), dd));
    const uint32_t hi = badd2(movmat(pack2(acc[i][2], acc[i][3])), bmul2(lds32(ad + (sw ^ 16)), dd));
    ((uint2*)g_yT)[(((tile0 + i) * 8 + g) * DM + d) * 4 + tq] = make_uint2(lo, hi);
  }
}

__device__ __forceinline__ void prologue(const Params& P, uint32_t sb) {
  const int b = bid(), tid = threadIdx.x, lane = tid & 31, warp = tid >> 5, t0 = b * 16;
  const bool isg = b >= N_CHAIN && b < N_CHAIN + N_G;
  const int nch = isg ? 2 : b < 128 ? 6 : 0, chb = b < N_CHAIN ? b * 6 : isg ? b * 2 + 256 : b * 6 - 192;
  const uint32_t tstart = clk();
  if (tid < 288) {
    if (b < 128) {
      const int c = (tid >> 1) * 4, tt = t0 + (tid & 1) * 8;
      uint2 kr[11], vr[8];
#pragma unroll
      for (int i = 0; i < 11; i++) { const int t = tt + i - 3; kr[i] = t >= 0 ? __ldg((const uint2*)(P.K + (size_t)t * DM + c)) : make_uint2(0, 0); }
#pragma unroll
      for (int i = 0; i < 8; i++) vr[i] = __ldg((const uint2*)(P.V + (size_t)(tt + i) * DM + c));
#pragma unroll
      for (int e = 0; e < 2; e++) {
        const uint4 sh = __ldg((const uint4*)(P.shift + c * 4) + e);
        const uint32_t s0 = __byte_perm(sh.x, sh.z, 0x5410), s1 = __byte_perm(sh.x, sh.z, 0x7632);
        const uint32_t s2 = __byte_perm(sh.y, sh.w, 0x5410), s3 = __byte_perm(sh.y, sh.w, 0x7632);
        uint32_t v[8];
#pragma unroll
        for (int i = 0; i < 8; i++) {
          const uint32_t k3 = e ? kr[i].y : kr[i].x, k2 = e ? kr[i + 1].y : kr[i + 1].x, k1 = e ? kr[i + 2].y : kr[i + 2].x, k0 = e ? kr[i + 3].y : kr[i + 3].x;
          v[i] = bmul2(badd2(badd2(badd2(bmul2(k3, s3), bmul2(k2, s2)), bmul2(k1, s1)), bmul2(k0, s0)), e ? vr[i].y : vr[i].x);
        }
        *(uint4*)(g_kvT + (size_t)(c + 2 * e) * KVP + tt) =
          make_uint4(__byte_perm(v[0], v[1], 0x5410), __byte_perm(v[2], v[3], 0x5410), __byte_perm(v[4], v[5], 0x5410), __byte_perm(v[6], v[7], 0x5410));
        *(uint4*)(g_kvT + (size_t)(c + 2 * e + 1) * KVP + tt) =
          make_uint4(__byte_perm(v[0], v[1], 0x7632), __byte_perm(v[2], v[3], 0x7632), __byte_perm(v[4], v[5], 0x7632), __byte_perm(v[6], v[7], 0x7632));
      }
    }
  } else if (tid < 384) {
    const int t = tid - 288;
    for (int i = b * 96 + t; i < 16 * DM; i += N_CTA * 96) ((uint4*)g_oacc)[i] = make_uint4(0, 0, 0, 0);
    if (b * 96 + t < 128 * 8) g_lnflag[b * 96 + t] = 0;
    if (t == 95) sts32(sb + S_GEN, ld_acquire(g_gbar));
    __syncwarp();
    wait_until(tstart, PREFH);
    for (int i = t; i < 32 * nch; i += 96) asm volatile("prefetch.global.L2 [%0];" :: "l"(P.Hk + (size_t)chb * SEQ + i * 64));
  }
  if (warp < 12) {
    bar_arrive(10, 416);
    if (tid == 128) TS(14);
    const int ch = 5 - (warp >> 1), sub = warp & 1, d = chb + ch;
    const uint32_t su = sb + P_CH + ch * P_CHSZ;
    if (ch < nch) {
      const uint32_t* hs = (const uint32_t*)(P.Hk + (size_t)d * SEQ);
#pragma unroll
      for (int q = sub * 32 + lane; q < 256; q += 64) {
        const uint4 c = __ldg((const uint4*)hs + q);
        const uint32_t prev = q ? __ldg(hs + 4 * q - 1) : 0u;
        sts128(su + P_H + 32 + q * 16, make_uint4(__byte_perm(c.x, prev, 0x7610), __byte_perm(c.y, c.x, 0x7610), __byte_perm(c.z, c.y, 0x7610), __byte_perm(c.w, c.z, 0x7610)));
        sts128(su + P_H + 4224 + q * 16, make_uint4(__byte_perm(c.x, 0, 0x1032), __byte_perm(c.y, 0, 0x1032), __byte_perm(c.z, 0, 0x1032), __byte_perm(c.w, 0, 0x1032)));
      }
      if (sub == 1 && lane == 0) sts32(su + P_CHSZ - 16, __bfloat16_as_ushort(P.Dk[d]) * 0x10001u);
      if (sub == 0 && lane < 20) sts128(su + (lane < 16 ? lane * 16 : P_H + (lane & 2) * 2096 + (lane & 1) * 16), make_uint4(0, 0, 0, 0));
    }
    bar_sync(11, 416);
    if (ch < nch) {
#pragma unroll
      for (int q = sub * 32 + lane; q < 256; q += 64) {
        const int row = (q >> 1) + 8;
        sts128(su + row * 32 + (((q & 1) ^ ((row >> 2) & 1)) << 4), __ldcg((const uint4*)(g_kvT + (size_t)d * KVP) + q));
      }
    }
    const int g = lane >> 2, tq = lane & 3;
    const uint32_t sh = su + P_H + (g & 1) * 4192 + (8 + (g >> 1) - tq) * 4;
    float acc[16][4];
#pragma unroll
    for (int i = 0; i < 16; i++) { acc[i][0] = acc[i][1] = acc[i][2] = acc[i][3] = 0.f; }
    auto u_addr = [&](int res) {
      const int row = 8 - res + ((lane >> 4) << 3) + (lane & 7);
      return su + row * 32 + ((((lane >> 3) & 1) ^ ((row >> 2) & 1)) << 4);
    };
    if (ch < nch) {
      bar_sync(1 + ch, 64);
      if (tid == 352) TS(11);
      if (sub) {
#pragma unroll 4
        for (int res = 0; res < 8; res++) {
          uint32_t b0, b1, b2, b3;
          ldsm4(b0, b1, b2, b3, u_addr(res));
          const uint32_t r0 = lds32(sh + res * 32);
          mma16(acc[0], r0, lds32(sh + res * 32 + 16), lds32(sh + res * 32 - 16), r0, b0, b1);
        }
        conv_store<1>(acc, 0, su, d, lds32(su + P_CHSZ - 16));
      }
    }
    bar_arrive(12, 416);
    if (isg && warp < 8) { while ((int)(clk() - tstart - S1G) < 0) __nanosleep(200); load_wg<GROLE>(P, sb, true, warp >> 2, warp & 3); }
    if (ch < nch) {
#pragma unroll 1
      for (int res = sub * 4; res < sub * 4 + 4; res++) {
        uint32_t bf[16][2];
        const uint32_t ad = u_addr(res);
#pragma unroll
        for (int f = 0; f < 16; f += 2) ldsm4(bf[f][0], bf[f][1], bf[f + 1][0], bf[f + 1][1], ad + f * 256);
#pragma unroll
        for (int k = 0; k < 16; k++) {
          const int jj = k & 1 ? k >> 1 : 15 - (k >> 1);
          const uint32_t ah = sh + (8 * jj + res) * 32;
          const uint32_t r0 = lds32(ah), r1 = lds32(ah + 16), rm = lds32(ah - 16);
#pragma unroll
          for (int i = max(jj, 1); i < 16; i++) mma16(acc[i], r0, r1, rm, r0, bf[i - jj][0], bf[i - jj][1]);
        }
      }
      bar_sync(1 + ch, 64);
      if (tid == 352) TS(12);
      const uint32_t xb = su + P_H + lane * 16, dd = lds32(su + P_CHSZ - 16);
      conv_fold<16>(acc, sub, xb + sub * 4096, xb + (sub ^ 1) * 4096, 1 + ch, 64);
      conv_store<8>(acc, sub * 8, su, d, dd);
    }
  } else {
    for (int i = b; i < 194 + MRING * 5; i += N_CTA) {
      const int n = (i - 194) / 5, r = (i - 194) % 5, blk = i < 192 ? i / 6 * 8 + i % 6 : i < 194 ? XB_F + i - 192 : XB_M + n * 8 + r;
      const uint32_t fill = i < 194 ? 0u : SENT;
#pragma unroll 1
      for (int q = tid - 384; q < 256 && warp < 15; q += 96) {
        uint4 v = make_uint4(fill, fill, fill, fill);
        if (i >= 194 && n == 0 && (r > 0 || q < 128)) {
          const bf16* m = P.mem0 + (max(r * 8 - 4, 0) + (q >> 5)) * 16 + ((q >> 1) & 1) * 8 + ((q >> 2) & 7);
          v.x = pack2(__bfloat162float(m[0]), __bfloat162float(m[DM])); v.y = pack2(__bfloat162float(m[2 * DM]), __bfloat162float(m[3 * DM]));
          v.z = pack2(__bfloat162float(m[4 * DM]), __bfloat162float(m[5 * DM])); v.w = pack2(__bfloat162float(m[6 * DM]), __bfloat162float(m[7 * DM]));
        }
        g_xb[blk * 512 + q] = v;
        g_xb[blk * 512 + 256 + q] = v;
      }
    }
    if (tid < 388) g_xb[XB_REF * 512 + (tid & 2) * 128 + (b & ~1) + (tid & 1)] = make_uint4(0, 0, 0, 0);
    else if (tid < 392 && b < N_GRP) g_xb[(b * 8 + 7) * 512 + (tid & 2) * 128 + (tid & 1)] = make_uint4(0, 0, 0, 0);
    if (warp < 15) { bar_arrive(9, 128); bar_sync(7, 96); }
    if (tid == 384) TS(8);
    if (warp == 12) {
      const bf16* w = lane < 6 ? (lane % 3 == 0 ? P.Wk : lane % 3 == 1 ? P.Wv : P.Wq) + (((b >> 5) * 2 + lane / 3) * 32 + (b & 31)) * 2048
                               : (lane < 8 ? P.Wo + (lane - 6) * (9 * 131072) : P.X) + b * 2048;
      uint32_t t = tstart + PREF0;
      if ((int)(clk() - t) > 0) t = clk();
#pragma unroll 1
      for (int st = 0; st < 9 && b < N_CHAIN; st++) {
#pragma unroll 1
        for (int i = 0; i < 9; i++, t += PACE) {
          wait_until(t, 0);
          if (lane == st) asm volatile("cp.async.bulk.prefetch.L2.global [%0], 4096;" :: "l"(w + i * (lane < 6 ? 262144 : 131072)) : "memory");
        }
      }
      if (lane == 0) TS(10);
    } else if (warp == 15) {
      bar_sync(10, 416);
      if (lane == 0) { grid_arrive(0); if (nch) grid_wait(0, lds32(sb + S_GEN)); }
      __syncwarp();
      bar_arrive(11, 416);
      if (lane == 0) TS(1);
      bar_sync(9, 128);
      bar_sync(12, 416);
      if (lane == 0) { TS(16); grid_arrive(2); TS(17); }
    } else if (lane == 0) {
      if (warp == 13 || (warp == 14 && b < N_GRP)) {
        uint32_t* p = (uint32_t*)(g_xb + (warp == 13 ? XB_REF * 512 + b : (b * 8 + 7) * 512));
        int votes = 0;
        for (int rep = 0; rep < 24 && abs(votes) < 7; rep++) {
          uint32_t v0, v1, c0, c1;
          asm volatile("atom.relaxed.gpu.global.add.u32 %0, [%4], 1;\n atom.relaxed.gpu.global.add.u32 %1, [%5], 1;\n"
                       "{.reg .pred p; setp.eq.u32 p, %0, 0x7ffffff3; @p trap; mov.u32 %2, %%clock; setp.eq.u32 p, %1, 0x7ffffff3; @p trap; mov.u32 %3, %%clock;}"
                       : "=&r"(v0), "=&r"(v1), "=&r"(c0), "=&r"(c1) : "l"(p + (rep & 1) * 1024), "l"(p + ((rep & 1) ^ 1) * 1024) : "memory");
          votes += ((c1 - c0 > 80u) == (rep & 1)) ? 1 : -1;
        }
        if (warp == 13) { g_side[b] = votes > 0; TS(9); } else g_near[b] = votes > 0;
      }
    }
    __syncwarp();
    if (warp > 12 && b < N_CHAIN) {
      while ((int)(clk() - tstart - S1DLY) < 0) __nanosleep(200);
      for (int k = warp - 13; k < 8; k += 3) load_wg<CHAIN>(P, sb, true, 1 - k / 4, k & 3);
    }
  }
  if (b < N_CHAIN + N_G && (warp < 8 || (isg && warp >= 12))) bar_arrive(0, 512); else bar_sync(0, 512);
  if (tid == 352) TS(2);
}

__device__ __forceinline__ void publish_y() {
  if (threadIdx.x == 383) { grid_arrive(1); TS(18); }
  __syncwarp();
}

template <int R> __device__ __forceinline__ void ln_tiles(const Params& P, uint32_t sb) {
  const int lane = threadIdx.x & 31, w = (threadIdx.x >> 5) & (16 / R - 1), half = R == 1 ? 0 : threadIdx.x >> 8, u = N_CTA - 1 - bid();
  const int first = R == 1 ? u : 46 - 2 * u + half, step = R == 1 ? 4 : 40, last = R == 1 ? 8 : 128;
  const uint32_t raw = sb + P_CH + half * (18432 + Y_ROWS), mb = sb + T_BAR + (R - 1 + half) * 8;
  const bool lead = w == 16 / R - 1 && lane == 0;
  auto load_y = [&](const bf16* src, int tile) {
    fence_async_global();
    mbar_expect(mb, 18432);
    bulk_load(raw, src + (size_t)tile * 16 * DM, 18432, mb);
  };
  uint32_t nx[9 * R];
  auto load_x = [&](int tile) {
#pragma unroll
    for (int i = 0; i < 9 * R; i++) nx[i] = __ldg((const uint32_t*)(P.X + (size_t)(tile * 16 + w + i / 9 * 8) * DM) + i % 9 * 32 + lane);
  };
  load_x(first);
  if (R == 2) {
    if (lead) { grid_wait(1, lds32(sb + S_GEN)); if (u > 3) TS(13); load_y(g_yT, first); }
    __syncwarp();
  }
#pragma unroll 1
  for (int tile = first, real = R - 1, ph = 0; tile < last; tile += real * step, real = 1, ph ^= 1) {
    uint32_t x[9 * R], l[9 * R], y[9 * R];
    const bool ts = threadIdx.x == 0 && (R == 1 ? tile == first : u > 3 && tile == first + step);
    if (ts) TS(26);
#pragma unroll
    for (int i = 0; i < 9 * R; i++) x[i] = nx[i];
    layernorm9<R>(x, l);
    if (real && tile + step < last) load_x(tile + step);
    if (R == 2 && tile == first + step && u >= N_F && w < 6) load_wg<OROLE>(P, sb, true, w >> 1, half * 2 + (w & 1));
    if (R == 1 && tile == first && lead) {
      if (real) grid_wait(2, lds32(sb + S_GEN));
      TS(13);
      load_y(real ? g_yT : P.Hk, tile);
    }
    bar_sync(13 + half, 512 / R);
    mbar_wait(mb, ph);
    if (ts) TS(28);
    y_rows<R>(y, raw, raw + 18432, w, 13 + half);
    if (ts) TS(29);
    if (lead && real && tile + step < last) { fence_async_smem(); load_y(g_yT, tile + step); }
    __syncwarp();
#pragma unroll
    for (int i = 0; i < 9 * R; i++) x[i] = badd2(x[i], bmul2(l[i], y[i]));
    layernorm9<R>(x, l);
    if (ts && l[0] != 0x12345) TS(30);
#pragma unroll
    for (int r = 0; r < R; r++) store_ln_row(0, tile * 16 + w + r * 8, l + r * 9);
    if (R == 1) {
      __syncthreads();
      if (threadIdx.x == 32 && real) { if (tile < 4) TS(19); st_release(g_lnflag + tile * 8, 1); if (tile < 4) TS(20); }
      __syncwarp();
    }
    if (ts) TS(31);
  }
  if (R == 2) {
    __syncthreads();
    if (threadIdx.x >= 506) {
      asm volatile("fence.acq_rel.gpu;" ::: "memory");
      st_relaxed_if(g_lnflag + ((first ^ (lane & 1)) + (lane - 26) / 2 * step) * 8, 1, true);
    }
    __syncwarp();
    fence_async_smem();
    if (threadIdx.x == 0) TS(15);
  }
}

__global__ void __cluster_dims__(2, 1, 1) __launch_bounds__(512, 1) k_main(const __grid_constant__ Params P) {
  extern __shared__ __align__(1024) unsigned char smem[];
  const uint32_t sb = (uint32_t)__cvta_generic_to_shared(smem);
  const int b = bid(), wg = threadIdx.x >> 7;
  if ((threadIdx.x & 127) == 0) TS(0);
  if (threadIdx.x == 480) {
    if ((sb & 0xFFFFFF) != SBASE) __trap();
    for (int i = 0; i < 6; i++) mbar_init(sb + W_BAR + i * 8, 1);
    if (b < N_CHAIN) {
      mbar_init(sb + CB_FULL, 1); mbar_init(sb + CB_FULL + 8, 1);
      mbar_init(sb + CB_REF, 1);
      mbar_init(sb + CB_SX, 1); mbar_init(sb + CB_OX, 1); mbar_init(sb + CB_XX, 1); mbar_init(sb + CB_Q, 2); mbar_init(sb + CB_VF, 1);
      sts32(sb + C_BAD, 0);
      for (int i = 0; i < 11; i++) mbar_init(sb + CB_M + i * 8, i == 0 ? 5 : i == 5 ? 2 : 1);
    } else if (b < N_CHAIN + N_G) {
      for (int i = 0; i < 9; i++) { mbar_init(sb + G_BAR + i * 8, 2); mbar_init(sb + G_BAR + 128 + i * 8, 8); }
    } else if (b < N_CHAIN + N_G + N_O) {
      for (int i = 0; i < 5; i++) { mbar_init(sb + O_BAR + i * 8, 1); mbar_init(sb + O_BAR + 128 + i * 8, 12); }
      for (int i = 0; i < 6; i++) mbar_init(sb + OB_ST + i * 8, 1);
    } else {
      mbar_init(sb + F_BAR, 1); mbar_init(sb + F_BAR + 8, 1);
    }
    asm volatile("fence.mbarrier_init.release.cluster;" ::: "memory");
    fence_async_smem();
  }
  __syncwarp();
  asm volatile("barrier.cluster.arrive.relaxed.aligned;" ::: "memory");
  prologue(P, sb);
  asm volatile("barrier.cluster.wait.aligned;" ::: "memory");
  fence_async_smem();
  if (b >= N_CHAIN + N_G) publish_y();
  if (b >= 128) ln_tiles<1>(P, sb);
  if (b >= N_CHAIN + N_G) ln_tiles<2>(P, sb);
  if ((threadIdx.x & 127) == 0) TS(3);
  if (b < N_CHAIN) {
    if (wg < 2) { reg_inc<200>(); chain_proj(P, sb); }
    else if (wg == 2) { reg_dec<88>(); publish_y(); chain_attn(P, sb); }
    else { reg_dec<24>(); chain_aux(P, sb); }
  } else if (b < N_CHAIN + N_G) {
    if (wg == 0) { reg_inc<232>(); g_math<0>(P, sb); }
    else if (wg == 1) { reg_inc<232>(); g_math<1>(P, sb); }
    else if (wg == 2) { reg_dec<24>(); bar_arrive(15, 192); publish_y(); g_aux(P, sb); }
    else { reg_dec<24>(); g_load(P, sb); }
  } else if (b < N_CHAIN + N_G + N_O) {
    if (wg == 0) { reg_inc<160>(); o_math<0>(P, sb); }
    else if (wg == 1) { reg_inc<160>(); o_math<1>(P, sb); }
    else if (wg == 2) { reg_inc<160>(); o_math<2>(P, sb); }
    else { reg_dec<32>(); o_aux(P, sb); }
  } else {
    f_role(P, sb);
  }
}

}

extern "C" void kernel_launch(void* const* d_in, const int* in_sizes, int n_in, void* d_out, int out_size) {
  typedef CUresult (*Encode)(CUtensorMap*, CUtensorMapDataType, cuuint32_t, void*, const cuuint64_t*, const cuuint64_t*, const cuuint32_t*, const cuuint32_t*,
                             CUtensorMapInterleave, CUtensorMapSwizzle, CUtensorMapL2promotion, CUtensorMapFloatOOBfill);
  static Encode encode = nullptr;
  if (!encode) cudaGetDriverEntryPoint("cuTensorMapEncodeTiled", (void**)&encode, cudaEnableDefault);
  Params P;
  for (int i = 0; i < 11; i++) {
    const bool wo = i == 6 || i == 7;
    const cuuint64_t cols = wo ? DM : HD, rows = HD + DM - cols, pitch = cols * 2;
    const cuuint64_t dim[4][5] = {{cols, 2, 8, 2, 18}, {cols, 16, 1, 1, rows / 16}, {cols, 2, 4, 4, rows / 32}, {64, 16, 64, 2, 18}};
    const cuuint64_t stride[4][4] = {{8 * pitch, pitch, 16 * pitch, 32 * pitch}, {pitch, pitch, pitch, 16 * pitch},
                                     {pitch, 8 * pitch, 2 * pitch, 32 * pitch}, {pitch, 128, 16 * pitch, 32 * pitch}};
    const cuuint32_t box[4][5] = {{64, 2, 8, 1, 18}, {64, 16, 1, 1, 1}, {64, 2, 4, 2, 1}, {64, 16, 2, 1, 18}}, one[5] = {1, 1, 1, 1, 1};
    const int k = i < 3 ? 0 : i < 7 ? 1 : i < 8 ? 2 : 3;
    encode(&P.map[i], CU_TENSOR_MAP_DATA_TYPE_BFLOAT16, 5, d_in[wo ? 11 : 8 + (i & 7) % 3], dim[k], stride[k], box[k], one,
           CU_TENSOR_MAP_INTERLEAVE_NONE, CU_TENSOR_MAP_SWIZZLE_128B, CU_TENSOR_MAP_L2_PROMOTION_L2_128B, CU_TENSOR_MAP_FLOAT_OOB_FILL_NONE);
  }
  P.X = (const bf16*)d_in[0]; P.K = (const bf16*)d_in[1]; P.V = (const bf16*)d_in[2];
  P.shift = (const bf16*)d_in[3]; P.Hk = (const bf16*)d_in[4]; P.Dk = (const bf16*)d_in[5];
  P.mem0 = (const bf16*)d_in[7];
  P.Wq = (const bf16*)d_in[8]; P.Wk = (const bf16*)d_in[9]; P.Wv = (const bf16*)d_in[10]; P.Wo = (const bf16*)d_in[11];
  P.out = (bf16*)d_out;
  for (int i = 0; i < 25; i++) P.dly[i] = h_dly[i];
  cudaFuncSetAttribute(k_main, cudaFuncAttributeMaxDynamicSharedMemorySize, SMEM_BYTES);
  k_main<<<N_CTA, 512, SMEM_BYTES>>>(P);
}
```

```cpp
#include <cuda.h>
#include <cuda_runtime.h>
#include <cuda_bf16.h>
#include <stdint.h>

namespace {

typedef __nv_bfloat16 bf16;

constexpr int SEQ = 2048, DM = 576, HD = 4096, NSEG = 64;
constexpr int LAG = 7, STEPS = NSEG + LAG, RING = 8;
constexpr int LOCK0 = 3, QRING = LOCK0 + 1;
static_assert(LAG < RING, "ring");
constexpr int N_CHAIN = 64, N_G = 48, N_O = 18, N_F = 2;
constexpr uint32_t SBASE = 1024;
constexpr uint32_t SENT = 0xFFFFFFFFu;
constexpr int SPIN_MAX = 1 << 22;

__device__ __forceinline__ uint32_t bid() {
  uint32_t b;
  asm volatile("mov.u32 %0, %%ctaid.x;" : "=r"(b));
  return b < 6 ? b + 106 : b < 8 ? b + 122 : b < 114 ? b - 8 : b < 130 ? b - 2 : b;
}
__device__ __forceinline__ uint32_t chain_id() { return blockIdx.x - 8; }
constexpr int KVP = SEQ + 64;
__device__ __align__(1024) bf16 g_kvT[DM * KVP];
__device__ __align__(1024) bf16 g_yT[DM * SEQ];
__device__ __align__(1024) unsigned char g_lnimg[2 * NSEG * 9 * 4096];
__device__ __align__(1024) unsigned char g_qkv[QRING * N_CHAIN * 24576];
__device__ __align__(1024) unsigned char g_oimg[RING * N_CHAIN * 8192];
constexpr int ARING = 16;
static_assert(ARING >= LAG + 9, "accumulator ring");
__device__ __align__(1024) float g_oacc[ARING * 64 * DM];
constexpr int MRING = LAG + 4, N_GRP = 32 + MRING + 1;
constexpr int XB_M = 256, XB_F = XB_M + MRING * 8, XB_REF = XB_F + 2, N_CTA = N_CHAIN + N_G + N_O + N_F;
__device__ __align__(65536) uint4 g_xb[N_GRP * 4096];
#define g_mimg ((uint32_t*)(g_xb + XB_M * 512))
__device__ uint32_t g_near[N_GRP];
__device__ uint32_t g_side[N_CTA];
__device__ __align__(128) uint32_t g_gbar[3 * 32];
constexpr int FL_G = 0, FL_F = 96 * 8, FL_OCNT = FL_F + 2 * 8, OCRING = 16, FL_TICK = 992, FL_O = 2048, FL_SYNC = FL_O + 128;
static_assert(FL_OCNT + OCRING * 8 <= FL_TICK, "flag block");
#define g_fl ((uint32_t*)(g_xb + XB_F * 512))
__device__ __align__(1024) uint32_t g_lnflag[128 * 8];
#define TS(slot)

#define CNT(slot, tries)
#define T3(slot)
#define TR(slot)
#define TRV(slot, val)
#define TRD(slot, dep)
#define TRSYNC()
#define TRDUMP(n)
#define CLK(t) "{.reg .b64 x; .reg .b32 h; mov.u64 x, %%clock64; mov.b64 {" t ", h}, x;}"
__device__ __forceinline__ uint32_t clk() { uint32_t t; asm volatile(CLK("%0") : "=r"(t) :: "memory"); return t; }
__device__ __forceinline__ void wait_until(uint32_t t0, uint32_t d) {
  asm volatile("{.reg .pred p; .reg .u32 t;\n"
               "W: " CLK("t") " sub.u32 t, t, %0; setp.lt.s32 p, t, 0; @p bra.uni W;}"
               :: "r"(t0 + d) : "memory");
}
__device__ __forceinline__ uint32_t pack2(float lo, float hi) {
  uint32_t r; asm("cvt.rn.bf16x2.f32 %0, %1, %2;" : "=r"(r) : "f"(hi), "f"(lo)); return r;
}
__device__ __forceinline__ float bf_lo(uint32_t v) { return __uint_as_float(v << 16); }
__device__ __forceinline__ float bf_hi(uint32_t v) { return __uint_as_float(v & 0xFFFF0000u); }

__device__ __forceinline__ void st_b128(void* p, uint32_t a, uint32_t b, uint32_t c, uint32_t d) {
  asm volatile("{.reg .b128 v; mov.b128 v, {%1,%2,%3,%4}; st.relaxed.gpu.global.b128 [%0], v;}" :: "l"(p), "r"(a), "r"(b), "r"(c), "r"(d) : "memory");
}
__device__ __forceinline__ void st_relaxed_if(void* p, uint32_t a, bool on) {
  asm volatile("{.reg .pred p; setp.ne.u32 p, %2, 0; @p st.relaxed.gpu.global.u32 [%0], %1;}" :: "l"(p), "r"(a), "r"((uint32_t)on) : "memory");
}
__device__ __forceinline__ uint32_t ld_acquire(const uint32_t* p) {
  uint32_t v; asm volatile("ld.acquire.gpu.global.u32 %0, [%1];" : "=r"(v) : "l"(p) : "memory"); return v;
}
__device__ __forceinline__ void st_release(uint32_t* p, uint32_t v) {
  asm volatile("st.release.gpu.global.u32 [%0], %1;" :: "l"(p), "r"(v) : "memory");
}
__device__ __forceinline__ void bulk_reduce(float* dst, uint32_t src, uint32_t bytes) {
  asm volatile("cp.reduce.async.bulk.global.shared::cta.bulk_group.add.f32 [%0], [%1], %2;" :: "l"(dst), "r"(src), "r"(bytes) : "memory");
}
__device__ __forceinline__ void bulk_done_inc(uint32_t* p) {
  asm volatile("cp.async.bulk.wait_group 0;\n"
               "fence.proxy.async.global;\nfence.release.gpu;\n"
               "red.relaxed.gpu.global.add.u32 [%0], 1;\nred.relaxed.gpu.global.add.u32 [%0+4096], 1;" :: "l"(p) : "memory");
}
__device__ __forceinline__ void flag_release(uint32_t* p, uint32_t v) {
  asm volatile("fence.release.gpu;\nst.relaxed.gpu.global.u32 [%0], %1;\nst.relaxed.gpu.global.u32 [%0+4096], %1;" :: "l"(p), "r"(v) : "memory");
}
__device__ __forceinline__ void spin_guard(int& it) {
  asm volatile("{.reg .pred p; add.s32 %0, %0, 1; setp.gt.s32 p, %0, %1; @p trap;}" : "+r"(it) : "n"(SPIN_MAX));
}
__device__ __forceinline__ void wait_flags(const uint32_t* p, uint32_t v) {
  int it = 0;
  while (true) {
    uint32_t x; asm volatile("ld.relaxed.gpu.global.u32 %0, [%1];" : "=r"(x) : "l"(p) : "memory");
    if (__all_sync(~0u, x >= v)) break;
    spin_guard(it);
  }
  asm volatile("fence.acquire.gpu;" ::: "memory");
}
__device__ __forceinline__ uint32_t timer_sample() {
  uint32_t g;
  asm volatile("{.reg .b64 x; .reg .b32 h; mov.u64 x, %%globaltimer; mov.b64 {%0, h}, x;}" : "=r"(g) :: "memory");
  return (g >> 5) * 57 - clk();
}
template <int N> __device__ __forceinline__ uint32_t timer_offset() {
  const uint32_t base = timer_sample();
  int best = 0;
#pragma unroll 1
  for (int i = 0; i < N; i++) {
    const int a = timer_sample() - base, b = timer_sample() - base, c = timer_sample() - base;
    best = max(max(best, a), max(b, c));
  }
  return base + best;
}
__device__ __forceinline__ void grid_arrive(int i) {
  asm volatile("red.release.gpu.global.add.u32 [%0], %1;" :: "l"(g_gbar + i * 32), "r"(bid() ? 1u : 257u - N_CTA) : "memory");
}
__device__ __forceinline__ void grid_wait(int i, uint32_t gen) {
  int it = 0;
  while (((ld_acquire(g_gbar + i * 32) ^ gen) >> 8) == 0) spin_guard(it);
}
__device__ __forceinline__ bool elect() {
  uint32_t r; asm volatile("{.reg .pred p; elect.sync _|p, -1; selp.u32 %0, 1, 0, p;}" : "=r"(r)); return r;
}
__device__ __forceinline__ void bar_sync(int id, int cnt) { asm volatile("bar.sync %0, %1;" :: "r"(id), "r"(cnt) : "memory"); }
__device__ __forceinline__ void bar_arrive(int id, int cnt) { asm volatile("bar.arrive %0, %1;" :: "r"(id), "r"(cnt) : "memory"); }
template <int id, int cnt> __device__ __forceinline__ void bar_arrive_after(uint32_t a, uint32_t b) {
  asm volatile("{.reg .pred p; setp.ne.u32 p, %2, 0xfff12345; setp.ne.and.u32 p, %3, 0xfff12345, p; @p bar.arrive %0, %1;}" :: "n"(id), "n"(cnt), "r"(a), "r"(b) : "memory");
}
template <int id, int cnt> __device__ __forceinline__ void bar_sync_after(uint32_t a) {
  asm volatile("{.reg .pred p; setp.ne.u32 p, %2, 0xfff12345; @p bar.sync %0, %1;}" :: "n"(id), "n"(cnt), "r"(a) : "memory");
}
__device__ __forceinline__ void fence_async_smem() { asm volatile("fence.proxy.async.shared::cta;" ::: "memory"); }
__device__ __forceinline__ void fence_async_global() { asm volatile("fence.proxy.async.global;" ::: "memory"); }
__device__ __forceinline__ void mbar_init(uint32_t mb, int cnt) { asm volatile("mbarrier.init.shared::cta.b64 [%0], %1;" :: "r"(mb), "r"(cnt) : "memory"); }
__device__ __forceinline__ void mbar_arrive(uint32_t mb) { asm volatile("mbarrier.arrive.shared::cta.b64 _, [%0];" :: "r"(mb) : "memory"); }
__device__ __forceinline__ void mbar_expect(uint32_t mb, uint32_t bytes) {
  asm volatile("mbarrier.arrive.expect_tx.shared::cta.b64 _, [%0], %1;" :: "r"(mb), "r"(bytes) : "memory");
}
__device__ __forceinline__ void mbar_wait(uint32_t mb, uint32_t parity) {
  asm volatile("{.reg .pred p;\nW: mbarrier.try_wait.parity.shared::cta.b64 p, [%0], %1;\n@!p bra W;}" :: "r"(mb), "r"(parity) : "memory");
}
template <int K> __device__ __forceinline__ void mbar_wait_step(uint32_t mb, int n) {
  asm volatile("{.reg .pred p; .reg .b32 t; add.u32 t, %1, %2; and.b32 t, t, 1;\nW: mbarrier.try_wait.parity.shared::cta.b64 p, [%0], t;\n@!p bra W;}" :: "r"(mb), "r"(n), "n"(2 * K) : "memory");
}
__device__ __forceinline__ void bulk_load(uint32_t dst, const void* src, uint32_t bytes, uint32_t mb) {
  asm volatile("cp.async.bulk.shared::cluster.global.mbarrier::complete_tx::bytes [%0], [%1], %2, [%3];" :: "r"(dst), "l"(src), "r"(bytes), "r"(mb) : "memory");
}
__device__ __forceinline__ void bulk_store(void* dst, uint32_t src, uint32_t bytes) {
  asm volatile("cp.async.bulk.global.shared::cta.bulk_group [%0], [%1], %2;" :: "l"(dst), "r"(src), "r"(bytes) : "memory");
}
__device__ __forceinline__ uint32_t mapa(uint32_t a, uint32_t rank) {
  uint32_t r; asm("mapa.shared::cluster.u32 %0, %1, %2;" : "=r"(r) : "r"(a), "r"(rank)); return r;
}
__device__ __forceinline__ void st_async4(uint32_t dst, float a, float b, float c, float d, uint32_t mb) {
  asm volatile("st.async.shared::cluster.mbarrier::complete_tx::bytes.v4.f32 [%0], {%1,%2,%3,%4}, [%5];" :: "r"(dst), "f"(a), "f"(b), "f"(c), "f"(d), "r"(mb) : "memory");
}
__device__ __forceinline__ void st_async1(uint32_t dst, uint32_t a, uint32_t mb) {
  asm volatile("st.async.shared::cluster.mbarrier::complete_tx::bytes.u32 [%0], %1, [%2];" :: "r"(dst), "r"(a), "r"(mb) : "memory");
}
__device__ __forceinline__ uint4 lds128(uint32_t a) {
  uint4 v; asm volatile("ld.shared.v4.u32 {%0,%1,%2,%3}, [%4];" : "=r"(v.x), "=r"(v.y), "=r"(v.z), "=r"(v.w) : "r"(a) : "memory"); return v;
}
__device__ __forceinline__ uint2 lds64(uint32_t a) {
  uint2 v; asm volatile("ld.shared.v2.u32 {%0,%1}, [%2];" : "=r"(v.x), "=r"(v.y) : "r"(a) : "memory"); return v;
}
__device__ __forceinline__ uint32_t lds32(uint32_t a) {
  uint32_t v; asm volatile("ld.shared.u32 %0, [%1];" : "=r"(v) : "r"(a) : "memory"); return v;
}
__device__ __forceinline__ void sts128(uint32_t a, uint4 v) {
  asm volatile("st.shared.v4.u32 [%0], {%1,%2,%3,%4};" :: "r"(a), "r"(v.x), "r"(v.y), "r"(v.z), "r"(v.w) : "memory");
}
__device__ __forceinline__ void sts32(uint32_t a, uint32_t x) { asm volatile("st.shared.u32 [%0], %1;" :: "r"(a), "r"(x) : "memory"); }
__device__ __forceinline__ void ldsm4(uint32_t& r0, uint32_t& r1, uint32_t& r2, uint32_t& r3, uint32_t a) {
  asm volatile("ldmatrix.sync.aligned.m8n8.x4.shared.b16 {%0,%1,%2,%3}, [%4];" : "=r"(r0), "=r"(r1), "=r"(r2), "=r"(r3) : "r"(a) : "memory");
}
__device__ __forceinline__ void ldsm4t(uint32_t& r0, uint32_t& r1, uint32_t& r2, uint32_t& r3, uint32_t a) {
  asm volatile("ldmatrix.sync.aligned.m8n8.x4.trans.shared.b16 {%0,%1,%2,%3}, [%4];" : "=r"(r0), "=r"(r1), "=r"(r2), "=r"(r3) : "r"(a) : "memory");
}
__device__ __forceinline__ void stsm4(uint32_t a, uint32_t r0, uint32_t r1, uint32_t r2, uint32_t r3) {
  asm volatile("stmatrix.sync.aligned.m8n8.x4.shared.b16 [%0], {%1,%2,%3,%4};" :: "r"(a), "r"(r0), "r"(r1), "r"(r2), "r"(r3) : "memory");
}
__device__ __forceinline__ uint32_t movmat(uint32_t a) {
  uint32_t d; asm volatile("movmatrix.sync.aligned.m8n8.trans.b16 %0, %1;" : "=r"(d) : "r"(a)); return d;
}
__device__ __forceinline__ void mma16(float* d, uint32_t a0, uint32_t a1, uint32_t a2, uint32_t a3, uint32_t b0, uint32_t b1) {
  asm volatile("mma.sync.aligned.m16n8k16.row.col.f32.bf16.bf16.f32 {%0,%1,%2,%3}, {%4,%5,%6,%7}, {%8,%9}, {%0,%1,%2,%3};"
    : "+f"(d[0]), "+f"(d[1]), "+f"(d[2]), "+f"(d[3]) : "r"(a0), "r"(a1), "r"(a2), "r"(a3), "r"(b0), "r"(b1));
}
__device__ __forceinline__ void mma8(float* d, uint32_t a0, uint32_t a1, uint32_t b0) {
  asm volatile("mma.sync.aligned.m16n8k8.row.col.f32.bf16.bf16.f32 {%0,%1,%2,%3}, {%4,%5}, {%6}, {%0,%1,%2,%3};"
    : "+f"(d[0]), "+f"(d[1]), "+f"(d[2]), "+f"(d[3]) : "r"(a0), "r"(a1), "r"(b0));
}
__device__ __forceinline__ float rcp(float x) { float r; asm("rcp.approx.ftz.f32 %0, %1;" : "=f"(r) : "f"(x)); return r; }
__device__ __forceinline__ float ex2(float x) { float r; asm("ex2.approx.ftz.f32 %0, %1;" : "=f"(r) : "f"(x)); return r; }

__host__ __device__ constexpr uint64_t mkdesc(uint32_t off, uint32_t lbo, uint32_t sbo, uint32_t swz) {
  return (uint64_t)((SBASE + off) >> 4) | ((uint64_t)(lbo >> 4) << 16) | ((uint64_t)(sbo >> 4) << 32) | ((uint64_t)swz << 62);
}
__host__ __device__ constexpr uint64_t desc_sw128(uint32_t off) { return mkdesc(off, 16, 1024, 1); }
__host__ __device__ constexpr uint64_t desc_n16(uint32_t off) { return mkdesc(off, 256, 128, 0); }
__host__ __device__ constexpr uint64_t desc_m(uint32_t off) { return mkdesc(off, 16, 256, 3); }

__host__ __device__ constexpr uint64_t desc_sw64(uint32_t off) { return mkdesc(off, 16, 512, 2); }

__device__ __forceinline__ void wg_fence() { asm volatile("wgmma.fence.sync.aligned;" ::: "memory"); }
__device__ __forceinline__ void wg_commit() { asm volatile("wgmma.commit_group.sync.aligned;" ::: "memory"); }
template <int N> __device__ __forceinline__ void wg_wait() { asm volatile("wgmma.wait_group.sync.aligned %0;" :: "n"(N) : "memory"); }

#define ACC8(d) "+f"(d[0]), "+f"(d[1]), "+f"(d[2]), "+f"(d[3]), "+f"(d[4]), "+f"(d[5]), "+f"(d[6]), "+f"(d[7])
#define ACC32(d) ACC8(d), ACC8((d + 8)), ACC8((d + 16)), ACC8((d + 24))
#define R8 "{%0,%1,%2,%3,%4,%5,%6,%7}"
#define R32 "{%0,%1,%2,%3,%4,%5,%6,%7,%8,%9,%10,%11,%12,%13,%14,%15,%16,%17,%18,%19,%20,%21,%22,%23,%24,%25,%26,%27,%28,%29,%30,%31}"
template <int SD> __device__ __forceinline__ void wg_rs16(float* d, const uint32_t* a, uint64_t db) {
  asm volatile("wgmma.mma_async.sync.aligned.m64n16k16.f32.bf16.bf16 " R8 ", {%8,%9,%10,%11}, %12, %13, 1, 1, 1;"
    : ACC8(d) : "r"(a[0]), "r"(a[1]), "r"(a[2]), "r"(a[3]), "l"(db), "n"(SD));
}
template <int SD> __device__ __forceinline__ void wg_ss16(float* d, uint64_t da, uint64_t db) {
  asm volatile("wgmma.mma_async.sync.aligned.m64n16k16.f32.bf16.bf16 " R8 ", %8, %9, %10, 1, 1, 1, 1;"
    : ACC8(d) : "l"(da), "l"(db), "n"(SD));
}
template <int SD, uint64_t DA, uint64_t DB> __device__ __forceinline__ void wg_ss16o(float* d, uint32_t oa, uint32_t ob) {
  asm volatile("{.reg .b32 x, y; .reg .b64 a, b; add.u32 x, %8, %10; add.u32 y, %9, %12; mov.b64 a, {x, %11}; mov.b64 b, {y, %13};\n"
               "wgmma.mma_async.sync.aligned.m64n16k16.f32.bf16.bf16 " R8 ", a, b, %14, 1, 1, 1, 1;}"
    : ACC8(d) : "r"(oa), "r"(ob), "n"((uint32_t)DA), "n"((uint32_t)(DA >> 32)), "n"((uint32_t)DB), "n"((uint32_t)(DB >> 32)), "n"(SD));
}
template <int SD> __device__ __forceinline__ void wg_rs64(float* d, const uint32_t* a, uint64_t db) {
  asm volatile("wgmma.mma_async.sync.aligned.m64n64k16.f32.bf16.bf16 " R32 ", {%32,%33,%34,%35}, %36, %37, 1, 1, 0;"
    : ACC32(d) : "r"(a[0]), "r"(a[1]), "r"(a[2]), "r"(a[3]), "l"(db), "n"(SD));
}
template <int SD> __device__ __forceinline__ void wg_ss64(float* d, uint64_t da, uint64_t db) {
  asm volatile("wgmma.mma_async.sync.aligned.m64n64k16.f32.bf16.bf16 " R32 ", %32, %33, %34, 1, 1, 1, 0;"
    : ACC32(d) : "l"(da), "l"(db), "n"(SD));
}
#define WG_RSO(NAME, SHAPE, REGS, ACC, A, TB) \
template <int SD, uint64_t DB> __device__ __forceinline__ void NAME(float* d, uint32_t a0, uint32_t a1, uint32_t a2, uint32_t a3, uint32_t ob) { \
  asm volatile("{.reg .b64 b; mov.b64 b, {" A(4) ", " A(5) "};\nwgmma.mma_async.sync.aligned." SHAPE ".f32.bf16.bf16 " REGS \
               ", {" A(0) "," A(1) "," A(2) "," A(3) "}, b, " A(6) ", 1, 1, " TB ";}" \
    : ACC(d) : "r"(a0), "r"(a1), "r"(a2), "r"(a3), "r"(ob + (uint32_t)DB), "n"((uint32_t)(DB >> 32)), "n"(SD)); \
}
#define ACC4(d) "+f"(d[0]), "+f"(d[1]), "+f"(d[2]), "+f"(d[3])
#define ACC16(d) ACC8(d), ACC8((d + 8))
#define OP4(i) OP4_##i
#define OP4_0 "%4"
#define OP4_1 "%5"
#define OP4_2 "%6"
#define OP4_3 "%7"
#define OP4_4 "%8"
#define OP4_5 "%9"
#define OP4_6 "%10"
#define OP16(i) OP16_##i
#define OP16_0 "%16"
#define OP16_1 "%17"
#define OP16_2 "%18"
#define OP16_3 "%19"
#define OP16_4 "%20"
#define OP16_5 "%21"
#define OP16_6 "%22"
#define OP32(i) OP32_##i
#define OP32_0 "%32"
#define OP32_1 "%33"
#define OP32_2 "%34"
#define OP32_3 "%35"
#define OP32_4 "%36"
#define OP32_5 "%37"
#define OP32_6 "%38"
WG_RSO(wg_rs8o, "m64n8k16", "{%0,%1,%2,%3}", ACC4, OP4, "1")
#define R16 "{%0,%1,%2,%3,%4,%5,%6,%7,%8,%9,%10,%11,%12,%13,%14,%15}"
WG_RSO(wg_rs32o, "m64n32k16", R16, ACC16, OP16, "1")
WG_RSO(wg_rs64o, "m64n64k16", R32, ACC32, OP32, "0")
WG_RSO(wg_rs32k, "m64n32k16", R16, ACC16, OP16, "0")
template <uint64_t DA, uint64_t DB> __device__ __forceinline__ void wg_ss32k(float* d, uint32_t ob) {
  asm volatile("{.reg .b64 b; mov.b64 b, {%17, %18};\nwgmma.mma_async.sync.aligned.m64n32k16.f32.bf16.bf16 " R16 ", %16, b, 1, 1, 1, 1, 0;}"
    : ACC16(d) : "l"(DA), "r"(ob + (uint32_t)DB), "n"((uint32_t)(DB >> 32)));
}
template <int N> __device__ __forceinline__ void reg_inc() { asm volatile("setmaxnreg.inc.sync.aligned.u32 %0;" :: "n"(N)); }
template <int N> __device__ __forceinline__ void reg_dec() { asm volatile("setmaxnreg.dec.sync.aligned.u32 %0;" :: "n"(N)); }

template <int KS>
__device__ __forceinline__ void load_frags(uint32_t* a, uint32_t src) {
  const int lane = threadIdx.x & 31, w = (threadIdx.x >> 5) & 3;
  const int k = ((lane >> 4) << 3) + (lane & 7), u = w * 2 + ((lane >> 3) & 1);
  const uint32_t base = src + k * 128 + ((u ^ (k & 7)) << 4);
#pragma unroll
  for (int ks = 0; ks < KS; ks++) ldsm4t(a[ks * 4], a[ks * 4 + 1], a[ks * 4 + 2], a[ks * 4 + 3], base + ks * 2048);
}

__device__ __forceinline__ uint32_t badd2(uint32_t a, uint32_t b) { uint32_t r; asm("add.rn.bf16x2 %0, %1, %2;" : "=r"(r) : "r"(a), "r"(b)); return r; }
__device__ __forceinline__ uint32_t bsub2(uint32_t a, uint32_t b) { uint32_t r; asm("sub.rn.bf16x2 %0, %1, %2;" : "=r"(r) : "r"(a), "r"(b)); return r; }
__device__ __forceinline__ uint32_t bmul2(uint32_t a, uint32_t b) { uint32_t r; asm("mul.rn.bf16x2 %0, %1, %2;" : "=r"(r) : "r"(a), "r"(b)); return r; }
__device__ __forceinline__ uint32_t bfma2(uint32_t a, uint32_t b, uint32_t c) { uint32_t r; asm("fma.rn.bf16x2 %0, %1, %2, %3;" : "=r"(r) : "r"(a), "r"(b), "r"(c)); return r; }
template <int R> __device__ __forceinline__ void layernorm9(const uint32_t* x, uint32_t* o) {
  const uint32_t ones = 0x3F803F80u;
  float a[R][3][4], q[R], s[R];
#pragma unroll
  for (int i = 0; i < 9 * R; i++) {
    float* d = a[i % R][i / R % 3];
    if (i < 3 * R) d[0] = d[1] = d[2] = d[3] = 0.f;
    mma8(d, x[i % R * 9 + i / R], ones, x[i % R * 9 + i / R]);
  }
#pragma unroll
  for (int r = 0; r < R; r++) {
    q[r] = threadIdx.x & 4 ? a[r][0][1] + a[r][1][1] + a[r][2][1] : a[r][0][0] + a[r][1][0] + a[r][2][0];
    s[r] = (a[r][0][2] + a[r][0][3]) + (a[r][1][2] + a[r][1][3]) + (a[r][2][2] + a[r][2][3]);
  }
#pragma unroll
  for (int r = 0; r < R; r++) { q[r] += __shfl_xor_sync(~0u, q[r], 4); s[r] += __shfl_xor_sync(~0u, s[r], 1); }
#pragma unroll
  for (int r = 0; r < R; r++) { q[r] += __shfl_xor_sync(~0u, q[r], 9); s[r] += __shfl_xor_sync(~0u, s[r], 2); }
#pragma unroll
  for (int r = 0; r < R; r++) q[r] = __shfl_sync(~0u, q[r], 0) + __shfl_sync(~0u, q[r], 18);
#pragma unroll
  for (int r = 0; r < R; r++) {
    const float mean = s[r] * (1.f / DM), var = fmaxf(fmaf(q[r], 1.f / DM, -mean * mean), 0.f);
    float sd;
    asm("sqrt.approx.ftz.f32 %0, %1;" : "=f"(sd) : "f"(bf_lo(pack2(bf_lo(pack2(var, 0.f)) + 1e-5f, 0.f))));
    const float inv = rcp(bf_lo(pack2(sd, 0.f)));
    const uint32_t mb = pack2(mean, mean), hi = pack2(inv, inv), lo = pack2(inv - bf_lo(hi), inv - bf_lo(hi));
#pragma unroll
    for (int i = r * 9; i < r * 9 + 9; i++) {
      const uint32_t d = bsub2(x[i], mb);
      o[i] = bfma2(d, hi, bmul2(d, lo));
    }
  }
}
__device__ __forceinline__ void store_ln_row(int layer, int tok, const uint32_t* o) {
  const int lane = threadIdx.x & 31, r = tok & 31;
  unsigned char* p = g_lnimg + (size_t)(layer * NSEG + (tok >> 5)) * (9 * 4096) + r * 128 + (((lane >> 2) ^ (r & 7)) << 4) + (lane & 3) * 4;
#pragma unroll
  for (int i = 0; i < 9; i++) *(uint32_t*)(p + i * 4096) = o[i];
}
struct Params { CUtensorMap map[11]; const bf16 *X, *K, *V, *shift, *Hk, *Dk, *mem0, *Wq, *Wk, *Wv, *Wo; bf16* out; uint32_t dly[26]; };
#define DLYS P.dly[0]
#define DLYW P.dly[1]
#define DLYV P.dly[24]
#define DLYK P.dly[4]
#define DLYO P.dly[25]
#define DLYG P.dly[5]
#define KWIN P.dly[6]
#define KMIN P.dly[7]
#define PREF0 P.dly[19]
#define PACE P.dly[20]
#define S1G P.dly[21]
#define S1DLY P.dly[22]
#define PREFH P.dly[23]
uint32_t h_dly[26] = {800, 120, 150, 160, 3640, 4160, 2750, 1300, 1585, 1670, 1760, 2090, 2210, 2310, 2790, 2920, 3185, 3330, 3500, 7000, 160, 12500, 20500, 4000, 3540, 400};

constexpr uint32_t C_W = 0, C_M = 147456, C_KV = C_M + 18432, C_OS = C_KV + 24576, C_QM = C_KV + 32768, C_KM = C_QM + 2048,
                   C_VM = C_KM + 2048, C_OI = C_VM + 2048, C_SX = C_OI + 4096, C_KM2 = C_SX + 2560, C_VM2 = C_KM2 + 128,
                   C_KV2 = C_KM2 + 2048, C_Q = C_KV2 + 8192, C_BAR = C_Q + 8192;
constexpr uint32_t CB_FULL = C_BAR, CB_REF = C_BAR + 16, CB_SX = C_BAR + 32, CB_OX = C_BAR + 40, CB_XX = C_BAR + 48, CB_Q = C_BAR + 56, C_BAD = C_BAR + 64, W_BAR = C_BAR + 80, T_BAR = W_BAR + 24, S_GEN = C_BAR + 128, C_REF = C_BAR + 132, CB_VF = C_BAR + 144, CB_M = C_BAR + 160, CB_MV = C_BAR + 200;
constexpr uint32_t G_W = 0, G_RING = 147456, G_W2 = G_RING + 9 * 8192, G_BAR = G_W2 + 8192;
constexpr uint32_t O_W = 0, O_RING = 3 * 40960, O_ST = O_RING + 11 * 8192, O_BAR = O_ST + 16384, OB_ST = O_BAR + 64;
constexpr uint32_t F_A = 0, F_XY = 36864, F_L = F_XY + 36864, F_X = F_L + 18432, F_Y = F_L + 2 * 36864, F_BAR = C_BAR;
constexpr uint32_t SMEM_BYTES = C_BAR + 256;
static_assert(G_BAR + 256 <= SMEM_BYTES && O_BAR + 256 <= SMEM_BYTES && F_BAR + 16 <= SMEM_BYTES && SMEM_BYTES <= 232448, "smem map");
enum { B_INIT = 1, B_M, B_QK, B_S, B_V, B_O, B_X, B_WG0, B_WG1, B_WG2, B_G, B_OE, B_T, B_R };

__device__ __forceinline__ uint4 pack_partial(const float* d, uint32_t tag) {
  uint32_t x, z;
  asm("lop3.b32 %0, %2, 1, %4, 0xb8; lop3.b32 %1, %3, 1, %4, 0xb8;" : "=&r"(x), "=&r"(z) : "r"(pack2(d[0], d[1])), "r"(pack2(d[2], d[3])), "r"(tag));
  return make_uint4(x, pack2(d[4], d[5]), z, pack2(d[6], d[7]));
}
__device__ __forceinline__ void store_partial(uint4* p, const uint4& v) { st_b128(p, v.x, v.y, v.z, v.w); }
__device__ __forceinline__ void gather_reduce(const uint32_t* p, uint32_t* dst, uint32_t m0, bool shared, uint32_t tag, uint32_t lane, uint32_t sb, int n, int TS0) {
  int tries = 0;
  bool bad;
  TR(TS0);
  do {
    uint2 x[8];
#pragma unroll
    for (int i = 0; i < 8; i++)
      asm volatile("{.reg .b64 v; ld.relaxed.gpu.global.b64 v, [%2]; mov.b64 {%0, %1}, v;}" : "=r"(x[i].x), "=r"(x[i].y) : "l"(p + i * 128) : "memory");
    spin_guard(tries);
    float a = bf_lo(x[0].x), b = bf_hi(x[0].x), c = bf_lo(x[0].y), d = bf_hi(x[0].y);
    uint32_t t = x[0].x ^ tag;
#pragma unroll
    for (int i = 1; i < 8; i++) {
      a += bf_lo(x[i].x); b += bf_hi(x[i].x); c += bf_lo(x[i].y); d += bf_hi(x[i].y);
      asm("lop3.b32 %0, %0, %1, %2, 0xf6;" : "+r"(t) : "r"(x[i].x), "r"(tag));
    }
    bad = __any_sync(~0u, t & 1);
    const bool up = lane & 8;
    float u = (up ? c : a) + __shfl_xor_sync(~0u, up ? a : c, 8), v = (up ? d : b) + __shfl_xor_sync(~0u, up ? b : d, 8);
    if (shared) { u += __shfl_xor_sync(~0u, u, 4); v += __shfl_xor_sync(~0u, v, 4); }
    u += __shfl_xor_sync(~0u, u, 16);
    v += __shfl_xor_sync(~0u, v, 16);
    st_relaxed_if(dst, n < LAG && up ? m0 : pack2(u, v), !bad);
  } while (bad);
  if (shared) bar_arrive(B_WG2, 224);
  TR(TS0 + 3); TRV(TS0 + 2, tries);
  CNT((TS0 - 16) >> 2, tries);
}

constexpr int XR = 3;
__host__ __device__ constexpr int o_ks(int s) { return s & (s < 8 ? 3 : 7); }
constexpr uint32_t OPAT = 0x55555577u;
__host__ __device__ constexpr bool o_reg(int s) { return (OPAT >> s) & 1; }
__host__ __device__ constexpr int o_slot(int s) { int k = 0; for (int i = 0; i < s; i++) k += o_reg(i) == o_reg(s); return k; }
__device__ __forceinline__ int g_unit(int wg) {
  const int i = bid() - N_CHAIN;
  return i < 32 ? wg * 64 + i : 2 * i - 32 + wg;
}
__device__ __forceinline__ uint32_t pinned(uint32_t v) { return __shfl_sync(~0u, v, threadIdx.x & 31); }
template <class T> __device__ __forceinline__ T* pinned(T* p) { return (T*)__shfl_sync(~0u, (unsigned long long)p, threadIdx.x & 31); }
enum { CHAIN, GROLE, OROLE };
template <int ROLE, bool SYNC> __device__ __forceinline__ void load_box(const Params& P, uint32_t sb, bool regs, int wg, int i, uint32_t mb, bool on) {
  const int b = bid();
  int map, col = 0, ks = 0, c2 = 0, c3 = 0;
  uint32_t dst = wg * 73728;
  if (ROLE == CHAIN) {
    const int k = i - 1, st = __fns(regs ? OPAT : ~OPAT, 0, i) & 31;
    dst += i ? (17 + i) * 2048 : 0;
    if (wg || i == 0) { map = wg + i; col = b * 64; c3 = !regs; }
    else if (!regs && k >= 14) { map = 6; ks = b * 4 + k - 14; }
    else { map = 6; col = 64 + (st < 8 ? (st >> 2) * 64 : (st >> 3) * 128 + (b & 1) * 64); ks = (b * 4) ^ o_ks(st); }
  } else if (ROLE == GROLE) {
    const int q = g_unit(wg);
    map = ((q >> 5) + 1) % 3;
    if (i) { map += 3; col = (q & 31) * 128 + (i - 1) * 64; ks = 34; dst = G_W2 + wg * 4096 + (i - 1) * 2048; }
    else { map += 8; c2 = (q & 31) * 2; c3 = !regs; }
  } else {
    const int o = b - N_CHAIN - N_G, ksl = o / 3;
    map = 7; col = ((o % 3) * 3 + (wg + ksl) % 3) * 64; dst = (wg * (regs ? 24 : 20) + i) * 2048;
    ks = (ksl * 11 - max(ksl - 4, 0)) * 4 + (regs ? i / 3 * 5 + i % 3 * 2 : i < 16 ? i / 2 * 5 + 1 + i % 2 * 2 : i + 24);
    c3 = (ks & 1) * 2; ks >>= 1;
  }
  if (SYNC) { col = pinned(col); ks = pinned(ks); bar_sync(B_WG0 + wg, 256); }
  if (on) asm volatile("cp.async.bulk.tensor.5d.shared::cluster.global.tile.mbarrier::complete_tx::bytes [%0], [%1, {%2, %3, %4, %5, %6}], [%7];"
               :: "r"(sb + dst), "l"(&P.map[map]), "r"(col), "r"(0), "r"(c2), "r"(c3), "r"(ks), "r"(mb) : "memory");
}
template <int ROLE, bool SYNC = false> __device__ __forceinline__ void load_wg(const Params& P, uint32_t sb, bool regs, int wg, int quarter) {
  const int i = (threadIdx.x & 31) * 4 + quarter;
  const int n = ROLE == CHAIN ? 36 : ROLE == GROLE ? (regs ? 38 : 36) : regs ? 24 : bid() < N_CHAIN + N_G + 12 ? 20 : 16;
  const bool split = SYNC && wg == 0;
  const uint32_t mb = split && i ? sb + T_BAR : sb + W_BAR + wg * 8;
  load_box<ROLE, SYNC>(P, sb, regs, wg, i, mb, i < (ROLE == CHAIN ? (wg ? 2 : 19) : ROLE == GROLE ? n - 35 : n));
  if (i <= split) mbar_expect(mb, n * (split ? 1024 : 2048));
  __syncwarp();
}
__device__ __forceinline__ uint32_t near_half(uint32_t blk, uint32_t reader) {
  return __ldcg(g_near + (blk >> 3)) ^ (~blk & 1) ^ __ldcg(g_side + (blk >> 3)) ^ __ldcg(g_side + reader);
}

__device__ __forceinline__ uint32_t opaque_tid() { uint32_t t; asm volatile("mov.u32 %0, %%tid.x;" : "=r"(t)); return t; }
__device__ __forceinline__ void m_fetch(uint32_t sb, uint32_t src, uint32_t b, uint32_t mb) {
  bulk_load(sb + C_M + (b ? b * 4096 - 2048 : 0), (const unsigned char*)g_mimg + ((src ^ ((b & 1) * 4096)) + b * 8192), b ? 4096 : 2048, mb);
}
__device__ __forceinline__ uint32_t m_probe(uint32_t lane) { return lane * 32 + (lane & 4) * 4 + (lane >> 3) * 4; }
__device__ __forceinline__ uint32_t m_max(uint32_t a, uint32_t b) {
  return max(max(lds32(a), lds32(a + 1024)), max(lds32(b), lds32(b + 1024)));
}
template <int S0, int N> __device__ __forceinline__ void o_steps(float* d, const uint32_t* a) {
  constexpr int SD = o_ks(S0) != 0;
  if constexpr (o_reg(S0)) wg_rs16<SD>(d, a + (18 + o_slot(S0)) * 4, desc_n16(C_OI + o_ks(S0) * 512));
  else wg_ss16<SD>(d, desc_sw128(C_W + (18 + o_slot(S0)) * 2048), desc_n16(C_OI + o_ks(S0) * 512));
  if constexpr (N > 1) o_steps<S0 + 1, N - 1>(d, a);
}
template <int BASE, int KS, int N> __device__ __forceinline__ void m_steps(float* d, const uint32_t* a, uint32_t oa) {
  wg_rs16<KS != 0>(d, a + (BASE + KS / 2) * 4, desc_m(C_M + KS * 512));
  if constexpr (KS >= 36 - 2 * XR) wg_rs16<1>(d, a + (18 + XR + KS / 2) * 4, desc_m(C_M + KS * 512 + 512));
  else wg_ss16o<1, desc_sw128(C_W + (BASE + KS / 2) * 2048), desc_m(C_M + KS * 512 + 512)>(d, oa, 0);
  if constexpr (N > 2) m_steps<BASE, KS + 2, N - 2>(d, a, oa);
}

constexpr uint32_t VPAT = 0x15bbd249u;
template <int I, int R, int S> __device__ __forceinline__ void v_steps(float* d, const uint32_t* a) {
  constexpr bool reg = (VPAT >> I) & 1;
  if constexpr (reg) wg_rs16<1>(d, a + (18 + R) * 4, desc_m(C_M + R * 1024));
  else wg_ss16<1>(d, desc_sw128(C_W + (54 + S) * 2048), desc_m(C_M + S * 1024 + 512));
  if constexpr (I < 31) v_steps<I + 1, R + reg, S + !reg>(d, a);
  else static_assert(R + reg == 18, "pattern");
}

__device__ __forceinline__ void chain_proj(const Params& P, uint32_t sb) {
  const uint32_t c = chain_id(), h = c >> 1, j = c & 1, wid = __shfl_sync(~0u, threadIdx.x >> 5, 0), wg = wid >> 2, w = wid & 3;
  const uint32_t t = threadIdx.x & 127, lane = pinned(t & 31), mine = pinned(sb + t * 16), rb = mapa(sb, j ^ 1);
  const uint32_t theirs = pinned(rb + C_KM2 + w * 512 + lane * 4), oa = wg * 4608;
  uint32_t a[144 + 4 * XR];
  mbar_wait(sb + W_BAR + wg * 8, 0);
  if (threadIdx.x == 0) TS(23);
  load_frags<36>(a, sb + C_W + wg * 73728);
  fence_async_smem();
  bar_arrive(B_WG0 + wg, 256);
  if (threadIdx.x == 0) TS(24);
  bar_sync(B_WG2, 384);
  const uint32_t round = min(wid ^ 4, 5u), gdly = P.dly[8 + round], ps = t >> 2, pf = j * 16 + (ps >> 1);
  const bool shared = round < 3;
  uint4* const dsts = pinned(g_xb + (ps * 4096 + near_half(ps * 8, ps * 2) * 256 + c * 4 + (t & 3)));
  uint4* const dstf = pinned(g_xb + (pf * 4096 + 512 + near_half(pf * 8 + 1, pf * 2) * 256 + h * 8 + (t & 7)));
  const uint32_t* const gsrc = (const uint32_t*)g_xb + (h * 16384 + round % 3 * 4096 + near_half(h * 8 + !shared, h * 2) * 1024 +
                               (shared ? lane * 4 + j * 2 : 2048 + (lane & 24) * 4 + j * 16 + (lane & 7) * 2));
  uint32_t* gdst = g_mimg + (16384 + (lane >> 4) * 1024 +
                   (shared ? (round ? 1536 + round * 512 : 0) + c * 8 + (((lane >> 1) ^ c) & 4) + (lane & 3)
                           : (round - 1) * 2048 + c * 16 + (lane & 1) * 8 + (((lane >> 1) ^ (c * 2)) & 4) + ((lane >> 1) & 3)));
  const uint32_t m0 = __ldcg(gdst - 16384);
  mbar_wait(sb + W_BAR + wg * 8, 1);
  load_frags<XR>(a + 144, sb + C_W + wg * 73728 + (18 - XR) * 2048);
  bar_sync(B_INIT, 256);
  if ((threadIdx.x & 127) == 0) TS(4);

  uint32_t ring = 1;
#pragma unroll 1
  for (int n = 0; n < STEPS; n++) {
    float d[8], e[8];
    if (n + 1 == STEPS && !wg) { bar_arrive(B_QK, 416); break; }
#pragma unroll
    for (int i = 0; i < 8; i++) e[i] = 0.f;
    uint32_t redo = n + 1;
#pragma unroll 1
    do {
      mbar_wait(sb + CB_M, n & 1);
      wg_fence();
      m_steps<0, 0, 4>(d, a, oa);
      wg_commit();
      if (wg) { wg_fence(); m_steps<18, 0, 4>(e, a, 4608); wg_commit(); }
      if (wid == 0) TR(8);
      mbar_wait(sb + CB_M + 8, n & 1);
      wg_fence();
      m_steps<0, 4, 8>(d, a, oa);
      wg_commit();
      mbar_wait(sb + CB_MV, n & 1);
      asm volatile("{.reg .pred p; .reg .u32 t; ld.shared.u32 t, [%1]; setp.eq.u32 p, t, %0; selp.u32 %0, -1, 0, p;}" : "+r"(redo) : "r"(sb + C_BAD) : "memory");
    } while (redo);
    mbar_wait(sb + CB_MV + 8, n & 1);
    wg_fence();
    m_steps<0, 12, 8>(d, a, oa);
    wg_commit();
    mbar_wait(sb + CB_MV + 16, n & 1);
    wg_fence();
    m_steps<0, 20, 8>(d, a, oa);
    wg_commit();
    mbar_wait(sb + CB_MV + 24, n & 1);
    wg_fence();
    m_steps<0, 28, 8>(d, a, oa);
    wg_commit();
    wg_wait<0>();
    if (w == 0) TR(6 + wg);
    const uint32_t f0 = pack2(d[0], d[1]), f1 = pack2(d[4], d[5]), f2 = pack2(d[2], d[3]), f3 = pack2(d[6], d[7]);
    stsm4(mine + C_QM + wg * 2048, f0, f1, f2, f3);
    bar_arrive(B_QK, 416);
    const uint32_t tag = (n & 1) ^ 1;
    if (n == 0) mbar_wait(sb + T_BAR, 0);
    if (wg) {
      if (n + 1 < STEPS) bar_sync(B_S, 256);
      wg_fence();
      v_steps<0, 2, 2>(e, a);
      wg_commit();
      const uint32_t k0 = j ? f0 : f1, k1 = j ? f2 : f3;
      mbar_wait(sb + CB_SX, n & 1);
      wg_wait<0>();
      if (w == 0) TR(11);
      const uint32_t v0 = pack2(e[0], e[1]), v1 = pack2(e[4], e[5]), v2 = pack2(e[2], e[3]), v3 = pack2(e[6], e[7]);
      stsm4(mine + C_VM, v0, v1, v2, v3);
      bar_arrive(B_V, 256);
      st_async1(theirs, k0, rb + CB_XX);
      st_async1(theirs + 256, k1, rb + CB_XX);
      st_async1(theirs + 128, j ? v0 : v1, rb + CB_XX);
      st_async1(theirs + 384, j ? v2 : v3, rb + CB_XX);
      if (n + 1 == STEPS) break;
      bar_sync(B_O, 256);
      fence_async_smem();
      wg_fence();
#pragma unroll
      for (int ks = 0; ks < 4; ks++) {
        if (ks == 0) wg_ss16<0>(d, desc_sw128(C_W + 32 * 2048), desc_n16(C_OI));
        else wg_ss16<1>(d, desc_sw128(C_W + (32 + ks) * 2048), desc_n16(C_OI + ks * 512));
      }
      wg_commit();
      bar_arrive(B_X, 256);
      if (w == 0) TR(0);
      wg_wait<0>();
      store_partial(dsts, pack_partial(d, tag));
      bar_arrive(B_M, 160);
      if (w == 0) TR(1);
    } else {
      bar_sync(B_X, 256);
      wg_fence();
      o_steps<0, 4>(d, a);
      wg_commit();
      o_steps<4, 4>(e, a);
      wg_commit();
      wg_wait<1>();
      store_partial(dsts + 1024, pack_partial(d, tag));
      if (w == 0) TR(2);
      wg_wait<0>();
      store_partial(dsts + 2048, pack_partial(e, tag));
      if (w == 0) TR(3);
      wg_fence();
      o_steps<8, 4>(d, a);
      wg_commit();
      bar_sync(B_T, 256);
      if (w == 0) { TRV(61, 0); TR(12); }
      wg_fence();
      o_steps<12, 4>(d, a);
      wg_commit();
      o_steps<16, 8>(e, a);
      wg_commit();
      wg_wait<1>();
      store_partial(dstf, pack_partial(d, tag));
      if (w == 0) TR(4);
      wg_fence();
      o_steps<24, 8>(d, a);
      wg_commit();
      wg_wait<1>();
      store_partial(dstf + 1024, pack_partial(e, tag));
      bar_arrive(B_OE, 256);
      if (w == 0) TR(5);
      wg_wait<0>();
      store_partial(dstf + 2048, pack_partial(d, tag));
      if (w == 0) TR(15);
    }
    if ((wid ^ 4) < 6) {
      mbar_wait(sb + CB_REF, n & 1);
      wait_until(lds32(sb + C_REF), gdly);
      gather_reduce(gsrc, gdst, m0, shared, tag, lane, sb, n, 16 + round * 4);
      if (++ring == MRING) { ring = 0; gdst -= MRING * 16384; }
      gdst += 16384;
    }
  }
}

template <int KS> __device__ __forceinline__ void x_scores(float* s, float* sm, const uint4* q, uint32_t ok, uint32_t om) {
  wg_rs32o<KS != 0, desc_sw64(C_KV + KS * 1024)>(s, q[KS].x, q[KS].y, q[KS].z, q[KS].w, ok);
  wg_rs8o<KS != 0, desc_n16(C_KM + KS * 512)>(sm, q[KS].x, q[KS].y, q[KS].z, q[KS].w, om);
  if constexpr (KS < 3) x_scores<KS + 1>(s, sm, q, ok, om);
}

__device__ __forceinline__ void chain_attn(const Params& P, uint32_t sb) {
  const int c = chain_id(), j = c & 1;
  const int tid = threadIdx.x, lane = tid & 31, w = __shfl_sync(~0u, (tid >> 5) & 3, 0);
  const int l = w >> 1, u = w & 1;
  const uint32_t rb = mapa(sb, j ^ 1);
  const float sc = 0.08838834764831845f * 1.4426950408889634f;
  const uint32_t ones = 0x3F803F80u, sx = C_SX + l * 1280;
  const uint32_t km_off = C_KM + (lane >> 3) * 256 + l * 128 + (lane & 7) * 16;
  const uint32_t qm_off = C_QM + (lane >> 4) * 256 + l * 128 + (lane & 7) * 16, kmu = pinned(sb + km_off + u * 1024);
  const uint32_t kv_off = C_KV + l * 4096 + (lane & 15) * 64 + (((lane >> 4) ^ (u * 2) ^ ((lane >> 1) & 3)) << 4);

  load_wg<CHAIN, true>(P, sb, false, 1, w);
  if (lane == 0) mbar_arrive(sb + CB_M);
#pragma unroll 1
  for (int n = 0; n < STEPS; n++) {
    const uint32_t kvb = sb + kv_off + (n & 1) * 16384;
    mbar_wait(sb + CB_FULL + (n & 1) * 8, (n >> 1) & 1);
    if (n < 3 && tid == 256) TS(n ? 20 + n : 5);
    __syncwarp();
    {
      uint32_t km[8];
      uint4 kx[8];
#pragma unroll
      for (int i = 0; i < 8; i++) ldsm4t(kx[i].x, kx[i].y, kx[i].z, kx[i].w, (kvb ^ ((i & 1) * 32)) + (i >> 1) * 1024);
      mbar_wait_step<1>(sb + CB_VF, n);
      if (w == 1) TRD(60, kx[7].x);
      bar_sync(B_QK, 416);
      if (n + 1 == STEPS) {
        st_async4(rb + sx + u * 512 + lane * 16, 0.f, 0.f, 0.f, 0.f, rb + CB_SX);
        st_async1(rb + sx + 1024 + u * 128 + lane * 4, 0, rb + CB_SX);
        bar_sync(B_V, 256);
      } else {
      uint32_t qm[16];
#pragma unroll
      for (int ks = 0; ks < 4; ks++) ldsm4t(qm[4 * ks], qm[4 * ks + 1], qm[4 * ks + 2], qm[4 * ks + 3], sb + qm_off + ks * 512);
      ldsm4t(km[0], km[1], km[2], km[3], sb + km_off);
      ldsm4t(km[4], km[5], km[6], km[7], sb + km_off + 1024);
      float s[5][4];
      uint4 vx[4];
#pragma unroll
      for (int i = 0; i < 5; i++) { s[i][0] = s[i][1] = s[i][2] = s[i][3] = 0.f; }
#pragma unroll
      for (int ks = 0; ks < 4; ks++) {
        const uint32_t* q = qm + 4 * ks;
        if (ks == 1 || ks == 2) {
#pragma unroll
          for (int i = 2 * ks - 2; i < 2 * ks; i++) ldsm4(vx[i].x, vx[i].y, vx[i].z, vx[i].w, ((sb + kv_off) ^ ((i & 1) * 32)) + 8192 + (2 * u + (i >> 1)) * 1024);
        }
        mma16(s[1], q[0], q[1], q[2], q[3], kx[2 * ks].x, kx[2 * ks].y);
        mma16(s[2], q[0], q[1], q[2], q[3], kx[2 * ks].z, kx[2 * ks].w);
        mma16(s[0], q[0], q[1], q[2], q[3], km[2 * ks], km[2 * ks + 1]);
        mma16(s[3], q[0], q[1], q[2], q[3], kx[2 * ks + 1].x, kx[2 * ks + 1].y);
        mma16(s[4], q[0], q[1], q[2], q[3], kx[2 * ks + 1].z, kx[2 * ks + 1].w);
      }
      st_async4(rb + sx + u * 512 + lane * 16, s[1][0], s[1][1], s[2][0], s[2][1], rb + CB_SX);
      st_async1(rb + sx + 1024 + u * 128 + lane * 4, __float_as_uint(u ? s[0][1] : s[0][0]), rb + CB_SX);
      bar_arrive_after<B_S, 256>(__float_as_uint(s[3][0]), __float_as_uint(s[4][0]));
      mbar_wait_step<2>(sb + CB_SX, n);
      const uint4 p0 = lds128(sb + sx + u * 512 + lane * 16), p1 = lds128(sb + sx + (u ^ 1) * 512 + lane * 16);
      const uint2 p2 = make_uint2(lds32(sb + sx + 1024 + lane * 4), lds32(sb + sx + 1152 + lane * 4));
      float t[10] = {s[0][0] + __uint_as_float(p2.x), s[0][1] + __uint_as_float(p2.y),
                     s[1][0] + __uint_as_float(p0.x), s[1][1] + __uint_as_float(p0.y),
                     s[2][0] + __uint_as_float(p0.z), s[2][1] + __uint_as_float(p0.w),
                     s[3][0] + __uint_as_float(p1.x), s[3][1] + __uint_as_float(p1.y),
                     s[4][0] + __uint_as_float(p1.z), s[4][1] + __uint_as_float(p1.w)};
      float mx = fmaxf(fmaxf(fmaxf(fmaxf(t[2], t[3]), fmaxf(t[4], t[5])), fmaxf(fmaxf(t[6], t[7]), fmaxf(t[8], t[9]))), fmaxf(t[0], t[1]));
      mx = fmaxf(fmaxf(mx, __shfl_xor_sync(~0u, mx, 1)), fmaxf(__shfl_xor_sync(~0u, mx, 2), __shfl_xor_sync(~0u, mx, 3)));
      const float ms = -mx * sc;
#pragma unroll
      for (int i = 0; i < 10; i++) t[i] = ex2(fmaf(t[i], sc, ms));
      uint32_t p[5];
#pragma unroll
      for (int i = 0; i < 5; i++) p[i] = pack2(t[2 * i], t[2 * i + 1]);
      p[1] |= (p[0] & p[3] & p[4]) & 0x80008000u;
      float o[2][4], z[4] = {0.f, 0.f, 0.f, 0.f};
      mma16(z, ones, ones, ones, ones, p[1], p[2]);
#pragma unroll
      for (int i = 0; i < 2; i++) {
        o[i][0] = o[i][1] = o[i][2] = o[i][3] = 0.f;
        mma16(o[i], vx[2 * i].x, vx[2 * i].y, vx[2 * i].z, vx[2 * i].w, p[1], p[2]);
      }
      mma16(z, ones, ones, ones, ones, p[3], p[4]);
#pragma unroll
      for (int i = 0; i < 2; i++) mma16(o[i], vx[2 * i + 1].x, vx[2 * i + 1].y, vx[2 * i + 1].z, vx[2 * i + 1].w, p[3], p[4]);
      mma8(z, ones, ones, p[0]);
      bar_sync_after<B_V, 256>(p[1]);
      ldsm4(km[0], km[1], km[2], km[3], kmu + (C_VM - C_KM));
      mma8(o[0], km[0], km[1], p[0]);
      mma8(o[1], km[2], km[3], p[0]);
      const float i0 = rcp(z[0]), i1 = rcp(z[1]);
      const uint32_t oo = C_OI + u * 1024 + l * 128 + lane * 4;
      uint32_t ow[4];
#pragma unroll
      for (int i = 0; i < 2; i++) { ow[2 * i] = pack2(o[i][0] * i0, o[i][1] * i1); ow[2 * i + 1] = pack2(o[i][2] * i0, o[i][3] * i1); }
      stsm4(kmu + (C_OI - C_KM), ow[0], ow[1], ow[2], ow[3]);
      bar_arrive(B_O, 256);
#pragma unroll
      for (int i = 0; i < 4; i++) st_async1(rb + oo + 2048 + i * 256, ow[i], rb + CB_OX);
      }
    }
    {
      const uint32_t lane = opaque_tid() & 31, own = ((n & 1) * 16384 + j * 4096) >> 4;
      float s[16], sm[4], r[16], rm[4];
      {
        uint4 q[4];
        mbar_wait_step<3>(sb + CB_Q, n);
#pragma unroll
        for (int ks = 0; ks < 4; ks++)
          ldsm4t(q[ks].x, q[ks].y, q[ks].z, q[ks].w, sb + C_Q + (lane & 8) * 512 + ks * 1024 + (lane & 16) * 32 + (lane & 7) * 64 + (((w ^ (lane >> 1)) & 3) << 4));
        mbar_wait_step<3>(sb + CB_XX, n);
        if (n + 1 < STEPS) mbar_wait_step<3>(sb + CB_OX, n);
        fence_async_smem();
        if (n + 1 < STEPS) { bar_arrive(B_T, 256); bar_sync(B_OE, 256); }
        if (w == 1) { TRV(61, 0); TR(9); }
        wg_fence();
        x_scores<0>(s, sm, q, own, j * 8);
        x_scores<0>(r, rm, q, (C_KV2 - C_KV) >> 4, (C_KM2 - C_KM) >> 4);
        wg_commit();
        wg_wait<0>();
      }
      const float neg = -1e9f * 11.313708498984761f;
      const int tok = (lane & 24) + 2 * w + ((lane >> 2) & 1), lim = tok - 8 * (int)(lane & 3);
      float t[10] = {sm[0] + rm[2], sm[1] + rm[3]};
#pragma unroll
      for (int i = 0; i < 8; i++) t[2 + i] = i > lim ? neg : s[(i >> 1) * 4 + (i & 1)] + r[(i >> 1) * 4 + (i & 1) + 2];
      float mx = fmaxf(fmaxf(fmaxf(fmaxf(t[2], t[3]), fmaxf(t[4], t[5])), fmaxf(fmaxf(t[6], t[7]), fmaxf(t[8], t[9]))), fmaxf(t[0], t[1]));
      mx = fmaxf(fmaxf(mx, __shfl_xor_sync(~0u, mx, 1)), fmaxf(__shfl_xor_sync(~0u, mx, 2), __shfl_xor_sync(~0u, mx, 3)));
      const float ms = -mx * sc;
#pragma unroll
      for (int i = 0; i < 10; i++) t[i] = ex2(fmaf(t[i], sc, ms));
      uint32_t p[5];
#pragma unroll
      for (int i = 0; i < 5; i++) p[i] = pack2(t[2 * i], t[2 * i + 1]);
      float z = ((t[0] + t[1]) + (t[2] + t[3])) + ((t[4] + t[5]) + (t[6] + t[7])) + (t[8] + t[9]);
      const uint32_t row = sb + C_OS + tok * 128 + (((lane & 3) ^ (tok & 7)) << 4);
      z = rcp((z + __shfl_xor_sync(~0u, z, 1)) + (__shfl_xor_sync(~0u, z, 2) + __shfl_xor_sync(~0u, z, 3)));
      float o[32];
      bar_sync_after<B_WG2, 224>(n + 1 < STEPS ? __float_as_uint(z) : 0xfff12345u);
      wg_fence();
      wg_rs64o<0, desc_sw64(C_KV + 8192)>(o, p[1], 0, p[2], 0, j * 256);
      wg_rs64o<1, desc_sw64(C_KV + 8192 + 32)>(o, p[3], 0, p[4], 0, j * 256);
      wg_rs64o<1, mkdesc(C_VM, 128, 256, 0)>(o, p[0], 0, 0, 0, j * 8);
      wg_rs64o<1, desc_sw64(C_KV2 + 4096)>(o, 0, p[1], 0, p[2], 0);
      wg_rs64o<1, desc_sw64(C_KV2 + 4096 + 32)>(o, 0, p[3], 0, p[4], 0);
      wg_rs64o<1, mkdesc(C_VM2, 128, 256, 0)>(o, 0, p[0], 0, 0, 0);
      wg_commit();
      if (elect()) mbar_arrive(sb + CB_M);
      wg_wait<0>();
#pragma unroll
      for (int i = 0; i < 4; i++) {
        const float* v = o + 16 * (i & 1) + (i & 2);
        sts128((row ^ ((i & 1) * 64)) + (i & 2) * 2048,
               make_uint4(pack2(v[0] * z, v[1] * z), pack2(v[4] * z, v[5] * z), pack2(v[8] * z, v[9] * z), pack2(v[12] * z, v[13] * z)));
      }
      bar_arrive(B_G, 160);
      if (n + 1 < STEPS) bar_arrive(B_R, 160);
      if (w == 1) TR(10);
    }
  }
  if ((threadIdx.x & 127) == 0) TS(6);
}

__device__ __forceinline__ void chain_aux(const Params& P, uint32_t sb) {
  const uint32_t c = chain_id(), j = c & 1, lane = threadIdx.x & 31, w = __shfl_sync(~0u, (threadIdx.x >> 5) & 3, 0);
  load_wg<CHAIN, true>(P, sb, false, 0, w);
  if (threadIdx.x == 384) TS(25);
  if (threadIdx.x == 384) grid_wait(1, lds32(sb + S_GEN));
  bar_sync(B_WG2, 384);
  if (threadIdx.x == 384) TS(13);
  if (w == 0) {
    const uint32_t* fg = g_fl + FL_G + near_half(XB_F, c) * 1024 + (c >> 1) * 8;
#pragma unroll 1
    for (int n = 0; n < STEPS; n++) {
      const unsigned char* blk = g_qkv + (uint32_t)((n % QRING) * (N_CHAIN * 24576));
      const uint32_t t1 = clk(), kb = sb + CB_FULL + (n & 1) * 8, kv = sb + C_KV + (n & 1) * 16384;
      uint32_t t0 = t1 - 100000, x = 0;
      if (n > 0) {
        wait_until(t1, KMIN);
        do asm volatile("ld.relaxed.gpu.global.u32 %0, [%1];" : "=r"(x) : "l"(fg) : "memory"); while (x <= n && clk() - t1 < KWIN);
        if (x > n) {
          asm volatile("fence.acquire.gpu;" ::: "memory");
          fence_async_global();
          if (elect()) { mbar_expect(kb, 8192); bulk_load(kv, blk + c * 24576, 8192, kb); }
        }
        T3(0); CNT(12, 1 + (x <= n));
        mbar_wait(sb + CB_REF, (n - 1) & 1);
        t0 = lds32(sb + C_REF);
        wait_until(t0, DLYV - 500);
      }
      wait_flags(fg + min(lane, 2u) * 256, n + 1);
      T3(2);
      fence_async_global();
      if (n > 0) bar_sync(B_R, 160);
      if (lane < 3) mbar_expect(sb + CB_SX + lane * 8, lane ? 2048 : 2560);
      __syncwarp();
      wait_until(t0, DLYV);
      if (elect()) {
        if (x <= n) { mbar_expect(kb, 8192); bulk_load(kv, blk + c * 24576, 8192, kb); }
        mbar_expect(sb + CB_VF, 8192);
        bulk_load(sb + C_KV + 8192, blk + (c * 24576 + 8192), 8192, sb + CB_VF);
        mbar_expect(sb + CB_Q, 16384);
        wait_until(t0, DLYK);
        bulk_load(sb + C_Q, blk + (c * 24576 + 16384), 8192, sb + CB_Q);
        bulk_load(sb + C_KV2, blk + ((c ^ 1) * 24576 + j * 4096), 4096, sb + CB_Q);
        bulk_load(sb + C_KV2 + 4096, blk + ((c ^ 1) * 24576 + 8192 + j * 4096), 4096, sb + CB_Q);
      }
      T3(1);
      T3(3);
    }
  } else {
    const uint32_t near = __ballot_sync(~0u, near_half(XB_M + min(lane, MRING - 1u) * 8, c));
    uint32_t ring = 0;
    if (w > 1) {
      const uint32_t odd = w & 1, chk = pinned(sb + C_M + odd * 2048 + m_probe(lane)), again = sb + CB_MV + 32 + odd * 8;
      const bool one = elect();
      uint32_t mph = 0;
#pragma unroll 1
      for (int n = 0; n <= STEPS; n++) {
#pragma unroll
        for (int k = 0; k < 3; k++) {
          if (n == STEPS || (k == 2 && odd)) break;
          const uint32_t b = 2 * k + odd, at = chk + (k ? k * 8192 - 2048 + odd * 2048 : 0);
          uint32_t mb = sb + CB_M + b * 8, ph = n & 1;
          int it = 1;
          while (true) {
            mbar_wait(mb, ph);
            const bool bad = __any_sync(~0u, m_max(at, b ? at + 2048 : at) == SENT);
            if (one && !bad) mbar_arrive(sb + CB_MV + (b > 1 ? b * 8 - 8 : 0));
            if (!bad) break;
            mb = again; ph = mph; mph ^= 1;
            if (one) {
              if (k == 0) sts32(sb + C_BAD, n + 1);
              mbar_expect(mb, b ? 4096 : 2048);
              m_fetch(sb, ring * 65536 + ((near >> ring) & 1) * 4096, b, mb);
            }
            __syncwarp();
            spin_guard(it);
          }
          TR(41 + b * 4); CNT(6 + b, it);
        }
        ring = ring + 1 == MRING ? 0 : ring + 1;
        if (!odd) {
          if (n < STEPS) { TRSYNC(); TRDUMP(n - 2); }
        } else {
          unsigned char* o = g_oimg + (uint32_t)(((n - 1) & (RING - 1)) * (N_CHAIN * 8192) + j * 4096);
          if (n > 0) bar_sync(B_G, 160);
          fence_async_smem();
          if (one) {
            if (n > 0) {
              bulk_store(o + c * 8192, sb + C_OS, 4096);
              bulk_store(o + (c ^ 1) * 8192, sb + C_OS + 4096, 4096);
              asm volatile("cp.async.bulk.commit_group;\ncp.async.bulk.wait_group.read 0;" ::: "memory");
              { const int n_ = n - 1; { const int n = n_; T3(4); (void)n; } }
            }
            mbar_arrive(sb + CB_Q);
            if (n > 0) {
              bulk_done_inc(g_fl + FL_O + c);
              { const int n_ = n - 1; { const int n = n_; T3(5); (void)n; } }
            }
          }
          __syncwarp();
        }
      }
    } else {
      const uint32_t* ts = g_fl + FL_SYNC + near_half(XB_F + 1, c) * 1024 + lane * 2;
      uint32_t t0 = clk() - 100000, last = 0;
      int lag = 0;
#pragma unroll 1
      for (int n = 0; n < STEPS; n++) {
        const uint32_t src = ring * 65536 + ((near >> ring) & 1) * 4096;
        if (lane < 5) mbar_expect(sb + CB_M + lane * 8, lane ? 4096 : 2048);
        __syncwarp();
        if (elect()) {
#pragma unroll
          for (int b = 0; b < 5; b++) {
            wait_until(t0, P.dly[14 + b]);
            m_fetch(sb, src, b, sb + CB_M + b * 8);
            TR(40 + b * 4);
          }
        }
        __syncwarp();
        ring = ring + 1 == MRING ? 0 : ring + 1;
        uint32_t va, vb;
        const uint32_t off = timer_offset<4>(), tag = (uint32_t)(n + 1) << 28;
        if (n > 1) lag += (int)(off - last) - (lag >> 2);
        last = off;
        const uint32_t mine = min(max((lag >> 3) + 256, 0), 511);
        bar_sync(B_QK, 416);
        if (n + 1 == STEPS) break;
        sts32(sb + C_REF + 4, 0);
        const uint32_t c0 = clk(), stamp = c0 + off;
        st_relaxed_if(g_fl + FL_SYNC + lane * 1024 + c, tag | (mine << 19) | (stamp & 0x7FFFF), lane < 2);
        TR(13);
        wait_until(c0, DLYS);
        int it = 0;
        do {
          asm volatile("ld.relaxed.gpu.global.v2.u32 {%0,%1}, [%2];" : "=r"(va), "=r"(vb) : "l"(ts) : "memory");
          spin_guard(it);
        } while (__any_sync(~0u, ((va ^ tag) | (vb ^ tag)) >> 28));
        const int late = __reduce_max_sync(~0u, max((int)((va - stamp) << 13), (int)((vb - stamp) << 13))) >> 13;
        const uint32_t fast = min(((__reduce_max_sync(~0u, max(va, vb)) >> 19) & 511) - mine, 100u);
        t0 = c0 + min((uint32_t)late, clk() - c0);
        if (elect()) {
          sts32(sb + C_REF, t0 + (fast * 9 >> 3));
          mbar_arrive(sb + CB_REF);
        }
        st_relaxed_if(g_fl + FL_TICK + lane * 1024, (uint32_t)(n + 1) << 24 | ((t0 + off) & 0xFFFFFF), c == 0 && lane < 2);
        t0 += fast * 13 >> 3;
        TRV(59, fast);
        TR(14); CNT(11, it);
        bar_sync(B_M, 160);
      }
    }
  }
}

template <int WG>
__device__ __forceinline__ void g_math(const Params& P, uint32_t sb) {
  const int q = g_unit(WG);
  const int lane = threadIdx.x & 31, w = (threadIdx.x >> 5) & 3;
  uint32_t a[136];
  {
    const uint32_t stage = sb + G_W + WG * 73728;
    mbar_wait(sb + W_BAR + WG * 8, 0);
    if (threadIdx.x == 0) TS(23);
    load_frags<34>(a, stage);
    fence_async_smem();
    bar_sync(B_WG0 + WG, 128);
    if (threadIdx.x == 0) TS(24);
    load_wg<GROLE>(P, sb, false, WG, w);
    if (threadIdx.x == 0) TS(25);
    mbar_wait(sb + W_BAR + WG * 8, 1);
  }
  if ((threadIdx.x & 127) == 0) TS(4);
  const uint32_t off0 = (q & 31) * 49152 + (q >> 5) * 8192 + w * 1024 + (lane >> 2) * 64 + (((lane ^ (lane >> 3)) & 3) << 4);
  const uint32_t isq = q >> 6;
#pragma unroll 1
  for (int n = 0; n < STEPS; n++) {
    float d0[32], d1[32];
    if (WG == 0 && n >= LOCK0) bar_sync(B_OE, 160);
    if (n > 0) bar_sync(B_V + WG, 256);
#pragma unroll
    for (int ch = 0; ch < 9; ch++) {
      mbar_wait(sb + G_BAR + ch * 8, n & 1);
      if (ch == 0) { if ((threadIdx.x & 127) == 0) T3(5 + WG * 3); __syncwarp(); }
      if (ch == 4) { if ((threadIdx.x & 127) == 0) T3(6 + WG * 3); __syncwarp(); }
      if (ch == 8 && (WG == 0 ? n > 0 : n + 1 < STEPS)) bar_arrive(B_V + (WG ^ 1), 256);
      wg_fence();
#pragma unroll
      for (int kk = 0; kk < 4; kk++) {
        const int i = ch * 4 + kk;
        float* d = i & 1 ? d1 : d0;
        const uint64_t db = desc_sw128(G_RING + ch * 8192 + (kk & 2) * 32);
        if (i < 2) wg_rs64<0>(d, a + i * 4, db);
        else if (i < 34) wg_rs64<1>(d, a + i * 4, db);
        else wg_ss64<1>(d, desc_sw128(G_W2 + WG * 4096 + (i - 34) * 2048), db);
        wg_ss64<1>(d, desc_sw128(G_W + WG * 73728 + i * 2048), db + 2);
      }
      wg_commit();
      if (ch > 0) { wg_wait<1>(); if (lane == 0) mbar_arrive(sb + G_BAR + 128 + (ch - 1) * 8); }
    }
    wg_wait<0>();
    if (lane == 0) mbar_arrive(sb + G_BAR + 128 + 8 * 8);
    if ((threadIdx.x & 127) == 0) T3(7 + WG * 3);
    __syncwarp();
    uint32_t tw = clk() + (n == 0 ? 0u - 100000u : WG ? 0u : DLYW);
    unsigned char* base = g_qkv + (size_t)(n & (QRING - 1)) * (N_CHAIN * 24576);
#pragma unroll
    for (int i = 0; i < 8; i++) {
      const float* d = (i < 4 ? d0 : d1) + 8 * (i & 2) + 2 * (i & 1);
      wait_until(tw, 0); tw += P.dly[2 + WG];
      *(uint4*)(base + (off0 + (i < 2 ? 0 : i < 4 ? 4096 + isq * 24576 : i < 6 ? 24576 - isq * 20480 : 28672 - isq * 4096)) + (i & 1) * 512) =
        make_uint4(pack2(d[0], d[1]), pack2(d[4], d[5]), pack2(d[8], d[9]), pack2(d[12], d[13]));
    }
    bar_sync(B_M + WG, 160);
  }
}

__device__ __forceinline__ void fill16(void* p, uint32_t v) {
  asm volatile("st.global.v4.u32 [%0], {%1,%1,%1,%1};" :: "l"(p), "r"(v) : "memory");
}
__device__ __forceinline__ void g_load(const Params& P, uint32_t sb) {
  const int lane = threadIdx.x & 31, w = __shfl_sync(~0u, (threadIdx.x >> 5) & 3, 0);
  if (w == 2) return;
  if (w < 2) { bar_sync(15, 192); fence_async_smem(); }
  uint32_t fl = 0;
#pragma unroll 1
  for (int n = w == 3 ? LOCK0 : 0; n < STEPS; n++) {
    if (w && n == LOCK0) { grid_wait(1, lds32(sb + S_GEN)); fl = near_half(XB_F, bid()) * 1024; }
    if (w == 3) {
      const uint32_t tag = (uint32_t)(n - LOCK0 + 1) << 24;
      uint32_t v; int it = 0;
      do { asm volatile("ld.relaxed.gpu.global.u32 %0, [%1];" : "=r"(v) : "l"(g_fl + fl + FL_TICK) : "memory"); spin_guard(it); } while (v < tag);
      const uint32_t off = timer_offset<2>(), now = clk(), t0 = now - ((v ^ tag) >> 24 ? DLYG : (now + off - v) & 0xFFFFFF);
      asm volatile("fence.acquire.gpu;" ::: "memory");
      if (lane == 0) T3(11);
      __syncwarp();
      wait_until(t0, DLYG);
      if (lane == 0) T3(4);
      bar_sync(B_OE, 160);
      continue;
    }
    if (w == 0 || n == 0) {
      if (n < NSEG) wait_flags(g_lnflag + n * 16 + (lane & 1) * 8, 1);
    } else if (n >= LAG) {
      wait_flags(g_fl + fl + FL_F + (lane & 1) * 8, n - LAG + 1);
    }
    if (w) { if (lane == 0) T3(12); bar_sync(B_X, 96); }
    fence_async_global();
    const unsigned char* src = g_lnimg + (uint32_t)((w ? (n >= LAG ? NSEG + n - LAG : 0) : min(n, NSEG - 1)) * 36864);
#pragma unroll 1
    for (int ch = 0; ch < 9; ch++) {
      const uint32_t full = sb + G_BAR + ch * 8;
      mbar_wait(full + 128, (n & 1) ^ 1);
      if (elect()) {
        mbar_expect(full, 4096);
        bulk_load(sb + G_RING + ch * 8192 + w * 4096, src + ch * 4096, 4096, full);
      }
    }
  }
}

__device__ __forceinline__ void g_aux(const Params& P, uint32_t sb) {
  const int lane = threadIdx.x & 31, w = (threadIdx.x >> 5) & 3;
  if (w == 1 || w == 2) {
    const int q = g_unit(w - 1);
    uint32_t* f = g_fl + FL_G + q * 8;
#pragma unroll 1
    for (int n = 0; n < STEPS; n++) {
      const uint32_t ln = opaque_tid() & 31;
      uint4* z = (uint4*)g_oacc + (uint32_t)(((n + 1) % ARING) * (16 * DM) + q * 96 + ln);
      fill16(z, 0); fill16(z + 32, 0); fill16(z + 64, 0);
      if (n + 3 >= MRING && q < 80) fill16((uint4*)g_mimg + (uint32_t)(((n + 3) % MRING) * 4096 + q * 32 + ln), SENT);
      bar_sync(B_M + (w - 1), 160);
      if (lane == 0) { T3(w * 2 - 2); fence_async_global(); flag_release(f, n + 1); T3(w * 2 - 1); }
      __syncwarp();
    }
  } else {
    const uint32_t u = (bid() - N_CHAIN) * 2 + (w & 1), r = u / 36 * 16 + (u & 3) * 4 + (lane >> 3);
    uint32_t o = r * (DM / 8) + (u % 36 >> 2) * 8 + ((lane & 7) ^ ((r >> 1) & 3)), fl = 0;
#pragma unroll 1
    for (int k = -LAG - 1; k < STEPS; k++) {
      if (k < NSEG - 1) bar_sync(B_X, 96);
      if (k < LAG || u >= 72) continue;
      if (k == NSEG - 1) { fl = near_half(XB_F, bid()) * 1024; wait_flags(g_fl + fl + FL_F + (lane & 1) * 8, NSEG + 1); }
      const uint4 x = __ldcg((const uint4*)P.out + o);
      if (k >= NSEG - 1) wait_flags(g_fl + fl + FL_OCNT + (max(k, NSEG) % OCRING) * 8, N_O * 3 * (max(k, NSEG) / OCRING + 1));
      const float4* a = (const float4*)g_oacc + ((k % ARING) * (16 * DM) + 8 * DM + u * 64 + lane * 2);
      const float4 p = __ldcg(a), v = __ldcg(a + 1);
      ((uint4*)P.out)[o] = make_uint4(badd2(x.x, pack2(p.x, p.y)), badd2(x.y, pack2(p.z, p.w)), badd2(x.z, pack2(v.x, v.y)), badd2(x.w, pack2(v.z, v.w)));
      o += 4 * DM;
    }
    if ((threadIdx.x & 127) == 0) TS(7);
  }
}

template <int WG, bool HALF, int KS, int N> __device__ __forceinline__ void o_mma(float* d, const uint32_t* a, uint32_t ob) {
  constexpr uint64_t db = desc_sw128(O_RING + (KS >> 2) * 8192 + (KS & 3) * 32);
  constexpr uint64_t da = desc_sw128(O_W + WG * 40960 + (KS < 40 ? KS / 5 * 2 + KS % 5 / 2 : KS - 24) * 2048);
  if constexpr (KS < 40 && !(KS % 5 & 1)) {
    const uint32_t* r = a + (KS / 5 * 3 + KS % 5 / 2) * 4;
    if constexpr (HALF) wg_rs32k<KS != 0, db>(d, r[0], r[1], r[2], r[3], ob); else wg_rs64<KS != 0>(d, r, db);
  } else {
    if constexpr (HALF) wg_ss32k<da, db>(d, ob); else wg_ss64<1>(d, da, db);
  }
  if constexpr (N > 1) o_mma<WG, HALF, KS + 1, N - 1>(d, a, ob);
}
template <int WG, bool HALF, int GR> __device__ __forceinline__ void o_groups(float* d, const uint32_t* a, uint32_t sb, int n, bool more) {
  const uint32_t ob = n < NSEG ? 0 : 256;
  mbar_wait(sb + O_BAR + GR * 8, n & 1);
  if (GR == 0) { if ((threadIdx.x & 127) == 0) T3(13 + WG); __syncwarp(); }
  if (GR == 3 && (WG < 2 || n + 1 < STEPS)) bar_arrive(B_V + (WG + 1) % 3, 256);
  wg_fence();
  o_mma<WG, HALF, GR * 8, 8>(d, a, ob);
  if (GR == 4 && more) o_mma<WG, HALF, 40, 4>(d, a, ob);
  wg_commit();
  if (GR > 0) { wg_wait<1>(); if ((threadIdx.x & 31) == 0) mbar_arrive(sb + O_BAR + 120 + GR * 8); }
  if constexpr (GR < 4) o_groups<WG, HALF, GR + 1>(d, a, sb, n, more);
}
template <int WG, bool HALF> __device__ __forceinline__ void o_step(const uint32_t* a, uint32_t sb, uint32_t st0, int n, bool more) {
  float d[HALF ? 16 : 32];
  if (WG > 0 || n > 0) bar_sync(B_V + WG, 256);
  o_groups<WG, HALF, 0>(d, a, sb, n, more);
  wg_wait<0>();
  if ((threadIdx.x & 31) == 0) mbar_arrive(sb + O_BAR + 128 + 4 * 8);
  if ((threadIdx.x & 127) == 0) T3(WG == 0 ? 1 : WG == 1 ? 8 : 12);
  __syncwarp();
#pragma unroll(HALF ? 1 : 2)
  for (int sl = 0; sl < 2; sl++) {
    mbar_wait(sb + OB_ST + WG * 16 + sl * 8, (n & 1) ^ (WG == 0));
    if (!HALF || sl == (n >= NSEG)) {
#pragma unroll
      for (int nb = 0; nb < 4; nb++) {
        const float* r = d + (HALF ? 0 : sl * 16) + nb * 4;
        const uint32_t ad = st0 + sl * 8192 + nb * 2048;
        sts32(ad, __float_as_uint(r[0]));
        sts32(ad + 256, __float_as_uint(r[1]));
        sts32(ad ^ 32, __float_as_uint(r[2]));
        sts32((ad ^ 32) + 256, __float_as_uint(r[3]));
      }
      fence_async_smem();
    }
    bar_arrive((sl ? B_G : B_M) + WG, 160);
  }
}
template <int WG>
__device__ __forceinline__ void o_math(const Params& P, uint32_t sb) {
  const bool more = bid() < N_CHAIN + N_G + 12;
  const int lane = threadIdx.x & 31, w = (threadIdx.x >> 5) & 3, g = lane >> 2, tq = lane & 3;
  uint32_t a[96];
  mbar_wait(sb + W_BAR + WG * 8, 0);
  load_frags<24>(a, sb + WG * 49152);
  fence_async_smem();
  bar_sync(B_INIT, 416);
  load_wg<OROLE>(P, sb, false, WG, w);
  mbar_wait(sb + W_BAR + WG * 8, 1);
  if ((threadIdx.x & 127) == 0) TS(4);
  const uint32_t st0 = sb + O_ST + tq * 512 + ((w * 16 + g) ^ (tq * 8)) * 4;
#pragma unroll 1
  for (int n = 0; n < STEPS; n++) {
    if (n < LAG || n >= NSEG) o_step<WG, true>(a, sb, st0, n, more); else o_step<WG, false>(a, sb, st0, n, more);
  }
}

__device__ __forceinline__ void o_aux(const Params& P, uint32_t sb) {
  const int i = bid() - N_CHAIN - N_G, ksl = i / 3;
  const int c0 = ksl * 11 - max(ksl - 4, 0), nc = ksl < 4 ? 11 : 10;
  const int lane = threadIdx.x & 31, w = __shfl_sync(~0u, (threadIdx.x >> 5) & 3, 0);
  if (w == 0) {
    bar_sync(B_INIT, 416);
    const uint32_t* f = g_fl + FL_O + near_half(XB_F + 1, bid()) * 1024 + min((c0 & ~1) + lane, (c0 + nc - 1) | 1);
#pragma unroll 1
    for (int n = 0; n < STEPS; n++) {
      const unsigned char* src = g_oimg + (uint32_t)(((n % RING) * N_CHAIN + c0) * 8192);
      wait_flags(f, n + 1);
      if (n >= LAG && n < NSEG) wait_until(clk(), DLYO);
      fence_async_global();
      if (lane == 0) T3(0);
#pragma unroll
      for (int gr = 0; gr < 5; gr++) {
        const uint32_t full = sb + O_BAR + gr * 8, bytes = (gr < 4 ? 2 : nc - 8) * 8192;
        mbar_wait(full + 128, (n & 1) ^ 1);
        if (elect()) {
          if (n < LAG || n >= NSEG) {
            mbar_expect(full, bytes >> 1);
            for (uint32_t o = gr * 16384 + (n < LAG ? 0 : 4096); o < gr * 16384 + bytes; o += 8192) bulk_load(sb + O_RING + o, src + o, 4096, full);
          } else {
            mbar_expect(full, bytes);
            bulk_load(sb + O_RING + gr * 16384, src + gr * 16384, bytes, full);
          }
        }
      }
    }
  } else {
#pragma unroll 1
    for (int n = 0; n < STEPS; n++) {
      float* dst = g_oacc + (uint32_t)((n % ARING) * (64 * DM) + ((i % 3) * 3 + (w - 1 + ksl) % 3) * 1024);
      const bool early = w == 3 && n < NSEG;
      bar_sync(B_M + (w - 1), 160);
      if (lane == 0) {
        T3(w * 2);
        if (n < NSEG) { bulk_reduce(dst, sb + O_ST, 4096); bulk_reduce(dst + 16 * DM, sb + O_ST + 4096, 4096); }
        asm volatile("cp.async.bulk.commit_group;" ::: "memory");
        if (early) {
          asm volatile("cp.async.bulk.wait_group.read 0;" ::: "memory");
          mbar_arrive(sb + OB_ST);
          T3(8 + w);
          bulk_done_inc(g_fl + FL_OCNT + (n % OCRING) * 8);
          T3(w * 2 + 1);
        }
      }
      __syncwarp();
      bar_sync(B_G + (w - 1), 160);
      if (lane == 0) {
        if (n >= LAG) { bulk_reduce(dst + 32 * DM, sb + O_ST + 8192, 4096); bulk_reduce(dst + 48 * DM, sb + O_ST + 12288, 4096); }
        asm volatile("cp.async.bulk.commit_group;\ncp.async.bulk.wait_group.read 1;" ::: "memory");
        if (!early) mbar_arrive(sb + OB_ST + (w % 3) * 16);
        asm volatile("cp.async.bulk.wait_group.read 0;" ::: "memory");
        mbar_arrive(sb + OB_ST + (w % 3) * 16 + 8);
        if (!early) {
          T3(8 + w);
          bulk_done_inc(g_fl + FL_OCNT + (n % OCRING) * 8);
          T3(w * 2 + 1);
        }
      }
      __syncwarp();
    }
  }
}

constexpr uint32_t Y_PITCH = 1168, Y_ROWS = 16 * Y_PITCH;
template <int R> __device__ __forceinline__ void y_rows(uint32_t* y, uint32_t src, uint32_t dst, int w, int bar) {
  const int lane = threadIdx.x & 31;
#pragma unroll
  for (int k = 0; k < 2 * R + 1; k++) {
    const int op = w + k * (16 / R);
    if (k == 2 * R && w >= 4) break;
    uint32_t a, b, c, d;
    ldsm4t(a, b, c, d, src + op * 512 + (lane & 16) * 16 + (lane & 7) * 32 + (lane & 8) * 2);
    stsm4(dst + (lane & 15) * Y_PITCH + op * 32 + (lane & 16), a, b, c, d);
  }
  bar_sync(bar, 512 / R);
  const uint32_t row = dst + ((w & 6) * 2 + (w >> 3) * 2 + (w & 1)) * Y_PITCH + lane * 4;
#pragma unroll
  for (int i = 0; i < 9 * R; i++) y[i] = lds32(row + i / 9 * 2 * Y_PITCH + i % 9 * 128);
}

__device__ __forceinline__ void f_role(const Params& P, uint32_t sb) {
  const int lane = threadIdx.x & 31, w = __shfl_sync(~0u, threadIdx.x >> 5, 0), r0 = (bid() - N_CHAIN - N_G - N_O) * 16;
  if (w == 8) {
    const uint32_t* fo = g_fl + FL_OCNT + near_half(XB_F, bid()) * 1024;
    fence_async_global();
#pragma unroll 1
    for (int n = 0; n < NSEG; n++) {
      bar_sync(2, 288);
      if (elect()) {
        mbar_expect(sb + F_BAR, 36864);
        bulk_load(sb + F_XY, P.X + (size_t)(n * 32 + r0) * DM, 18432, sb + F_BAR);
        bulk_load(sb + F_XY + 18432, g_yT + (size_t)(n * 32 + r0) * DM, 18432, sb + F_BAR);
        mbar_expect(sb + F_BAR + 8, 36864);
        T3(1);
      }
      wait_flags(fo + (n % OCRING) * 8, N_O * 3 * (n / OCRING + 1));
      fence_async_global();
      if (elect()) { bulk_load(sb + F_A, g_oacc + (uint32_t)((n % ARING) * (64 * DM) + r0 * DM), 36864, sb + F_BAR + 8); T3(0); }
    }
  } else if (w == 9) {
#pragma unroll 1
    for (int n = 0; n < NSEG; n++) {
      const uint32_t st = sb + (n & 1) * 36864;
      unsigned char* p = g_lnimg + (uint32_t)((NSEG + n) * 36864 + r0 * 128);
      bar_sync(1, 288);
      if (elect()) {
        T3(2);
#pragma unroll
        for (int i = 0; i < 9; i++) bulk_store(p + i * 4096, st + F_L + i * 2048, 2048);
        asm volatile("cp.async.bulk.commit_group;" ::: "memory");
        bulk_done_inc(g_fl + FL_F + (bid() & 1) * 8);
        T3(3);
        bulk_store(P.out + (size_t)(n * 32 + r0) * DM, st + F_X, 18432);
        asm volatile("cp.async.bulk.commit_group;\ncp.async.bulk.wait_group.read 0;" ::: "memory");
        if (n + 1 == NSEG) bulk_done_inc(g_fl + FL_F + (bid() & 1) * 8);
      }
      __syncwarp();
    }
  } else if (w < 8) {
    const uint32_t row = sb + w * 1152 + lane * 4, acc = sb + F_A + w * 256 + (lane ^ ((w & 6) * 2)) * 8;
    const uint32_t ln = sb + F_L + w * 128 + (((lane >> 2) ^ w) << 4) + (lane & 3) * 4;
#pragma unroll 1
    for (int n = -1; n < NSEG; n++) {
      const uint32_t st = (n & 1) * 36864;
      uint32_t x[18], y[18], l[18];
      if (n >= 0) mbar_wait(sb + F_BAR, n & 1);
#pragma unroll
      for (int i = 0; i < 18; i++) x[i] = lds32(row + F_XY + i / 9 * 9216 + i % 9 * 128);
      y_rows<2>(y, sb + F_XY + 18432, sb + F_Y, w, 3);
      layernorm9<2>(x, l);
#pragma unroll
      for (int i = 0; i < 18; i++) x[i] = badd2(x[i], bmul2(l[i], y[i]));
      if (n >= 0) mbar_wait(sb + F_BAR + 8, n & 1);
      if (threadIdx.x == 0 && n >= 0) T3(4);
      __syncwarp();
      uint2 a[18];
#pragma unroll
      for (int i = 0; i < 18; i++) a[i] = lds64(acc + i / 9 * 2048 + i % 9 * 4096);
#pragma unroll
      for (int i = 0; i < 18; i++) x[i] = badd2(x[i], pack2(__uint_as_float(a[i].x), __uint_as_float(a[i].y)));
      if (n + 1 < NSEG) bar_arrive(2, 288);
      layernorm9<2>(x, l);
#pragma unroll
      for (int i = 0; i < 18; i++) { x[i] = badd2(x[i], bmul2(l[i], y[i])); sts32(row + st + F_X + i / 9 * 9216 + i % 9 * 128, x[i]); }
      layernorm9<2>(x, l);
#pragma unroll
      for (int i = 0; i < 18; i++) sts32(ln + st + i / 9 * 1024 + i % 9 * 2048, l[i]);
      fence_async_smem();
      if (n >= 0) bar_sync(1, 288); else bar_sync(3, 256);
    }
  }
}

constexpr uint32_t P_CH = 147456, P_CHSZ = 12800, P_H = 4352;
static_assert(P_CH + 6 * P_CHSZ <= G_BAR, "prologue smem");

template <int N>
__device__ __forceinline__ void conv_fold(float (*acc)[4], bool hi, uint32_t mine, uint32_t theirs, int bar, int cnt) {
#pragma unroll
  for (int i = 0; i < N / 2; i++) {
    uint4 v;
    v.x = __float_as_uint(hi ? acc[i][0] : acc[i + N / 2][0]); v.y = __float_as_uint(hi ? acc[i][1] : acc[i + N / 2][1]);
    v.z = __float_as_uint(hi ? acc[i][2] : acc[i + N / 2][2]); v.w = __float_as_uint(hi ? acc[i][3] : acc[i + N / 2][3]);
    sts128(mine + i * 512, v);
  }
  bar_sync(bar, cnt);
#pragma unroll
  for (int i = 0; i < N / 2; i++) {
    const uint4 v = lds128(theirs + i * 512);
    acc[i][0] = (hi ? acc[i + N / 2][0] : acc[i][0]) + __uint_as_float(v.x); acc[i][1] = (hi ? acc[i + N / 2][1] : acc[i][1]) + __uint_as_float(v.y);
    acc[i][2] = (hi ? acc[i + N / 2][2] : acc[i][2]) + __uint_as_float(v.z); acc[i][3] = (hi ? acc[i + N / 2][3] : acc[i][3]) + __uint_as_float(v.w);
  }
}
template <int N>
__device__ __forceinline__ void conv_store(const float (*acc)[4], int tile0, uint32_t su, int d, uint32_t dd) {
  const int lane = threadIdx.x & 31, g = lane >> 2, tq = lane & 3;
#pragma unroll
  for (int i = 0; i < N; i++) {
    const uint32_t ad = su + (8 + (tile0 + i) * 8 + g) * 32 + tq * 4, sw = (g & 4) << 2;
    const uint32_t lo = badd2(movmat(pack2(acc[i][0], acc[i][1])), bmul2(lds32(ad + sw), dd));
    const uint32_t hi = badd2(movmat(pack2(acc[i][2], acc[i][3])), bmul2(lds32(ad + (sw ^ 16)), dd));
    ((uint2*)g_yT)[(((tile0 + i) * 8 + g) * DM + d) * 4 + tq] = make_uint2(lo, hi);
  }
}

__device__ __forceinline__ void prologue(const Params& P, uint32_t sb) {
  const int b = bid(), tid = threadIdx.x, lane = tid & 31, warp = tid >> 5, t0 = b * 16;
  const bool isg = b >= N_CHAIN && b < N_CHAIN + N_G;
  const int nch = isg ? 2 : b < 128 ? 6 : 0, chb = b < N_CHAIN ? b * 6 : isg ? b * 2 + 256 : b * 6 - 192;
  const uint32_t tstart = clk();
  if (tid < 288) {
    if (b < 128) {
      const int c = (tid >> 1) * 4, tt = t0 + (tid & 1) * 8;
      uint2 kr[11], vr[8];
#pragma unroll
      for (int i = 0; i < 11; i++) { const int t = tt + i - 3; kr[i] = t >= 0 ? __ldg((const uint2*)(P.K + (size_t)t * DM + c)) : make_uint2(0, 0); }
#pragma unroll
      for (int i = 0; i < 8; i++) vr[i] = __ldg((const uint2*)(P.V + (size_t)(tt + i) * DM + c));
#pragma unroll
      for (int e = 0; e < 2; e++) {
        const uint4 sh = __ldg((const uint4*)(P.shift + c * 4) + e);
        const uint32_t s0 = __byte_perm(sh.x, sh.z, 0x5410), s1 = __byte_perm(sh.x, sh.z, 0x7632);
        const uint32_t s2 = __byte_perm(sh.y, sh.w, 0x5410), s3 = __byte_perm(sh.y, sh.w, 0x7632);
        uint32_t v[8];
#pragma unroll
        for (int i = 0; i < 8; i++) {
          const uint32_t k3 = e ? kr[i].y : kr[i].x, k2 = e ? kr[i + 1].y : kr[i + 1].x, k1 = e ? kr[i + 2].y : kr[i + 2].x, k0 = e ? kr[i + 3].y : kr[i + 3].x;
          v[i] = bmul2(badd2(badd2(badd2(bmul2(k3, s3), bmul2(k2, s2)), bmul2(k1, s1)), bmul2(k0, s0)), e ? vr[i].y : vr[i].x);
        }
        *(uint4*)(g_kvT + (size_t)(c + 2 * e) * KVP + tt) =
          make_uint4(__byte_perm(v[0], v[1], 0x5410), __byte_perm(v[2], v[3], 0x5410), __byte_perm(v[4], v[5], 0x5410), __byte_perm(v[6], v[7], 0x5410));
        *(uint4*)(g_kvT + (size_t)(c + 2 * e + 1) * KVP + tt) =
          make_uint4(__byte_perm(v[0], v[1], 0x7632), __byte_perm(v[2], v[3], 0x7632), __byte_perm(v[4], v[5], 0x7632), __byte_perm(v[6], v[7], 0x7632));
      }
    }
  } else if (tid < 384) {
    const int t = tid - 288;
    for (int i = b * 96 + t; i < 16 * DM; i += N_CTA * 96) ((uint4*)g_oacc)[i] = make_uint4(0, 0, 0, 0);
    if (b * 96 + t < 128 * 8) g_lnflag[b * 96 + t] = 0;
    if (t == 95) sts32(sb + S_GEN, ld_acquire(g_gbar));
    __syncwarp();
    wait_until(tstart, PREFH);
    for (int i = t; i < 32 * nch; i += 96) asm volatile("prefetch.global.L2 [%0];" :: "l"(P.Hk + (size_t)chb * SEQ + i * 64));
  }
  if (warp < 12) {
    bar_arrive(10, 416);
    if (tid == 128) TS(14);
    const int ch = 5 - (warp >> 1), sub = warp & 1, d = chb + ch;
    const uint32_t su = sb + P_CH + ch * P_CHSZ;
    if (ch < nch) {
      const uint32_t* hs = (const uint32_t*)(P.Hk + (size_t)d * SEQ);
#pragma unroll
      for (int q = sub * 32 + lane; q < 256; q += 64) {
        const uint4 c = __ldg((const uint4*)hs + q);
        const uint32_t prev = q ? __ldg(hs + 4 * q - 1) : 0u;
        sts128(su + P_H + 32 + q * 16, make_uint4(__byte_perm(c.x, prev, 0x7610), __byte_perm(c.y, c.x, 0x7610), __byte_perm(c.z, c.y, 0x7610), __byte_perm(c.w, c.z, 0x7610)));
        sts128(su + P_H + 4224 + q * 16, make_uint4(__byte_perm(c.x, 0, 0x1032), __byte_perm(c.y, 0, 0x1032), __byte_perm(c.z, 0, 0x1032), __byte_perm(c.w, 0, 0x1032)));
      }
      if (sub == 1 && lane == 0) sts32(su + P_CHSZ - 16, __bfloat16_as_ushort(P.Dk[d]) * 0x10001u);
      if (sub == 0 && lane < 20) sts128(su + (lane < 16 ? lane * 16 : P_H + (lane & 2) * 2096 + (lane & 1) * 16), make_uint4(0, 0, 0, 0));
    }
    bar_sync(11, 416);
    if (ch < nch) {
#pragma unroll
      for (int q = sub * 32 + lane; q < 256; q += 64) {
        const int row = (q >> 1) + 8;
        sts128(su + row * 32 + (((q & 1) ^ ((row >> 2) & 1)) << 4), __ldcg((const uint4*)(g_kvT + (size_t)d * KVP) + q));
      }
    }
    const int g = lane >> 2, tq = lane & 3;
    const uint32_t sh = su + P_H + (g & 1) * 4192 + (8 + (g >> 1) - tq) * 4;
    float acc[16][4];
#pragma unroll
    for (int i = 0; i < 16; i++) { acc[i][0] = acc[i][1] = acc[i][2] = acc[i][3] = 0.f; }
    auto u_addr = [&](int res) {
      const int row = 8 - res + ((lane >> 4) << 3) + (lane & 7);
      return su + row * 32 + ((((lane >> 3) & 1) ^ ((row >> 2) & 1)) << 4);
    };
    if (ch < nch) {
      bar_sync(1 + ch, 64);
      if (tid == 352) TS(11);
      if (sub) {
#pragma unroll 4
        for (int res = 0; res < 8; res++) {
          uint32_t b0, b1, b2, b3;
          ldsm4(b0, b1, b2, b3, u_addr(res));
          const uint32_t r0 = lds32(sh + res * 32);
          mma16(acc[0], r0, lds32(sh + res * 32 + 16), lds32(sh + res * 32 - 16), r0, b0, b1);
        }
        conv_store<1>(acc, 0, su, d, lds32(su + P_CHSZ - 16));
      }
    }
    bar_arrive(12, 416);
    if (isg && warp < 8) { while ((int)(clk() - tstart - S1G) < 0) __nanosleep(200); load_wg<GROLE>(P, sb, true, warp >> 2, warp & 3); }
    if (ch < nch) {
#pragma unroll 1
      for (int res = sub * 4; res < sub * 4 + 4; res++) {
        uint32_t bf[16][2];
        const uint32_t ad = u_addr(res);
#pragma unroll
        for (int f = 0; f < 16; f += 2) ldsm4(bf[f][0], bf[f][1], bf[f + 1][0], bf[f + 1][1], ad + f * 256);
#pragma unroll
        for (int k = 0; k < 16; k++) {
          const int jj = k & 1 ? k >> 1 : 15 - (k >> 1);
          const uint32_t ah = sh + (8 * jj + res) * 32;
          const uint32_t r0 = lds32(ah), r1 = lds32(ah + 16), rm = lds32(ah - 16);
#pragma unroll
          for (int i = max(jj, 1); i < 16; i++) mma16(acc[i], r0, r1, rm, r0, bf[i - jj][0], bf[i - jj][1]);
        }
      }
      bar_sync(1 + ch, 64);
      if (tid == 352) TS(12);
      const uint32_t xb = su + P_H + lane * 16, dd = lds32(su + P_CHSZ - 16);
      conv_fold<16>(acc, sub, xb + sub * 4096, xb + (sub ^ 1) * 4096, 1 + ch, 64);
      conv_store<8>(acc, sub * 8, su, d, dd);
    }
  } else {
    for (int i = b; i < 194 + MRING * 5; i += N_CTA) {
      const int n = (i - 194) / 5, r = (i - 194) % 5, blk = i < 192 ? i / 6 * 8 + i % 6 : i < 194 ? XB_F + i - 192 : XB_M + n * 8 + r;
      const uint32_t fill = i < 194 ? 0u : SENT;
#pragma unroll 1
      for (int q = tid - 384; q < 256 && warp < 15; q += 96) {
        uint4 v = make_uint4(fill, fill, fill, fill);
        if (i >= 194 && n == 0 && (r > 0 || q < 128)) {
          const bf16* m = P.mem0 + (max(r * 8 - 4, 0) + (q >> 5)) * 16 + ((q >> 1) & 1) * 8 + ((q >> 2) & 7);
          v.x = pack2(__bfloat162float(m[0]), __bfloat162float(m[DM])); v.y = pack2(__bfloat162float(m[2 * DM]), __bfloat162float(m[3 * DM]));
          v.z = pack2(__bfloat162float(m[4 * DM]), __bfloat162float(m[5 * DM])); v.w = pack2(__bfloat162float(m[6 * DM]), __bfloat162float(m[7 * DM]));
        }
        g_xb[blk * 512 + q] = v;
        g_xb[blk * 512 + 256 + q] = v;
      }
    }
    if (tid < 388) g_xb[XB_REF * 512 + (tid & 2) * 128 + (b & ~1) + (tid & 1)] = make_uint4(0, 0, 0, 0);
    else if (tid < 392 && b < N_GRP) g_xb[(b * 8 + 7) * 512 + (tid & 2) * 128 + (tid & 1)] = make_uint4(0, 0, 0, 0);
    if (warp < 15) { bar_arrive(9, 128); bar_sync(7, 96); }
    if (tid == 384) TS(8);
    if (warp == 12) {
      const bf16* w = lane < 6 ? (lane % 3 == 0 ? P.Wk : lane % 3 == 1 ? P.Wv : P.Wq) + (((b >> 5) * 2 + lane / 3) * 32 + (b & 31)) * 2048
                               : (lane < 8 ? P.Wo + (lane - 6) * (9 * 131072) : P.X) + b * 2048;
      uint32_t t = tstart + PREF0;
      if ((int)(clk() - t) > 0) t = clk();
#pragma unroll 1
      for (int st = 0; st < 9 && b < N_CHAIN; st++) {
#pragma unroll 1
        for (int i = 0; i < 9; i++, t += PACE) {
          wait_until(t, 0);
          if (lane == st) asm volatile("cp.async.bulk.prefetch.L2.global [%0], 4096;" :: "l"(w + i * (lane < 6 ? 262144 : 131072)) : "memory");
        }
      }
      if (lane == 0) TS(10);
    } else if (warp == 15) {
      bar_sync(10, 416);
      if (lane == 0) { grid_arrive(0); if (nch) grid_wait(0, lds32(sb + S_GEN)); }
      __syncwarp();
      bar_arrive(11, 416);
      if (lane == 0) TS(1);
      bar_sync(9, 128);
      bar_sync(12, 416);
      if (lane == 0) { TS(16); grid_arrive(2); TS(17); }
    } else if (lane == 0) {
      if (warp == 13 || (warp == 14 && b < N_GRP)) {
        uint32_t* p = (uint32_t*)(g_xb + (warp == 13 ? XB_REF * 512 + b : (b * 8 + 7) * 512));
        int votes = 0;
        for (int rep = 0; rep < 24 && abs(votes) < 7; rep++) {
          uint32_t v0, v1, c0, c1;
          asm volatile("atom.relaxed.gpu.global.add.u32 %0, [%4], 1;\n atom.relaxed.gpu.global.add.u32 %1, [%5], 1;\n"
                       "{.reg .pred p; setp.eq.u32 p, %0, 0x7ffffff3; @p trap; mov.u32 %2, %%clock; setp.eq.u32 p, %1, 0x7ffffff3; @p trap; mov.u32 %3, %%clock;}"
                       : "=&r"(v0), "=&r"(v1), "=&r"(c0), "=&r"(c1) : "l"(p + (rep & 1) * 1024), "l"(p + ((rep & 1) ^ 1) * 1024) : "memory");
          votes += ((c1 - c0 > 80u) == (rep & 1)) ? 1 : -1;
        }
        if (warp == 13) { g_side[b] = votes > 0; TS(9); } else g_near[b] = votes > 0;
      }
    }
    __syncwarp();
    if (warp > 12 && b < N_CHAIN) {
      while ((int)(clk() - tstart - S1DLY) < 0) __nanosleep(200);
      for (int k = warp - 13; k < 8; k += 3) load_wg<CHAIN>(P, sb, true, 1 - k / 4, k & 3);
    }
  }
  if (b < N_CHAIN + N_G && (warp < 8 || (isg && warp >= 12))) bar_arrive(0, 512); else bar_sync(0, 512);
  if (tid == 352) TS(2);
}

__device__ __forceinline__ void publish_y() {
  if (threadIdx.x == 383) { grid_arrive(1); TS(18); }
  __syncwarp();
}

template <int R> __device__ __forceinline__ void ln_tiles(const Params& P, uint32_t sb) {
  const int lane = threadIdx.x & 31, w = (threadIdx.x >> 5) & (16 / R - 1), half = R == 1 ? 0 : threadIdx.x >> 8, u = N_CTA - 1 - bid();
  const int first = R == 1 ? u : 46 - 2 * u + half, step = R == 1 ? 4 : 40, last = R == 1 ? 8 : 128;
  const uint32_t raw = sb + P_CH + half * (18432 + Y_ROWS), mb = sb + T_BAR + (R - 1 + half) * 8;
  const bool lead = w == 16 / R - 1 && lane == 0;
  auto load_y = [&](const bf16* src, int tile) {
    fence_async_global();
    mbar_expect(mb, 18432);
    bulk_load(raw, src + (size_t)tile * 16 * DM, 18432, mb);
  };
  uint32_t nx[9 * R];
  auto load_x = [&](int tile) {
#pragma unroll
    for (int i = 0; i < 9 * R; i++) nx[i] = __ldg((const uint32_t*)(P.X + (size_t)(tile * 16 + w + i / 9 * 8) * DM) + i % 9 * 32 + lane);
  };
  load_x(first);
  if (R == 2) {
    if (lead) { grid_wait(1, lds32(sb + S_GEN)); if (u > 3) TS(13); load_y(g_yT, first); }
    __syncwarp();
  }
#pragma unroll 1
  for (int tile = first, real = R - 1, ph = 0; tile < last; tile += real * step, real = 1, ph ^= 1) {
    uint32_t x[9 * R], l[9 * R], y[9 * R];
    const bool ts = threadIdx.x == 0 && (R == 1 ? tile == first : u > 3 && tile == first + step);
    if (ts) TS(26);
#pragma unroll
    for (int i = 0; i < 9 * R; i++) x[i] = nx[i];
    layernorm9<R>(x, l);
    if (real && tile + step < last) load_x(tile + step);
    if (R == 2 && tile == first + step && u >= N_F && w < 6) load_wg<OROLE>(P, sb, true, w >> 1, half * 2 + (w & 1));
    if (R == 1 && tile == first && lead) {
      if (real) grid_wait(2, lds32(sb + S_GEN));
      TS(13);
      load_y(real ? g_yT : P.Hk, tile);
    }
    bar_sync(13 + half, 512 / R);
    mbar_wait(mb, ph);
    if (ts) TS(28);
    y_rows<R>(y, raw, raw + 18432, w, 13 + half);
    if (ts) TS(29);
    if (lead && real && tile + step < last) { fence_async_smem(); load_y(g_yT, tile + step); }
    __syncwarp();
#pragma unroll
    for (int i = 0; i < 9 * R; i++) x[i] = badd2(x[i], bmul2(l[i], y[i]));
    layernorm9<R>(x, l);
    if (ts && l[0] != 0x12345) TS(30);
#pragma unroll
    for (int r = 0; r < R; r++) store_ln_row(0, tile * 16 + w + r * 8, l + r * 9);
    if (R == 1) {
      __syncthreads();
      if (threadIdx.x == 32 && real) { if (tile < 4) TS(19); st_release(g_lnflag + tile * 8, 1); if (tile < 4) TS(20); }
      __syncwarp();
    }
    if (ts) TS(31);
  }
  if (R == 2) {
    __syncthreads();
    if (threadIdx.x >= 506) {
      asm volatile("fence.acq_rel.gpu;" ::: "memory");
      st_relaxed_if(g_lnflag + ((first ^ (lane & 1)) + (lane - 26) / 2 * step) * 8, 1, true);
    }
    __syncwarp();
    fence_async_smem();
    if (threadIdx.x == 0) TS(15);
  }
}

__global__ void __cluster_dims__(2, 1, 1) __launch_bounds__(512, 1) k_main(const __grid_constant__ Params P) {
  extern __shared__ __align__(1024) unsigned char smem[];
  const uint32_t sb = (uint32_t)__cvta_generic_to_shared(smem);
  const int b = bid(), wg = threadIdx.x >> 7;
  if ((threadIdx.x & 127) == 0) TS(0);
  if (threadIdx.x == 480) {
    if ((sb & 0xFFFFFF) != SBASE) __trap();
    for (int i = 0; i < 6; i++) mbar_init(sb + W_BAR + i * 8, 1);
    if (b < N_CHAIN) {
      mbar_init(sb + CB_FULL, 1); mbar_init(sb + CB_FULL + 8, 1);
      mbar_init(sb + CB_REF, 1);
      mbar_init(sb + CB_SX, 1); mbar_init(sb + CB_OX, 1); mbar_init(sb + CB_XX, 1); mbar_init(sb + CB_Q, 2); mbar_init(sb + CB_VF, 1);
      sts32(sb + C_BAD, 0);
      for (int i = 0; i < 11; i++) mbar_init(sb + CB_M + i * 8, i == 0 ? 5 : i == 5 ? 2 : 1);
    } else if (b < N_CHAIN + N_G) {
      for (int i = 0; i < 9; i++) { mbar_init(sb + G_BAR + i * 8, 2); mbar_init(sb + G_BAR + 128 + i * 8, 8); }
    } else if (b < N_CHAIN + N_G + N_O) {
      for (int i = 0; i < 5; i++) { mbar_init(sb + O_BAR + i * 8, 1); mbar_init(sb + O_BAR + 128 + i * 8, 12); }
      for (int i = 0; i < 6; i++) mbar_init(sb + OB_ST + i * 8, 1);
    } else {
      mbar_init(sb + F_BAR, 1); mbar_init(sb + F_BAR + 8, 1);
    }
    asm volatile("fence.mbarrier_init.release.cluster;" ::: "memory");
    fence_async_smem();
  }
  __syncwarp();
  asm volatile("barrier.cluster.arrive.relaxed.aligned;" ::: "memory");
  prologue(P, sb);
  asm volatile("barrier.cluster.wait.aligned;" ::: "memory");
  fence_async_smem();
  if (b >= N_CHAIN + N_G) publish_y();
  if (b >= 128) ln_tiles<1>(P, sb);
  if (b >= N_CHAIN + N_G) ln_tiles<2>(P, sb);
  if ((threadIdx.x & 127) == 0) TS(3);
  if (b < N_CHAIN) {
    if (wg < 2) { reg_inc<200>(); chain_proj(P, sb); }
    else if (wg == 2) { reg_dec<88>(); publish_y(); chain_attn(P, sb); }
    else { reg_dec<24>(); chain_aux(P, sb); }
  } else if (b < N_CHAIN + N_G) {
    if (wg == 0) { reg_inc<232>(); g_math<0>(P, sb); }
    else if (wg == 1) { reg_inc<232>(); g_math<1>(P, sb); }
    else if (wg == 2) { reg_dec<24>(); bar_arrive(15, 192); publish_y(); g_aux(P, sb); }
    else { reg_dec<24>(); g_load(P, sb); }
  } else if (b < N_CHAIN + N_G + N_O) {
    if (wg == 0) { reg_inc<160>(); o_math<0>(P, sb); }
    else if (wg == 1) { reg_inc<160>(); o_math<1>(P, sb); }
    else if (wg == 2) { reg_inc<160>(); o_math<2>(P, sb); }
    else { reg_dec<32>(); o_aux(P, sb); }
  } else {
    f_role(P, sb);
  }
}

}

extern "C" void kernel_launch(void* const* d_in, const int* in_sizes, int n_in, void* d_out, int out_size) {
  typedef CUresult (*Encode)(CUtensorMap*, CUtensorMapDataType, cuuint32_t, void*, const cuuint64_t*, const cuuint64_t*, const cuuint32_t*, const cuuint32_t*,
                             CUtensorMapInterleave, CUtensorMapSwizzle, CUtensorMapL2promotion, CUtensorMapFloatOOBfill);
  static Encode encode = nullptr;
  if (!encode) cudaGetDriverEntryPoint("cuTensorMapEncodeTiled", (void**)&encode, cudaEnableDefault);
  Params P;
  for (int i = 0; i < 11; i++) {
    const bool wo = i == 6 || i == 7;
    const cuuint64_t cols = wo ? DM : HD, rows = HD + DM - cols, pitch = cols * 2;
    const cuuint64_t dim[4][5] = {{cols, 2, 8, 2, 18}, {cols, 16, 1, 1, rows / 16}, {cols, 2, 4, 4, rows / 32}, {64, 16, 64, 2, 18}};
    const cuuint64_t stride[4][4] = {{8 * pitch, pitch, 16 * pitch, 32 * pitch}, {pitch, pitch, pitch, 16 * pitch},
                                     {pitch, 8 * pitch, 2 * pitch, 32 * pitch}, {pitch, 128, 16 * pitch, 32 * pitch}};
    const cuuint32_t box[4][5] = {{64, 2, 8, 1, 18}, {64, 16, 1, 1, 1}, {64, 2, 4, 2, 1}, {64, 16, 2, 1, 18}}, one[5] = {1, 1, 1, 1, 1};
    const int k = i < 3 ? 0 : i < 7 ? 1 : i < 8 ? 2 : 3;
    encode(&P.map[i], CU_TENSOR_MAP_DATA_TYPE_BFLOAT16, 5, d_in[wo ? 11 : 8 + (i & 7) % 3], dim[k], stride[k], box[k], one,
           CU_TENSOR_MAP_INTERLEAVE_NONE, CU_TENSOR_MAP_SWIZZLE_128B, CU_TENSOR_MAP_L2_PROMOTION_L2_128B, CU_TENSOR_MAP_FLOAT_OOB_FILL_NONE);
  }
  P.X = (const bf16*)d_in[0]; P.K = (const bf16*)d_in[1]; P.V = (const bf16*)d_in[2];
  P.shift = (const bf16*)d_in[3]; P.Hk = (const bf16*)d_in[4]; P.Dk = (const bf16*)d_in[5];
  P.mem0 = (const bf16*)d_in[7];
  P.Wq = (const bf16*)d_in[8]; P.Wk = (const bf16*)d_in[9]; P.Wv = (const bf16*)d_in[10]; P.Wo = (const bf16*)d_in[11];
  P.out = (bf16*)d_out;
  for (int i = 0; i < 26; i++) P.dly[i] = h_dly[i];
  cudaFuncSetAttribute(k_main, cudaFuncAttributeMaxDynamicSharedMemorySize, SMEM_BYTES);
  k_main<<<N_CTA, 512, SMEM_BYTES>>>(P);
}
```

```cpp
#include <cuda.h>
#include <cuda_runtime.h>
#include <cuda_bf16.h>
#include <stdint.h>

namespace {

typedef __nv_bfloat16 bf16;

constexpr int SEQ = 2048, DM = 576, HD = 4096, NSEG = 64;
constexpr int LAG = 7, STEPS = NSEG + LAG, RING = 8;
constexpr int LOCK0 = 3, QRING = LOCK0 + 1;
static_assert(LAG < RING, "ring");
constexpr int N_CHAIN = 64, N_G = 48, N_O = 18, N_F = 2;
constexpr uint32_t SBASE = 1024;
constexpr uint32_t SENT = 0xFFFFFFFFu;
constexpr int SPIN_MAX = 1 << 22;

__device__ __forceinline__ uint32_t bid() {
  uint32_t b;
  asm volatile("mov.u32 %0, %%ctaid.x;" : "=r"(b));
  return b < 6 ? b + 106 : b < 8 ? b + 122 : b < 114 ? b - 8 : b < 130 ? b - 2 : b;
}
__device__ __forceinline__ uint32_t chain_id() { return blockIdx.x - 8; }
constexpr int KVP = SEQ + 64;
__device__ __align__(1024) bf16 g_kvT[DM * KVP];
__device__ __align__(1024) bf16 g_yT[DM * SEQ];
__device__ __align__(1024) unsigned char g_lnimg[2 * NSEG * 9 * 4096];
__device__ __align__(1024) unsigned char g_qkv[QRING * N_CHAIN * 24576];
__device__ __align__(1024) unsigned char g_oimg[RING * N_CHAIN * 8192];
constexpr int ARING = 16;
static_assert(ARING >= LAG + 9, "accumulator ring");
__device__ __align__(1024) float g_oacc[ARING * 64 * DM];
constexpr int MRING = LAG + 4, N_GRP = 32 + MRING + 1;
constexpr int XB_M = 256, XB_F = XB_M + MRING * 8, XB_REF = XB_F + 2, N_CTA = N_CHAIN + N_G + N_O + N_F;
__device__ __align__(65536) uint4 g_xb[N_GRP * 4096];
#define g_mimg ((uint32_t*)(g_xb + XB_M * 512))
__device__ uint32_t g_near[N_GRP];
__device__ uint32_t g_side[N_CTA];
__device__ __align__(128) uint32_t g_gbar[3 * 32];
constexpr int FL_G = 0, FL_F = 96 * 8, FL_OCNT = FL_F + 2 * 8, OCRING = 16, FL_TICK = 992, FL_O = 2048, FL_SYNC = FL_O + 128;
static_assert(FL_OCNT + OCRING * 8 <= FL_TICK, "flag block");
#define g_fl ((uint32_t*)(g_xb + XB_F * 512))
__device__ __align__(1024) uint32_t g_lnflag[128 * 8];
#define TS(slot)

#define CNT(slot, tries)
#define T3(slot)
#define TR(slot)
#define TRV(slot, val)
#define TRD(slot, dep)
#define TRSYNC()
#define TRDUMP(n)
#define CLK(t) "{.reg .b64 x; .reg .b32 h; mov.u64 x, %%clock64; mov.b64 {" t ", h}, x;}"
__device__ __forceinline__ uint32_t clk() { uint32_t t; asm volatile(CLK("%0") : "=r"(t) :: "memory"); return t; }
__device__ __forceinline__ void wait_until(uint32_t t0, uint32_t d) {
  asm volatile("{.reg .pred p; .reg .u32 t;\n"
               "W: " CLK("t") " sub.u32 t, t, %0; setp.lt.s32 p, t, 0; @p bra.uni W;}"
               :: "r"(t0 + d) : "memory");
}
__device__ __forceinline__ uint32_t pack2(float lo, float hi) {
  uint32_t r; asm("cvt.rn.bf16x2.f32 %0, %1, %2;" : "=r"(r) : "f"(hi), "f"(lo)); return r;
}
__device__ __forceinline__ float bf_lo(uint32_t v) { return __uint_as_float(v << 16); }
__device__ __forceinline__ float bf_hi(uint32_t v) { return __uint_as_float(v & 0xFFFF0000u); }

__device__ __forceinline__ void st_b128(void* p, uint32_t a, uint32_t b, uint32_t c, uint32_t d) {
  asm volatile("{.reg .b128 v; mov.b128 v, {%1,%2,%3,%4}; st.relaxed.gpu.global.b128 [%0], v;}" :: "l"(p), "r"(a), "r"(b), "r"(c), "r"(d) : "memory");
}
__device__ __forceinline__ void st_relaxed_if(void* p, uint32_t a, bool on) {
  asm volatile("{.reg .pred p; setp.ne.u32 p, %2, 0; @p st.relaxed.gpu.global.u32 [%0], %1;}" :: "l"(p), "r"(a), "r"((uint32_t)on) : "memory");
}
__device__ __forceinline__ uint32_t ld_acquire(const uint32_t* p) {
  uint32_t v; asm volatile("ld.acquire.gpu.global.u32 %0, [%1];" : "=r"(v) : "l"(p) : "memory"); return v;
}
__device__ __forceinline__ void st_release(uint32_t* p, uint32_t v) {
  asm volatile("st.release.gpu.global.u32 [%0], %1;" :: "l"(p), "r"(v) : "memory");
}
__device__ __forceinline__ void bulk_reduce(float* dst, uint32_t src, uint32_t bytes) {
  asm volatile("cp.reduce.async.bulk.global.shared::cta.bulk_group.add.f32 [%0], [%1], %2;" :: "l"(dst), "r"(src), "r"(bytes) : "memory");
}
__device__ __forceinline__ void bulk_done_inc(uint32_t* p) {
  asm volatile("cp.async.bulk.wait_group 0;\n"
               "fence.proxy.async.global;\nfence.release.gpu;\n"
               "red.relaxed.gpu.global.add.u32 [%0], 1;\nred.relaxed.gpu.global.add.u32 [%0+4096], 1;" :: "l"(p) : "memory");
}
__device__ __forceinline__ void flag_release(uint32_t* p, uint32_t v) {
  asm volatile("fence.release.gpu;\nst.relaxed.gpu.global.u32 [%0], %1;\nst.relaxed.gpu.global.u32 [%0+4096], %1;" :: "l"(p), "r"(v) : "memory");
}
__device__ __forceinline__ void spin_guard(int& it) {
  asm volatile("{.reg .pred p; add.s32 %0, %0, 1; setp.gt.s32 p, %0, %1; @p trap;}" : "+r"(it) : "n"(SPIN_MAX));
}
__device__ __forceinline__ void wait_flags(const uint32_t* p, uint32_t v) {
  int it = 0;
  while (true) {
    uint32_t x; asm volatile("ld.relaxed.gpu.global.u32 %0, [%1];" : "=r"(x) : "l"(p) : "memory");
    if (__all_sync(~0u, x >= v)) break;
    spin_guard(it);
  }
  asm volatile("fence.acquire.gpu;" ::: "memory");
}
__device__ __forceinline__ uint32_t timer_sample() {
  uint32_t g;
  asm volatile("{.reg .b64 x; .reg .b32 h; mov.u64 x, %%globaltimer; mov.b64 {%0, h}, x;}" : "=r"(g) :: "memory");
  return (g >> 5) * 57 - clk();
}
template <int N> __device__ __forceinline__ uint32_t timer_offset() {
  const uint32_t base = timer_sample();
  int best = 0;
#pragma unroll 1
  for (int i = 0; i < N; i++) {
    const int a = timer_sample() - base, b = timer_sample() - base, c = timer_sample() - base;
    best = max(max(best, a), max(b, c));
  }
  return base + best;
}
__device__ __forceinline__ void grid_arrive(int i) {
  asm volatile("red.release.gpu.global.add.u32 [%0], %1;" :: "l"(g_gbar + i * 32), "r"(bid() ? 1u : 257u - N_CTA) : "memory");
}
__device__ __forceinline__ void grid_wait(int i, uint32_t gen) {
  int it = 0;
  while (((ld_acquire(g_gbar + i * 32) ^ gen) >> 8) == 0) spin_guard(it);
}
__device__ __forceinline__ bool elect() {
  uint32_t r; asm volatile("{.reg .pred p; elect.sync _|p, -1; selp.u32 %0, 1, 0, p;}" : "=r"(r)); return r;
}
__device__ __forceinline__ void bar_sync(int id, int cnt) { asm volatile("bar.sync %0, %1;" :: "r"(id), "r"(cnt) : "memory"); }
__device__ __forceinline__ void bar_arrive(int id, int cnt) { asm volatile("bar.arrive %0, %1;" :: "r"(id), "r"(cnt) : "memory"); }
template <int id, int cnt> __device__ __forceinline__ void bar_arrive_after(uint32_t a, uint32_t b) {
  asm volatile("{.reg .pred p; setp.ne.u32 p, %2, 0xfff12345; setp.ne.and.u32 p, %3, 0xfff12345, p; @p bar.arrive %0, %1;}" :: "n"(id), "n"(cnt), "r"(a), "r"(b) : "memory");
}
template <int id, int cnt> __device__ __forceinline__ void bar_sync_after(uint32_t a) {
  asm volatile("{.reg .pred p; setp.ne.u32 p, %2, 0xfff12345; @p bar.sync %0, %1;}" :: "n"(id), "n"(cnt), "r"(a) : "memory");
}
__device__ __forceinline__ void fence_async_smem() { asm volatile("fence.proxy.async.shared::cta;" ::: "memory"); }
__device__ __forceinline__ void fence_async_global() { asm volatile("fence.proxy.async.global;" ::: "memory"); }
__device__ __forceinline__ void mbar_init(uint32_t mb, int cnt) { asm volatile("mbarrier.init.shared::cta.b64 [%0], %1;" :: "r"(mb), "r"(cnt) : "memory"); }
__device__ __forceinline__ void mbar_arrive(uint32_t mb) { asm volatile("mbarrier.arrive.shared::cta.b64 _, [%0];" :: "r"(mb) : "memory"); }
__device__ __forceinline__ void mbar_expect(uint32_t mb, uint32_t bytes) {
  asm volatile("mbarrier.arrive.expect_tx.shared::cta.b64 _, [%0], %1;" :: "r"(mb), "r"(bytes) : "memory");
}
__device__ __forceinline__ void mbar_wait(uint32_t mb, uint32_t parity) {
  asm volatile("{.reg .pred p;\nW: mbarrier.try_wait.parity.shared::cta.b64 p, [%0], %1;\n@!p bra W;}" :: "r"(mb), "r"(parity) : "memory");
}
template <int K> __device__ __forceinline__ void mbar_wait_step(uint32_t mb, int n) {
  asm volatile("{.reg .pred p; .reg .b32 t; add.u32 t, %1, %2; and.b32 t, t, 1;\nW: mbarrier.try_wait.parity.shared::cta.b64 p, [%0], t;\n@!p bra W;}" :: "r"(mb), "r"(n), "n"(2 * K) : "memory");
}
__device__ __forceinline__ void bulk_load(uint32_t dst, const void* src, uint32_t bytes, uint32_t mb) {
  asm volatile("cp.async.bulk.shared::cluster.global.mbarrier::complete_tx::bytes [%0], [%1], %2, [%3];" :: "r"(dst), "l"(src), "r"(bytes), "r"(mb) : "memory");
}
__device__ __forceinline__ void bulk_store(void* dst, uint32_t src, uint32_t bytes) {
  asm volatile("cp.async.bulk.global.shared::cta.bulk_group [%0], [%1], %2;" :: "l"(dst), "r"(src), "r"(bytes) : "memory");
}
__device__ __forceinline__ uint32_t mapa(uint32_t a, uint32_t rank) {
  uint32_t r; asm("mapa.shared::cluster.u32 %0, %1, %2;" : "=r"(r) : "r"(a), "r"(rank)); return r;
}
__device__ __forceinline__ void st_async4(uint32_t dst, float a, float b, float c, float d, uint32_t mb) {
  asm volatile("st.async.shared::cluster.mbarrier::complete_tx::bytes.v4.f32 [%0], {%1,%2,%3,%4}, [%5];" :: "r"(dst), "f"(a), "f"(b), "f"(c), "f"(d), "r"(mb) : "memory");
}
__device__ __forceinline__ void st_async1(uint32_t dst, uint32_t a, uint32_t mb) {
  asm volatile("st.async.shared::cluster.mbarrier::complete_tx::bytes.u32 [%0], %1, [%2];" :: "r"(dst), "r"(a), "r"(mb) : "memory");
}
__device__ __forceinline__ uint4 lds128(uint32_t a) {
  uint4 v; asm volatile("ld.shared.v4.u32 {%0,%1,%2,%3}, [%4];" : "=r"(v.x), "=r"(v.y), "=r"(v.z), "=r"(v.w) : "r"(a) : "memory"); return v;
}
__device__ __forceinline__ uint2 lds64(uint32_t a) {
  uint2 v; asm volatile("ld.shared.v2.u32 {%0,%1}, [%2];" : "=r"(v.x), "=r"(v.y) : "r"(a) : "memory"); return v;
}
__device__ __forceinline__ uint32_t lds32(uint32_t a) {
  uint32_t v; asm volatile("ld.shared.u32 %0, [%1];" : "=r"(v) : "r"(a) : "memory"); return v;
}
__device__ __forceinline__ void sts128(uint32_t a, uint4 v) {
  asm volatile("st.shared.v4.u32 [%0], {%1,%2,%3,%4};" :: "r"(a), "r"(v.x), "r"(v.y), "r"(v.z), "r"(v.w) : "memory");
}
__device__ __forceinline__ void sts32(uint32_t a, uint32_t x) { asm volatile("st.shared.u32 [%0], %1;" :: "r"(a), "r"(x) : "memory"); }
__device__ __forceinline__ void ldsm4(uint32_t& r0, uint32_t& r1, uint32_t& r2, uint32_t& r3, uint32_t a) {
  asm volatile("ldmatrix.sync.aligned.m8n8.x4.shared.b16 {%0,%1,%2,%3}, [%4];" : "=r"(r0), "=r"(r1), "=r"(r2), "=r"(r3) : "r"(a) : "memory");
}
__device__ __forceinline__ void ldsm4t(uint32_t& r0, uint32_t& r1, uint32_t& r2, uint32_t& r3, uint32_t a) {
  asm volatile("ldmatrix.sync.aligned.m8n8.x4.trans.shared.b16 {%0,%1,%2,%3}, [%4];" : "=r"(r0), "=r"(r1), "=r"(r2), "=r"(r3) : "r"(a) : "memory");
}
__device__ __forceinline__ void stsm4(uint32_t a, uint32_t r0, uint32_t r1, uint32_t r2, uint32_t r3) {
  asm volatile("stmatrix.sync.aligned.m8n8.x4.shared.b16 [%0], {%1,%2,%3,%4};" :: "r"(a), "r"(r0), "r"(r1), "r"(r2), "r"(r3) : "memory");
}
__device__ __forceinline__ uint32_t movmat(uint32_t a) {
  uint32_t d; asm volatile("movmatrix.sync.aligned.m8n8.trans.b16 %0, %1;" : "=r"(d) : "r"(a)); return d;
}
__device__ __forceinline__ void mma16(float* d, uint32_t a0, uint32_t a1, uint32_t a2, uint32_t a3, uint32_t b0, uint32_t b1) {
  asm volatile("mma.sync.aligned.m16n8k16.row.col.f32.bf16.bf16.f32 {%0,%1,%2,%3}, {%4,%5,%6,%7}, {%8,%9}, {%0,%1,%2,%3};"
    : "+f"(d[0]), "+f"(d[1]), "+f"(d[2]), "+f"(d[3]) : "r"(a0), "r"(a1), "r"(a2), "r"(a3), "r"(b0), "r"(b1));
}
__device__ __forceinline__ void mma8(float* d, uint32_t a0, uint32_t a1, uint32_t b0) {
  asm volatile("mma.sync.aligned.m16n8k8.row.col.f32.bf16.bf16.f32 {%0,%1,%2,%3}, {%4,%5}, {%6}, {%0,%1,%2,%3};"
    : "+f"(d[0]), "+f"(d[1]), "+f"(d[2]), "+f"(d[3]) : "r"(a0), "r"(a1), "r"(b0));
}
__device__ __forceinline__ float rcp(float x) { float r; asm("rcp.approx.ftz.f32 %0, %1;" : "=f"(r) : "f"(x)); return r; }
__device__ __forceinline__ float ex2(float x) { float r; asm("ex2.approx.ftz.f32 %0, %1;" : "=f"(r) : "f"(x)); return r; }

__host__ __device__ constexpr uint64_t mkdesc(uint32_t off, uint32_t lbo, uint32_t sbo, uint32_t swz) {
  return (uint64_t)((SBASE + off) >> 4) | ((uint64_t)(lbo >> 4) << 16) | ((uint64_t)(sbo >> 4) << 32) | ((uint64_t)swz << 62);
}
__host__ __device__ constexpr uint64_t desc_sw128(uint32_t off) { return mkdesc(off, 16, 1024, 1); }
__host__ __device__ constexpr uint64_t desc_n16(uint32_t off) { return mkdesc(off, 256, 128, 0); }
__host__ __device__ constexpr uint64_t desc_m(uint32_t off) { return mkdesc(off, 16, 256, 3); }

__host__ __device__ constexpr uint64_t desc_sw64(uint32_t off) { return mkdesc(off, 16, 512, 2); }

__device__ __forceinline__ void wg_fence() { asm volatile("wgmma.fence.sync.aligned;" ::: "memory"); }
__device__ __forceinline__ void wg_commit() { asm volatile("wgmma.commit_group.sync.aligned;" ::: "memory"); }
template <int N> __device__ __forceinline__ void wg_wait() { asm volatile("wgmma.wait_group.sync.aligned %0;" :: "n"(N) : "memory"); }

#define ACC8(d) "+f"(d[0]), "+f"(d[1]), "+f"(d[2]), "+f"(d[3]), "+f"(d[4]), "+f"(d[5]), "+f"(d[6]), "+f"(d[7])
#define ACC32(d) ACC8(d), ACC8((d + 8)), ACC8((d + 16)), ACC8((d + 24))
#define R8 "{%0,%1,%2,%3,%4,%5,%6,%7}"
#define R32 "{%0,%1,%2,%3,%4,%5,%6,%7,%8,%9,%10,%11,%12,%13,%14,%15,%16,%17,%18,%19,%20,%21,%22,%23,%24,%25,%26,%27,%28,%29,%30,%31}"
template <int SD> __device__ __forceinline__ void wg_rs16(float* d, const uint32_t* a, uint64_t db) {
  asm volatile("wgmma.mma_async.sync.aligned.m64n16k16.f32.bf16.bf16 " R8 ", {%8,%9,%10,%11}, %12, %13, 1, 1, 1;"
    : ACC8(d) : "r"(a[0]), "r"(a[1]), "r"(a[2]), "r"(a[3]), "l"(db), "n"(SD));
}
template <int SD> __device__ __forceinline__ void wg_ss16(float* d, uint64_t da, uint64_t db) {
  asm volatile("wgmma.mma_async.sync.aligned.m64n16k16.f32.bf16.bf16 " R8 ", %8, %9, %10, 1, 1, 1, 1;"
    : ACC8(d) : "l"(da), "l"(db), "n"(SD));
}
template <int SD, uint64_t DA, uint64_t DB> __device__ __forceinline__ void wg_ss16o(float* d, uint32_t oa, uint32_t ob) {
  asm volatile("{.reg .b32 x, y; .reg .b64 a, b; add.u32 x, %8, %10; add.u32 y, %9, %12; mov.b64 a, {x, %11}; mov.b64 b, {y, %13};\n"
               "wgmma.mma_async.sync.aligned.m64n16k16.f32.bf16.bf16 " R8 ", a, b, %14, 1, 1, 1, 1;}"
    : ACC8(d) : "r"(oa), "r"(ob), "n"((uint32_t)DA), "n"((uint32_t)(DA >> 32)), "n"((uint32_t)DB), "n"((uint32_t)(DB >> 32)), "n"(SD));
}
template <int SD> __device__ __forceinline__ void wg_rs64(float* d, const uint32_t* a, uint64_t db) {
  asm volatile("wgmma.mma_async.sync.aligned.m64n64k16.f32.bf16.bf16 " R32 ", {%32,%33,%34,%35}, %36, %37, 1, 1, 0;"
    : ACC32(d) : "r"(a[0]), "r"(a[1]), "r"(a[2]), "r"(a[3]), "l"(db), "n"(SD));
}
template <int SD> __device__ __forceinline__ void wg_ss64(float* d, uint64_t da, uint64_t db) {
  asm volatile("wgmma.mma_async.sync.aligned.m64n64k16.f32.bf16.bf16 " R32 ", %32, %33, %34, 1, 1, 1, 0;"
    : ACC32(d) : "l"(da), "l"(db), "n"(SD));
}
#define WG_RSO(NAME, SHAPE, REGS, ACC, A, TB) \
template <int SD, uint64_t DB> __device__ __forceinline__ void NAME(float* d, uint32_t a0, uint32_t a1, uint32_t a2, uint32_t a3, uint32_t ob) { \
  asm volatile("{.reg .b64 b; mov.b64 b, {" A(4) ", " A(5) "};\nwgmma.mma_async.sync.aligned." SHAPE ".f32.bf16.bf16 " REGS \
               ", {" A(0) "," A(1) "," A(2) "," A(3) "}, b, " A(6) ", 1, 1, " TB ";}" \
    : ACC(d) : "r"(a0), "r"(a1), "r"(a2), "r"(a3), "r"(ob + (uint32_t)DB), "n"((uint32_t)(DB >> 32)), "n"(SD)); \
}
#define ACC4(d) "+f"(d[0]), "+f"(d[1]), "+f"(d[2]), "+f"(d[3])
#define ACC16(d) ACC8(d), ACC8((d + 8))
#define OP4(i) OP4_##i
#define OP4_0 "%4"
#define OP4_1 "%5"
#define OP4_2 "%6"
#define OP4_3 "%7"
#define OP4_4 "%8"
#define OP4_5 "%9"
#define OP4_6 "%10"
#define OP16(i) OP16_##i
#define OP16_0 "%16"
#define OP16_1 "%17"
#define OP16_2 "%18"
#define OP16_3 "%19"
#define OP16_4 "%20"
#define OP16_5 "%21"
#define OP16_6 "%22"
#define OP32(i) OP32_##i
#define OP32_0 "%32"
#define OP32_1 "%33"
#define OP32_2 "%34"
#define OP32_3 "%35"
#define OP32_4 "%36"
#define OP32_5 "%37"
#define OP32_6 "%38"
WG_RSO(wg_rs8o, "m64n8k16", "{%0,%1,%2,%3}", ACC4, OP4, "1")
#define R16 "{%0,%1,%2,%3,%4,%5,%6,%7,%8,%9,%10,%11,%12,%13,%14,%15}"
WG_RSO(wg_rs32o, "m64n32k16", R16, ACC16, OP16, "1")
WG_RSO(wg_rs64o, "m64n64k16", R32, ACC32, OP32, "0")
WG_RSO(wg_rs32k, "m64n32k16", R16, ACC16, OP16, "0")
template <uint64_t DA, uint64_t DB> __device__ __forceinline__ void wg_ss32k(float* d, uint32_t ob) {
  asm volatile("{.reg .b64 b; mov.b64 b, {%17, %18};\nwgmma.mma_async.sync.aligned.m64n32k16.f32.bf16.bf16 " R16 ", %16, b, 1, 1, 1, 1, 0;}"
    : ACC16(d) : "l"(DA), "r"(ob + (uint32_t)DB), "n"((uint32_t)(DB >> 32)));
}
template <int N> __device__ __forceinline__ void reg_inc() { asm volatile("setmaxnreg.inc.sync.aligned.u32 %0;" :: "n"(N)); }
template <int N> __device__ __forceinline__ void reg_dec() { asm volatile("setmaxnreg.dec.sync.aligned.u32 %0;" :: "n"(N)); }

template <int KS>
__device__ __forceinline__ void load_frags(uint32_t* a, uint32_t src) {
  const int lane = threadIdx.x & 31, w = (threadIdx.x >> 5) & 3;
  const int k = ((lane >> 4) << 3) + (lane & 7), u = w * 2 + ((lane >> 3) & 1);
  const uint32_t base = src + k * 128 + ((u ^ (k & 7)) << 4);
#pragma unroll
  for (int ks = 0; ks < KS; ks++) ldsm4t(a[ks * 4], a[ks * 4 + 1], a[ks * 4 + 2], a[ks * 4 + 3], base + ks * 2048);
}

__device__ __forceinline__ uint32_t badd2(uint32_t a, uint32_t b) { uint32_t r; asm("add.rn.bf16x2 %0, %1, %2;" : "=r"(r) : "r"(a), "r"(b)); return r; }
__device__ __forceinline__ uint32_t bsub2(uint32_t a, uint32_t b) { uint32_t r; asm("sub.rn.bf16x2 %0, %1, %2;" : "=r"(r) : "r"(a), "r"(b)); return r; }
__device__ __forceinline__ uint32_t bmul2(uint32_t a, uint32_t b) { uint32_t r; asm("mul.rn.bf16x2 %0, %1, %2;" : "=r"(r) : "r"(a), "r"(b)); return r; }
__device__ __forceinline__ uint32_t bfma2(uint32_t a, uint32_t b, uint32_t c) { uint32_t r; asm("fma.rn.bf16x2 %0, %1, %2, %3;" : "=r"(r) : "r"(a), "r"(b), "r"(c)); return r; }
template <int R> __device__ __forceinline__ void layernorm9(const uint32_t* x, uint32_t* o) {
  const uint32_t ones = 0x3F803F80u;
  float a[R][3][4], q[R], s[R];
#pragma unroll
  for (int i = 0; i < 9 * R; i++) {
    float* d = a[i % R][i / R % 3];
    if (i < 3 * R) d[0] = d[1] = d[2] = d[3] = 0.f;
    mma8(d, x[i % R * 9 + i / R], ones, x[i % R * 9 + i / R]);
  }
#pragma unroll
  for (int r = 0; r < R; r++) {
    q[r] = threadIdx.x & 4 ? a[r][0][1] + a[r][1][1] + a[r][2][1] : a[r][0][0] + a[r][1][0] + a[r][2][0];
    s[r] = (a[r][0][2] + a[r][0][3]) + (a[r][1][2] + a[r][1][3]) + (a[r][2][2] + a[r][2][3]);
  }
#pragma unroll
  for (int r = 0; r < R; r++) { q[r] += __shfl_xor_sync(~0u, q[r], 4); s[r] += __shfl_xor_sync(~0u, s[r], 1); }
#pragma unroll
  for (int r = 0; r < R; r++) { q[r] += __shfl_xor_sync(~0u, q[r], 9); s[r] += __shfl_xor_sync(~0u, s[r], 2); }
#pragma unroll
  for (int r = 0; r < R; r++) q[r] = __shfl_sync(~0u, q[r], 0) + __shfl_sync(~0u, q[r], 18);
#pragma unroll
  for (int r = 0; r < R; r++) {
    const float mean = s[r] * (1.f / DM), var = fmaxf(fmaf(q[r], 1.f / DM, -mean * mean), 0.f);
    float sd;
    asm("sqrt.approx.ftz.f32 %0, %1;" : "=f"(sd) : "f"(bf_lo(pack2(bf_lo(pack2(var, 0.f)) + 1e-5f, 0.f))));
    const float inv = rcp(bf_lo(pack2(sd, 0.f)));
    const uint32_t mb = pack2(mean, mean), hi = pack2(inv, inv), lo = pack2(inv - bf_lo(hi), inv - bf_lo(hi));
#pragma unroll
    for (int i = r * 9; i < r * 9 + 9; i++) {
      const uint32_t d = bsub2(x[i], mb);
      o[i] = bfma2(d, hi, bmul2(d, lo));
    }
  }
}
__device__ __forceinline__ void store_ln_row(int layer, int tok, const uint32_t* o) {
  const int lane = threadIdx.x & 31, r = tok & 31;
  unsigned char* p = g_lnimg + (size_t)(layer * NSEG + (tok >> 5)) * (9 * 4096) + r * 128 + (((lane >> 2) ^ (r & 7)) << 4) + (lane & 3) * 4;
#pragma unroll
  for (int i = 0; i < 9; i++) *(uint32_t*)(p + i * 4096) = o[i];
}
struct Params { CUtensorMap map[11]; const bf16 *X, *K, *V, *shift, *Hk, *Dk, *mem0, *Wq, *Wk, *Wv, *Wo; bf16* out; uint32_t dly[30]; };
#define DLYS P.dly[0]
#define DLYW P.dly[1]
#define DLYV P.dly[24]
#define DLYK P.dly[4]
#define DLYO P.dly[25]
#define DLYG P.dly[5]
#define KWIN P.dly[6]
#define KMIN P.dly[7]
#define PREF0 P.dly[19]
#define PACE P.dly[20]
#define S1G P.dly[21]
#define S1DLY P.dly[22]
#define PREFH P.dly[23]
uint32_t h_dly[30] = {800, 120, 150, 160, 3640, 4160, 2750, 1300, 1585, 1670, 1760, 2090, 2210, 2310, 2790, 2920, 3185, 3330, 3500, 7000, 160, 12500, 20500, 4000, 3540, 400, 800, 100, 300, 150};

constexpr uint32_t C_W = 0, C_M = 147456, C_KV = C_M + 18432, C_OS = C_KV + 24576, C_QM = C_KV + 32768, C_KM = C_QM + 2048,
                   C_VM = C_KM + 2048, C_OI = C_VM + 2048, C_SX = C_OI + 4096, C_KM2 = C_SX + 2560, C_VM2 = C_KM2 + 128,
                   C_KV2 = C_KM2 + 2048, C_Q = C_KV2 + 8192, C_BAR = C_Q + 8192;
constexpr uint32_t CB_FULL = C_BAR, CB_REF = C_BAR + 16, CB_SX = C_BAR + 32, CB_OX = C_BAR + 40, CB_XX = C_BAR + 48, CB_Q = C_BAR + 56, C_BAD = C_BAR + 64, W_BAR = C_BAR + 80, T_BAR = W_BAR + 24, S_GEN = C_BAR + 128, C_REF = C_BAR + 132, CB_VF = C_BAR + 144, CB_M = C_BAR + 160, CB_MV = C_BAR + 200;
constexpr uint32_t G_W = 0, G_RING = 147456, G_W2 = G_RING + 9 * 8192, G_BAR = G_W2 + 8192;
constexpr uint32_t O_W = 0, O_RING = 3 * 40960, O_ST = O_RING + 11 * 8192, O_BAR = O_ST + 16384, OB_ST = O_BAR + 64;
constexpr uint32_t F_A = 0, F_XY = 36864, F_L = F_XY + 36864, F_X = F_L + 18432, F_Y = F_L + 2 * 36864, F_BAR = C_BAR;
constexpr uint32_t SMEM_BYTES = C_BAR + 256;
static_assert(G_BAR + 256 <= SMEM_BYTES && O_BAR + 256 <= SMEM_BYTES && F_BAR + 16 <= SMEM_BYTES && SMEM_BYTES <= 232448, "smem map");
enum { B_INIT = 1, B_M, B_QK, B_S, B_V, B_O, B_X, B_WG0, B_WG1, B_WG2, B_G, B_OE, B_T, B_R };

__device__ __forceinline__ uint4 pack_partial(const float* d, uint32_t tag) {
  uint32_t x, z;
  asm("lop3.b32 %0, %2, 1, %4, 0xb8; lop3.b32 %1, %3, 1, %4, 0xb8;" : "=&r"(x), "=&r"(z) : "r"(pack2(d[0], d[1])), "r"(pack2(d[2], d[3])), "r"(tag));
  return make_uint4(x, pack2(d[4], d[5]), z, pack2(d[6], d[7]));
}
__device__ __forceinline__ void store_partial(uint4* p, const uint4& v) { st_b128(p, v.x, v.y, v.z, v.w); }
__device__ __forceinline__ void gather_reduce(const uint32_t* p, uint32_t* dst, uint32_t m0, bool shared, uint32_t tag, uint32_t lane, uint32_t sb, int n, int TS0) {
  int tries = 0;
  bool bad;
  TR(TS0);
  do {
    uint2 x[8];
#pragma unroll
    for (int i = 0; i < 8; i++)
      asm volatile("{.reg .b64 v; ld.relaxed.gpu.global.b64 v, [%2]; mov.b64 {%0, %1}, v;}" : "=r"(x[i].x), "=r"(x[i].y) : "l"(p + i * 128) : "memory");
    spin_guard(tries);
    float a = bf_lo(x[0].x), b = bf_hi(x[0].x), c = bf_lo(x[0].y), d = bf_hi(x[0].y);
    uint32_t t = x[0].x ^ tag;
#pragma unroll
    for (int i = 1; i < 8; i++) {
      a += bf_lo(x[i].x); b += bf_hi(x[i].x); c += bf_lo(x[i].y); d += bf_hi(x[i].y);
      asm("lop3.b32 %0, %0, %1, %2, 0xf6;" : "+r"(t) : "r"(x[i].x), "r"(tag));
    }
    bad = __any_sync(~0u, t & 1);
    const bool up = lane & 8;
    float u = (up ? c : a) + __shfl_xor_sync(~0u, up ? a : c, 8), v = (up ? d : b) + __shfl_xor_sync(~0u, up ? b : d, 8);
    if (shared) { u += __shfl_xor_sync(~0u, u, 4); v += __shfl_xor_sync(~0u, v, 4); }
    u += __shfl_xor_sync(~0u, u, 16);
    v += __shfl_xor_sync(~0u, v, 16);
    st_relaxed_if(dst, n < LAG && up ? m0 : pack2(u, v), !bad);
  } while (bad);
  if (shared) bar_arrive(B_WG2, 224);
  TR(TS0 + 3); TRV(TS0 + 2, tries);
  CNT((TS0 - 16) >> 2, tries);
}

constexpr int XR = 3;
__host__ __device__ constexpr int o_ks(int s) { return s & (s < 8 ? 3 : 7); }
constexpr uint32_t OPAT = 0x55555577u;
__host__ __device__ constexpr bool o_reg(int s) { return (OPAT >> s) & 1; }
__host__ __device__ constexpr int o_slot(int s) { int k = 0; for (int i = 0; i < s; i++) k += o_reg(i) == o_reg(s); return k; }
__device__ __forceinline__ int g_unit(int wg) {
  const int i = bid() - N_CHAIN;
  return i < 32 ? wg * 64 + i : 2 * i - 32 + wg;
}
__device__ __forceinline__ uint32_t pinned(uint32_t v) { return __shfl_sync(~0u, v, threadIdx.x & 31); }
template <class T> __device__ __forceinline__ T* pinned(T* p) { return (T*)__shfl_sync(~0u, (unsigned long long)p, threadIdx.x & 31); }
enum { CHAIN, GROLE, OROLE };
template <int ROLE, bool SYNC> __device__ __forceinline__ void load_box(const Params& P, uint32_t sb, bool regs, int wg, int i, uint32_t mb, bool on) {
  const int b = bid();
  int map, col = 0, ks = 0, c2 = 0, c3 = 0;
  uint32_t dst = wg * 73728;
  if (ROLE == CHAIN) {
    const int k = i - 1, st = __fns(regs ? OPAT : ~OPAT, 0, i) & 31;
    dst += i ? (17 + i) * 2048 : 0;
    if (wg || i == 0) { map = wg + i; col = b * 64; c3 = !regs; }
    else if (!regs && k >= 14) { map = 6; ks = b * 4 + k - 14; }
    else { map = 6; col = 64 + (st < 8 ? (st >> 2) * 64 : (st >> 3) * 128 + (b & 1) * 64); ks = (b * 4) ^ o_ks(st); }
  } else if (ROLE == GROLE) {
    const int q = g_unit(wg);
    map = ((q >> 5) + 1) % 3;
    if (i) { map += 3; col = (q & 31) * 128 + (i - 1) * 64; ks = 34; dst = G_W2 + wg * 4096 + (i - 1) * 2048; }
    else { map += 8; c2 = (q & 31) * 2; c3 = !regs; }
  } else {
    const int o = b - N_CHAIN - N_G, ksl = o / 3;
    map = 7; col = ((o % 3) * 3 + (wg + ksl) % 3) * 64; dst = (wg * (regs ? 24 : 20) + i) * 2048;
    ks = (ksl * 11 - max(ksl - 4, 0)) * 4 + (regs ? i / 3 * 5 + i % 3 * 2 : i < 16 ? i / 2 * 5 + 1 + i % 2 * 2 : i + 24);
    c3 = (ks & 1) * 2; ks >>= 1;
  }
  if (SYNC) { col = pinned(col); ks = pinned(ks); bar_sync(B_WG0 + wg, 256); }
  if (on) asm volatile("cp.async.bulk.tensor.5d.shared::cluster.global.tile.mbarrier::complete_tx::bytes [%0], [%1, {%2, %3, %4, %5, %6}], [%7];"
               :: "r"(sb + dst), "l"(&P.map[map]), "r"(col), "r"(0), "r"(c2), "r"(c3), "r"(ks), "r"(mb) : "memory");
}
template <int ROLE, bool SYNC = false> __device__ __forceinline__ void load_wg(const Params& P, uint32_t sb, bool regs, int wg, int quarter) {
  const int i = (threadIdx.x & 31) * 4 + quarter;
  const int n = ROLE == CHAIN ? 36 : ROLE == GROLE ? (regs ? 38 : 36) : regs ? 24 : bid() < N_CHAIN + N_G + 12 ? 20 : 16;
  const bool split = SYNC && wg == 0;
  const uint32_t mb = split && i ? sb + T_BAR : sb + W_BAR + wg * 8;
  load_box<ROLE, SYNC>(P, sb, regs, wg, i, mb, i < (ROLE == CHAIN ? (wg ? 2 : 19) : ROLE == GROLE ? n - 35 : n));
  if (i <= split) mbar_expect(mb, n * (split ? 1024 : 2048));
  __syncwarp();
}
__device__ __forceinline__ uint32_t near_half(uint32_t blk, uint32_t reader) {
  return __ldcg(g_near + (blk >> 3)) ^ (~blk & 1) ^ __ldcg(g_side + (blk >> 3)) ^ __ldcg(g_side + reader);
}

__device__ __forceinline__ uint32_t opaque_tid() { uint32_t t; asm volatile("mov.u32 %0, %%tid.x;" : "=r"(t)); return t; }
__device__ __forceinline__ void m_fetch(uint32_t sb, uint32_t src, uint32_t b, uint32_t mb) {
  bulk_load(sb + C_M + (b ? b * 4096 - 2048 : 0), (const unsigned char*)g_mimg + ((src ^ ((b & 1) * 4096)) + b * 8192), b ? 4096 : 2048, mb);
}
__device__ __forceinline__ uint32_t m_probe(uint32_t lane) { return lane * 32 + (lane & 4) * 4 + (lane >> 3) * 4; }
__device__ __forceinline__ uint32_t m_max(uint32_t a, uint32_t b) {
  return max(max(lds32(a), lds32(a + 1024)), max(lds32(b), lds32(b + 1024)));
}
template <int S0, int N> __device__ __forceinline__ void o_steps(float* d, const uint32_t* a) {
  constexpr int SD = o_ks(S0) != 0;
  if constexpr (o_reg(S0)) wg_rs16<SD>(d, a + (18 + o_slot(S0)) * 4, desc_n16(C_OI + o_ks(S0) * 512));
  else wg_ss16<SD>(d, desc_sw128(C_W + (18 + o_slot(S0)) * 2048), desc_n16(C_OI + o_ks(S0) * 512));
  if constexpr (N > 1) o_steps<S0 + 1, N - 1>(d, a);
}
template <int BASE, int KS, int N> __device__ __forceinline__ void m_steps(float* d, const uint32_t* a, uint32_t oa) {
  wg_rs16<KS != 0>(d, a + (BASE + KS / 2) * 4, desc_m(C_M + KS * 512));
  if constexpr (KS >= 36 - 2 * XR) wg_rs16<1>(d, a + (18 + XR + KS / 2) * 4, desc_m(C_M + KS * 512 + 512));
  else wg_ss16o<1, desc_sw128(C_W + (BASE + KS / 2) * 2048), desc_m(C_M + KS * 512 + 512)>(d, oa, 0);
  if constexpr (N > 2) m_steps<BASE, KS + 2, N - 2>(d, a, oa);
}

constexpr uint32_t VPAT = 0x15bbd249u;
template <int I, int R, int S> __device__ __forceinline__ void v_steps(float* d, const uint32_t* a) {
  constexpr bool reg = (VPAT >> I) & 1;
  if constexpr (reg) wg_rs16<1>(d, a + (18 + R) * 4, desc_m(C_M + R * 1024));
  else wg_ss16<1>(d, desc_sw128(C_W + (54 + S) * 2048), desc_m(C_M + S * 1024 + 512));
  if constexpr (I < 31) v_steps<I + 1, R + reg, S + !reg>(d, a);
  else static_assert(R + reg == 18, "pattern");
}

__device__ __forceinline__ void chain_proj(const Params& P, uint32_t sb) {
  const uint32_t c = chain_id(), h = c >> 1, j = c & 1, wid = __shfl_sync(~0u, threadIdx.x >> 5, 0), wg = wid >> 2, w = wid & 3;
  const uint32_t t = threadIdx.x & 127, lane = pinned(t & 31), mine = pinned(sb + t * 16), rb = mapa(sb, j ^ 1);
  const uint32_t theirs = pinned(rb + C_KM2 + w * 512 + lane * 4), oa = wg * 4608;
  uint32_t a[144 + 4 * XR];
  mbar_wait(sb + W_BAR + wg * 8, 0);
  if (threadIdx.x == 0) TS(23);
  load_frags<36>(a, sb + C_W + wg * 73728);
  fence_async_smem();
  bar_arrive(B_WG0 + wg, 256);
  if (threadIdx.x == 0) TS(24);
  bar_sync(B_WG2, 384);
  const uint32_t round = min(wid ^ 4, 5u), gdly = P.dly[8 + round], ps = t >> 2, pf = j * 16 + (ps >> 1);
  const bool shared = round < 3;
  uint4* const dsts = pinned(g_xb + (ps * 4096 + near_half(ps * 8, ps * 2) * 256 + c * 4 + (t & 3)));
  uint4* const dstf = pinned(g_xb + (pf * 4096 + 512 + near_half(pf * 8 + 1, pf * 2) * 256 + h * 8 + (t & 7)));
  const uint32_t* const gsrc = (const uint32_t*)g_xb + (h * 16384 + round % 3 * 4096 + near_half(h * 8 + !shared, h * 2) * 1024 +
                               (shared ? lane * 4 + j * 2 : 2048 + (lane & 24) * 4 + j * 16 + (lane & 7) * 2));
  uint32_t* gdst = g_mimg + (16384 + (lane >> 4) * 1024 +
                   (shared ? (round ? 1536 + round * 512 : 0) + c * 8 + (((lane >> 1) ^ c) & 4) + (lane & 3)
                           : (round - 1) * 2048 + c * 16 + (lane & 1) * 8 + (((lane >> 1) ^ (c * 2)) & 4) + ((lane >> 1) & 3)));
  const uint32_t m0 = __ldcg(gdst - 16384);
  mbar_wait(sb + W_BAR + wg * 8, 1);
  load_frags<XR>(a + 144, sb + C_W + wg * 73728 + (18 - XR) * 2048);
  bar_sync(B_INIT, 256);
  if ((threadIdx.x & 127) == 0) TS(4);

  uint32_t ring = 1;
#pragma unroll 1
  for (int n = 0; n < STEPS; n++) {
    float d[8], e[8];
    if (n + 1 == STEPS && !wg) { bar_arrive(B_QK, 416); break; }
#pragma unroll
    for (int i = 0; i < 8; i++) e[i] = 0.f;
    uint32_t redo = n + 1;
#pragma unroll 1
    do {
      mbar_wait(sb + CB_M, n & 1);
      wg_fence();
      m_steps<0, 0, 4>(d, a, oa);
      wg_commit();
      if (wg) { wg_fence(); m_steps<18, 0, 4>(e, a, 4608); wg_commit(); }
      if (wid == 0) TR(8);
      mbar_wait(sb + CB_M + 8, n & 1);
      wg_fence();
      m_steps<0, 4, 8>(d, a, oa);
      wg_commit();
      mbar_wait(sb + CB_MV, n & 1);
      asm volatile("{.reg .pred p; .reg .u32 t; ld.shared.u32 t, [%1]; setp.eq.u32 p, t, %0; selp.u32 %0, -1, 0, p;}" : "+r"(redo) : "r"(sb + C_BAD) : "memory");
    } while (redo);
    mbar_wait(sb + CB_MV + 8, n & 1);
    wg_fence();
    m_steps<0, 12, 8>(d, a, oa);
    wg_commit();
    mbar_wait(sb + CB_MV + 16, n & 1);
    wg_fence();
    m_steps<0, 20, 8>(d, a, oa);
    wg_commit();
    mbar_wait(sb + CB_MV + 24, n & 1);
    wg_fence();
    m_steps<0, 28, 8>(d, a, oa);
    wg_commit();
    wg_wait<0>();
    if (w == 0) TR(6 + wg);
    const uint32_t f0 = pack2(d[0], d[1]), f1 = pack2(d[4], d[5]), f2 = pack2(d[2], d[3]), f3 = pack2(d[6], d[7]);
    stsm4(mine + C_QM + wg * 2048, f0, f1, f2, f3);
    bar_arrive(B_QK, 416);
    const uint32_t tag = (n & 1) ^ 1;
    if (n == 0) mbar_wait(sb + T_BAR, 0);
    if (wg) {
      if (n + 1 < STEPS) bar_sync(B_S, 256);
      wg_fence();
      v_steps<0, 2, 2>(e, a);
      wg_commit();
      const uint32_t k0 = j ? f0 : f1, k1 = j ? f2 : f3;
      mbar_wait(sb + CB_SX, n & 1);
      wg_wait<0>();
      if (w == 0) TR(11);
      const uint32_t v0 = pack2(e[0], e[1]), v1 = pack2(e[4], e[5]), v2 = pack2(e[2], e[3]), v3 = pack2(e[6], e[7]);
      stsm4(mine + C_VM, v0, v1, v2, v3);
      bar_arrive(B_V, 256);
      st_async1(theirs, k0, rb + CB_XX);
      st_async1(theirs + 256, k1, rb + CB_XX);
      st_async1(theirs + 128, j ? v0 : v1, rb + CB_XX);
      st_async1(theirs + 384, j ? v2 : v3, rb + CB_XX);
      if (n + 1 == STEPS) break;
      bar_sync(B_O, 256);
      fence_async_smem();
      wg_fence();
#pragma unroll
      for (int ks = 0; ks < 4; ks++) {
        if (ks == 0) wg_ss16<0>(d, desc_sw128(C_W + 32 * 2048), desc_n16(C_OI));
        else wg_ss16<1>(d, desc_sw128(C_W + (32 + ks) * 2048), desc_n16(C_OI + ks * 512));
      }
      wg_commit();
      bar_arrive(B_X, 256);
      if (w == 0) TR(0);
      wg_wait<0>();
      store_partial(dsts, pack_partial(d, tag));
      bar_arrive(B_M, 160);
      if (w == 0) TR(1);
    } else {
      bar_sync(B_X, 256);
      wg_fence();
      o_steps<0, 4>(d, a);
      wg_commit();
      o_steps<4, 4>(e, a);
      wg_commit();
      wg_wait<1>();
      store_partial(dsts + 1024, pack_partial(d, tag));
      if (w == 0) TR(2);
      wg_wait<0>();
      store_partial(dsts + 2048, pack_partial(e, tag));
      if (w == 0) TR(3);
      wg_fence();
      o_steps<8, 4>(d, a);
      wg_commit();
      bar_sync(B_T, 256);
      if (w == 0) { TRV(61, 0); TR(12); }
      wg_fence();
      o_steps<12, 4>(d, a);
      wg_commit();
      o_steps<16, 8>(e, a);
      wg_commit();
      wg_wait<1>();
      store_partial(dstf, pack_partial(d, tag));
      if (w == 0) TR(4);
      wg_fence();
      o_steps<24, 8>(d, a);
      wg_commit();
      wg_wait<1>();
      store_partial(dstf + 1024, pack_partial(e, tag));
      bar_arrive(B_OE, 256);
      if (w == 0) TR(5);
      wg_wait<0>();
      store_partial(dstf + 2048, pack_partial(d, tag));
      if (w == 0) TR(15);
    }
    if ((wid ^ 4) < 6) {
      mbar_wait(sb + CB_REF, n & 1);
      wait_until(lds32(sb + C_REF), gdly);
      gather_reduce(gsrc, gdst, m0, shared, tag, lane, sb, n, 16 + round * 4);
      if (++ring == MRING) { ring = 0; gdst -= MRING * 16384; }
      gdst += 16384;
    }
  }
}

template <int KS> __device__ __forceinline__ void x_scores(float* s, float* sm, const uint4* q, uint32_t ok, uint32_t om) {
  wg_rs32o<KS != 0, desc_sw64(C_KV + KS * 1024)>(s, q[KS].x, q[KS].y, q[KS].z, q[KS].w, ok);
  wg_rs8o<KS != 0, desc_n16(C_KM + KS * 512)>(sm, q[KS].x, q[KS].y, q[KS].z, q[KS].w, om);
  if constexpr (KS < 3) x_scores<KS + 1>(s, sm, q, ok, om);
}

__device__ __forceinline__ void chain_attn(const Params& P, uint32_t sb) {
  const int c = chain_id(), j = c & 1;
  const int tid = threadIdx.x, lane = tid & 31, w = __shfl_sync(~0u, (tid >> 5) & 3, 0);
  const int l = w >> 1, u = w & 1;
  const uint32_t rb = mapa(sb, j ^ 1);
  const float sc = 0.08838834764831845f * 1.4426950408889634f;
  const uint32_t ones = 0x3F803F80u, sx = C_SX + l * 1280;
  const uint32_t km_off = C_KM + (lane >> 3) * 256 + l * 128 + (lane & 7) * 16;
  const uint32_t qm_off = C_QM + (lane >> 4) * 256 + l * 128 + (lane & 7) * 16, kmu = pinned(sb + km_off + u * 1024);
  const uint32_t kv_off = C_KV + l * 4096 + (lane & 15) * 64 + (((lane >> 4) ^ (u * 2) ^ ((lane >> 1) & 3)) << 4);

  load_wg<CHAIN, true>(P, sb, false, 1, w);
  if (lane == 0) mbar_arrive(sb + CB_M);
#pragma unroll 1
  for (int n = 0; n < STEPS; n++) {
    const uint32_t kvb = sb + kv_off + (n & 1) * 16384;
    mbar_wait(sb + CB_FULL + (n & 1) * 8, (n >> 1) & 1);
    if (n < 3 && tid == 256) TS(n ? 20 + n : 5);
    __syncwarp();
    {
      uint32_t km[8];
      uint4 kx[8];
#pragma unroll
      for (int i = 0; i < 8; i++) ldsm4t(kx[i].x, kx[i].y, kx[i].z, kx[i].w, (kvb ^ ((i & 1) * 32)) + (i >> 1) * 1024);
      mbar_wait_step<1>(sb + CB_VF, n);
      if (w == 1) TRD(60, kx[7].x);
      bar_sync(B_QK, 416);
      if (n + 1 == STEPS) {
        st_async4(rb + sx + u * 512 + lane * 16, 0.f, 0.f, 0.f, 0.f, rb + CB_SX);
        st_async1(rb + sx + 1024 + u * 128 + lane * 4, 0, rb + CB_SX);
        bar_sync(B_V, 256);
      } else {
      uint32_t qm[16];
#pragma unroll
      for (int ks = 0; ks < 4; ks++) ldsm4t(qm[4 * ks], qm[4 * ks + 1], qm[4 * ks + 2], qm[4 * ks + 3], sb + qm_off + ks * 512);
      ldsm4t(km[0], km[1], km[2], km[3], sb + km_off);
      ldsm4t(km[4], km[5], km[6], km[7], sb + km_off + 1024);
      float s[5][4];
      uint4 vx[4];
#pragma unroll
      for (int i = 0; i < 5; i++) { s[i][0] = s[i][1] = s[i][2] = s[i][3] = 0.f; }
#pragma unroll
      for (int ks = 0; ks < 4; ks++) {
        const uint32_t* q = qm + 4 * ks;
        if (ks == 1 || ks == 2) {
#pragma unroll
          for (int i = 2 * ks - 2; i < 2 * ks; i++) ldsm4(vx[i].x, vx[i].y, vx[i].z, vx[i].w, ((sb + kv_off) ^ ((i & 1) * 32)) + 8192 + (2 * u + (i >> 1)) * 1024);
        }
        mma16(s[1], q[0], q[1], q[2], q[3], kx[2 * ks].x, kx[2 * ks].y);
        mma16(s[2], q[0], q[1], q[2], q[3], kx[2 * ks].z, kx[2 * ks].w);
        mma16(s[0], q[0], q[1], q[2], q[3], km[2 * ks], km[2 * ks + 1]);
        mma16(s[3], q[0], q[1], q[2], q[3], kx[2 * ks + 1].x, kx[2 * ks + 1].y);
        mma16(s[4], q[0], q[1], q[2], q[3], kx[2 * ks + 1].z, kx[2 * ks + 1].w);
      }
      st_async4(rb + sx + u * 512 + lane * 16, s[1][0], s[1][1], s[2][0], s[2][1], rb + CB_SX);
      st_async1(rb + sx + 1024 + u * 128 + lane * 4, __float_as_uint(u ? s[0][1] : s[0][0]), rb + CB_SX);
      bar_arrive_after<B_S, 256>(__float_as_uint(s[3][0]), __float_as_uint(s[4][0]));
      mbar_wait_step<2>(sb + CB_SX, n);
      const uint4 p0 = lds128(sb + sx + u * 512 + lane * 16), p1 = lds128(sb + sx + (u ^ 1) * 512 + lane * 16);
      const uint2 p2 = make_uint2(lds32(sb + sx + 1024 + lane * 4), lds32(sb + sx + 1152 + lane * 4));
      float t[10] = {s[0][0] + __uint_as_float(p2.x), s[0][1] + __uint_as_float(p2.y),
                     s[1][0] + __uint_as_float(p0.x), s[1][1] + __uint_as_float(p0.y),
                     s[2][0] + __uint_as_float(p0.z), s[2][1] + __uint_as_float(p0.w),
                     s[3][0] + __uint_as_float(p1.x), s[3][1] + __uint_as_float(p1.y),
                     s[4][0] + __uint_as_float(p1.z), s[4][1] + __uint_as_float(p1.w)};
      float mx = fmaxf(fmaxf(fmaxf(fmaxf(t[2], t[3]), fmaxf(t[4], t[5])), fmaxf(fmaxf(t[6], t[7]), fmaxf(t[8], t[9]))), fmaxf(t[0], t[1]));
      mx = fmaxf(fmaxf(mx, __shfl_xor_sync(~0u, mx, 1)), fmaxf(__shfl_xor_sync(~0u, mx, 2), __shfl_xor_sync(~0u, mx, 3)));
      const float ms = -mx * sc;
#pragma unroll
      for (int i = 0; i < 10; i++) t[i] = ex2(fmaf(t[i], sc, ms));
      uint32_t p[5];
#pragma unroll
      for (int i = 0; i < 5; i++) p[i] = pack2(t[2 * i], t[2 * i + 1]);
      p[1] |= (p[0] & p[3] & p[4]) & 0x80008000u;
      float o[2][4], z[4] = {0.f, 0.f, 0.f, 0.f};
      mma16(z, ones, ones, ones, ones, p[1], p[2]);
#pragma unroll
      for (int i = 0; i < 2; i++) {
        o[i][0] = o[i][1] = o[i][2] = o[i][3] = 0.f;
        mma16(o[i], vx[2 * i].x, vx[2 * i].y, vx[2 * i].z, vx[2 * i].w, p[1], p[2]);
      }
      mma16(z, ones, ones, ones, ones, p[3], p[4]);
#pragma unroll
      for (int i = 0; i < 2; i++) mma16(o[i], vx[2 * i + 1].x, vx[2 * i + 1].y, vx[2 * i + 1].z, vx[2 * i + 1].w, p[3], p[4]);
      mma8(z, ones, ones, p[0]);
      bar_sync_after<B_V, 256>(p[1]);
      ldsm4(km[0], km[1], km[2], km[3], kmu + (C_VM - C_KM));
      mma8(o[0], km[0], km[1], p[0]);
      mma8(o[1], km[2], km[3], p[0]);
      const float i0 = rcp(z[0]), i1 = rcp(z[1]);
      const uint32_t oo = C_OI + u * 1024 + l * 128 + lane * 4;
      uint32_t ow[4];
#pragma unroll
      for (int i = 0; i < 2; i++) { ow[2 * i] = pack2(o[i][0] * i0, o[i][1] * i1); ow[2 * i + 1] = pack2(o[i][2] * i0, o[i][3] * i1); }
      stsm4(kmu + (C_OI - C_KM), ow[0], ow[1], ow[2], ow[3]);
      bar_arrive(B_O, 256);
#pragma unroll
      for (int i = 0; i < 4; i++) st_async1(rb + oo + 2048 + i * 256, ow[i], rb + CB_OX);
      }
    }
    {
      const uint32_t lane = opaque_tid() & 31, own = ((n & 1) * 16384 + j * 4096) >> 4;
      float s[16], sm[4], r[16], rm[4];
      {
        uint4 q[4];
        mbar_wait_step<3>(sb + CB_Q, n);
#pragma unroll
        for (int ks = 0; ks < 4; ks++)
          ldsm4t(q[ks].x, q[ks].y, q[ks].z, q[ks].w, sb + C_Q + (lane & 8) * 512 + ks * 1024 + (lane & 16) * 32 + (lane & 7) * 64 + (((w ^ (lane >> 1)) & 3) << 4));
        mbar_wait_step<3>(sb + CB_XX, n);
        if (n + 1 < STEPS) mbar_wait_step<3>(sb + CB_OX, n);
        fence_async_smem();
        if (n + 1 < STEPS) { bar_arrive(B_T, 256); bar_sync(B_OE, 256); }
        if (w == 1) { TRV(61, 0); TR(9); }
        wg_fence();
        x_scores<0>(s, sm, q, own, j * 8);
        x_scores<0>(r, rm, q, (C_KV2 - C_KV) >> 4, (C_KM2 - C_KM) >> 4);
        wg_commit();
        wg_wait<0>();
      }
      const float neg = -1e9f * 11.313708498984761f;
      const int tok = (lane & 24) + 2 * w + ((lane >> 2) & 1), lim = tok - 8 * (int)(lane & 3);
      float t[10] = {sm[0] + rm[2], sm[1] + rm[3]};
#pragma unroll
      for (int i = 0; i < 8; i++) t[2 + i] = i > lim ? neg : s[(i >> 1) * 4 + (i & 1)] + r[(i >> 1) * 4 + (i & 1) + 2];
      float mx = fmaxf(fmaxf(fmaxf(fmaxf(t[2], t[3]), fmaxf(t[4], t[5])), fmaxf(fmaxf(t[6], t[7]), fmaxf(t[8], t[9]))), fmaxf(t[0], t[1]));
      mx = fmaxf(fmaxf(mx, __shfl_xor_sync(~0u, mx, 1)), fmaxf(__shfl_xor_sync(~0u, mx, 2), __shfl_xor_sync(~0u, mx, 3)));
      const float ms = -mx * sc;
#pragma unroll
      for (int i = 0; i < 10; i++) t[i] = ex2(fmaf(t[i], sc, ms));
      uint32_t p[5];
#pragma unroll
      for (int i = 0; i < 5; i++) p[i] = pack2(t[2 * i], t[2 * i + 1]);
      float z = ((t[0] + t[1]) + (t[2] + t[3])) + ((t[4] + t[5]) + (t[6] + t[7])) + (t[8] + t[9]);
      const uint32_t row = sb + C_OS + tok * 128 + (((lane & 3) ^ (tok & 7)) << 4);
      z = rcp((z + __shfl_xor_sync(~0u, z, 1)) + (__shfl_xor_sync(~0u, z, 2) + __shfl_xor_sync(~0u, z, 3)));
      float o[32];
      bar_sync_after<B_WG2, 224>(n + 1 < STEPS ? __float_as_uint(z) : 0xfff12345u);
      wg_fence();
      wg_rs64o<0, desc_sw64(C_KV + 8192)>(o, p[1], 0, p[2], 0, j * 256);
      wg_rs64o<1, desc_sw64(C_KV + 8192 + 32)>(o, p[3], 0, p[4], 0, j * 256);
      wg_rs64o<1, mkdesc(C_VM, 128, 256, 0)>(o, p[0], 0, 0, 0, j * 8);
      wg_rs64o<1, desc_sw64(C_KV2 + 4096)>(o, 0, p[1], 0, p[2], 0);
      wg_rs64o<1, desc_sw64(C_KV2 + 4096 + 32)>(o, 0, p[3], 0, p[4], 0);
      wg_rs64o<1, mkdesc(C_VM2, 128, 256, 0)>(o, 0, p[0], 0, 0, 0);
      wg_commit();
      if (elect()) mbar_arrive(sb + CB_M);
      wg_wait<0>();
#pragma unroll
      for (int i = 0; i < 4; i++) {
        const float* v = o + 16 * (i & 1) + (i & 2);
        sts128((row ^ ((i & 1) * 64)) + (i & 2) * 2048,
               make_uint4(pack2(v[0] * z, v[1] * z), pack2(v[4] * z, v[5] * z), pack2(v[8] * z, v[9] * z), pack2(v[12] * z, v[13] * z)));
      }
      bar_arrive(B_G, 160);
      if (n + 1 < STEPS) bar_arrive(B_R, 160);
      if (w == 1) TR(10);
    }
  }
  if ((threadIdx.x & 127) == 0) TS(6);
}

__device__ __forceinline__ void chain_aux(const Params& P, uint32_t sb) {
  const uint32_t c = chain_id(), j = c & 1, lane = threadIdx.x & 31, w = __shfl_sync(~0u, (threadIdx.x >> 5) & 3, 0);
  load_wg<CHAIN, true>(P, sb, false, 0, w);
  if (threadIdx.x == 384) TS(25);
  if (threadIdx.x == 384) grid_wait(1, lds32(sb + S_GEN));
  bar_sync(B_WG2, 384);
  if (threadIdx.x == 384) TS(13);
  if (w == 0) {
    const uint32_t* fg = g_fl + FL_G + near_half(XB_F, c) * 1024 + (c >> 1) * 8;
#pragma unroll 1
    for (int n = 0; n < STEPS; n++) {
      const unsigned char* blk = g_qkv + (uint32_t)((n % QRING) * (N_CHAIN * 24576));
      const uint32_t t1 = clk(), kb = sb + CB_FULL + (n & 1) * 8, kv = sb + C_KV + (n & 1) * 16384;
      uint32_t t0 = t1 - 100000, x = 0;
      if (n > 0) {
        wait_until(t1, KMIN);
        do asm volatile("ld.relaxed.gpu.global.u32 %0, [%1];" : "=r"(x) : "l"(fg) : "memory"); while (x <= n && clk() - t1 < KWIN);
        if (x > n) {
          asm volatile("fence.acquire.gpu;" ::: "memory");
          fence_async_global();
          if (elect()) { mbar_expect(kb, 8192); bulk_load(kv, blk + c * 24576, 8192, kb); }
        }
        T3(0); CNT(12, 1 + (x <= n));
        mbar_wait(sb + CB_REF, (n - 1) & 1);
        t0 = lds32(sb + C_REF);
        wait_until(t0, DLYV - 500);
      }
      wait_flags(fg + min(lane, 2u) * 256, n + 1);
      T3(2);
      fence_async_global();
      if (n > 0) bar_sync(B_R, 160);
      if (lane < 3) mbar_expect(sb + CB_SX + lane * 8, lane ? 2048 : 2560);
      __syncwarp();
      wait_until(t0, DLYV);
      if (elect()) {
        if (x <= n) { mbar_expect(kb, 8192); bulk_load(kv, blk + c * 24576, 8192, kb); }
        mbar_expect(sb + CB_VF, 8192);
        bulk_load(sb + C_KV + 8192, blk + (c * 24576 + 8192), 8192, sb + CB_VF);
        mbar_expect(sb + CB_Q, 16384);
        wait_until(t0, DLYK);
        bulk_load(sb + C_Q, blk + (c * 24576 + 16384), 8192, sb + CB_Q);
        bulk_load(sb + C_KV2, blk + ((c ^ 1) * 24576 + j * 4096), 4096, sb + CB_Q);
        bulk_load(sb + C_KV2 + 4096, blk + ((c ^ 1) * 24576 + 8192 + j * 4096), 4096, sb + CB_Q);
      }
      T3(1);
      T3(3);
    }
  } else {
    const uint32_t near = __ballot_sync(~0u, near_half(XB_M + min(lane, MRING - 1u) * 8, c));
    uint32_t ring = 0;
    if (w > 1) {
      const uint32_t odd = w & 1, chk = pinned(sb + C_M + odd * 2048 + m_probe(lane)), again = sb + CB_MV + 32 + odd * 8;
      const bool one = elect();
      uint32_t mph = 0;
#pragma unroll 1
      for (int n = 0; n <= STEPS; n++) {
#pragma unroll
        for (int k = 0; k < 3; k++) {
          if (n == STEPS || (k == 2 && odd)) break;
          const uint32_t b = 2 * k + odd, at = chk + (k ? k * 8192 - 2048 + odd * 2048 : 0);
          uint32_t mb = sb + CB_M + b * 8, ph = n & 1;
          int it = 1;
          while (true) {
            mbar_wait(mb, ph);
            const bool bad = __any_sync(~0u, m_max(at, b ? at + 2048 : at) == SENT);
            if (one && !bad) mbar_arrive(sb + CB_MV + (b > 1 ? b * 8 - 8 : 0));
            if (!bad) break;
            mb = again; ph = mph; mph ^= 1;
            if (one) {
              if (k == 0) sts32(sb + C_BAD, n + 1);
              mbar_expect(mb, b ? 4096 : 2048);
              m_fetch(sb, ring * 65536 + ((near >> ring) & 1) * 4096, b, mb);
            }
            __syncwarp();
            spin_guard(it);
          }
          TR(41 + b * 4); CNT(6 + b, it);
        }
        ring = ring + 1 == MRING ? 0 : ring + 1;
        if (!odd) {
          if (n < STEPS) { TRSYNC(); TRDUMP(n - 2); }
        } else {
          unsigned char* o = g_oimg + (uint32_t)(((n - 1) & (RING - 1)) * (N_CHAIN * 8192) + j * 4096);
          if (n > 0) bar_sync(B_G, 160);
          fence_async_smem();
          if (one) {
            if (n > 0) {
              bulk_store(o + c * 8192, sb + C_OS, 4096);
              bulk_store(o + (c ^ 1) * 8192, sb + C_OS + 4096, 4096);
              asm volatile("cp.async.bulk.commit_group;\ncp.async.bulk.wait_group.read 0;" ::: "memory");
              { const int n_ = n - 1; { const int n = n_; T3(4); (void)n; } }
            }
            mbar_arrive(sb + CB_Q);
            if (n > 0) {
              bulk_done_inc(g_fl + FL_O + c);
              { const int n_ = n - 1; { const int n = n_; T3(5); (void)n; } }
            }
          }
          __syncwarp();
        }
      }
    } else {
      const uint32_t* ts = g_fl + FL_SYNC + near_half(XB_F + 1, c) * 1024 + lane * 2;
      uint32_t t0 = clk() - 100000, last = 0;
      int lag = 0;
#pragma unroll 1
      for (int n = 0; n < STEPS; n++) {
        const uint32_t src = ring * 65536 + ((near >> ring) & 1) * 4096;
        if (lane < 5) mbar_expect(sb + CB_M + lane * 8, lane ? 4096 : 2048);
        __syncwarp();
        if (elect()) {
#pragma unroll
          for (int b = 0; b < 5; b++) {
            wait_until(t0, P.dly[14 + b]);
            m_fetch(sb, src, b, sb + CB_M + b * 8);
            TR(40 + b * 4);
          }
        }
        __syncwarp();
        ring = ring + 1 == MRING ? 0 : ring + 1;
        uint32_t va, vb;
        const uint32_t off = timer_offset<4>(), tag = (uint32_t)(n + 1) << 28;
        if (n > 1) lag += (int)(off - last) - (lag >> 2);
        last = off;
        const uint32_t mine = min(max((lag >> 3) + 256, 0), 511);
        bar_sync(B_QK, 416);
        if (n + 1 == STEPS) break;
        sts32(sb + C_REF + 4, 0);
        const uint32_t c0 = clk(), stamp = c0 + off;
        st_relaxed_if(g_fl + FL_SYNC + lane * 1024 + c, tag | (mine << 19) | (stamp & 0x7FFFF), lane < 2);
        TR(13);
        wait_until(c0, DLYS);
        int it = 0;
        do {
          asm volatile("ld.relaxed.gpu.global.v2.u32 {%0,%1}, [%2];" : "=r"(va), "=r"(vb) : "l"(ts) : "memory");
          spin_guard(it);
        } while (__any_sync(~0u, ((va ^ tag) | (vb ^ tag)) >> 28));
        const int late = __reduce_max_sync(~0u, max((int)((va - stamp) << 13), (int)((vb - stamp) << 13))) >> 13;
        const uint32_t fast = min(((__reduce_max_sync(~0u, max(va, vb)) >> 19) & 511) - mine, 100u);
        t0 = c0 + min((uint32_t)late, clk() - c0) + (n < 2 ? P.dly[26 + n] : 0);
        if (elect()) {
          sts32(sb + C_REF, t0 + (fast * 9 >> 3));
          mbar_arrive(sb + CB_REF);
        }
        st_relaxed_if(g_fl + FL_TICK + lane * 1024, (uint32_t)(n + 1) << 24 | ((t0 + off) & 0xFFFFFF), c == 0 && lane < 2);
        t0 += (fast * 13 >> 3) + (n < 2 ? P.dly[28 + n] : 0);
        TRV(59, fast);
        TR(14); CNT(11, it);
        bar_sync(B_M, 160);
      }
    }
  }
}

template <int WG>
__device__ __forceinline__ void g_math(const Params& P, uint32_t sb) {
  const int q = g_unit(WG);
  const int lane = threadIdx.x & 31, w = (threadIdx.x >> 5) & 3;
  uint32_t a[136];
  {
    const uint32_t stage = sb + G_W + WG * 73728;
    mbar_wait(sb + W_BAR + WG * 8, 0);
    if (threadIdx.x == 0) TS(23);
    load_frags<34>(a, stage);
    fence_async_smem();
    bar_sync(B_WG0 + WG, 128);
    if (threadIdx.x == 0) TS(24);
    load_wg<GROLE>(P, sb, false, WG, w);
    if (threadIdx.x == 0) TS(25);
    mbar_wait(sb + W_BAR + WG * 8, 1);
  }
  if ((threadIdx.x & 127) == 0) TS(4);
  const uint32_t off0 = (q & 31) * 49152 + (q >> 5) * 8192 + w * 1024 + (lane >> 2) * 64 + (((lane ^ (lane >> 3)) & 3) << 4);
  const uint32_t isq = q >> 6;
#pragma unroll 1
  for (int n = 0; n < STEPS; n++) {
    float d0[32], d1[32];
    if (WG == 0 && n >= LOCK0) bar_sync(B_OE, 160);
    if (n > 0) bar_sync(B_V + WG, 256);
#pragma unroll
    for (int ch = 0; ch < 9; ch++) {
      mbar_wait(sb + G_BAR + ch * 8, n & 1);
      if (ch == 0) { if ((threadIdx.x & 127) == 0) T3(5 + WG * 3); __syncwarp(); }
      if (ch == 4) { if ((threadIdx.x & 127) == 0) T3(6 + WG * 3); __syncwarp(); }
      if (ch == 8 && (WG == 0 ? n > 0 : n + 1 < STEPS)) bar_arrive(B_V + (WG ^ 1), 256);
      wg_fence();
#pragma unroll
      for (int kk = 0; kk < 4; kk++) {
        const int i = ch * 4 + kk;
        float* d = i & 1 ? d1 : d0;
        const uint64_t db = desc_sw128(G_RING + ch * 8192 + (kk & 2) * 32);
        if (i < 2) wg_rs64<0>(d, a + i * 4, db);
        else if (i < 34) wg_rs64<1>(d, a + i * 4, db);
        else wg_ss64<1>(d, desc_sw128(G_W2 + WG * 4096 + (i - 34) * 2048), db);
        wg_ss64<1>(d, desc_sw128(G_W + WG * 73728 + i * 2048), db + 2);
      }
      wg_commit();
      if (ch > 0) { wg_wait<1>(); if (lane == 0) mbar_arrive(sb + G_BAR + 128 + (ch - 1) * 8); }
    }
    wg_wait<0>();
    if (lane == 0) mbar_arrive(sb + G_BAR + 128 + 8 * 8);
    if ((threadIdx.x & 127) == 0) T3(7 + WG * 3);
    __syncwarp();
    uint32_t tw = clk() + (n == 0 ? 0u - 100000u : WG ? 0u : DLYW);
    unsigned char* base = g_qkv + (size_t)(n & (QRING - 1)) * (N_CHAIN * 24576);
#pragma unroll
    for (int i = 0; i < 8; i++) {
      const float* d = (i < 4 ? d0 : d1) + 8 * (i & 2) + 2 * (i & 1);
      wait_until(tw, 0); tw += P.dly[2 + WG];
      *(uint4*)(base + (off0 + (i < 2 ? 0 : i < 4 ? 4096 + isq * 24576 : i < 6 ? 24576 - isq * 20480 : 28672 - isq * 4096)) + (i & 1) * 512) =
        make_uint4(pack2(d[0], d[1]), pack2(d[4], d[5]), pack2(d[8], d[9]), pack2(d[12], d[13]));
    }
    bar_sync(B_M + WG, 160);
  }
}

__device__ __forceinline__ void fill16(void* p, uint32_t v) {
  asm volatile("st.global.v4.u32 [%0], {%1,%1,%1,%1};" :: "l"(p), "r"(v) : "memory");
}
__device__ __forceinline__ void g_load(const Params& P, uint32_t sb) {
  const int lane = threadIdx.x & 31, w = __shfl_sync(~0u, (threadIdx.x >> 5) & 3, 0);
  if (w == 2) return;
  if (w < 2) { bar_sync(15, 192); fence_async_smem(); }
  uint32_t fl = 0;
#pragma unroll 1
  for (int n = w == 3 ? LOCK0 : 0; n < STEPS; n++) {
    if (w && n == LOCK0) { grid_wait(1, lds32(sb + S_GEN)); fl = near_half(XB_F, bid()) * 1024; }
    if (w == 3) {
      const uint32_t tag = (uint32_t)(n - LOCK0 + 1) << 24;
      uint32_t v; int it = 0;
      do { asm volatile("ld.relaxed.gpu.global.u32 %0, [%1];" : "=r"(v) : "l"(g_fl + fl + FL_TICK) : "memory"); spin_guard(it); } while (v < tag);
      const uint32_t off = timer_offset<2>(), now = clk(), t0 = now - ((v ^ tag) >> 24 ? DLYG : (now + off - v) & 0xFFFFFF);
      asm volatile("fence.acquire.gpu;" ::: "memory");
      if (lane == 0) T3(11);
      __syncwarp();
      wait_until(t0, DLYG);
      if (lane == 0) T3(4);
      bar_sync(B_OE, 160);
      continue;
    }
    if (w == 0 || n == 0) {
      if (n < NSEG) wait_flags(g_lnflag + n * 16 + (lane & 1) * 8, 1);
    } else if (n >= LAG) {
      wait_flags(g_fl + fl + FL_F + (lane & 1) * 8, n - LAG + 1);
    }
    if (w) { if (lane == 0) T3(12); bar_sync(B_X, 96); }
    fence_async_global();
    const unsigned char* src = g_lnimg + (uint32_t)((w ? (n >= LAG ? NSEG + n - LAG : 0) : min(n, NSEG - 1)) * 36864);
#pragma unroll 1
    for (int ch = 0; ch < 9; ch++) {
      const uint32_t full = sb + G_BAR + ch * 8;
      mbar_wait(full + 128, (n & 1) ^ 1);
      if (elect()) {
        mbar_expect(full, 4096);
        bulk_load(sb + G_RING + ch * 8192 + w * 4096, src + ch * 4096, 4096, full);
      }
    }
  }
}

__device__ __forceinline__ void g_aux(const Params& P, uint32_t sb) {
  const int lane = threadIdx.x & 31, w = (threadIdx.x >> 5) & 3;
  if (w == 1 || w == 2) {
    const int q = g_unit(w - 1);
    uint32_t* f = g_fl + FL_G + q * 8;
#pragma unroll 1
    for (int n = 0; n < STEPS; n++) {
      const uint32_t ln = opaque_tid() & 31;
      uint4* z = (uint4*)g_oacc + (uint32_t)(((n + 1) % ARING) * (16 * DM) + q * 96 + ln);
      fill16(z, 0); fill16(z + 32, 0); fill16(z + 64, 0);
      if (n + 3 >= MRING && q < 80) fill16((uint4*)g_mimg + (uint32_t)(((n + 3) % MRING) * 4096 + q * 32 + ln), SENT);
      bar_sync(B_M + (w - 1), 160);
      if (lane == 0) { T3(w * 2 - 2); fence_async_global(); flag_release(f, n + 1); T3(w * 2 - 1); }
      __syncwarp();
    }
  } else {
    const uint32_t u = (bid() - N_CHAIN) * 2 + (w & 1), r = u / 36 * 16 + (u & 3) * 4 + (lane >> 3);
    uint32_t o = r * (DM / 8) + (u % 36 >> 2) * 8 + ((lane & 7) ^ ((r >> 1) & 3)), fl = 0;
#pragma unroll 1
    for (int k = -LAG - 1; k < STEPS; k++) {
      if (k < NSEG - 1) bar_sync(B_X, 96);
      if (k < LAG || u >= 72) continue;
      if (k == NSEG - 1) { fl = near_half(XB_F, bid()) * 1024; wait_flags(g_fl + fl + FL_F + (lane & 1) * 8, NSEG + 1); }
      const uint4 x = __ldcg((const uint4*)P.out + o);
      if (k >= NSEG - 1) wait_flags(g_fl + fl + FL_OCNT + (max(k, NSEG) % OCRING) * 8, N_O * 3 * (max(k, NSEG) / OCRING + 1));
      const float4* a = (const float4*)g_oacc + ((k % ARING) * (16 * DM) + 8 * DM + u * 64 + lane * 2);
      const float4 p = __ldcg(a), v = __ldcg(a + 1);
      ((uint4*)P.out)[o] = make_uint4(badd2(x.x, pack2(p.x, p.y)), badd2(x.y, pack2(p.z, p.w)), badd2(x.z, pack2(v.x, v.y)), badd2(x.w, pack2(v.z, v.w)));
      o += 4 * DM;
    }
    if ((threadIdx.x & 127) == 0) TS(7);
  }
}

template <int WG, bool HALF, int KS, int N> __device__ __forceinline__ void o_mma(float* d, const uint32_t* a, uint32_t ob) {
  constexpr uint64_t db = desc_sw128(O_RING + (KS >> 2) * 8192 + (KS & 3) * 32);
  constexpr uint64_t da = desc_sw128(O_W + WG * 40960 + (KS < 40 ? KS / 5 * 2 + KS % 5 / 2 : KS - 24) * 2048);
  if constexpr (KS < 40 && !(KS % 5 & 1)) {
    const uint32_t* r = a + (KS / 5 * 3 + KS % 5 / 2) * 4;
    if constexpr (HALF) wg_rs32k<KS != 0, db>(d, r[0], r[1], r[2], r[3], ob); else wg_rs64<KS != 0>(d, r, db);
  } else {
    if constexpr (HALF) wg_ss32k<da, db>(d, ob); else wg_ss64<1>(d, da, db);
  }
  if constexpr (N > 1) o_mma<WG, HALF, KS + 1, N - 1>(d, a, ob);
}
template <int WG, bool HALF, int GR> __device__ __forceinline__ void o_groups(float* d, const uint32_t* a, uint32_t sb, int n, bool more) {
  const uint32_t ob = n < NSEG ? 0 : 256;
  mbar_wait(sb + O_BAR + GR * 8, n & 1);
  if (GR == 0) { if ((threadIdx.x & 127) == 0) T3(13 + WG); __syncwarp(); }
  if (GR == 3 && (WG < 2 || n + 1 < STEPS)) bar_arrive(B_V + (WG + 1) % 3, 256);
  wg_fence();
  o_mma<WG, HALF, GR * 8, 8>(d, a, ob);
  if (GR == 4 && more) o_mma<WG, HALF, 40, 4>(d, a, ob);
  wg_commit();
  if (GR > 0) { wg_wait<1>(); if ((threadIdx.x & 31) == 0) mbar_arrive(sb + O_BAR + 120 + GR * 8); }
  if constexpr (GR < 4) o_groups<WG, HALF, GR + 1>(d, a, sb, n, more);
}
template <int WG, bool HALF> __device__ __forceinline__ void o_step(const uint32_t* a, uint32_t sb, uint32_t st0, int n, bool more) {
  float d[HALF ? 16 : 32];
  if (WG > 0 || n > 0) bar_sync(B_V + WG, 256);
  o_groups<WG, HALF, 0>(d, a, sb, n, more);
  wg_wait<0>();
  if ((threadIdx.x & 31) == 0) mbar_arrive(sb + O_BAR + 128 + 4 * 8);
  if ((threadIdx.x & 127) == 0) T3(WG == 0 ? 1 : WG == 1 ? 8 : 12);
  __syncwarp();
#pragma unroll(HALF ? 1 : 2)
  for (int sl = 0; sl < 2; sl++) {
    mbar_wait(sb + OB_ST + WG * 16 + sl * 8, (n & 1) ^ (WG == 0));
    if (!HALF || sl == (n >= NSEG)) {
#pragma unroll
      for (int nb = 0; nb < 4; nb++) {
        const float* r = d + (HALF ? 0 : sl * 16) + nb * 4;
        const uint32_t ad = st0 + sl * 8192 + nb * 2048;
        sts32(ad, __float_as_uint(r[0]));
        sts32(ad + 256, __float_as_uint(r[1]));
        sts32(ad ^ 32, __float_as_uint(r[2]));
        sts32((ad ^ 32) + 256, __float_as_uint(r[3]));
      }
      fence_async_smem();
    }
    bar_arrive((sl ? B_G : B_M) + WG, 160);
  }
}
template <int WG>
__device__ __forceinline__ void o_math(const Params& P, uint32_t sb) {
  const bool more = bid() < N_CHAIN + N_G + 12;
  const int lane = threadIdx.x & 31, w = (threadIdx.x >> 5) & 3, g = lane >> 2, tq = lane & 3;
  uint32_t a[96];
  mbar_wait(sb + W_BAR + WG * 8, 0);
  load_frags<24>(a, sb + WG * 49152);
  fence_async_smem();
  bar_sync(B_INIT, 416);
  load_wg<OROLE>(P, sb, false, WG, w);
  mbar_wait(sb + W_BAR + WG * 8, 1);
  if ((threadIdx.x & 127) == 0) TS(4);
  const uint32_t st0 = sb + O_ST + tq * 512 + ((w * 16 + g) ^ (tq * 8)) * 4;
#pragma unroll 1
  for (int n = 0; n < STEPS; n++) {
    if (n < LAG || n >= NSEG) o_step<WG, true>(a, sb, st0, n, more); else o_step<WG, false>(a, sb, st0, n, more);
  }
}

__device__ __forceinline__ void o_aux(const Params& P, uint32_t sb) {
  const int i = bid() - N_CHAIN - N_G, ksl = i / 3;
  const int c0 = ksl * 11 - max(ksl - 4, 0), nc = ksl < 4 ? 11 : 10;
  const int lane = threadIdx.x & 31, w = __shfl_sync(~0u, (threadIdx.x >> 5) & 3, 0);
  if (w == 0) {
    bar_sync(B_INIT, 416);
    const uint32_t* f = g_fl + FL_O + near_half(XB_F + 1, bid()) * 1024 + min((c0 & ~1) + lane, (c0 + nc - 1) | 1);
#pragma unroll 1
    for (int n = 0; n < STEPS; n++) {
      const unsigned char* src = g_oimg + (uint32_t)(((n % RING) * N_CHAIN + c0) * 8192);
      wait_flags(f, n + 1);
      if (n >= LAG && n < NSEG) wait_until(clk(), DLYO);
      fence_async_global();
      if (lane == 0) T3(0);
#pragma unroll
      for (int gr = 0; gr < 5; gr++) {
        const uint32_t full = sb + O_BAR + gr * 8, bytes = (gr < 4 ? 2 : nc - 8) * 8192;
        mbar_wait(full + 128, (n & 1) ^ 1);
        if (elect()) {
          if (n < LAG || n >= NSEG) {
            mbar_expect(full, bytes >> 1);
            for (uint32_t o = gr * 16384 + (n < LAG ? 0 : 4096); o < gr * 16384 + bytes; o += 8192) bulk_load(sb + O_RING + o, src + o, 4096, full);
          } else {
            mbar_expect(full, bytes);
            bulk_load(sb + O_RING + gr * 16384, src + gr * 16384, bytes, full);
          }
        }
      }
    }
  } else {
#pragma unroll 1
    for (int n = 0; n < STEPS; n++) {
      float* dst = g_oacc + (uint32_t)((n % ARING) * (64 * DM) + ((i % 3) * 3 + (w - 1 + ksl) % 3) * 1024);
      const bool early = w == 3 && n < NSEG;
      bar_sync(B_M + (w - 1), 160);
      if (lane == 0) {
        T3(w * 2);
        if (n < NSEG) { bulk_reduce(dst, sb + O_ST, 4096); bulk_reduce(dst + 16 * DM, sb + O_ST + 4096, 4096); }
        asm volatile("cp.async.bulk.commit_group;" ::: "memory");
        if (early) {
          asm volatile("cp.async.bulk.wait_group.read 0;" ::: "memory");
          mbar_arrive(sb + OB_ST);
          T3(8 + w);
          bulk_done_inc(g_fl + FL_OCNT + (n % OCRING) * 8);
          T3(w * 2 + 1);
        }
      }
      __syncwarp();
      bar_sync(B_G + (w - 1), 160);
      if (lane == 0) {
        if (n >= LAG) { bulk_reduce(dst + 32 * DM, sb + O_ST + 8192, 4096); bulk_reduce(dst + 48 * DM, sb + O_ST + 12288, 4096); }
        asm volatile("cp.async.bulk.commit_group;\ncp.async.bulk.wait_group.read 1;" ::: "memory");
        if (!early) mbar_arrive(sb + OB_ST + (w % 3) * 16);
        asm volatile("cp.async.bulk.wait_group.read 0;" ::: "memory");
        mbar_arrive(sb + OB_ST + (w % 3) * 16 + 8);
        if (!early) {
          T3(8 + w);
          bulk_done_inc(g_fl + FL_OCNT + (n % OCRING) * 8);
          T3(w * 2 + 1);
        }
      }
      __syncwarp();
    }
  }
}

constexpr uint32_t Y_PITCH = 1168, Y_ROWS = 16 * Y_PITCH;
template <int R> __device__ __forceinline__ void y_rows(uint32_t* y, uint32_t src, uint32_t dst, int w, int bar) {
  const int lane = threadIdx.x & 31;
#pragma unroll
  for (int k = 0; k < 2 * R + 1; k++) {
    const int op = w + k * (16 / R);
    if (k == 2 * R && w >= 4) break;
    uint32_t a, b, c, d;
    ldsm4t(a, b, c, d, src + op * 512 + (lane & 16) * 16 + (lane & 7) * 32 + (lane & 8) * 2);
    stsm4(dst + (lane & 15) * Y_PITCH + op * 32 + (lane & 16), a, b, c, d);
  }
  bar_sync(bar, 512 / R);
  const uint32_t row = dst + ((w & 6) * 2 + (w >> 3) * 2 + (w & 1)) * Y_PITCH + lane * 4;
#pragma unroll
  for (int i = 0; i < 9 * R; i++) y[i] = lds32(row + i / 9 * 2 * Y_PITCH + i % 9 * 128);
}

__device__ __forceinline__ void f_role(const Params& P, uint32_t sb) {
  const int lane = threadIdx.x & 31, w = __shfl_sync(~0u, threadIdx.x >> 5, 0), r0 = (bid() - N_CHAIN - N_G - N_O) * 16;
  if (w == 8) {
    const uint32_t* fo = g_fl + FL_OCNT + near_half(XB_F, bid()) * 1024;
    fence_async_global();
#pragma unroll 1
    for (int n = 0; n < NSEG; n++) {
      bar_sync(2, 288);
      if (elect()) {
        mbar_expect(sb + F_BAR, 36864);
        bulk_load(sb + F_XY, P.X + (size_t)(n * 32 + r0) * DM, 18432, sb + F_BAR);
        bulk_load(sb + F_XY + 18432, g_yT + (size_t)(n * 32 + r0) * DM, 18432, sb + F_BAR);
        mbar_expect(sb + F_BAR + 8, 36864);
        T3(1);
      }
      wait_flags(fo + (n % OCRING) * 8, N_O * 3 * (n / OCRING + 1));
      fence_async_global();
      if (elect()) { bulk_load(sb + F_A, g_oacc + (uint32_t)((n % ARING) * (64 * DM) + r0 * DM), 36864, sb + F_BAR + 8); T3(0); }
    }
  } else if (w == 9) {
#pragma unroll 1
    for (int n = 0; n < NSEG; n++) {
      const uint32_t st = sb + (n & 1) * 36864;
      unsigned char* p = g_lnimg + (uint32_t)((NSEG + n) * 36864 + r0 * 128);
      bar_sync(1, 288);
      if (elect()) {
        T3(2);
#pragma unroll
        for (int i = 0; i < 9; i++) bulk_store(p + i * 4096, st + F_L + i * 2048, 2048);
        asm volatile("cp.async.bulk.commit_group;" ::: "memory");
        bulk_done_inc(g_fl + FL_F + (bid() & 1) * 8);
        T3(3);
        bulk_store(P.out + (size_t)(n * 32 + r0) * DM, st + F_X, 18432);
        asm volatile("cp.async.bulk.commit_group;\ncp.async.bulk.wait_group.read 0;" ::: "memory");
        if (n + 1 == NSEG) bulk_done_inc(g_fl + FL_F + (bid() & 1) * 8);
      }
      __syncwarp();
    }
  } else if (w < 8) {
    const uint32_t row = sb + w * 1152 + lane * 4, acc = sb + F_A + w * 256 + (lane ^ ((w & 6) * 2)) * 8;
    const uint32_t ln = sb + F_L + w * 128 + (((lane >> 2) ^ w) << 4) + (lane & 3) * 4;
#pragma unroll 1
    for (int n = -1; n < NSEG; n++) {
      const uint32_t st = (n & 1) * 36864;
      uint32_t x[18], y[18], l[18];
      if (n >= 0) mbar_wait(sb + F_BAR, n & 1);
#pragma unroll
      for (int i = 0; i < 18; i++) x[i] = lds32(row + F_XY + i / 9 * 9216 + i % 9 * 128);
      y_rows<2>(y, sb + F_XY + 18432, sb + F_Y, w, 3);
      layernorm9<2>(x, l);
#pragma unroll
      for (int i = 0; i < 18; i++) x[i] = badd2(x[i], bmul2(l[i], y[i]));
      if (n >= 0) mbar_wait(sb + F_BAR + 8, n & 1);
      if (threadIdx.x == 0 && n >= 0) T3(4);
      __syncwarp();
      uint2 a[18];
#pragma unroll
      for (int i = 0; i < 18; i++) a[i] = lds64(acc + i / 9 * 2048 + i % 9 * 4096);
#pragma unroll
      for (int i = 0; i < 18; i++) x[i] = badd2(x[i], pack2(__uint_as_float(a[i].x), __uint_as_float(a[i].y)));
      if (n + 1 < NSEG) bar_arrive(2, 288);
      layernorm9<2>(x, l);
#pragma unroll
      for (int i = 0; i < 18; i++) { x[i] = badd2(x[i], bmul2(l[i], y[i])); sts32(row + st + F_X + i / 9 * 9216 + i % 9 * 128, x[i]); }
      layernorm9<2>(x, l);
#pragma unroll
      for (int i = 0; i < 18; i++) sts32(ln + st + i / 9 * 1024 + i % 9 * 2048, l[i]);
      fence_async_smem();
      if (n >= 0) bar_sync(1, 288); else bar_sync(3, 256);
    }
  }
}

constexpr uint32_t P_CH = 147456, P_CHSZ = 12800, P_H = 4352;
static_assert(P_CH + 6 * P_CHSZ <= G_BAR, "prologue smem");

template <int N>
__device__ __forceinline__ void conv_fold(float (*acc)[4], bool hi, uint32_t mine, uint32_t theirs, int bar, int cnt) {
#pragma unroll
  for (int i = 0; i < N / 2; i++) {
    uint4 v;
    v.x = __float_as_uint(hi ? acc[i][0] : acc[i + N / 2][0]); v.y = __float_as_uint(hi ? acc[i][1] : acc[i + N / 2][1]);
    v.z = __float_as_uint(hi ? acc[i][2] : acc[i + N / 2][2]); v.w = __float_as_uint(hi ? acc[i][3] : acc[i + N / 2][3]);
    sts128(mine + i * 512, v);
  }
  bar_sync(bar, cnt);
#pragma unroll
  for (int i = 0; i < N / 2; i++) {
    const uint4 v = lds128(theirs + i * 512);
    acc[i][0] = (hi ? acc[i + N / 2][0] : acc[i][0]) + __uint_as_float(v.x); acc[i][1] = (hi ? acc[i + N / 2][1] : acc[i][1]) + __uint_as_float(v.y);
    acc[i][2] = (hi ? acc[i + N / 2][2] : acc[i][2]) + __uint_as_float(v.z); acc[i][3] = (hi ? acc[i + N / 2][3] : acc[i][3]) + __uint_as_float(v.w);
  }
}
template <int N>
__device__ __forceinline__ void conv_store(const float (*acc)[4], int tile0, uint32_t su, int d, uint32_t dd) {
  const int lane = threadIdx.x & 31, g = lane >> 2, tq = lane & 3;
#pragma unroll
  for (int i = 0; i < N; i++) {
    const uint32_t ad = su + (8 + (tile0 + i) * 8 + g) * 32 + tq * 4, sw = (g & 4) << 2;
    const uint32_t lo = badd2(movmat(pack2(acc[i][0], acc[i][1])), bmul2(lds32(ad + sw), dd));
    const uint32_t hi = badd2(movmat(pack2(acc[i][2], acc[i][3])), bmul2(lds32(ad + (sw ^ 16)), dd));
    ((uint2*)g_yT)[(((tile0 + i) * 8 + g) * DM + d) * 4 + tq] = make_uint2(lo, hi);
  }
}

__device__ __forceinline__ void prologue(const Params& P, uint32_t sb) {
  const int b = bid(), tid = threadIdx.x, lane = tid & 31, warp = tid >> 5, t0 = b * 16;
  const bool isg = b >= N_CHAIN && b < N_CHAIN + N_G;
  const int nch = isg ? 2 : b < 128 ? 6 : 0, chb = b < N_CHAIN ? b * 6 : isg ? b * 2 + 256 : b * 6 - 192;
  const uint32_t tstart = clk();
  if (tid < 288) {
    if (b < 128) {
      const int c = (tid >> 1) * 4, tt = t0 + (tid & 1) * 8;
      uint2 kr[11], vr[8];
#pragma unroll
      for (int i = 0; i < 11; i++) { const int t = tt + i - 3; kr[i] = t >= 0 ? __ldg((const uint2*)(P.K + (size_t)t * DM + c)) : make_uint2(0, 0); }
#pragma unroll
      for (int i = 0; i < 8; i++) vr[i] = __ldg((const uint2*)(P.V + (size_t)(tt + i) * DM + c));
#pragma unroll
      for (int e = 0; e < 2; e++) {
        const uint4 sh = __ldg((const uint4*)(P.shift + c * 4) + e);
        const uint32_t s0 = __byte_perm(sh.x, sh.z, 0x5410), s1 = __byte_perm(sh.x, sh.z, 0x7632);
        const uint32_t s2 = __byte_perm(sh.y, sh.w, 0x5410), s3 = __byte_perm(sh.y, sh.w, 0x7632);
        uint32_t v[8];
#pragma unroll
        for (int i = 0; i < 8; i++) {
          const uint32_t k3 = e ? kr[i].y : kr[i].x, k2 = e ? kr[i + 1].y : kr[i + 1].x, k1 = e ? kr[i + 2].y : kr[i + 2].x, k0 = e ? kr[i + 3].y : kr[i + 3].x;
          v[i] = bmul2(badd2(badd2(badd2(bmul2(k3, s3), bmul2(k2, s2)), bmul2(k1, s1)), bmul2(k0, s0)), e ? vr[i].y : vr[i].x);
        }
        *(uint4*)(g_kvT + (size_t)(c + 2 * e) * KVP + tt) =
          make_uint4(__byte_perm(v[0], v[1], 0x5410), __byte_perm(v[2], v[3], 0x5410), __byte_perm(v[4], v[5], 0x5410), __byte_perm(v[6], v[7], 0x5410));
        *(uint4*)(g_kvT + (size_t)(c + 2 * e + 1) * KVP + tt) =
          make_uint4(__byte_perm(v[0], v[1], 0x7632), __byte_perm(v[2], v[3], 0x7632), __byte_perm(v[4], v[5], 0x7632), __byte_perm(v[6], v[7], 0x7632));
      }
    }
  } else if (tid < 384) {
    const int t = tid - 288;
    for (int i = b * 96 + t; i < 16 * DM; i += N_CTA * 96) ((uint4*)g_oacc)[i] = make_uint4(0, 0, 0, 0);
    if (b * 96 + t < 128 * 8) g_lnflag[b * 96 + t] = 0;
    if (t == 95) sts32(sb + S_GEN, ld_acquire(g_gbar));
    __syncwarp();
    wait_until(tstart, PREFH);
    for (int i = t; i < 32 * nch; i += 96) asm volatile("prefetch.global.L2 [%0];" :: "l"(P.Hk + (size_t)chb * SEQ + i * 64));
  }
  if (warp < 12) {
    bar_arrive(10, 416);
    if (tid == 128) TS(14);
    const int ch = 5 - (warp >> 1), sub = warp & 1, d = chb + ch;
    const uint32_t su = sb + P_CH + ch * P_CHSZ;
    if (ch < nch) {
      const uint32_t* hs = (const uint32_t*)(P.Hk + (size_t)d * SEQ);
#pragma unroll
      for (int q = sub * 32 + lane; q < 256; q += 64) {
        const uint4 c = __ldg((const uint4*)hs + q);
        const uint32_t prev = q ? __ldg(hs + 4 * q - 1) : 0u;
        sts128(su + P_H + 32 + q * 16, make_uint4(__byte_perm(c.x, prev, 0x7610), __byte_perm(c.y, c.x, 0x7610), __byte_perm(c.z, c.y, 0x7610), __byte_perm(c.w, c.z, 0x7610)));
        sts128(su + P_H + 4224 + q * 16, make_uint4(__byte_perm(c.x, 0, 0x1032), __byte_perm(c.y, 0, 0x1032), __byte_perm(c.z, 0, 0x1032), __byte_perm(c.w, 0, 0x1032)));
      }
      if (sub == 1 && lane == 0) sts32(su + P_CHSZ - 16, __bfloat16_as_ushort(P.Dk[d]) * 0x10001u);
      if (sub == 0 && lane < 20) sts128(su + (lane < 16 ? lane * 16 : P_H + (lane & 2) * 2096 + (lane & 1) * 16), make_uint4(0, 0, 0, 0));
    }
    bar_sync(11, 416);
    if (ch < nch) {
#pragma unroll
      for (int q = sub * 32 + lane; q < 256; q += 64) {
        const int row = (q >> 1) + 8;
        sts128(su + row * 32 + (((q & 1) ^ ((row >> 2) & 1)) << 4), __ldcg((const uint4*)(g_kvT + (size_t)d * KVP) + q));
      }
    }
    const int g = lane >> 2, tq = lane & 3;
    const uint32_t sh = su + P_H + (g & 1) * 4192 + (8 + (g >> 1) - tq) * 4;
    float acc[16][4];
#pragma unroll
    for (int i = 0; i < 16; i++) { acc[i][0] = acc[i][1] = acc[i][2] = acc[i][3] = 0.f; }
    auto u_addr = [&](int res) {
      const int row = 8 - res + ((lane >> 4) << 3) + (lane & 7);
      return su + row * 32 + ((((lane >> 3) & 1) ^ ((row >> 2) & 1)) << 4);
    };
    if (ch < nch) {
      bar_sync(1 + ch, 64);
      if (tid == 352) TS(11);
      if (sub) {
#pragma unroll 4
        for (int res = 0; res < 8; res++) {
          uint32_t b0, b1, b2, b3;
          ldsm4(b0, b1, b2, b3, u_addr(res));
          const uint32_t r0 = lds32(sh + res * 32);
          mma16(acc[0], r0, lds32(sh + res * 32 + 16), lds32(sh + res * 32 - 16), r0, b0, b1);
        }
        conv_store<1>(acc, 0, su, d, lds32(su + P_CHSZ - 16));
      }
    }
    bar_arrive(12, 416);
    if (isg && warp < 8) { while ((int)(clk() - tstart - S1G) < 0) __nanosleep(200); load_wg<GROLE>(P, sb, true, warp >> 2, warp & 3); }
    if (ch < nch) {
#pragma unroll 1
      for (int res = sub * 4; res < sub * 4 + 4; res++) {
        uint32_t bf[16][2];
        const uint32_t ad = u_addr(res);
#pragma unroll
        for (int f = 0; f < 16; f += 2) ldsm4(bf[f][0], bf[f][1], bf[f + 1][0], bf[f + 1][1], ad + f * 256);
#pragma unroll
        for (int k = 0; k < 16; k++) {
          const int jj = k & 1 ? k >> 1 : 15 - (k >> 1);
          const uint32_t ah = sh + (8 * jj + res) * 32;
          const uint32_t r0 = lds32(ah), r1 = lds32(ah + 16), rm = lds32(ah - 16);
#pragma unroll
          for (int i = max(jj, 1); i < 16; i++) mma16(acc[i], r0, r1, rm, r0, bf[i - jj][0], bf[i - jj][1]);
        }
      }
      bar_sync(1 + ch, 64);
      if (tid == 352) TS(12);
      const uint32_t xb = su + P_H + lane * 16, dd = lds32(su + P_CHSZ - 16);
      conv_fold<16>(acc, sub, xb + sub * 4096, xb + (sub ^ 1) * 4096, 1 + ch, 64);
      conv_store<8>(acc, sub * 8, su, d, dd);
    }
  } else {
    for (int i = b; i < 194 + MRING * 5; i += N_CTA) {
      const int n = (i - 194) / 5, r = (i - 194) % 5, blk = i < 192 ? i / 6 * 8 + i % 6 : i < 194 ? XB_F + i - 192 : XB_M + n * 8 + r;
      const uint32_t fill = i < 194 ? 0u : SENT;
#pragma unroll 1
      for (int q = tid - 384; q < 256 && warp < 15; q += 96) {
        uint4 v = make_uint4(fill, fill, fill, fill);
        if (i >= 194 && n == 0 && (r > 0 || q < 128)) {
          const bf16* m = P.mem0 + (max(r * 8 - 4, 0) + (q >> 5)) * 16 + ((q >> 1) & 1) * 8 + ((q >> 2) & 7);
          v.x = pack2(__bfloat162float(m[0]), __bfloat162float(m[DM])); v.y = pack2(__bfloat162float(m[2 * DM]), __bfloat162float(m[3 * DM]));
          v.z = pack2(__bfloat162float(m[4 * DM]), __bfloat162float(m[5 * DM])); v.w = pack2(__bfloat162float(m[6 * DM]), __bfloat162float(m[7 * DM]));
        }
        g_xb[blk * 512 + q] = v;
        g_xb[blk * 512 + 256 + q] = v;
      }
    }
    if (tid < 388) g_xb[XB_REF * 512 + (tid & 2) * 128 + (b & ~1) + (tid & 1)] = make_uint4(0, 0, 0, 0);
    else if (tid < 392 && b < N_GRP) g_xb[(b * 8 + 7) * 512 + (tid & 2) * 128 + (tid & 1)] = make_uint4(0, 0, 0, 0);
    if (warp < 15) { bar_arrive(9, 128); bar_sync(7, 96); }
    if (tid == 384) TS(8);
    if (warp == 12) {
      const bf16* w = lane < 6 ? (lane % 3 == 0 ? P.Wk : lane % 3 == 1 ? P.Wv : P.Wq) + (((b >> 5) * 2 + lane / 3) * 32 + (b & 31)) * 2048
                               : (lane < 8 ? P.Wo + (lane - 6) * (9 * 131072) : P.X) + b * 2048;
      uint32_t t = tstart + PREF0;
      if ((int)(clk() - t) > 0) t = clk();
#pragma unroll 1
      for (int st = 0; st < 9 && b < N_CHAIN; st++) {
#pragma unroll 1
        for (int i = 0; i < 9; i++, t += PACE) {
          wait_until(t, 0);
          if (lane == st) asm volatile("cp.async.bulk.prefetch.L2.global [%0], 4096;" :: "l"(w + i * (lane < 6 ? 262144 : 131072)) : "memory");
        }
      }
      if (lane == 0) TS(10);
    } else if (warp == 15) {
      bar_sync(10, 416);
      if (lane == 0) { grid_arrive(0); if (nch) grid_wait(0, lds32(sb + S_GEN)); }
      __syncwarp();
      bar_arrive(11, 416);
      if (lane == 0) TS(1);
      bar_sync(9, 128);
      bar_sync(12, 416);
      if (lane == 0) { TS(16); grid_arrive(2); TS(17); }
    } else if (lane == 0) {
      if (warp == 13 || (warp == 14 && b < N_GRP)) {
        uint32_t* p = (uint32_t*)(g_xb + (warp == 13 ? XB_REF * 512 + b : (b * 8 + 7) * 512));
        int votes = 0;
        for (int rep = 0; rep < 24 && abs(votes) < 7; rep++) {
          uint32_t v0, v1, c0, c1;
          asm volatile("atom.relaxed.gpu.global.add.u32 %0, [%4], 1;\n atom.relaxed.gpu.global.add.u32 %1, [%5], 1;\n"
                       "{.reg .pred p; setp.eq.u32 p, %0, 0x7ffffff3; @p trap; mov.u32 %2, %%clock; setp.eq.u32 p, %1, 0x7ffffff3; @p trap; mov.u32 %3, %%clock;}"
                       : "=&r"(v0), "=&r"(v1), "=&r"(c0), "=&r"(c1) : "l"(p + (rep & 1) * 1024), "l"(p + ((rep & 1) ^ 1) * 1024) : "memory");
          votes += ((c1 - c0 > 80u) == (rep & 1)) ? 1 : -1;
        }
        if (warp == 13) { g_side[b] = votes > 0; TS(9); } else g_near[b] = votes > 0;
      }
    }
    __syncwarp();
    if (warp > 12 && b < N_CHAIN) {
      while ((int)(clk() - tstart - S1DLY) < 0) __nanosleep(200);
      for (int k = warp - 13; k < 8; k += 3) load_wg<CHAIN>(P, sb, true, 1 - k / 4, k & 3);
    }
  }
  if (b < N_CHAIN + N_G && (warp < 8 || (isg && warp >= 12))) bar_arrive(0, 512); else bar_sync(0, 512);
  if (tid == 352) TS(2);
}

__device__ __forceinline__ void publish_y() {
  if (threadIdx.x == 383) { grid_arrive(1); TS(18); }
  __syncwarp();
}

template <int R> __device__ __forceinline__ void ln_tiles(const Params& P, uint32_t sb) {
  const int lane = threadIdx.x & 31, w = (threadIdx.x >> 5) & (16 / R - 1), half = R == 1 ? 0 : threadIdx.x >> 8, u = N_CTA - 1 - bid();
  const int first = R == 1 ? u : 46 - 2 * u + half, step = R == 1 ? 4 : 40, last = R == 1 ? 8 : 128;
  const uint32_t raw = sb + P_CH + half * (18432 + Y_ROWS), mb = sb + T_BAR + (R - 1 + half) * 8;
  const bool lead = w == 16 / R - 1 && lane == 0;
  auto load_y = [&](const bf16* src, int tile) {
    fence_async_global();
    mbar_expect(mb, 18432);
    bulk_load(raw, src + (size_t)tile * 16 * DM, 18432, mb);
  };
  uint32_t nx[9 * R];
  auto load_x = [&](int tile) {
#pragma unroll
    for (int i = 0; i < 9 * R; i++) nx[i] = __ldg((const uint32_t*)(P.X + (size_t)(tile * 16 + w + i / 9 * 8) * DM) + i % 9 * 32 + lane);
  };
  load_x(first);
  if (R == 2) {
    if (lead) { grid_wait(1, lds32(sb + S_GEN)); if (u > 3) TS(13); load_y(g_yT, first); }
    __syncwarp();
  }
#pragma unroll 1
  for (int tile = first, real = R - 1, ph = 0; tile < last; tile += real * step, real = 1, ph ^= 1) {
    uint32_t x[9 * R], l[9 * R], y[9 * R];
    const bool ts = threadIdx.x == 0 && (R == 1 ? tile == first : u > 3 && tile == first + step);
    if (ts) TS(26);
#pragma unroll
    for (int i = 0; i < 9 * R; i++) x[i] = nx[i];
    layernorm9<R>(x, l);
    if (real && tile + step < last) load_x(tile + step);
    if (R == 2 && tile == first + step && u >= N_F && w < 6) load_wg<OROLE>(P, sb, true, w >> 1, half * 2 + (w & 1));
    if (R == 1 && tile == first && lead) {
      if (real) grid_wait(2, lds32(sb + S_GEN));
      TS(13);
      load_y(real ? g_yT : P.Hk, tile);
    }
    bar_sync(13 + half, 512 / R);
    mbar_wait(mb, ph);
    if (ts) TS(28);
    y_rows<R>(y, raw, raw + 18432, w, 13 + half);
    if (ts) TS(29);
    if (lead && real && tile + step < last) { fence_async_smem(); load_y(g_yT, tile + step); }
    __syncwarp();
#pragma unroll
    for (int i = 0; i < 9 * R; i++) x[i] = badd2(x[i], bmul2(l[i], y[i]));
    layernorm9<R>(x, l);
    if (ts && l[0] != 0x12345) TS(30);
#pragma unroll
    for (int r = 0; r < R; r++) store_ln_row(0, tile * 16 + w + r * 8, l + r * 9);
    if (R == 1) {
      __syncthreads();
      if (threadIdx.x == 32 && real) { if (tile < 4) TS(19); st_release(g_lnflag + tile * 8, 1); if (tile < 4) TS(20); }
      __syncwarp();
    }
    if (ts) TS(31);
  }
  if (R == 2) {
    __syncthreads();
    if (threadIdx.x >= 506) {
      asm volatile("fence.acq_rel.gpu;" ::: "memory");
      st_relaxed_if(g_lnflag + ((first ^ (lane & 1)) + (lane - 26) / 2 * step) * 8, 1, true);
    }
    __syncwarp();
    fence_async_smem();
    if (threadIdx.x == 0) TS(15);
  }
}

__global__ void __cluster_dims__(2, 1, 1) __launch_bounds__(512, 1) k_main(const __grid_constant__ Params P) {
  extern __shared__ __align__(1024) unsigned char smem[];
  const uint32_t sb = (uint32_t)__cvta_generic_to_shared(smem);
  const int b = bid(), wg = threadIdx.x >> 7;
  if ((threadIdx.x & 127) == 0) TS(0);
  if (threadIdx.x == 480) {
    if ((sb & 0xFFFFFF) != SBASE) __trap();
    for (int i = 0; i < 6; i++) mbar_init(sb + W_BAR + i * 8, 1);
    if (b < N_CHAIN) {
      mbar_init(sb + CB_FULL, 1); mbar_init(sb + CB_FULL + 8, 1);
      mbar_init(sb + CB_REF, 1);
      mbar_init(sb + CB_SX, 1); mbar_init(sb + CB_OX, 1); mbar_init(sb + CB_XX, 1); mbar_init(sb + CB_Q, 2); mbar_init(sb + CB_VF, 1);
      sts32(sb + C_BAD, 0);
      for (int i = 0; i < 11; i++) mbar_init(sb + CB_M + i * 8, i == 0 ? 5 : i == 5 ? 2 : 1);
    } else if (b < N_CHAIN + N_G) {
      for (int i = 0; i < 9; i++) { mbar_init(sb + G_BAR + i * 8, 2); mbar_init(sb + G_BAR + 128 + i * 8, 8); }
    } else if (b < N_CHAIN + N_G + N_O) {
      for (int i = 0; i < 5; i++) { mbar_init(sb + O_BAR + i * 8, 1); mbar_init(sb + O_BAR + 128 + i * 8, 12); }
      for (int i = 0; i < 6; i++) mbar_init(sb + OB_ST + i * 8, 1);
    } else {
      mbar_init(sb + F_BAR, 1); mbar_init(sb + F_BAR + 8, 1);
    }
    asm volatile("fence.mbarrier_init.release.cluster;" ::: "memory");
    fence_async_smem();
  }
  __syncwarp();
  asm volatile("barrier.cluster.arrive.relaxed.aligned;" ::: "memory");
  prologue(P, sb);
  asm volatile("barrier.cluster.wait.aligned;" ::: "memory");
  fence_async_smem();
  if (b >= N_CHAIN + N_G) publish_y();
  if (b >= 128) ln_tiles<1>(P, sb);
  if (b >= N_CHAIN + N_G) ln_tiles<2>(P, sb);
  if ((threadIdx.x & 127) == 0) TS(3);
  if (b < N_CHAIN) {
    if (wg < 2) { reg_inc<200>(); chain_proj(P, sb); }
    else if (wg == 2) { reg_dec<88>(); publish_y(); chain_attn(P, sb); }
    else { reg_dec<24>(); chain_aux(P, sb); }
  } else if (b < N_CHAIN + N_G) {
    if (wg == 0) { reg_inc<232>(); g_math<0>(P, sb); }
    else if (wg == 1) { reg_inc<232>(); g_math<1>(P, sb); }
    else if (wg == 2) { reg_dec<24>(); bar_arrive(15, 192); publish_y(); g_aux(P, sb); }
    else { reg_dec<24>(); g_load(P, sb); }
  } else if (b < N_CHAIN + N_G + N_O) {
    if (wg == 0) { reg_inc<160>(); o_math<0>(P, sb); }
    else if (wg == 1) { reg_inc<160>(); o_math<1>(P, sb); }
    else if (wg == 2) { reg_inc<160>(); o_math<2>(P, sb); }
    else { reg_dec<32>(); o_aux(P, sb); }
  } else {
    f_role(P, sb);
  }
}

}

extern "C" void kernel_launch(void* const* d_in, const int* in_sizes, int n_in, void* d_out, int out_size) {
  typedef CUresult (*Encode)(CUtensorMap*, CUtensorMapDataType, cuuint32_t, void*, const cuuint64_t*, const cuuint64_t*, const cuuint32_t*, const cuuint32_t*,
                             CUtensorMapInterleave, CUtensorMapSwizzle, CUtensorMapL2promotion, CUtensorMapFloatOOBfill);
  static Encode encode = nullptr;
  if (!encode) cudaGetDriverEntryPoint("cuTensorMapEncodeTiled", (void**)&encode, cudaEnableDefault);
  Params P;
  for (int i = 0; i < 11; i++) {
    const bool wo = i == 6 || i == 7;
    const cuuint64_t cols = wo ? DM : HD, rows = HD + DM - cols, pitch = cols * 2;
    const cuuint64_t dim[4][5] = {{cols, 2, 8, 2, 18}, {cols, 16, 1, 1, rows / 16}, {cols, 2, 4, 4, rows / 32}, {64, 16, 64, 2, 18}};
    const cuuint64_t stride[4][4] = {{8 * pitch, pitch, 16 * pitch, 32 * pitch}, {pitch, pitch, pitch, 16 * pitch},
                                     {pitch, 8 * pitch, 2 * pitch, 32 * pitch}, {pitch, 128, 16 * pitch, 32 * pitch}};
    const cuuint32_t box[4][5] = {{64, 2, 8, 1, 18}, {64, 16, 1, 1, 1}, {64, 2, 4, 2, 1}, {64, 16, 2, 1, 18}}, one[5] = {1, 1, 1, 1, 1};
    const int k = i < 3 ? 0 : i < 7 ? 1 : i < 8 ? 2 : 3;
    encode(&P.map[i], CU_TENSOR_MAP_DATA_TYPE_BFLOAT16, 5, d_in[wo ? 11 : 8 + (i & 7) % 3], dim[k], stride[k], box[k], one,
           CU_TENSOR_MAP_INTERLEAVE_NONE, CU_TENSOR_MAP_SWIZZLE_128B, CU_TENSOR_MAP_L2_PROMOTION_L2_128B, CU_TENSOR_MAP_FLOAT_OOB_FILL_NONE);
  }
  P.X = (const bf16*)d_in[0]; P.K = (const bf16*)d_in[1]; P.V = (const bf16*)d_in[2];
  P.shift = (const bf16*)d_in[3]; P.Hk = (const bf16*)d_in[4]; P.Dk = (const bf16*)d_in[5];
  P.mem0 = (const bf16*)d_in[7];
  P.Wq = (const bf16*)d_in[8]; P.Wk = (const bf16*)d_in[9]; P.Wv = (const bf16*)d_in[10]; P.Wo = (const bf16*)d_in[11];
  P.out = (bf16*)d_out;
  for (int i = 0; i < 30; i++) P.dly[i] = h_dly[i];
  cudaFuncSetAttribute(k_main, cudaFuncAttributeMaxDynamicSharedMemorySize, SMEM_BYTES);
  k_main<<<N_CTA, 512, SMEM_BYTES>>>(P);
}
```

```cpp
#include <cuda.h>
#include <cuda_runtime.h>
#include <cuda_bf16.h>
#include <stdint.h>

namespace {

typedef __nv_bfloat16 bf16;

constexpr int SEQ = 2048, DM = 576, HD = 4096, NSEG = 64;
constexpr int LAG = 7, STEPS = NSEG + LAG, RING = 8;
constexpr int LOCK0 = 3, QRING = LOCK0 + 1;
static_assert(LAG < RING, "ring");
constexpr int N_CHAIN = 64, N_G = 48, N_O = 18, N_F = 2;
constexpr uint32_t SBASE = 1024;
constexpr uint32_t SENT = 0xFFFFFFFFu;
constexpr int SPIN_MAX = 1 << 22;

__device__ __forceinline__ uint32_t bid() {
  uint32_t b;
  asm volatile("mov.u32 %0, %%ctaid.x;" : "=r"(b));
  return b < 6 ? b + 106 : b < 8 ? b + 122 : b < 114 ? b - 8 : b < 130 ? b - 2 : b;
}
__device__ __forceinline__ uint32_t chain_id() { return blockIdx.x - 8; }
constexpr int KVP = SEQ + 64;
__device__ __align__(1024) bf16 g_kvT[DM * KVP];
__device__ __align__(1024) bf16 g_yT[DM * SEQ];
__device__ __align__(1024) unsigned char g_lnimg[2 * NSEG * 9 * 4096];
__device__ __align__(1024) unsigned char g_qkv[QRING * N_CHAIN * 24576];
__device__ __align__(1024) unsigned char g_oimg[RING * N_CHAIN * 8192];
constexpr int ARING = 16;
static_assert(ARING >= LAG + 9, "accumulator ring");
__device__ __align__(1024) float g_oacc[ARING * 64 * DM];
constexpr int MRING = LAG + 4, N_GRP = 32 + MRING + 1;
constexpr int XB_M = 256, XB_F = XB_M + MRING * 8, XB_REF = XB_F + 2, N_CTA = N_CHAIN + N_G + N_O + N_F;
__device__ __align__(65536) uint4 g_xb[N_GRP * 4096];
#define g_mimg ((uint32_t*)(g_xb + XB_M * 512))
__device__ uint32_t g_near[N_GRP];
__device__ uint32_t g_side[N_CTA];
__device__ __align__(128) uint32_t g_gbar[3 * 32];
constexpr int FL_G = 0, FL_F = 96 * 8, FL_OCNT = FL_F + 2 * 8, OCRING = 16, FL_TICK = 992, FL_O = 2048, FL_SYNC = FL_O + 128;
static_assert(FL_OCNT + OCRING * 8 <= FL_TICK, "flag block");
#define g_fl ((uint32_t*)(g_xb + XB_F * 512))
__device__ __align__(1024) uint32_t g_lnflag[128 * 8];
#define TS(slot)

#define CNT(slot, tries)
#define T3(slot)
#define TR(slot)
#define TRV(slot, val)
#define TRD(slot, dep)
#define TRSYNC()
#define TRDUMP(n)
#define CLK(t) "{.reg .b64 x; .reg .b32 h; mov.u64 x, %%clock64; mov.b64 {" t ", h}, x;}"
__device__ __forceinline__ uint32_t clk() { uint32_t t; asm volatile(CLK("%0") : "=r"(t) :: "memory"); return t; }
__device__ __forceinline__ void wait_until(uint32_t t0, uint32_t d) {
  asm volatile("{.reg .pred p; .reg .u32 t;\n"
               "W: " CLK("t") " sub.u32 t, t, %0; setp.lt.s32 p, t, 0; @p bra.uni W;}"
               :: "r"(t0 + d) : "memory");
}
__device__ __forceinline__ uint32_t pack2(float lo, float hi) {
  uint32_t r; asm("cvt.rn.bf16x2.f32 %0, %1, %2;" : "=r"(r) : "f"(hi), "f"(lo)); return r;
}
__device__ __forceinline__ float bf_lo(uint32_t v) { return __uint_as_float(v << 16); }
__device__ __forceinline__ float bf_hi(uint32_t v) { return __uint_as_float(v & 0xFFFF0000u); }

__device__ __forceinline__ void st_b128(void* p, uint32_t a, uint32_t b, uint32_t c, uint32_t d) {
  asm volatile("{.reg .b128 v; mov.b128 v, {%1,%2,%3,%4}; st.relaxed.gpu.global.b128 [%0], v;}" :: "l"(p), "r"(a), "r"(b), "r"(c), "r"(d) : "memory");
}
__device__ __forceinline__ void st_relaxed_if(void* p, uint32_t a, bool on) {
  asm volatile("{.reg .pred p; setp.ne.u32 p, %2, 0; @p st.relaxed.gpu.global.u32 [%0], %1;}" :: "l"(p), "r"(a), "r"((uint32_t)on) : "memory");
}
__device__ __forceinline__ uint32_t ld_acquire(const uint32_t* p) {
  uint32_t v; asm volatile("ld.acquire.gpu.global.u32 %0, [%1];" : "=r"(v) : "l"(p) : "memory"); return v;
}
__device__ __forceinline__ void st_release(uint32_t* p, uint32_t v) {
  asm volatile("st.release.gpu.global.u32 [%0], %1;" :: "l"(p), "r"(v) : "memory");
}
__device__ __forceinline__ void bulk_reduce(float* dst, uint32_t src, uint32_t bytes) {
  asm volatile("cp.reduce.async.bulk.global.shared::cta.bulk_group.add.f32 [%0], [%1], %2;" :: "l"(dst), "r"(src), "r"(bytes) : "memory");
}
__device__ __forceinline__ void bulk_done_inc(uint32_t* p) {
  asm volatile("cp.async.bulk.wait_group 0;\n"
               "fence.proxy.async.global;\nfence.release.gpu;\n"
               "red.relaxed.gpu.global.add.u32 [%0], 1;\nred.relaxed.gpu.global.add.u32 [%0+4096], 1;" :: "l"(p) : "memory");
}
__device__ __forceinline__ void flag_release(uint32_t* p, uint32_t v) {
  asm volatile("fence.release.gpu;\nst.relaxed.gpu.global.u32 [%0], %1;\nst.relaxed.gpu.global.u32 [%0+4096], %1;" :: "l"(p), "r"(v) : "memory");
}
__device__ __forceinline__ void spin_guard(int& it) {
  asm volatile("{.reg .pred p; add.s32 %0, %0, 1; setp.gt.s32 p, %0, %1; @p trap;}" : "+r"(it) : "n"(SPIN_MAX));
}
__device__ __forceinline__ void wait_flags(const uint32_t* p, uint32_t v) {
  int it = 0;
  while (true) {
    uint32_t x; asm volatile("ld.relaxed.gpu.global.u32 %0, [%1];" : "=r"(x) : "l"(p) : "memory");
    if (__all_sync(~0u, x >= v)) break;
    spin_guard(it);
  }
  asm volatile("fence.acquire.gpu;" ::: "memory");
}
__device__ __forceinline__ uint32_t timer_sample() {
  uint32_t g;
  asm volatile("{.reg .b64 x; .reg .b32 h; mov.u64 x, %%globaltimer; mov.b64 {%0, h}, x;}" : "=r"(g) :: "memory");
  return (g >> 5) * 57 - clk();
}
template <int N> __device__ __forceinline__ uint32_t timer_offset() {
  const uint32_t base = timer_sample();
  int best = 0;
#pragma unroll 1
  for (int i = 0; i < N; i++) {
    const int a = timer_sample() - base, b = timer_sample() - base, c = timer_sample() - base;
    best = max(max(best, a), max(b, c));
  }
  return base + best;
}
__device__ __forceinline__ void grid_arrive(int i) {
  asm volatile("red.release.gpu.global.add.u32 [%0], %1;" :: "l"(g_gbar + i * 32), "r"(bid() ? 1u : 257u - N_CTA) : "memory");
}
__device__ __forceinline__ void grid_wait(int i, uint32_t gen) {
  int it = 0;
  while (((ld_acquire(g_gbar + i * 32) ^ gen) >> 8) == 0) spin_guard(it);
}
__device__ __forceinline__ bool elect() {
  uint32_t r; asm volatile("{.reg .pred p; elect.sync _|p, -1; selp.u32 %0, 1, 0, p;}" : "=r"(r)); return r;
}
__device__ __forceinline__ void bar_sync(int id, int cnt) { asm volatile("bar.sync %0, %1;" :: "r"(id), "r"(cnt) : "memory"); }
__device__ __forceinline__ void bar_arrive(int id, int cnt) { asm volatile("bar.arrive %0, %1;" :: "r"(id), "r"(cnt) : "memory"); }
template <int id, int cnt> __device__ __forceinline__ void bar_arrive_after(uint32_t a, uint32_t b) {
  asm volatile("{.reg .pred p; setp.ne.u32 p, %2, 0xfff12345; setp.ne.and.u32 p, %3, 0xfff12345, p; @p bar.arrive %0, %1;}" :: "n"(id), "n"(cnt), "r"(a), "r"(b) : "memory");
}
template <int id, int cnt> __device__ __forceinline__ void bar_sync_after(uint32_t a) {
  asm volatile("{.reg .pred p; setp.ne.u32 p, %2, 0xfff12345; @p bar.sync %0, %1;}" :: "n"(id), "n"(cnt), "r"(a) : "memory");
}
__device__ __forceinline__ void fence_async_smem() { asm volatile("fence.proxy.async.shared::cta;" ::: "memory"); }
__device__ __forceinline__ void fence_async_global() { asm volatile("fence.proxy.async.global;" ::: "memory"); }
__device__ __forceinline__ void mbar_init(uint32_t mb, int cnt) { asm volatile("mbarrier.init.shared::cta.b64 [%0], %1;" :: "r"(mb), "r"(cnt) : "memory"); }
__device__ __forceinline__ void mbar_arrive(uint32_t mb) { asm volatile("mbarrier.arrive.shared::cta.b64 _, [%0];" :: "r"(mb) : "memory"); }
__device__ __forceinline__ void mbar_expect(uint32_t mb, uint32_t bytes) {
  asm volatile("mbarrier.arrive.expect_tx.shared::cta.b64 _, [%0], %1;" :: "r"(mb), "r"(bytes) : "memory");
}
__device__ __forceinline__ void mbar_wait(uint32_t mb, uint32_t parity) {
  asm volatile("{.reg .pred p;\nW: mbarrier.try_wait.parity.shared::cta.b64 p, [%0], %1;\n@!p bra W;}" :: "r"(mb), "r"(parity) : "memory");
}
template <int K> __device__ __forceinline__ void mbar_wait_step(uint32_t mb, int n) {
  asm volatile("{.reg .pred p; .reg .b32 t; add.u32 t, %1, %2; and.b32 t, t, 1;\nW: mbarrier.try_wait.parity.shared::cta.b64 p, [%0], t;\n@!p bra W;}" :: "r"(mb), "r"(n), "n"(2 * K) : "memory");
}
__device__ __forceinline__ void bulk_load(uint32_t dst, const void* src, uint32_t bytes, uint32_t mb) {
  asm volatile("cp.async.bulk.shared::cluster.global.mbarrier::complete_tx::bytes [%0], [%1], %2, [%3];" :: "r"(dst), "l"(src), "r"(bytes), "r"(mb) : "memory");
}
__device__ __forceinline__ void bulk_store(void* dst, uint32_t src, uint32_t bytes) {
  asm volatile("cp.async.bulk.global.shared::cta.bulk_group [%0], [%1], %2;" :: "l"(dst), "r"(src), "r"(bytes) : "memory");
}
__device__ __forceinline__ uint32_t mapa(uint32_t a, uint32_t rank) {
  uint32_t r; asm("mapa.shared::cluster.u32 %0, %1, %2;" : "=r"(r) : "r"(a), "r"(rank)); return r;
}
__device__ __forceinline__ void st_async4(uint32_t dst, float a, float b, float c, float d, uint32_t mb) {
  asm volatile("st.async.shared::cluster.mbarrier::complete_tx::bytes.v4.f32 [%0], {%1,%2,%3,%4}, [%5];" :: "r"(dst), "f"(a), "f"(b), "f"(c), "f"(d), "r"(mb) : "memory");
}
__device__ __forceinline__ void st_async1(uint32_t dst, uint32_t a, uint32_t mb) {
  asm volatile("st.async.shared::cluster.mbarrier::complete_tx::bytes.u32 [%0], %1, [%2];" :: "r"(dst), "r"(a), "r"(mb) : "memory");
}
__device__ __forceinline__ uint4 lds128(uint32_t a) {
  uint4 v; asm volatile("ld.shared.v4.u32 {%0,%1,%2,%3}, [%4];" : "=r"(v.x), "=r"(v.y), "=r"(v.z), "=r"(v.w) : "r"(a) : "memory"); return v;
}
__device__ __forceinline__ uint2 lds64(uint32_t a) {
  uint2 v; asm volatile("ld.shared.v2.u32 {%0,%1}, [%2];" : "=r"(v.x), "=r"(v.y) : "r"(a) : "memory"); return v;
}
__device__ __forceinline__ uint32_t lds32(uint32_t a) {
  uint32_t v; asm volatile("ld.shared.u32 %0, [%1];" : "=r"(v) : "r"(a) : "memory"); return v;
}
__device__ __forceinline__ void sts128(uint32_t a, uint4 v) {
  asm volatile("st.shared.v4.u32 [%0], {%1,%2,%3,%4};" :: "r"(a), "r"(v.x), "r"(v.y), "r"(v.z), "r"(v.w) : "memory");
}
__device__ __forceinline__ void sts32(uint32_t a, uint32_t x) { asm volatile("st.shared.u32 [%0], %1;" :: "r"(a), "r"(x) : "memory"); }
__device__ __forceinline__ void ldsm4(uint32_t& r0, uint32_t& r1, uint32_t& r2, uint32_t& r3, uint32_t a) {
  asm volatile("ldmatrix.sync.aligned.m8n8.x4.shared.b16 {%0,%1,%2,%3}, [%4];" : "=r"(r0), "=r"(r1), "=r"(r2), "=r"(r3) : "r"(a) : "memory");
}
__device__ __forceinline__ void ldsm4t(uint32_t& r0, uint32_t& r1, uint32_t& r2, uint32_t& r3, uint32_t a) {
  asm volatile("ldmatrix.sync.aligned.m8n8.x4.trans.shared.b16 {%0,%1,%2,%3}, [%4];" : "=r"(r0), "=r"(r1), "=r"(r2), "=r"(r3) : "r"(a) : "memory");
}
__device__ __forceinline__ void stsm4(uint32_t a, uint32_t r0, uint32_t r1, uint32_t r2, uint32_t r3) {
  asm volatile("stmatrix.sync.aligned.m8n8.x4.shared.b16 [%0], {%1,%2,%3,%4};" :: "r"(a), "r"(r0), "r"(r1), "r"(r2), "r"(r3) : "memory");
}
__device__ __forceinline__ uint32_t movmat(uint32_t a) {
  uint32_t d; asm volatile("movmatrix.sync.aligned.m8n8.trans.b16 %0, %1;" : "=r"(d) : "r"(a)); return d;
}
__device__ __forceinline__ void mma16(float* d, uint32_t a0, uint32_t a1, uint32_t a2, uint32_t a3, uint32_t b0, uint32_t b1) {
  asm volatile("mma.sync.aligned.m16n8k16.row.col.f32.bf16.bf16.f32 {%0,%1,%2,%3}, {%4,%5,%6,%7}, {%8,%9}, {%0,%1,%2,%3};"
    : "+f"(d[0]), "+f"(d[1]), "+f"(d[2]), "+f"(d[3]) : "r"(a0), "r"(a1), "r"(a2), "r"(a3), "r"(b0), "r"(b1));
}
__device__ __forceinline__ void mma8(float* d, uint32_t a0, uint32_t a1, uint32_t b0) {
  asm volatile("mma.sync.aligned.m16n8k8.row.col.f32.bf16.bf16.f32 {%0,%1,%2,%3}, {%4,%5}, {%6}, {%0,%1,%2,%3};"
    : "+f"(d[0]), "+f"(d[1]), "+f"(d[2]), "+f"(d[3]) : "r"(a0), "r"(a1), "r"(b0));
}
__device__ __forceinline__ float rcp(float x) { float r; asm("rcp.approx.ftz.f32 %0, %1;" : "=f"(r) : "f"(x)); return r; }
__device__ __forceinline__ float ex2(float x) { float r; asm("ex2.approx.ftz.f32 %0, %1;" : "=f"(r) : "f"(x)); return r; }

__host__ __device__ constexpr uint64_t mkdesc(uint32_t off, uint32_t lbo, uint32_t sbo, uint32_t swz) {
  return (uint64_t)((SBASE + off) >> 4) | ((uint64_t)(lbo >> 4) << 16) | ((uint64_t)(sbo >> 4) << 32) | ((uint64_t)swz << 62);
}
__host__ __device__ constexpr uint64_t desc_sw128(uint32_t off) { return mkdesc(off, 16, 1024, 1); }
__host__ __device__ constexpr uint64_t desc_n16(uint32_t off) { return mkdesc(off, 256, 128, 0); }
__host__ __device__ constexpr uint64_t desc_m(uint32_t off) { return mkdesc(off, 16, 256, 3); }

__host__ __device__ constexpr uint64_t desc_sw64(uint32_t off) { return mkdesc(off, 16, 512, 2); }

__device__ __forceinline__ void wg_fence() { asm volatile("wgmma.fence.sync.aligned;" ::: "memory"); }
__device__ __forceinline__ void wg_commit() { asm volatile("wgmma.commit_group.sync.aligned;" ::: "memory"); }
template <int N> __device__ __forceinline__ void wg_wait() { asm volatile("wgmma.wait_group.sync.aligned %0;" :: "n"(N) : "memory"); }

#define ACC8(d) "+f"(d[0]), "+f"(d[1]), "+f"(d[2]), "+f"(d[3]), "+f"(d[4]), "+f"(d[5]), "+f"(d[6]), "+f"(d[7])
#define ACC32(d) ACC8(d), ACC8((d + 8)), ACC8((d + 16)), ACC8((d + 24))
#define R8 "{%0,%1,%2,%3,%4,%5,%6,%7}"
#define R32 "{%0,%1,%2,%3,%4,%5,%6,%7,%8,%9,%10,%11,%12,%13,%14,%15,%16,%17,%18,%19,%20,%21,%22,%23,%24,%25,%26,%27,%28,%29,%30,%31}"
template <int SD> __device__ __forceinline__ void wg_rs16(float* d, const uint32_t* a, uint64_t db) {
  asm volatile("wgmma.mma_async.sync.aligned.m64n16k16.f32.bf16.bf16 " R8 ", {%8,%9,%10,%11}, %12, %13, 1, 1, 1;"
    : ACC8(d) : "r"(a[0]), "r"(a[1]), "r"(a[2]), "r"(a[3]), "l"(db), "n"(SD));
}
template <int SD> __device__ __forceinline__ void wg_ss16(float* d, uint64_t da, uint64_t db) {
  asm volatile("wgmma.mma_async.sync.aligned.m64n16k16.f32.bf16.bf16 " R8 ", %8, %9, %10, 1, 1, 1, 1;"
    : ACC8(d) : "l"(da), "l"(db), "n"(SD));
}
template <int SD, uint64_t DA, uint64_t DB> __device__ __forceinline__ void wg_ss16o(float* d, uint32_t oa, uint32_t ob) {
  asm volatile("{.reg .b32 x, y; .reg .b64 a, b; add.u32 x, %8, %10; add.u32 y, %9, %12; mov.b64 a, {x, %11}; mov.b64 b, {y, %13};\n"
               "wgmma.mma_async.sync.aligned.m64n16k16.f32.bf16.bf16 " R8 ", a, b, %14, 1, 1, 1, 1;}"
    : ACC8(d) : "r"(oa), "r"(ob), "n"((uint32_t)DA), "n"((uint32_t)(DA >> 32)), "n"((uint32_t)DB), "n"((uint32_t)(DB >> 32)), "n"(SD));
}
template <int SD> __device__ __forceinline__ void wg_rs64(float* d, const uint32_t* a, uint64_t db) {
  asm volatile("wgmma.mma_async.sync.aligned.m64n64k16.f32.bf16.bf16 " R32 ", {%32,%33,%34,%35}, %36, %37, 1, 1, 0;"
    : ACC32(d) : "r"(a[0]), "r"(a[1]), "r"(a[2]), "r"(a[3]), "l"(db), "n"(SD));
}
template <int SD> __device__ __forceinline__ void wg_ss64(float* d, uint64_t da, uint64_t db) {
  asm volatile("wgmma.mma_async.sync.aligned.m64n64k16.f32.bf16.bf16 " R32 ", %32, %33, %34, 1, 1, 1, 0;"
    : ACC32(d) : "l"(da), "l"(db), "n"(SD));
}
#define WG_RSO(NAME, SHAPE, REGS, ACC, A, TB) \
template <int SD, uint64_t DB> __device__ __forceinline__ void NAME(float* d, uint32_t a0, uint32_t a1, uint32_t a2, uint32_t a3, uint32_t ob) { \
  asm volatile("{.reg .b64 b; mov.b64 b, {" A(4) ", " A(5) "};\nwgmma.mma_async.sync.aligned." SHAPE ".f32.bf16.bf16 " REGS \
               ", {" A(0) "," A(1) "," A(2) "," A(3) "}, b, " A(6) ", 1, 1, " TB ";}" \
    : ACC(d) : "r"(a0), "r"(a1), "r"(a2), "r"(a3), "r"(ob + (uint32_t)DB), "n"((uint32_t)(DB >> 32)), "n"(SD)); \
}
#define ACC4(d) "+f"(d[0]), "+f"(d[1]), "+f"(d[2]), "+f"(d[3])
#define ACC16(d) ACC8(d), ACC8((d + 8))
#define OP4(i) OP4_##i
#define OP4_0 "%4"
#define OP4_1 "%5"
#define OP4_2 "%6"
#define OP4_3 "%7"
#define OP4_4 "%8"
#define OP4_5 "%9"
#define OP4_6 "%10"
#define OP16(i) OP16_##i
#define OP16_0 "%16"
#define OP16_1 "%17"
#define OP16_2 "%18"
#define OP16_3 "%19"
#define OP16_4 "%20"
#define OP16_5 "%21"
#define OP16_6 "%22"
#define OP32(i) OP32_##i
#define OP32_0 "%32"
#define OP32_1 "%33"
#define OP32_2 "%34"
#define OP32_3 "%35"
#define OP32_4 "%36"
#define OP32_5 "%37"
#define OP32_6 "%38"
WG_RSO(wg_rs8o, "m64n8k16", "{%0,%1,%2,%3}", ACC4, OP4, "1")
#define R16 "{%0,%1,%2,%3,%4,%5,%6,%7,%8,%9,%10,%11,%12,%13,%14,%15}"
WG_RSO(wg_rs32o, "m64n32k16", R16, ACC16, OP16, "1")
WG_RSO(wg_rs64o, "m64n64k16", R32, ACC32, OP32, "0")
WG_RSO(wg_rs32k, "m64n32k16", R16, ACC16, OP16, "0")
template <uint64_t DA, uint64_t DB> __device__ __forceinline__ void wg_ss32k(float* d, uint32_t ob) {
  asm volatile("{.reg .b64 b; mov.b64 b, {%17, %18};\nwgmma.mma_async.sync.aligned.m64n32k16.f32.bf16.bf16 " R16 ", %16, b, 1, 1, 1, 1, 0;}"
    : ACC16(d) : "l"(DA), "r"(ob + (uint32_t)DB), "n"((uint32_t)(DB >> 32)));
}
template <int N> __device__ __forceinline__ void reg_inc() { asm volatile("setmaxnreg.inc.sync.aligned.u32 %0;" :: "n"(N)); }
template <int N> __device__ __forceinline__ void reg_dec() { asm volatile("setmaxnreg.dec.sync.aligned.u32 %0;" :: "n"(N)); }

template <int KS>
__device__ __forceinline__ void load_frags(uint32_t* a, uint32_t src) {
  const int lane = threadIdx.x & 31, w = (threadIdx.x >> 5) & 3;
  const int k = ((lane >> 4) << 3) + (lane & 7), u = w * 2 + ((lane >> 3) & 1);
  const uint32_t base = src + k * 128 + ((u ^ (k & 7)) << 4);
#pragma unroll
  for (int ks = 0; ks < KS; ks++) ldsm4t(a[ks * 4], a[ks * 4 + 1], a[ks * 4 + 2], a[ks * 4 + 3], base + ks * 2048);
}

__device__ __forceinline__ uint32_t badd2(uint32_t a, uint32_t b) { uint32_t r; asm("add.rn.bf16x2 %0, %1, %2;" : "=r"(r) : "r"(a), "r"(b)); return r; }
__device__ __forceinline__ uint32_t bsub2(uint32_t a, uint32_t b) { uint32_t r; asm("sub.rn.bf16x2 %0, %1, %2;" : "=r"(r) : "r"(a), "r"(b)); return r; }
__device__ __forceinline__ uint32_t bmul2(uint32_t a, uint32_t b) { uint32_t r; asm("mul.rn.bf16x2 %0, %1, %2;" : "=r"(r) : "r"(a), "r"(b)); return r; }
__device__ __forceinline__ uint32_t bfma2(uint32_t a, uint32_t b, uint32_t c) { uint32_t r; asm("fma.rn.bf16x2 %0, %1, %2, %3;" : "=r"(r) : "r"(a), "r"(b), "r"(c)); return r; }
template <int R> __device__ __forceinline__ void layernorm9(const uint32_t* x, uint32_t* o) {
  const uint32_t ones = 0x3F803F80u;
  float a[R][3][4], q[R], s[R];
#pragma unroll
  for (int i = 0; i < 9 * R; i++) {
    float* d = a[i % R][i / R % 3];
    if (i < 3 * R) d[0] = d[1] = d[2] = d[3] = 0.f;
    mma8(d, x[i % R * 9 + i / R], ones, x[i % R * 9 + i / R]);
  }
#pragma unroll
  for (int r = 0; r < R; r++) {
    q[r] = threadIdx.x & 4 ? a[r][0][1] + a[r][1][1] + a[r][2][1] : a[r][0][0] + a[r][1][0] + a[r][2][0];
    s[r] = (a[r][0][2] + a[r][0][3]) + (a[r][1][2] + a[r][1][3]) + (a[r][2][2] + a[r][2][3]);
  }
#pragma unroll
  for (int r = 0; r < R; r++) { q[r] += __shfl_xor_sync(~0u, q[r], 4); s[r] += __shfl_xor_sync(~0u, s[r], 1); }
#pragma unroll
  for (int r = 0; r < R; r++) { q[r] += __shfl_xor_sync(~0u, q[r], 9); s[r] += __shfl_xor_sync(~0u, s[r], 2); }
#pragma unroll
  for (int r = 0; r < R; r++) q[r] = __shfl_sync(~0u, q[r], 0) + __shfl_sync(~0u, q[r], 18);
#pragma unroll
  for (int r = 0; r < R; r++) {
    const float mean = s[r] * (1.f / DM), var = fmaxf(fmaf(q[r], 1.f / DM, -mean * mean), 0.f);
    float sd;
    asm("sqrt.approx.ftz.f32 %0, %1;" : "=f"(sd) : "f"(bf_lo(pack2(bf_lo(pack2(var, 0.f)) + 1e-5f, 0.f))));
    const float inv = rcp(bf_lo(pack2(sd, 0.f)));
    const uint32_t mb = pack2(mean, mean), hi = pack2(inv, inv), lo = pack2(inv - bf_lo(hi), inv - bf_lo(hi));
#pragma unroll
    for (int i = r * 9; i < r * 9 + 9; i++) {
      const uint32_t d = bsub2(x[i], mb);
      o[i] = bfma2(d, hi, bmul2(d, lo));
    }
  }
}
__device__ __forceinline__ void store_ln_row(int layer, int tok, const uint32_t* o) {
  const int lane = threadIdx.x & 31, r = tok & 31;
  unsigned char* p = g_lnimg + (size_t)(layer * NSEG + (tok >> 5)) * (9 * 4096) + r * 128 + (((lane >> 2) ^ (r & 7)) << 4) + (lane & 3) * 4;
#pragma unroll
  for (int i = 0; i < 9; i++) *(uint32_t*)(p + i * 4096) = o[i];
}
struct Params { CUtensorMap map[11]; const bf16 *X, *K, *V, *shift, *Hk, *Dk, *mem0, *Wq, *Wk, *Wv, *Wo; bf16* out; uint32_t dly[30]; };
#define DLYS P.dly[0]
#define DLYW P.dly[1]
#define DLYV P.dly[24]
#define DLYK P.dly[4]
#define DLYO P.dly[25]
#define DLYG P.dly[5]
#define KWIN P.dly[6]
#define KMIN P.dly[7]
#define PREF0 P.dly[19]
#define PACE P.dly[20]
#define S1G P.dly[21]
#define S1DLY P.dly[22]
#define PREFH P.dly[23]
uint32_t h_dly[30] = {800, 120, 150, 160, 3640, 4160, 2750, 1300, 1585, 1670, 1760, 2090, 2210, 2310, 2790, 2920, 3185, 3330, 3500, 7000, 160, 12500, 20500, 4000, 3540, 400, 800, 100, 300, 150};

constexpr uint32_t C_W = 0, C_M = 147456, C_KV = C_M + 18432, C_OS = C_KV + 24576, C_QM = C_KV + 32768, C_KM = C_QM + 2048,
                   C_VM = C_KM + 2048, C_OI = C_VM + 2048, C_SX = C_OI + 4096, C_KM2 = C_SX + 2560, C_VM2 = C_KM2 + 128,
                   C_KV2 = C_KM2 + 2048, C_Q = C_KV2 + 8192, C_BAR = C_Q + 8192;
constexpr uint32_t CB_FULL = C_BAR, CB_REF = C_BAR + 16, CB_SX = C_BAR + 32, CB_OX = C_BAR + 40, CB_XX = C_BAR + 48, CB_Q = C_BAR + 56, C_BAD = C_BAR + 64, W_BAR = C_BAR + 80, T_BAR = W_BAR + 24, S_GEN = C_BAR + 128, C_REF = C_BAR + 132, CB_VF = C_BAR + 144, CB_M = C_BAR + 160, CB_MV = C_BAR + 200;
constexpr uint32_t G_W = 0, G_RING = 147456, G_W2 = G_RING + 9 * 8192, G_BAR = G_W2 + 8192;
constexpr uint32_t O_W = 0, O_RING = 3 * 40960, O_ST = O_RING + 11 * 8192, O_BAR = O_ST + 16384, OB_ST = O_BAR + 64;
constexpr uint32_t F_A = 0, F_XY = 36864, F_L = F_XY + 36864, F_X = F_L + 18432, F_Y = F_L + 2 * 36864, F_BAR = C_BAR;
constexpr uint32_t SMEM_BYTES = C_BAR + 256;
static_assert(G_BAR + 256 <= SMEM_BYTES && O_BAR + 256 <= SMEM_BYTES && F_BAR + 16 <= SMEM_BYTES && SMEM_BYTES <= 232448, "smem map");
enum { B_INIT = 1, B_M, B_QK, B_S, B_V, B_O, B_X, B_WG0, B_WG1, B_WG2, B_G, B_OE, B_T, B_R };

__device__ __forceinline__ uint4 pack_partial(const float* d, uint32_t tag) {
  uint32_t x, z;
  asm("lop3.b32 %0, %2, 1, %4, 0xb8; lop3.b32 %1, %3, 1, %4, 0xb8;" : "=&r"(x), "=&r"(z) : "r"(pack2(d[0], d[1])), "r"(pack2(d[2], d[3])), "r"(tag));
  return make_uint4(x, pack2(d[4], d[5]), z, pack2(d[6], d[7]));
}
__device__ __forceinline__ void store_partial(uint4* p, const uint4& v) { st_b128(p, v.x, v.y, v.z, v.w); }
__device__ __forceinline__ void gather_reduce(const uint32_t* p, uint32_t* dst, uint32_t m0, bool shared, uint32_t tag, uint32_t lane, uint32_t sb, int n, int TS0) {
  int tries = 0;
  bool bad;
  TR(TS0);
  do {
    uint2 x[8];
#pragma unroll
    for (int i = 0; i < 8; i++)
      asm volatile("{.reg .b64 v; ld.relaxed.gpu.global.b64 v, [%2]; mov.b64 {%0, %1}, v;}" : "=r"(x[i].x), "=r"(x[i].y) : "l"(p + i * 128) : "memory");
    spin_guard(tries);
    float a = bf_lo(x[0].x), b = bf_hi(x[0].x), c = bf_lo(x[0].y), d = bf_hi(x[0].y);
    uint32_t t = x[0].x ^ tag;
#pragma unroll
    for (int i = 1; i < 8; i++) {
      a += bf_lo(x[i].x); b += bf_hi(x[i].x); c += bf_lo(x[i].y); d += bf_hi(x[i].y);
      asm("lop3.b32 %0, %0, %1, %2, 0xf6;" : "+r"(t) : "r"(x[i].x), "r"(tag));
    }
    bad = __any_sync(~0u, t & 1);
    const bool up = lane & 8;
    float u = (up ? c : a) + __shfl_xor_sync(~0u, up ? a : c, 8), v = (up ? d : b) + __shfl_xor_sync(~0u, up ? b : d, 8);
    if (shared) { u += __shfl_xor_sync(~0u, u, 4); v += __shfl_xor_sync(~0u, v, 4); }
    u += __shfl_xor_sync(~0u, u, 16);
    v += __shfl_xor_sync(~0u, v, 16);
    st_relaxed_if(dst, n < LAG && up ? m0 : pack2(u, v), !bad);
  } while (bad);
  if (shared) bar_arrive(B_WG2, 224);
  TR(TS0 + 3); TRV(TS0 + 2, tries);
  CNT((TS0 - 16) >> 2, tries);
}

constexpr int XR = 3;
__host__ __device__ constexpr int o_ks(int s) { return s & (s < 8 ? 3 : 7); }
constexpr uint32_t OPAT = 0x55555577u;
__host__ __device__ constexpr bool o_reg(int s) { return (OPAT >> s) & 1; }
__host__ __device__ constexpr int o_slot(int s) { int k = 0; for (int i = 0; i < s; i++) k += o_reg(i) == o_reg(s); return k; }
__device__ __forceinline__ int g_unit(int wg) {
  const int i = bid() - N_CHAIN;
  return i < 32 ? wg * 64 + i : 2 * i - 32 + wg;
}
__device__ __forceinline__ uint32_t pinned(uint32_t v) { return __shfl_sync(~0u, v, threadIdx.x & 31); }
template <class T> __device__ __forceinline__ T* pinned(T* p) { return (T*)__shfl_sync(~0u, (unsigned long long)p, threadIdx.x & 31); }
enum { CHAIN, GROLE, OROLE };
template <int ROLE, bool SYNC> __device__ __forceinline__ void load_box(const Params& P, uint32_t sb, bool regs, int wg, int i, uint32_t mb, bool on) {
  const int b = bid();
  int map, col = 0, ks = 0, c2 = 0, c3 = 0;
  uint32_t dst = wg * 73728;
  if (ROLE == CHAIN) {
    const int k = i - 1, st = __fns(regs ? OPAT : ~OPAT, 0, i) & 31;
    dst += i ? (17 + i) * 2048 : 0;
    if (wg || i == 0) { map = wg + i; col = b * 64; c3 = !regs; }
    else if (!regs && k >= 14) { map = 6; ks = b * 4 + k - 14; }
    else { map = 6; col = 64 + (st < 8 ? (st >> 2) * 64 : (st >> 3) * 128 + (b & 1) * 64); ks = (b * 4) ^ o_ks(st); }
  } else if (ROLE == GROLE) {
    const int q = g_unit(wg);
    map = ((q >> 5) + 1) % 3;
    if (i) { map += 3; col = (q & 31) * 128 + (i - 1) * 64; ks = 34; dst = G_W2 + wg * 4096 + (i - 1) * 2048; }
    else { map += 8; c2 = (q & 31) * 2; c3 = !regs; }
  } else {
    const int o = b - N_CHAIN - N_G, ksl = o / 3;
    map = 7; col = ((o % 3) * 3 + (wg + ksl) % 3) * 64; dst = (wg * (regs ? 24 : 20) + i) * 2048;
    ks = (ksl * 11 - max(ksl - 4, 0)) * 4 + (regs ? i / 3 * 5 + i % 3 * 2 : i < 16 ? i / 2 * 5 + 1 + i % 2 * 2 : i + 24);
    c3 = (ks & 1) * 2; ks >>= 1;
  }
  if (SYNC) { col = pinned(col); ks = pinned(ks); bar_sync(B_WG0 + wg, 256); }
  if (on) asm volatile("cp.async.bulk.tensor.5d.shared::cluster.global.tile.mbarrier::complete_tx::bytes [%0], [%1, {%2, %3, %4, %5, %6}], [%7];"
               :: "r"(sb + dst), "l"(&P.map[map]), "r"(col), "r"(0), "r"(c2), "r"(c3), "r"(ks), "r"(mb) : "memory");
}
template <int ROLE, bool SYNC = false> __device__ __forceinline__ void load_wg(const Params& P, uint32_t sb, bool regs, int wg, int quarter) {
  const int i = (threadIdx.x & 31) * 4 + quarter;
  const int n = ROLE == CHAIN ? 36 : ROLE == GROLE ? (regs ? 38 : 36) : regs ? 24 : bid() < N_CHAIN + N_G + 12 ? 20 : 16;
  const bool split = SYNC && wg == 0;
  const uint32_t mb = split && i ? sb + T_BAR : sb + W_BAR + wg * 8;
  load_box<ROLE, SYNC>(P, sb, regs, wg, i, mb, i < (ROLE == CHAIN ? (wg ? 2 : 19) : ROLE == GROLE ? n - 35 : n));
  if (i <= split) mbar_expect(mb, n * (split ? 1024 : 2048));
  __syncwarp();
}
__device__ __forceinline__ uint32_t near_half(uint32_t blk, uint32_t reader) {
  return __ldcg(g_near + (blk >> 3)) ^ (~blk & 1) ^ __ldcg(g_side + (blk >> 3)) ^ __ldcg(g_side + reader);
}

__device__ __forceinline__ uint32_t opaque_tid() { uint32_t t; asm volatile("mov.u32 %0, %%tid.x;" : "=r"(t)); return t; }
__device__ __forceinline__ void m_fetch(uint32_t sb, uint32_t src, uint32_t b, uint32_t mb) {
  bulk_load(sb + C_M + (b ? b * 4096 - 2048 : 0), (const unsigned char*)g_mimg + ((src ^ ((b & 1) * 4096)) + b * 8192), b ? 4096 : 2048, mb);
}
__device__ __forceinline__ uint32_t m_probe(uint32_t lane) { return lane * 32 + (lane & 4) * 4 + (lane >> 3) * 4; }
__device__ __forceinline__ uint32_t m_max(uint32_t a, uint32_t b) {
  return max(max(lds32(a), lds32(a + 1024)), max(lds32(b), lds32(b + 1024)));
}
template <int S0, int N> __device__ __forceinline__ void o_steps(float* d, const uint32_t* a) {
  constexpr int SD = o_ks(S0) != 0;
  if constexpr (o_reg(S0)) wg_rs16<SD>(d, a + (18 + o_slot(S0)) * 4, desc_n16(C_OI + o_ks(S0) * 512));
  else wg_ss16<SD>(d, desc_sw128(C_W + (18 + o_slot(S0)) * 2048), desc_n16(C_OI + o_ks(S0) * 512));
  if constexpr (N > 1) o_steps<S0 + 1, N - 1>(d, a);
}
template <int BASE, int KS, int N> __device__ __forceinline__ void m_steps(float* d, const uint32_t* a, uint32_t oa) {
  wg_rs16<KS != 0>(d, a + (BASE + KS / 2) * 4, desc_m(C_M + KS * 512));
  if constexpr (KS >= 36 - 2 * XR) wg_rs16<1>(d, a + (18 + XR + KS / 2) * 4, desc_m(C_M + KS * 512 + 512));
  else wg_ss16o<1, desc_sw128(C_W + (BASE + KS / 2) * 2048), desc_m(C_M + KS * 512 + 512)>(d, oa, 0);
  if constexpr (N > 2) m_steps<BASE, KS + 2, N - 2>(d, a, oa);
}

constexpr uint32_t VPAT = 0x15bbd249u;
template <int I, int R, int S> __device__ __forceinline__ void v_steps(float* d, const uint32_t* a) {
  constexpr bool reg = (VPAT >> I) & 1;
  if constexpr (reg) wg_rs16<1>(d, a + (18 + R) * 4, desc_m(C_M + R * 1024));
  else wg_ss16<1>(d, desc_sw128(C_W + (54 + S) * 2048), desc_m(C_M + S * 1024 + 512));
  if constexpr (I < 31) v_steps<I + 1, R + reg, S + !reg>(d, a);
  else static_assert(R + reg == 18, "pattern");
}

__device__ __forceinline__ void chain_proj(const Params& P, uint32_t sb) {
  const uint32_t c = chain_id(), h = c >> 1, j = c & 1, wid = __shfl_sync(~0u, threadIdx.x >> 5, 0), wg = wid >> 2, w = wid & 3;
  const uint32_t t = threadIdx.x & 127, lane = pinned(t & 31), mine = pinned(sb + t * 16), rb = mapa(sb, j ^ 1);
  const uint32_t theirs = pinned(rb + C_KM2 + w * 512 + lane * 4), oa = wg * 4608;
  uint32_t a[144 + 4 * XR];
  mbar_wait(sb + W_BAR + wg * 8, 0);
  if (threadIdx.x == 0) TS(23);
  load_frags<36>(a, sb + C_W + wg * 73728);
  fence_async_smem();
  bar_arrive(B_WG0 + wg, 256);
  if (threadIdx.x == 0) TS(24);
  bar_sync(B_WG2, 384);
  const uint32_t round = min(wid ^ 4, 5u), gdly = P.dly[8 + round], ps = t >> 2, pf = j * 16 + (ps >> 1);
  const bool shared = round < 3;
  uint4* const dsts = pinned(g_xb + (ps * 4096 + near_half(ps * 8, ps * 2) * 256 + c * 4 + (t & 3)));
  uint4* const dstf = pinned(g_xb + (pf * 4096 + 512 + near_half(pf * 8 + 1, pf * 2) * 256 + h * 8 + (t & 7)));
  const uint32_t* const gsrc = (const uint32_t*)g_xb + (h * 16384 + round % 3 * 4096 + near_half(h * 8 + !shared, h * 2) * 1024 +
                               (shared ? lane * 4 + j * 2 : 2048 + (lane & 24) * 4 + j * 16 + (lane & 7) * 2));
  uint32_t* gdst = g_mimg + (16384 + (lane >> 4) * 1024 +
                   (shared ? (round ? 1536 + round * 512 : 0) + c * 8 + (((lane >> 1) ^ c) & 4) + (lane & 3)
                           : (round - 1) * 2048 + c * 16 + (lane & 1) * 8 + (((lane >> 1) ^ (c * 2)) & 4) + ((lane >> 1) & 3)));
  const uint32_t m0 = __ldcg(gdst - 16384);
  mbar_wait(sb + W_BAR + wg * 8, 1);
  load_frags<XR>(a + 144, sb + C_W + wg * 73728 + (18 - XR) * 2048);
  bar_sync(B_INIT, 256);
  if ((threadIdx.x & 127) == 0) TS(4);

  uint32_t ring = 1;
#pragma unroll 1
  for (int n = 0; n < STEPS; n++) {
    float d[8], e[8];
    if (n + 1 == STEPS && !wg) { bar_arrive(B_QK, 416); break; }
#pragma unroll
    for (int i = 0; i < 8; i++) e[i] = 0.f;
    uint32_t redo = n + 1;
#pragma unroll 1
    do {
      mbar_wait(sb + CB_M, n & 1);
      wg_fence();
      m_steps<0, 0, 4>(d, a, oa);
      wg_commit();
      if (wg) { wg_fence(); m_steps<18, 0, 4>(e, a, 4608); wg_commit(); }
      if (wid == 0) TR(8);
      mbar_wait(sb + CB_M + 8, n & 1);
      wg_fence();
      m_steps<0, 4, 8>(d, a, oa);
      wg_commit();
      mbar_wait(sb + CB_MV, n & 1);
      asm volatile("{.reg .pred p; .reg .u32 t; ld.shared.u32 t, [%1]; setp.eq.u32 p, t, %0; selp.u32 %0, -1, 0, p;}" : "+r"(redo) : "r"(sb + C_BAD) : "memory");
    } while (redo);
    mbar_wait(sb + CB_MV + 8, n & 1);
    wg_fence();
    m_steps<0, 12, 8>(d, a, oa);
    wg_commit();
    mbar_wait(sb + CB_MV + 16, n & 1);
    wg_fence();
    m_steps<0, 20, 8>(d, a, oa);
    wg_commit();
    mbar_wait(sb + CB_MV + 24, n & 1);
    wg_fence();
    m_steps<0, 28, 8>(d, a, oa);
    wg_commit();
    wg_wait<0>();
    if (w == 0) TR(6 + wg);
    const uint32_t f0 = pack2(d[0], d[1]), f1 = pack2(d[4], d[5]), f2 = pack2(d[2], d[3]), f3 = pack2(d[6], d[7]);
    stsm4(mine + C_QM + wg * 2048, f0, f1, f2, f3);
    bar_arrive(B_QK, 416);
    const uint32_t tag = (n & 1) ^ 1;
    if (n == 0) mbar_wait(sb + T_BAR, 0);
    if (wg) {
      if (n + 1 < STEPS) bar_sync(B_S, 256);
      wg_fence();
      v_steps<0, 2, 2>(e, a);
      wg_commit();
      const uint32_t k0 = j ? f0 : f1, k1 = j ? f2 : f3;
      mbar_wait(sb + CB_SX, n & 1);
      wg_wait<0>();
      if (w == 0) TR(11);
      const uint32_t v0 = pack2(e[0], e[1]), v1 = pack2(e[4], e[5]), v2 = pack2(e[2], e[3]), v3 = pack2(e[6], e[7]);
      stsm4(mine + C_VM, v0, v1, v2, v3);
      bar_arrive(B_V, 256);
      st_async1(theirs, k0, rb + CB_XX);
      st_async1(theirs + 256, k1, rb + CB_XX);
      st_async1(theirs + 128, j ? v0 : v1, rb + CB_XX);
      st_async1(theirs + 384, j ? v2 : v3, rb + CB_XX);
      if (n + 1 == STEPS) break;
      bar_sync(B_O, 256);
      fence_async_smem();
      wg_fence();
#pragma unroll
      for (int ks = 0; ks < 4; ks++) {
        if (ks == 0) wg_ss16<0>(d, desc_sw128(C_W + 32 * 2048), desc_n16(C_OI));
        else wg_ss16<1>(d, desc_sw128(C_W + (32 + ks) * 2048), desc_n16(C_OI + ks * 512));
      }
      wg_commit();
      bar_arrive(B_X, 256);
      if (w == 0) TR(0);
      wg_wait<0>();
      store_partial(dsts, pack_partial(d, tag));
      bar_arrive(B_M, 160);
      if (w == 0) TR(1);
    } else {
      bar_sync(B_X, 256);
      wg_fence();
      o_steps<0, 4>(d, a);
      wg_commit();
      o_steps<4, 4>(e, a);
      wg_commit();
      wg_wait<1>();
      store_partial(dsts + 1024, pack_partial(d, tag));
      if (w == 0) TR(2);
      wg_wait<0>();
      store_partial(dsts + 2048, pack_partial(e, tag));
      if (w == 0) TR(3);
      wg_fence();
      o_steps<8, 4>(d, a);
      wg_commit();
      bar_sync(B_T, 256);
      if (w == 0) { TRV(61, 0); TR(12); }
      wg_fence();
      o_steps<12, 4>(d, a);
      wg_commit();
      o_steps<16, 8>(e, a);
      wg_commit();
      wg_wait<1>();
      store_partial(dstf, pack_partial(d, tag));
      if (w == 0) TR(4);
      wg_fence();
      o_steps<24, 8>(d, a);
      wg_commit();
      wg_wait<1>();
      store_partial(dstf + 1024, pack_partial(e, tag));
      bar_arrive(B_OE, 256);
      if (w == 0) TR(5);
      wg_wait<0>();
      store_partial(dstf + 2048, pack_partial(d, tag));
      if (w == 0) TR(15);
    }
    if ((wid ^ 4) < 6) {
      mbar_wait(sb + CB_REF, n & 1);
      wait_until(lds32(sb + C_REF), gdly);
      gather_reduce(gsrc, gdst, m0, shared, tag, lane, sb, n, 16 + round * 4);
      if (++ring == MRING) { ring = 0; gdst -= MRING * 16384; }
      gdst += 16384;
    }
  }
}

template <int KS> __device__ __forceinline__ void x_scores(float* s, float* sm, const uint4* q, uint32_t ok, uint32_t om) {
  wg_rs32o<KS != 0, desc_sw64(C_KV + KS * 1024)>(s, q[KS].x, q[KS].y, q[KS].z, q[KS].w, ok);
  wg_rs8o<KS != 0, desc_n16(C_KM + KS * 512)>(sm, q[KS].x, q[KS].y, q[KS].z, q[KS].w, om);
  if constexpr (KS < 3) x_scores<KS + 1>(s, sm, q, ok, om);
}

__device__ __forceinline__ void chain_attn(const Params& P, uint32_t sb) {
  const int c = chain_id(), j = c & 1;
  const int tid = threadIdx.x, lane = tid & 31, w = __shfl_sync(~0u, (tid >> 5) & 3, 0);
  const int l = w >> 1, u = w & 1;
  const uint32_t rb = mapa(sb, j ^ 1);
  const float sc = 0.08838834764831845f * 1.4426950408889634f;
  const uint32_t ones = 0x3F803F80u, sx = C_SX + l * 1280;
  const uint32_t km_off = C_KM + (lane >> 3) * 256 + l * 128 + (lane & 7) * 16;
  const uint32_t qm_off = C_QM + (lane >> 4) * 256 + l * 128 + (lane & 7) * 16, kmu = pinned(sb + km_off + u * 1024);
  const uint32_t kv_off = C_KV + l * 4096 + (lane & 15) * 64 + (((lane >> 4) ^ (u * 2) ^ ((lane >> 1) & 3)) << 4);

  load_wg<CHAIN, true>(P, sb, false, 1, w);
  if (lane == 0) mbar_arrive(sb + CB_M);
#pragma unroll 1
  for (int n = 0; n < STEPS; n++) {
    const uint32_t kvb = sb + kv_off + (n & 1) * 16384;
    mbar_wait(sb + CB_FULL + (n & 1) * 8, (n >> 1) & 1);
    if (n < 3 && tid == 256) TS(n ? 20 + n : 5);
    __syncwarp();
    {
      uint32_t km[8];
      uint4 kx[8];
#pragma unroll
      for (int i = 0; i < 8; i++) ldsm4t(kx[i].x, kx[i].y, kx[i].z, kx[i].w, (kvb ^ ((i & 1) * 32)) + (i >> 1) * 1024);
      mbar_wait_step<1>(sb + CB_VF, n);
      if (w == 1) TRD(60, kx[7].x);
      bar_sync(B_QK, 416);
      if (n + 1 == STEPS) {
        st_async4(rb + sx + u * 512 + lane * 16, 0.f, 0.f, 0.f, 0.f, rb + CB_SX);
        st_async1(rb + sx + 1024 + u * 128 + lane * 4, 0, rb + CB_SX);
        bar_sync(B_V, 256);
      } else {
      uint32_t qm[16];
#pragma unroll
      for (int ks = 0; ks < 4; ks++) ldsm4t(qm[4 * ks], qm[4 * ks + 1], qm[4 * ks + 2], qm[4 * ks + 3], sb + qm_off + ks * 512);
      ldsm4t(km[0], km[1], km[2], km[3], sb + km_off);
      ldsm4t(km[4], km[5], km[6], km[7], sb + km_off + 1024);
      float s[5][4];
      uint4 vx[4];
#pragma unroll
      for (int i = 0; i < 5; i++) { s[i][0] = s[i][1] = s[i][2] = s[i][3] = 0.f; }
#pragma unroll
      for (int ks = 0; ks < 4; ks++) {
        const uint32_t* q = qm + 4 * ks;
        if (ks == 1 || ks == 2) {
#pragma unroll
          for (int i = 2 * ks - 2; i < 2 * ks; i++) ldsm4(vx[i].x, vx[i].y, vx[i].z, vx[i].w, ((sb + kv_off) ^ ((i & 1) * 32)) + 8192 + (2 * u + (i >> 1)) * 1024);
        }
        mma16(s[1], q[0], q[1], q[2], q[3], kx[2 * ks].x, kx[2 * ks].y);
        mma16(s[2], q[0], q[1], q[2], q[3], kx[2 * ks].z, kx[2 * ks].w);
        mma16(s[0], q[0], q[1], q[2], q[3], km[2 * ks], km[2 * ks + 1]);
        mma16(s[3], q[0], q[1], q[2], q[3], kx[2 * ks + 1].x, kx[2 * ks + 1].y);
        mma16(s[4], q[0], q[1], q[2], q[3], kx[2 * ks + 1].z, kx[2 * ks + 1].w);
      }
      st_async4(rb + sx + u * 512 + lane * 16, s[1][0], s[1][1], s[2][0], s[2][1], rb + CB_SX);
      st_async1(rb + sx + 1024 + u * 128 + lane * 4, __float_as_uint(u ? s[0][1] : s[0][0]), rb + CB_SX);
      bar_arrive_after<B_S, 256>(__float_as_uint(s[3][0]), __float_as_uint(s[4][0]));
      mbar_wait_step<2>(sb + CB_SX, n);
      const uint4 p0 = lds128(sb + sx + u * 512 + lane * 16), p1 = lds128(sb + sx + (u ^ 1) * 512 + lane * 16);
      const uint2 p2 = make_uint2(lds32(sb + sx + 1024 + lane * 4), lds32(sb + sx + 1152 + lane * 4));
      float t[10] = {s[0][0] + __uint_as_float(p2.x), s[0][1] + __uint_as_float(p2.y),
                     s[1][0] + __uint_as_float(p0.x), s[1][1] + __uint_as_float(p0.y),
                     s[2][0] + __uint_as_float(p0.z), s[2][1] + __uint_as_float(p0.w),
                     s[3][0] + __uint_as_float(p1.x), s[3][1] + __uint_as_float(p1.y),
                     s[4][0] + __uint_as_float(p1.z), s[4][1] + __uint_as_float(p1.w)};
      float mx = fmaxf(fmaxf(fmaxf(fmaxf(t[2], t[3]), fmaxf(t[4], t[5])), fmaxf(fmaxf(t[6], t[7]), fmaxf(t[8], t[9]))), fmaxf(t[0], t[1]));
      mx = fmaxf(fmaxf(mx, __shfl_xor_sync(~0u, mx, 1)), fmaxf(__shfl_xor_sync(~0u, mx, 2), __shfl_xor_sync(~0u, mx, 3)));
      const float ms = -mx * sc;
#pragma unroll
      for (int i = 0; i < 10; i++) t[i] = ex2(fmaf(t[i], sc, ms));
      uint32_t p[5];
#pragma unroll
      for (int i = 0; i < 5; i++) p[i] = pack2(t[2 * i], t[2 * i + 1]);
      p[1] |= (p[0] & p[3] & p[4]) & 0x80008000u;
      float o[2][4], z[4] = {0.f, 0.f, 0.f, 0.f};
      mma16(z, ones, ones, ones, ones, p[1], p[2]);
#pragma unroll
      for (int i = 0; i < 2; i++) {
        o[i][0] = o[i][1] = o[i][2] = o[i][3] = 0.f;
        mma16(o[i], vx[2 * i].x, vx[2 * i].y, vx[2 * i].z, vx[2 * i].w, p[1], p[2]);
      }
      mma16(z, ones, ones, ones, ones, p[3], p[4]);
#pragma unroll
      for (int i = 0; i < 2; i++) mma16(o[i], vx[2 * i + 1].x, vx[2 * i + 1].y, vx[2 * i + 1].z, vx[2 * i + 1].w, p[3], p[4]);
      mma8(z, ones, ones, p[0]);
      bar_sync_after<B_V, 256>(p[1]);
      ldsm4(km[0], km[1], km[2], km[3], kmu + (C_VM - C_KM));
      mma8(o[0], km[0], km[1], p[0]);
      mma8(o[1], km[2], km[3], p[0]);
      const float i0 = rcp(z[0]), i1 = rcp(z[1]);
      const uint32_t oo = C_OI + u * 1024 + l * 128 + lane * 4;
      uint32_t ow[4];
#pragma unroll
      for (int i = 0; i < 2; i++) { ow[2 * i] = pack2(o[i][0] * i0, o[i][1] * i1); ow[2 * i + 1] = pack2(o[i][2] * i0, o[i][3] * i1); }
      stsm4(kmu + (C_OI - C_KM), ow[0], ow[1], ow[2], ow[3]);
      bar_arrive(B_O, 256);
#pragma unroll
      for (int i = 0; i < 4; i++) st_async1(rb + oo + 2048 + i * 256, ow[i], rb + CB_OX);
      }
    }
    {
      const uint32_t lane = opaque_tid() & 31, own = ((n & 1) * 16384 + j * 4096) >> 4;
      float s[16], sm[4], r[16], rm[4];
      {
        uint4 q[4];
        mbar_wait_step<3>(sb + CB_Q, n);
#pragma unroll
        for (int ks = 0; ks < 4; ks++)
          ldsm4t(q[ks].x, q[ks].y, q[ks].z, q[ks].w, sb + C_Q + (lane & 8) * 512 + ks * 1024 + (lane & 16) * 32 + (lane & 7) * 64 + (((w ^ (lane >> 1)) & 3) << 4));
        mbar_wait_step<3>(sb + CB_XX, n);
        if (n + 1 < STEPS) mbar_wait_step<3>(sb + CB_OX, n);
        fence_async_smem();
        if (n + 1 < STEPS) { bar_arrive(B_T, 256); bar_sync(B_OE, 256); }
        if (w == 1) { TRV(61, 0); TR(9); }
        wg_fence();
        x_scores<0>(s, sm, q, own, j * 8);
        x_scores<0>(r, rm, q, (C_KV2 - C_KV) >> 4, (C_KM2 - C_KM) >> 4);
        wg_commit();
        wg_wait<0>();
      }
      const float neg = -1e9f * 11.313708498984761f;
      const int tok = (lane & 24) + 2 * w + ((lane >> 2) & 1), lim = tok - 8 * (int)(lane & 3);
      float t[10] = {sm[0] + rm[2], sm[1] + rm[3]};
#pragma unroll
      for (int i = 0; i < 8; i++) t[2 + i] = i > lim ? neg : s[(i >> 1) * 4 + (i & 1)] + r[(i >> 1) * 4 + (i & 1) + 2];
      float mx = fmaxf(fmaxf(fmaxf(fmaxf(t[2], t[3]), fmaxf(t[4], t[5])), fmaxf(fmaxf(t[6], t[7]), fmaxf(t[8], t[9]))), fmaxf(t[0], t[1]));
      mx = fmaxf(fmaxf(mx, __shfl_xor_sync(~0u, mx, 1)), fmaxf(__shfl_xor_sync(~0u, mx, 2), __shfl_xor_sync(~0u, mx, 3)));
      const float ms = -mx * sc;
#pragma unroll
      for (int i = 0; i < 10; i++) t[i] = ex2(fmaf(t[i], sc, ms));
      uint32_t p[5];
#pragma unroll
      for (int i = 0; i < 5; i++) p[i] = pack2(t[2 * i], t[2 * i + 1]);
      float z = ((t[0] + t[1]) + (t[2] + t[3])) + ((t[4] + t[5]) + (t[6] + t[7])) + (t[8] + t[9]);
      const uint32_t row = sb + C_OS + tok * 128 + (((lane & 3) ^ (tok & 7)) << 4);
      z = rcp((z + __shfl_xor_sync(~0u, z, 1)) + (__shfl_xor_sync(~0u, z, 2) + __shfl_xor_sync(~0u, z, 3)));
      float o[32];
      bar_sync_after<B_WG2, 224>(n + 1 < STEPS ? __float_as_uint(z) : 0xfff12345u);
      wg_fence();
      wg_rs64o<0, desc_sw64(C_KV + 8192)>(o, p[1], 0, p[2], 0, j * 256);
      wg_rs64o<1, desc_sw64(C_KV + 8192 + 32)>(o, p[3], 0, p[4], 0, j * 256);
      wg_rs64o<1, mkdesc(C_VM, 128, 256, 0)>(o, p[0], 0, 0, 0, j * 8);
      wg_rs64o<1, desc_sw64(C_KV2 + 4096)>(o, 0, p[1], 0, p[2], 0);
      wg_rs64o<1, desc_sw64(C_KV2 + 4096 + 32)>(o, 0, p[3], 0, p[4], 0);
      wg_rs64o<1, mkdesc(C_VM2, 128, 256, 0)>(o, 0, p[0], 0, 0, 0);
      wg_commit();
      if (elect()) mbar_arrive(sb + CB_M);
      wg_wait<0>();
#pragma unroll
      for (int i = 0; i < 4; i++) {
        const float* v = o + 16 * (i & 1) + (i & 2);
        sts128((row ^ ((i & 1) * 64)) + (i & 2) * 2048,
               make_uint4(pack2(v[0] * z, v[1] * z), pack2(v[4] * z, v[5] * z), pack2(v[8] * z, v[9] * z), pack2(v[12] * z, v[13] * z)));
      }
      bar_arrive(B_G, 160);
      if (n + 1 < STEPS) bar_arrive(B_R, 160);
      if (w == 1) TR(10);
    }
  }
  if ((threadIdx.x & 127) == 0) TS(6);
}

__device__ __forceinline__ void chain_aux(const Params& P, uint32_t sb) {
  const uint32_t c = chain_id(), j = c & 1, lane = threadIdx.x & 31, w = __shfl_sync(~0u, (threadIdx.x >> 5) & 3, 0);
  load_wg<CHAIN, true>(P, sb, false, 0, w);
  if (threadIdx.x == 384) TS(25);
  if (threadIdx.x == 384) grid_wait(1, lds32(sb + S_GEN));
  bar_sync(B_WG2, 384);
  if (threadIdx.x == 384) TS(13);
  if (w == 0) {
    const uint32_t* fg = g_fl + FL_G + near_half(XB_F, c) * 1024 + (c >> 1) * 8;
#pragma unroll 1
    for (int n = 0; n < STEPS; n++) {
      const unsigned char* blk = g_qkv + (uint32_t)((n % QRING) * (N_CHAIN * 24576));
      const uint32_t t1 = clk(), kb = sb + CB_FULL + (n & 1) * 8, kv = sb + C_KV + (n & 1) * 16384;
      uint32_t t0 = t1 - 100000, x = 0;
      if (n > 0) {
        wait_until(t1, KMIN);
        do asm volatile("ld.relaxed.gpu.global.u32 %0, [%1];" : "=r"(x) : "l"(fg) : "memory"); while (x <= n && clk() - t1 < KWIN);
        if (x > n) {
          asm volatile("fence.acquire.gpu;" ::: "memory");
          fence_async_global();
          if (elect()) { mbar_expect(kb, 8192); bulk_load(kv, blk + c * 24576, 8192, kb); }
        }
        T3(0); CNT(12, 1 + (x <= n));
        mbar_wait(sb + CB_REF, (n - 1) & 1);
        t0 = lds32(sb + C_REF);
        wait_until(t0, DLYV - 500);
      }
      wait_flags(fg + min(lane, 2u) * 256, n + 1);
      T3(2);
      fence_async_global();
      if (n > 0) bar_sync(B_R, 160);
      if (lane < 3) mbar_expect(sb + CB_SX + lane * 8, lane ? 2048 : 2560);
      __syncwarp();
      wait_until(t0, DLYV);
      if (elect()) {
        if (x <= n) { mbar_expect(kb, 8192); bulk_load(kv, blk + c * 24576, 8192, kb); }
        mbar_expect(sb + CB_VF, 8192);
        bulk_load(sb + C_KV + 8192, blk + (c * 24576 + 8192), 8192, sb + CB_VF);
        mbar_expect(sb + CB_Q, 16384);
        wait_until(t0, DLYK);
        bulk_load(sb + C_Q, blk + (c * 24576 + 16384), 8192, sb + CB_Q);
        bulk_load(sb + C_KV2, blk + ((c ^ 1) * 24576 + j * 4096), 4096, sb + CB_Q);
        bulk_load(sb + C_KV2 + 4096, blk + ((c ^ 1) * 24576 + 8192 + j * 4096), 4096, sb + CB_Q);
      }
      T3(1);
      T3(3);
    }
  } else {
    const uint32_t near = __ballot_sync(~0u, near_half(XB_M + min(lane, MRING - 1u) * 8, c));
    uint32_t ring = 0;
    if (w > 1) {
      const uint32_t odd = w & 1, chk = pinned(sb + C_M + odd * 2048 + m_probe(lane)), again = sb + CB_MV + 32 + odd * 8;
      const bool one = elect();
      uint32_t mph = 0;
#pragma unroll 1
      for (int n = 0; n <= STEPS; n++) {
#pragma unroll
        for (int k = 0; k < 3; k++) {
          if (n == STEPS || (k == 2 && odd)) break;
          const uint32_t b = 2 * k + odd, at = chk + (k ? k * 8192 - 2048 + odd * 2048 : 0);
          uint32_t mb = sb + CB_M + b * 8, ph = n & 1;
          int it = 1;
          while (true) {
            mbar_wait(mb, ph);
            const bool bad = __any_sync(~0u, m_max(at, b ? at + 2048 : at) == SENT);
            if (one && !bad) mbar_arrive(sb + CB_MV + (b > 1 ? b * 8 - 8 : 0));
            if (!bad) break;
            mb = again; ph = mph; mph ^= 1;
            if (one) {
              if (k == 0) sts32(sb + C_BAD, n + 1);
              mbar_expect(mb, b ? 4096 : 2048);
              m_fetch(sb, ring * 65536 + ((near >> ring) & 1) * 4096, b, mb);
            }
            __syncwarp();
            spin_guard(it);
          }
          TR(41 + b * 4); CNT(6 + b, it);
        }
        ring = ring + 1 == MRING ? 0 : ring + 1;
        if (!odd) {
          if (n < STEPS) { TRSYNC(); TRDUMP(n - 2); }
        } else {
          unsigned char* o = g_oimg + (uint32_t)(((n - 1) & (RING - 1)) * (N_CHAIN * 8192) + j * 4096);
          if (n > 0) bar_sync(B_G, 160);
          fence_async_smem();
          if (one) {
            if (n > 0) {
              bulk_store(o + c * 8192, sb + C_OS, 4096);
              bulk_store(o + (c ^ 1) * 8192, sb + C_OS + 4096, 4096);
              asm volatile("cp.async.bulk.commit_group;\ncp.async.bulk.wait_group.read 0;" ::: "memory");
              { const int n_ = n - 1; { const int n = n_; T3(4); (void)n; } }
            }
            mbar_arrive(sb + CB_Q);
            if (n > 0) {
              bulk_done_inc(g_fl + FL_O + c);
              { const int n_ = n - 1; { const int n = n_; T3(5); (void)n; } }
            }
          }
          __syncwarp();
        }
      }
    } else {
      const uint32_t* ts = g_fl + FL_SYNC + near_half(XB_F + 1, c) * 1024 + lane * 2;
      uint32_t t0 = clk() - 100000, last = 0;
      int lag = 0;
#pragma unroll 1
      for (int n = 0; n < STEPS; n++) {
        const uint32_t src = ring * 65536 + ((near >> ring) & 1) * 4096;
        if (lane < 5) mbar_expect(sb + CB_M + lane * 8, lane ? 4096 : 2048);
        __syncwarp();
        if (elect()) {
#pragma unroll
          for (int b = 0; b < 5; b++) {
            wait_until(t0, P.dly[14 + b]);
            m_fetch(sb, src, b, sb + CB_M + b * 8);
            TR(40 + b * 4);
          }
        }
        __syncwarp();
        ring = ring + 1 == MRING ? 0 : ring + 1;
        uint32_t va, vb;
        const uint32_t off = timer_offset<4>(), tag = (uint32_t)(n + 1) << 28;
        if (n > 1) lag += (int)(off - last) - (lag >> 2);
        last = off;
        const uint32_t mine = min(max((lag >> 3) + 256, 0), 511);
        bar_sync(B_QK, 416);
        if (n + 1 == STEPS) break;
        sts32(sb + C_REF + 4, 0);
        const uint32_t c0 = clk(), stamp = c0 + off;
        st_relaxed_if(g_fl + FL_SYNC + lane * 1024 + c, tag | (mine << 19) | (stamp & 0x7FFFF), lane < 2);
        TR(13);
        wait_until(c0, DLYS);
        int it = 0;
        do {
          asm volatile("ld.relaxed.gpu.global.v2.u32 {%0,%1}, [%2];" : "=r"(va), "=r"(vb) : "l"(ts) : "memory");
          spin_guard(it);
        } while (__any_sync(~0u, ((va ^ tag) | (vb ^ tag)) >> 28));
        const int late = __reduce_max_sync(~0u, max((int)((va - stamp) << 13), (int)((vb - stamp) << 13))) >> 13;
        const uint32_t fast = min(((__reduce_max_sync(~0u, max(va, vb)) >> 19) & 511) - mine, 100u);
        t0 = c0 + min((uint32_t)late, clk() - c0) + (n < 2 ? P.dly[26 + n] : 0);
        if (elect()) {
          sts32(sb + C_REF, t0 + (fast * 9 >> 3));
          mbar_arrive(sb + CB_REF);
        }
        st_relaxed_if(g_fl + FL_TICK + lane * 1024, (uint32_t)(n + 1) << 24 | ((t0 + off) & 0xFFFFFF), c == 0 && lane < 2);
        t0 += (fast * 13 >> 3) + (n < 2 ? P.dly[28 + n] : 0);
        TRV(59, fast);
        TR(14); CNT(11, it);
        bar_sync(B_M, 160);
      }
    }
  }
}

template <int WG>
__device__ __forceinline__ void g_math(const Params& P, uint32_t sb) {
  const int q = g_unit(WG);
  const int lane = threadIdx.x & 31, w = (threadIdx.x >> 5) & 3;
  uint32_t a[136];
  {
    const uint32_t stage = sb + G_W + WG * 73728;
    mbar_wait(sb + W_BAR + WG * 8, 0);
    if (threadIdx.x == 0) TS(23);
    load_frags<34>(a, stage);
    fence_async_smem();
    bar_sync(B_WG0 + WG, 128);
    if (threadIdx.x == 0) TS(24);
    load_wg<GROLE>(P, sb, false, WG, w);
    if (threadIdx.x == 0) TS(25);
    mbar_wait(sb + W_BAR + WG * 8, 1);
  }
  if ((threadIdx.x & 127) == 0) TS(4);
  const uint32_t off0 = (q & 31) * 49152 + (q >> 5) * 8192 + w * 1024 + (lane >> 2) * 64 + (((lane ^ (lane >> 3)) & 3) << 4);
  const uint32_t isq = q >> 6;
#pragma unroll 1
  for (int n = 0; n < STEPS; n++) {
    float d0[32], d1[32];
    if (WG == 0 && n >= LOCK0) bar_sync(B_OE, 160);
    if (n > 0) bar_sync(B_V + WG, 256);
#pragma unroll
    for (int ch = 0; ch < 9; ch++) {
      mbar_wait(sb + G_BAR + ch * 8, n & 1);
      if (ch == 0) { if ((threadIdx.x & 127) == 0) T3(5 + WG * 3); __syncwarp(); }
      if (ch == 4) { if ((threadIdx.x & 127) == 0) T3(6 + WG * 3); __syncwarp(); }
      if (ch == 8 && (WG == 0 ? n > 0 : n + 1 < STEPS)) bar_arrive(B_V + (WG ^ 1), 256);
      wg_fence();
#pragma unroll
      for (int kk = 0; kk < 4; kk++) {
        const int i = ch * 4 + kk;
        float* d = i & 1 ? d1 : d0;
        const uint64_t db = desc_sw128(G_RING + ch * 8192 + (kk & 2) * 32);
        if (i < 2) wg_rs64<0>(d, a + i * 4, db);
        else if (i < 34) wg_rs64<1>(d, a + i * 4, db);
        else wg_ss64<1>(d, desc_sw128(G_W2 + WG * 4096 + (i - 34) * 2048), db);
        wg_ss64<1>(d, desc_sw128(G_W + WG * 73728 + i * 2048), db + 2);
      }
      wg_commit();
      if (ch > 0) { wg_wait<1>(); if (lane == 0) mbar_arrive(sb + G_BAR + 128 + (ch - 1) * 8); }
    }
    wg_wait<0>();
    if (lane == 0) mbar_arrive(sb + G_BAR + 128 + 8 * 8);
    if ((threadIdx.x & 127) == 0) T3(7 + WG * 3);
    __syncwarp();
    uint32_t tw = clk() + (n == 0 ? 0u - 100000u : WG ? 0u : DLYW);
    unsigned char* base = g_qkv + (size_t)(n & (QRING - 1)) * (N_CHAIN * 24576);
#pragma unroll
    for (int i = 0; i < 8; i++) {
      const float* d = (i < 4 ? d0 : d1) + 8 * (i & 2) + 2 * (i & 1);
      wait_until(tw, 0); tw += P.dly[2 + WG];
      *(uint4*)(base + (off0 + (i < 2 ? 0 : i < 4 ? 4096 + isq * 24576 : i < 6 ? 24576 - isq * 20480 : 28672 - isq * 4096)) + (i & 1) * 512) =
        make_uint4(pack2(d[0], d[1]), pack2(d[4], d[5]), pack2(d[8], d[9]), pack2(d[12], d[13]));
    }
    bar_sync(B_M + WG, 160);
  }
}

__device__ __forceinline__ void fill16(void* p, uint32_t v) {
  asm volatile("st.global.v4.u32 [%0], {%1,%1,%1,%1};" :: "l"(p), "r"(v) : "memory");
}
__device__ __forceinline__ void g_load(const Params& P, uint32_t sb) {
  const int lane = threadIdx.x & 31, w = __shfl_sync(~0u, (threadIdx.x >> 5) & 3, 0);
  if (w == 2) return;
  if (w < 2) { bar_sync(15, 192); fence_async_smem(); }
  uint32_t fl = 0;
#pragma unroll 1
  for (int n = w == 3 ? LOCK0 : 0; n < STEPS; n++) {
    if (w && n == LOCK0) { grid_wait(1, lds32(sb + S_GEN)); fl = near_half(XB_F, bid()) * 1024; }
    if (w == 3) {
      const uint32_t tag = (uint32_t)(n - LOCK0 + 1) << 24;
      uint32_t v; int it = 0;
      do { asm volatile("ld.relaxed.gpu.global.u32 %0, [%1];" : "=r"(v) : "l"(g_fl + fl + FL_TICK) : "memory"); spin_guard(it); } while (v < tag);
      const uint32_t off = timer_offset<2>(), now = clk(), t0 = now - ((v ^ tag) >> 24 ? DLYG : (now + off - v) & 0xFFFFFF);
      asm volatile("fence.acquire.gpu;" ::: "memory");
      if (lane == 0) T3(11);
      __syncwarp();
      wait_until(t0, DLYG);
      if (lane == 0) T3(4);
      bar_sync(B_OE, 160);
      continue;
    }
    if (w == 0) {
      if (n < NSEG) wait_flags(g_lnflag + n * 16 + (lane & 1) * 8, 1);
    } else if (n >= LAG) {
      wait_flags(g_fl + fl + FL_F + (lane & 1) * 8, n - LAG + 1);
    }
    if (w) { if (lane == 0) T3(12); bar_sync(B_X, 96); }
    fence_async_global();
    const unsigned char* src = g_lnimg + (uint32_t)((w ? NSEG + n - LAG : n) * 36864);
#pragma unroll 1
    for (int ch = 0; ch < 9; ch++) {
      const uint32_t full = sb + G_BAR + ch * 8;
      mbar_wait(full + 128, (n & 1) ^ 1);
      if (w ? n < LAG : n >= NSEG) {
        if (elect()) mbar_arrive(full);
      } else if (elect()) {
        mbar_expect(full, 4096);
        bulk_load(sb + G_RING + ch * 8192 + w * 4096, src + ch * 4096, 4096, full);
      }
    }
  }
}

__device__ __forceinline__ void g_aux(const Params& P, uint32_t sb) {
  const int lane = threadIdx.x & 31, w = (threadIdx.x >> 5) & 3;
  if (w == 1 || w == 2) {
    const int q = g_unit(w - 1);
    uint32_t* f = g_fl + FL_G + q * 8;
#pragma unroll 1
    for (int n = 0; n < STEPS; n++) {
      const uint32_t ln = opaque_tid() & 31;
      uint4* z = (uint4*)g_oacc + (uint32_t)(((n + 1) % ARING) * (16 * DM) + q * 96 + ln);
      fill16(z, 0); fill16(z + 32, 0); fill16(z + 64, 0);
      if (n + 3 >= MRING && q < 80) fill16((uint4*)g_mimg + (uint32_t)(((n + 3) % MRING) * 4096 + q * 32 + ln), SENT);
      bar_sync(B_M + (w - 1), 160);
      if (lane == 0) { T3(w * 2 - 2); fence_async_global(); flag_release(f, n + 1); T3(w * 2 - 1); }
      __syncwarp();
    }
  } else {
    const uint32_t u = (bid() - N_CHAIN) * 2 + (w & 1), r = u / 36 * 16 + (u & 3) * 4 + (lane >> 3);
    uint32_t o = r * (DM / 8) + (u % 36 >> 2) * 8 + ((lane & 7) ^ ((r >> 1) & 3)), fl = 0;
#pragma unroll 1
    for (int k = -LAG - 1; k < STEPS; k++) {
      if (k < NSEG - 1) bar_sync(B_X, 96);
      if (k < LAG || u >= 72) continue;
      if (k == NSEG - 1) { fl = near_half(XB_F, bid()) * 1024; wait_flags(g_fl + fl + FL_F + (lane & 1) * 8, NSEG + 1); }
      const uint4 x = __ldcg((const uint4*)P.out + o);
      if (k >= NSEG - 1) wait_flags(g_fl + fl + FL_OCNT + (max(k, NSEG) % OCRING) * 8, N_O * 3 * (max(k, NSEG) / OCRING + 1));
      const float4* a = (const float4*)g_oacc + ((k % ARING) * (16 * DM) + 8 * DM + u * 64 + lane * 2);
      const float4 p = __ldcg(a), v = __ldcg(a + 1);
      ((uint4*)P.out)[o] = make_uint4(badd2(x.x, pack2(p.x, p.y)), badd2(x.y, pack2(p.z, p.w)), badd2(x.z, pack2(v.x, v.y)), badd2(x.w, pack2(v.z, v.w)));
      o += 4 * DM;
    }
    if ((threadIdx.x & 127) == 0) TS(7);
  }
}

template <int WG, bool HALF, int KS, int N> __device__ __forceinline__ void o_mma(float* d, const uint32_t* a, uint32_t ob) {
  constexpr uint64_t db = desc_sw128(O_RING + (KS >> 2) * 8192 + (KS & 3) * 32);
  constexpr uint64_t da = desc_sw128(O_W + WG * 40960 + (KS < 40 ? KS / 5 * 2 + KS % 5 / 2 : KS - 24) * 2048);
  if constexpr (KS < 40 && !(KS % 5 & 1)) {
    const uint32_t* r = a + (KS / 5 * 3 + KS % 5 / 2) * 4;
    if constexpr (HALF) wg_rs32k<KS != 0, db>(d, r[0], r[1], r[2], r[3], ob); else wg_rs64<KS != 0>(d, r, db);
  } else {
    if constexpr (HALF) wg_ss32k<da, db>(d, ob); else wg_ss64<1>(d, da, db);
  }
  if constexpr (N > 1) o_mma<WG, HALF, KS + 1, N - 1>(d, a, ob);
}
template <int WG, bool HALF, int GR> __device__ __forceinline__ void o_groups(float* d, const uint32_t* a, uint32_t sb, int n, bool more) {
  const uint32_t ob = n < NSEG ? 0 : 256;
  mbar_wait(sb + O_BAR + GR * 8, n & 1);
  if (GR == 0) { if ((threadIdx.x & 127) == 0) T3(13 + WG); __syncwarp(); }
  if (GR == 3 && (WG < 2 || n + 1 < STEPS)) bar_arrive(B_V + (WG + 1) % 3, 256);
  wg_fence();
  o_mma<WG, HALF, GR * 8, 8>(d, a, ob);
  if (GR == 4 && more) o_mma<WG, HALF, 40, 4>(d, a, ob);
  wg_commit();
  if (GR > 0) { wg_wait<1>(); if ((threadIdx.x & 31) == 0) mbar_arrive(sb + O_BAR + 120 + GR * 8); }
  if constexpr (GR < 4) o_groups<WG, HALF, GR + 1>(d, a, sb, n, more);
}
template <int WG, bool HALF> __device__ __forceinline__ void o_step(const uint32_t* a, uint32_t sb, uint32_t st0, int n, bool more) {
  float d[HALF ? 16 : 32];
  if (WG > 0 || n > 0) bar_sync(B_V + WG, 256);
  o_groups<WG, HALF, 0>(d, a, sb, n, more);
  wg_wait<0>();
  if ((threadIdx.x & 31) == 0) mbar_arrive(sb + O_BAR + 128 + 4 * 8);
  if ((threadIdx.x & 127) == 0) T3(WG == 0 ? 1 : WG == 1 ? 8 : 12);
  __syncwarp();
#pragma unroll(HALF ? 1 : 2)
  for (int sl = 0; sl < 2; sl++) {
    mbar_wait(sb + OB_ST + WG * 16 + sl * 8, (n & 1) ^ (WG == 0));
    if (!HALF || sl == (n >= NSEG)) {
#pragma unroll
      for (int nb = 0; nb < 4; nb++) {
        const float* r = d + (HALF ? 0 : sl * 16) + nb * 4;
        const uint32_t ad = st0 + sl * 8192 + nb * 2048;
        sts32(ad, __float_as_uint(r[0]));
        sts32(ad + 256, __float_as_uint(r[1]));
        sts32(ad ^ 32, __float_as_uint(r[2]));
        sts32((ad ^ 32) + 256, __float_as_uint(r[3]));
      }
      fence_async_smem();
    }
    bar_arrive((sl ? B_G : B_M) + WG, 160);
  }
}
template <int WG>
__device__ __forceinline__ void o_math(const Params& P, uint32_t sb) {
  const bool more = bid() < N_CHAIN + N_G + 12;
  const int lane = threadIdx.x & 31, w = (threadIdx.x >> 5) & 3, g = lane >> 2, tq = lane & 3;
  uint32_t a[96];
  mbar_wait(sb + W_BAR + WG * 8, 0);
  load_frags<24>(a, sb + WG * 49152);
  fence_async_smem();
  bar_sync(B_INIT, 416);
  load_wg<OROLE>(P, sb, false, WG, w);
  mbar_wait(sb + W_BAR + WG * 8, 1);
  if ((threadIdx.x & 127) == 0) TS(4);
  const uint32_t st0 = sb + O_ST + tq * 512 + ((w * 16 + g) ^ (tq * 8)) * 4;
#pragma unroll 1
  for (int n = 0; n < STEPS; n++) {
    if (n < LAG || n >= NSEG) o_step<WG, true>(a, sb, st0, n, more); else o_step<WG, false>(a, sb, st0, n, more);
  }
}

__device__ __forceinline__ void o_aux(const Params& P, uint32_t sb) {
  const int i = bid() - N_CHAIN - N_G, ksl = i / 3;
  const int c0 = ksl * 11 - max(ksl - 4, 0), nc = ksl < 4 ? 11 : 10;
  const int lane = threadIdx.x & 31, w = __shfl_sync(~0u, (threadIdx.x >> 5) & 3, 0);
  if (w == 0) {
    bar_sync(B_INIT, 416);
    const uint32_t* f = g_fl + FL_O + near_half(XB_F + 1, bid()) * 1024 + min((c0 & ~1) + lane, (c0 + nc - 1) | 1);
#pragma unroll 1
    for (int n = 0; n < STEPS; n++) {
      const unsigned char* src = g_oimg + (uint32_t)(((n % RING) * N_CHAIN + c0) * 8192);
      wait_flags(f, n + 1);
      if (n >= LAG && n < NSEG) wait_until(clk(), DLYO);
      fence_async_global();
      if (lane == 0) T3(0);
#pragma unroll
      for (int gr = 0; gr < 5; gr++) {
        const uint32_t full = sb + O_BAR + gr * 8, bytes = (gr < 4 ? 2 : nc - 8) * 8192;
        mbar_wait(full + 128, (n & 1) ^ 1);
        if (elect()) {
          if (n < LAG || n >= NSEG) {
            mbar_expect(full, bytes >> 1);
            for (uint32_t o = gr * 16384 + (n < LAG ? 0 : 4096); o < gr * 16384 + bytes; o += 8192) bulk_load(sb + O_RING + o, src + o, 4096, full);
          } else {
            mbar_expect(full, bytes);
            bulk_load(sb + O_RING + gr * 16384, src + gr * 16384, bytes, full);
          }
        }
      }
    }
  } else {
#pragma unroll 1
    for (int n = 0; n < STEPS; n++) {
      float* dst = g_oacc + (uint32_t)((n % ARING) * (64 * DM) + ((i % 3) * 3 + (w - 1 + ksl) % 3) * 1024);
      const bool early = w == 3 && n < NSEG;
      bar_sync(B_M + (w - 1), 160);
      if (lane == 0) {
        T3(w * 2);
        if (n < NSEG) { bulk_reduce(dst, sb + O_ST, 4096); bulk_reduce(dst + 16 * DM, sb + O_ST + 4096, 4096); }
        asm volatile("cp.async.bulk.commit_group;" ::: "memory");
        if (early) {
          asm volatile("cp.async.bulk.wait_group.read 0;" ::: "memory");
          mbar_arrive(sb + OB_ST);
          T3(8 + w);
          bulk_done_inc(g_fl + FL_OCNT + (n % OCRING) * 8);
          T3(w * 2 + 1);
        }
      }
      __syncwarp();
      bar_sync(B_G + (w - 1), 160);
      if (lane == 0) {
        if (n >= LAG) { bulk_reduce(dst + 32 * DM, sb + O_ST + 8192, 4096); bulk_reduce(dst + 48 * DM, sb + O_ST + 12288, 4096); }
        asm volatile("cp.async.bulk.commit_group;\ncp.async.bulk.wait_group.read 1;" ::: "memory");
        if (!early) mbar_arrive(sb + OB_ST + (w % 3) * 16);
        asm volatile("cp.async.bulk.wait_group.read 0;" ::: "memory");
        mbar_arrive(sb + OB_ST + (w % 3) * 16 + 8);
        if (!early) {
          T3(8 + w);
          bulk_done_inc(g_fl + FL_OCNT + (n % OCRING) * 8);
          T3(w * 2 + 1);
        }
      }
      __syncwarp();
    }
  }
}

constexpr uint32_t Y_PITCH = 1168, Y_ROWS = 16 * Y_PITCH;
template <int R> __device__ __forceinline__ void y_rows(uint32_t* y, uint32_t src, uint32_t dst, int w, int bar) {
  const int lane = threadIdx.x & 31;
#pragma unroll
  for (int k = 0; k < 2 * R + 1; k++) {
    const int op = w + k * (16 / R);
    if (k == 2 * R && w >= 4) break;
    uint32_t a, b, c, d;
    ldsm4t(a, b, c, d, src + op * 512 + (lane & 16) * 16 + (lane & 7) * 32 + (lane & 8) * 2);
    stsm4(dst + (lane & 15) * Y_PITCH + op * 32 + (lane & 16), a, b, c, d);
  }
  bar_sync(bar, 512 / R);
  const uint32_t row = dst + ((w & 6) * 2 + (w >> 3) * 2 + (w & 1)) * Y_PITCH + lane * 4;
#pragma unroll
  for (int i = 0; i < 9 * R; i++) y[i] = lds32(row + i / 9 * 2 * Y_PITCH + i % 9 * 128);
}

__device__ __forceinline__ void f_role(const Params& P, uint32_t sb) {
  const int lane = threadIdx.x & 31, w = __shfl_sync(~0u, threadIdx.x >> 5, 0), r0 = (bid() - N_CHAIN - N_G - N_O) * 16;
  if (w == 8) {
    const uint32_t* fo = g_fl + FL_OCNT + near_half(XB_F, bid()) * 1024;
    fence_async_global();
#pragma unroll 1
    for (int n = 0; n < NSEG; n++) {
      bar_sync(2, 288);
      if (elect()) {
        mbar_expect(sb + F_BAR, 36864);
        bulk_load(sb + F_XY, P.X + (size_t)(n * 32 + r0) * DM, 18432, sb + F_BAR);
        bulk_load(sb + F_XY + 18432, g_yT + (size_t)(n * 32 + r0) * DM, 18432, sb + F_BAR);
        mbar_expect(sb + F_BAR + 8, 36864);
        T3(1);
      }
      wait_flags(fo + (n % OCRING) * 8, N_O * 3 * (n / OCRING + 1));
      fence_async_global();
      if (elect()) { bulk_load(sb + F_A, g_oacc + (uint32_t)((n % ARING) * (64 * DM) + r0 * DM), 36864, sb + F_BAR + 8); T3(0); }
    }
  } else if (w == 9) {
#pragma unroll 1
    for (int n = 0; n < NSEG; n++) {
      const uint32_t st = sb + (n & 1) * 36864;
      unsigned char* p = g_lnimg + (uint32_t)((NSEG + n) * 36864 + r0 * 128);
      bar_sync(1, 288);
      if (elect()) {
        T3(2);
#pragma unroll
        for (int i = 0; i < 9; i++) bulk_store(p + i * 4096, st + F_L + i * 2048, 2048);
        asm volatile("cp.async.bulk.commit_group;" ::: "memory");
        bulk_done_inc(g_fl + FL_F + (bid() & 1) * 8);
        T3(3);
        bulk_store(P.out + (size_t)(n * 32 + r0) * DM, st + F_X, 18432);
        asm volatile("cp.async.bulk.commit_group;\ncp.async.bulk.wait_group.read 0;" ::: "memory");
        if (n + 1 == NSEG) bulk_done_inc(g_fl + FL_F + (bid() & 1) * 8);
      }
      __syncwarp();
    }
  } else if (w < 8) {
    const uint32_t row = sb + w * 1152 + lane * 4, acc = sb + F_A + w * 256 + (lane ^ ((w & 6) * 2)) * 8;
    const uint32_t ln = sb + F_L + w * 128 + (((lane >> 2) ^ w) << 4) + (lane & 3) * 4;
#pragma unroll 1
    for (int n = -1; n < NSEG; n++) {
      const uint32_t st = (n & 1) * 36864;
      uint32_t x[18], y[18], l[18];
      if (n >= 0) mbar_wait(sb + F_BAR, n & 1);
#pragma unroll
      for (int i = 0; i < 18; i++) x[i] = lds32(row + F_XY + i / 9 * 9216 + i % 9 * 128);
      y_rows<2>(y, sb + F_XY + 18432, sb + F_Y, w, 3);
      layernorm9<2>(x, l);
#pragma unroll
      for (int i = 0; i < 18; i++) x[i] = badd2(x[i], bmul2(l[i], y[i]));
      if (n >= 0) mbar_wait(sb + F_BAR + 8, n & 1);
      if (threadIdx.x == 0 && n >= 0) T3(4);
      __syncwarp();
      uint2 a[18];
#pragma unroll
      for (int i = 0; i < 18; i++) a[i] = lds64(acc + i / 9 * 2048 + i % 9 * 4096);
#pragma unroll
      for (int i = 0; i < 18; i++) x[i] = badd2(x[i], pack2(__uint_as_float(a[i].x), __uint_as_float(a[i].y)));
      if (n + 1 < NSEG) bar_arrive(2, 288);
      layernorm9<2>(x, l);
#pragma unroll
      for (int i = 0; i < 18; i++) { x[i] = badd2(x[i], bmul2(l[i], y[i])); sts32(row + st + F_X + i / 9 * 9216 + i % 9 * 128, x[i]); }
      layernorm9<2>(x, l);
#pragma unroll
      for (int i = 0; i < 18; i++) sts32(ln + st + i / 9 * 1024 + i % 9 * 2048, l[i]);
      fence_async_smem();
      if (n >= 0) bar_sync(1, 288); else bar_sync(3, 256);
    }
  }
}

constexpr uint32_t P_CH = 147456, P_CHSZ = 12800, P_H = 4352;
static_assert(P_CH + 6 * P_CHSZ <= G_BAR, "prologue smem");

template <int N>
__device__ __forceinline__ void conv_fold(float (*acc)[4], bool hi, uint32_t mine, uint32_t theirs, int bar, int cnt) {
#pragma unroll
  for (int i = 0; i < N / 2; i++) {
    uint4 v;
    v.x = __float_as_uint(hi ? acc[i][0] : acc[i + N / 2][0]); v.y = __float_as_uint(hi ? acc[i][1] : acc[i + N / 2][1]);
    v.z = __float_as_uint(hi ? acc[i][2] : acc[i + N / 2][2]); v.w = __float_as_uint(hi ? acc[i][3] : acc[i + N / 2][3]);
    sts128(mine + i * 512, v);
  }
  bar_sync(bar, cnt);
#pragma unroll
  for (int i = 0; i < N / 2; i++) {
    const uint4 v = lds128(theirs + i * 512);
    acc[i][0] = (hi ? acc[i + N / 2][0] : acc[i][0]) + __uint_as_float(v.x); acc[i][1] = (hi ? acc[i + N / 2][1] : acc[i][1]) + __uint_as_float(v.y);
    acc[i][2] = (hi ? acc[i + N / 2][2] : acc[i][2]) + __uint_as_float(v.z); acc[i][3] = (hi ? acc[i + N / 2][3] : acc[i][3]) + __uint_as_float(v.w);
  }
}
template <int N>
__device__ __forceinline__ void conv_store(const float (*acc)[4], int tile0, uint32_t su, int d, uint32_t dd) {
  const int lane = threadIdx.x & 31, g = lane >> 2, tq = lane & 3;
#pragma unroll
  for (int i = 0; i < N; i++) {
    const uint32_t ad = su + (8 + (tile0 + i) * 8 + g) * 32 + tq * 4, sw = (g & 4) << 2;
    const uint32_t lo = badd2(movmat(pack2(acc[i][0], acc[i][1])), bmul2(lds32(ad + sw), dd));
    const uint32_t hi = badd2(movmat(pack2(acc[i][2], acc[i][3])), bmul2(lds32(ad + (sw ^ 16)), dd));
    ((uint2*)g_yT)[(((tile0 + i) * 8 + g) * DM + d) * 4 + tq] = make_uint2(lo, hi);
  }
}

__device__ __forceinline__ void prologue(const Params& P, uint32_t sb) {
  const int b = bid(), tid = threadIdx.x, lane = tid & 31, warp = tid >> 5, t0 = b * 16;
  const bool isg = b >= N_CHAIN && b < N_CHAIN + N_G;
  const int nch = isg ? 2 : b < 128 ? 6 : 0, chb = b < N_CHAIN ? b * 6 : isg ? b * 2 + 256 : b * 6 - 192;
  const uint32_t tstart = clk();
  if (tid < 288) {
    if (b < 128) {
      const int c = (tid >> 1) * 4, tt = t0 + (tid & 1) * 8;
      uint2 kr[11], vr[8];
#pragma unroll
      for (int i = 0; i < 11; i++) { const int t = tt + i - 3; kr[i] = t >= 0 ? __ldg((const uint2*)(P.K + (size_t)t * DM + c)) : make_uint2(0, 0); }
#pragma unroll
      for (int i = 0; i < 8; i++) vr[i] = __ldg((const uint2*)(P.V + (size_t)(tt + i) * DM + c));
#pragma unroll
      for (int e = 0; e < 2; e++) {
        const uint4 sh = __ldg((const uint4*)(P.shift + c * 4) + e);
        const uint32_t s0 = __byte_perm(sh.x, sh.z, 0x5410), s1 = __byte_perm(sh.x, sh.z, 0x7632);
        const uint32_t s2 = __byte_perm(sh.y, sh.w, 0x5410), s3 = __byte_perm(sh.y, sh.w, 0x7632);
        uint32_t v[8];
#pragma unroll
        for (int i = 0; i < 8; i++) {
          const uint32_t k3 = e ? kr[i].y : kr[i].x, k2 = e ? kr[i + 1].y : kr[i + 1].x, k1 = e ? kr[i + 2].y : kr[i + 2].x, k0 = e ? kr[i + 3].y : kr[i + 3].x;
          v[i] = bmul2(badd2(badd2(badd2(bmul2(k3, s3), bmul2(k2, s2)), bmul2(k1, s1)), bmul2(k0, s0)), e ? vr[i].y : vr[i].x);
        }
        *(uint4*)(g_kvT + (size_t)(c + 2 * e) * KVP + tt) =
          make_uint4(__byte_perm(v[0], v[1], 0x5410), __byte_perm(v[2], v[3], 0x5410), __byte_perm(v[4], v[5], 0x5410), __byte_perm(v[6], v[7], 0x5410));
        *(uint4*)(g_kvT + (size_t)(c + 2 * e + 1) * KVP + tt) =
          make_uint4(__byte_perm(v[0], v[1], 0x7632), __byte_perm(v[2], v[3], 0x7632), __byte_perm(v[4], v[5], 0x7632), __byte_perm(v[6], v[7], 0x7632));
      }
    }
  } else if (tid < 384) {
    const int t = tid - 288;
    for (int i = b * 96 + t; i < 16 * DM; i += N_CTA * 96) ((uint4*)g_oacc)[i] = make_uint4(0, 0, 0, 0);
    if (b * 96 + t < 128 * 8) g_lnflag[b * 96 + t] = 0;
    if (t == 95) sts32(sb + S_GEN, ld_acquire(g_gbar));
    __syncwarp();
    wait_until(tstart, PREFH);
    for (int i = t; i < 32 * nch; i += 96) asm volatile("prefetch.global.L2 [%0];" :: "l"(P.Hk + (size_t)chb * SEQ + i * 64));
  }
  if (warp < 12) {
    bar_arrive(10, 416);
    if (tid == 128) TS(14);
    const int ch = 5 - (warp >> 1), sub = warp & 1, d = chb + ch;
    const uint32_t su = sb + P_CH + ch * P_CHSZ;
    if (ch < nch) {
      const uint32_t* hs = (const uint32_t*)(P.Hk + (size_t)d * SEQ);
#pragma unroll
      for (int q = sub * 32 + lane; q < 256; q += 64) {
        const uint4 c = __ldg((const uint4*)hs + q);
        const uint32_t prev = q ? __ldg(hs + 4 * q - 1) : 0u;
        sts128(su + P_H + 32 + q * 16, make_uint4(__byte_perm(c.x, prev, 0x7610), __byte_perm(c.y, c.x, 0x7610), __byte_perm(c.z, c.y, 0x7610), __byte_perm(c.w, c.z, 0x7610)));
        sts128(su + P_H + 4224 + q * 16, make_uint4(__byte_perm(c.x, 0, 0x1032), __byte_perm(c.y, 0, 0x1032), __byte_perm(c.z, 0, 0x1032), __byte_perm(c.w, 0, 0x1032)));
      }
      if (sub == 1 && lane == 0) sts32(su + P_CHSZ - 16, __bfloat16_as_ushort(P.Dk[d]) * 0x10001u);
      if (sub == 0 && lane < 20) sts128(su + (lane < 16 ? lane * 16 : P_H + (lane & 2) * 2096 + (lane & 1) * 16), make_uint4(0, 0, 0, 0));
    }
    bar_sync(11, 416);
    if (ch < nch) {
#pragma unroll
      for (int q = sub * 32 + lane; q < 256; q += 64) {
        const int row = (q >> 1) + 8;
        sts128(su + row * 32 + (((q & 1) ^ ((row >> 2) & 1)) << 4), __ldcg((const uint4*)(g_kvT + (size_t)d * KVP) + q));
      }
    }
    const int g = lane >> 2, tq = lane & 3;
    const uint32_t sh = su + P_H + (g & 1) * 4192 + (8 + (g >> 1) - tq) * 4;
    float acc[16][4];
#pragma unroll
    for (int i = 0; i < 16; i++) { acc[i][0] = acc[i][1] = acc[i][2] = acc[i][3] = 0.f; }
    auto u_addr = [&](int res) {
      const int row = 8 - res + ((lane >> 4) << 3) + (lane & 7);
      return su + row * 32 + ((((lane >> 3) & 1) ^ ((row >> 2) & 1)) << 4);
    };
    if (ch < nch) {
      bar_sync(1 + ch, 64);
      if (tid == 352) TS(11);
      if (sub) {
#pragma unroll 4
        for (int res = 0; res < 8; res++) {
          uint32_t b0, b1, b2, b3;
          ldsm4(b0, b1, b2, b3, u_addr(res));
          const uint32_t r0 = lds32(sh + res * 32);
          mma16(acc[0], r0, lds32(sh + res * 32 + 16), lds32(sh + res * 32 - 16), r0, b0, b1);
        }
        conv_store<1>(acc, 0, su, d, lds32(su + P_CHSZ - 16));
      }
    }
    bar_arrive(12, 416);
    if (isg && warp < 8) { while ((int)(clk() - tstart - S1G) < 0) __nanosleep(200); load_wg<GROLE>(P, sb, true, warp >> 2, warp & 3); }
    if (ch < nch) {
#pragma unroll 1
      for (int res = sub * 4; res < sub * 4 + 4; res++) {
        uint32_t bf[16][2];
        const uint32_t ad = u_addr(res);
#pragma unroll
        for (int f = 0; f < 16; f += 2) ldsm4(bf[f][0], bf[f][1], bf[f + 1][0], bf[f + 1][1], ad + f * 256);
#pragma unroll
        for (int k = 0; k < 16; k++) {
          const int jj = k & 1 ? k >> 1 : 15 - (k >> 1);
          const uint32_t ah = sh + (8 * jj + res) * 32;
          const uint32_t r0 = lds32(ah), r1 = lds32(ah + 16), rm = lds32(ah - 16);
#pragma unroll
          for (int i = max(jj, 1); i < 16; i++) mma16(acc[i], r0, r1, rm, r0, bf[i - jj][0], bf[i - jj][1]);
        }
      }
      bar_sync(1 + ch, 64);
      if (tid == 352) TS(12);
      const uint32_t xb = su + P_H + lane * 16, dd = lds32(su + P_CHSZ - 16);
      conv_fold<16>(acc, sub, xb + sub * 4096, xb + (sub ^ 1) * 4096, 1 + ch, 64);
      conv_store<8>(acc, sub * 8, su, d, dd);
    }
  } else {
    for (int i = b; i < 194 + MRING * 5; i += N_CTA) {
      const int n = (i - 194) / 5, r = (i - 194) % 5, blk = i < 192 ? i / 6 * 8 + i % 6 : i < 194 ? XB_F + i - 192 : XB_M + n * 8 + r;
      const uint32_t fill = i < 194 ? 0u : SENT;
#pragma unroll 1
      for (int q = tid - 384; q < 256 && warp < 15; q += 96) {
        uint4 v = make_uint4(fill, fill, fill, fill);
        if (i >= 194 && n == 0 && (r > 0 || q < 128)) {
          const bf16* m = P.mem0 + (max(r * 8 - 4, 0) + (q >> 5)) * 16 + ((q >> 1) & 1) * 8 + ((q >> 2) & 7);
          v.x = pack2(__bfloat162float(m[0]), __bfloat162float(m[DM])); v.y = pack2(__bfloat162float(m[2 * DM]), __bfloat162float(m[3 * DM]));
          v.z = pack2(__bfloat162float(m[4 * DM]), __bfloat162float(m[5 * DM])); v.w = pack2(__bfloat162float(m[6 * DM]), __bfloat162float(m[7 * DM]));
        }
        g_xb[blk * 512 + q] = v;
        g_xb[blk * 512 + 256 + q] = v;
      }
    }
    if (tid < 388) g_xb[XB_REF * 512 + (tid & 2) * 128 + (b & ~1) + (tid & 1)] = make_uint4(0, 0, 0, 0);
    else if (tid < 392 && b < N_GRP) g_xb[(b * 8 + 7) * 512 + (tid & 2) * 128 + (tid & 1)] = make_uint4(0, 0, 0, 0);
    if (warp < 15) { bar_arrive(9, 128); bar_sync(7, 96); }
    if (tid == 384) TS(8);
    if (warp == 12) {
      const bf16* w = lane < 6 ? (lane % 3 == 0 ? P.Wk : lane % 3 == 1 ? P.Wv : P.Wq) + (((b >> 5) * 2 + lane / 3) * 32 + (b & 31)) * 2048
                               : (lane < 8 ? P.Wo + (lane - 6) * (9 * 131072) : P.X) + b * 2048;
      uint32_t t = tstart + PREF0;
      if ((int)(clk() - t) > 0) t = clk();
#pragma unroll 1
      for (int st = 0; st < 9 && b < N_CHAIN; st++) {
#pragma unroll 1
        for (int i = 0; i < 9; i++, t += PACE) {
          wait_until(t, 0);
          if (lane == st) asm volatile("cp.async.bulk.prefetch.L2.global [%0], 4096;" :: "l"(w + i * (lane < 6 ? 262144 : 131072)) : "memory");
        }
      }
      if (lane == 0) TS(10);
    } else if (warp == 15) {
      bar_sync(10, 416);
      if (lane == 0) { grid_arrive(0); if (nch) grid_wait(0, lds32(sb + S_GEN)); }
      __syncwarp();
      bar_arrive(11, 416);
      if (lane == 0) TS(1);
      bar_sync(9, 128);
      bar_sync(12, 416);
      if (lane == 0) { TS(16); grid_arrive(2); TS(17); }
    } else if (lane == 0) {
      if (warp == 13 || (warp == 14 && b < N_GRP)) {
        uint32_t* p = (uint32_t*)(g_xb + (warp == 13 ? XB_REF * 512 + b : (b * 8 + 7) * 512));
        int votes = 0;
        for (int rep = 0; rep < 24 && abs(votes) < 7; rep++) {
          uint32_t v0, v1, c0, c1;
          asm volatile("atom.relaxed.gpu.global.add.u32 %0, [%4], 1;\n atom.relaxed.gpu.global.add.u32 %1, [%5], 1;\n"
                       "{.reg .pred p; setp.eq.u32 p, %0, 0x7ffffff3; @p trap; mov.u32 %2, %%clock; setp.eq.u32 p, %1, 0x7ffffff3; @p trap; mov.u32 %3, %%clock;}"
                       : "=&r"(v0), "=&r"(v1), "=&r"(c0), "=&r"(c1) : "l"(p + (rep & 1) * 1024), "l"(p + ((rep & 1) ^ 1) * 1024) : "memory");
          votes += ((c1 - c0 > 80u) == (rep & 1)) ? 1 : -1;
        }
        if (warp == 13) { g_side[b] = votes > 0; TS(9); } else g_near[b] = votes > 0;
      }
    }
    __syncwarp();
    if (warp > 12 && b < N_CHAIN) {
      while ((int)(clk() - tstart - S1DLY) < 0) __nanosleep(200);
      for (int k = warp - 13; k < 8; k += 3) load_wg<CHAIN>(P, sb, true, 1 - k / 4, k & 3);
    }
  }
  if (b < N_CHAIN + N_G && (warp < 8 || (isg && warp >= 12))) bar_arrive(0, 512); else bar_sync(0, 512);
  if (tid == 352) TS(2);
}

__device__ __forceinline__ void publish_y() {
  if (threadIdx.x == 383) { grid_arrive(1); TS(18); }
  __syncwarp();
}

template <int R> __device__ __forceinline__ void ln_tiles(const Params& P, uint32_t sb) {
  const int lane = threadIdx.x & 31, w = (threadIdx.x >> 5) & (16 / R - 1), half = R == 1 ? 0 : threadIdx.x >> 8, u = N_CTA - 1 - bid();
  const int first = R == 1 ? u : 46 - 2 * u + half, step = R == 1 ? 4 : 40, last = R == 1 ? 8 : 128;
  const uint32_t raw = sb + P_CH + half * (18432 + Y_ROWS), mb = sb + T_BAR + (R - 1 + half) * 8;
  const bool lead = w == 16 / R - 1 && lane == 0;
  auto load_y = [&](const bf16* src, int tile) {
    fence_async_global();
    mbar_expect(mb, 18432);
    bulk_load(raw, src + (size_t)tile * 16 * DM, 18432, mb);
  };
  uint32_t nx[9 * R];
  auto load_x = [&](int tile) {
#pragma unroll
    for (int i = 0; i < 9 * R; i++) nx[i] = __ldg((const uint32_t*)(P.X + (size_t)(tile * 16 + w + i / 9 * 8) * DM) + i % 9 * 32 + lane);
  };
  load_x(first);
  if (R == 2) {
    if (lead) { grid_wait(1, lds32(sb + S_GEN)); if (u > 3) TS(13); load_y(g_yT, first); }
    __syncwarp();
  }
#pragma unroll 1
  for (int tile = first, real = R - 1, ph = 0; tile < last; tile += real * step, real = 1, ph ^= 1) {
    uint32_t x[9 * R], l[9 * R], y[9 * R];
    const bool ts = threadIdx.x == 0 && (R == 1 ? tile == first : u > 3 && tile == first + step);
    if (ts) TS(26);
#pragma unroll
    for (int i = 0; i < 9 * R; i++) x[i] = nx[i];
    layernorm9<R>(x, l);
    if (real && tile + step < last) load_x(tile + step);
    if (R == 2 && tile == first + step && u >= N_F && w < 6) load_wg<OROLE>(P, sb, true, w >> 1, half * 2 + (w & 1));
    if (R == 1 && tile == first && lead) {
      if (real) grid_wait(2, lds32(sb + S_GEN));
      TS(13);
      load_y(real ? g_yT : P.Hk, tile);
    }
    bar_sync(13 + half, 512 / R);
    mbar_wait(mb, ph);
    if (ts) TS(28);
    y_rows<R>(y, raw, raw + 18432, w, 13 + half);
    if (ts) TS(29);
    if (lead && real && tile + step < last) { fence_async_smem(); load_y(g_yT, tile + step); }
    __syncwarp();
#pragma unroll
    for (int i = 0; i < 9 * R; i++) x[i] = badd2(x[i], bmul2(l[i], y[i]));
    layernorm9<R>(x, l);
    if (ts && l[0] != 0x12345) TS(30);
#pragma unroll
    for (int r = 0; r < R; r++) store_ln_row(0, tile * 16 + w + r * 8, l + r * 9);
    if (R == 1) {
      __syncthreads();
      if (threadIdx.x == 32 && real) { if (tile < 4) TS(19); st_release(g_lnflag + tile * 8, 1); if (tile < 4) TS(20); }
      __syncwarp();
    }
    if (ts) TS(31);
  }
  if (R == 2) {
    __syncthreads();
    if (threadIdx.x >= 506) {
      asm volatile("fence.acq_rel.gpu;" ::: "memory");
      st_relaxed_if(g_lnflag + ((first ^ (lane & 1)) + (lane - 26) / 2 * step) * 8, 1, true);
    }
    __syncwarp();
    fence_async_smem();
    if (threadIdx.x == 0) TS(15);
  }
}

__global__ void __cluster_dims__(2, 1, 1) __launch_bounds__(512, 1) k_main(const __grid_constant__ Params P) {
  extern __shared__ __align__(1024) unsigned char smem[];
  const uint32_t sb = (uint32_t)__cvta_generic_to_shared(smem);
  const int b = bid(), wg = threadIdx.x >> 7;
  if ((threadIdx.x & 127) == 0) TS(0);
  if (threadIdx.x == 480) {
    if ((sb & 0xFFFFFF) != SBASE) __trap();
    for (int i = 0; i < 6; i++) mbar_init(sb + W_BAR + i * 8, 1);
    if (b < N_CHAIN) {
      mbar_init(sb + CB_FULL, 1); mbar_init(sb + CB_FULL + 8, 1);
      mbar_init(sb + CB_REF, 1);
      mbar_init(sb + CB_SX, 1); mbar_init(sb + CB_OX, 1); mbar_init(sb + CB_XX, 1); mbar_init(sb + CB_Q, 2); mbar_init(sb + CB_VF, 1);
      sts32(sb + C_BAD, 0);
      for (int i = 0; i < 11; i++) mbar_init(sb + CB_M + i * 8, i == 0 ? 5 : i == 5 ? 2 : 1);
    } else if (b < N_CHAIN + N_G) {
      for (int i = 0; i < 9; i++) { mbar_init(sb + G_BAR + i * 8, 2); mbar_init(sb + G_BAR + 128 + i * 8, 8); }
    } else if (b < N_CHAIN + N_G + N_O) {
      for (int i = 0; i < 5; i++) { mbar_init(sb + O_BAR + i * 8, 1); mbar_init(sb + O_BAR + 128 + i * 8, 12); }
      for (int i = 0; i < 6; i++) mbar_init(sb + OB_ST + i * 8, 1);
    } else {
      mbar_init(sb + F_BAR, 1); mbar_init(sb + F_BAR + 8, 1);
    }
    asm volatile("fence.mbarrier_init.release.cluster;" ::: "memory");
    fence_async_smem();
  }
  __syncwarp();
  asm volatile("barrier.cluster.arrive.relaxed.aligned;" ::: "memory");
  prologue(P, sb);
  asm volatile("barrier.cluster.wait.aligned;" ::: "memory");
  fence_async_smem();
  if (b >= N_CHAIN + N_G) publish_y();
  if (b >= 128) ln_tiles<1>(P, sb);
  if (b >= N_CHAIN + N_G) ln_tiles<2>(P, sb);
  if ((threadIdx.x & 127) == 0) TS(3);
  if (b < N_CHAIN) {
    if (wg < 2) { reg_inc<200>(); chain_proj(P, sb); }
    else if (wg == 2) { reg_dec<88>(); publish_y(); chain_attn(P, sb); }
    else { reg_dec<24>(); chain_aux(P, sb); }
  } else if (b < N_CHAIN + N_G) {
    if (wg == 0) { reg_inc<232>(); g_math<0>(P, sb); }
    else if (wg == 1) { reg_inc<232>(); g_math<1>(P, sb); }
    else if (wg == 2) {
      reg_dec<24>();
      for (int i = threadIdx.x & 127; i < 9 * 256; i += 128) sts128(sb + G_RING + 4096 + (i >> 8) * 8192 + (i & 255) * 16, make_uint4(0, 0, 0, 0));
      fence_async_smem();
      bar_arrive(15, 192);
      publish_y();
      g_aux(P, sb);
    }
    else { reg_dec<24>(); g_load(P, sb); }
  } else if (b < N_CHAIN + N_G + N_O) {
    if (wg == 0) { reg_inc<160>(); o_math<0>(P, sb); }
    else if (wg == 1) { reg_inc<160>(); o_math<1>(P, sb); }
    else if (wg == 2) { reg_inc<160>(); o_math<2>(P, sb); }
    else { reg_dec<32>(); o_aux(P, sb); }
  } else {
    f_role(P, sb);
  }
}

}

extern "C" void kernel_launch(void* const* d_in, const int* in_sizes, int n_in, void* d_out, int out_size) {
  typedef CUresult (*Encode)(CUtensorMap*, CUtensorMapDataType, cuuint32_t, void*, const cuuint64_t*, const cuuint64_t*, const cuuint32_t*, const cuuint32_t*,
                             CUtensorMapInterleave, CUtensorMapSwizzle, CUtensorMapL2promotion, CUtensorMapFloatOOBfill);
  static Encode encode = nullptr;
  if (!encode) cudaGetDriverEntryPoint("cuTensorMapEncodeTiled", (void**)&encode, cudaEnableDefault);
  Params P;
  for (int i = 0; i < 11; i++) {
    const bool wo = i == 6 || i == 7;
    const cuuint64_t cols = wo ? DM : HD, rows = HD + DM - cols, pitch = cols * 2;
    const cuuint64_t dim[4][5] = {{cols, 2, 8, 2, 18}, {cols, 16, 1, 1, rows / 16}, {cols, 2, 4, 4, rows / 32}, {64, 16, 64, 2, 18}};
    const cuuint64_t stride[4][4] = {{8 * pitch, pitch, 16 * pitch, 32 * pitch}, {pitch, pitch, pitch, 16 * pitch},
                                     {pitch, 8 * pitch, 2 * pitch, 32 * pitch}, {pitch, 128, 16 * pitch, 32 * pitch}};
    const cuuint32_t box[4][5] = {{64, 2, 8, 1, 18}, {64, 16, 1, 1, 1}, {64, 2, 4, 2, 1}, {64, 16, 2, 1, 18}}, one[5] = {1, 1, 1, 1, 1};
    const int k = i < 3 ? 0 : i < 7 ? 1 : i < 8 ? 2 : 3;
    encode(&P.map[i], CU_TENSOR_MAP_DATA_TYPE_BFLOAT16, 5, d_in[wo ? 11 : 8 + (i & 7) % 3], dim[k], stride[k], box[k], one,
           CU_TENSOR_MAP_INTERLEAVE_NONE, CU_TENSOR_MAP_SWIZZLE_128B, CU_TENSOR_MAP_L2_PROMOTION_L2_128B, CU_TENSOR_MAP_FLOAT_OOB_FILL_NONE);
  }
  P.X = (const bf16*)d_in[0]; P.K = (const bf16*)d_in[1]; P.V = (const bf16*)d_in[2];
  P.shift = (const bf16*)d_in[3]; P.Hk = (const bf16*)d_in[4]; P.Dk = (const bf16*)d_in[5];
  P.mem0 = (const bf16*)d_in[7];
  P.Wq = (const bf16*)d_in[8]; P.Wk = (const bf16*)d_in[9]; P.Wv = (const bf16*)d_in[10]; P.Wo = (const bf16*)d_in[11];
  P.out = (bf16*)d_out;
  for (int i = 0; i < 30; i++) P.dly[i] = h_dly[i];
  cudaFuncSetAttribute(k_main, cudaFuncAttributeMaxDynamicSharedMemorySize, SMEM_BYTES);
  k_main<<<N_CTA, 512, SMEM_BYTES>>>(P);
}
```

```cpp
#include <cuda.h>
#include <cuda_runtime.h>
#include <cuda_bf16.h>
#include <stdint.h>

namespace {

typedef __nv_bfloat16 bf16;

constexpr int SEQ = 2048, DM = 576, HD = 4096, NSEG = 64;
constexpr int LAG = 7, STEPS = NSEG + LAG, RING = 8;
constexpr int LOCK0 = 3, QRING = LOCK0 + 1;
static_assert(LAG < RING, "ring");
constexpr int N_CHAIN = 64, N_G = 48, N_O = 18, N_F = 2;
constexpr uint32_t SBASE = 1024;
constexpr uint32_t SENT = 0xFFFFFFFFu;
constexpr int SPIN_MAX = 1 << 22;

__device__ __forceinline__ uint32_t bid() {
  uint32_t b;
  asm volatile("mov.u32 %0, %%ctaid.x;" : "=r"(b));
  return b < 6 ? b + 106 : b < 8 ? b + 122 : b < 114 ? b - 8 : b < 130 ? b - 2 : b;
}
__device__ __forceinline__ uint32_t chain_id() { return blockIdx.x - 8; }
constexpr int KVP = SEQ + 64;
__device__ __align__(1024) bf16 g_kvT[DM * KVP];
__device__ __align__(1024) bf16 g_yT[DM * SEQ];
__device__ __align__(1024) unsigned char g_lnimg[2 * NSEG * 9 * 4096];
__device__ __align__(1024) unsigned char g_qkv[QRING * N_CHAIN * 24576];
__device__ __align__(1024) unsigned char g_oimg[RING * N_CHAIN * 8192];
constexpr int ARING = 16;
static_assert(ARING >= LAG + 9, "accumulator ring");
__device__ __align__(1024) float g_oacc[ARING * 64 * DM];
constexpr int MRING = LAG + 4, N_GRP = 32 + MRING + 1;
constexpr int XB_M = 256, XB_F = XB_M + MRING * 8, XB_REF = XB_F + 2, N_CTA = N_CHAIN + N_G + N_O + N_F;
__device__ __align__(65536) uint4 g_xb[N_GRP * 4096];
#define g_mimg ((uint32_t*)(g_xb + XB_M * 512))
__device__ uint32_t g_near[N_GRP];
__device__ uint32_t g_side[N_CTA];
__device__ __align__(128) uint32_t g_gbar[3 * 32];
constexpr int FL_G = 0, FL_F = 96 * 8, FL_OCNT = FL_F + 2 * 8, OCRING = 16, FL_TICK = 992, FL_O = 2048, FL_SYNC = FL_O + 128;
static_assert(FL_OCNT + OCRING * 8 <= FL_TICK, "flag block");
#define g_fl ((uint32_t*)(g_xb + XB_F * 512))
__device__ __align__(1024) uint32_t g_lnflag[128 * 8];
#define TS(slot)

#define CNT(slot, tries)
#define T3(slot)
#define TR(slot)
#define TRV(slot, val)
#define TRD(slot, dep)
#define TRSYNC()
#define TRDUMP(n)
#define CLK(t) "{.reg .b64 x; .reg .b32 h; mov.u64 x, %%clock64; mov.b64 {" t ", h}, x;}"
__device__ __forceinline__ uint32_t clk() { uint32_t t; asm volatile(CLK("%0") : "=r"(t) :: "memory"); return t; }
__device__ __forceinline__ void wait_until(uint32_t t0, uint32_t d) {
  asm volatile("{.reg .pred p; .reg .u32 t;\n"
               "W: " CLK("t") " sub.u32 t, t, %0; setp.lt.s32 p, t, 0; @p bra.uni W;}"
               :: "r"(t0 + d) : "memory");
}
__device__ __forceinline__ uint32_t pack2(float lo, float hi) {
  uint32_t r; asm("cvt.rn.bf16x2.f32 %0, %1, %2;" : "=r"(r) : "f"(hi), "f"(lo)); return r;
}
__device__ __forceinline__ float bf_lo(uint32_t v) { return __uint_as_float(v << 16); }
__device__ __forceinline__ float bf_hi(uint32_t v) { return __uint_as_float(v & 0xFFFF0000u); }

__device__ __forceinline__ void st_b128(void* p, uint32_t a, uint32_t b, uint32_t c, uint32_t d) {
  asm volatile("{.reg .b128 v; mov.b128 v, {%1,%2,%3,%4}; st.relaxed.gpu.global.b128 [%0], v;}" :: "l"(p), "r"(a), "r"(b), "r"(c), "r"(d) : "memory");
}
__device__ __forceinline__ void st_relaxed_if(void* p, uint32_t a, bool on) {
  asm volatile("{.reg .pred p; setp.ne.u32 p, %2, 0; @p st.relaxed.gpu.global.u32 [%0], %1;}" :: "l"(p), "r"(a), "r"((uint32_t)on) : "memory");
}
__device__ __forceinline__ uint32_t ld_acquire(const uint32_t* p) {
  uint32_t v; asm volatile("ld.acquire.gpu.global.u32 %0, [%1];" : "=r"(v) : "l"(p) : "memory"); return v;
}
__device__ __forceinline__ void st_release(uint32_t* p, uint32_t v) {
  asm volatile("st.release.gpu.global.u32 [%0], %1;" :: "l"(p), "r"(v) : "memory");
}
__device__ __forceinline__ void bulk_reduce(float* dst, uint32_t src, uint32_t bytes) {
  asm volatile("cp.reduce.async.bulk.global.shared::cta.bulk_group.add.f32 [%0], [%1], %2;" :: "l"(dst), "r"(src), "r"(bytes) : "memory");
}
__device__ __forceinline__ void bulk_done_inc(uint32_t* p) {
  asm volatile("cp.async.bulk.wait_group 0;\n"
               "fence.proxy.async.global;\nfence.release.gpu;\n"
               "red.relaxed.gpu.global.add.u32 [%0], 1;\nred.relaxed.gpu.global.add.u32 [%0+4096], 1;" :: "l"(p) : "memory");
}
__device__ __forceinline__ void flag_release(uint32_t* p, uint32_t v) {
  asm volatile("fence.release.gpu;\nst.relaxed.gpu.global.u32 [%0], %1;\nst.relaxed.gpu.global.u32 [%0+4096], %1;" :: "l"(p), "r"(v) : "memory");
}
__device__ __forceinline__ void spin_guard(int& it) {
  asm volatile("{.reg .pred p; add.s32 %0, %0, 1; setp.gt.s32 p, %0, %1; @p trap;}" : "+r"(it) : "n"(SPIN_MAX));
}
__device__ __forceinline__ void wait_flags(const uint32_t* p, uint32_t v) {
  int it = 0;
  while (true) {
    uint32_t x; asm volatile("ld.relaxed.gpu.global.u32 %0, [%1];" : "=r"(x) : "l"(p) : "memory");
    if (__all_sync(~0u, x >= v)) break;
    spin_guard(it);
  }
  asm volatile("fence.acquire.gpu;" ::: "memory");
}
__device__ __forceinline__ uint32_t timer_sample() {
  uint32_t g;
  asm volatile("{.reg .b64 x; .reg .b32 h; mov.u64 x, %%globaltimer; mov.b64 {%0, h}, x;}" : "=r"(g) :: "memory");
  return (g >> 5) * 57 - clk();
}
template <int N> __device__ __forceinline__ uint32_t timer_offset() {
  const uint32_t base = timer_sample();
  int best = 0;
#pragma unroll 1
  for (int i = 0; i < N; i++) {
    const int a = timer_sample() - base, b = timer_sample() - base, c = timer_sample() - base;
    best = max(max(best, a), max(b, c));
  }
  return base + best;
}
__device__ __forceinline__ void grid_arrive(int i) {
  asm volatile("red.release.gpu.global.add.u32 [%0], %1;" :: "l"(g_gbar + i * 32), "r"(bid() ? 1u : 257u - N_CTA) : "memory");
}
__device__ __forceinline__ void grid_wait(int i, uint32_t gen) {
  int it = 0;
  while (((ld_acquire(g_gbar + i * 32) ^ gen) >> 8) == 0) spin_guard(it);
}
__device__ __forceinline__ bool elect() {
  uint32_t r; asm volatile("{.reg .pred p; elect.sync _|p, -1; selp.u32 %0, 1, 0, p;}" : "=r"(r)); return r;
}
__device__ __forceinline__ void bar_sync(int id, int cnt) { asm volatile("bar.sync %0, %1;" :: "r"(id), "r"(cnt) : "memory"); }
__device__ __forceinline__ void bar_arrive(int id, int cnt) { asm volatile("bar.arrive %0, %1;" :: "r"(id), "r"(cnt) : "memory"); }
template <int id, int cnt> __device__ __forceinline__ void bar_arrive_after(uint32_t a, uint32_t b) {
  asm volatile("{.reg .pred p; setp.ne.u32 p, %2, 0xfff12345; setp.ne.and.u32 p, %3, 0xfff12345, p; @p bar.arrive %0, %1;}" :: "n"(id), "n"(cnt), "r"(a), "r"(b) : "memory");
}
template <int id, int cnt> __device__ __forceinline__ void bar_sync_after(uint32_t a) {
  asm volatile("{.reg .pred p; setp.ne.u32 p, %2, 0xfff12345; @p bar.sync %0, %1;}" :: "n"(id), "n"(cnt), "r"(a) : "memory");
}
__device__ __forceinline__ void fence_async_smem() { asm volatile("fence.proxy.async.shared::cta;" ::: "memory"); }
__device__ __forceinline__ void fence_async_global() { asm volatile("fence.proxy.async.global;" ::: "memory"); }
__device__ __forceinline__ void mbar_init(uint32_t mb, int cnt) { asm volatile("mbarrier.init.shared::cta.b64 [%0], %1;" :: "r"(mb), "r"(cnt) : "memory"); }
__device__ __forceinline__ void mbar_arrive(uint32_t mb) { asm volatile("mbarrier.arrive.shared::cta.b64 _, [%0];" :: "r"(mb) : "memory"); }
__device__ __forceinline__ void mbar_expect(uint32_t mb, uint32_t bytes) {
  asm volatile("mbarrier.arrive.expect_tx.shared::cta.b64 _, [%0], %1;" :: "r"(mb), "r"(bytes) : "memory");
}
__device__ __forceinline__ void mbar_wait(uint32_t mb, uint32_t parity) {
  asm volatile("{.reg .pred p;\nW: mbarrier.try_wait.parity.shared::cta.b64 p, [%0], %1;\n@!p bra W;}" :: "r"(mb), "r"(parity) : "memory");
}
template <int K> __device__ __forceinline__ void mbar_wait_step(uint32_t mb, int n) {
  asm volatile("{.reg .pred p; .reg .b32 t; add.u32 t, %1, %2; and.b32 t, t, 1;\nW: mbarrier.try_wait.parity.shared::cta.b64 p, [%0], t;\n@!p bra W;}" :: "r"(mb), "r"(n), "n"(2 * K) : "memory");
}
__device__ __forceinline__ void bulk_load(uint32_t dst, const void* src, uint32_t bytes, uint32_t mb) {
  asm volatile("cp.async.bulk.shared::cluster.global.mbarrier::complete_tx::bytes [%0], [%1], %2, [%3];" :: "r"(dst), "l"(src), "r"(bytes), "r"(mb) : "memory");
}
__device__ __forceinline__ void bulk_store(void* dst, uint32_t src, uint32_t bytes) {
  asm volatile("cp.async.bulk.global.shared::cta.bulk_group [%0], [%1], %2;" :: "l"(dst), "r"(src), "r"(bytes) : "memory");
}
__device__ __forceinline__ uint32_t mapa(uint32_t a, uint32_t rank) {
  uint32_t r; asm("mapa.shared::cluster.u32 %0, %1, %2;" : "=r"(r) : "r"(a), "r"(rank)); return r;
}
__device__ __forceinline__ void st_async4(uint32_t dst, float a, float b, float c, float d, uint32_t mb) {
  asm volatile("st.async.shared::cluster.mbarrier::complete_tx::bytes.v4.f32 [%0], {%1,%2,%3,%4}, [%5];" :: "r"(dst), "f"(a), "f"(b), "f"(c), "f"(d), "r"(mb) : "memory");
}
__device__ __forceinline__ void st_async1(uint32_t dst, uint32_t a, uint32_t mb) {
  asm volatile("st.async.shared::cluster.mbarrier::complete_tx::bytes.u32 [%0], %1, [%2];" :: "r"(dst), "r"(a), "r"(mb) : "memory");
}
__device__ __forceinline__ uint4 lds128(uint32_t a) {
  uint4 v; asm volatile("ld.shared.v4.u32 {%0,%1,%2,%3}, [%4];" : "=r"(v.x), "=r"(v.y), "=r"(v.z), "=r"(v.w) : "r"(a) : "memory"); return v;
}
__device__ __forceinline__ uint2 lds64(uint32_t a) {
  uint2 v; asm volatile("ld.shared.v2.u32 {%0,%1}, [%2];" : "=r"(v.x), "=r"(v.y) : "r"(a) : "memory"); return v;
}
__device__ __forceinline__ uint32_t lds32(uint32_t a) {
  uint32_t v; asm volatile("ld.shared.u32 %0, [%1];" : "=r"(v) : "r"(a) : "memory"); return v;
}
__device__ __forceinline__ void sts128(uint32_t a, uint4 v) {
  asm volatile("st.shared.v4.u32 [%0], {%1,%2,%3,%4};" :: "r"(a), "r"(v.x), "r"(v.y), "r"(v.z), "r"(v.w) : "memory");
}
__device__ __forceinline__ void sts32(uint32_t a, uint32_t x) { asm volatile("st.shared.u32 [%0], %1;" :: "r"(a), "r"(x) : "memory"); }
__device__ __forceinline__ void ldsm4(uint32_t& r0, uint32_t& r1, uint32_t& r2, uint32_t& r3, uint32_t a) {
  asm volatile("ldmatrix.sync.aligned.m8n8.x4.shared.b16 {%0,%1,%2,%3}, [%4];" : "=r"(r0), "=r"(r1), "=r"(r2), "=r"(r3) : "r"(a) : "memory");
}
__device__ __forceinline__ void ldsm4t(uint32_t& r0, uint32_t& r1, uint32_t& r2, uint32_t& r3, uint32_t a) {
  asm volatile("ldmatrix.sync.aligned.m8n8.x4.trans.shared.b16 {%0,%1,%2,%3}, [%4];" : "=r"(r0), "=r"(r1), "=r"(r2), "=r"(r3) : "r"(a) : "memory");
}
__device__ __forceinline__ void stsm4(uint32_t a, uint32_t r0, uint32_t r1, uint32_t r2, uint32_t r3) {
  asm volatile("stmatrix.sync.aligned.m8n8.x4.shared.b16 [%0], {%1,%2,%3,%4};" :: "r"(a), "r"(r0), "r"(r1), "r"(r2), "r"(r3) : "memory");
}
__device__ __forceinline__ uint32_t movmat(uint32_t a) {
  uint32_t d; asm volatile("movmatrix.sync.aligned.m8n8.trans.b16 %0, %1;" : "=r"(d) : "r"(a)); return d;
}
__device__ __forceinline__ void mma16(float* d, uint32_t a0, uint32_t a1, uint32_t a2, uint32_t a3, uint32_t b0, uint32_t b1) {
  asm volatile("mma.sync.aligned.m16n8k16.row.col.f32.bf16.bf16.f32 {%0,%1,%2,%3}, {%4,%5,%6,%7}, {%8,%9}, {%0,%1,%2,%3};"
    : "+f"(d[0]), "+f"(d[1]), "+f"(d[2]), "+f"(d[3]) : "r"(a0), "r"(a1), "r"(a2), "r"(a3), "r"(b0), "r"(b1));
}
__device__ __forceinline__ void mma8(float* d, uint32_t a0, uint32_t a1, uint32_t b0) {
  asm volatile("mma.sync.aligned.m16n8k8.row.col.f32.bf16.bf16.f32 {%0,%1,%2,%3}, {%4,%5}, {%6}, {%0,%1,%2,%3};"
    : "+f"(d[0]), "+f"(d[1]), "+f"(d[2]), "+f"(d[3]) : "r"(a0), "r"(a1), "r"(b0));
}
__device__ __forceinline__ float rcp(float x) { float r; asm("rcp.approx.ftz.f32 %0, %1;" : "=f"(r) : "f"(x)); return r; }
__device__ __forceinline__ float ex2(float x) { float r; asm("ex2.approx.ftz.f32 %0, %1;" : "=f"(r) : "f"(x)); return r; }

__host__ __device__ constexpr uint64_t mkdesc(uint32_t off, uint32_t lbo, uint32_t sbo, uint32_t swz) {
  return (uint64_t)((SBASE + off) >> 4) | ((uint64_t)(lbo >> 4) << 16) | ((uint64_t)(sbo >> 4) << 32) | ((uint64_t)swz << 62);
}
__host__ __device__ constexpr uint64_t desc_sw128(uint32_t off) { return mkdesc(off, 16, 1024, 1); }
__host__ __device__ constexpr uint64_t desc_n16(uint32_t off) { return mkdesc(off, 256, 128, 0); }
__host__ __device__ constexpr uint64_t desc_m(uint32_t off) { return mkdesc(off, 16, 256, 3); }

__host__ __device__ constexpr uint64_t desc_sw64(uint32_t off) { return mkdesc(off, 16, 512, 2); }

__device__ __forceinline__ void wg_fence() { asm volatile("wgmma.fence.sync.aligned;" ::: "memory"); }
__device__ __forceinline__ void wg_commit() { asm volatile("wgmma.commit_group.sync.aligned;" ::: "memory"); }
template <int N> __device__ __forceinline__ void wg_wait() { asm volatile("wgmma.wait_group.sync.aligned %0;" :: "n"(N) : "memory"); }

#define ACC8(d) "+f"(d[0]), "+f"(d[1]), "+f"(d[2]), "+f"(d[3]), "+f"(d[4]), "+f"(d[5]), "+f"(d[6]), "+f"(d[7])
#define ACC32(d) ACC8(d), ACC8((d + 8)), ACC8((d + 16)), ACC8((d + 24))
#define R8 "{%0,%1,%2,%3,%4,%5,%6,%7}"
#define R32 "{%0,%1,%2,%3,%4,%5,%6,%7,%8,%9,%10,%11,%12,%13,%14,%15,%16,%17,%18,%19,%20,%21,%22,%23,%24,%25,%26,%27,%28,%29,%30,%31}"
template <int SD> __device__ __forceinline__ void wg_rs16(float* d, const uint32_t* a, uint64_t db) {
  asm volatile("wgmma.mma_async.sync.aligned.m64n16k16.f32.bf16.bf16 " R8 ", {%8,%9,%10,%11}, %12, %13, 1, 1, 1;"
    : ACC8(d) : "r"(a[0]), "r"(a[1]), "r"(a[2]), "r"(a[3]), "l"(db), "n"(SD));
}
template <int SD> __device__ __forceinline__ void wg_ss16(float* d, uint64_t da, uint64_t db) {
  asm volatile("wgmma.mma_async.sync.aligned.m64n16k16.f32.bf16.bf16 " R8 ", %8, %9, %10, 1, 1, 1, 1;"
    : ACC8(d) : "l"(da), "l"(db), "n"(SD));
}
template <int SD, uint64_t DA, uint64_t DB> __device__ __forceinline__ void wg_ss16o(float* d, uint32_t oa, uint32_t ob) {
  asm volatile("{.reg .b32 x, y; .reg .b64 a, b; add.u32 x, %8, %10; add.u32 y, %9, %12; mov.b64 a, {x, %11}; mov.b64 b, {y, %13};\n"
               "wgmma.mma_async.sync.aligned.m64n16k16.f32.bf16.bf16 " R8 ", a, b, %14, 1, 1, 1, 1;}"
    : ACC8(d) : "r"(oa), "r"(ob), "n"((uint32_t)DA), "n"((uint32_t)(DA >> 32)), "n"((uint32_t)DB), "n"((uint32_t)(DB >> 32)), "n"(SD));
}
template <int SD> __device__ __forceinline__ void wg_rs64(float* d, const uint32_t* a, uint64_t db) {
  asm volatile("wgmma.mma_async.sync.aligned.m64n64k16.f32.bf16.bf16 " R32 ", {%32,%33,%34,%35}, %36, %37, 1, 1, 0;"
    : ACC32(d) : "r"(a[0]), "r"(a[1]), "r"(a[2]), "r"(a[3]), "l"(db), "n"(SD));
}
template <int SD> __device__ __forceinline__ void wg_ss64(float* d, uint64_t da, uint64_t db) {
  asm volatile("wgmma.mma_async.sync.aligned.m64n64k16.f32.bf16.bf16 " R32 ", %32, %33, %34, 1, 1, 1, 0;"
    : ACC32(d) : "l"(da), "l"(db), "n"(SD));
}
#define WG_RSO(NAME, SHAPE, REGS, ACC, A, TB) \
template <int SD, uint64_t DB> __device__ __forceinline__ void NAME(float* d, uint32_t a0, uint32_t a1, uint32_t a2, uint32_t a3, uint32_t ob) { \
  asm volatile("{.reg .b64 b; mov.b64 b, {" A(4) ", " A(5) "};\nwgmma.mma_async.sync.aligned." SHAPE ".f32.bf16.bf16 " REGS \
               ", {" A(0) "," A(1) "," A(2) "," A(3) "}, b, " A(6) ", 1, 1, " TB ";}" \
    : ACC(d) : "r"(a0), "r"(a1), "r"(a2), "r"(a3), "r"(ob + (uint32_t)DB), "n"((uint32_t)(DB >> 32)), "n"(SD)); \
}
#define ACC4(d) "+f"(d[0]), "+f"(d[1]), "+f"(d[2]), "+f"(d[3])
#define ACC16(d) ACC8(d), ACC8((d + 8))
#define OP4(i) OP4_##i
#define OP4_0 "%4"
#define OP4_1 "%5"
#define OP4_2 "%6"
#define OP4_3 "%7"
#define OP4_4 "%8"
#define OP4_5 "%9"
#define OP4_6 "%10"
#define OP16(i) OP16_##i
#define OP16_0 "%16"
#define OP16_1 "%17"
#define OP16_2 "%18"
#define OP16_3 "%19"
#define OP16_4 "%20"
#define OP16_5 "%21"
#define OP16_6 "%22"
#define OP32(i) OP32_##i
#define OP32_0 "%32"
#define OP32_1 "%33"
#define OP32_2 "%34"
#define OP32_3 "%35"
#define OP32_4 "%36"
#define OP32_5 "%37"
#define OP32_6 "%38"
WG_RSO(wg_rs8o, "m64n8k16", "{%0,%1,%2,%3}", ACC4, OP4, "1")
#define R16 "{%0,%1,%2,%3,%4,%5,%6,%7,%8,%9,%10,%11,%12,%13,%14,%15}"
WG_RSO(wg_rs32o, "m64n32k16", R16, ACC16, OP16, "1")
WG_RSO(wg_rs64o, "m64n64k16", R32, ACC32, OP32, "0")
WG_RSO(wg_rs32k, "m64n32k16", R16, ACC16, OP16, "0")
template <uint64_t DA, uint64_t DB> __device__ __forceinline__ void wg_ss32k(float* d, uint32_t ob) {
  asm volatile("{.reg .b64 b; mov.b64 b, {%17, %18};\nwgmma.mma_async.sync.aligned.m64n32k16.f32.bf16.bf16 " R16 ", %16, b, 1, 1, 1, 1, 0;}"
    : ACC16(d) : "l"(DA), "r"(ob + (uint32_t)DB), "n"((uint32_t)(DB >> 32)));
}
template <int N> __device__ __forceinline__ void reg_inc() { asm volatile("setmaxnreg.inc.sync.aligned.u32 %0;" :: "n"(N)); }
template <int N> __device__ __forceinline__ void reg_dec() { asm volatile("setmaxnreg.dec.sync.aligned.u32 %0;" :: "n"(N)); }

template <int KS>
__device__ __forceinline__ void load_frags(uint32_t* a, uint32_t src) {
  const int lane = threadIdx.x & 31, w = (threadIdx.x >> 5) & 3;
  const int k = ((lane >> 4) << 3) + (lane & 7), u = w * 2 + ((lane >> 3) & 1);
  const uint32_t base = src + k * 128 + ((u ^ (k & 7)) << 4);
#pragma unroll
  for (int ks = 0; ks < KS; ks++) ldsm4t(a[ks * 4], a[ks * 4 + 1], a[ks * 4 + 2], a[ks * 4 + 3], base + ks * 2048);
}

__device__ __forceinline__ uint32_t badd2(uint32_t a, uint32_t b) { uint32_t r; asm("add.rn.bf16x2 %0, %1, %2;" : "=r"(r) : "r"(a), "r"(b)); return r; }
__device__ __forceinline__ uint32_t bsub2(uint32_t a, uint32_t b) { uint32_t r; asm("sub.rn.bf16x2 %0, %1, %2;" : "=r"(r) : "r"(a), "r"(b)); return r; }
__device__ __forceinline__ uint32_t bmul2(uint32_t a, uint32_t b) { uint32_t r; asm("mul.rn.bf16x2 %0, %1, %2;" : "=r"(r) : "r"(a), "r"(b)); return r; }
__device__ __forceinline__ uint32_t bfma2(uint32_t a, uint32_t b, uint32_t c) { uint32_t r; asm("fma.rn.bf16x2 %0, %1, %2, %3;" : "=r"(r) : "r"(a), "r"(b), "r"(c)); return r; }
template <int R> __device__ __forceinline__ void layernorm9(const uint32_t* x, uint32_t* o) {
  const uint32_t ones = 0x3F803F80u;
  float a[R][3][4], q[R], s[R];
#pragma unroll
  for (int i = 0; i < 9 * R; i++) {
    float* d = a[i % R][i / R % 3];
    if (i < 3 * R) d[0] = d[1] = d[2] = d[3] = 0.f;
    mma8(d, x[i % R * 9 + i / R], ones, x[i % R * 9 + i / R]);
  }
#pragma unroll
  for (int r = 0; r < R; r++) {
    q[r] = threadIdx.x & 4 ? a[r][0][1] + a[r][1][1] + a[r][2][1] : a[r][0][0] + a[r][1][0] + a[r][2][0];
    s[r] = (a[r][0][2] + a[r][0][3]) + (a[r][1][2] + a[r][1][3]) + (a[r][2][2] + a[r][2][3]);
  }
#pragma unroll
  for (int r = 0; r < R; r++) { q[r] += __shfl_xor_sync(~0u, q[r], 4); s[r] += __shfl_xor_sync(~0u, s[r], 1); }
#pragma unroll
  for (int r = 0; r < R; r++) { q[r] += __shfl_xor_sync(~0u, q[r], 9); s[r] += __shfl_xor_sync(~0u, s[r], 2); }
#pragma unroll
  for (int r = 0; r < R; r++) q[r] = __shfl_sync(~0u, q[r], 0) + __shfl_sync(~0u, q[r], 18);
#pragma unroll
  for (int r = 0; r < R; r++) {
    const float mean = s[r] * (1.f / DM), var = fmaxf(fmaf(q[r], 1.f / DM, -mean * mean), 0.f);
    float sd;
    asm("sqrt.approx.ftz.f32 %0, %1;" : "=f"(sd) : "f"(bf_lo(pack2(bf_lo(pack2(var, 0.f)) + 1e-5f, 0.f))));
    const float inv = rcp(bf_lo(pack2(sd, 0.f)));
    const uint32_t mb = pack2(mean, mean), hi = pack2(inv, inv), lo = pack2(inv - bf_lo(hi), inv - bf_lo(hi));
#pragma unroll
    for (int i = r * 9; i < r * 9 + 9; i++) {
      const uint32_t d = bsub2(x[i], mb);
      o[i] = bfma2(d, hi, bmul2(d, lo));
    }
  }
}
__device__ __forceinline__ void store_ln_row(int layer, int tok, const uint32_t* o) {
  const int lane = threadIdx.x & 31, r = tok & 31;
  unsigned char* p = g_lnimg + (size_t)(layer * NSEG + (tok >> 5)) * (9 * 4096) + r * 128 + (((lane >> 2) ^ (r & 7)) << 4) + (lane & 3) * 4;
#pragma unroll
  for (int i = 0; i < 9; i++) *(uint32_t*)(p + i * 4096) = o[i];
}
struct Params { CUtensorMap map[11]; const bf16 *X, *K, *V, *shift, *Hk, *Dk, *mem0, *Wq, *Wk, *Wv, *Wo; bf16* out; uint32_t dly[31]; };
#define DLYS P.dly[0]
#define DLYW P.dly[1]
#define DLYV P.dly[24]
#define DLYK P.dly[4]
#define DLYO P.dly[25]
#define DLYG P.dly[5]
#define KWIN P.dly[6]
#define KMIN P.dly[7]
#define PREF0 P.dly[19]
#define PACE P.dly[20]
#define S1G P.dly[21]
#define S1DLY P.dly[22]
#define PREFH P.dly[23]
uint32_t h_dly[31] = {800, 120, 150, 160, 3640, 4160, 2750, 1300, 1585, 1670, 1760, 2090, 2210, 2310, 2790, 2920, 3185, 3330, 3500, 7000, 160, 12500, 20500, 4000, 3540, 400, 800, 100, 300, 150};

constexpr uint32_t C_W = 0, C_M = 147456, C_KV = C_M + 18432, C_OS = C_KV + 24576, C_QM = C_KV + 32768, C_KM = C_QM + 2048,
                   C_VM = C_KM + 2048, C_OI = C_VM + 2048, C_SX = C_OI + 4096, C_KM2 = C_SX + 2560, C_VM2 = C_KM2 + 128,
                   C_KV2 = C_KM2 + 2048, C_Q = C_KV2 + 8192, C_BAR = C_Q + 8192;
constexpr uint32_t CB_FULL = C_BAR, CB_REF = C_BAR + 16, CB_SX = C_BAR + 32, CB_OX = C_BAR + 40, CB_XX = C_BAR + 48, CB_Q = C_BAR + 56, C_BAD = C_BAR + 64, W_BAR = C_BAR + 80, T_BAR = W_BAR + 24, S_GEN = C_BAR + 128, C_REF = C_BAR + 132, CB_VF = C_BAR + 144, CB_M = C_BAR + 160, CB_MV = C_BAR + 200;
constexpr uint32_t G_W = 0, G_RING = 147456, G_W2 = G_RING + 9 * 8192, G_BAR = G_W2 + 8192;
constexpr uint32_t O_W = 0, O_RING = 3 * 40960, O_ST = O_RING + 11 * 8192, O_BAR = O_ST + 16384, OB_ST = O_BAR + 64;
constexpr uint32_t F_A = 0, F_XY = 36864, F_L = F_XY + 36864, F_X = F_L + 18432, F_Y = F_L + 2 * 36864, F_BAR = C_BAR;
constexpr uint32_t SMEM_BYTES = C_BAR + 256;
static_assert(G_BAR + 256 <= SMEM_BYTES && O_BAR + 256 <= SMEM_BYTES && F_BAR + 16 <= SMEM_BYTES && SMEM_BYTES <= 232448, "smem map");
enum { B_INIT = 1, B_M, B_QK, B_S, B_V, B_O, B_X, B_WG0, B_WG1, B_WG2, B_G, B_OE, B_T, B_R };

__device__ __forceinline__ uint4 pack_partial(const float* d, uint32_t tag) {
  uint32_t x, z;
  asm("lop3.b32 %0, %2, 1, %4, 0xb8; lop3.b32 %1, %3, 1, %4, 0xb8;" : "=&r"(x), "=&r"(z) : "r"(pack2(d[0], d[1])), "r"(pack2(d[2], d[3])), "r"(tag));
  return make_uint4(x, pack2(d[4], d[5]), z, pack2(d[6], d[7]));
}
__device__ __forceinline__ void store_partial(uint4* p, const uint4& v) { st_b128(p, v.x, v.y, v.z, v.w); }
__device__ __forceinline__ void gather_reduce(const uint32_t* p, uint32_t* dst, uint32_t m0, bool shared, uint32_t tag, uint32_t lane, uint32_t sb, int n, int TS0) {
  int tries = 0;
  bool bad;
  TR(TS0);
  do {
    uint2 x[8];
#pragma unroll
    for (int i = 0; i < 8; i++)
      asm volatile("{.reg .b64 v; ld.relaxed.gpu.global.b64 v, [%2]; mov.b64 {%0, %1}, v;}" : "=r"(x[i].x), "=r"(x[i].y) : "l"(p + i * 128) : "memory");
    spin_guard(tries);
    float a = bf_lo(x[0].x), b = bf_hi(x[0].x), c = bf_lo(x[0].y), d = bf_hi(x[0].y);
    uint32_t t = x[0].x ^ tag;
#pragma unroll
    for (int i = 1; i < 8; i++) {
      a += bf_lo(x[i].x); b += bf_hi(x[i].x); c += bf_lo(x[i].y); d += bf_hi(x[i].y);
      asm("lop3.b32 %0, %0, %1, %2, 0xf6;" : "+r"(t) : "r"(x[i].x), "r"(tag));
    }
    bad = __any_sync(~0u, t & 1);
    const bool up = lane & 8;
    float u = (up ? c : a) + __shfl_xor_sync(~0u, up ? a : c, 8), v = (up ? d : b) + __shfl_xor_sync(~0u, up ? b : d, 8);
    if (shared) { u += __shfl_xor_sync(~0u, u, 4); v += __shfl_xor_sync(~0u, v, 4); }
    u += __shfl_xor_sync(~0u, u, 16);
    v += __shfl_xor_sync(~0u, v, 16);
    st_relaxed_if(dst, n < LAG && up ? m0 : pack2(u, v), !bad);
  } while (bad);
  if (shared) bar_arrive(B_WG2, 224);
  TR(TS0 + 3); TRV(TS0 + 2, tries);
  CNT((TS0 - 16) >> 2, tries);
}

constexpr int XR = 3;
__host__ __device__ constexpr int o_ks(int s) { return s & (s < 8 ? 3 : 7); }
constexpr uint32_t OPAT = 0x55555577u;
__host__ __device__ constexpr bool o_reg(int s) { return (OPAT >> s) & 1; }
__host__ __device__ constexpr int o_slot(int s) { int k = 0; for (int i = 0; i < s; i++) k += o_reg(i) == o_reg(s); return k; }
__device__ __forceinline__ int g_unit(int wg) {
  const int i = bid() - N_CHAIN;
  return i < 32 ? wg * 64 + i : 2 * i - 32 + wg;
}
__device__ __forceinline__ uint32_t pinned(uint32_t v) { return __shfl_sync(~0u, v, threadIdx.x & 31); }
template <class T> __device__ __forceinline__ T* pinned(T* p) { return (T*)__shfl_sync(~0u, (unsigned long long)p, threadIdx.x & 31); }
enum { CHAIN, GROLE, OROLE };
template <int ROLE, bool SYNC> __device__ __forceinline__ void load_box(const Params& P, uint32_t sb, bool regs, int wg, int i, uint32_t mb, bool on) {
  const int b = bid();
  int map, col = 0, ks = 0, c2 = 0, c3 = 0;
  uint32_t dst = wg * 73728;
  if (ROLE == CHAIN) {
    const int k = i - 1, st = __fns(regs ? OPAT : ~OPAT, 0, i) & 31;
    dst += i ? (17 + i) * 2048 : 0;
    if (wg || i == 0) { map = wg + i; col = b * 64; c3 = !regs; }
    else if (!regs && k >= 14) { map = 6; ks = b * 4 + k - 14; }
    else { map = 6; col = 64 + (st < 8 ? (st >> 2) * 64 : (st >> 3) * 128 + (b & 1) * 64); ks = (b * 4) ^ o_ks(st); }
  } else if (ROLE == GROLE) {
    const int q = g_unit(wg);
    map = ((q >> 5) + 1) % 3;
    if (i) { map += 3; col = (q & 31) * 128 + (i - 1) * 64; ks = 34; dst = G_W2 + wg * 4096 + (i - 1) * 2048; }
    else { map += 8; c2 = (q & 31) * 2; c3 = !regs; }
  } else {
    const int o = b - N_CHAIN - N_G, ksl = o / 3;
    map = 7; col = ((o % 3) * 3 + (wg + ksl) % 3) * 64; dst = (wg * (regs ? 24 : 20) + i) * 2048;
    ks = (ksl * 11 - max(ksl - 4, 0)) * 4 + (regs ? i / 3 * 5 + i % 3 * 2 : i < 16 ? i / 2 * 5 + 1 + i % 2 * 2 : i + 24);
    c3 = (ks & 1) * 2; ks >>= 1;
  }
  if (SYNC) { col = pinned(col); ks = pinned(ks); bar_sync(B_WG0 + wg, 256); }
  if (on) asm volatile("cp.async.bulk.tensor.5d.shared::cluster.global.tile.mbarrier::complete_tx::bytes [%0], [%1, {%2, %3, %4, %5, %6}], [%7];"
               :: "r"(sb + dst), "l"(&P.map[map]), "r"(col), "r"(0), "r"(c2), "r"(c3), "r"(ks), "r"(mb) : "memory");
}
template <int ROLE, bool SYNC = false> __device__ __forceinline__ void load_wg(const Params& P, uint32_t sb, bool regs, int wg, int quarter) {
  const int i = (threadIdx.x & 31) * 4 + quarter;
  const int n = ROLE == CHAIN ? 36 : ROLE == GROLE ? (regs ? 38 : 36) : regs ? 24 : bid() < N_CHAIN + N_G + 12 ? 20 : 16;
  const bool split = SYNC && wg == 0;
  const uint32_t mb = split && i ? sb + T_BAR : sb + W_BAR + wg * 8;
  load_box<ROLE, SYNC>(P, sb, regs, wg, i, mb, i < (ROLE == CHAIN ? (wg ? 2 : 19) : ROLE == GROLE ? n - 35 : n));
  if (i <= split) mbar_expect(mb, n * (split ? 1024 : 2048));
  __syncwarp();
}
__device__ __forceinline__ uint32_t near_half(uint32_t blk, uint32_t reader) {
  return __ldcg(g_near + (blk >> 3)) ^ (~blk & 1) ^ __ldcg(g_side + (blk >> 3)) ^ __ldcg(g_side + reader);
}

__device__ __forceinline__ uint32_t opaque_tid() { uint32_t t; asm volatile("mov.u32 %0, %%tid.x;" : "=r"(t)); return t; }
__device__ __forceinline__ void m_fetch(uint32_t sb, uint32_t src, uint32_t b, uint32_t mb) {
  bulk_load(sb + C_M + (b ? b * 4096 - 2048 : 0), (const unsigned char*)g_mimg + ((src ^ ((b & 1) * 4096)) + b * 8192), b ? 4096 : 2048, mb);
}
__device__ __forceinline__ uint32_t m_probe(uint32_t lane) { return lane * 32 + (lane & 4) * 4 + (lane >> 3) * 4; }
__device__ __forceinline__ uint32_t m_max(uint32_t a, uint32_t b) {
  return max(max(lds32(a), lds32(a + 1024)), max(lds32(b), lds32(b + 1024)));
}
template <int S0, int N> __device__ __forceinline__ void o_steps(float* d, const uint32_t* a) {
  constexpr int SD = o_ks(S0) != 0;
  if constexpr (o_reg(S0)) wg_rs16<SD>(d, a + (18 + o_slot(S0)) * 4, desc_n16(C_OI + o_ks(S0) * 512));
  else wg_ss16<SD>(d, desc_sw128(C_W + (18 + o_slot(S0)) * 2048), desc_n16(C_OI + o_ks(S0) * 512));
  if constexpr (N > 1) o_steps<S0 + 1, N - 1>(d, a);
}
template <int BASE, int KS, int N> __device__ __forceinline__ void m_steps(float* d, const uint32_t* a, uint32_t oa) {
  wg_rs16<KS != 0>(d, a + (BASE + KS / 2) * 4, desc_m(C_M + KS * 512));
  if constexpr (KS >= 36 - 2 * XR) wg_rs16<1>(d, a + (18 + XR + KS / 2) * 4, desc_m(C_M + KS * 512 + 512));
  else wg_ss16o<1, desc_sw128(C_W + (BASE + KS / 2) * 2048), desc_m(C_M + KS * 512 + 512)>(d, oa, 0);
  if constexpr (N > 2) m_steps<BASE, KS + 2, N - 2>(d, a, oa);
}

constexpr uint32_t VPAT = 0x15bbd249u;
template <int I, int R, int S> __device__ __forceinline__ void v_steps(float* d, const uint32_t* a) {
  constexpr bool reg = (VPAT >> I) & 1;
  if constexpr (reg) wg_rs16<1>(d, a + (18 + R) * 4, desc_m(C_M + R * 1024));
  else wg_ss16<1>(d, desc_sw128(C_W + (54 + S) * 2048), desc_m(C_M + S * 1024 + 512));
  if constexpr (I < 31) v_steps<I + 1, R + reg, S + !reg>(d, a);
  else static_assert(R + reg == 18, "pattern");
}

__device__ __forceinline__ void chain_proj(const Params& P, uint32_t sb) {
  const uint32_t c = chain_id(), h = c >> 1, j = c & 1, wid = __shfl_sync(~0u, threadIdx.x >> 5, 0), wg = wid >> 2, w = wid & 3;
  const uint32_t t = threadIdx.x & 127, lane = pinned(t & 31), mine = pinned(sb + t * 16), rb = mapa(sb, j ^ 1);
  const uint32_t theirs = pinned(rb + C_KM2 + w * 512 + lane * 4), oa = wg * 4608;
  uint32_t a[144 + 4 * XR];
  mbar_wait(sb + W_BAR + wg * 8, 0);
  if (threadIdx.x == 0) TS(23);
  load_frags<36>(a, sb + C_W + wg * 73728);
  fence_async_smem();
  bar_arrive(B_WG0 + wg, 256);
  if (threadIdx.x == 0) TS(24);
  bar_sync(B_WG2, 384);
  const uint32_t round = min(wid ^ 4, 5u), gdly = P.dly[8 + round], ps = t >> 2, pf = j * 16 + (ps >> 1);
  const bool shared = round < 3;
  uint4* const dsts = pinned(g_xb + (ps * 4096 + near_half(ps * 8, ps * 2) * 256 + c * 4 + (t & 3)));
  uint4* const dstf = pinned(g_xb + (pf * 4096 + 512 + near_half(pf * 8 + 1, pf * 2) * 256 + h * 8 + (t & 7)));
  const uint32_t* const gsrc = (const uint32_t*)g_xb + (h * 16384 + round % 3 * 4096 + near_half(h * 8 + !shared, h * 2) * 1024 +
                               (shared ? lane * 4 + j * 2 : 2048 + (lane & 24) * 4 + j * 16 + (lane & 7) * 2));
  uint32_t* gdst = g_mimg + (16384 + (lane >> 4) * 1024 +
                   (shared ? (round ? 1536 + round * 512 : 0) + c * 8 + (((lane >> 1) ^ c) & 4) + (lane & 3)
                           : (round - 1) * 2048 + c * 16 + (lane & 1) * 8 + (((lane >> 1) ^ (c * 2)) & 4) + ((lane >> 1) & 3)));
  const uint32_t m0 = __ldcg(gdst - 16384);
  mbar_wait(sb + W_BAR + wg * 8, 1);
  load_frags<XR>(a + 144, sb + C_W + wg * 73728 + (18 - XR) * 2048);
  bar_sync(B_INIT, 256);
  if ((threadIdx.x & 127) == 0) TS(4);

  uint32_t ring = 1;
#pragma unroll 1
  for (int n = 0; n < STEPS; n++) {
    float d[8], e[8];
    if (n + 1 == STEPS && !wg) { bar_arrive(B_QK, 416); break; }
#pragma unroll
    for (int i = 0; i < 8; i++) e[i] = 0.f;
    uint32_t redo = n + 1;
#pragma unroll 1
    do {
      mbar_wait(sb + CB_M, n & 1);
      wg_fence();
      m_steps<0, 0, 4>(d, a, oa);
      wg_commit();
      if (wg) { wg_fence(); m_steps<18, 0, 4>(e, a, 4608); wg_commit(); }
      if (wid == 0) TR(8);
      mbar_wait(sb + CB_M + 8, n & 1);
      wg_fence();
      m_steps<0, 4, 8>(d, a, oa);
      wg_commit();
      mbar_wait(sb + CB_MV, n & 1);
      asm volatile("{.reg .pred p; .reg .u32 t; ld.shared.u32 t, [%1]; setp.eq.u32 p, t, %0; selp.u32 %0, -1, 0, p;}" : "+r"(redo) : "r"(sb + C_BAD) : "memory");
    } while (redo);
    mbar_wait(sb + CB_MV + 8, n & 1);
    wg_fence();
    m_steps<0, 12, 8>(d, a, oa);
    wg_commit();
    mbar_wait(sb + CB_MV + 16, n & 1);
    wg_fence();
    m_steps<0, 20, 8>(d, a, oa);
    wg_commit();
    mbar_wait(sb + CB_MV + 24, n & 1);
    wg_fence();
    m_steps<0, 28, 8>(d, a, oa);
    wg_commit();
    wg_wait<0>();
    if (w == 0) TR(6 + wg);
    const uint32_t f0 = pack2(d[0], d[1]), f1 = pack2(d[4], d[5]), f2 = pack2(d[2], d[3]), f3 = pack2(d[6], d[7]);
    stsm4(mine + C_QM + wg * 2048, f0, f1, f2, f3);
    bar_arrive(B_QK, 416);
    const uint32_t tag = (n & 1) ^ 1;
    if (n == 0) mbar_wait(sb + T_BAR, 0);
    if (wg) {
      if (n + 1 < STEPS) bar_sync(B_S, 256);
      wg_fence();
      v_steps<0, 2, 2>(e, a);
      wg_commit();
      const uint32_t k0 = j ? f0 : f1, k1 = j ? f2 : f3;
      mbar_wait(sb + CB_SX, n & 1);
      wg_wait<0>();
      if (w == 0) TR(11);
      const uint32_t v0 = pack2(e[0], e[1]), v1 = pack2(e[4], e[5]), v2 = pack2(e[2], e[3]), v3 = pack2(e[6], e[7]);
      stsm4(mine + C_VM, v0, v1, v2, v3);
      bar_arrive(B_V, 256);
      st_async1(theirs, k0, rb + CB_XX);
      st_async1(theirs + 256, k1, rb + CB_XX);
      st_async1(theirs + 128, j ? v0 : v1, rb + CB_XX);
      st_async1(theirs + 384, j ? v2 : v3, rb + CB_XX);
      if (n + 1 == STEPS) break;
      bar_sync(B_O, 256);
      fence_async_smem();
      wg_fence();
#pragma unroll
      for (int ks = 0; ks < 4; ks++) {
        if (ks == 0) wg_ss16<0>(d, desc_sw128(C_W + 32 * 2048), desc_n16(C_OI));
        else wg_ss16<1>(d, desc_sw128(C_W + (32 + ks) * 2048), desc_n16(C_OI + ks * 512));
      }
      wg_commit();
      bar_arrive(B_X, 256);
      if (w == 0) TR(0);
      wg_wait<0>();
      store_partial(dsts, pack_partial(d, tag));
      bar_arrive(B_M, 160);
      if (w == 0) TR(1);
    } else {
      bar_sync(B_X, 256);
      wg_fence();
      o_steps<0, 4>(d, a);
      wg_commit();
      o_steps<4, 4>(e, a);
      wg_commit();
      wg_wait<1>();
      store_partial(dsts + 1024, pack_partial(d, tag));
      if (w == 0) TR(2);
      wg_wait<0>();
      store_partial(dsts + 2048, pack_partial(e, tag));
      if (w == 0) TR(3);
      wg_fence();
      o_steps<8, 4>(d, a);
      wg_commit();
      bar_sync(B_T, 160);
      if (w == 0) { TRV(61, 0); TR(12); }
      wg_fence();
      o_steps<12, 4>(d, a);
      wg_commit();
      o_steps<16, 8>(e, a);
      wg_commit();
      wg_wait<1>();
      store_partial(dstf, pack_partial(d, tag));
      if (w == 0) TR(4);
      wg_fence();
      o_steps<24, 8>(d, a);
      wg_commit();
      wg_wait<1>();
      store_partial(dstf + 1024, pack_partial(e, tag));
      bar_arrive(B_OE, 256);
      if (w == 0) TR(5);
      wg_wait<0>();
      store_partial(dstf + 2048, pack_partial(d, tag));
      if (w == 0) TR(15);
    }
    if ((wid ^ 4) < 6) {
      mbar_wait(sb + CB_REF, n & 1);
      wait_until(lds32(sb + C_REF), gdly);
      gather_reduce(gsrc, gdst, m0, shared, tag, lane, sb, n, 16 + round * 4);
      if (++ring == MRING) { ring = 0; gdst -= MRING * 16384; }
      gdst += 16384;
    }
  }
}

template <int KS> __device__ __forceinline__ void x_scores(float* s, float* sm, const uint4* q, uint32_t ok, uint32_t om) {
  wg_rs32o<KS != 0, desc_sw64(C_KV + KS * 1024)>(s, q[KS].x, q[KS].y, q[KS].z, q[KS].w, ok);
  wg_rs8o<KS != 0, desc_n16(C_KM + KS * 512)>(sm, q[KS].x, q[KS].y, q[KS].z, q[KS].w, om);
  if constexpr (KS < 3) x_scores<KS + 1>(s, sm, q, ok, om);
}

__device__ __forceinline__ void chain_attn(const Params& P, uint32_t sb) {
  const int c = chain_id(), j = c & 1;
  const int tid = threadIdx.x, lane = tid & 31, w = __shfl_sync(~0u, (tid >> 5) & 3, 0);
  const int l = w >> 1, u = w & 1;
  const uint32_t rb = mapa(sb, j ^ 1);
  const float sc = 0.08838834764831845f * 1.4426950408889634f;
  const uint32_t ones = 0x3F803F80u, sx = C_SX + l * 1280;
  const uint32_t km_off = C_KM + (lane >> 3) * 256 + l * 128 + (lane & 7) * 16;
  const uint32_t qm_off = C_QM + (lane >> 4) * 256 + l * 128 + (lane & 7) * 16, kmu = pinned(sb + km_off + u * 1024);
  const uint32_t kv_off = C_KV + l * 4096 + (lane & 15) * 64 + (((lane >> 4) ^ (u * 2) ^ ((lane >> 1) & 3)) << 4);

  load_wg<CHAIN, true>(P, sb, false, 1, w);
  if (lane == 0) mbar_arrive(sb + CB_M);
#pragma unroll 1
  for (int n = 0; n < STEPS; n++) {
    const uint32_t kvb = sb + kv_off + (n & 1) * 16384;
    mbar_wait(sb + CB_FULL + (n & 1) * 8, (n >> 1) & 1);
    if (n < 3 && tid == 256) TS(n ? 20 + n : 5);
    __syncwarp();
    uint4 q[4];
    auto load_q = [&]() {
      const uint32_t ln = opaque_tid() & 31;
#pragma unroll
      for (int ks = 0; ks < 4; ks++)
        ldsm4t(q[ks].x, q[ks].y, q[ks].z, q[ks].w, sb + C_Q + (ln & 8) * 512 + ks * 1024 + (ln & 16) * 32 + (ln & 7) * 64 + (((w ^ (ln >> 1)) & 3) << 4));
    };
    {
      uint32_t km[8];
      uint4 kx[8];
#pragma unroll
      for (int i = 0; i < 8; i++) ldsm4t(kx[i].x, kx[i].y, kx[i].z, kx[i].w, (kvb ^ ((i & 1) * 32)) + (i >> 1) * 1024);
      mbar_wait_step<1>(sb + CB_VF, n);
      if (w == 1) TRD(60, kx[7].x);
      bar_sync(B_QK, 416);
      if (n + 1 == STEPS) {
        st_async4(rb + sx + u * 512 + lane * 16, 0.f, 0.f, 0.f, 0.f, rb + CB_SX);
        st_async1(rb + sx + 1024 + u * 128 + lane * 4, 0, rb + CB_SX);
        bar_sync(B_V, 256);
        mbar_wait_step<5>(sb + CB_Q, n);
        load_q();
      } else {
      uint32_t qm[16];
#pragma unroll
      for (int ks = 0; ks < 4; ks++) ldsm4t(qm[4 * ks], qm[4 * ks + 1], qm[4 * ks + 2], qm[4 * ks + 3], sb + qm_off + ks * 512);
      ldsm4t(km[0], km[1], km[2], km[3], sb + km_off);
      ldsm4t(km[4], km[5], km[6], km[7], sb + km_off + 1024);
      float s[5][4];
      uint4 vx[4];
#pragma unroll
      for (int i = 0; i < 5; i++) { s[i][0] = s[i][1] = s[i][2] = s[i][3] = 0.f; }
#pragma unroll
      for (int ks = 0; ks < 4; ks++) {
        const uint32_t* x = qm + 4 * ks;
        if (ks == 1 || ks == 2) {
#pragma unroll
          for (int i = 2 * ks - 2; i < 2 * ks; i++) ldsm4(vx[i].x, vx[i].y, vx[i].z, vx[i].w, ((sb + kv_off) ^ ((i & 1) * 32)) + 8192 + (2 * u + (i >> 1)) * 1024);
        }
        mma16(s[1], x[0], x[1], x[2], x[3], kx[2 * ks].x, kx[2 * ks].y);
        mma16(s[2], x[0], x[1], x[2], x[3], kx[2 * ks].z, kx[2 * ks].w);
        mma16(s[0], x[0], x[1], x[2], x[3], km[2 * ks], km[2 * ks + 1]);
        mma16(s[3], x[0], x[1], x[2], x[3], kx[2 * ks + 1].x, kx[2 * ks + 1].y);
        mma16(s[4], x[0], x[1], x[2], x[3], kx[2 * ks + 1].z, kx[2 * ks + 1].w);
      }
      st_async4(rb + sx + u * 512 + lane * 16, s[1][0], s[1][1], s[2][0], s[2][1], rb + CB_SX);
      st_async1(rb + sx + 1024 + u * 128 + lane * 4, __float_as_uint(u ? s[0][1] : s[0][0]), rb + CB_SX);
      bar_arrive_after<B_S, 256>(__float_as_uint(s[3][0]), __float_as_uint(s[4][0]));
      mbar_wait_step<2>(sb + CB_Q, n);
      mbar_wait_step<2>(sb + CB_SX, n);
      const uint4 p0 = lds128(sb + sx + u * 512 + lane * 16), p1 = lds128(sb + sx + (u ^ 1) * 512 + lane * 16);
      const uint2 p2 = make_uint2(lds32(sb + sx + 1024 + lane * 4), lds32(sb + sx + 1152 + lane * 4));
      float t[10] = {s[0][0] + __uint_as_float(p2.x), s[0][1] + __uint_as_float(p2.y),
                     s[1][0] + __uint_as_float(p0.x), s[1][1] + __uint_as_float(p0.y),
                     s[2][0] + __uint_as_float(p0.z), s[2][1] + __uint_as_float(p0.w),
                     s[3][0] + __uint_as_float(p1.x), s[3][1] + __uint_as_float(p1.y),
                     s[4][0] + __uint_as_float(p1.z), s[4][1] + __uint_as_float(p1.w)};
      float mx = fmaxf(fmaxf(fmaxf(fmaxf(t[2], t[3]), fmaxf(t[4], t[5])), fmaxf(fmaxf(t[6], t[7]), fmaxf(t[8], t[9]))), fmaxf(t[0], t[1]));
      mx = fmaxf(fmaxf(mx, __shfl_xor_sync(~0u, mx, 1)), fmaxf(__shfl_xor_sync(~0u, mx, 2), __shfl_xor_sync(~0u, mx, 3)));
      const float ms = -mx * sc;
#pragma unroll
      for (int i = 0; i < 10; i++) t[i] = ex2(fmaf(t[i], sc, ms));
      uint32_t p[5];
#pragma unroll
      for (int i = 0; i < 5; i++) p[i] = pack2(t[2 * i], t[2 * i + 1]);
      p[1] |= (p[0] & p[3] & p[4]) & 0x80008000u;
      float o[2][4], z[4] = {0.f, 0.f, 0.f, 0.f};
      mma16(z, ones, ones, ones, ones, p[1], p[2]);
#pragma unroll
      for (int i = 0; i < 2; i++) {
        o[i][0] = o[i][1] = o[i][2] = o[i][3] = 0.f;
        mma16(o[i], vx[2 * i].x, vx[2 * i].y, vx[2 * i].z, vx[2 * i].w, p[1], p[2]);
      }
      mma16(z, ones, ones, ones, ones, p[3], p[4]);
#pragma unroll
      for (int i = 0; i < 2; i++) mma16(o[i], vx[2 * i + 1].x, vx[2 * i + 1].y, vx[2 * i + 1].z, vx[2 * i + 1].w, p[3], p[4]);
      mma8(z, ones, ones, p[0]);
      bar_sync_after<B_V, 256>(p[1]);
      ldsm4(km[0], km[1], km[2], km[3], kmu + (C_VM - C_KM));
      load_q();
      mma8(o[0], km[0], km[1], p[0]);
      mma8(o[1], km[2], km[3], p[0]);
      const float i0 = rcp(z[0]), i1 = rcp(z[1]);
      const uint32_t oo = C_OI + u * 1024 + l * 128 + lane * 4;
      uint32_t ow[4];
#pragma unroll
      for (int i = 0; i < 2; i++) { ow[2 * i] = pack2(o[i][0] * i0, o[i][1] * i1); ow[2 * i + 1] = pack2(o[i][2] * i0, o[i][3] * i1); }
      stsm4(kmu + (C_OI - C_KM), ow[0], ow[1], ow[2], ow[3]);
      bar_arrive(B_O, 256);
#pragma unroll
      for (int i = 0; i < 4; i++) st_async1(rb + oo + 2048 + i * 256, ow[i], rb + CB_OX);
      }
    }
    {
      const uint32_t lane = opaque_tid() & 31, own = ((n & 1) * 16384 + j * 4096) >> 4;
      float s[16], sm[4], r[16], rm[4];
      {
        mbar_wait_step<3>(sb + CB_XX, n);
        fence_async_smem();
        if (n + 1 < STEPS) bar_sync(B_OE, 256);
        if (w == 1) { TRV(61, 0); TR(9); }
        wg_fence();
        x_scores<0>(s, sm, q, own, j * 8);
        x_scores<0>(r, rm, q, (C_KV2 - C_KV) >> 4, (C_KM2 - C_KM) >> 4);
        wg_commit();
        wg_wait<0>();
      }
      const float neg = -1e9f * 11.313708498984761f;
      const int tok = (lane & 24) + 2 * w + ((lane >> 2) & 1), lim = tok - 8 * (int)(lane & 3);
      float t[10] = {sm[0] + rm[2], sm[1] + rm[3]};
#pragma unroll
      for (int i = 0; i < 8; i++) t[2 + i] = i > lim ? neg : s[(i >> 1) * 4 + (i & 1)] + r[(i >> 1) * 4 + (i & 1) + 2];
      float mx = fmaxf(fmaxf(fmaxf(fmaxf(t[2], t[3]), fmaxf(t[4], t[5])), fmaxf(fmaxf(t[6], t[7]), fmaxf(t[8], t[9]))), fmaxf(t[0], t[1]));
      mx = fmaxf(fmaxf(mx, __shfl_xor_sync(~0u, mx, 1)), fmaxf(__shfl_xor_sync(~0u, mx, 2), __shfl_xor_sync(~0u, mx, 3)));
      const float ms = -mx * sc;
#pragma unroll
      for (int i = 0; i < 10; i++) t[i] = ex2(fmaf(t[i], sc, ms));
      uint32_t p[5];
#pragma unroll
      for (int i = 0; i < 5; i++) p[i] = pack2(t[2 * i], t[2 * i + 1]);
      float z = ((t[0] + t[1]) + (t[2] + t[3])) + ((t[4] + t[5]) + (t[6] + t[7])) + (t[8] + t[9]);
      const uint32_t row = sb + C_OS + tok * 128 + (((lane & 3) ^ (tok & 7)) << 4);
      z = rcp((z + __shfl_xor_sync(~0u, z, 1)) + (__shfl_xor_sync(~0u, z, 2) + __shfl_xor_sync(~0u, z, 3)));
      float o[32];
      bar_sync_after<B_WG2, 224>(n + 1 < STEPS ? __float_as_uint(z) : 0xfff12345u);
      wg_fence();
      wg_rs64o<0, desc_sw64(C_KV + 8192)>(o, p[1], 0, p[2], 0, j * 256);
      wg_rs64o<1, desc_sw64(C_KV + 8192 + 32)>(o, p[3], 0, p[4], 0, j * 256);
      wg_rs64o<1, mkdesc(C_VM, 128, 256, 0)>(o, p[0], 0, 0, 0, j * 8);
      wg_rs64o<1, desc_sw64(C_KV2 + 4096)>(o, 0, p[1], 0, p[2], 0);
      wg_rs64o<1, desc_sw64(C_KV2 + 4096 + 32)>(o, 0, p[3], 0, p[4], 0);
      wg_rs64o<1, mkdesc(C_VM2, 128, 256, 0)>(o, 0, p[0], 0, 0, 0);
      wg_commit();
      if (elect()) mbar_arrive(sb + CB_M);
      wg_wait<0>();
#pragma unroll
      for (int i = 0; i < 4; i++) {
        const float* v = o + 16 * (i & 1) + (i & 2);
        sts128((row ^ ((i & 1) * 64)) + (i & 2) * 2048,
               make_uint4(pack2(v[0] * z, v[1] * z), pack2(v[4] * z, v[5] * z), pack2(v[8] * z, v[9] * z), pack2(v[12] * z, v[13] * z)));
      }
      bar_arrive(B_G, 160);
      if (n + 1 < STEPS) bar_arrive(B_R, 160);
      if (w == 1) TR(10);
    }
  }
  if ((threadIdx.x & 127) == 0) TS(6);
}

__device__ __forceinline__ void chain_aux(const Params& P, uint32_t sb) {
  const uint32_t c = chain_id(), j = c & 1, lane = threadIdx.x & 31, w = __shfl_sync(~0u, (threadIdx.x >> 5) & 3, 0);
  load_wg<CHAIN, true>(P, sb, false, 0, w);
  if (threadIdx.x == 384) TS(25);
  if (threadIdx.x == 384) grid_wait(1, lds32(sb + S_GEN));
  bar_sync(B_WG2, 384);
  if (threadIdx.x == 384) TS(13);
  if (w == 0) {
    const uint32_t* fg = g_fl + FL_G + near_half(XB_F, c) * 1024 + (c >> 1) * 8;
#pragma unroll 1
    for (int n = 0; n < STEPS; n++) {
      const unsigned char* blk = g_qkv + (uint32_t)((n % QRING) * (N_CHAIN * 24576));
      const uint32_t t1 = clk(), kb = sb + CB_FULL + (n & 1) * 8, kv = sb + C_KV + (n & 1) * 16384;
      uint32_t t0 = t1 - 100000, x = 0;
      if (n > 0) {
        wait_until(t1, KMIN);
        do asm volatile("ld.relaxed.gpu.global.u32 %0, [%1];" : "=r"(x) : "l"(fg) : "memory"); while (x <= n && clk() - t1 < KWIN);
        if (x > n) {
          asm volatile("fence.acquire.gpu;" ::: "memory");
          fence_async_global();
          if (elect()) { mbar_expect(kb, 8192); bulk_load(kv, blk + c * 24576, 8192, kb); }
        }
        T3(0); CNT(12, 1 + (x <= n));
        mbar_wait(sb + CB_REF, (n - 1) & 1);
        t0 = lds32(sb + C_REF);
        wait_until(t0, DLYV - 500);
      }
      wait_flags(fg + min(lane, 2u) * 256, n + 1);
      T3(2);
      fence_async_global();
      if (n > 0) bar_sync(B_R, 160);
      if (lane < 3) mbar_expect(sb + CB_SX + lane * 8, lane ? 2048 : 2560);
      __syncwarp();
      wait_until(t0, DLYV);
      if (elect()) {
        if (x <= n) { mbar_expect(kb, 8192); bulk_load(kv, blk + c * 24576, 8192, kb); }
        mbar_expect(sb + CB_VF, 8192);
        bulk_load(sb + C_KV + 8192, blk + (c * 24576 + 8192), 8192, sb + CB_VF);
        mbar_expect(sb + CB_Q, 16384);
        wait_until(t0, DLYK);
        bulk_load(sb + C_Q, blk + (c * 24576 + 16384), 8192, sb + CB_Q);
        bulk_load(sb + C_KV2, blk + ((c ^ 1) * 24576 + j * 4096), 4096, sb + CB_Q);
        bulk_load(sb + C_KV2 + 4096, blk + ((c ^ 1) * 24576 + 8192 + j * 4096), 4096, sb + CB_Q);
      }
      T3(1);
      T3(3);
    }
  } else {
    const uint32_t near = __ballot_sync(~0u, near_half(XB_M + min(lane, MRING - 1u) * 8, c));
    uint32_t ring = 0;
    if (w > 1) {
      const uint32_t odd = w & 1, chk = pinned(sb + C_M + odd * 2048 + m_probe(lane)), again = sb + CB_MV + 32 + odd * 8;
      const bool one = elect();
      uint32_t mph = 0;
#pragma unroll 1
      for (int n = 0; n <= STEPS; n++) {
#pragma unroll
        for (int k = 0; k < 3; k++) {
          if (n == STEPS || (k == 2 && odd)) break;
          const uint32_t b = 2 * k + odd, at = chk + (k ? k * 8192 - 2048 + odd * 2048 : 0);
          uint32_t mb = sb + CB_M + b * 8, ph = n & 1;
          int it = 1;
          while (true) {
            mbar_wait(mb, ph);
            const bool bad = __any_sync(~0u, m_max(at, b ? at + 2048 : at) == SENT);
            if (one && !bad) mbar_arrive(sb + CB_MV + (b > 1 ? b * 8 - 8 : 0));
            if (!bad) break;
            mb = again; ph = mph; mph ^= 1;
            if (one) {
              if (k == 0) sts32(sb + C_BAD, n + 1);
              mbar_expect(mb, b ? 4096 : 2048);
              m_fetch(sb, ring * 65536 + ((near >> ring) & 1) * 4096, b, mb);
            }
            __syncwarp();
            spin_guard(it);
          }
          TR(41 + b * 4); CNT(6 + b, it);
        }
        ring = ring + 1 == MRING ? 0 : ring + 1;
        if (!odd) {
          if (n < STEPS) { TRSYNC(); TRDUMP(n - 2); }
          if (n + 1 < STEPS) {
            mbar_wait(sb + CB_OX, n & 1);
            fence_async_smem();
            if (P.dly[30]) wait_until(clk(), P.dly[30]);
            bar_arrive(B_T, 160);
          }
        } else {
          unsigned char* o = g_oimg + (uint32_t)(((n - 1) & (RING - 1)) * (N_CHAIN * 8192) + j * 4096);
          if (n > 0) bar_sync(B_G, 160);
          fence_async_smem();
          if (one) {
            if (n > 0) {
              bulk_store(o + c * 8192, sb + C_OS, 4096);
              bulk_store(o + (c ^ 1) * 8192, sb + C_OS + 4096, 4096);
              asm volatile("cp.async.bulk.commit_group;\ncp.async.bulk.wait_group.read 0;" ::: "memory");
              { const int n_ = n - 1; { const int n = n_; T3(4); (void)n; } }
            }
            mbar_arrive(sb + CB_Q);
            if (n > 0) {
              bulk_done_inc(g_fl + FL_O + c);
              { const int n_ = n - 1; { const int n = n_; T3(5); (void)n; } }
            }
          }
          __syncwarp();
        }
      }
    } else {
      const uint32_t* ts = g_fl + FL_SYNC + near_half(XB_F + 1, c) * 1024 + lane * 2;
      uint32_t t0 = clk() - 100000, last = 0;
      int lag = 0;
#pragma unroll 1
      for (int n = 0; n < STEPS; n++) {
        const uint32_t src = ring * 65536 + ((near >> ring) & 1) * 4096;
        if (lane < 5) mbar_expect(sb + CB_M + lane * 8, lane ? 4096 : 2048);
        __syncwarp();
        if (elect()) {
#pragma unroll
          for (int b = 0; b < 5; b++) {
            wait_until(t0, P.dly[14 + b]);
            m_fetch(sb, src, b, sb + CB_M + b * 8);
            TR(40 + b * 4);
          }
        }
        __syncwarp();
        ring = ring + 1 == MRING ? 0 : ring + 1;
        uint32_t va, vb;
        const uint32_t off = timer_offset<4>(), tag = (uint32_t)(n + 1) << 28;
        if (n > 1) lag += (int)(off - last) - (lag >> 2);
        last = off;
        const uint32_t mine = min(max((lag >> 3) + 256, 0), 511);
        bar_sync(B_QK, 416);
        if (n + 1 == STEPS) break;
        sts32(sb + C_REF + 4, 0);
        const uint32_t c0 = clk(), stamp = c0 + off;
        st_relaxed_if(g_fl + FL_SYNC + lane * 1024 + c, tag | (mine << 19) | (stamp & 0x7FFFF), lane < 2);
        TR(13);
        wait_until(c0, DLYS);
        int it = 0;
        do {
          asm volatile("ld.relaxed.gpu.global.v2.u32 {%0,%1}, [%2];" : "=r"(va), "=r"(vb) : "l"(ts) : "memory");
          spin_guard(it);
        } while (__any_sync(~0u, ((va ^ tag) | (vb ^ tag)) >> 28));
        const int late = __reduce_max_sync(~0u, max((int)((va - stamp) << 13), (int)((vb - stamp) << 13))) >> 13;
        const uint32_t fast = min(((__reduce_max_sync(~0u, max(va, vb)) >> 19) & 511) - mine, 100u);
        t0 = c0 + min((uint32_t)late, clk() - c0) + (n < 2 ? P.dly[26 + n] : 0);
        if (elect()) {
          sts32(sb + C_REF, t0 + (fast * 9 >> 3));
          mbar_arrive(sb + CB_REF);
        }
        st_relaxed_if(g_fl + FL_TICK + lane * 1024, (uint32_t)(n + 1) << 24 | ((t0 + off) & 0xFFFFFF), c == 0 && lane < 2);
        t0 += (fast * 13 >> 3) + (n < 2 ? P.dly[28 + n] : 0);
        TRV(59, fast);
        TR(14); CNT(11, it);
        bar_sync(B_M, 160);
      }
    }
  }
}

template <int WG>
__device__ __forceinline__ void g_math(const Params& P, uint32_t sb) {
  const int q = g_unit(WG);
  const int lane = threadIdx.x & 31, w = (threadIdx.x >> 5) & 3;
  uint32_t a[136];
  {
    const uint32_t stage = sb + G_W + WG * 73728;
    mbar_wait(sb + W_BAR + WG * 8, 0);
    if (threadIdx.x == 0) TS(23);
    load_frags<34>(a, stage);
    fence_async_smem();
    bar_sync(B_WG0 + WG, 128);
    if (threadIdx.x == 0) TS(24);
    load_wg<GROLE>(P, sb, false, WG, w);
    if (threadIdx.x == 0) TS(25);
    mbar_wait(sb + W_BAR + WG * 8, 1);
  }
  if ((threadIdx.x & 127) == 0) TS(4);
  const uint32_t off0 = (q & 31) * 49152 + (q >> 5) * 8192 + w * 1024 + (lane >> 2) * 64 + (((lane ^ (lane >> 3)) & 3) << 4);
  const uint32_t isq = q >> 6;
#pragma unroll 1
  for (int n = 0; n < STEPS; n++) {
    float d0[32], d1[32];
    if (WG == 0 && n >= LOCK0) bar_sync(B_OE, 160);
    if (n > 0) bar_sync(B_V + WG, 256);
#pragma unroll
    for (int ch = 0; ch < 9; ch++) {
      mbar_wait(sb + G_BAR + ch * 8, n & 1);
      if (ch == 0) { if ((threadIdx.x & 127) == 0) T3(5 + WG * 3); __syncwarp(); }
      if (ch == 4) { if ((threadIdx.x & 127) == 0) T3(6 + WG * 3); __syncwarp(); }
      if (ch == 8 && (WG == 0 ? n > 0 : n + 1 < STEPS)) bar_arrive(B_V + (WG ^ 1), 256);
      wg_fence();
#pragma unroll
      for (int kk = 0; kk < 4; kk++) {
        const int i = ch * 4 + kk;
        float* d = i & 1 ? d1 : d0;
        const uint64_t db = desc_sw128(G_RING + ch * 8192 + (kk & 2) * 32);
        if (i < 2) wg_rs64<0>(d, a + i * 4, db);
        else if (i < 34) wg_rs64<1>(d, a + i * 4, db);
        else wg_ss64<1>(d, desc_sw128(G_W2 + WG * 4096 + (i - 34) * 2048), db);
        wg_ss64<1>(d, desc_sw128(G_W + WG * 73728 + i * 2048), db + 2);
      }
      wg_commit();
      if (ch > 0) { wg_wait<1>(); if (lane == 0) mbar_arrive(sb + G_BAR + 128 + (ch - 1) * 8); }
    }
    wg_wait<0>();
    if (lane == 0) mbar_arrive(sb + G_BAR + 128 + 8 * 8);
    if ((threadIdx.x & 127) == 0) T3(7 + WG * 3);
    __syncwarp();
    uint32_t tw = clk() + (n == 0 ? 0u - 100000u : WG ? 0u : DLYW);
    unsigned char* base = g_qkv + (size_t)(n & (QRING - 1)) * (N_CHAIN * 24576);
#pragma unroll
    for (int i = 0; i < 8; i++) {
      const float* d = (i < 4 ? d0 : d1) + 8 * (i & 2) + 2 * (i & 1);
      wait_until(tw, 0); tw += P.dly[2 + WG];
      *(uint4*)(base + (off0 + (i < 2 ? 0 : i < 4 ? 4096 + isq * 24576 : i < 6 ? 24576 - isq * 20480 : 28672 - isq * 4096)) + (i & 1) * 512) =
        make_uint4(pack2(d[0], d[1]), pack2(d[4], d[5]), pack2(d[8], d[9]), pack2(d[12], d[13]));
    }
    bar_sync(B_M + WG, 160);
  }
}

__device__ __forceinline__ void fill16(void* p, uint32_t v) {
  asm volatile("st.global.v4.u32 [%0], {%1,%1,%1,%1};" :: "l"(p), "r"(v) : "memory");
}
__device__ __forceinline__ void g_load(const Params& P, uint32_t sb) {
  const int lane = threadIdx.x & 31, w = __shfl_sync(~0u, (threadIdx.x >> 5) & 3, 0);
  if (w == 2) return;
  if (w < 2) { bar_sync(15, 192); fence_async_smem(); }
  uint32_t fl = 0;
#pragma unroll 1
  for (int n = w == 3 ? LOCK0 : 0; n < STEPS; n++) {
    if (w && n == LOCK0) { grid_wait(1, lds32(sb + S_GEN)); fl = near_half(XB_F, bid()) * 1024; }
    if (w == 3) {
      const uint32_t tag = (uint32_t)(n - LOCK0 + 1) << 24;
      uint32_t v; int it = 0;
      do { asm volatile("ld.relaxed.gpu.global.u32 %0, [%1];" : "=r"(v) : "l"(g_fl + fl + FL_TICK) : "memory"); spin_guard(it); } while (v < tag);
      const uint32_t off = timer_offset<2>(), now = clk(), t0 = now - ((v ^ tag) >> 24 ? DLYG : (now + off - v) & 0xFFFFFF);
      asm volatile("fence.acquire.gpu;" ::: "memory");
      if (lane == 0) T3(11);
      __syncwarp();
      wait_until(t0, DLYG);
      if (lane == 0) T3(4);
      bar_sync(B_OE, 160);
      continue;
    }
    if (w == 0) {
      if (n < NSEG) wait_flags(g_lnflag + n * 16 + (lane & 1) * 8, 1);
    } else if (n >= LAG) {
      wait_flags(g_fl + fl + FL_F + (lane & 1) * 8, n - LAG + 1);
    }
    if (w) { if (lane == 0) T3(12); bar_sync(B_X, 96); }
    fence_async_global();
    const unsigned char* src = g_lnimg + (uint32_t)((w ? NSEG + n - LAG : n) * 36864);
#pragma unroll 1
    for (int ch = 0; ch < 9; ch++) {
      const uint32_t full = sb + G_BAR + ch * 8;
      mbar_wait(full + 128, (n & 1) ^ 1);
      if (w ? n < LAG : n >= NSEG) {
        if (elect()) mbar_arrive(full);
      } else if (elect()) {
        mbar_expect(full, 4096);
        bulk_load(sb + G_RING + ch * 8192 + w * 4096, src + ch * 4096, 4096, full);
      }
    }
  }
}

__device__ __forceinline__ void g_aux(const Params& P, uint32_t sb) {
  const int lane = threadIdx.x & 31, w = (threadIdx.x >> 5) & 3;
  if (w == 1 || w == 2) {
    const int q = g_unit(w - 1);
    uint32_t* f = g_fl + FL_G + q * 8;
#pragma unroll 1
    for (int n = 0; n < STEPS; n++) {
      const uint32_t ln = opaque_tid() & 31;
      uint4* z = (uint4*)g_oacc + (uint32_t)(((n + 1) % ARING) * (16 * DM) + q * 96 + ln);
      fill16(z, 0); fill16(z + 32, 0); fill16(z + 64, 0);
      if (n + 3 >= MRING && q < 80) fill16((uint4*)g_mimg + (uint32_t)(((n + 3) % MRING) * 4096 + q * 32 + ln), SENT);
      bar_sync(B_M + (w - 1), 160);
      if (lane == 0) { T3(w * 2 - 2); fence_async_global(); flag_release(f, n + 1); T3(w * 2 - 1); }
      __syncwarp();
    }
  } else {
    const uint32_t u = (bid() - N_CHAIN) * 2 + (w & 1), r = u / 36 * 16 + (u & 3) * 4 + (lane >> 3);
    uint32_t o = r * (DM / 8) + (u % 36 >> 2) * 8 + ((lane & 7) ^ ((r >> 1) & 3)), fl = 0;
#pragma unroll 1
    for (int k = -LAG - 1; k < STEPS; k++) {
      if (k < NSEG - 1) bar_sync(B_X, 96);
      if (k < LAG || u >= 72) continue;
      if (k == NSEG - 1) { fl = near_half(XB_F, bid()) * 1024; wait_flags(g_fl + fl + FL_F + (lane & 1) * 8, NSEG + 1); }
      const uint4 x = __ldcg((const uint4*)P.out + o);
      if (k >= NSEG - 1) wait_flags(g_fl + fl + FL_OCNT + (max(k, NSEG) % OCRING) * 8, N_O * 3 * (max(k, NSEG) / OCRING + 1));
      const float4* a = (const float4*)g_oacc + ((k % ARING) * (16 * DM) + 8 * DM + u * 64 + lane * 2);
      const float4 p = __ldcg(a), v = __ldcg(a + 1);
      ((uint4*)P.out)[o] = make_uint4(badd2(x.x, pack2(p.x, p.y)), badd2(x.y, pack2(p.z, p.w)), badd2(x.z, pack2(v.x, v.y)), badd2(x.w, pack2(v.z, v.w)));
      o += 4 * DM;
    }
    if ((threadIdx.x & 127) == 0) TS(7);
  }
}

template <int WG, bool HALF, int KS, int N> __device__ __forceinline__ void o_mma(float* d, const uint32_t* a, uint32_t ob) {
  constexpr uint64_t db = desc_sw128(O_RING + (KS >> 2) * 8192 + (KS & 3) * 32);
  constexpr uint64_t da = desc_sw128(O_W + WG * 40960 + (KS < 40 ? KS / 5 * 2 + KS % 5 / 2 : KS - 24) * 2048);
  if constexpr (KS < 40 && !(KS % 5 & 1)) {
    const uint32_t* r = a + (KS / 5 * 3 + KS % 5 / 2) * 4;
    if constexpr (HALF) wg_rs32k<KS != 0, db>(d, r[0], r[1], r[2], r[3], ob); else wg_rs64<KS != 0>(d, r, db);
  } else {
    if constexpr (HALF) wg_ss32k<da, db>(d, ob); else wg_ss64<1>(d, da, db);
  }
  if constexpr (N > 1) o_mma<WG, HALF, KS + 1, N - 1>(d, a, ob);
}
template <int WG, bool HALF, int GR> __device__ __forceinline__ void o_groups(float* d, const uint32_t* a, uint32_t sb, int n, bool more) {
  const uint32_t ob = n < NSEG ? 0 : 256;
  mbar_wait(sb + O_BAR + GR * 8, n & 1);
  if (GR == 0) { if ((threadIdx.x & 127) == 0) T3(13 + WG); __syncwarp(); }
  if (GR == 3 && (WG < 2 || n + 1 < STEPS)) bar_arrive(B_V + (WG + 1) % 3, 256);
  wg_fence();
  o_mma<WG, HALF, GR * 8, 8>(d, a, ob);
  if (GR == 4 && more) o_mma<WG, HALF, 40, 4>(d, a, ob);
  wg_commit();
  if (GR > 0) { wg_wait<1>(); if ((threadIdx.x & 31) == 0) mbar_arrive(sb + O_BAR + 120 + GR * 8); }
  if constexpr (GR < 4) o_groups<WG, HALF, GR + 1>(d, a, sb, n, more);
}
template <int WG, bool HALF> __device__ __forceinline__ void o_step(const uint32_t* a, uint32_t sb, uint32_t st0, int n, bool more) {
  float d[HALF ? 16 : 32];
  if (WG > 0 || n > 0) bar_sync(B_V + WG, 256);
  o_groups<WG, HALF, 0>(d, a, sb, n, more);
  wg_wait<0>();
  if ((threadIdx.x & 31) == 0) mbar_arrive(sb + O_BAR + 128 + 4 * 8);
  if ((threadIdx.x & 127) == 0) T3(WG == 0 ? 1 : WG == 1 ? 8 : 12);
  __syncwarp();
#pragma unroll(HALF ? 1 : 2)
  for (int sl = 0; sl < 2; sl++) {
    mbar_wait(sb + OB_ST + WG * 16 + sl * 8, (n & 1) ^ (WG == 0));
    if (!HALF || sl == (n >= NSEG)) {
#pragma unroll
      for (int nb = 0; nb < 4; nb++) {
        const float* r = d + (HALF ? 0 : sl * 16) + nb * 4;
        const uint32_t ad = st0 + sl * 8192 + nb * 2048;
        sts32(ad, __float_as_uint(r[0]));
        sts32(ad + 256, __float_as_uint(r[1]));
        sts32(ad ^ 32, __float_as_uint(r[2]));
        sts32((ad ^ 32) + 256, __float_as_uint(r[3]));
      }
      fence_async_smem();
    }
    bar_arrive((sl ? B_G : B_M) + WG, 160);
  }
}
template <int WG>
__device__ __forceinline__ void o_math(const Params& P, uint32_t sb) {
  const bool more = bid() < N_CHAIN + N_G + 12;
  const int lane = threadIdx.x & 31, w = (threadIdx.x >> 5) & 3, g = lane >> 2, tq = lane & 3;
  uint32_t a[96];
  mbar_wait(sb + W_BAR + WG * 8, 0);
  load_frags<24>(a, sb + WG * 49152);
  fence_async_smem();
  bar_sync(B_INIT, 416);
  load_wg<OROLE>(P, sb, false, WG, w);
  mbar_wait(sb + W_BAR + WG * 8, 1);
  if ((threadIdx.x & 127) == 0) TS(4);
  const uint32_t st0 = sb + O_ST + tq * 512 + ((w * 16 + g) ^ (tq * 8)) * 4;
#pragma unroll 1
  for (int n = 0; n < STEPS; n++) {
    if (n < LAG || n >= NSEG) o_step<WG, true>(a, sb, st0, n, more); else o_step<WG, false>(a, sb, st0, n, more);
  }
}

__device__ __forceinline__ void o_aux(const Params& P, uint32_t sb) {
  const int i = bid() - N_CHAIN - N_G, ksl = i / 3;
  const int c0 = ksl * 11 - max(ksl - 4, 0), nc = ksl < 4 ? 11 : 10;
  const int lane = threadIdx.x & 31, w = __shfl_sync(~0u, (threadIdx.x >> 5) & 3, 0);
  if (w == 0) {
    bar_sync(B_INIT, 416);
    const uint32_t* f = g_fl + FL_O + near_half(XB_F + 1, bid()) * 1024 + min((c0 & ~1) + lane, (c0 + nc - 1) | 1);
#pragma unroll 1
    for (int n = 0; n < STEPS; n++) {
      const unsigned char* src = g_oimg + (uint32_t)(((n % RING) * N_CHAIN + c0) * 8192);
      wait_flags(f, n + 1);
      if (n >= LAG && n < NSEG) wait_until(clk(), DLYO);
      fence_async_global();
      if (lane == 0) T3(0);
#pragma unroll
      for (int gr = 0; gr < 5; gr++) {
        const uint32_t full = sb + O_BAR + gr * 8, bytes = (gr < 4 ? 2 : nc - 8) * 8192;
        mbar_wait(full + 128, (n & 1) ^ 1);
        if (elect()) {
          if (n < LAG || n >= NSEG) {
            mbar_expect(full, bytes >> 1);
            for (uint32_t o = gr * 16384 + (n < LAG ? 0 : 4096); o < gr * 16384 + bytes; o += 8192) bulk_load(sb + O_RING + o, src + o, 4096, full);
          } else {
            mbar_expect(full, bytes);
            bulk_load(sb + O_RING + gr * 16384, src + gr * 16384, bytes, full);
          }
        }
      }
    }
  } else {
#pragma unroll 1
    for (int n = 0; n < STEPS; n++) {
      float* dst = g_oacc + (uint32_t)((n % ARING) * (64 * DM) + ((i % 3) * 3 + (w - 1 + ksl) % 3) * 1024);
      const bool early = w == 3 && n < NSEG;
      bar_sync(B_M + (w - 1), 160);
      if (lane == 0) {
        T3(w * 2);
        if (n < NSEG) { bulk_reduce(dst, sb + O_ST, 4096); bulk_reduce(dst + 16 * DM, sb + O_ST + 4096, 4096); }
        asm volatile("cp.async.bulk.commit_group;" ::: "memory");
        if (early) {
          asm volatile("cp.async.bulk.wait_group.read 0;" ::: "memory");
          mbar_arrive(sb + OB_ST);
          T3(8 + w);
          bulk_done_inc(g_fl + FL_OCNT + (n % OCRING) * 8);
          T3(w * 2 + 1);
        }
      }
      __syncwarp();
      bar_sync(B_G + (w - 1), 160);
      if (lane == 0) {
        if (n >= LAG) { bulk_reduce(dst + 32 * DM, sb + O_ST + 8192, 4096); bulk_reduce(dst + 48 * DM, sb + O_ST + 12288, 4096); }
        asm volatile("cp.async.bulk.commit_group;\ncp.async.bulk.wait_group.read 1;" ::: "memory");
        if (!early) mbar_arrive(sb + OB_ST + (w % 3) * 16);
        asm volatile("cp.async.bulk.wait_group.read 0;" ::: "memory");
        mbar_arrive(sb + OB_ST + (w % 3) * 16 + 8);
        if (!early) {
          T3(8 + w);
          bulk_done_inc(g_fl + FL_OCNT + (n % OCRING) * 8);
          T3(w * 2 + 1);
        }
      }
      __syncwarp();
    }
  }
}

constexpr uint32_t Y_PITCH = 1168, Y_ROWS = 16 * Y_PITCH;
template <int R> __device__ __forceinline__ void y_rows(uint32_t* y, uint32_t src, uint32_t dst, int w, int bar) {
  const int lane = threadIdx.x & 31;
#pragma unroll
  for (int k = 0; k < 2 * R + 1; k++) {
    const int op = w + k * (16 / R);
    if (k == 2 * R && w >= 4) break;
    uint32_t a, b, c, d;
    ldsm4t(a, b, c, d, src + op * 512 + (lane & 16) * 16 + (lane & 7) * 32 + (lane & 8) * 2);
    stsm4(dst + (lane & 15) * Y_PITCH + op * 32 + (lane & 16), a, b, c, d);
  }
  bar_sync(bar, 512 / R);
  const uint32_t row = dst + ((w & 6) * 2 + (w >> 3) * 2 + (w & 1)) * Y_PITCH + lane * 4;
#pragma unroll
  for (int i = 0; i < 9 * R; i++) y[i] = lds32(row + i / 9 * 2 * Y_PITCH + i % 9 * 128);
}

__device__ __forceinline__ void f_role(const Params& P, uint32_t sb) {
  const int lane = threadIdx.x & 31, w = __shfl_sync(~0u, threadIdx.x >> 5, 0), r0 = (bid() - N_CHAIN - N_G - N_O) * 16;
  if (w == 8) {
    const uint32_t* fo = g_fl + FL_OCNT + near_half(XB_F, bid()) * 1024;
    fence_async_global();
#pragma unroll 1
    for (int n = 0; n < NSEG; n++) {
      bar_sync(2, 288);
      if (elect()) {
        mbar_expect(sb + F_BAR, 36864);
        bulk_load(sb + F_XY, P.X + (size_t)(n * 32 + r0) * DM, 18432, sb + F_BAR);
        bulk_load(sb + F_XY + 18432, g_yT + (size_t)(n * 32 + r0) * DM, 18432, sb + F_BAR);
        mbar_expect(sb + F_BAR + 8, 36864);
        T3(1);
      }
      wait_flags(fo + (n % OCRING) * 8, N_O * 3 * (n / OCRING + 1));
      fence_async_global();
      if (elect()) { bulk_load(sb + F_A, g_oacc + (uint32_t)((n % ARING) * (64 * DM) + r0 * DM), 36864, sb + F_BAR + 8); T3(0); }
    }
  } else if (w == 9) {
#pragma unroll 1
    for (int n = 0; n < NSEG; n++) {
      const uint32_t st = sb + (n & 1) * 36864;
      unsigned char* p = g_lnimg + (uint32_t)((NSEG + n) * 36864 + r0 * 128);
      bar_sync(1, 288);
      if (elect()) {
        T3(2);
#pragma unroll
        for (int i = 0; i < 9; i++) bulk_store(p + i * 4096, st + F_L + i * 2048, 2048);
        asm volatile("cp.async.bulk.commit_group;" ::: "memory");
        bulk_done_inc(g_fl + FL_F + (bid() & 1) * 8);
        T3(3);
        bulk_store(P.out + (size_t)(n * 32 + r0) * DM, st + F_X, 18432);
        asm volatile("cp.async.bulk.commit_group;\ncp.async.bulk.wait_group.read 0;" ::: "memory");
        if (n + 1 == NSEG) bulk_done_inc(g_fl + FL_F + (bid() & 1) * 8);
      }
      __syncwarp();
    }
  } else if (w < 8) {
    const uint32_t row = sb + w * 1152 + lane * 4, acc = sb + F_A + w * 256 + (lane ^ ((w & 6) * 2)) * 8;
    const uint32_t ln = sb + F_L + w * 128 + (((lane >> 2) ^ w) << 4) + (lane & 3) * 4;
#pragma unroll 1
    for (int n = -1; n < NSEG; n++) {
      const uint32_t st = (n & 1) * 36864;
      uint32_t x[18], y[18], l[18];
      if (n >= 0) mbar_wait(sb + F_BAR, n & 1);
#pragma unroll
      for (int i = 0; i < 18; i++) x[i] = lds32(row + F_XY + i / 9 * 9216 + i % 9 * 128);
      y_rows<2>(y, sb + F_XY + 18432, sb + F_Y, w, 3);
      layernorm9<2>(x, l);
#pragma unroll
      for (int i = 0; i < 18; i++) x[i] = badd2(x[i], bmul2(l[i], y[i]));
      if (n >= 0) mbar_wait(sb + F_BAR + 8, n & 1);
      if (threadIdx.x == 0 && n >= 0) T3(4);
      __syncwarp();
      uint2 a[18];
#pragma unroll
      for (int i = 0; i < 18; i++) a[i] = lds64(acc + i / 9 * 2048 + i % 9 * 4096);
#pragma unroll
      for (int i = 0; i < 18; i++) x[i] = badd2(x[i], pack2(__uint_as_float(a[i].x), __uint_as_float(a[i].y)));
      if (n + 1 < NSEG) bar_arrive(2, 288);
      layernorm9<2>(x, l);
#pragma unroll
      for (int i = 0; i < 18; i++) { x[i] = badd2(x[i], bmul2(l[i], y[i])); sts32(row + st + F_X + i / 9 * 9216 + i % 9 * 128, x[i]); }
      layernorm9<2>(x, l);
#pragma unroll
      for (int i = 0; i < 18; i++) sts32(ln + st + i / 9 * 1024 + i % 9 * 2048, l[i]);
      fence_async_smem();
      if (n >= 0) bar_sync(1, 288); else bar_sync(3, 256);
    }
  }
}

constexpr uint32_t P_CH = 147456, P_CHSZ = 12800, P_H = 4352;
static_assert(P_CH + 6 * P_CHSZ <= G_BAR, "prologue smem");

template <int N>
__device__ __forceinline__ void conv_fold(float (*acc)[4], bool hi, uint32_t mine, uint32_t theirs, int bar, int cnt) {
#pragma unroll
  for (int i = 0; i < N / 2; i++) {
    uint4 v;
    v.x = __float_as_uint(hi ? acc[i][0] : acc[i + N / 2][0]); v.y = __float_as_uint(hi ? acc[i][1] : acc[i + N / 2][1]);
    v.z = __float_as_uint(hi ? acc[i][2] : acc[i + N / 2][2]); v.w = __float_as_uint(hi ? acc[i][3] : acc[i + N / 2][3]);
    sts128(mine + i * 512, v);
  }
  bar_sync(bar, cnt);
#pragma unroll
  for (int i = 0; i < N / 2; i++) {
    const uint4 v = lds128(theirs + i * 512);
    acc[i][0] = (hi ? acc[i + N / 2][0] : acc[i][0]) + __uint_as_float(v.x); acc[i][1] = (hi ? acc[i + N / 2][1] : acc[i][1]) + __uint_as_float(v.y);
    acc[i][2] = (hi ? acc[i + N / 2][2] : acc[i][2]) + __uint_as_float(v.z); acc[i][3] = (hi ? acc[i + N / 2][3] : acc[i][3]) + __uint_as_float(v.w);
  }
}
template <int N>
__device__ __forceinline__ void conv_store(const float (*acc)[4], int tile0, uint32_t su, int d, uint32_t dd) {
  const int lane = threadIdx.x & 31, g = lane >> 2, tq = lane & 3;
#pragma unroll
  for (int i = 0; i < N; i++) {
    const uint32_t ad = su + (8 + (tile0 + i) * 8 + g) * 32 + tq * 4, sw = (g & 4) << 2;
    const uint32_t lo = badd2(movmat(pack2(acc[i][0], acc[i][1])), bmul2(lds32(ad + sw), dd));
    const uint32_t hi = badd2(movmat(pack2(acc[i][2], acc[i][3])), bmul2(lds32(ad + (sw ^ 16)), dd));
    ((uint2*)g_yT)[(((tile0 + i) * 8 + g) * DM + d) * 4 + tq] = make_uint2(lo, hi);
  }
}

__device__ __forceinline__ void prologue(const Params& P, uint32_t sb) {
  const int b = bid(), tid = threadIdx.x, lane = tid & 31, warp = tid >> 5, t0 = b * 16;
  const bool isg = b >= N_CHAIN && b < N_CHAIN + N_G;
  const int nch = isg ? 2 : b < 128 ? 6 : 0, chb = b < N_CHAIN ? b * 6 : isg ? b * 2 + 256 : b * 6 - 192;
  const uint32_t tstart = clk();
  if (tid < 288) {
    if (b < 128) {
      const int c = (tid >> 1) * 4, tt = t0 + (tid & 1) * 8;
      uint2 kr[11], vr[8];
#pragma unroll
      for (int i = 0; i < 11; i++) { const int t = tt + i - 3; kr[i] = t >= 0 ? __ldg((const uint2*)(P.K + (size_t)t * DM + c)) : make_uint2(0, 0); }
#pragma unroll
      for (int i = 0; i < 8; i++) vr[i] = __ldg((const uint2*)(P.V + (size_t)(tt + i) * DM + c));
#pragma unroll
      for (int e = 0; e < 2; e++) {
        const uint4 sh = __ldg((const uint4*)(P.shift + c * 4) + e);
        const uint32_t s0 = __byte_perm(sh.x, sh.z, 0x5410), s1 = __byte_perm(sh.x, sh.z, 0x7632);
        const uint32_t s2 = __byte_perm(sh.y, sh.w, 0x5410), s3 = __byte_perm(sh.y, sh.w, 0x7632);
        uint32_t v[8];
#pragma unroll
        for (int i = 0; i < 8; i++) {
          const uint32_t k3 = e ? kr[i].y : kr[i].x, k2 = e ? kr[i + 1].y : kr[i + 1].x, k1 = e ? kr[i + 2].y : kr[i + 2].x, k0 = e ? kr[i + 3].y : kr[i + 3].x;
          v[i] = bmul2(badd2(badd2(badd2(bmul2(k3, s3), bmul2(k2, s2)), bmul2(k1, s1)), bmul2(k0, s0)), e ? vr[i].y : vr[i].x);
        }
        *(uint4*)(g_kvT + (size_t)(c + 2 * e) * KVP + tt) =
          make_uint4(__byte_perm(v[0], v[1], 0x5410), __byte_perm(v[2], v[3], 0x5410), __byte_perm(v[4], v[5], 0x5410), __byte_perm(v[6], v[7], 0x5410));
        *(uint4*)(g_kvT + (size_t)(c + 2 * e + 1) * KVP + tt) =
          make_uint4(__byte_perm(v[0], v[1], 0x7632), __byte_perm(v[2], v[3], 0x7632), __byte_perm(v[4], v[5], 0x7632), __byte_perm(v[6], v[7], 0x7632));
      }
    }
  } else if (tid < 384) {
    const int t = tid - 288;
    for (int i = b * 96 + t; i < 16 * DM; i += N_CTA * 96) ((uint4*)g_oacc)[i] = make_uint4(0, 0, 0, 0);
    if (b * 96 + t < 128 * 8) g_lnflag[b * 96 + t] = 0;
    if (t == 95) sts32(sb + S_GEN, ld_acquire(g_gbar));
    __syncwarp();
    wait_until(tstart, PREFH);
    for (int i = t; i < 32 * nch; i += 96) asm volatile("prefetch.global.L2 [%0];" :: "l"(P.Hk + (size_t)chb * SEQ + i * 64));
  }
  if (warp < 12) {
    bar_arrive(10, 416);
    if (tid == 128) TS(14);
    const int ch = 5 - (warp >> 1), sub = warp & 1, d = chb + ch;
    const uint32_t su = sb + P_CH + ch * P_CHSZ;
    if (ch < nch) {
      const uint32_t* hs = (const uint32_t*)(P.Hk + (size_t)d * SEQ);
#pragma unroll
      for (int q = sub * 32 + lane; q < 256; q += 64) {
        const uint4 c = __ldg((const uint4*)hs + q);
        const uint32_t prev = q ? __ldg(hs + 4 * q - 1) : 0u;
        sts128(su + P_H + 32 + q * 16, make_uint4(__byte_perm(c.x, prev, 0x7610), __byte_perm(c.y, c.x, 0x7610), __byte_perm(c.z, c.y, 0x7610), __byte_perm(c.w, c.z, 0x7610)));
        sts128(su + P_H + 4224 + q * 16, make_uint4(__byte_perm(c.x, 0, 0x1032), __byte_perm(c.y, 0, 0x1032), __byte_perm(c.z, 0, 0x1032), __byte_perm(c.w, 0, 0x1032)));
      }
      if (sub == 1 && lane == 0) sts32(su + P_CHSZ - 16, __bfloat16_as_ushort(P.Dk[d]) * 0x10001u);
      if (sub == 0 && lane < 20) sts128(su + (lane < 16 ? lane * 16 : P_H + (lane & 2) * 2096 + (lane & 1) * 16), make_uint4(0, 0, 0, 0));
    }
    bar_sync(11, 416);
    if (ch < nch) {
#pragma unroll
      for (int q = sub * 32 + lane; q < 256; q += 64) {
        const int row = (q >> 1) + 8;
        sts128(su + row * 32 + (((q & 1) ^ ((row >> 2) & 1)) << 4), __ldcg((const uint4*)(g_kvT + (size_t)d * KVP) + q));
      }
    }
    const int g = lane >> 2, tq = lane & 3;
    const uint32_t sh = su + P_H + (g & 1) * 4192 + (8 + (g >> 1) - tq) * 4;
    float acc[16][4];
#pragma unroll
    for (int i = 0; i < 16; i++) { acc[i][0] = acc[i][1] = acc[i][2] = acc[i][3] = 0.f; }
    auto u_addr = [&](int res) {
      const int row = 8 - res + ((lane >> 4) << 3) + (lane & 7);
      return su + row * 32 + ((((lane >> 3) & 1) ^ ((row >> 2) & 1)) << 4);
    };
    if (ch < nch) {
      bar_sync(1 + ch, 64);
      if (tid == 352) TS(11);
      if (sub) {
#pragma unroll 4
        for (int res = 0; res < 8; res++) {
          uint32_t b0, b1, b2, b3;
          ldsm4(b0, b1, b2, b3, u_addr(res));
          const uint32_t r0 = lds32(sh + res * 32);
          mma16(acc[0], r0, lds32(sh + res * 32 + 16), lds32(sh + res * 32 - 16), r0, b0, b1);
        }
        conv_store<1>(acc, 0, su, d, lds32(su + P_CHSZ - 16));
      }
    }
    bar_arrive(12, 416);
    if (isg && warp < 8) { while ((int)(clk() - tstart - S1G) < 0) __nanosleep(200); load_wg<GROLE>(P, sb, true, warp >> 2, warp & 3); }
    if (ch < nch) {
#pragma unroll 1
      for (int res = sub * 4; res < sub * 4 + 4; res++) {
        uint32_t bf[16][2];
        const uint32_t ad = u_addr(res);
#pragma unroll
        for (int f = 0; f < 16; f += 2) ldsm4(bf[f][0], bf[f][1], bf[f + 1][0], bf[f + 1][1], ad + f * 256);
#pragma unroll
        for (int k = 0; k < 16; k++) {
          const int jj = k & 1 ? k >> 1 : 15 - (k >> 1);
          const uint32_t ah = sh + (8 * jj + res) * 32;
          const uint32_t r0 = lds32(ah), r1 = lds32(ah + 16), rm = lds32(ah - 16);
#pragma unroll
          for (int i = max(jj, 1); i < 16; i++) mma16(acc[i], r0, r1, rm, r0, bf[i - jj][0], bf[i - jj][1]);
        }
      }
      bar_sync(1 + ch, 64);
      if (tid == 352) TS(12);
      const uint32_t xb = su + P_H + lane * 16, dd = lds32(su + P_CHSZ - 16);
      conv_fold<16>(acc, sub, xb + sub * 4096, xb + (sub ^ 1) * 4096, 1 + ch, 64);
      conv_store<8>(acc, sub * 8, su, d, dd);
    }
  } else {
    for (int i = b; i < 194 + MRING * 5; i += N_CTA) {
      const int n = (i - 194) / 5, r = (i - 194) % 5, blk = i < 192 ? i / 6 * 8 + i % 6 : i < 194 ? XB_F + i - 192 : XB_M + n * 8 + r;
      const uint32_t fill = i < 194 ? 0u : SENT;
#pragma unroll 1
      for (int q = tid - 384; q < 256 && warp < 15; q += 96) {
        uint4 v = make_uint4(fill, fill, fill, fill);
        if (i >= 194 && n == 0 && (r > 0 || q < 128)) {
          const bf16* m = P.mem0 + (max(r * 8 - 4, 0) + (q >> 5)) * 16 + ((q >> 1) & 1) * 8 + ((q >> 2) & 7);
          v.x = pack2(__bfloat162float(m[0]), __bfloat162float(m[DM])); v.y = pack2(__bfloat162float(m[2 * DM]), __bfloat162float(m[3 * DM]));
          v.z = pack2(__bfloat162float(m[4 * DM]), __bfloat162float(m[5 * DM])); v.w = pack2(__bfloat162float(m[6 * DM]), __bfloat162float(m[7 * DM]));
        }
        g_xb[blk * 512 + q] = v;
        g_xb[blk * 512 + 256 + q] = v;
      }
    }
    if (tid < 388) g_xb[XB_REF * 512 + (tid & 2) * 128 + (b & ~1) + (tid & 1)] = make_uint4(0, 0, 0, 0);
    else if (tid < 392 && b < N_GRP) g_xb[(b * 8 + 7) * 512 + (tid & 2) * 128 + (tid & 1)] = make_uint4(0, 0, 0, 0);
    if (warp < 15) { bar_arrive(9, 128); bar_sync(7, 96); }
    if (tid == 384) TS(8);
    if (warp == 12) {
      const bf16* w = lane < 6 ? (lane % 3 == 0 ? P.Wk : lane % 3 == 1 ? P.Wv : P.Wq) + (((b >> 5) * 2 + lane / 3) * 32 + (b & 31)) * 2048
                               : (lane < 8 ? P.Wo + (lane - 6) * (9 * 131072) : P.X) + b * 2048;
      uint32_t t = tstart + PREF0;
      if ((int)(clk() - t) > 0) t = clk();
#pragma unroll 1
      for (int st = 0; st < 9 && b < N_CHAIN; st++) {
#pragma unroll 1
        for (int i = 0; i < 9; i++, t += PACE) {
          wait_until(t, 0);
          if (lane == st) asm volatile("cp.async.bulk.prefetch.L2.global [%0], 4096;" :: "l"(w + i * (lane < 6 ? 262144 : 131072)) : "memory");
        }
      }
      if (lane == 0) TS(10);
    } else if (warp == 15) {
      bar_sync(10, 416);
      if (lane == 0) { grid_arrive(0); if (nch) grid_wait(0, lds32(sb + S_GEN)); }
      __syncwarp();
      bar_arrive(11, 416);
      if (lane == 0) TS(1);
      bar_sync(9, 128);
      bar_sync(12, 416);
      if (lane == 0) { TS(16); grid_arrive(2); TS(17); }
    } else if (lane == 0) {
      if (warp == 13 || (warp == 14 && b < N_GRP)) {
        uint32_t* p = (uint32_t*)(g_xb + (warp == 13 ? XB_REF * 512 + b : (b * 8 + 7) * 512));
        int votes = 0;
        for (int rep = 0; rep < 24 && abs(votes) < 7; rep++) {
          uint32_t v0, v1, c0, c1;
          asm volatile("atom.relaxed.gpu.global.add.u32 %0, [%4], 1;\n atom.relaxed.gpu.global.add.u32 %1, [%5], 1;\n"
                       "{.reg .pred p; setp.eq.u32 p, %0, 0x7ffffff3; @p trap; mov.u32 %2, %%clock; setp.eq.u32 p, %1, 0x7ffffff3; @p trap; mov.u32 %3, %%clock;}"
                       : "=&r"(v0), "=&r"(v1), "=&r"(c0), "=&r"(c1) : "l"(p + (rep & 1) * 1024), "l"(p + ((rep & 1) ^ 1) * 1024) : "memory");
          votes += ((c1 - c0 > 80u) == (rep & 1)) ? 1 : -1;
        }
        if (warp == 13) { g_side[b] = votes > 0; TS(9); } else g_near[b] = votes > 0;
      }
    }
    __syncwarp();
    if (warp > 12 && b < N_CHAIN) {
      while ((int)(clk() - tstart - S1DLY) < 0) __nanosleep(200);
      for (int k = warp - 13; k < 8; k += 3) load_wg<CHAIN>(P, sb, true, 1 - k / 4, k & 3);
    }
  }
  if (b < N_CHAIN + N_G && (warp < 8 || (isg && warp >= 12))) bar_arrive(0, 512); else bar_sync(0, 512);
  if (tid == 352) TS(2);
}

__device__ __forceinline__ void publish_y() {
  if (threadIdx.x == 383) { grid_arrive(1); TS(18); }
  __syncwarp();
}

template <int R> __device__ __forceinline__ void ln_tiles(const Params& P, uint32_t sb) {
  const int lane = threadIdx.x & 31, w = (threadIdx.x >> 5) & (16 / R - 1), half = R == 1 ? 0 : threadIdx.x >> 8, u = N_CTA - 1 - bid();
  const int first = R == 1 ? u : 46 - 2 * u + half, step = R == 1 ? 4 : 40, last = R == 1 ? 8 : 128;
  const uint32_t raw = sb + P_CH + half * (18432 + Y_ROWS), mb = sb + T_BAR + (R - 1 + half) * 8;
  const bool lead = w == 16 / R - 1 && lane == 0;
  auto load_y = [&](const bf16* src, int tile) {
    fence_async_global();
    mbar_expect(mb, 18432);
    bulk_load(raw, src + (size_t)tile * 16 * DM, 18432, mb);
  };
  uint32_t nx[9 * R];
  auto load_x = [&](int tile) {
#pragma unroll
    for (int i = 0; i < 9 * R; i++) nx[i] = __ldg((const uint32_t*)(P.X + (size_t)(tile * 16 + w + i / 9 * 8) * DM) + i % 9 * 32 + lane);
  };
  load_x(first);
  if (R == 2) {
    if (lead) { grid_wait(1, lds32(sb + S_GEN)); if (u > 3) TS(13); load_y(g_yT, first); }
    __syncwarp();
  }
#pragma unroll 1
  for (int tile = first, real = R - 1, ph = 0; tile < last; tile += real * step, real = 1, ph ^= 1) {
    uint32_t x[9 * R], l[9 * R], y[9 * R];
    const bool ts = threadIdx.x == 0 && (R == 1 ? tile == first : u > 3 && tile == first + step);
    if (ts) TS(26);
#pragma unroll
    for (int i = 0; i < 9 * R; i++) x[i] = nx[i];
    layernorm9<R>(x, l);
    if (real && tile + step < last) load_x(tile + step);
    if (R == 2 && tile == first + step && u >= N_F && w < 6) load_wg<OROLE>(P, sb, true, w >> 1, half * 2 + (w & 1));
    if (R == 1 && tile == first && lead) {
      if (real) grid_wait(2, lds32(sb + S_GEN));
      TS(13);
      load_y(real ? g_yT : P.Hk, tile);
    }
    bar_sync(13 + half, 512 / R);
    mbar_wait(mb, ph);
    if (ts) TS(28);
    y_rows<R>(y, raw, raw + 18432, w, 13 + half);
    if (ts) TS(29);
    if (lead && real && tile + step < last) { fence_async_smem(); load_y(g_yT, tile + step); }
    __syncwarp();
#pragma unroll
    for (int i = 0; i < 9 * R; i++) x[i] = badd2(x[i], bmul2(l[i], y[i]));
    layernorm9<R>(x, l);
    if (ts && l[0] != 0x12345) TS(30);
#pragma unroll
    for (int r = 0; r < R; r++) store_ln_row(0, tile * 16 + w + r * 8, l + r * 9);
    if (R == 1) {
      __syncthreads();
      if (threadIdx.x == 32 && real) { if (tile < 4) TS(19); st_release(g_lnflag + tile * 8, 1); if (tile < 4) TS(20); }
      __syncwarp();
    }
    if (ts) TS(31);
  }
  if (R == 2) {
    __syncthreads();
    if (threadIdx.x >= 506) {
      asm volatile("fence.acq_rel.gpu;" ::: "memory");
      st_relaxed_if(g_lnflag + ((first ^ (lane & 1)) + (lane - 26) / 2 * step) * 8, 1, true);
    }
    __syncwarp();
    fence_async_smem();
    if (threadIdx.x == 0) TS(15);
  }
}

__global__ void __cluster_dims__(2, 1, 1) __launch_bounds__(512, 1) k_main(const __grid_constant__ Params P) {
  extern __shared__ __align__(1024) unsigned char smem[];
  const uint32_t sb = (uint32_t)__cvta_generic_to_shared(smem);
  const int b = bid(), wg = threadIdx.x >> 7;
  if ((threadIdx.x & 127) == 0) TS(0);
  if (threadIdx.x == 480) {
    if ((sb & 0xFFFFFF) != SBASE) __trap();
    for (int i = 0; i < 6; i++) mbar_init(sb + W_BAR + i * 8, 1);
    if (b < N_CHAIN) {
      mbar_init(sb + CB_FULL, 1); mbar_init(sb + CB_FULL + 8, 1);
      mbar_init(sb + CB_REF, 1);
      mbar_init(sb + CB_SX, 1); mbar_init(sb + CB_OX, 1); mbar_init(sb + CB_XX, 1); mbar_init(sb + CB_Q, 2); mbar_init(sb + CB_VF, 1);
      sts32(sb + C_BAD, 0);
      for (int i = 0; i < 11; i++) mbar_init(sb + CB_M + i * 8, i == 0 ? 5 : i == 5 ? 2 : 1);
    } else if (b < N_CHAIN + N_G) {
      for (int i = 0; i < 9; i++) { mbar_init(sb + G_BAR + i * 8, 2); mbar_init(sb + G_BAR + 128 + i * 8, 8); }
    } else if (b < N_CHAIN + N_G + N_O) {
      for (int i = 0; i < 5; i++) { mbar_init(sb + O_BAR + i * 8, 1); mbar_init(sb + O_BAR + 128 + i * 8, 12); }
      for (int i = 0; i < 6; i++) mbar_init(sb + OB_ST + i * 8, 1);
    } else {
      mbar_init(sb + F_BAR, 1); mbar_init(sb + F_BAR + 8, 1);
    }
    asm volatile("fence.mbarrier_init.release.cluster;" ::: "memory");
    fence_async_smem();
  }
  __syncwarp();
  asm volatile("barrier.cluster.arrive.relaxed.aligned;" ::: "memory");
  prologue(P, sb);
  asm volatile("barrier.cluster.wait.aligned;" ::: "memory");
  fence_async_smem();
  if (b >= N_CHAIN + N_G) publish_y();
  if (b >= 128) ln_tiles<1>(P, sb);
  if (b >= N_CHAIN + N_G) ln_tiles<2>(P, sb);
  if ((threadIdx.x & 127) == 0) TS(3);
  if (b < N_CHAIN) {
    if (wg < 2) { reg_inc<200>(); chain_proj(P, sb); }
    else if (wg == 2) { reg_dec<88>(); publish_y(); chain_attn(P, sb); }
    else { reg_dec<24>(); chain_aux(P, sb); }
  } else if (b < N_CHAIN + N_G) {
    if (wg == 0) { reg_inc<232>(); g_math<0>(P, sb); }
    else if (wg == 1) { reg_inc<232>(); g_math<1>(P, sb); }
    else if (wg == 2) {
      reg_dec<24>();
      for (int i = threadIdx.x & 127; i < 9 * 256; i += 128) sts128(sb + G_RING + 4096 + (i >> 8) * 8192 + (i & 255) * 16, make_uint4(0, 0, 0, 0));
      fence_async_smem();
      bar_arrive(15, 192);
      publish_y();
      g_aux(P, sb);
    }
    else { reg_dec<24>(); g_load(P, sb); }
  } else if (b < N_CHAIN + N_G + N_O) {
    if (wg == 0) { reg_inc<160>(); o_math<0>(P, sb); }
    else if (wg == 1) { reg_inc<160>(); o_math<1>(P, sb); }
    else if (wg == 2) { reg_inc<160>(); o_math<2>(P, sb); }
    else { reg_dec<32>(); o_aux(P, sb); }
  } else {
    f_role(P, sb);
  }
}

}

extern "C" void kernel_launch(void* const* d_in, const int* in_sizes, int n_in, void* d_out, int out_size) {
  typedef CUresult (*Encode)(CUtensorMap*, CUtensorMapDataType, cuuint32_t, void*, const cuuint64_t*, const cuuint64_t*, const cuuint32_t*, const cuuint32_t*,
                             CUtensorMapInterleave, CUtensorMapSwizzle, CUtensorMapL2promotion, CUtensorMapFloatOOBfill);
  static Encode encode = nullptr;
  if (!encode) cudaGetDriverEntryPoint("cuTensorMapEncodeTiled", (void**)&encode, cudaEnableDefault);
  Params P;
  for (int i = 0; i < 11; i++) {
    const bool wo = i == 6 || i == 7;
    const cuuint64_t cols = wo ? DM : HD, rows = HD + DM - cols, pitch = cols * 2;
    const cuuint64_t dim[4][5] = {{cols, 2, 8, 2, 18}, {cols, 16, 1, 1, rows / 16}, {cols, 2, 4, 4, rows / 32}, {64, 16, 64, 2, 18}};
    const cuuint64_t stride[4][4] = {{8 * pitch, pitch, 16 * pitch, 32 * pitch}, {pitch, pitch, pitch, 16 * pitch},
                                     {pitch, 8 * pitch, 2 * pitch, 32 * pitch}, {pitch, 128, 16 * pitch, 32 * pitch}};
    const cuuint32_t box[4][5] = {{64, 2, 8, 1, 18}, {64, 16, 1, 1, 1}, {64, 2, 4, 2, 1}, {64, 16, 2, 1, 18}}, one[5] = {1, 1, 1, 1, 1};
    const int k = i < 3 ? 0 : i < 7 ? 1 : i < 8 ? 2 : 3;
    encode(&P.map[i], CU_TENSOR_MAP_DATA_TYPE_BFLOAT16, 5, d_in[wo ? 11 : 8 + (i & 7) % 3], dim[k], stride[k], box[k], one,
           CU_TENSOR_MAP_INTERLEAVE_NONE, CU_TENSOR_MAP_SWIZZLE_128B, CU_TENSOR_MAP_L2_PROMOTION_L2_128B, CU_TENSOR_MAP_FLOAT_OOB_FILL_NONE);
  }
  P.X = (const bf16*)d_in[0]; P.K = (const bf16*)d_in[1]; P.V = (const bf16*)d_in[2];
  P.shift = (const bf16*)d_in[3]; P.Hk = (const bf16*)d_in[4]; P.Dk = (const bf16*)d_in[5];
  P.mem0 = (const bf16*)d_in[7];
  P.Wq = (const bf16*)d_in[8]; P.Wk = (const bf16*)d_in[9]; P.Wv = (const bf16*)d_in[10]; P.Wo = (const bf16*)d_in[11];
  P.out = (bf16*)d_out;
  for (int i = 0; i < 31; i++) P.dly[i] = h_dly[i];
  cudaFuncSetAttribute(k_main, cudaFuncAttributeMaxDynamicSharedMemorySize, SMEM_BYTES);
  k_main<<<N_CTA, 512, SMEM_BYTES>>>(P);
}
```
